```python
import torch

def _softmax(x, axis=-1):
    return torch.softmax(x, dim=axis)
def _gelu(x):
    return torch.nn.functional.gelu(x, approximate="tanh")
def _silu(x):
    return torch.nn.functional.silu(x)
def _sigmoid(x):
    return torch.sigmoid(x)
def _layernorm(x, axis=-1, eps=1e-5):
    m = x.mean(dim=axis, keepdim=True)
    v = x.var(dim=axis, keepdim=True, unbiased=False)
    return (x - m) / torch.sqrt(v + eps)
def _scatter_add(tgt, idx, src, axis=0):
    return tgt.clone().index_add_(axis, idx, src)
def _segment_sum(src, seg, n):
    out = torch.zeros((n,) + src.shape[1:], dtype=src.dtype)
    return out.index_add_(0, seg, src)
def _pad(x, pw):
    flat = tuple(v for pair in reversed(pw) for v in pair)
    return torch.nn.functional.pad(x, flat)

kernel_name = 'interleave_layers__sliding_local_dilated__linear_kernel_hedgehog__prompt'

def setup_inputs():

    _w = (lambda a: (lambda t: t.to(torch.bfloat16) if t.is_floating_point() else t)(torch.as_tensor(a)))
    def _A_setup():
        B, S, D = 1, 2048, 1024
        return {
            "x": _w((lambda *s: torch.randn(*s, dtype=torch.bfloat16) * 0.05)(B, S, D)),
            "wqkv": _w((lambda *s: torch.randn(*s, dtype=torch.bfloat16) * 0.05)(D, 3 * D)),
            "wo": _w((lambda *s: torch.randn(*s, dtype=torch.bfloat16) * 0.05)(D, D)),
        }
    _A_in = _A_setup()

    def _B_setup():
        B, S, D, H = 1, 2048, 1024, 32
        Dh = D // H
        return {
            "x": _w((lambda *s: torch.randn(*s, dtype=torch.bfloat16) * 0.05)(B, S, D)),
            "wqkv": _w((lambda *s: torch.randn(*s, dtype=torch.bfloat16) * 0.4)(D, 3 * D)),
            "w_phi": _w((lambda *s: torch.randn(*s, dtype=torch.bfloat16) * 0.4)(H, Dh, Dh) * (Dh ** -0.5)),
            "wo": _w((lambda *s: torch.randn(*s, dtype=torch.bfloat16) * 0.1)(D, D)),
        }
    _B_in = _B_setup()

    return {
        "A_x": _A_in["x"],
        "A_wqkv": _A_in["wqkv"],
        "A_wo": _A_in["wo"],
        "B_x": _B_in["x"],
        "B_wqkv": _B_in["wqkv"],
        "B_w_phi": _B_in["w_phi"],
        "B_wo": _B_in["wo"],
    }

def reference(A_x, A_wqkv, A_wo, B_x, B_wqkv, B_w_phi, B_wo):
    def _A_ref(x, wqkv, wo):
        B, S, D = x.shape
        H = 32; Dh = D // H
        W, dil = 8, 2
        qkv = (lambda x, *d: x.permute(*d))((x @ wqkv).reshape(B, S, 3, H, Dh), 2, 0, 3, 1, 4)
        q, k, v = qkv[0], qkv[1], qkv[2]
        scale = Dh ** -0.5
        pos = torch.arange(S)
        off = torch.arange(W) * dil
        idx = pos[:, None] - off[None, :]
        mask = idx >= 0
        idx_c = torch.where(mask, idx, 0).reshape(-1)
        kg = k[:, :, idx_c, :].reshape(B, H, S, W, Dh)
        vg = v[:, :, idx_c, :].reshape(B, H, S, W, Dh)
        logits = torch.einsum("bhsd,bhswd->bhsw", q, kg) * scale
        logits = torch.where(mask[None, None, :, :], logits, -1e9)
        attn = _softmax(logits, axis=-1)
        o = torch.einsum("bhsw,bhswd->bhsd", attn, vg)
        return (lambda x, *d: x.permute(*d))(o, 0, 2, 1, 3).reshape(B, S, D) @ wo

    def _B_ref(x, wqkv, w_phi, wo):
        B, S, D = x.shape
        H = 32; Dh = D // H
        qkv = (lambda x, *d: x.permute(*d))((x @ wqkv).reshape(B, S, 3, H, Dh), 2, 0, 3, 1, 4)
        q, k, v = qkv[0], qkv[1], qkv[2]
        pq = torch.einsum("bhsd,hdf->bhsf", q, w_phi)
        pk = torch.einsum("bhsd,hdf->bhsf", k, w_phi)
        phi_q = torch.concatenate([_softmax(pq, axis=-1), _softmax(-pq, axis=-1)], axis=-1)
        phi_k = torch.concatenate([_softmax(pk, axis=-1), _softmax(-pk, axis=-1)], axis=-1)
        kv = torch.einsum("bhsf,bhsd->bhfd", phi_k, v)
        z  = torch.einsum("bhsf->bhf", phi_k)
        num = torch.einsum("bhqf,bhfd->bhqd", phi_q, kv)
        den = torch.einsum("bhqf,bhf->bhq", phi_q, z)[..., None] + 1e-6
        o = num / den
        return (lambda x, *d: x.permute(*d))(o, 0, 2, 1, 3).reshape(B, S, D) @ wo

    x = A_x
    x = x + _A_ref(_layernorm(x, axis=-1), A_wqkv, A_wo)
    x = x + _B_ref(_layernorm(x, axis=-1), B_wqkv, B_w_phi, B_wo)
    x = x + _A_ref(_layernorm(x, axis=-1), A_wqkv, A_wo)
    x = x + _B_ref(_layernorm(x, axis=-1), B_wqkv, B_w_phi, B_wo)
    return x
```

```cpp
#include <cuda_runtime.h>
#include <cuda_bf16.h>
#include <cuda.h>
#include <stdint.h>

namespace {

__device__ __forceinline__ void wgmma_ss_n256(float (&d)[128], uint32_t da, uint32_t db, int sd) {
  asm volatile("{\n.reg .pred p;\n.reg .b64 a, b;\nsetp.ne.b32 p, %130, 0;\nmov.b64 a, {%128, 0x40000040};\nmov.b64 b, {%129, 0x40000040};\n"
    "wgmma.mma_async.sync.aligned.m64n256k16.f32.bf16.bf16 {%0,%1,%2,%3,%4,%5,%6,%7,%8,%9,%10,%11,%12,%13,%14,%15,%16,%17,%18,%19,%20,%21,%22,%23,%24,%25,%26,%27,%28,%29,%30,%31,%32,%33,%34,%35,%36,%37,%38,%39,%40,%41,%42,%43,%44,%45,%46,%47,%48,%49,%50,%51,%52,%53,%54,%55,%56,%57,%58,%59,%60,%61,%62,%63,%64,%65,%66,%67,%68,%69,%70,%71,%72,%73,%74,%75,%76,%77,%78,%79,%80,%81,%82,%83,%84,%85,%86,%87,%88,%89,%90,%91,%92,%93,%94,%95,%96,%97,%98,%99,%100,%101,%102,%103,%104,%105,%106,%107,%108,%109,%110,%111,%112,%113,%114,%115,%116,%117,%118,%119,%120,%121,%122,%123,%124,%125,%126,%127}, a, b, p, 1, 1, 0, 1;\n}\n"
    : "+f"(d[0]),"+f"(d[1]),"+f"(d[2]),"+f"(d[3]),"+f"(d[4]),"+f"(d[5]),"+f"(d[6]),"+f"(d[7]),"+f"(d[8]),"+f"(d[9]),"+f"(d[10]),"+f"(d[11]),"+f"(d[12]),"+f"(d[13]),"+f"(d[14]),"+f"(d[15]),"+f"(d[16]),"+f"(d[17]),"+f"(d[18]),"+f"(d[19]),"+f"(d[20]),"+f"(d[21]),"+f"(d[22]),"+f"(d[23]),"+f"(d[24]),"+f"(d[25]),"+f"(d[26]),"+f"(d[27]),"+f"(d[28]),"+f"(d[29]),"+f"(d[30]),"+f"(d[31]),"+f"(d[32]),"+f"(d[33]),"+f"(d[34]),"+f"(d[35]),"+f"(d[36]),"+f"(d[37]),"+f"(d[38]),"+f"(d[39]),"+f"(d[40]),"+f"(d[41]),"+f"(d[42]),"+f"(d[43]),"+f"(d[44]),"+f"(d[45]),"+f"(d[46]),"+f"(d[47]),"+f"(d[48]),"+f"(d[49]),"+f"(d[50]),"+f"(d[51]),"+f"(d[52]),"+f"(d[53]),"+f"(d[54]),"+f"(d[55]),"+f"(d[56]),"+f"(d[57]),"+f"(d[58]),"+f"(d[59]),"+f"(d[60]),"+f"(d[61]),"+f"(d[62]),"+f"(d[63]),"+f"(d[64]),"+f"(d[65]),"+f"(d[66]),"+f"(d[67]),"+f"(d[68]),"+f"(d[69]),"+f"(d[70]),"+f"(d[71]),"+f"(d[72]),"+f"(d[73]),"+f"(d[74]),"+f"(d[75]),"+f"(d[76]),"+f"(d[77]),"+f"(d[78]),"+f"(d[79]),"+f"(d[80]),"+f"(d[81]),"+f"(d[82]),"+f"(d[83]),"+f"(d[84]),"+f"(d[85]),"+f"(d[86]),"+f"(d[87]),"+f"(d[88]),"+f"(d[89]),"+f"(d[90]),"+f"(d[91]),"+f"(d[92]),"+f"(d[93]),"+f"(d[94]),"+f"(d[95]),"+f"(d[96]),"+f"(d[97]),"+f"(d[98]),"+f"(d[99]),"+f"(d[100]),"+f"(d[101]),"+f"(d[102]),"+f"(d[103]),"+f"(d[104]),"+f"(d[105]),"+f"(d[106]),"+f"(d[107]),"+f"(d[108]),"+f"(d[109]),"+f"(d[110]),"+f"(d[111]),"+f"(d[112]),"+f"(d[113]),"+f"(d[114]),"+f"(d[115]),"+f"(d[116]),"+f"(d[117]),"+f"(d[118]),"+f"(d[119]),"+f"(d[120]),"+f"(d[121]),"+f"(d[122]),"+f"(d[123]),"+f"(d[124]),"+f"(d[125]),"+f"(d[126]),"+f"(d[127])
    : "r"(da), "r"(db), "r"(sd));
}
__device__ __forceinline__ void wgmma_ss_n128(float (&d)[64], uint32_t da, uint32_t db, int sd) {
  asm volatile("{\n.reg .pred p;\n.reg .b64 a, b;\nsetp.ne.b32 p, %66, 0;\nmov.b64 a, {%64, 0x40000040};\nmov.b64 b, {%65, 0x40000040};\n"
    "wgmma.mma_async.sync.aligned.m64n128k16.f32.bf16.bf16 {%0,%1,%2,%3,%4,%5,%6,%7,%8,%9,%10,%11,%12,%13,%14,%15,%16,%17,%18,%19,%20,%21,%22,%23,%24,%25,%26,%27,%28,%29,%30,%31,%32,%33,%34,%35,%36,%37,%38,%39,%40,%41,%42,%43,%44,%45,%46,%47,%48,%49,%50,%51,%52,%53,%54,%55,%56,%57,%58,%59,%60,%61,%62,%63}, a, b, p, 1, 1, 0, 1;\n}\n"
    : "+f"(d[0]),"+f"(d[1]),"+f"(d[2]),"+f"(d[3]),"+f"(d[4]),"+f"(d[5]),"+f"(d[6]),"+f"(d[7]),"+f"(d[8]),"+f"(d[9]),"+f"(d[10]),"+f"(d[11]),"+f"(d[12]),"+f"(d[13]),"+f"(d[14]),"+f"(d[15]),"+f"(d[16]),"+f"(d[17]),"+f"(d[18]),"+f"(d[19]),"+f"(d[20]),"+f"(d[21]),"+f"(d[22]),"+f"(d[23]),"+f"(d[24]),"+f"(d[25]),"+f"(d[26]),"+f"(d[27]),"+f"(d[28]),"+f"(d[29]),"+f"(d[30]),"+f"(d[31]),"+f"(d[32]),"+f"(d[33]),"+f"(d[34]),"+f"(d[35]),"+f"(d[36]),"+f"(d[37]),"+f"(d[38]),"+f"(d[39]),"+f"(d[40]),"+f"(d[41]),"+f"(d[42]),"+f"(d[43]),"+f"(d[44]),"+f"(d[45]),"+f"(d[46]),"+f"(d[47]),"+f"(d[48]),"+f"(d[49]),"+f"(d[50]),"+f"(d[51]),"+f"(d[52]),"+f"(d[53]),"+f"(d[54]),"+f"(d[55]),"+f"(d[56]),"+f"(d[57]),"+f"(d[58]),"+f"(d[59]),"+f"(d[60]),"+f"(d[61]),"+f"(d[62]),"+f"(d[63])
    : "r"(da), "r"(db), "r"(sd));
}
__device__ __forceinline__ void wgmma_ss_n40_tt(float (&d)[20], uint32_t da, uint32_t db, int sd) {
  asm volatile("{\n.reg .pred p;\n.reg .b64 a, b;\nsetp.ne.b32 p, %22, 0;\nmov.b64 a, {%20, 0x40000040};\nmov.b64 b, {%21, 0x8};\n"
    "wgmma.mma_async.sync.aligned.m64n40k16.f32.bf16.bf16 {%0,%1,%2,%3,%4,%5,%6,%7,%8,%9,%10,%11,%12,%13,%14,%15,%16,%17,%18,%19}, a, b, p, 1, 1, 1, 1;\n}\n"
    : "+f"(d[0]),"+f"(d[1]),"+f"(d[2]),"+f"(d[3]),"+f"(d[4]),"+f"(d[5]),"+f"(d[6]),"+f"(d[7]),"+f"(d[8]),"+f"(d[9]),"+f"(d[10]),"+f"(d[11]),"+f"(d[12]),"+f"(d[13]),"+f"(d[14]),"+f"(d[15]),"+f"(d[16]),"+f"(d[17]),"+f"(d[18]),"+f"(d[19])
    : "r"(da), "r"(db), "r"(sd));
}
__device__ __forceinline__ void wgmma_rs_n32(float (&d)[16], uint32_t a0, uint32_t a1, uint32_t a2, uint32_t a3, uint32_t db, int sd) {
  asm volatile("{\n.reg .pred p;\n.reg .b64 b;\nsetp.ne.b32 p, %21, 0;\nmov.b64 b, {%20, 0x80000020};\n"
    "wgmma.mma_async.sync.aligned.m64n32k16.f32.bf16.bf16 {%0,%1,%2,%3,%4,%5,%6,%7,%8,%9,%10,%11,%12,%13,%14,%15}, {%16,%17,%18,%19}, b, p, 1, 1, 1;\n}\n"
    : "+f"(d[0]),"+f"(d[1]),"+f"(d[2]),"+f"(d[3]),"+f"(d[4]),"+f"(d[5]),"+f"(d[6]),"+f"(d[7]),"+f"(d[8]),"+f"(d[9]),"+f"(d[10]),"+f"(d[11]),"+f"(d[12]),"+f"(d[13]),"+f"(d[14]),"+f"(d[15])
    : "r"(a0), "r"(a1), "r"(a2), "r"(a3), "r"(db), "r"(sd));
}
__device__ __forceinline__ void wgmma_rs_n40(float (&d)[20], uint32_t a0, uint32_t a1, uint32_t a2, uint32_t a3, uint32_t db, int sd) {
  asm volatile("{\n.reg .pred p;\n.reg .b64 b;\nsetp.ne.b32 p, %25, 0;\nmov.b64 b, {%24, 0x10};\n"
    "wgmma.mma_async.sync.aligned.m64n40k16.f32.bf16.bf16 {%0,%1,%2,%3,%4,%5,%6,%7,%8,%9,%10,%11,%12,%13,%14,%15,%16,%17,%18,%19}, {%20,%21,%22,%23}, b, p, 1, 1, 1;\n}\n"
    : "+f"(d[0]),"+f"(d[1]),"+f"(d[2]),"+f"(d[3]),"+f"(d[4]),"+f"(d[5]),"+f"(d[6]),"+f"(d[7]),"+f"(d[8]),"+f"(d[9]),"+f"(d[10]),"+f"(d[11]),"+f"(d[12]),"+f"(d[13]),"+f"(d[14]),"+f"(d[15]),"+f"(d[16]),"+f"(d[17]),"+f"(d[18]),"+f"(d[19])
    : "r"(a0), "r"(a1), "r"(a2), "r"(a3), "r"(db), "r"(sd));
}
__device__ __forceinline__ void wgmma_rs_n8(float (&d)[4], uint32_t a0, uint32_t a1, uint32_t a2, uint32_t a3, uint32_t db, int sd) {
  asm volatile("{\n.reg .pred p;\n.reg .b64 b;\nsetp.ne.b32 p, %9, 0;\nmov.b64 b, {%8, 0x8};\n"
    "wgmma.mma_async.sync.aligned.m64n8k16.f32.bf16.bf16 {%0,%1,%2,%3}, {%4,%5,%6,%7}, b, p, 1, 1, 0;\n}\n"
    : "+f"(d[0]),"+f"(d[1]),"+f"(d[2]),"+f"(d[3])
    : "r"(a0), "r"(a1), "r"(a2), "r"(a3), "r"(db), "r"(sd));
}
__device__ __forceinline__ void wgmma_rs_n256(float (&d)[128], uint32_t a0, uint32_t a1, uint32_t a2, uint32_t a3, uint32_t db, int sd) {
  asm volatile("{\n.reg .pred p;\n.reg .b64 b;\nsetp.ne.b32 p, %133, 0;\nmov.b64 b, {%132, 0x6};\n"
    "wgmma.mma_async.sync.aligned.m64n256k16.f32.bf16.bf16 {%0,%1,%2,%3,%4,%5,%6,%7,%8,%9,%10,%11,%12,%13,%14,%15,%16,%17,%18,%19,%20,%21,%22,%23,%24,%25,%26,%27,%28,%29,%30,%31,%32,%33,%34,%35,%36,%37,%38,%39,%40,%41,%42,%43,%44,%45,%46,%47,%48,%49,%50,%51,%52,%53,%54,%55,%56,%57,%58,%59,%60,%61,%62,%63,%64,%65,%66,%67,%68,%69,%70,%71,%72,%73,%74,%75,%76,%77,%78,%79,%80,%81,%82,%83,%84,%85,%86,%87,%88,%89,%90,%91,%92,%93,%94,%95,%96,%97,%98,%99,%100,%101,%102,%103,%104,%105,%106,%107,%108,%109,%110,%111,%112,%113,%114,%115,%116,%117,%118,%119,%120,%121,%122,%123,%124,%125,%126,%127}, {%128,%129,%130,%131}, b, p, 1, 1, 1;\n}\n"
    : "+f"(d[0]),"+f"(d[1]),"+f"(d[2]),"+f"(d[3]),"+f"(d[4]),"+f"(d[5]),"+f"(d[6]),"+f"(d[7]),"+f"(d[8]),"+f"(d[9]),"+f"(d[10]),"+f"(d[11]),"+f"(d[12]),"+f"(d[13]),"+f"(d[14]),"+f"(d[15]),"+f"(d[16]),"+f"(d[17]),"+f"(d[18]),"+f"(d[19]),"+f"(d[20]),"+f"(d[21]),"+f"(d[22]),"+f"(d[23]),"+f"(d[24]),"+f"(d[25]),"+f"(d[26]),"+f"(d[27]),"+f"(d[28]),"+f"(d[29]),"+f"(d[30]),"+f"(d[31]),"+f"(d[32]),"+f"(d[33]),"+f"(d[34]),"+f"(d[35]),"+f"(d[36]),"+f"(d[37]),"+f"(d[38]),"+f"(d[39]),"+f"(d[40]),"+f"(d[41]),"+f"(d[42]),"+f"(d[43]),"+f"(d[44]),"+f"(d[45]),"+f"(d[46]),"+f"(d[47]),"+f"(d[48]),"+f"(d[49]),"+f"(d[50]),"+f"(d[51]),"+f"(d[52]),"+f"(d[53]),"+f"(d[54]),"+f"(d[55]),"+f"(d[56]),"+f"(d[57]),"+f"(d[58]),"+f"(d[59]),"+f"(d[60]),"+f"(d[61]),"+f"(d[62]),"+f"(d[63]),"+f"(d[64]),"+f"(d[65]),"+f"(d[66]),"+f"(d[67]),"+f"(d[68]),"+f"(d[69]),"+f"(d[70]),"+f"(d[71]),"+f"(d[72]),"+f"(d[73]),"+f"(d[74]),"+f"(d[75]),"+f"(d[76]),"+f"(d[77]),"+f"(d[78]),"+f"(d[79]),"+f"(d[80]),"+f"(d[81]),"+f"(d[82]),"+f"(d[83]),"+f"(d[84]),"+f"(d[85]),"+f"(d[86]),"+f"(d[87]),"+f"(d[88]),"+f"(d[89]),"+f"(d[90]),"+f"(d[91]),"+f"(d[92]),"+f"(d[93]),"+f"(d[94]),"+f"(d[95]),"+f"(d[96]),"+f"(d[97]),"+f"(d[98]),"+f"(d[99]),"+f"(d[100]),"+f"(d[101]),"+f"(d[102]),"+f"(d[103]),"+f"(d[104]),"+f"(d[105]),"+f"(d[106]),"+f"(d[107]),"+f"(d[108]),"+f"(d[109]),"+f"(d[110]),"+f"(d[111]),"+f"(d[112]),"+f"(d[113]),"+f"(d[114]),"+f"(d[115]),"+f"(d[116]),"+f"(d[117]),"+f"(d[118]),"+f"(d[119]),"+f"(d[120]),"+f"(d[121]),"+f"(d[122]),"+f"(d[123]),"+f"(d[124]),"+f"(d[125]),"+f"(d[126]),"+f"(d[127])
    : "r"(a0), "r"(a1), "r"(a2), "r"(a3), "r"(db), "r"(sd));
}
__device__ __forceinline__ void wgmma_rs_n128(float (&d)[64], uint32_t a0, uint32_t a1, uint32_t a2, uint32_t a3, uint32_t db, int sd) {
  asm volatile("{\n.reg .pred p;\n.reg .b64 b;\nsetp.ne.b32 p, %69, 0;\nmov.b64 b, {%68, 0x6};\n"
    "wgmma.mma_async.sync.aligned.m64n128k16.f32.bf16.bf16 {%0,%1,%2,%3,%4,%5,%6,%7,%8,%9,%10,%11,%12,%13,%14,%15,%16,%17,%18,%19,%20,%21,%22,%23,%24,%25,%26,%27,%28,%29,%30,%31,%32,%33,%34,%35,%36,%37,%38,%39,%40,%41,%42,%43,%44,%45,%46,%47,%48,%49,%50,%51,%52,%53,%54,%55,%56,%57,%58,%59,%60,%61,%62,%63}, {%64,%65,%66,%67}, b, p, 1, 1, 1;\n}\n"
    : "+f"(d[0]),"+f"(d[1]),"+f"(d[2]),"+f"(d[3]),"+f"(d[4]),"+f"(d[5]),"+f"(d[6]),"+f"(d[7]),"+f"(d[8]),"+f"(d[9]),"+f"(d[10]),"+f"(d[11]),"+f"(d[12]),"+f"(d[13]),"+f"(d[14]),"+f"(d[15]),"+f"(d[16]),"+f"(d[17]),"+f"(d[18]),"+f"(d[19]),"+f"(d[20]),"+f"(d[21]),"+f"(d[22]),"+f"(d[23]),"+f"(d[24]),"+f"(d[25]),"+f"(d[26]),"+f"(d[27]),"+f"(d[28]),"+f"(d[29]),"+f"(d[30]),"+f"(d[31]),"+f"(d[32]),"+f"(d[33]),"+f"(d[34]),"+f"(d[35]),"+f"(d[36]),"+f"(d[37]),"+f"(d[38]),"+f"(d[39]),"+f"(d[40]),"+f"(d[41]),"+f"(d[42]),"+f"(d[43]),"+f"(d[44]),"+f"(d[45]),"+f"(d[46]),"+f"(d[47]),"+f"(d[48]),"+f"(d[49]),"+f"(d[50]),"+f"(d[51]),"+f"(d[52]),"+f"(d[53]),"+f"(d[54]),"+f"(d[55]),"+f"(d[56]),"+f"(d[57]),"+f"(d[58]),"+f"(d[59]),"+f"(d[60]),"+f"(d[61]),"+f"(d[62]),"+f"(d[63])
    : "r"(a0), "r"(a1), "r"(a2), "r"(a3), "r"(db), "r"(sd));
}

__device__ __forceinline__ uint32_t smem_u32(const void* p) { return (uint32_t)__cvta_generic_to_shared(p); }
__device__ __forceinline__ void mbar_init(uint32_t bar, uint32_t cnt) { asm volatile("mbarrier.init.shared::cta.b64 [%0], %1;" ::"r"(bar), "r"(cnt)); }
__device__ __forceinline__ void mbar_expect_tx(uint32_t bar, uint32_t bytes) { asm volatile("mbarrier.arrive.expect_tx.shared::cta.b64 _, [%0], %1;" ::"r"(bar), "r"(bytes) : "memory"); }
__device__ __forceinline__ void mbar_arrive(uint32_t bar) { asm volatile("mbarrier.arrive.shared::cta.b64 _, [%0];" ::"r"(bar) : "memory"); }
__device__ __forceinline__ void mbar_wait(uint32_t bar, uint32_t parity) {
  asm volatile("{\n.reg .pred p;\nLAB_WAIT:\nmbarrier.try_wait.parity.shared::cta.b64 p, [%0], %1;\n@p bra DONE;\nbra LAB_WAIT;\nDONE:\n}" ::"r"(bar), "r"(parity) : "memory");
}
__device__ __forceinline__ void mbar_wait2(uint32_t a, uint32_t pa, uint32_t b, uint32_t pb) {
  asm volatile("{\n.reg .pred p, q;\nLAB_WAIT:\nmbarrier.try_wait.parity.shared::cta.b64 p, [%0], %1;\nmbarrier.try_wait.parity.shared::cta.b64 q, [%2], %3;\n"
               "and.pred p, p, q;\n@p bra DONE;\nbra LAB_WAIT;\nDONE:\n}" ::"r"(a), "r"(pa), "r"(b), "r"(pb) : "memory");
}
__device__ __forceinline__ void mbar_wait3(uint32_t a, uint32_t pa, uint32_t b, uint32_t pb) {
  asm volatile("{\n.reg .pred p, q, r;\nLAB_WAIT:\nmbarrier.try_wait.parity.shared::cta.b64 p, [%0], %1;\nmbarrier.try_wait.parity.shared::cta.b64 q, [%2], %3;\n"
               "mbarrier.try_wait.parity.shared::cta.b64 r, [%2+8], %3;\nand.pred p, p, q;\nand.pred p, p, r;\n@p bra DONE;\nbra LAB_WAIT;\nDONE:\n}" ::"r"(a), "r"(pa), "r"(b), "r"(pb) : "memory");
}
__device__ __forceinline__ bool mbar_probe2(uint32_t a, uint32_t pa, uint32_t b, uint32_t pb) {
  uint32_t ok;
  asm volatile("{\n.reg .pred p, q;\nmbarrier.test_wait.parity.shared::cta.b64 p, [%1], %2;\nmbarrier.test_wait.parity.shared::cta.b64 q, [%3], %4;\n"
               "and.pred p, p, q;\nselp.u32 %0, 1, 0, p;\n}" : "=r"(ok) : "r"(a), "r"(pa), "r"(b), "r"(pb) : "memory");
  return ok != 0;
}
__device__ __forceinline__ void tma_load_3d(uint32_t dst, const CUtensorMap* tm, uint32_t bar, int c0, int c1, int c2) {
  asm volatile("cp.async.bulk.tensor.3d.shared::cluster.global.mbarrier::complete_tx::bytes [%0], [%1, {%3, %4, %5}], [%2];"
               ::"r"(dst), "l"(tm), "r"(bar), "r"(c0), "r"(c1), "r"(c2) : "memory");
}
__device__ __forceinline__ void tma_load_2d(uint32_t dst, const CUtensorMap* tm, uint32_t bar, int c0, int c1) {
  asm volatile("cp.async.bulk.tensor.2d.shared::cluster.global.mbarrier::complete_tx::bytes [%0], [%1, {%3, %4}], [%2];"
               ::"r"(dst), "l"(tm), "r"(bar), "r"(c0), "r"(c1) : "memory");
}
__device__ __forceinline__ void tma_prefetch_3d(const CUtensorMap* tm, int c0, int c1, int c2) {
  asm volatile("cp.async.bulk.prefetch.tensor.3d.L2.global [%0, {%1, %2, %3}];" ::"l"(tm), "r"(c0), "r"(c1), "r"(c2) : "memory");
}
__device__ __forceinline__ void bulk_load(uint32_t dst, const void* g, uint32_t bytes, uint32_t bar) {
  asm volatile("cp.async.bulk.shared::cluster.global.mbarrier::complete_tx::bytes [%0], [%1], %2, [%3];" ::"r"(dst), "l"(g), "r"(bytes), "r"(bar) : "memory");
}
__device__ __forceinline__ void prefetch_map(const CUtensorMap* tm) { asm volatile("prefetch.tensormap [%0];" ::"l"(tm) : "memory"); }
__device__ __forceinline__ void fence_async_smem() { asm volatile("fence.proxy.async.shared::cta;" ::: "memory"); }
__device__ __forceinline__ void fence_async_global() { asm volatile("fence.proxy.async.global;" ::: "memory"); }
__device__ __forceinline__ void fence_gpu() { asm volatile("fence.release.gpu;" ::: "memory"); }
__device__ __forceinline__ void st_flag(unsigned* p, unsigned v) { asm volatile("st.relaxed.gpu.global.u32 [%0], %1;" ::"l"(p), "r"(v) : "memory"); }
__device__ __forceinline__ unsigned ld_flag(const unsigned* p) { unsigned v; asm volatile("ld.relaxed.gpu.global.u32 %0, [%1];" : "=r"(v) : "l"(p) : "memory"); return v; }
__device__ __forceinline__ uint4 ldcg4(const void* p) { uint4 v; asm volatile("ld.global.cg.v4.u32 {%0,%1,%2,%3}, [%4];" : "=r"(v.x), "=r"(v.y), "=r"(v.z), "=r"(v.w) : "l"(p)); return v; }
__device__ __forceinline__ uint4 ld_pkt(const uint4* p) {
  uint4 v; asm volatile("{\n.reg .b128 t;\nld.relaxed.gpu.global.b128 t, [%4];\nmov.b128 {%0,%1,%2,%3}, t;\n}" : "=r"(v.x), "=r"(v.y), "=r"(v.z), "=r"(v.w) : "l"(p) : "memory"); return v;
}
__device__ __forceinline__ void st_pkt(uint4* p, uint32_t a, uint32_t b, uint32_t c, uint32_t tag) {
  asm volatile("{\n.reg .b128 t;\nmov.b128 t, {%1,%2,%3,%4};\nst.relaxed.gpu.global.b128 [%0], t;\n}" ::"l"(p), "r"(a), "r"(b), "r"(c), "r"(tag) : "memory");
}
__device__ __forceinline__ void sts64(uint32_t addr, uint32_t a, uint32_t b) { asm volatile("st.shared.v2.u32 [%0], {%1,%2};" ::"r"(addr), "r"(a), "r"(b) : "memory"); }
__device__ __forceinline__ uint32_t mul2(uint32_t a, uint32_t b) { uint32_t r; asm("mul.rn.bf16x2 %0, %1, %2;" : "=r"(r) : "r"(a), "r"(b)); return r; }
__device__ __forceinline__ bool elect() {
  uint32_t p; asm volatile("{\n.reg .pred q;\nelect.sync _|q, 0xffffffff;\nselp.u32 %0, 1, 0, q;\n}" : "=r"(p)); return p != 0;
}
__device__ __forceinline__ void wgmma_fence() { asm volatile("wgmma.fence.sync.aligned;" ::: "memory"); }
__device__ __forceinline__ void wgmma_commit() { asm volatile("wgmma.commit_group.sync.aligned;" ::: "memory"); }
template <int N> __device__ __forceinline__ void wgmma_wait() { asm volatile("wgmma.wait_group.sync.aligned %0;" ::"n"(N) : "memory"); }
template <int N> __device__ __forceinline__ void fence_regs(float (&d)[N]) {
#pragma unroll
  for (int i = 0; i < N; i++) asm volatile("" : "+f"(d[i])::"memory");
}
template <int R> __device__ __forceinline__ void reg_alloc() { asm volatile("setmaxnreg.inc.sync.aligned.u32 %0;" ::"n"(R)); }
template <int R> __device__ __forceinline__ void reg_dealloc() { asm volatile("setmaxnreg.dec.sync.aligned.u32 %0;" ::"n"(R)); }
__device__ __forceinline__ void wg_bar(int w) { asm volatile("bar.sync %0, 128;" ::"r"(w + 1) : "memory"); }
__device__ __forceinline__ constexpr uint32_t desc_lo(uint32_t addr, uint32_t lbo) { return (addr >> 4) + ((lbo >> 4) << 16); }
__device__ __forceinline__ uint32_t pack2(float lo, float hi) { uint32_t r; asm("cvt.rn.bf16x2.f32 %0, %1, %2;" : "=r"(r) : "f"(hi), "f"(lo)); return r; }
__device__ __forceinline__ float lo16(uint32_t v) { return __uint_as_float(v << 16); }
__device__ __forceinline__ float hi16(uint32_t v) { return __uint_as_float(v & 0xFFFF0000u); }
__device__ __forceinline__ float ex2(float x) { float r; asm("ex2.approx.ftz.f32 %0, %1;" : "=f"(r) : "f"(x)); return r; }
__device__ __forceinline__ float rcp(float x) { float r; asm("rcp.approx.ftz.f32 %0, %1;" : "=f"(r) : "f"(x)); return r; }
__device__ __forceinline__ uint32_t movm(uint32_t a) { uint32_t d; asm volatile("movmatrix.sync.aligned.m8n8.trans.b16 %0, %1;" : "=r"(d) : "r"(a)); return d; }
__device__ __forceinline__ void stsm4(uint32_t addr, uint32_t a, uint32_t b, uint32_t c, uint32_t d) {
  asm volatile("stmatrix.sync.aligned.m8n8.x4.shared.b16 [%0], {%1,%2,%3,%4};" ::"r"(addr), "r"(a), "r"(b), "r"(c), "r"(d) : "memory");
}
__device__ __forceinline__ void ldsm4(uint32_t addr, uint32_t (&r)[4]) {
  asm volatile("ldmatrix.sync.aligned.m8n8.x4.shared.b16 {%0,%1,%2,%3}, [%4];" : "=r"(r[0]), "=r"(r[1]), "=r"(r[2]), "=r"(r[3]) : "r"(addr) : "memory");
}
__device__ __forceinline__ void sts128(uint32_t addr, uint32_t a, uint32_t b, uint32_t c, uint32_t d) {
  asm volatile("st.shared.v4.u32 [%0], {%1,%2,%3,%4};" ::"r"(addr), "r"(a), "r"(b), "r"(c), "r"(d) : "memory");
}
__device__ __forceinline__ void lds128(uint32_t addr, uint32_t& a, uint32_t& b, uint32_t& c, uint32_t& d) {
  asm volatile("ld.shared.v4.u32 {%0,%1,%2,%3}, [%4];" : "=r"(a), "=r"(b), "=r"(c), "=r"(d) : "r"(addr) : "memory");
}
__device__ __forceinline__ float2 lds64f(uint32_t addr) { float2 v; asm volatile("ld.shared.v2.f32 {%0,%1}, [%2];" : "=f"(v.x), "=f"(v.y) : "r"(addr) : "memory"); return v; }
__device__ __forceinline__ void mma16816(float (&d)[4], uint32_t a0, uint32_t a1, uint32_t a2, uint32_t a3, uint32_t b0, uint32_t b1) {
  asm("mma.sync.aligned.m16n8k16.row.col.f32.bf16.bf16.f32 {%0,%1,%2,%3}, {%4,%5,%6,%7}, {%8,%9}, {%0,%1,%2,%3};"
      : "+f"(d[0]), "+f"(d[1]), "+f"(d[2]), "+f"(d[3]) : "r"(a0), "r"(a1), "r"(a2), "r"(a3), "r"(b0), "r"(b1));
}
__device__ __forceinline__ void mma1688(float (&d)[4], uint32_t a0, uint32_t a1, uint32_t b0) {
  asm("mma.sync.aligned.m16n8k8.row.col.f32.bf16.bf16.f32 {%0,%1,%2,%3}, {%4,%5}, {%6}, {%0,%1,%2,%3};"
      : "+f"(d[0]), "+f"(d[1]), "+f"(d[2]), "+f"(d[3]) : "r"(a0), "r"(a1), "r"(b0));
}

__device__ __forceinline__ float qsum(float v) { v += __shfl_xor_sync(0xffffffffu, v, 1); v += __shfl_xor_sync(0xffffffffu, v, 2); return v; }

constexpr int NCTA = 128;
#define NB_ 6
#define NA_ 5
constexpr int NB = NB_;
constexpr int NA = NA_;
constexpr uint32_t SLOT = 16384;
constexpr uint32_t SB = 1024;
constexpr uint32_t OFF_B = 0;
constexpr uint32_t OFF_A = NB * SLOT;
constexpr uint32_t OFF_S = OFF_A + NA * SLOT;
constexpr uint32_t OFF_T = OFF_S + 20480;
constexpr uint32_t OFF_CS = OFF_T + 24576;
constexpr uint32_t OFF_ONE = OFF_CS + 4640;
constexpr uint32_t OFF_MR = OFF_ONE + 144;
constexpr uint32_t OFF_BAR = OFF_MR + 1024;
constexpr uint32_t BAR_FULLB = OFF_BAR;
constexpr uint32_t BAR_FULLA = BAR_FULLB + 64;
constexpr uint32_t BAR_EMPTYB = BAR_FULLA + 64;
constexpr uint32_t BAR_EMPTYA = BAR_EMPTYB + 64;
constexpr uint32_t BAR_SIGP = BAR_EMPTYA + 64;
constexpr uint32_t BAR_SIGT = BAR_EMPTYA + 48;
constexpr uint32_t BAR_STAT = BAR_SIGP + 64;
constexpr uint32_t BAR_HALO = BAR_STAT + 16;
constexpr uint32_t BAR_CS = BAR_HALO + 8;
constexpr uint32_t BAR_WPHI = BAR_CS + 16;
constexpr uint32_t BAR_KV = BAR_WPHI + 8;
constexpr uint32_t BAR_STG = BAR_KV + 16;
constexpr uint32_t BAR_EPOCH = BAR_STG + 48;
constexpr uint32_t OFF_EPOCH = OFF_BAR + 7 * 64;
static_assert(BAR_EPOCH < OFF_EPOCH, "barriers");
constexpr uint32_t SMEM_BYTES = OFF_EPOCH + 8;
static_assert(SMEM_BYTES <= 232448 && NB % 2 == 0 && NB <= 8 && NA <= 6, "smem");

#define CREGS 208
#define PREGS 88
#define PF0 21
#define PFS 2
#define PRE_A 2
#define PRE_B 4
#define CSB 4
#define KB 8
#define PNX 2
#define PNO 2
#define RLIM 1.8446744e19f
#define DEFER 3
#define DEFL 2
#define TSK 3
#define TSL 3
constexpr int NTHREADS = 384;

struct Params {
  CUtensorMap mx[4];
  CUtensorMap mo;
  CUtensorMap mw[2];
  CUtensorMap mwo[2];
  CUtensorMap mwphi;
  CUtensorMap mcs[2];
  uint4* xp[5];
};

__device__ __align__(256) __nv_bfloat16 g_o[2048 * 1024];
__device__ __align__(256) uint4 g_stats[16][2][8][32];
__device__ __align__(256) uint4 g_halo[16][8][2][256];
__device__ __align__(256) float g_cs[2][2][3072];
__device__ __align__(256) uint4 g_kvpart[8][16][3][16][32];
__device__ __align__(256) uint32_t g_kvfin[8][16][320];
__device__ __align__(256) unsigned g_xflag[4][2][16][32];
__device__ __align__(256) unsigned g_oflag[4][2][16][32];
__device__ __align__(256) unsigned g_hflag[2][16][8][32];
__device__ __align__(256) unsigned g_kvfflag[2][8][2][32];
__device__ __align__(256) unsigned g_csflag[2][8][32];
__device__ __align__(256) unsigned g_kvhint[8][16][32];
__device__ unsigned g_ctr;
#define TS(who, id) do {} while (0)
#define TSW(id) do {} while (0)

__device__ __forceinline__ int cta_m() { return ((blockIdx.x >> 2) & 12) | (blockIdx.x & 3); }
__device__ __forceinline__ int cta_j() { return ((blockIdx.x >> 2) & 3) | ((blockIdx.x >> 4) & 4); }
struct Ring { uint32_t s, ph; };
template <int N> __device__ __forceinline__ void adv(Ring& r) { if (++r.s == N) { r.s = 0; r.ph ^= 1; } }
template <int N> __device__ __forceinline__ void rewind2(Ring& r) { if (r.s < 2) { r.s += N - 2; r.ph ^= 1; } else r.s -= 2; }
__device__ __forceinline__ int other_tile(int t, int j) { return (t == (j | 4) ? 7 : t) ^ (~j & 4); }
__device__ __forceinline__ int q_order(int i, int j) { return 2 * (i >= 14 ? j : other_tile(i >> 1, j)) + (i & 1); }
__device__ __forceinline__ int o_order(int i, int j) {
  if (i < 2) return 2 * j + i;
  const int odd = i >= 9;
  return 2 * other_tile(i - 2 - 7 * odd, j) + odd;
}
__device__ __forceinline__ int kv_order(int i, int j, int L) { return L > 0 ? o_order(i, j) : (i + 14 + 2 * (j & 4)) & 15; }

__device__ __forceinline__ unsigned poll_flags(const unsigned* f, int n, unsigned need, unsigned tag) {
  const int lane = threadIdx.x & 31;
  unsigned mask; int it = 0;
  do {
    unsigned v = lane < n ? ld_flag(f + lane) : 0u;
    mask = __ballot_sync(0xffffffffu, lane < n && v == tag);
    if (++it > (1 << 22)) __trap();
  } while ((mask & need) != need);
  fence_async_global();
  return mask;
}
template <bool WAIT = true>
__device__ __forceinline__ unsigned get_tag(uint32_t sb) {
  if (WAIT) mbar_wait(sb + BAR_EPOCH, 0);
  unsigned t; asm volatile("ld.shared.u32 %0, [%1];" : "=r"(t) : "r"(sb + OFF_EPOCH) : "memory");
  return t;
}

__device__ __forceinline__ int lane_id() { int l; asm volatile("mov.u32 %0, %%laneid;" : "=r"(l)); return l; }
__device__ __forceinline__ unsigned seq4(unsigned tag, int L) { return 8u | ((tag & 1u) << 2) | (unsigned)L; }
constexpr float LOG2E = 1.4426950408889634f;

__device__ __forceinline__ void sched_fence(uint32_t sb) { mbar_wait(sb + BAR_EPOCH, 0); }
struct Ctx {
  static constexpr uint32_t sb = SB;
  uint32_t ab, da0;
  int w, warp, lane, g, c, m, j;
  bool elected;
  Ring ra, rb;
  uint32_t pa, pb;
  uint32_t mrow, mxor, mhi;
  __device__ __forceinline__ uint32_t aslot(uint32_t s) const { return ab + s * SLOT; }
  __device__ __forceinline__ uint32_t fullA(uint32_t s) const { return sb + BAR_FULLA + s * 8; }
  __device__ __forceinline__ uint32_t fullB(uint32_t s) const { return sb + BAR_FULLB + s * 8; }
  __device__ __forceinline__ void releaseA(uint32_t s) const { if (elected) mbar_arrive(sb + BAR_EMPTYA + s * 8); }
  __device__ __forceinline__ void releaseB(uint32_t s) const { if (elected) mbar_arrive(sb + BAR_EMPTYB + s * 8); }
  __device__ __forceinline__ uint32_t maddr(uint32_t tile, uint32_t ch) const { return tile + mrow + (((ch + mhi) ^ mxor) << 4); }
  __device__ __forceinline__ uint32_t held(int i) const { return ra.s + i < 2 ? ra.s + i + NA - 2 : ra.s + i - 2; }
};

template <int N, bool FIRST>
__device__ __forceinline__ void gemm_issue(float (&acc)[N / 2], Ctx& x, bool ready = false) {
  if (!ready) {
    if (N == 256) mbar_wait3(x.fullA(x.ra.s), x.ra.ph, x.fullB(x.rb.s), x.rb.ph);
    else mbar_wait2(x.fullA(x.ra.s), x.ra.ph, x.fullB(x.rb.s), x.rb.ph);
  }
  const uint32_t da = x.da0 + x.ra.s * (SLOT / 16), db = desc_lo(SB + OFF_B, 8192) + x.rb.s * (SLOT / 16);
  wgmma_fence();
#pragma unroll
  for (int k = 0; k < 4; k++) {
    if constexpr (N == 256) wgmma_ss_n256(acc, da + 2 * k, db + 128 * k, !(FIRST && k == 0));
    else wgmma_ss_n128(acc, da + 2 * k, db + 128 * k, !(FIRST && k == 0));
  }
  wgmma_commit();
}
template <int N>
__device__ __forceinline__ void gemm_next(Ctx& x) {
  x.pa = x.ra.s; x.pb = x.rb.s;
  if (N == 256) x.rb.s++;
  adv<NA>(x.ra); adv<NB>(x.rb);
}
template <int N>
__device__ __forceinline__ void gemm_release(Ctx& x, bool relA) {
  if (relA) x.releaseA(x.pa);
  x.releaseB(x.pb);
  if (N == 256) x.releaseB(x.pb + 1);
}
template <int N>
__device__ __forceinline__ void gemm_retire(Ctx& x, bool relA) { wgmma_wait<1>(); gemm_release<N>(x, relA); gemm_next<N>(x); }
__device__ __forceinline__ void gemm_run(float (&acc)[64], Ctx& x, int n, int hold) {
  bool ready = false;
#pragma unroll 1
  for (; n > 0; n--) {
    gemm_issue<128, false>(acc, x, ready);
    const uint32_t pa = x.pa, pb = x.pb;
    gemm_next<128>(x);
    ready = mbar_probe2(x.fullA(x.ra.s), x.ra.ph, x.fullB(x.rb.s), x.rb.ph);
    wgmma_wait<1>();
    if (n > hold) x.releaseA(pa);
    x.releaseB(pb);
  }
}
__device__ __forceinline__ void gemm_end(float (&acc)[64], Ctx& x) { wgmma_wait<0>(); fence_regs(acc); gemm_release<128>(x, false); }

__device__ __forceinline__ void load_x32(float* a, uint32_t tile, uint32_t ch, const Ctx& x) {
#pragma unroll
  for (int p = 0; p < 2; p++) {
    uint32_t v[4];
    ldsm4(x.maddr(tile, ch + 2 * p), v);
#pragma unroll
    for (int i = 0; i < 4; i++) { a[8 * p + 2 * i] = lo16(v[i]); a[8 * p + 2 * i + 1] = hi16(v[i]); }
  }
}

__device__ __forceinline__ void rows_load(uint4* r, uint32_t tile, const Ctx& x) {
#pragma unroll
  for (int q = 0; q < 4; q++) {
    const uint32_t row = x.warp * 16 + 4 * q + (x.lane >> 3);
    lds128(tile + row * 128 + (((x.lane & 7) ^ (row & 7)) << 4), r[q].x, r[q].y, r[q].z, r[q].w);
  }
}
__device__ __forceinline__ void rows_store(const uint4* r, uint4* g, const Ctx& x) {
  g += (x.warp * 16 + (x.lane >> 3)) * 256 + (x.lane & 7);
#pragma unroll
  for (int q = 0; q < 4; q++) g[q * 1024] = r[q];
}
__device__ __forceinline__ void publish(int id, const Ctx& x) { __syncwarp(); if (x.lane == 0) mbar_arrive(x.sb + BAR_SIGP + id * 8); }
__device__ __forceinline__ void tile_out(uint32_t tile, uint4* g, int id, const Ctx& x) {
  uint4 r[4];
  __syncwarp();
  rows_load(r, tile, x); rows_store(r, g, x); publish(id, x);
}

template <int N>
__device__ __forceinline__ void stats_acc(const float* a, float (&t)[4]) {
#pragma unroll
  for (int i = 0; i < N; i++) { t[i & 2] += a[i]; t[(i & 2) + 1] = fmaf(a[i], a[i], t[(i & 2) + 1]); }
}
__device__ __forceinline__ void stats_send(float (&t)[4], int L, const Ctx& x) {
  const unsigned seq = seq4(get_tag<false>(x.sb), L);
#pragma unroll
  for (int q = 0; q < 4; q++) t[q] = qsum(t[q]);
  if (x.c == 0) st_pkt(&g_stats[x.m][x.w][x.j][x.warp * 8 + x.g], __float_as_uint(t[0]), __float_as_uint(t[1]), __float_as_uint(t[2]), (__float_as_uint(t[3]) & ~15u) | seq);
}
__device__ __forceinline__ void out_epilogue(const float (&acc)[64], uint4 (&r1)[4], uint4* g, int L, Ctx& x) {
  const uint32_t t0 = x.aslot(x.ra.s), t1 = x.aslot(x.ra.s + 1 == NA ? 0 : x.ra.s + 1);
#pragma unroll
  for (int p = 0; p < 8; p++) {
    stsm4(x.maddr(p < 4 ? t0 : t1, (p & 3) * 2), pack2(acc[8 * p], acc[8 * p + 1]), pack2(acc[8 * p + 2], acc[8 * p + 3]),
          pack2(acc[8 * p + 4], acc[8 * p + 5]), pack2(acc[8 * p + 6], acc[8 * p + 7]));
    if (p == 3) { tile_out(t0, g, 2, x); sched_fence(x.sb); }
  }
  __syncwarp();
  rows_load(r1, t1, x);
  if (L < 3) {
    float t[4] = {0.f, 0.f, 0.f, 0.f}, u[4] = {0.f, 0.f, 0.f, 0.f};
    stats_acc<32>(acc, t); stats_acc<32>(acc + 32, u);
#pragma unroll
    for (int q = 0; q < 4; q++) t[q] += u[q];
    stats_send(t, L + 1, x);
    fence_async_smem();
    wg_bar(x.w);
  }
}

struct Stats { float rstd0, rstd1; };

__device__ __forceinline__ void hedgehog_pre(const float* a, float (&p)[64], uint32_t parity) {
  uint32_t f[32];
#pragma unroll
  for (int i = 0; i < 32; i++) f[i] = pack2(a[2 * i], a[2 * i + 1]);
  mbar_wait(SB + BAR_WPHI, parity);
  wgmma_fence();
#pragma unroll
  for (int q = 0; q < 8; q++) {
    wgmma_rs_n32(reinterpret_cast<float (&)[16]>(p[16 * (q >> 1)]), f[4 * q], f[4 * q + 1], f[4 * q + 2], f[4 * q + 3], desc_lo(SB + OFF_T, 512) + q * 64, q & 1);
    if ((q & 3) == 3) wgmma_commit();
  }
}
template <int NH>
__device__ __forceinline__ void hedgehog_prep(const float* a, const Stats& st, float* mm) {
#pragma unroll
  for (int t = 0; t < 4 * NH; t++) {
    const float* p = a + 4 * t;
    float* q = mm + (t & ~3);
    const float x0 = fmaxf(p[0], p[1]), x1 = fmaxf(p[2], p[3]);
    if ((t & 3) == 0) { q[0] = x0; q[1] = x1; }
    else { q[0] = fmaxf(q[0], x0); q[1] = fmaxf(q[1], x1); }
  }
#pragma unroll
  for (int d = 1; d <= 2; d++)
#pragma unroll
    for (int i = 0; i < 4 * NH; i++) if (!(i & 2)) mm[i] = fmaxf(mm[i], __shfl_xor_sync(0xffffffffu, mm[i], d));
#pragma unroll
  for (int i = 0; i < 4 * NH; i++) if (!(i & 2)) mm[i] = fmaf(mm[i], ((i & 1) ? st.rstd1 : st.rstd0) * -LOG2E, 30.f);
}
__device__ __forceinline__ bool hedgehog_exp(const float* p, const float* mm, const Stats& st, uint32_t (&f)[16]) {
  const float sc0 = st.rstd0 * LOG2E, sc1 = st.rstd1 * LOG2E;
  bool ok = true;
#pragma unroll
  for (int t = 0; t < 4; t++) {
    const float* q = p + 4 * t;
    const float a = ex2(fmaf(q[0], sc0, mm[0])), b = ex2(fmaf(q[1], sc0, mm[0])), c = ex2(fmaf(q[2], sc1, mm[1])), d = ex2(fmaf(q[3], sc1, mm[1]));
    const float u = a * b, v = c * d, r = rcp(u * v), ru = r * v, rv = r * u;
    f[2 * t] = pack2(a, b); f[2 * t + 1] = pack2(c, d);
    f[8 + 2 * t] = pack2(ru * b, ru * a); f[9 + 2 * t] = pack2(rv * d, rv * c);
    ok = ok && ru + rv <= RLIM;
  }
  return ok;
}
__device__ __forceinline__ void hedgehog_fix(bool ok, const float* p, const Stats& st, uint32_t (&f)[16]) {
  if (__builtin_expect(!__all_sync(0xffffffffu, ok), 0)) {
    float n0 = p[0], n1 = p[2];
#pragma unroll
    for (int i = 0; i < 16; i++) { if (i & 2) n1 = fminf(n1, p[i]); else n0 = fminf(n0, p[i]); }
#pragma unroll
    for (int d = 1; d <= 2; d++) { n0 = fminf(n0, __shfl_xor_sync(0xffffffffu, n0, d)); n1 = fminf(n1, __shfl_xor_sync(0xffffffffu, n1, d)); }
#pragma unroll
    for (int i = 0; i < 8; i++) {
      const float n = (i & 1) ? n1 : n0, sc = ((i & 1) ? st.rstd1 : st.rstd0) * LOG2E;
      f[8 + i] = pack2(ex2((n - p[2 * i]) * sc), ex2((n - p[2 * i + 1]) * sc));
    }
  }
}
__device__ __forceinline__ void cta_bar() { asm volatile("bar.sync 3, 256;" ::: "memory"); }

template <int N> __device__ __forceinline__ void pin(const uint32_t* v, uint32_t addr) {
#pragma unroll
  for (int i = 0; i < N; i += 4)
    asm volatile("{\n.reg .pred p;\nsetp.eq.u32 p, %0, 0;\n@p st.shared.v4.u32 [%0], {%1,%2,%3,%4};\n}" ::"r"(addr), "r"(v[i]), "r"(v[i + 1]), "r"(v[i + 2]), "r"(v[i + 3]) : "memory");
}

__device__ __forceinline__ void consumer(const Params& P, uint32_t sb, int w) {
  Ctx x;
  x.w = w;
  x.ab = sb + OFF_A + w * 8192; x.da0 = desc_lo(sb + OFF_A, 16) + w * 512;
  x.lane = threadIdx.x & 31; x.warp = __shfl_sync(0xffffffffu, (threadIdx.x >> 5) & 3, 0); x.g = x.lane >> 2; x.c = x.lane & 3;
  x.m = cta_m(); x.j = cta_j();
  x.elected = (threadIdx.x & 127) == 0;
  x.ra = {0, 0}; x.rb = {0, 0}; x.pa = x.pb = 0;
  {
    const uint32_t row = x.warp * 16 + (x.lane & 15);
    x.mrow = row * 128; x.mxor = row & 7; x.mhi = x.lane >> 4;
  }
  const int goff = (x.m * 128 + w) * 128 + x.j * 16;
  uint4 r1[4];
#pragma unroll
  for (int i = 0; i < 4; i++) r1[i] = make_uint4(0, 0, 0, 0);
  TSW(0);
#pragma unroll 1
  for (int L = 0; L < 4; L++) {
    float acc[64];
    float kv[128];
    gemm_issue<256, true>(kv, x); gemm_next<256>(x);
    {
      int i = 1;
      bool rel = true;
      float t[4] = {0.f, 0.f, 0.f, 0.f};
#pragma unroll 1
      for (int seg = 0; seg < 3; seg++) {
        const int end = seg < 2 ? (L == 0 ? 3 + 2 * (x.j & 3) + seg : 2 + seg * 2) : 16;
#pragma unroll 1
        while (true) {
          gemm_issue<256, false>(kv, x);
          if (++i == end) break;
          wgmma_wait<1>();
          if (rel) gemm_release<256>(x, true);
          rel = true;
          gemm_next<256>(x);
          if (i == 5) TSW(8 + L * 12);
          if (i == 11) TSW(10 + L * 12);
        }
        if (seg < 2 && L == 0) {
          float a[32];
          const uint32_t tile = x.aslot(x.ra.s);
          load_x32(a, tile, 0, x); load_x32(a + 16, tile, 4, x);
          stats_acc<32>(a, t);
          if (seg == 1) { mbar_wait(sb + BAR_EPOCH, 0); stats_send(t, 0, x); }
          fence_async_smem();
          wg_bar(w);
        }
        if (seg == 1 && L > 0) { rows_store(r1, P.xp[L] + goff + 8, x); publish(3, x); }
        wgmma_wait<1>();
        if (rel) gemm_release<256>(x, true);
        rel = true;
        gemm_next<256>(x);
        if (seg == 0 && L > 0) { wgmma_wait<0>(); gemm_release<256>(x, true); rel = false; }
      }
    }
    Stats st;
    uint32_t ma0, ma1;
    const uint32_t dcs = desc_lo(sb + OFF_CS, 0);
    {
      mbar_wait(sb + BAR_STAT, L & 1);
      const uint32_t a = sb + OFF_MR + w * 512 + (x.warp * 8 + x.g) * 16;
      const float2 u = lds64f(a), v = lds64f(a + 8);
      st.rstd0 = u.y; st.rstd1 = v.y;
      const uint32_t h = pack2(-u.x, -v.x), l = pack2(-u.x - lo16(h), -v.x - hi16(h));
      const int k = 2 * x.c - 3 * (L & 1);
      const uint32_t e0 = k == 2 ? l : ((unsigned)k < 2 ? h : 0u), e1 = k == 1 ? l : ((unsigned)(k + 1) < 2 ? h : 0u);
      ma0 = __byte_perm(e0, e1, 0x5410); ma1 = __byte_perm(e0, e1, 0x7632);
      mbar_wait(sb + BAR_CS + (L & 1) * 8, 0);
      wgmma_fence();
      wgmma_rs_n256(kv, ma0, ma1, 0u, 0u, dcs + 96, 1);
      wgmma_commit();
      wgmma_wait<0>();
      fence_regs(kv);
      if (L & 1) x.releaseA(x.pa);
      else gemm_release<256>(x, true);
    }
    auto q_start = [&]() {
      wgmma_fence();
      wgmma_rs_n128(acc, ma0, ma1, 0u, 0u, dcs, 0);
      gemm_issue<128, false>(acc, x); gemm_next<128>(x);
    };
    TSW(2 + L * 12);
    if ((L & 1) == 0) {
      uint32_t P0[32], P1[32], PH[32];
#pragma unroll
      for (int t = 0; t < 16; t++) { P0[t] = pack2(kv[4 * t] * st.rstd0, kv[4 * t + 1] * st.rstd0); P1[t] = pack2(kv[4 * t + 2] * st.rstd1, kv[4 * t + 3] * st.rstd1); }
      pin<16>(P0, x.mrow + 16);
      {
#pragma unroll
        for (int q = 0; q < 4; q++) sts128((x.warp < 3 ? sb + OFF_T + w * 12288 + x.warp * 4096 : sb + OFF_S + 16384 + w * 2048) + x.lane * 16 + q * 512, P1[4 * q], P1[4 * q + 1], P1[4 * q + 2], P1[4 * q + 3]);
      }
      q_start();
      TSW(3 + L * 12);
#pragma unroll
      for (int s = 0; s < 4; s++) {
#pragma unroll
        for (int t = 16 + 8 * (s & 1); t < 24 + 8 * (s & 1); t++) {
          if (s < 2) P1[t] = movm(pack2(kv[4 * t + 2] * st.rstd1, kv[4 * t + 3] * st.rstd1));
          else P0[t] = movm(pack2(kv[4 * t] * st.rstd0, kv[4 * t + 1] * st.rstd0));
        }
        if (s < 3) { gemm_issue<128, false>(acc, x); gemm_retire<128>(x, true); }
        if (s == 1) {
          if (x.warp < 3) {
#pragma unroll
            for (int q = 4; q < 8; q++) sts128(sb + OFF_T + w * 12288 + x.warp * 4096 + x.lane * 16 + q * 512, P1[4 * q], P1[4 * q + 1], P1[4 * q + 2], P1[4 * q + 3]);
          } else {
            uint4* dst = &g_halo[x.m][x.j][w][x.lane];
#pragma unroll
            for (int q = 0; q < 8; q++) dst[q * 32] = make_uint4(P1[4 * q], P1[4 * q + 1], P1[4 * q + 2], P1[4 * q + 3]);
            __syncwarp();
            if (x.lane == 0) mbar_arrive(sb + BAR_SIGT);
          }
          gemm_issue<128, false>(acc, x);
          gemm_retire<128>(x, true);
        }
      }
      TSW(4 + L * 12);
      gemm_run(acc, x, 10, 0);
      gemm_issue<128, false>(acc, x);
      {
        wg_bar(w);
        uint32_t tr = sb + OFF_T + w * 12288 + (x.warp - 1) * 4096;
        if (x.warp == 0) {
          tr = x.m > 0 ? sb + OFF_S + 8192 + w * 4096 : tr + 4096;
          if (x.m > 0) mbar_wait(sb + BAR_HALO, L >> 1);
        }
#pragma unroll
        for (int q = 0; q < 8; q++) lds128(tr + x.lane * 16 + q * 512, PH[4 * q], PH[4 * q + 1], PH[4 * q + 2], PH[4 * q + 3]);
      }
      gemm_retire<128>(x, false);
      gemm_end(acc, x);
      TSW(5 + L * 12);
      const bool first = (x.m == 0) && (x.warp == 0);
      const bool hi0 = 2 * x.c > x.g, hi1 = 2 * x.c + 1 > x.g;
      const uint32_t mhi = (hi0 ? 0xFFFFu : 0u) | (hi1 ? 0xFFFF0000u : 0u);
      const float sc0 = st.rstd0 * (0.17677669529663687f * LOG2E), sc1 = st.rstd1 * (0.17677669529663687f * LOG2E);
#pragma unroll
      for (int hp = 0; hp < 2; hp++) {
        const uint32_t tile = x.aslot(x.held(hp));
        uint32_t px[2], py[2];
        float s[2][3][4];
#pragma unroll
        for (int u = 0; u < 2; u++) {
#pragma unroll
          for (int q = 0; q < 12; q++) s[u][q >> 2][q & 3] = 0.f;
#pragma unroll
          for (int ks = 0; ks < 2; ks++) {
            const int t = 8 * hp + 4 * u + 2 * ks;
            const uint32_t a0 = pack2(acc[4 * t], acc[4 * t + 1]), a1 = pack2(acc[4 * t + 2], acc[4 * t + 3]);
            const uint32_t a2 = pack2(acc[4 * t + 4], acc[4 * t + 5]), a3 = pack2(acc[4 * t + 6], acc[4 * t + 7]);
            mma16816(s[u][0], a0, a1, a2, a3, PH[t], PH[t + 1]);
            mma16816(s[u][1], a0, a1, a2, a3, P0[t], P0[t + 1]);
            mma16816(s[u][2], a0, a1, a2, a3, P1[t], P1[t + 1]);
          }
        }
        load_x32(acc + 32 * hp, tile, 0, x);
        load_x32(acc + 32 * hp + 16, tile, 4, x);
        float e[2][4], r[2][2];
#pragma unroll
        for (int u = 0; u < 2; u++) {
          e[u][0] = (hi0 ? s[u][0][0] : s[u][1][0]) * sc0; e[u][1] = (hi1 ? s[u][0][1] : s[u][1][1]) * sc0;
          e[u][2] = (hi0 ? s[u][1][2] : s[u][2][2]) * sc1; e[u][3] = (hi1 ? s[u][1][3] : s[u][2][3]) * sc1;
          if (first) { if (hi0) e[u][0] = -1e30f; if (hi1) e[u][1] = -1e30f; }
          r[u][0] = fmaxf(e[u][0], e[u][1]); r[u][1] = fmaxf(e[u][2], e[u][3]);
        }
#pragma unroll
        for (int d = 1; d <= 2; d++)
#pragma unroll
          for (int q = 0; q < 4; q++) r[q >> 1][q & 1] = fmaxf(r[q >> 1][q & 1], __shfl_xor_sync(0xffffffffu, r[q >> 1][q & 1], d));
#pragma unroll
        for (int u = 0; u < 2; u++) {
#pragma unroll
          for (int q = 0; q < 4; q++) e[u][q] = ex2(e[u][q] - r[u][q >> 1]);
          r[u][0] = e[u][0] + e[u][1]; r[u][1] = e[u][2] + e[u][3];
        }
#pragma unroll
        for (int d = 1; d <= 2; d++)
#pragma unroll
          for (int q = 0; q < 4; q++) r[q >> 1][q & 1] += __shfl_xor_sync(0xffffffffu, r[q >> 1][q & 1], d);
#pragma unroll
        for (int u = 0; u < 2; u++) {
          const float rx = rcp(r[u][0]), ry = rcp(r[u][1]);
          px[u] = pack2(e[u][0] * rx, e[u][1] * rx); py[u] = pack2(e[u][2] * ry, e[u][3] * ry);
        }
        uint32_t o[8][2];
#pragma unroll
        for (int q = 0; q < 8; q++) {
          float d[4] = {0.f, 0.f, 0.f, 0.f};
          const int t = 16 + 8 * hp + q, u = q >> 2;
          mma16816(d, px[u] & mhi, 0u, px[u] & ~mhi, py[u] & mhi, PH[t], P0[t]);
          mma1688(d, 0u, py[u] & ~mhi, P1[t]);
          o[q][0] = pack2(d[0], d[1]); o[q][1] = pack2(d[2], d[3]);
        }
#pragma unroll
        for (int q = 0; q < 4; q++) stsm4(x.maddr(tile, 2 * q), o[2 * q][0], o[2 * q][1], o[2 * q + 1][0], o[2 * q + 1][1]);
        tile_out(tile, reinterpret_cast<uint4*>(g_o) + goff + 8 * hp, hp, x);
        if (hp == 0) sched_fence(sb);
      }
    } else {
      {
        float mm[16], d[20], p[64];
        const uint32_t b0 = x.pb;
        hedgehog_pre(kv, p, 0);
        const uint32_t tV = sb + OFF_S + w * 10240 + (2 * x.warp + ((x.lane >> 3) & 1)) * 1280 + (x.lane & 7) * 16;
        {
          const float i0 = rcp(st.rstd0), i1 = rcp(st.rstd1);
          const uint32_t h = pack2(i0, i1), u0 = pack2(lo16(h), i0 - lo16(h)), u1 = pack2(hi16(h), i1 - hi16(h));
          stsm4(tV + 512 + x.mhi * 640, u0, u1, u0, u1);
        }
        const unsigned tag = get_tag<false>(sb) * 4 + L;
        const uint32_t da = desc_lo(sb + OFF_B, 1024) + (b0 + w) * (SLOT / 16), db = desc_lo(sb + OFF_S, 1280) + w * 40;
        auto store_partial = [&](int hp) {
          fence_regs(d);
          uint4* dst = &g_kvpart[x.j][(2 * hp + w) * 4 + x.warp][0][x.m][x.lane];
          st_pkt(dst, pack2(d[0], d[1]), pack2(d[2], d[3]), pack2(d[4], d[5]), tag);
          st_pkt(dst + 512, pack2(d[6], d[7]), pack2(d[8], d[9]), pack2(d[10], d[11]), tag);
          st_pkt(dst + 1024, pack2(d[12], d[13]), pack2(d[14], d[15]), pack2(d[16] + d[17], d[18] + d[19]), tag);
          if (x.lane == 0) st_flag(&g_kvhint[x.j][(2 * hp + w) * 4 + x.warp][x.m], tag);
        };
        uint32_t f[2][16];
        float sm[4];
        bool ok;
        auto expo = [&](int h) { ok = hedgehog_exp(p + 16 * h, mm + 4 * h, st, f[h & 1]); };
        auto sums = [&](int h) {
          hedgehog_fix(ok, p + 16 * h, st, f[h & 1]);
          const uint32_t (&a)[16] = f[h & 1];
          wgmma_fence();
#pragma unroll
          for (int ks = 0; ks < 4; ks++) wgmma_rs_n8(sm, a[4 * ks], a[4 * ks + 1], a[4 * ks + 2], a[4 * ks + 3], desc_lo(sb + OFF_ONE, 0) + (ks >> 1), ks);
          wgmma_commit();
        };
        wgmma_wait<1>();
        fence_regs(reinterpret_cast<float (&)[32]>(p[0]));
        hedgehog_prep<2>(p, st, mm);
        expo(0);
        wgmma_wait<0>();
        fence_regs(reinterpret_cast<float (&)[32]>(p[32]));
        hedgehog_prep<2>(p + 32, st, mm + 8);
        sums(0);
        TSW(3 + L * 12);
#pragma unroll
        for (int h = 0; h < 4; h++) {
          if (h < 3) expo(h + 1);
          wgmma_wait<0>();
          fence_regs(sm);
          if (h == 2) { store_partial(0); cta_bar(); }
          uint32_t r[4];
#pragma unroll
          for (int q = 0; q < 4; q++) { const float v = rcp(sm[q]) * ((q & 2) ? st.rstd1 : st.rstd0); r[q] = pack2(v, v); }
#pragma unroll
          for (int q = 0; q < 2; q++) {
            const float* u = kv + 64 + 16 * h + 8 * q;
            stsm4(tV + (h & 1) * 640 + (2 * q + x.mhi) * 128, pack2(u[0], u[1]), pack2(u[2], u[3]), pack2(u[4], u[5]), pack2(u[6], u[7]));
          }
          const uint32_t tile = sb + OFF_B + (b0 + (h & 1)) * SLOT + w * 8192;
          if (h == 0) cta_bar();
#pragma unroll
          for (int q = 0; q < 4; q++) {
            const uint32_t* u = f[h & 1] + 4 * q;
            stsm4(x.maddr(tile, 2 * q), mul2(u[0], r[q >> 1]), mul2(u[1], r[2 + (q >> 1)]), mul2(u[2], r[q >> 1]), mul2(u[3], r[2 + (q >> 1)]));
          }
          if (h < 3) sums(h + 1);
          if (h & 1) {
            fence_async_smem();
            cta_bar();
            wgmma_fence();
#pragma unroll
            for (int ks = 0; ks < 8; ks++) wgmma_ss_n40_tt(d, da + 128 * ks, db + 160 * ks, ks);
            wgmma_commit();
          }
        }
        q_start();
        wgmma_wait<1>();
        x.releaseB(b0); x.releaseB(b0 + 1);
        store_partial(1);
      }
      TSW(4 + L * 12);
      gemm_run(acc, x, 15, 1);
      gemm_end(acc, x);
      TSW(5 + L * 12);
      {
        float mm[16], dp[2][20], dn[2][20], p[64];
        hedgehog_pre(acc, p, 1);
        wgmma_wait<1>();
        fence_regs(reinterpret_cast<float (&)[32]>(p[0]));
        hedgehog_prep<2>(p, st, mm);
        uint32_t f[4][16];
        bool ok[4];
        auto expo = [&](int h) { ok[h] = hedgehog_exp(p + 16 * h, mm + 4 * h, st, f[h]); };
        auto fix = [&](int h) { hedgehog_fix(ok[h], p + 16 * h, st, f[h]); };
        auto mma = [&](int h) {
          if (!(h & 1)) mbar_wait(sb + BAR_KV + h * 4, L >> 1);
          if (h == 0) TSW(9 + L * 12);
          const uint32_t db = desc_lo(sb + OFF_S + h * 5120, 128);
          const uint32_t (&a)[16] = f[h];
          wgmma_fence();
          wgmma_rs_n40(dp[h & 1], a[0], a[1], a[2], a[3], db, 0);
          wgmma_rs_n40(dn[h & 1], a[8], a[9], a[10], a[11], db + 160, 0);
          wgmma_rs_n40(dp[h & 1], a[4], a[5], a[6], a[7], db + 80, 1);
          wgmma_rs_n40(dn[h & 1], a[12], a[13], a[14], a[15], db + 240, 1);
          wgmma_commit();
        };
        auto fin = [&](int h) {
          const uint32_t tile = x.aslot(x.held(h >> 1));
          load_x32(acc + 16 * h, tile, (h & 1) * 4, x);
          wgmma_wait<0>();
          float (&u)[20] = dp[h & 1];
          float (&v)[20] = dn[h & 1];
          fence_regs(u); fence_regs(v);
          float c0 = u[17] * rcp(v[17]), c1 = u[19] * rcp(v[19]);
          const float a0_ = rcp(fmaf(v[16], c0, fmaf(u[17], 1e-6f, u[16]))), a1_ = rcp(fmaf(v[18], c1, fmaf(u[19], 1e-6f, u[18])));
          c0 *= a0_; c1 *= a1_;
          uint32_t o[8];
#pragma unroll
          for (int t = 0; t < 4; t++) {
            o[2 * t] = pack2(fmaf(u[4 * t], a0_, v[4 * t] * c0), fmaf(u[4 * t + 1], a0_, v[4 * t + 1] * c0));
            o[2 * t + 1] = pack2(fmaf(u[4 * t + 2], a1_, v[4 * t + 2] * c1), fmaf(u[4 * t + 3], a1_, v[4 * t + 3] * c1));
          }
          stsm4(x.maddr(tile, (h & 1) * 4), o[0], o[1], o[2], o[3]);
          stsm4(x.maddr(tile, (h & 1) * 4 + 2), o[4], o[5], o[6], o[7]);
          if (h & 1) tile_out(tile, reinterpret_cast<uint4*>(g_o) + goff + 8 * (h >> 1), h >> 1, x);
        };
        expo(0);
        wgmma_wait<0>();
        fence_regs(reinterpret_cast<float (&)[32]>(p[32]));
        hedgehog_prep<2>(p + 32, st, mm + 8);
        fix(0); mma(0);
        expo(1); fin(0); fix(1); mma(1);
        expo(2); fin(1); fix(2); mma(2);
        expo(3); fin(2); fix(3); mma(3);
        fin(3);
      }
    }
    fence_async_smem();
    wg_bar(w);
    TSW(6 + L * 12);
    rewind2<NA>(x.ra);
    gemm_issue<128, false>(acc, x); gemm_next<128>(x);
#pragma unroll 1
    for (int seg = L >= TSL ? 0 : 1; seg < 2; seg++) {
      gemm_run(acc, x, L >= TSL ? (seg ? TSK : 15 - TSK) : 15, seg);
      if (L >= TSL) {
        if (seg == 0 && w == 1) asm volatile("bar.sync 6, 256;" ::: "memory");
        if (seg == 1 && w == 0) asm volatile("bar.arrive 6, 256;" ::: "memory");
      }
    }
    gemm_end(acc, x);
    TSW(7 + L * 12);
    rewind2<NA>(x.ra);
    out_epilogue(acc, r1, P.xp[L + 1] + goff, L, x);
    TSW(13 + L * 12);
  }
  rows_store(r1, P.xp[4] + goff + 8, x);
}

__device__ __forceinline__ void b_producer(const Params& P, uint32_t sb) {
  const int j = cta_j();
  Ring r = {PRE_B % NB, PRE_B < NB};
  auto load = [&](const CUtensorMap* tm, int kb, int chunk) {
    mbar_wait(sb + BAR_EMPTYB + r.s * 8, r.ph);
    if (elect()) {
      mbar_expect_tx(sb + BAR_FULLB + r.s * 8, SLOT);
      tma_load_3d(sb + OFF_B + r.s * SLOT, tm, sb + BAR_FULLB + r.s * 8, 0, kb * 64, chunk);
    }
    adv<NB>(r);
  };
#pragma unroll 1
  for (int L = 0; L < 4; L++) {
    const int wt = L & 1;
#pragma unroll 1
    for (int i = L == 0 ? PRE_B : 0; i < 32; i++) {
      load(&P.mw[wt], kv_order(i >> 1, j, L), 16 + (i & 1) * 16 + 2 * j);
      if (L == 0 && i >= PF0 && i < PF0 + 5 * PFS && (i - PF0) % PFS == 0 && elect()) {
        const int p = (i - PF0) / PFS;
        tma_prefetch_3d(p == 0 ? &P.mwo[0] : (p == 4 ? &P.mwo[1] : &P.mw[1]), 0, cta_m() * 64, ((p - 1) & 3) % 3 * 16 + 2 * j);
      }
      if (L == 0 && i < 9) TS(6, 4 + i);
      if (L == 2 && (i & 1)) TS(7, 32 + (i >> 1));
    }
#pragma unroll 1
    for (int i = 0; i < 32; i++) {
      if (DEFER && i == 16 && ((DEFL >> wt) & 1)) {
        Ring q = r;
        for (int u = 0; u < DEFER; u++) adv<NB>(q);
        mbar_wait(sb + BAR_EMPTYB + q.s * 8, q.ph);
      }
      load(i < 16 ? &P.mw[wt] : &P.mwo[wt], i < 16 ? q_order(i, j) : o_order(i - 16, j), 2 * j);
    }
  }
}

__device__ __forceinline__ void a_loader(const Params& P, uint32_t sb) {
  const int j = cta_j(), m = cta_m();
  Ring r = {PRE_A % NA, PRE_A < NA};
  auto load = [&](const CUtensorMap* tm, int c0, int c1, int c2) {
    mbar_wait(sb + BAR_EMPTYA + r.s * 8, r.ph);
    if (elect()) {
      mbar_expect_tx(sb + BAR_FULLA + r.s * 8, SLOT);
      tma_load_3d(sb + OFF_A + r.s * SLOT, tm, sb + BAR_FULLA + r.s * 8, c0, c1, c2);
    }
    adv<NA>(r);
  };
#pragma unroll 1
  for (int i = PRE_A; i < 16; i++) { load(&P.mx[0], kv_order(i, j, 0) * 64, m * 64, 0); if (i < 8) TS(6, 21 + i); }
  const unsigned tag = get_tag(sb);
#pragma unroll 1
  for (int L = 0; L < 4; L++) {
#pragma unroll 1
    for (int i = 0; i < 16; i++) load(&P.mx[L], q_order(i, j) * 64, m * 64, 0);
    if (L & 1) {
#pragma unroll 1
      for (int p = 0; p < 2; p++) {
        poll_flags(&g_kvfflag[L >> 1][j][p][0], 8, 0xFFu, tag);
        if (elect()) { mbar_expect_tx(sb + BAR_KV + p * 8, 10240); bulk_load(sb + OFF_S + p * 10240, &g_kvfin[j][8 * p][0], 10240, sb + BAR_KV + p * 8); }
      }
      TS(4, 14 + L);
    }
#pragma unroll 1
    for (int p = 0; p < (L < 3 ? 2 : 1); p++) {
      const unsigned* flags = p == 0 ? &g_oflag[L][0][m][0] : &g_xflag[L + 1][0][m][0];
      const CUtensorMap* tm = p == 0 ? &P.mo : &P.mx[L + 1];
      unsigned seen = 0;
#pragma unroll 1
      for (int i = 2; i < 16; i++) {
        const int c0 = o_order(i, j) * 64;
        mbar_wait(sb + BAR_EMPTYA + r.s * 8, r.ph);
        if (elect()) mbar_expect_tx(sb + BAR_FULLA + r.s * 8, SLOT);
        if (i == 2) mbar_wait(sb + BAR_SIGP + p * 16, L & 1);
        if (i == 2 || i == 9 || (i == 6 && seen != 0xFFFFFFFFu)) {
          const int lane = threadIdx.x & 31, nn = p == 1 ? PNX : PNO;
          const unsigned* f = flags + (i == 9 ? 512 : 0) + (lane & 7);
          if (i == 2) f += (((lane >> 3) & (nn - 1)) - (m & (nn - 1))) * 32;
          const unsigned need = i == 2 ? 0x0F0F0F0Fu << (~j & 4) : 0xFFFFFFFFu;
          int it = 0;
          do { seen = __ballot_sync(0xffffffffu, ld_flag(f) == tag); if (++it > (1 << 22)) __trap(); } while ((seen & need) != need);
          fence_async_global();
        }
        if (elect()) tma_load_3d(sb + OFF_A + r.s * SLOT, tm, sb + BAR_FULLA + r.s * 8, c0, m * 64, 0);
        adv<NA>(r);
        if (i == 2) TS(2, p == 0 ? 5 + L * 8 : 9 + L * 8);
        if (L == 1 && p == 1) TS(7, 16 + i);
      }
    }
  }
}

__device__ __forceinline__ void helper_bar() { asm volatile("bar.sync 4, 64;" ::: "memory"); }
__device__ __forceinline__ void helper(const Params& P, uint32_t sb, int w) {
  const int j = cta_j(), m = cta_m();
  if (w == 0) {
    if (elect()) {
      const unsigned t = atomicAdd(&g_ctr, 1u) / NCTA + 1u;
      asm volatile("st.shared.u32 [%0], %1;" ::"r"(sb + OFF_EPOCH), "r"(t) : "memory");
      mbar_arrive(sb + BAR_EPOCH);
    }
  }
  const unsigned tag = get_tag(sb);
  mbar_wait(sb + BAR_FULLB + 24, 0);
  const uint32_t stg = sb + OFF_T + w * 12288, stb = sb + BAR_STG + w * 24;
  Ring rs = {0, 0};
#pragma unroll 1
  for (int L = 0; L < 4; L++) {
    const int lane = lane_id();
    if (L < 2) {
      if (m < 12) {
        const int part = ((m >> 2) + 1) % 3, col = part * 1024 + 128 * j + (m & 3) * 32;
        const CUtensorMap* tm = &P.mcs[L];
        const int nb = 8 + L * (w ? CSB : -CSB);
        float a[8] = {0.f, 0.f, 0.f, 0.f, 0.f, 0.f, 0.f, 0.f};
#pragma unroll 1
        for (int b = -3; b < nb; b++) {
          uint4 v[8];
          if (b >= 0) {
            mbar_wait(stb + rs.s * 8, rs.ph);
#pragma unroll
            for (int u = 0; u < 8; u++) lds128(stg + rs.s * 4096 + u * 512 + lane * 16, v[u].x, v[u].y, v[u].z, v[u].w);
            fence_async_smem();
            __syncwarp();
          }
          const uint32_t sl = b < 0 ? (rs.s + b + 3) % 3 : rs.s;
          if (b + 3 < nb && elect()) { mbar_expect_tx(stb + sl * 8, 4096); tma_load_2d(stg + sl * 4096, tm, stb + sl * 8, col, (w * (16 - nb) + b + 3) * 64); }
          if (b >= 0) {
            adv<3>(rs);
#pragma unroll
            for (int u = 0; u < 8; u++) {
              a[0] += lo16(v[u].x); a[1] += hi16(v[u].x); a[2] += lo16(v[u].y); a[3] += hi16(v[u].y);
              a[4] += lo16(v[u].z); a[5] += hi16(v[u].z); a[6] += lo16(v[u].w); a[7] += hi16(v[u].w);
            }
          }
        }
#pragma unroll
        for (int u = 0; u < 8; u++) {
          a[u] += __shfl_xor_sync(0xffffffffu, a[u], 4); a[u] += __shfl_xor_sync(0xffffffffu, a[u], 8); a[u] += __shfl_xor_sync(0xffffffffu, a[u], 16);
        }
        if (lane < 4) {
          float4* dst = reinterpret_cast<float4*>(&g_cs[L][w][col + lane * 8]);
          dst[0] = make_float4(a[0], a[1], a[2], a[3]); dst[1] = make_float4(a[4], a[5], a[6], a[7]);
        }
        helper_bar();
        if (w == 0 && elect()) { fence_gpu(); st_flag(&g_csflag[L][j][m], tag); }
      }
      if (w == 0) TS(4, 1 + L * 2);
    }
    auto load_wphi = [&]() { if (w == 0 && elect()) { mbar_expect_tx(sb + BAR_WPHI, 8192); tma_load_2d(sb + OFF_T, &P.mwphi, sb + BAR_WPHI, 0, 128 * j); } };
    if (L & 1) load_wphi();
    if (w == 1) {
      if (L > 0) mbar_wait(sb + BAR_SIGP + 24, (L - 1) & 1);
#pragma unroll 1
      for (int p = 0; p < 2; p++) {
        uint4 v[8];
        for (int it = 0;; it++) {
          bool ok = true;
#pragma unroll
          for (int t = 0; t < 8; t++) v[t] = ld_pkt(&g_stats[m][p][t][lane]);
#pragma unroll
          for (int t = 0; t < 8; t++) ok = ok && (v[t].w & 15u) == seq4(tag, L);
          if (__all_sync(0xffffffffu, ok)) break;
          __nanosleep(200);
          if (it > (1 << 20)) __trap();
        }
        float s0 = 0.f, q0 = 0.f, s1 = 0.f, q1 = 0.f;
#pragma unroll
        for (int t = 0; t < 8; t++) { s0 += __uint_as_float(v[t].x); q0 += __uint_as_float(v[t].y); s1 += __uint_as_float(v[t].z); q1 += __uint_as_float(v[t].w & ~15u); }
        s0 *= (1.f / 1024); s1 *= (1.f / 1024);
        sts128(sb + OFF_MR + p * 512 + lane * 16, __float_as_uint(s0), __float_as_uint(rsqrtf(fmaxf(q0 * (1.f / 1024) - s0 * s0, 0.f) + 1e-5f)),
               __float_as_uint(s1), __float_as_uint(rsqrtf(fmaxf(q1 * (1.f / 1024) - s1 * s1, 0.f) + 1e-5f)));
      }
      __syncwarp();
      if (elect()) {
        mbar_arrive(sb + BAR_STAT);
      }
      TS(2, 0 + L * 8);
    } else if (L < 2) {
      poll_flags(&g_csflag[L][j][0], 12, 0xFFFu, tag);
#pragma unroll
      for (int p = 0; p < 3; p++) {
        const uint4 u = ldcg4(&g_cs[L][0][p * 1024 + 128 * j + lane * 4]), v = ldcg4(&g_cs[L][1][p * 1024 + 128 * j + lane * 4]);
        const float c0 = __uint_as_float(u.x) + __uint_as_float(v.x), c1 = __uint_as_float(u.y) + __uint_as_float(v.y);
        const float c2 = __uint_as_float(u.z) + __uint_as_float(v.z), c3 = __uint_as_float(u.w) + __uint_as_float(v.w);
        const uint32_t h0 = pack2(c0, c1), h1 = pack2(c2, c3), dst = sb + OFF_CS + (p * 16 + (lane >> 1)) * 96 + L * 48 + (lane & 1) * 8;
        sts64(dst, h0, h1); sts64(dst + 16, pack2(c0 - lo16(h0), c1 - hi16(h0)), pack2(c2 - lo16(h1), c3 - hi16(h1))); sts64(dst + 32, h0, h1);
        if (L == 0) { sts64(dst + 48, 0u, 0u); sts64(dst + 64, 0u, 0u); sts64(dst + 80, 0u, 0u); }
      }
      if (L == 0 && lane < 22) { const uint32_t v = lane >= 4 && !(lane & 2) ? 0x3F803F80u : 0u; sts64(sb + OFF_CS + 4608 + lane * 8, v, v); }
      fence_async_smem();
      __syncwarp();
      if (elect()) mbar_arrive(sb + BAR_CS + L * 8);
      TS(4, 2 + L * 2);
    }
    if (L & 1) {
      const uint32_t buf = sb + OFF_T + w * 16384;
      poll_flags(&g_kvhint[j][m][0], 16, 0xFFFFu, tag * 4 + L);
      if (w == 0) TS(4, 6 + L * 2);
      for (int it = 0;; it++) {
        if (elect()) { mbar_expect_tx(stb + rs.s * 8, 16384 >> w); bulk_load(buf, &g_kvpart[j][m][2 * w][0][0], 16384 >> w, stb + rs.s * 8); }
        mbar_wait(stb + rs.s * 8, rs.ph);
        adv<3>(rs);
        bool ok = true;
#pragma unroll 1
        for (int pk = 0; pk < 2 - w; pk++) {
          float a[6] = {0.f, 0.f, 0.f, 0.f, 0.f, 0.f};
#pragma unroll 1
          for (int b = 0; b < 16; b += KB) {
            uint4 v[KB];
#pragma unroll
            for (int u = 0; u < KB; u++) lds128(buf + (pk * 16 + b + u) * 512 + lane * 16, v[u].x, v[u].y, v[u].z, v[u].w);
#pragma unroll
            for (int u = 0; u < KB; u++) {
              a[0] += lo16(v[u].x); a[1] += hi16(v[u].x); a[2] += lo16(v[u].y); a[3] += hi16(v[u].y); a[4] += lo16(v[u].z); a[5] += hi16(v[u].z);
              ok = ok && v[u].w == tag * 4 + L;
            }
          }
          uint32_t* img = &g_kvfin[j][m][(2 * w + pk) * 96 + lane];
          img[0] = pack2(a[0], a[1]); img[32] = pack2(a[2], a[3]); img[64] = pack2(a[4], w ? 1.f : a[5]);
          if (w) img[96] = pack2(a[5], 1.f);
        }
        fence_async_smem();
        if (__all_sync(0xffffffffu, ok)) break;
        if (it > (1 << 16)) __trap();
      }
      if (w == 0) TS(4, 7 + L * 2);
      helper_bar();
      load_wphi();
      if (w == 1 && elect()) { fence_gpu(); st_flag(&g_kvfflag[L >> 1][j][m >> 3][m & 7], tag); }
      if (w == 1 && L == 1) TS(4, 20);
    } else {
      mbar_wait(sb + BAR_SIGT, L >> 1);
      if (w == 0) {
        if (elect()) { fence_gpu(); st_flag(&g_hflag[L >> 1][m][j][0], tag); }
      } else if (m > 0) {
        poll_flags(&g_hflag[L >> 1][m - 1][j][0], 1, 1u, tag);
        if (elect()) { mbar_expect_tx(sb + BAR_HALO, 8192); bulk_load(sb + OFF_S + 8192, &g_halo[m - 1][j][0][0], 8192, sb + BAR_HALO); }
        TS(2, 2 + L * 8);
      }
    }
#pragma unroll 1
    for (int e = 0; e < (L < 3 && w == 0 ? 3 : 1); e++) {
      mbar_wait(sb + BAR_SIGP + (e == 0 ? w : e + 1) * 8, L & 1);
      TS(e == 2 ? 3 : 2 + w, (e ? 6 : 3) + L * 8);
      if (elect()) { fence_gpu(); st_flag(e == 0 ? &g_oflag[L][w][m][j] : &g_xflag[L + 1][e - 1][m][j], tag); }
      TS(e == 2 ? 3 : 2 + w, (e ? 7 : 4) + L * 8);
    }
  }
}

__global__ void __launch_bounds__(NTHREADS, 1) fused_kernel(const __grid_constant__ Params P) {
  extern __shared__ __align__(1024) uint8_t smem_raw[];
  constexpr uint32_t sb = SB;
  const int tid = threadIdx.x;
  const int warp = __shfl_sync(0xffffffffu, tid >> 5, 0);
  if (elect()) {
    if (warp == 11) { prefetch_map(&P.mx[0]); prefetch_map(&P.mw[0]); if (smem_u32(smem_raw) != SB) __trap(); }
    if (warp < 7) {
#pragma unroll
      for (int i = 0; i < 8; i++) mbar_init(sb + OFF_BAR + (warp * 8 + i) * 8, warp == 2 || warp == 3 ? 2 : (warp == 4 ? 8 : 1));
    }
    asm volatile("fence.mbarrier_init.release.cluster;" ::: "memory");
    if (warp < 2) {
      const int j = cta_j();
#pragma unroll 1
      for (int i = 0; i < (warp == 0 ? PRE_B : PRE_A); i++) {
        const uint32_t bar = sb + BAR_FULLB + warp * 64 + i * 8;
        mbar_expect_tx(bar, SLOT);
        if (warp == 0) tma_load_3d(sb + OFF_B + i * SLOT, &P.mw[0], bar, 0, kv_order(i >> 1, j, 0) * 64, 16 + (i & 1) * 16 + 2 * j);
        else tma_load_3d(sb + OFF_A + i * SLOT, &P.mx[0], bar, kv_order(i, j, 0) * 64, cta_m() * 64, 0);
      }
    }
  }
  if (tid == 0) TS(6, 0);
  __syncthreads();
  if (tid == 0) TS(6, 2);
  if (warp < 4) {
    reg_dealloc<PREGS>();
    if (warp == 0) b_producer(P, sb);
    else if (warp == 1) a_loader(P, sb);
    else helper(P, sb, warp - 2);
  } else {
    reg_alloc<CREGS>();
    consumer(P, sb, (warp >> 2) - 1);
  }
}

typedef CUresult (*EncodeFn)(CUtensorMap*, CUtensorMapDataType, cuuint32_t, void*, const cuuint64_t*, const cuuint64_t*,
                             const cuuint32_t*, const cuuint32_t*, CUtensorMapInterleave, CUtensorMapSwizzle,
                             CUtensorMapL2promotion, CUtensorMapFloatOOBfill);

void encode(EncodeFn fn, CUtensorMap* m, const void* ptr, int rank, const cuuint64_t* dims, const cuuint64_t* strides,
            const cuuint32_t* box, CUtensorMapSwizzle swz) {
  const cuuint32_t es[3] = {1, 1, 1};
  fn(m, CU_TENSOR_MAP_DATA_TYPE_BFLOAT16, rank, const_cast<void*>(ptr), dims, strides, box, es, CU_TENSOR_MAP_INTERLEAVE_NONE,
     swz, CU_TENSOR_MAP_L2_PROMOTION_L2_256B, CU_TENSOR_MAP_FLOAT_OOB_FILL_NONE);
}
void encode_w(EncodeFn fn, CUtensorMap* m, const void* ptr, int ncols) {
  const cuuint64_t d[3] = {64, 1024, (cuuint64_t)ncols / 64}, s[2] = {(cuuint64_t)ncols * 2, 128};
  const cuuint32_t box[3] = {64, 64, 2};
  encode(fn, m, ptr, 3, d, s, box, CU_TENSOR_MAP_SWIZZLE_128B);
}

void encode_cs(EncodeFn fn, CUtensorMap* m, const void* ptr, int ncols) {
  const cuuint64_t d[2] = {(cuuint64_t)ncols, 1024}, s[1] = {(cuuint64_t)ncols * 2};
  const cuuint32_t box[2] = {32, 64};
  encode(fn, m, ptr, 2, d, s, box, CU_TENSOR_MAP_SWIZZLE_NONE);
}

}

extern "C" void kernel_launch(void* const* d_in, const int* in_sizes, int n_in, void* d_out, int out_size) {
  (void)in_sizes; (void)n_in; (void)out_size;
  void* fnp = nullptr;
  cudaDriverEntryPointQueryResult q;
  cudaGetDriverEntryPoint("cuTensorMapEncodeTiled", &fnp, cudaEnableDefault, &q);
  EncodeFn fn = (EncodeFn)fnp;
  void* po = nullptr;
  cudaGetSymbolAddress(&po, g_o);
  Params P;
  {
    const cuuint64_t dims[3] = {1024, 1024, 2}, strides[2] = {4096, 2048};
    const cuuint32_t box[3] = {64, 64, 2};
    const void* xs[5] = {d_in[0], d_out, d_out, d_out, d_out};
    for (int i = 0; i < 5; i++) P.xp[i] = (uint4*)xs[i];
    for (int i = 0; i < 4; i++) encode(fn, &P.mx[i], xs[i], 3, dims, strides, box, CU_TENSOR_MAP_SWIZZLE_128B);
    encode(fn, &P.mo, po, 3, dims, strides, box, CU_TENSOR_MAP_SWIZZLE_128B);
  }
  encode_w(fn, &P.mw[0], d_in[1], 3072);
  encode_w(fn, &P.mw[1], d_in[4], 3072);
  encode_w(fn, &P.mwo[0], d_in[2], 1024);
  encode_w(fn, &P.mwo[1], d_in[6], 1024);
  encode_cs(fn, &P.mcs[0], d_in[1], 3072);
  encode_cs(fn, &P.mcs[1], d_in[4], 3072);
  {
    const cuuint64_t dims[2] = {32, 1024}, strides[1] = {64};
    const cuuint32_t box[2] = {32, 128};
    encode(fn, &P.mwphi, d_in[5], 2, dims, strides, box, CU_TENSOR_MAP_SWIZZLE_64B);
  }
  cudaFuncSetAttribute(fused_kernel, cudaFuncAttributeMaxDynamicSharedMemorySize, SMEM_BYTES);
  fused_kernel<<<NCTA, NTHREADS, SMEM_BYTES, cudaStreamPerThread>>>(P);
}
```

```cpp
#include <cuda_runtime.h>
#include <cuda_bf16.h>
#include <cuda.h>
#include <stdint.h>

namespace {

__device__ __forceinline__ void wgmma_ss_n256(float (&d)[128], uint32_t da, uint32_t db, int sd) {
  asm volatile("{\n.reg .pred p;\n.reg .b64 a, b;\nsetp.ne.b32 p, %130, 0;\nmov.b64 a, {%128, 0x40000040};\nmov.b64 b, {%129, 0x40000040};\n"
    "wgmma.mma_async.sync.aligned.m64n256k16.f32.bf16.bf16 {%0,%1,%2,%3,%4,%5,%6,%7,%8,%9,%10,%11,%12,%13,%14,%15,%16,%17,%18,%19,%20,%21,%22,%23,%24,%25,%26,%27,%28,%29,%30,%31,%32,%33,%34,%35,%36,%37,%38,%39,%40,%41,%42,%43,%44,%45,%46,%47,%48,%49,%50,%51,%52,%53,%54,%55,%56,%57,%58,%59,%60,%61,%62,%63,%64,%65,%66,%67,%68,%69,%70,%71,%72,%73,%74,%75,%76,%77,%78,%79,%80,%81,%82,%83,%84,%85,%86,%87,%88,%89,%90,%91,%92,%93,%94,%95,%96,%97,%98,%99,%100,%101,%102,%103,%104,%105,%106,%107,%108,%109,%110,%111,%112,%113,%114,%115,%116,%117,%118,%119,%120,%121,%122,%123,%124,%125,%126,%127}, a, b, p, 1, 1, 0, 1;\n}\n"
    : "+f"(d[0]),"+f"(d[1]),"+f"(d[2]),"+f"(d[3]),"+f"(d[4]),"+f"(d[5]),"+f"(d[6]),"+f"(d[7]),"+f"(d[8]),"+f"(d[9]),"+f"(d[10]),"+f"(d[11]),"+f"(d[12]),"+f"(d[13]),"+f"(d[14]),"+f"(d[15]),"+f"(d[16]),"+f"(d[17]),"+f"(d[18]),"+f"(d[19]),"+f"(d[20]),"+f"(d[21]),"+f"(d[22]),"+f"(d[23]),"+f"(d[24]),"+f"(d[25]),"+f"(d[26]),"+f"(d[27]),"+f"(d[28]),"+f"(d[29]),"+f"(d[30]),"+f"(d[31]),"+f"(d[32]),"+f"(d[33]),"+f"(d[34]),"+f"(d[35]),"+f"(d[36]),"+f"(d[37]),"+f"(d[38]),"+f"(d[39]),"+f"(d[40]),"+f"(d[41]),"+f"(d[42]),"+f"(d[43]),"+f"(d[44]),"+f"(d[45]),"+f"(d[46]),"+f"(d[47]),"+f"(d[48]),"+f"(d[49]),"+f"(d[50]),"+f"(d[51]),"+f"(d[52]),"+f"(d[53]),"+f"(d[54]),"+f"(d[55]),"+f"(d[56]),"+f"(d[57]),"+f"(d[58]),"+f"(d[59]),"+f"(d[60]),"+f"(d[61]),"+f"(d[62]),"+f"(d[63]),"+f"(d[64]),"+f"(d[65]),"+f"(d[66]),"+f"(d[67]),"+f"(d[68]),"+f"(d[69]),"+f"(d[70]),"+f"(d[71]),"+f"(d[72]),"+f"(d[73]),"+f"(d[74]),"+f"(d[75]),"+f"(d[76]),"+f"(d[77]),"+f"(d[78]),"+f"(d[79]),"+f"(d[80]),"+f"(d[81]),"+f"(d[82]),"+f"(d[83]),"+f"(d[84]),"+f"(d[85]),"+f"(d[86]),"+f"(d[87]),"+f"(d[88]),"+f"(d[89]),"+f"(d[90]),"+f"(d[91]),"+f"(d[92]),"+f"(d[93]),"+f"(d[94]),"+f"(d[95]),"+f"(d[96]),"+f"(d[97]),"+f"(d[98]),"+f"(d[99]),"+f"(d[100]),"+f"(d[101]),"+f"(d[102]),"+f"(d[103]),"+f"(d[104]),"+f"(d[105]),"+f"(d[106]),"+f"(d[107]),"+f"(d[108]),"+f"(d[109]),"+f"(d[110]),"+f"(d[111]),"+f"(d[112]),"+f"(d[113]),"+f"(d[114]),"+f"(d[115]),"+f"(d[116]),"+f"(d[117]),"+f"(d[118]),"+f"(d[119]),"+f"(d[120]),"+f"(d[121]),"+f"(d[122]),"+f"(d[123]),"+f"(d[124]),"+f"(d[125]),"+f"(d[126]),"+f"(d[127])
    : "r"(da), "r"(db), "r"(sd));
}
__device__ __forceinline__ void wgmma_ss_n128(float (&d)[64], uint32_t da, uint32_t db, int sd) {
  asm volatile("{\n.reg .pred p;\n.reg .b64 a, b;\nsetp.ne.b32 p, %66, 0;\nmov.b64 a, {%64, 0x40000040};\nmov.b64 b, {%65, 0x40000040};\n"
    "wgmma.mma_async.sync.aligned.m64n128k16.f32.bf16.bf16 {%0,%1,%2,%3,%4,%5,%6,%7,%8,%9,%10,%11,%12,%13,%14,%15,%16,%17,%18,%19,%20,%21,%22,%23,%24,%25,%26,%27,%28,%29,%30,%31,%32,%33,%34,%35,%36,%37,%38,%39,%40,%41,%42,%43,%44,%45,%46,%47,%48,%49,%50,%51,%52,%53,%54,%55,%56,%57,%58,%59,%60,%61,%62,%63}, a, b, p, 1, 1, 0, 1;\n}\n"
    : "+f"(d[0]),"+f"(d[1]),"+f"(d[2]),"+f"(d[3]),"+f"(d[4]),"+f"(d[5]),"+f"(d[6]),"+f"(d[7]),"+f"(d[8]),"+f"(d[9]),"+f"(d[10]),"+f"(d[11]),"+f"(d[12]),"+f"(d[13]),"+f"(d[14]),"+f"(d[15]),"+f"(d[16]),"+f"(d[17]),"+f"(d[18]),"+f"(d[19]),"+f"(d[20]),"+f"(d[21]),"+f"(d[22]),"+f"(d[23]),"+f"(d[24]),"+f"(d[25]),"+f"(d[26]),"+f"(d[27]),"+f"(d[28]),"+f"(d[29]),"+f"(d[30]),"+f"(d[31]),"+f"(d[32]),"+f"(d[33]),"+f"(d[34]),"+f"(d[35]),"+f"(d[36]),"+f"(d[37]),"+f"(d[38]),"+f"(d[39]),"+f"(d[40]),"+f"(d[41]),"+f"(d[42]),"+f"(d[43]),"+f"(d[44]),"+f"(d[45]),"+f"(d[46]),"+f"(d[47]),"+f"(d[48]),"+f"(d[49]),"+f"(d[50]),"+f"(d[51]),"+f"(d[52]),"+f"(d[53]),"+f"(d[54]),"+f"(d[55]),"+f"(d[56]),"+f"(d[57]),"+f"(d[58]),"+f"(d[59]),"+f"(d[60]),"+f"(d[61]),"+f"(d[62]),"+f"(d[63])
    : "r"(da), "r"(db), "r"(sd));
}
__device__ __forceinline__ void wgmma_ss_n40_tt(float (&d)[20], uint32_t da, uint32_t db, int sd) {
  asm volatile("{\n.reg .pred p;\n.reg .b64 a, b;\nsetp.ne.b32 p, %22, 0;\nmov.b64 a, {%20, 0x40000040};\nmov.b64 b, {%21, 0x8};\n"
    "wgmma.mma_async.sync.aligned.m64n40k16.f32.bf16.bf16 {%0,%1,%2,%3,%4,%5,%6,%7,%8,%9,%10,%11,%12,%13,%14,%15,%16,%17,%18,%19}, a, b, p, 1, 1, 1, 1;\n}\n"
    : "+f"(d[0]),"+f"(d[1]),"+f"(d[2]),"+f"(d[3]),"+f"(d[4]),"+f"(d[5]),"+f"(d[6]),"+f"(d[7]),"+f"(d[8]),"+f"(d[9]),"+f"(d[10]),"+f"(d[11]),"+f"(d[12]),"+f"(d[13]),"+f"(d[14]),"+f"(d[15]),"+f"(d[16]),"+f"(d[17]),"+f"(d[18]),"+f"(d[19])
    : "r"(da), "r"(db), "r"(sd));
}
__device__ __forceinline__ void wgmma_rs_n32(float (&d)[16], uint32_t a0, uint32_t a1, uint32_t a2, uint32_t a3, uint32_t db, int sd) {
  asm volatile("{\n.reg .pred p;\n.reg .b64 b;\nsetp.ne.b32 p, %21, 0;\nmov.b64 b, {%20, 0x80000020};\n"
    "wgmma.mma_async.sync.aligned.m64n32k16.f32.bf16.bf16 {%0,%1,%2,%3,%4,%5,%6,%7,%8,%9,%10,%11,%12,%13,%14,%15}, {%16,%17,%18,%19}, b, p, 1, 1, 1;\n}\n"
    : "+f"(d[0]),"+f"(d[1]),"+f"(d[2]),"+f"(d[3]),"+f"(d[4]),"+f"(d[5]),"+f"(d[6]),"+f"(d[7]),"+f"(d[8]),"+f"(d[9]),"+f"(d[10]),"+f"(d[11]),"+f"(d[12]),"+f"(d[13]),"+f"(d[14]),"+f"(d[15])
    : "r"(a0), "r"(a1), "r"(a2), "r"(a3), "r"(db), "r"(sd));
}
__device__ __forceinline__ void wgmma_rs_n40(float (&d)[20], uint32_t a0, uint32_t a1, uint32_t a2, uint32_t a3, uint32_t db, int sd) {
  asm volatile("{\n.reg .pred p;\n.reg .b64 b;\nsetp.ne.b32 p, %25, 0;\nmov.b64 b, {%24, 0x10};\n"
    "wgmma.mma_async.sync.aligned.m64n40k16.f32.bf16.bf16 {%0,%1,%2,%3,%4,%5,%6,%7,%8,%9,%10,%11,%12,%13,%14,%15,%16,%17,%18,%19}, {%20,%21,%22,%23}, b, p, 1, 1, 1;\n}\n"
    : "+f"(d[0]),"+f"(d[1]),"+f"(d[2]),"+f"(d[3]),"+f"(d[4]),"+f"(d[5]),"+f"(d[6]),"+f"(d[7]),"+f"(d[8]),"+f"(d[9]),"+f"(d[10]),"+f"(d[11]),"+f"(d[12]),"+f"(d[13]),"+f"(d[14]),"+f"(d[15]),"+f"(d[16]),"+f"(d[17]),"+f"(d[18]),"+f"(d[19])
    : "r"(a0), "r"(a1), "r"(a2), "r"(a3), "r"(db), "r"(sd));
}
__device__ __forceinline__ void wgmma_rs_n8(float (&d)[4], uint32_t a0, uint32_t a1, uint32_t a2, uint32_t a3, uint32_t db, int sd) {
  asm volatile("{\n.reg .pred p;\n.reg .b64 b;\nsetp.ne.b32 p, %9, 0;\nmov.b64 b, {%8, 0x8};\n"
    "wgmma.mma_async.sync.aligned.m64n8k16.f32.bf16.bf16 {%0,%1,%2,%3}, {%4,%5,%6,%7}, b, p, 1, 1, 0;\n}\n"
    : "+f"(d[0]),"+f"(d[1]),"+f"(d[2]),"+f"(d[3])
    : "r"(a0), "r"(a1), "r"(a2), "r"(a3), "r"(db), "r"(sd));
}
__device__ __forceinline__ void wgmma_rs_n256(float (&d)[128], uint32_t a0, uint32_t a1, uint32_t a2, uint32_t a3, uint32_t db, int sd) {
  asm volatile("{\n.reg .pred p;\n.reg .b64 b;\nsetp.ne.b32 p, %133, 0;\nmov.b64 b, {%132, 0x6};\n"
    "wgmma.mma_async.sync.aligned.m64n256k16.f32.bf16.bf16 {%0,%1,%2,%3,%4,%5,%6,%7,%8,%9,%10,%11,%12,%13,%14,%15,%16,%17,%18,%19,%20,%21,%22,%23,%24,%25,%26,%27,%28,%29,%30,%31,%32,%33,%34,%35,%36,%37,%38,%39,%40,%41,%42,%43,%44,%45,%46,%47,%48,%49,%50,%51,%52,%53,%54,%55,%56,%57,%58,%59,%60,%61,%62,%63,%64,%65,%66,%67,%68,%69,%70,%71,%72,%73,%74,%75,%76,%77,%78,%79,%80,%81,%82,%83,%84,%85,%86,%87,%88,%89,%90,%91,%92,%93,%94,%95,%96,%97,%98,%99,%100,%101,%102,%103,%104,%105,%106,%107,%108,%109,%110,%111,%112,%113,%114,%115,%116,%117,%118,%119,%120,%121,%122,%123,%124,%125,%126,%127}, {%128,%129,%130,%131}, b, p, 1, 1, 1;\n}\n"
    : "+f"(d[0]),"+f"(d[1]),"+f"(d[2]),"+f"(d[3]),"+f"(d[4]),"+f"(d[5]),"+f"(d[6]),"+f"(d[7]),"+f"(d[8]),"+f"(d[9]),"+f"(d[10]),"+f"(d[11]),"+f"(d[12]),"+f"(d[13]),"+f"(d[14]),"+f"(d[15]),"+f"(d[16]),"+f"(d[17]),"+f"(d[18]),"+f"(d[19]),"+f"(d[20]),"+f"(d[21]),"+f"(d[22]),"+f"(d[23]),"+f"(d[24]),"+f"(d[25]),"+f"(d[26]),"+f"(d[27]),"+f"(d[28]),"+f"(d[29]),"+f"(d[30]),"+f"(d[31]),"+f"(d[32]),"+f"(d[33]),"+f"(d[34]),"+f"(d[35]),"+f"(d[36]),"+f"(d[37]),"+f"(d[38]),"+f"(d[39]),"+f"(d[40]),"+f"(d[41]),"+f"(d[42]),"+f"(d[43]),"+f"(d[44]),"+f"(d[45]),"+f"(d[46]),"+f"(d[47]),"+f"(d[48]),"+f"(d[49]),"+f"(d[50]),"+f"(d[51]),"+f"(d[52]),"+f"(d[53]),"+f"(d[54]),"+f"(d[55]),"+f"(d[56]),"+f"(d[57]),"+f"(d[58]),"+f"(d[59]),"+f"(d[60]),"+f"(d[61]),"+f"(d[62]),"+f"(d[63]),"+f"(d[64]),"+f"(d[65]),"+f"(d[66]),"+f"(d[67]),"+f"(d[68]),"+f"(d[69]),"+f"(d[70]),"+f"(d[71]),"+f"(d[72]),"+f"(d[73]),"+f"(d[74]),"+f"(d[75]),"+f"(d[76]),"+f"(d[77]),"+f"(d[78]),"+f"(d[79]),"+f"(d[80]),"+f"(d[81]),"+f"(d[82]),"+f"(d[83]),"+f"(d[84]),"+f"(d[85]),"+f"(d[86]),"+f"(d[87]),"+f"(d[88]),"+f"(d[89]),"+f"(d[90]),"+f"(d[91]),"+f"(d[92]),"+f"(d[93]),"+f"(d[94]),"+f"(d[95]),"+f"(d[96]),"+f"(d[97]),"+f"(d[98]),"+f"(d[99]),"+f"(d[100]),"+f"(d[101]),"+f"(d[102]),"+f"(d[103]),"+f"(d[104]),"+f"(d[105]),"+f"(d[106]),"+f"(d[107]),"+f"(d[108]),"+f"(d[109]),"+f"(d[110]),"+f"(d[111]),"+f"(d[112]),"+f"(d[113]),"+f"(d[114]),"+f"(d[115]),"+f"(d[116]),"+f"(d[117]),"+f"(d[118]),"+f"(d[119]),"+f"(d[120]),"+f"(d[121]),"+f"(d[122]),"+f"(d[123]),"+f"(d[124]),"+f"(d[125]),"+f"(d[126]),"+f"(d[127])
    : "r"(a0), "r"(a1), "r"(a2), "r"(a3), "r"(db), "r"(sd));
}
__device__ __forceinline__ void wgmma_rs_n128(float (&d)[64], uint32_t a0, uint32_t a1, uint32_t a2, uint32_t a3, uint32_t db, int sd) {
  asm volatile("{\n.reg .pred p;\n.reg .b64 b;\nsetp.ne.b32 p, %69, 0;\nmov.b64 b, {%68, 0x6};\n"
    "wgmma.mma_async.sync.aligned.m64n128k16.f32.bf16.bf16 {%0,%1,%2,%3,%4,%5,%6,%7,%8,%9,%10,%11,%12,%13,%14,%15,%16,%17,%18,%19,%20,%21,%22,%23,%24,%25,%26,%27,%28,%29,%30,%31,%32,%33,%34,%35,%36,%37,%38,%39,%40,%41,%42,%43,%44,%45,%46,%47,%48,%49,%50,%51,%52,%53,%54,%55,%56,%57,%58,%59,%60,%61,%62,%63}, {%64,%65,%66,%67}, b, p, 1, 1, 1;\n}\n"
    : "+f"(d[0]),"+f"(d[1]),"+f"(d[2]),"+f"(d[3]),"+f"(d[4]),"+f"(d[5]),"+f"(d[6]),"+f"(d[7]),"+f"(d[8]),"+f"(d[9]),"+f"(d[10]),"+f"(d[11]),"+f"(d[12]),"+f"(d[13]),"+f"(d[14]),"+f"(d[15]),"+f"(d[16]),"+f"(d[17]),"+f"(d[18]),"+f"(d[19]),"+f"(d[20]),"+f"(d[21]),"+f"(d[22]),"+f"(d[23]),"+f"(d[24]),"+f"(d[25]),"+f"(d[26]),"+f"(d[27]),"+f"(d[28]),"+f"(d[29]),"+f"(d[30]),"+f"(d[31]),"+f"(d[32]),"+f"(d[33]),"+f"(d[34]),"+f"(d[35]),"+f"(d[36]),"+f"(d[37]),"+f"(d[38]),"+f"(d[39]),"+f"(d[40]),"+f"(d[41]),"+f"(d[42]),"+f"(d[43]),"+f"(d[44]),"+f"(d[45]),"+f"(d[46]),"+f"(d[47]),"+f"(d[48]),"+f"(d[49]),"+f"(d[50]),"+f"(d[51]),"+f"(d[52]),"+f"(d[53]),"+f"(d[54]),"+f"(d[55]),"+f"(d[56]),"+f"(d[57]),"+f"(d[58]),"+f"(d[59]),"+f"(d[60]),"+f"(d[61]),"+f"(d[62]),"+f"(d[63])
    : "r"(a0), "r"(a1), "r"(a2), "r"(a3), "r"(db), "r"(sd));
}

__device__ __forceinline__ uint32_t smem_u32(const void* p) { return (uint32_t)__cvta_generic_to_shared(p); }
__device__ __forceinline__ void mbar_init(uint32_t bar, uint32_t cnt) { asm volatile("mbarrier.init.shared::cta.b64 [%0], %1;" ::"r"(bar), "r"(cnt)); }
__device__ __forceinline__ void mbar_expect_tx(uint32_t bar, uint32_t bytes) { asm volatile("mbarrier.arrive.expect_tx.shared::cta.b64 _, [%0], %1;" ::"r"(bar), "r"(bytes) : "memory"); }
__device__ __forceinline__ void mbar_arrive(uint32_t bar) { asm volatile("mbarrier.arrive.shared::cta.b64 _, [%0];" ::"r"(bar) : "memory"); }
__device__ __forceinline__ void mbar_wait(uint32_t bar, uint32_t parity) {
  asm volatile("{\n.reg .pred p;\nLAB_WAIT:\nmbarrier.try_wait.parity.shared::cta.b64 p, [%0], %1;\n@p bra DONE;\nbra LAB_WAIT;\nDONE:\n}" ::"r"(bar), "r"(parity) : "memory");
}
__device__ __forceinline__ void mbar_wait2(uint32_t a, uint32_t pa, uint32_t b, uint32_t pb) {
  asm volatile("{\n.reg .pred p, q;\nLAB_WAIT:\nmbarrier.try_wait.parity.shared::cta.b64 p, [%0], %1;\nmbarrier.try_wait.parity.shared::cta.b64 q, [%2], %3;\n"
               "and.pred p, p, q;\n@p bra DONE;\nbra LAB_WAIT;\nDONE:\n}" ::"r"(a), "r"(pa), "r"(b), "r"(pb) : "memory");
}
__device__ __forceinline__ void mbar_wait3(uint32_t a, uint32_t pa, uint32_t b, uint32_t pb) {
  asm volatile("{\n.reg .pred p, q, r;\nLAB_WAIT:\nmbarrier.try_wait.parity.shared::cta.b64 p, [%0], %1;\nmbarrier.try_wait.parity.shared::cta.b64 q, [%2], %3;\n"
               "mbarrier.try_wait.parity.shared::cta.b64 r, [%2+8], %3;\nand.pred p, p, q;\nand.pred p, p, r;\n@p bra DONE;\nbra LAB_WAIT;\nDONE:\n}" ::"r"(a), "r"(pa), "r"(b), "r"(pb) : "memory");
}
__device__ __forceinline__ bool mbar_probe2(uint32_t a, uint32_t pa, uint32_t b, uint32_t pb) {
  uint32_t ok;
  asm volatile("{\n.reg .pred p, q;\nmbarrier.test_wait.parity.shared::cta.b64 p, [%1], %2;\nmbarrier.test_wait.parity.shared::cta.b64 q, [%3], %4;\n"
               "and.pred p, p, q;\nselp.u32 %0, 1, 0, p;\n}" : "=r"(ok) : "r"(a), "r"(pa), "r"(b), "r"(pb) : "memory");
  return ok != 0;
}
__device__ __forceinline__ void tma_load_3d(uint32_t dst, const CUtensorMap* tm, uint32_t bar, int c0, int c1, int c2) {
  asm volatile("cp.async.bulk.tensor.3d.shared::cluster.global.mbarrier::complete_tx::bytes [%0], [%1, {%3, %4, %5}], [%2];"
               ::"r"(dst), "l"(tm), "r"(bar), "r"(c0), "r"(c1), "r"(c2) : "memory");
}
__device__ __forceinline__ void tma_load_3d_mc(uint32_t dst, const CUtensorMap* tm, uint32_t bar, int c0, int c1, int c2) {
  asm volatile("cp.async.bulk.tensor.3d.shared::cluster.global.mbarrier::complete_tx::bytes.multicast::cluster [%0], [%1, {%3, %4, %5}], [%2], %6;"
               ::"r"(dst), "l"(tm), "r"(bar), "r"(c0), "r"(c1), "r"(c2), "h"((uint16_t)3) : "memory");
}
__device__ __forceinline__ uint32_t mapa(uint32_t a, uint32_t rank) { uint32_t r; asm("mapa.shared::cluster.u32 %0, %1, %2;" : "=r"(r) : "r"(a), "r"(rank)); return r; }
__device__ __forceinline__ void mbar_arrive_cluster(uint32_t bar) { asm volatile("mbarrier.arrive.relaxed.cluster.shared::cluster.b64 _, [%0];" ::"r"(bar) : "memory"); }
__device__ __forceinline__ void tma_load_2d(uint32_t dst, const CUtensorMap* tm, uint32_t bar, int c0, int c1) {
  asm volatile("cp.async.bulk.tensor.2d.shared::cluster.global.mbarrier::complete_tx::bytes [%0], [%1, {%3, %4}], [%2];"
               ::"r"(dst), "l"(tm), "r"(bar), "r"(c0), "r"(c1) : "memory");
}
__device__ __forceinline__ void tma_prefetch_3d(const CUtensorMap* tm, int c0, int c1, int c2) {
  asm volatile("cp.async.bulk.prefetch.tensor.3d.L2.global [%0, {%1, %2, %3}];" ::"l"(tm), "r"(c0), "r"(c1), "r"(c2) : "memory");
}
__device__ __forceinline__ void bulk_load(uint32_t dst, const void* g, uint32_t bytes, uint32_t bar) {
  asm volatile("cp.async.bulk.shared::cluster.global.mbarrier::complete_tx::bytes [%0], [%1], %2, [%3];" ::"r"(dst), "l"(g), "r"(bytes), "r"(bar) : "memory");
}
__device__ __forceinline__ void prefetch_map(const CUtensorMap* tm) { asm volatile("prefetch.tensormap [%0];" ::"l"(tm) : "memory"); }
__device__ __forceinline__ void fence_async_smem() { asm volatile("fence.proxy.async.shared::cta;" ::: "memory"); }
__device__ __forceinline__ void fence_async_global() { asm volatile("fence.proxy.async.global;" ::: "memory"); }
__device__ __forceinline__ void fence_gpu() { asm volatile("fence.release.gpu;" ::: "memory"); }
__device__ __forceinline__ void st_flag(unsigned* p, unsigned v) { asm volatile("st.relaxed.gpu.global.u32 [%0], %1;" ::"l"(p), "r"(v) : "memory"); }
__device__ __forceinline__ unsigned ld_flag(const unsigned* p) { unsigned v; asm volatile("ld.relaxed.gpu.global.u32 %0, [%1];" : "=r"(v) : "l"(p) : "memory"); return v; }
__device__ __forceinline__ uint4 ldcg4(const void* p) { uint4 v; asm volatile("ld.global.cg.v4.u32 {%0,%1,%2,%3}, [%4];" : "=r"(v.x), "=r"(v.y), "=r"(v.z), "=r"(v.w) : "l"(p)); return v; }
__device__ __forceinline__ uint4 ld_pkt(const uint4* p) {
  uint4 v; asm volatile("{\n.reg .b128 t;\nld.relaxed.gpu.global.b128 t, [%4];\nmov.b128 {%0,%1,%2,%3}, t;\n}" : "=r"(v.x), "=r"(v.y), "=r"(v.z), "=r"(v.w) : "l"(p) : "memory"); return v;
}
__device__ __forceinline__ void st_pkt(uint4* p, uint32_t a, uint32_t b, uint32_t c, uint32_t tag) {
  asm volatile("{\n.reg .b128 t;\nmov.b128 t, {%1,%2,%3,%4};\nst.relaxed.gpu.global.b128 [%0], t;\n}" ::"l"(p), "r"(a), "r"(b), "r"(c), "r"(tag) : "memory");
}
__device__ __forceinline__ void sts64(uint32_t addr, uint32_t a, uint32_t b) { asm volatile("st.shared.v2.u32 [%0], {%1,%2};" ::"r"(addr), "r"(a), "r"(b) : "memory"); }
__device__ __forceinline__ uint32_t mul2(uint32_t a, uint32_t b) { uint32_t r; asm("mul.rn.bf16x2 %0, %1, %2;" : "=r"(r) : "r"(a), "r"(b)); return r; }
__device__ __forceinline__ bool elect() {
  uint32_t p; asm volatile("{\n.reg .pred q;\nelect.sync _|q, 0xffffffff;\nselp.u32 %0, 1, 0, q;\n}" : "=r"(p)); return p != 0;
}
__device__ __forceinline__ void wgmma_fence() { asm volatile("wgmma.fence.sync.aligned;" ::: "memory"); }
__device__ __forceinline__ void wgmma_commit() { asm volatile("wgmma.commit_group.sync.aligned;" ::: "memory"); }
template <int N> __device__ __forceinline__ void wgmma_wait() { asm volatile("wgmma.wait_group.sync.aligned %0;" ::"n"(N) : "memory"); }
template <int N> __device__ __forceinline__ void fence_regs(float (&d)[N]) {
#pragma unroll
  for (int i = 0; i < N; i++) asm volatile("" : "+f"(d[i])::"memory");
}
template <int R> __device__ __forceinline__ void reg_alloc() { asm volatile("setmaxnreg.inc.sync.aligned.u32 %0;" ::"n"(R)); }
template <int R> __device__ __forceinline__ void reg_dealloc() { asm volatile("setmaxnreg.dec.sync.aligned.u32 %0;" ::"n"(R)); }
__device__ __forceinline__ void wg_bar(int w) { asm volatile("bar.sync %0, 128;" ::"r"(w + 1) : "memory"); }
__device__ __forceinline__ constexpr uint32_t desc_lo(uint32_t addr, uint32_t lbo) { return (addr >> 4) + ((lbo >> 4) << 16); }
__device__ __forceinline__ uint32_t pack2(float lo, float hi) { uint32_t r; asm("cvt.rn.bf16x2.f32 %0, %1, %2;" : "=r"(r) : "f"(hi), "f"(lo)); return r; }
__device__ __forceinline__ float lo16(uint32_t v) { return __uint_as_float(v << 16); }
__device__ __forceinline__ float hi16(uint32_t v) { return __uint_as_float(v & 0xFFFF0000u); }
__device__ __forceinline__ float ex2(float x) { float r; asm("ex2.approx.ftz.f32 %0, %1;" : "=f"(r) : "f"(x)); return r; }
__device__ __forceinline__ float rcp(float x) { float r; asm("rcp.approx.ftz.f32 %0, %1;" : "=f"(r) : "f"(x)); return r; }
__device__ __forceinline__ uint32_t movm(uint32_t a) { uint32_t d; asm volatile("movmatrix.sync.aligned.m8n8.trans.b16 %0, %1;" : "=r"(d) : "r"(a)); return d; }
__device__ __forceinline__ void stsm4(uint32_t addr, uint32_t a, uint32_t b, uint32_t c, uint32_t d) {
  asm volatile("stmatrix.sync.aligned.m8n8.x4.shared.b16 [%0], {%1,%2,%3,%4};" ::"r"(addr), "r"(a), "r"(b), "r"(c), "r"(d) : "memory");
}
__device__ __forceinline__ void ldsm4(uint32_t addr, uint32_t (&r)[4]) {
  asm volatile("ldmatrix.sync.aligned.m8n8.x4.shared.b16 {%0,%1,%2,%3}, [%4];" : "=r"(r[0]), "=r"(r[1]), "=r"(r[2]), "=r"(r[3]) : "r"(addr) : "memory");
}
__device__ __forceinline__ void sts128(uint32_t addr, uint32_t a, uint32_t b, uint32_t c, uint32_t d) {
  asm volatile("st.shared.v4.u32 [%0], {%1,%2,%3,%4};" ::"r"(addr), "r"(a), "r"(b), "r"(c), "r"(d) : "memory");
}
__device__ __forceinline__ void lds128(uint32_t addr, uint32_t& a, uint32_t& b, uint32_t& c, uint32_t& d) {
  asm volatile("ld.shared.v4.u32 {%0,%1,%2,%3}, [%4];" : "=r"(a), "=r"(b), "=r"(c), "=r"(d) : "r"(addr) : "memory");
}
__device__ __forceinline__ float2 lds64f(uint32_t addr) { float2 v; asm volatile("ld.shared.v2.f32 {%0,%1}, [%2];" : "=f"(v.x), "=f"(v.y) : "r"(addr) : "memory"); return v; }
__device__ __forceinline__ void mma16816(float (&d)[4], uint32_t a0, uint32_t a1, uint32_t a2, uint32_t a3, uint32_t b0, uint32_t b1) {
  asm("mma.sync.aligned.m16n8k16.row.col.f32.bf16.bf16.f32 {%0,%1,%2,%3}, {%4,%5,%6,%7}, {%8,%9}, {%0,%1,%2,%3};"
      : "+f"(d[0]), "+f"(d[1]), "+f"(d[2]), "+f"(d[3]) : "r"(a0), "r"(a1), "r"(a2), "r"(a3), "r"(b0), "r"(b1));
}
__device__ __forceinline__ void mma1688(float (&d)[4], uint32_t a0, uint32_t a1, uint32_t b0) {
  asm("mma.sync.aligned.m16n8k8.row.col.f32.bf16.bf16.f32 {%0,%1,%2,%3}, {%4,%5}, {%6}, {%0,%1,%2,%3};"
      : "+f"(d[0]), "+f"(d[1]), "+f"(d[2]), "+f"(d[3]) : "r"(a0), "r"(a1), "r"(b0));
}

__device__ __forceinline__ float qsum(float v) { v += __shfl_xor_sync(0xffffffffu, v, 1); v += __shfl_xor_sync(0xffffffffu, v, 2); return v; }

constexpr int NCTA = 132;
#define MC 0
#define NB_ 6
#define NA_ 5
constexpr int NB = NB_;
constexpr int NA = NA_;
constexpr uint32_t SLOT = 16384;
constexpr uint32_t SB = 1024;
constexpr uint32_t OFF_B = 0;
constexpr uint32_t OFF_A = NB * SLOT;
constexpr uint32_t OFF_S = OFF_A + NA * SLOT;
constexpr uint32_t OFF_T = OFF_S + 20480;
constexpr uint32_t OFF_CS = OFF_T + 24576;
constexpr uint32_t OFF_ONE = OFF_CS + 4640;
constexpr uint32_t OFF_MR = OFF_ONE + 144;
constexpr uint32_t OFF_BAR = OFF_MR + 1024;
constexpr uint32_t BAR_FULLB = OFF_BAR;
constexpr uint32_t BAR_FULLA = BAR_FULLB + 64;
constexpr uint32_t BAR_EMPTYB = BAR_FULLA + 64;
constexpr uint32_t BAR_EMPTYA = BAR_EMPTYB + 64;
constexpr uint32_t BAR_SIGP = BAR_EMPTYA + 64;
constexpr uint32_t BAR_SIGT = BAR_EMPTYA + 48;
constexpr uint32_t BAR_STAT = BAR_SIGP + 64;
constexpr uint32_t BAR_HALO = BAR_STAT + 16;
constexpr uint32_t BAR_CS = BAR_HALO + 8;
constexpr uint32_t BAR_WPHI = BAR_CS + 16;
constexpr uint32_t BAR_KV = BAR_WPHI + 8;
constexpr uint32_t BAR_STG = BAR_KV + 16;
constexpr uint32_t BAR_EPOCH = BAR_STG + 48;
constexpr uint32_t OFF_EPOCH = OFF_BAR + 7 * 64;
static_assert(BAR_EPOCH < OFF_EPOCH, "barriers");
constexpr uint32_t SMEM_BYTES = OFF_EPOCH + 8;
static_assert(SMEM_BYTES <= 232448 && NB % 2 == 0 && NB <= 8 && NA <= 6, "smem");

#define CREGS 208
#define PREGS 88
#define PF0 21
#define PFS 2
#define PRE_A 2
#define PRE_B 4
#define CSB 4
#define KB 8
#define PNX 2
#define PNO 2
#define RLIM 1.8446744e19f
#define DEFER 3
#define DEFL 2
#define TSK 3
#define TSL 3
constexpr int NTHREADS = 384;

struct Params {
  CUtensorMap mx[4];
  CUtensorMap mo;
  CUtensorMap mw[2];
  CUtensorMap mwo[2];
  CUtensorMap mwphi;
  CUtensorMap mcs[2];
  uint4* xp[5];
};

__device__ __align__(256) __nv_bfloat16 g_o[2048 * 1024];
__device__ __align__(256) uint4 g_stats[16][2][8][32];
__device__ __align__(256) uint4 g_halo[16][8][2][256];
__device__ __align__(256) float g_cs[2][2][3072];
__device__ __align__(256) uint4 g_kvpart[8][16][3][16][32];
__device__ __align__(256) uint32_t g_kvfin[8][16][320];
__device__ __align__(256) unsigned g_xflag[4][2][16][32];
__device__ __align__(256) unsigned g_oflag[4][2][16][32];
__device__ __align__(256) unsigned g_hflag[2][16][8][32];
__device__ __align__(256) unsigned g_kvfflag[2][8][2][32];
__device__ __align__(256) unsigned g_csflag[2][8][32];
__device__ __align__(256) unsigned g_kvhint[8][16][32];
__device__ unsigned g_ctr;
__device__ __forceinline__ unsigned vblock() {
  unsigned s, r;
  asm volatile("mov.u32 %0, %%smid;" : "=r"(s));
  if (MC) asm volatile("mov.u32 %0, %%cluster_ctarank;" : "=r"(r)); else r = s & 1;
  s >>= 1;
  const unsigned t = s - 32, q = (t * 37) >> 8;
  const unsigned hi = s < 60 ? 12 + (t - 7 * q) * 8 + q : (s < 62 ? s + 4 : s - 58);
  return __shfl_sync(0xffffffffu, 2 * (s < 32 ? (s & 7) * 8 + (s >> 3) : hi) + r, 0);
}
#define TS(who, id) do {} while (0)
#define TSW(id) do {} while (0)

__device__ __forceinline__ int cta_m(unsigned b) { return ((b >> 2) & 12) | (b & 3); }
__device__ __forceinline__ int cta_j(unsigned b) { return ((b >> 2) & 3) | ((b >> 4) & 4); }
struct Ring { uint32_t s, ph; };
template <int N> __device__ __forceinline__ void adv(Ring& r) { if (++r.s == N) { r.s = 0; r.ph ^= 1; } }
template <int N> __device__ __forceinline__ void rewind2(Ring& r) { if (r.s < 2) { r.s += N - 2; r.ph ^= 1; } else r.s -= 2; }
__device__ __forceinline__ int other_tile(int t, int j) { return (t == (j | 4) ? 7 : t) ^ (~j & 4); }
__device__ __forceinline__ int q_order(int i, int j) { return 2 * (i >= 14 ? j : other_tile(i >> 1, j)) + (i & 1); }
__device__ __forceinline__ int o_order(int i, int j) {
  if (i < 2) return 2 * j + i;
  const int odd = i >= 9;
  return 2 * other_tile(i - 2 - 7 * odd, j) + odd;
}
__device__ __forceinline__ int kv_order(int i, int j, int L) { return L > 0 ? o_order(i, j) : (i + 14 + 2 * (j & 4)) & 15; }

__device__ __forceinline__ unsigned poll_flags(const unsigned* f, int n, unsigned need, unsigned tag) {
  const int lane = threadIdx.x & 31;
  unsigned mask; int it = 0;
  do {
    unsigned v = lane < n ? ld_flag(f + lane) : 0u;
    mask = __ballot_sync(0xffffffffu, lane < n && v == tag);
    if (++it > (1 << 22)) __trap();
  } while ((mask & need) != need);
  fence_async_global();
  return mask;
}
template <bool WAIT = true>
__device__ __forceinline__ unsigned get_tag(uint32_t sb) {
  if (WAIT) mbar_wait(sb + BAR_EPOCH, 0);
  unsigned t; asm volatile("ld.shared.u32 %0, [%1];" : "=r"(t) : "r"(sb + OFF_EPOCH) : "memory");
  return t;
}

__device__ __forceinline__ int lane_id() { int l; asm volatile("mov.u32 %0, %%laneid;" : "=r"(l)); return l; }
__device__ __forceinline__ unsigned seq4(unsigned tag, int L) { return 8u | ((tag & 1u) << 2) | (unsigned)L; }
constexpr float LOG2E = 1.4426950408889634f;

__device__ __forceinline__ void sched_fence(uint32_t sb) { mbar_wait(sb + BAR_EPOCH, 0); }
struct Ctx {
  uint32_t sb;
  uint32_t ab, da0;
  int w, warp, lane, g, c;
  int goff;
  __device__ __forceinline__ int m() const { return goff >> 14; }
  __device__ __forceinline__ int j() const { return (goff >> 4) & 7; }
  bool elected, brel;
  uint32_t eb;
  Ring ra, rb;
  uint32_t pa, pb;
  uint32_t mrow, mxor, mhi;
  __device__ __forceinline__ uint32_t aslot(uint32_t s) const { return ab + s * SLOT; }
  __device__ __forceinline__ uint32_t fullA(uint32_t s) const { return sb + BAR_FULLA + s * 8; }
  __device__ __forceinline__ uint32_t fullB(uint32_t s) const { return sb + BAR_FULLB + s * 8; }
  __device__ __forceinline__ void releaseA(uint32_t s) const { if (elected) mbar_arrive(sb + BAR_EMPTYA + s * 8); }
  __device__ __forceinline__ void releaseB(uint32_t s) const { if (MC) { if (brel) mbar_arrive_cluster(eb + s * 8); } else if (elected) mbar_arrive(sb + BAR_EMPTYB + s * 8); }
  __device__ __forceinline__ uint32_t maddr(uint32_t tile, uint32_t ch) const { return tile + mrow + (((ch + mhi) ^ mxor) << 4); }
  __device__ __forceinline__ uint32_t held(int i) const { return ra.s + i < 2 ? ra.s + i + NA - 2 : ra.s + i - 2; }
};

template <int N, bool FIRST>
__device__ __forceinline__ void gemm_issue(float (&acc)[N / 2], Ctx& x, bool ready = false) {
  if (!ready) {
    if (N == 256) mbar_wait3(x.fullA(x.ra.s), x.ra.ph, x.fullB(x.rb.s), x.rb.ph);
    else mbar_wait2(x.fullA(x.ra.s), x.ra.ph, x.fullB(x.rb.s), x.rb.ph);
  }
  const uint32_t da = x.da0 + x.ra.s * (SLOT / 16), db = desc_lo(SB + OFF_B, 8192) + x.rb.s * (SLOT / 16);
  wgmma_fence();
#pragma unroll
  for (int k = 0; k < 4; k++) {
    if constexpr (N == 256) wgmma_ss_n256(acc, da + 2 * k, db + 128 * k, !(FIRST && k == 0));
    else wgmma_ss_n128(acc, da + 2 * k, db + 128 * k, !(FIRST && k == 0));
  }
  wgmma_commit();
}
template <int N>
__device__ __forceinline__ void gemm_next(Ctx& x) {
  x.pa = x.ra.s; x.pb = x.rb.s;
  if (N == 256) x.rb.s++;
  adv<NA>(x.ra); adv<NB>(x.rb);
}
template <int N>
__device__ __forceinline__ void gemm_release(Ctx& x, bool relA) {
  if (relA) x.releaseA(x.pa);
  x.releaseB(x.pb);
  if (N == 256) x.releaseB(x.pb + 1);
}
template <int N>
__device__ __forceinline__ void gemm_retire(Ctx& x, bool relA) { wgmma_wait<1>(); gemm_release<N>(x, relA); gemm_next<N>(x); }
__device__ __forceinline__ void gemm_run(float (&acc)[64], Ctx& x, int n, int hold) {
  bool ready = false;
#pragma unroll 1
  for (; n > 0; n--) {
    gemm_issue<128, false>(acc, x, ready);
    const uint32_t pa = x.pa, pb = x.pb;
    gemm_next<128>(x);
    ready = mbar_probe2(x.fullA(x.ra.s), x.ra.ph, x.fullB(x.rb.s), x.rb.ph);
    wgmma_wait<1>();
    if (n > hold) x.releaseA(pa);
    x.releaseB(pb);
  }
}
__device__ __forceinline__ void gemm_end(float (&acc)[64], Ctx& x) { wgmma_wait<0>(); fence_regs(acc); gemm_release<128>(x, false); }

__device__ __forceinline__ void load_x32(float* a, uint32_t tile, uint32_t ch, const Ctx& x) {
#pragma unroll
  for (int p = 0; p < 2; p++) {
    uint32_t v[4];
    ldsm4(x.maddr(tile, ch + 2 * p), v);
#pragma unroll
    for (int i = 0; i < 4; i++) { a[8 * p + 2 * i] = lo16(v[i]); a[8 * p + 2 * i + 1] = hi16(v[i]); }
  }
}

__device__ __forceinline__ void rows_load(uint4* r, uint32_t tile, const Ctx& x) {
#pragma unroll
  for (int q = 0; q < 4; q++) {
    const uint32_t row = x.warp * 16 + 4 * q + (x.lane >> 3);
    lds128(tile + row * 128 + (((x.lane & 7) ^ (row & 7)) << 4), r[q].x, r[q].y, r[q].z, r[q].w);
  }
}
__device__ __forceinline__ void rows_store(const uint4* r, uint4* g, const Ctx& x) {
  g += (x.warp * 16 + (x.lane >> 3)) * 256 + (x.lane & 7);
#pragma unroll
  for (int q = 0; q < 4; q++) g[q * 1024] = r[q];
}
__device__ __forceinline__ void publish(int id, const Ctx& x) { __syncwarp(); if (x.lane == 0) mbar_arrive(x.sb + BAR_SIGP + id * 8); }
__device__ __forceinline__ void tile_out(uint32_t tile, uint4* g, int id, const Ctx& x) {
  uint4 r[4];
  __syncwarp();
  rows_load(r, tile, x); rows_store(r, g, x); publish(id, x);
}

template <int N>
__device__ __forceinline__ void stats_acc(const float* a, float (&t)[4]) {
#pragma unroll
  for (int i = 0; i < N; i++) { t[i & 2] += a[i]; t[(i & 2) + 1] = fmaf(a[i], a[i], t[(i & 2) + 1]); }
}
__device__ __forceinline__ void stats_send(float (&t)[4], int L, const Ctx& x) {
  const unsigned seq = seq4(get_tag<false>(x.sb), L);
#pragma unroll
  for (int q = 0; q < 4; q++) t[q] = qsum(t[q]);
  if (x.c == 0) st_pkt(&g_stats[x.m()][x.w][x.j()][x.warp * 8 + x.g], __float_as_uint(t[0]), __float_as_uint(t[1]), __float_as_uint(t[2]), (__float_as_uint(t[3]) & ~15u) | seq);
}
__device__ __forceinline__ void out_epilogue(const float (&acc)[64], uint4 (&r1)[4], uint4* g, int L, Ctx& x) {
  const uint32_t t0 = x.aslot(x.ra.s), t1 = x.aslot(x.ra.s + 1 == NA ? 0 : x.ra.s + 1);
#pragma unroll
  for (int p = 0; p < 8; p++) {
    stsm4(x.maddr(p < 4 ? t0 : t1, (p & 3) * 2), pack2(acc[8 * p], acc[8 * p + 1]), pack2(acc[8 * p + 2], acc[8 * p + 3]),
          pack2(acc[8 * p + 4], acc[8 * p + 5]), pack2(acc[8 * p + 6], acc[8 * p + 7]));
    if (p == 3) { tile_out(t0, g, 2, x); sched_fence(x.sb); }
  }
  __syncwarp();
  rows_load(r1, t1, x);
  if (L < 3) {
    float t[4] = {0.f, 0.f, 0.f, 0.f}, u[4] = {0.f, 0.f, 0.f, 0.f};
    stats_acc<32>(acc, t); stats_acc<32>(acc + 32, u);
#pragma unroll
    for (int q = 0; q < 4; q++) t[q] += u[q];
    stats_send(t, L + 1, x);
    fence_async_smem();
    wg_bar(x.w);
  }
}

struct Stats { float rstd0, rstd1; };

__device__ __forceinline__ void hedgehog_pre(const float* a, float (&p)[64], uint32_t sb, uint32_t parity) {
  uint32_t f[32];
#pragma unroll
  for (int i = 0; i < 32; i++) f[i] = pack2(a[2 * i], a[2 * i + 1]);
  mbar_wait(sb + BAR_WPHI, parity);
  wgmma_fence();
#pragma unroll
  for (int q = 0; q < 8; q++) {
    wgmma_rs_n32(reinterpret_cast<float (&)[16]>(p[16 * (q >> 1)]), f[4 * q], f[4 * q + 1], f[4 * q + 2], f[4 * q + 3], desc_lo(SB + OFF_T, 512) + q * 64, q & 1);
    if ((q & 3) == 3) wgmma_commit();
  }
}
template <int NH>
__device__ __forceinline__ void hedgehog_prep(const float* a, const Stats& st, float* mm) {
#pragma unroll
  for (int t = 0; t < 4 * NH; t++) {
    const float* p = a + 4 * t;
    float* q = mm + (t & ~3);
    const float x0 = fmaxf(p[0], p[1]), x1 = fmaxf(p[2], p[3]);
    if ((t & 3) == 0) { q[0] = x0; q[1] = x1; }
    else { q[0] = fmaxf(q[0], x0); q[1] = fmaxf(q[1], x1); }
  }
#pragma unroll
  for (int d = 1; d <= 2; d++)
#pragma unroll
    for (int i = 0; i < 4 * NH; i++) if (!(i & 2)) mm[i] = fmaxf(mm[i], __shfl_xor_sync(0xffffffffu, mm[i], d));
#pragma unroll
  for (int i = 0; i < 4 * NH; i++) if (!(i & 2)) mm[i] = fmaf(mm[i], ((i & 1) ? st.rstd1 : st.rstd0) * -LOG2E, 30.f);
}
__device__ __forceinline__ bool hedgehog_exp(const float* p, const float* mm, const Stats& st, uint32_t (&f)[16]) {
  const float sc0 = st.rstd0 * LOG2E, sc1 = st.rstd1 * LOG2E;
  bool ok = true;
#pragma unroll
  for (int t = 0; t < 4; t++) {
    const float* q = p + 4 * t;
    const float a = ex2(fmaf(q[0], sc0, mm[0])), b = ex2(fmaf(q[1], sc0, mm[0])), c = ex2(fmaf(q[2], sc1, mm[1])), d = ex2(fmaf(q[3], sc1, mm[1]));
    const float u = a * b, v = c * d, r = rcp(u * v), ru = r * v, rv = r * u;
    f[2 * t] = pack2(a, b); f[2 * t + 1] = pack2(c, d);
    f[8 + 2 * t] = pack2(ru * b, ru * a); f[9 + 2 * t] = pack2(rv * d, rv * c);
    ok = ok && ru + rv <= RLIM;
  }
  return ok;
}
__device__ __forceinline__ void hedgehog_fix(bool ok, const float* p, const Stats& st, uint32_t (&f)[16]) {
  if (__builtin_expect(!__all_sync(0xffffffffu, ok), 0)) {
    float n0 = p[0], n1 = p[2];
#pragma unroll
    for (int i = 0; i < 16; i++) { if (i & 2) n1 = fminf(n1, p[i]); else n0 = fminf(n0, p[i]); }
#pragma unroll
    for (int d = 1; d <= 2; d++) { n0 = fminf(n0, __shfl_xor_sync(0xffffffffu, n0, d)); n1 = fminf(n1, __shfl_xor_sync(0xffffffffu, n1, d)); }
#pragma unroll
    for (int i = 0; i < 8; i++) {
      const float n = (i & 1) ? n1 : n0, sc = ((i & 1) ? st.rstd1 : st.rstd0) * LOG2E;
      f[8 + i] = pack2(ex2((n - p[2 * i]) * sc), ex2((n - p[2 * i + 1]) * sc));
    }
  }
}
__device__ __forceinline__ void cta_bar() { asm volatile("bar.sync 3, 256;" ::: "memory"); }

template <int N> __device__ __forceinline__ void pin(const uint32_t* v, uint32_t addr) {
#pragma unroll
  for (int i = 0; i < N; i += 4)
    asm volatile("{\n.reg .pred p;\nsetp.eq.u32 p, %0, 0;\n@p st.shared.v4.u32 [%0], {%1,%2,%3,%4};\n}" ::"r"(addr), "r"(v[i]), "r"(v[i + 1]), "r"(v[i + 2]), "r"(v[i + 3]) : "memory");
}

__device__ __forceinline__ void consumer(const Params& P, uint32_t sb, int w, unsigned vb) {
  Ctx x;
  x.w = w; x.sb = sb;
  x.ab = sb + OFF_A + w * 8192; x.da0 = desc_lo(SB + OFF_A, 16) + w * 512;
  x.lane = threadIdx.x & 31; x.warp = __shfl_sync(0xffffffffu, (threadIdx.x >> 5) & 3, 0); x.g = x.lane >> 2; x.c = x.lane & 3;
  x.goff = (cta_m(vb) * 128 + w) * 128 + cta_j(vb) * 16;
  asm volatile("" : "+r"(x.goff));
  x.elected = (threadIdx.x & 127) == 0;
  x.brel = (threadIdx.x & 95) == 0;
  x.eb = MC ? mapa(sb + BAR_EMPTYB, x.warp & 1) : 0;
  x.ra = {0, 0}; x.rb = {0, 0}; x.pa = x.pb = 0;
  {
    const uint32_t row = x.warp * 16 + (x.lane & 15);
    x.mrow = row * 128; x.mxor = row & 7; x.mhi = x.lane >> 4;
  }
  const int goff = x.goff;
  uint4 r1[4];
#pragma unroll
  for (int i = 0; i < 4; i++) r1[i] = make_uint4(0, 0, 0, 0);
  TSW(0);
#pragma unroll 1
  for (int L = 0; L < 4; L++) {
    float acc[64];
    float kv[128];
    gemm_issue<256, true>(kv, x); gemm_next<256>(x);
    {
      int i = 1;
      bool rel = true;
      float t[4] = {0.f, 0.f, 0.f, 0.f};
#pragma unroll 1
      for (int seg = 0; seg < 3; seg++) {
        const int end = seg < 2 ? (L == 0 ? 3 + 2 * (x.j() & 3) + seg : 2 + seg * 2) : 16;
#pragma unroll 1
        while (true) {
          gemm_issue<256, false>(kv, x);
          if (++i == end) break;
          wgmma_wait<1>();
          if (rel) gemm_release<256>(x, true);
          rel = true;
          gemm_next<256>(x);
          if (i == 5) TSW(8 + L * 12);
          if (i == 11) TSW(10 + L * 12);
        }
        if (seg < 2 && L == 0) {
          float a[32];
          const uint32_t tile = x.aslot(x.ra.s);
          load_x32(a, tile, 0, x); load_x32(a + 16, tile, 4, x);
          stats_acc<32>(a, t);
          if (seg == 1) { mbar_wait(sb + BAR_EPOCH, 0); stats_send(t, 0, x); }
          fence_async_smem();
          wg_bar(w);
        }
        if (seg == 1 && L > 0) { rows_store(r1, P.xp[L] + goff + 8, x); publish(3, x); }
        wgmma_wait<1>();
        if (rel) gemm_release<256>(x, true);
        rel = true;
        gemm_next<256>(x);
        if (seg == 0 && L > 0) { wgmma_wait<0>(); gemm_release<256>(x, true); rel = false; }
      }
    }
    Stats st;
    uint32_t ma0, ma1;
    const uint32_t dcs = desc_lo(SB + OFF_CS, 0);
    {
      mbar_wait(sb + BAR_STAT, L & 1);
      const uint32_t a = sb + OFF_MR + w * 512 + (x.warp * 8 + x.g) * 16;
      const float2 u = lds64f(a), v = lds64f(a + 8);
      st.rstd0 = u.y; st.rstd1 = v.y;
      const uint32_t h = pack2(-u.x, -v.x), l = pack2(-u.x - lo16(h), -v.x - hi16(h));
      const int k = 2 * x.c - 3 * (L & 1);
      const uint32_t e0 = k == 2 ? l : ((unsigned)k < 2 ? h : 0u), e1 = k == 1 ? l : ((unsigned)(k + 1) < 2 ? h : 0u);
      ma0 = __byte_perm(e0, e1, 0x5410); ma1 = __byte_perm(e0, e1, 0x7632);
      mbar_wait(sb + BAR_CS + (L & 1) * 8, 0);
      wgmma_fence();
      wgmma_rs_n256(kv, ma0, ma1, 0u, 0u, dcs + 96, 1);
      wgmma_commit();
      wgmma_wait<0>();
      fence_regs(kv);
      if (L & 1) x.releaseA(x.pa);
      else gemm_release<256>(x, true);
    }
    auto q_start = [&]() {
      wgmma_fence();
      wgmma_rs_n128(acc, ma0, ma1, 0u, 0u, dcs, 0);
      gemm_issue<128, false>(acc, x); gemm_next<128>(x);
    };
    TSW(2 + L * 12);
    if ((L & 1) == 0) {
      uint32_t P0[32], P1[32], PH[32];
#pragma unroll
      for (int t = 0; t < 16; t++) { P0[t] = pack2(kv[4 * t] * st.rstd0, kv[4 * t + 1] * st.rstd0); P1[t] = pack2(kv[4 * t + 2] * st.rstd1, kv[4 * t + 3] * st.rstd1); }
      pin<16>(P0, x.mrow + 16);
      {
#pragma unroll
        for (int q = 0; q < 4; q++) sts128((x.warp < 3 ? sb + OFF_T + w * 12288 + x.warp * 4096 : sb + OFF_S + 16384 + w * 2048) + x.lane * 16 + q * 512, P1[4 * q], P1[4 * q + 1], P1[4 * q + 2], P1[4 * q + 3]);
      }
      q_start();
      TSW(3 + L * 12);
#pragma unroll
      for (int s = 0; s < 4; s++) {
#pragma unroll
        for (int t = 16 + 8 * (s & 1); t < 24 + 8 * (s & 1); t++) {
          if (s < 2) P1[t] = movm(pack2(kv[4 * t + 2] * st.rstd1, kv[4 * t + 3] * st.rstd1));
          else P0[t] = movm(pack2(kv[4 * t] * st.rstd0, kv[4 * t + 1] * st.rstd0));
        }
        if (s < 3) { gemm_issue<128, false>(acc, x); gemm_retire<128>(x, true); }
        if (s == 1) {
          if (x.warp < 3) {
#pragma unroll
            for (int q = 4; q < 8; q++) sts128(sb + OFF_T + w * 12288 + x.warp * 4096 + x.lane * 16 + q * 512, P1[4 * q], P1[4 * q + 1], P1[4 * q + 2], P1[4 * q + 3]);
          } else {
            uint4* dst = &g_halo[x.m()][x.j()][w][x.lane];
#pragma unroll
            for (int q = 0; q < 8; q++) dst[q * 32] = make_uint4(P1[4 * q], P1[4 * q + 1], P1[4 * q + 2], P1[4 * q + 3]);
            __syncwarp();
            if (x.lane == 0) mbar_arrive(sb + BAR_SIGT);
          }
          gemm_issue<128, false>(acc, x);
          gemm_retire<128>(x, true);
        }
      }
      TSW(4 + L * 12);
      gemm_run(acc, x, 10, 0);
      gemm_issue<128, false>(acc, x);
      {
        wg_bar(w);
        uint32_t tr = sb + OFF_T + w * 12288 + (x.warp - 1) * 4096;
        if (x.warp == 0) {
          tr = x.m() > 0 ? sb + OFF_S + 8192 + w * 4096 : tr + 4096;
          if (x.m() > 0) mbar_wait(sb + BAR_HALO, L >> 1);
        }
#pragma unroll
        for (int q = 0; q < 8; q++) lds128(tr + x.lane * 16 + q * 512, PH[4 * q], PH[4 * q + 1], PH[4 * q + 2], PH[4 * q + 3]);
      }
      gemm_retire<128>(x, false);
      gemm_end(acc, x);
      TSW(5 + L * 12);
      const bool first = (x.m() == 0) && (x.warp == 0);
      const bool hi0 = 2 * x.c > x.g, hi1 = 2 * x.c + 1 > x.g;
      const uint32_t mhi = (hi0 ? 0xFFFFu : 0u) | (hi1 ? 0xFFFF0000u : 0u);
      const float sc0 = st.rstd0 * (0.17677669529663687f * LOG2E), sc1 = st.rstd1 * (0.17677669529663687f * LOG2E);
#pragma unroll
      for (int hp = 0; hp < 2; hp++) {
        const uint32_t tile = x.aslot(x.held(hp));
        uint32_t px[2], py[2];
        float s[2][3][4];
#pragma unroll
        for (int u = 0; u < 2; u++) {
#pragma unroll
          for (int q = 0; q < 12; q++) s[u][q >> 2][q & 3] = 0.f;
#pragma unroll
          for (int ks = 0; ks < 2; ks++) {
            const int t = 8 * hp + 4 * u + 2 * ks;
            const uint32_t a0 = pack2(acc[4 * t], acc[4 * t + 1]), a1 = pack2(acc[4 * t + 2], acc[4 * t + 3]);
            const uint32_t a2 = pack2(acc[4 * t + 4], acc[4 * t + 5]), a3 = pack2(acc[4 * t + 6], acc[4 * t + 7]);
            mma16816(s[u][0], a0, a1, a2, a3, PH[t], PH[t + 1]);
            mma16816(s[u][1], a0, a1, a2, a3, P0[t], P0[t + 1]);
            mma16816(s[u][2], a0, a1, a2, a3, P1[t], P1[t + 1]);
          }
        }
        load_x32(acc + 32 * hp, tile, 0, x);
        load_x32(acc + 32 * hp + 16, tile, 4, x);
        float e[2][4], r[2][2];
#pragma unroll
        for (int u = 0; u < 2; u++) {
          e[u][0] = (hi0 ? s[u][0][0] : s[u][1][0]) * sc0; e[u][1] = (hi1 ? s[u][0][1] : s[u][1][1]) * sc0;
          e[u][2] = (hi0 ? s[u][1][2] : s[u][2][2]) * sc1; e[u][3] = (hi1 ? s[u][1][3] : s[u][2][3]) * sc1;
          if (first) { if (hi0) e[u][0] = -1e30f; if (hi1) e[u][1] = -1e30f; }
          r[u][0] = fmaxf(e[u][0], e[u][1]); r[u][1] = fmaxf(e[u][2], e[u][3]);
        }
#pragma unroll
        for (int d = 1; d <= 2; d++)
#pragma unroll
          for (int q = 0; q < 4; q++) r[q >> 1][q & 1] = fmaxf(r[q >> 1][q & 1], __shfl_xor_sync(0xffffffffu, r[q >> 1][q & 1], d));
#pragma unroll
        for (int u = 0; u < 2; u++) {
#pragma unroll
          for (int q = 0; q < 4; q++) e[u][q] = ex2(e[u][q] - r[u][q >> 1]);
          r[u][0] = e[u][0] + e[u][1]; r[u][1] = e[u][2] + e[u][3];
        }
#pragma unroll
        for (int d = 1; d <= 2; d++)
#pragma unroll
          for (int q = 0; q < 4; q++) r[q >> 1][q & 1] += __shfl_xor_sync(0xffffffffu, r[q >> 1][q & 1], d);
#pragma unroll
        for (int u = 0; u < 2; u++) {
          const float rx = rcp(r[u][0]), ry = rcp(r[u][1]);
          px[u] = pack2(e[u][0] * rx, e[u][1] * rx); py[u] = pack2(e[u][2] * ry, e[u][3] * ry);
        }
        uint32_t o[8][2];
#pragma unroll
        for (int q = 0; q < 8; q++) {
          float d[4] = {0.f, 0.f, 0.f, 0.f};
          const int t = 16 + 8 * hp + q, u = q >> 2;
          mma16816(d, px[u] & mhi, 0u, px[u] & ~mhi, py[u] & mhi, PH[t], P0[t]);
          mma1688(d, 0u, py[u] & ~mhi, P1[t]);
          o[q][0] = pack2(d[0], d[1]); o[q][1] = pack2(d[2], d[3]);
        }
#pragma unroll
        for (int q = 0; q < 4; q++) stsm4(x.maddr(tile, 2 * q), o[2 * q][0], o[2 * q][1], o[2 * q + 1][0], o[2 * q + 1][1]);
        tile_out(tile, reinterpret_cast<uint4*>(g_o) + goff + 8 * hp, hp, x);
        if (hp == 0) sched_fence(sb);
      }
    } else {
      {
        float mm[16], d[20], p[64];
        const uint32_t b0 = x.pb;
        hedgehog_pre(kv, p, sb, 0);
        const uint32_t tV = sb + OFF_S + w * 10240 + (2 * x.warp + ((x.lane >> 3) & 1)) * 1280 + (x.lane & 7) * 16;
        {
          const float i0 = rcp(st.rstd0), i1 = rcp(st.rstd1);
          const uint32_t h = pack2(i0, i1), u0 = pack2(lo16(h), i0 - lo16(h)), u1 = pack2(hi16(h), i1 - hi16(h));
          stsm4(tV + 512 + x.mhi * 640, u0, u1, u0, u1);
        }
        const unsigned tag = get_tag<false>(sb) * 4 + L;
        const uint32_t da = desc_lo(SB + OFF_B, 1024) + (b0 + w) * (SLOT / 16), db = desc_lo(SB + OFF_S, 1280) + w * 40;
        auto store_partial = [&](int hp) {
          fence_regs(d);
          uint4* dst = &g_kvpart[x.j()][(2 * hp + w) * 4 + x.warp][0][x.m()][x.lane];
          st_pkt(dst, pack2(d[0], d[1]), pack2(d[2], d[3]), pack2(d[4], d[5]), tag);
          st_pkt(dst + 512, pack2(d[6], d[7]), pack2(d[8], d[9]), pack2(d[10], d[11]), tag);
          st_pkt(dst + 1024, pack2(d[12], d[13]), pack2(d[14], d[15]), pack2(d[16] + d[17], d[18] + d[19]), tag);
          if (x.lane == 0) st_flag(&g_kvhint[x.j()][(2 * hp + w) * 4 + x.warp][x.m()], tag);
        };
        uint32_t f[2][16];
        float sm[4];
        bool ok;
        auto expo = [&](int h) { ok = hedgehog_exp(p + 16 * h, mm + 4 * h, st, f[h & 1]); };
        auto sums = [&](int h) {
          hedgehog_fix(ok, p + 16 * h, st, f[h & 1]);
          const uint32_t (&a)[16] = f[h & 1];
          wgmma_fence();
#pragma unroll
          for (int ks = 0; ks < 4; ks++) wgmma_rs_n8(sm, a[4 * ks], a[4 * ks + 1], a[4 * ks + 2], a[4 * ks + 3], desc_lo(SB + OFF_ONE, 0) + (ks >> 1), ks);
          wgmma_commit();
        };
        wgmma_wait<1>();
        fence_regs(reinterpret_cast<float (&)[32]>(p[0]));
        hedgehog_prep<2>(p, st, mm);
        expo(0);
        wgmma_wait<0>();
        fence_regs(reinterpret_cast<float (&)[32]>(p[32]));
        hedgehog_prep<2>(p + 32, st, mm + 8);
        sums(0);
        TSW(3 + L * 12);
#pragma unroll
        for (int h = 0; h < 4; h++) {
          if (h < 3) expo(h + 1);
          wgmma_wait<0>();
          fence_regs(sm);
          if (h == 2) { store_partial(0); cta_bar(); }
          uint32_t r[4];
#pragma unroll
          for (int q = 0; q < 4; q++) { const float v = rcp(sm[q]) * ((q & 2) ? st.rstd1 : st.rstd0); r[q] = pack2(v, v); }
#pragma unroll
          for (int q = 0; q < 2; q++) {
            const float* u = kv + 64 + 16 * h + 8 * q;
            stsm4(tV + (h & 1) * 640 + (2 * q + x.mhi) * 128, pack2(u[0], u[1]), pack2(u[2], u[3]), pack2(u[4], u[5]), pack2(u[6], u[7]));
          }
          const uint32_t tile = sb + OFF_B + (b0 + (h & 1)) * SLOT + w * 8192;
          if (h == 0) cta_bar();
#pragma unroll
          for (int q = 0; q < 4; q++) {
            const uint32_t* u = f[h & 1] + 4 * q;
            stsm4(x.maddr(tile, 2 * q), mul2(u[0], r[q >> 1]), mul2(u[1], r[2 + (q >> 1)]), mul2(u[2], r[q >> 1]), mul2(u[3], r[2 + (q >> 1)]));
          }
          if (h < 3) sums(h + 1);
          if (h & 1) {
            fence_async_smem();
            cta_bar();
            wgmma_fence();
#pragma unroll
            for (int ks = 0; ks < 8; ks++) wgmma_ss_n40_tt(d, da + 128 * ks, db + 160 * ks, ks);
            wgmma_commit();
          }
        }
        q_start();
        wgmma_wait<1>();
        x.releaseB(b0); x.releaseB(b0 + 1);
        store_partial(1);
      }
      TSW(4 + L * 12);
      gemm_run(acc, x, 15, 1);
      gemm_end(acc, x);
      TSW(5 + L * 12);
      {
        float mm[16], dp[2][20], dn[2][20], p[64];
        hedgehog_pre(acc, p, sb, 1);
        wgmma_wait<1>();
        fence_regs(reinterpret_cast<float (&)[32]>(p[0]));
        hedgehog_prep<2>(p, st, mm);
        uint32_t f[4][16];
        bool ok[4];
        auto expo = [&](int h) { ok[h] = hedgehog_exp(p + 16 * h, mm + 4 * h, st, f[h]); };
        auto fix = [&](int h) { hedgehog_fix(ok[h], p + 16 * h, st, f[h]); };
        auto mma = [&](int h) {
          if (!(h & 1)) mbar_wait(sb + BAR_KV + h * 4, L >> 1);
          if (h == 0) TSW(9 + L * 12);
          const uint32_t db = desc_lo(SB + OFF_S + h * 5120, 128);
          const uint32_t (&a)[16] = f[h];
          wgmma_fence();
          wgmma_rs_n40(dp[h & 1], a[0], a[1], a[2], a[3], db, 0);
          wgmma_rs_n40(dn[h & 1], a[8], a[9], a[10], a[11], db + 160, 0);
          wgmma_rs_n40(dp[h & 1], a[4], a[5], a[6], a[7], db + 80, 1);
          wgmma_rs_n40(dn[h & 1], a[12], a[13], a[14], a[15], db + 240, 1);
          wgmma_commit();
        };
        auto fin = [&](int h) {
          const uint32_t tile = x.aslot(x.held(h >> 1));
          load_x32(acc + 16 * h, tile, (h & 1) * 4, x);
          wgmma_wait<0>();
          float (&u)[20] = dp[h & 1];
          float (&v)[20] = dn[h & 1];
          fence_regs(u); fence_regs(v);
          float c0 = u[17] * rcp(v[17]), c1 = u[19] * rcp(v[19]);
          const float a0_ = rcp(fmaf(v[16], c0, fmaf(u[17], 1e-6f, u[16]))), a1_ = rcp(fmaf(v[18], c1, fmaf(u[19], 1e-6f, u[18])));
          c0 *= a0_; c1 *= a1_;
          uint32_t o[8];
#pragma unroll
          for (int t = 0; t < 4; t++) {
            o[2 * t] = pack2(fmaf(u[4 * t], a0_, v[4 * t] * c0), fmaf(u[4 * t + 1], a0_, v[4 * t + 1] * c0));
            o[2 * t + 1] = pack2(fmaf(u[4 * t + 2], a1_, v[4 * t + 2] * c1), fmaf(u[4 * t + 3], a1_, v[4 * t + 3] * c1));
          }
          stsm4(x.maddr(tile, (h & 1) * 4), o[0], o[1], o[2], o[3]);
          stsm4(x.maddr(tile, (h & 1) * 4 + 2), o[4], o[5], o[6], o[7]);
          if (h & 1) tile_out(tile, reinterpret_cast<uint4*>(g_o) + goff + 8 * (h >> 1), h >> 1, x);
        };
        expo(0);
        wgmma_wait<0>();
        fence_regs(reinterpret_cast<float (&)[32]>(p[32]));
        hedgehog_prep<2>(p + 32, st, mm + 8);
        fix(0); mma(0);
        expo(1); fin(0); fix(1); mma(1);
        expo(2); fin(1); fix(2); mma(2);
        expo(3); fin(2); fix(3); mma(3);
        fin(3);
      }
    }
    fence_async_smem();
    wg_bar(w);
    TSW(6 + L * 12);
    rewind2<NA>(x.ra);
    gemm_issue<128, false>(acc, x); gemm_next<128>(x);
#pragma unroll 1
    for (int seg = L >= TSL ? 0 : 1; seg < 2; seg++) {
      gemm_run(acc, x, L >= TSL ? (seg ? TSK : 15 - TSK) : 15, seg);
      if (L >= TSL) {
        if (seg == 0 && w == 1) asm volatile("bar.sync 6, 256;" ::: "memory");
        if (seg == 1 && w == 0) asm volatile("bar.arrive 6, 256;" ::: "memory");
      }
    }
    gemm_end(acc, x);
    TSW(7 + L * 12);
    rewind2<NA>(x.ra);
    out_epilogue(acc, r1, P.xp[L + 1] + goff, L, x);
    TSW(13 + L * 12);
  }
  rows_store(r1, P.xp[4] + goff + 8, x);
}

__device__ __forceinline__ void b_producer(const Params& P, uint32_t sb, unsigned vb) {
  const int j = cta_j(vb);
  Ring r = {PRE_B % NB, PRE_B < NB};
  auto load = [&](const CUtensorMap* tm, int kb, int chunk) {
    mbar_wait(sb + BAR_EMPTYB + r.s * 8, r.ph);
    if (elect()) {
      mbar_expect_tx(sb + BAR_FULLB + r.s * 8, SLOT);
      if (MC) tma_load_3d_mc(sb + OFF_B + r.s * SLOT + (vb & 1) * 8192, tm, sb + BAR_FULLB + r.s * 8, 0, kb * 64, chunk + (vb & 1));
      else tma_load_3d(sb + OFF_B + r.s * SLOT, tm, sb + BAR_FULLB + r.s * 8, 0, kb * 64, chunk);
    }
    adv<NB>(r);
  };
#pragma unroll 1
  for (int L = 0; L < 4; L++) {
    const int wt = L & 1;
#pragma unroll 1
    for (int i = L == 0 ? PRE_B : 0; i < 32; i++) {
      load(&P.mw[wt], kv_order(i >> 1, j, L), 16 + (i & 1) * 16 + 2 * j);
      if (L == 0 && i >= PF0 && i < PF0 + 5 * PFS && (i - PF0) % PFS == 0 && elect()) {
        const int p = (i - PF0) / PFS;
        for (int q = 0; q <= MC; q++) tma_prefetch_3d(p == 0 ? &P.mwo[0] : (p == 4 ? &P.mwo[1] : &P.mw[1]), 0, cta_m(vb) * 64, ((p - 1) & 3) % 3 * 16 + 2 * j + q);
      }
      if (L == 0 && i < 9) TS(6, 4 + i);
      if (L == 2 && (i & 1)) TS(7, 32 + (i >> 1));
    }
#pragma unroll 1
    for (int i = 0; i < 32; i++) {
      if (DEFER && i == 16 && ((DEFL >> wt) & 1)) {
        Ring q = r;
        for (int u = 0; u < DEFER; u++) adv<NB>(q);
        mbar_wait(sb + BAR_EMPTYB + q.s * 8, q.ph);
      }
      load(i < 16 ? &P.mw[wt] : &P.mwo[wt], i < 16 ? q_order(i, j) : o_order(i - 16, j), 2 * j);
    }
  }
  if (MC) {
#pragma unroll 1
    for (int i = 0; i < NB; i++) { mbar_wait(sb + BAR_EMPTYB + r.s * 8, r.ph); adv<NB>(r); }
  }
}

__device__ __forceinline__ void a_loader(const Params& P, uint32_t sb, unsigned vb) {
  const int j = cta_j(vb), m = cta_m(vb);
  Ring r = {PRE_A % NA, PRE_A < NA};
  auto load = [&](const CUtensorMap* tm, int c0, int c1, int c2) {
    mbar_wait(sb + BAR_EMPTYA + r.s * 8, r.ph);
    if (elect()) {
      mbar_expect_tx(sb + BAR_FULLA + r.s * 8, SLOT);
      tma_load_3d(sb + OFF_A + r.s * SLOT, tm, sb + BAR_FULLA + r.s * 8, c0, c1, c2);
    }
    adv<NA>(r);
  };
#pragma unroll 1
  for (int i = PRE_A; i < 16; i++) { load(&P.mx[0], kv_order(i, j, 0) * 64, m * 64, 0); if (i < 8) TS(6, 21 + i); }
  const unsigned tag = get_tag(sb);
#pragma unroll 1
  for (int L = 0; L < 4; L++) {
#pragma unroll 1
    for (int i = 0; i < 16; i++) load(&P.mx[L], q_order(i, j) * 64, m * 64, 0);
    if (L & 1) {
#pragma unroll 1
      for (int p = 0; p < 2; p++) {
        poll_flags(&g_kvfflag[L >> 1][j][p][0], 8, 0xFFu, tag);
        if (elect()) { mbar_expect_tx(sb + BAR_KV + p * 8, 10240); bulk_load(sb + OFF_S + p * 10240, &g_kvfin[j][8 * p][0], 10240, sb + BAR_KV + p * 8); }
      }
      TS(4, 14 + L);
    }
#pragma unroll 1
    for (int p = 0; p < (L < 3 ? 2 : 1); p++) {
      const unsigned* flags = p == 0 ? &g_oflag[L][0][m][0] : &g_xflag[L + 1][0][m][0];
      const CUtensorMap* tm = p == 0 ? &P.mo : &P.mx[L + 1];
      unsigned seen = 0;
#pragma unroll 1
      for (int i = 2; i < 16; i++) {
        const int c0 = o_order(i, j) * 64;
        mbar_wait(sb + BAR_EMPTYA + r.s * 8, r.ph);
        if (elect()) mbar_expect_tx(sb + BAR_FULLA + r.s * 8, SLOT);
        if (i == 2) mbar_wait(sb + BAR_SIGP + p * 16, L & 1);
        if (i == 2 || i == 9 || (i == 6 && seen != 0xFFFFFFFFu)) {
          const int lane = threadIdx.x & 31, nn = p == 1 ? PNX : PNO;
          const unsigned* f = flags + (i == 9 ? 512 : 0) + (lane & 7);
          if (i == 2) f += (((lane >> 3) & (nn - 1)) - (m & (nn - 1))) * 32;
          const unsigned need = i == 2 ? 0x0F0F0F0Fu << (~j & 4) : 0xFFFFFFFFu;
          int it = 0;
          do { seen = __ballot_sync(0xffffffffu, ld_flag(f) == tag); if (++it > (1 << 22)) __trap(); } while ((seen & need) != need);
          fence_async_global();
        }
        if (elect()) tma_load_3d(sb + OFF_A + r.s * SLOT, tm, sb + BAR_FULLA + r.s * 8, c0, m * 64, 0);
        adv<NA>(r);
        if (i == 2) TS(2, p == 0 ? 5 + L * 8 : 9 + L * 8);
        if (L == 1 && p == 1) TS(7, 16 + i);
      }
    }
  }
}

__device__ __forceinline__ void helper_bar() { asm volatile("bar.sync 4, 64;" ::: "memory"); }
__device__ __forceinline__ void helper(const Params& P, uint32_t sb, int w, unsigned vb) {
  const int j = cta_j(vb), m = cta_m(vb);
  if (w == 0) {
    if (elect()) {
      const unsigned t = atomicAdd(&g_ctr, 1u) / NCTA + 1u;
      asm volatile("st.shared.u32 [%0], %1;" ::"r"(sb + OFF_EPOCH), "r"(t) : "memory");
      mbar_arrive(sb + BAR_EPOCH);
    }
  }
  const unsigned tag = get_tag(sb);
  mbar_wait(sb + BAR_FULLB + 24, 0);
  const uint32_t stg = sb + OFF_T + w * 12288, stb = sb + BAR_STG + w * 24;
  Ring rs = {0, 0};
#pragma unroll 1
  for (int L = 0; L < 4; L++) {
    const int lane = lane_id();
    if (L < 2) {
      if (m < 12) {
        const int part = ((m >> 2) + 1) % 3, col = part * 1024 + 128 * j + (m & 3) * 32;
        const CUtensorMap* tm = &P.mcs[L];
        const int nb = 8 + L * (w ? CSB : -CSB);
        float a[8] = {0.f, 0.f, 0.f, 0.f, 0.f, 0.f, 0.f, 0.f};
#pragma unroll 1
        for (int b = -3; b < nb; b++) {
          uint4 v[8];
          if (b >= 0) {
            mbar_wait(stb + rs.s * 8, rs.ph);
#pragma unroll
            for (int u = 0; u < 8; u++) lds128(stg + rs.s * 4096 + u * 512 + lane * 16, v[u].x, v[u].y, v[u].z, v[u].w);
            fence_async_smem();
            __syncwarp();
          }
          const uint32_t sl = b < 0 ? (rs.s + b + 3) % 3 : rs.s;
          if (b + 3 < nb && elect()) { mbar_expect_tx(stb + sl * 8, 4096); tma_load_2d(stg + sl * 4096, tm, stb + sl * 8, col, (w * (16 - nb) + b + 3) * 64); }
          if (b >= 0) {
            adv<3>(rs);
#pragma unroll
            for (int u = 0; u < 8; u++) {
              a[0] += lo16(v[u].x); a[1] += hi16(v[u].x); a[2] += lo16(v[u].y); a[3] += hi16(v[u].y);
              a[4] += lo16(v[u].z); a[5] += hi16(v[u].z); a[6] += lo16(v[u].w); a[7] += hi16(v[u].w);
            }
          }
        }
#pragma unroll
        for (int u = 0; u < 8; u++) {
          a[u] += __shfl_xor_sync(0xffffffffu, a[u], 4); a[u] += __shfl_xor_sync(0xffffffffu, a[u], 8); a[u] += __shfl_xor_sync(0xffffffffu, a[u], 16);
        }
        if (lane < 4) {
          float4* dst = reinterpret_cast<float4*>(&g_cs[L][w][col + lane * 8]);
          dst[0] = make_float4(a[0], a[1], a[2], a[3]); dst[1] = make_float4(a[4], a[5], a[6], a[7]);
        }
        helper_bar();
        if (w == 0 && elect()) { fence_gpu(); st_flag(&g_csflag[L][j][m], tag); }
      }
      if (w == 0) TS(4, 1 + L * 2);
    }
    auto load_wphi = [&]() { if (w == 0 && elect()) { mbar_expect_tx(sb + BAR_WPHI, 8192); tma_load_2d(sb + OFF_T, &P.mwphi, sb + BAR_WPHI, 0, 128 * j); } };
    if (L & 1) load_wphi();
    if (w == 1) {
      if (L > 0) mbar_wait(sb + BAR_SIGP + 24, (L - 1) & 1);
#pragma unroll 1
      for (int p = 0; p < 2; p++) {
        uint4 v[8];
        for (int it = 0;; it++) {
          bool ok = true;
#pragma unroll
          for (int t = 0; t < 8; t++) v[t] = ld_pkt(&g_stats[m][p][t][lane]);
#pragma unroll
          for (int t = 0; t < 8; t++) ok = ok && (v[t].w & 15u) == seq4(tag, L);
          if (__all_sync(0xffffffffu, ok)) break;
          __nanosleep(200);
          if (it > (1 << 20)) __trap();
        }
        float s0 = 0.f, q0 = 0.f, s1 = 0.f, q1 = 0.f;
#pragma unroll
        for (int t = 0; t < 8; t++) { s0 += __uint_as_float(v[t].x); q0 += __uint_as_float(v[t].y); s1 += __uint_as_float(v[t].z); q1 += __uint_as_float(v[t].w & ~15u); }
        s0 *= (1.f / 1024); s1 *= (1.f / 1024);
        sts128(sb + OFF_MR + p * 512 + lane * 16, __float_as_uint(s0), __float_as_uint(rsqrtf(fmaxf(q0 * (1.f / 1024) - s0 * s0, 0.f) + 1e-5f)),
               __float_as_uint(s1), __float_as_uint(rsqrtf(fmaxf(q1 * (1.f / 1024) - s1 * s1, 0.f) + 1e-5f)));
      }
      __syncwarp();
      if (elect()) {
        mbar_arrive(sb + BAR_STAT);
      }
      TS(2, 0 + L * 8);
    } else if (L < 2) {
      poll_flags(&g_csflag[L][j][0], 12, 0xFFFu, tag);
#pragma unroll
      for (int p = 0; p < 3; p++) {
        const uint4 u = ldcg4(&g_cs[L][0][p * 1024 + 128 * j + lane * 4]), v = ldcg4(&g_cs[L][1][p * 1024 + 128 * j + lane * 4]);
        const float c0 = __uint_as_float(u.x) + __uint_as_float(v.x), c1 = __uint_as_float(u.y) + __uint_as_float(v.y);
        const float c2 = __uint_as_float(u.z) + __uint_as_float(v.z), c3 = __uint_as_float(u.w) + __uint_as_float(v.w);
        const uint32_t h0 = pack2(c0, c1), h1 = pack2(c2, c3), dst = sb + OFF_CS + (p * 16 + (lane >> 1)) * 96 + L * 48 + (lane & 1) * 8;
        sts64(dst, h0, h1); sts64(dst + 16, pack2(c0 - lo16(h0), c1 - hi16(h0)), pack2(c2 - lo16(h1), c3 - hi16(h1))); sts64(dst + 32, h0, h1);
        if (L == 0) { sts64(dst + 48, 0u, 0u); sts64(dst + 64, 0u, 0u); sts64(dst + 80, 0u, 0u); }
      }
      if (L == 0 && lane < 22) { const uint32_t v = lane >= 4 && !(lane & 2) ? 0x3F803F80u : 0u; sts64(sb + OFF_CS + 4608 + lane * 8, v, v); }
      fence_async_smem();
      __syncwarp();
      if (elect()) mbar_arrive(sb + BAR_CS + L * 8);
      TS(4, 2 + L * 2);
    }
    if (L & 1) {
      const uint32_t buf = sb + OFF_T + w * 16384;
      poll_flags(&g_kvhint[j][m][0], 16, 0xFFFFu, tag * 4 + L);
      if (w == 0) TS(4, 6 + L * 2);
      for (int it = 0;; it++) {
        if (elect()) { mbar_expect_tx(stb + rs.s * 8, 16384 >> w); bulk_load(buf, &g_kvpart[j][m][2 * w][0][0], 16384 >> w, stb + rs.s * 8); }
        mbar_wait(stb + rs.s * 8, rs.ph);
        adv<3>(rs);
        bool ok = true;
#pragma unroll 1
        for (int pk = 0; pk < 2 - w; pk++) {
          float a[6] = {0.f, 0.f, 0.f, 0.f, 0.f, 0.f};
#pragma unroll 1
          for (int b = 0; b < 16; b += KB) {
            uint4 v[KB];
#pragma unroll
            for (int u = 0; u < KB; u++) lds128(buf + (pk * 16 + b + u) * 512 + lane * 16, v[u].x, v[u].y, v[u].z, v[u].w);
#pragma unroll
            for (int u = 0; u < KB; u++) {
              a[0] += lo16(v[u].x); a[1] += hi16(v[u].x); a[2] += lo16(v[u].y); a[3] += hi16(v[u].y); a[4] += lo16(v[u].z); a[5] += hi16(v[u].z);
              ok = ok && v[u].w == tag * 4 + L;
            }
          }
          uint32_t* img = &g_kvfin[j][m][(2 * w + pk) * 96 + lane];
          img[0] = pack2(a[0], a[1]); img[32] = pack2(a[2], a[3]); img[64] = pack2(a[4], w ? 1.f : a[5]);
          if (w) img[96] = pack2(a[5], 1.f);
        }
        fence_async_smem();
        if (__all_sync(0xffffffffu, ok)) break;
        if (it > (1 << 16)) __trap();
      }
      if (w == 0) TS(4, 7 + L * 2);
      helper_bar();
      load_wphi();
      if (w == 1 && elect()) { fence_gpu(); st_flag(&g_kvfflag[L >> 1][j][m >> 3][m & 7], tag); }
      if (w == 1 && L == 1) TS(4, 20);
    } else {
      mbar_wait(sb + BAR_SIGT, L >> 1);
      if (w == 0) {
        if (elect()) { fence_gpu(); st_flag(&g_hflag[L >> 1][m][j][0], tag); }
      } else if (m > 0) {
        poll_flags(&g_hflag[L >> 1][m - 1][j][0], 1, 1u, tag);
        if (elect()) { mbar_expect_tx(sb + BAR_HALO, 8192); bulk_load(sb + OFF_S + 8192, &g_halo[m - 1][j][0][0], 8192, sb + BAR_HALO); }
        TS(2, 2 + L * 8);
      }
    }
#pragma unroll 1
    for (int e = 0; e < (L < 3 && w == 0 ? 3 : 1); e++) {
      mbar_wait(sb + BAR_SIGP + (e == 0 ? w : e + 1) * 8, L & 1);
      TS(e == 2 ? 3 : 2 + w, (e ? 6 : 3) + L * 8);
      if (elect()) { fence_gpu(); st_flag(e == 0 ? &g_oflag[L][w][m][j] : &g_xflag[L + 1][e - 1][m][j], tag); }
      TS(e == 2 ? 3 : 2 + w, (e ? 7 : 4) + L * 8);
    }
  }
}

#define CLUSTER_ATTR
__global__ void CLUSTER_ATTR __launch_bounds__(NTHREADS, 1) fused_kernel(const __grid_constant__ Params P) {
  extern __shared__ __align__(1024) uint8_t smem_raw[];
  const uint32_t sb = MC ? smem_u32(smem_raw) : SB;
  const int tid = threadIdx.x;
  const unsigned vb = vblock();
  if (vb >= 128) {
    if (tid == 0) {
      const unsigned t = (atomicAdd(&g_ctr, 1u) / NCTA + 1u) * NCTA;
      int it = 0;
      while ((int)(ld_flag(&g_ctr) - t) < 0) { __nanosleep(500); if (++it > (1 << 20)) __trap(); }
    }
    return;
  }
  const int warp = __shfl_sync(0xffffffffu, tid >> 5, 0);
  const uint32_t sp = sb;
  if (elect()) {
    if (warp == 11) { prefetch_map(&P.mx[0]); prefetch_map(&P.mw[0]); if ((smem_u32(smem_raw) & 0xFFFFFF) != SB) __trap(); }
    if (warp < 7) {
#pragma unroll
      for (int i = 0; i < 8; i++) mbar_init(sb + OFF_BAR + (warp * 8 + i) * 8, warp == 2 ? 2 + 2 * MC : (warp == 3 ? 2 : (warp == 4 ? 8 : 1)));
    }
    asm volatile("fence.mbarrier_init.release.cluster;" ::: "memory");
    if (warp < 2) {
      const int j = cta_j(vb);
#pragma unroll 1
      for (int i = 0; i < (warp == 0 ? PRE_B : PRE_A); i++) {
        const uint32_t bar = sp + BAR_FULLB + warp * 64 + i * 8;
        mbar_expect_tx(bar, SLOT);
        if (warp == 0) { for (int q = 0; q <= MC; q++) tma_load_3d(sp + OFF_B + i * SLOT + q * 8192, &P.mw[0], bar, 0, kv_order(i >> 1, j, 0) * 64, 16 + (i & 1) * 16 + 2 * j + q); }
        else tma_load_3d(sp + OFF_A + i * SLOT, &P.mx[0], bar, kv_order(i, j, 0) * 64, cta_m(vb) * 64, 0);
      }
    }
  }
  if (tid == 0) TS(6, 0);
  if (MC) asm volatile("barrier.cluster.arrive.relaxed.aligned;\nbarrier.cluster.wait.aligned;" ::: "memory");
  else __syncthreads();
  if (tid == 0) TS(6, 2);
  if (warp < 4) {
    reg_dealloc<PREGS>();
    if (warp == 0) b_producer(P, sp, vb);
    else if (warp == 1) a_loader(P, sp, vb);
    else helper(P, sp, warp - 2, vb);
  } else {
    reg_alloc<CREGS>();
    consumer(P, sb, (warp >> 2) - 1, vb);
  }
}

typedef CUresult (*EncodeFn)(CUtensorMap*, CUtensorMapDataType, cuuint32_t, void*, const cuuint64_t*, const cuuint64_t*,
                             const cuuint32_t*, const cuuint32_t*, CUtensorMapInterleave, CUtensorMapSwizzle,
                             CUtensorMapL2promotion, CUtensorMapFloatOOBfill);

void encode(EncodeFn fn, CUtensorMap* m, const void* ptr, int rank, const cuuint64_t* dims, const cuuint64_t* strides,
            const cuuint32_t* box, CUtensorMapSwizzle swz) {
  const cuuint32_t es[3] = {1, 1, 1};
  fn(m, CU_TENSOR_MAP_DATA_TYPE_BFLOAT16, rank, const_cast<void*>(ptr), dims, strides, box, es, CU_TENSOR_MAP_INTERLEAVE_NONE,
     swz, CU_TENSOR_MAP_L2_PROMOTION_L2_256B, CU_TENSOR_MAP_FLOAT_OOB_FILL_NONE);
}
void encode_w(EncodeFn fn, CUtensorMap* m, const void* ptr, int ncols) {
  const cuuint64_t d[3] = {64, 1024, (cuuint64_t)ncols / 64}, s[2] = {(cuuint64_t)ncols * 2, 128};
  const cuuint32_t box[3] = {64, 64, MC ? 1 : 2};
  encode(fn, m, ptr, 3, d, s, box, CU_TENSOR_MAP_SWIZZLE_128B);
}

void encode_cs(EncodeFn fn, CUtensorMap* m, const void* ptr, int ncols) {
  const cuuint64_t d[2] = {(cuuint64_t)ncols, 1024}, s[1] = {(cuuint64_t)ncols * 2};
  const cuuint32_t box[2] = {32, 64};
  encode(fn, m, ptr, 2, d, s, box, CU_TENSOR_MAP_SWIZZLE_NONE);
}

}

extern "C" void kernel_launch(void* const* d_in, const int* in_sizes, int n_in, void* d_out, int out_size) {
  (void)in_sizes; (void)n_in; (void)out_size;
  void* fnp = nullptr;
  cudaDriverEntryPointQueryResult q;
  cudaGetDriverEntryPoint("cuTensorMapEncodeTiled", &fnp, cudaEnableDefault, &q);
  EncodeFn fn = (EncodeFn)fnp;
  void* po = nullptr;
  cudaGetSymbolAddress(&po, g_o);
  Params P;
  {
    const cuuint64_t dims[3] = {1024, 1024, 2}, strides[2] = {4096, 2048};
    const cuuint32_t box[3] = {64, 64, 2};
    const void* xs[5] = {d_in[0], d_out, d_out, d_out, d_out};
    for (int i = 0; i < 5; i++) P.xp[i] = (uint4*)xs[i];
    for (int i = 0; i < 4; i++) encode(fn, &P.mx[i], xs[i], 3, dims, strides, box, CU_TENSOR_MAP_SWIZZLE_128B);
    encode(fn, &P.mo, po, 3, dims, strides, box, CU_TENSOR_MAP_SWIZZLE_128B);
  }
  encode_w(fn, &P.mw[0], d_in[1], 3072);
  encode_w(fn, &P.mw[1], d_in[4], 3072);
  encode_w(fn, &P.mwo[0], d_in[2], 1024);
  encode_w(fn, &P.mwo[1], d_in[6], 1024);
  encode_cs(fn, &P.mcs[0], d_in[1], 3072);
  encode_cs(fn, &P.mcs[1], d_in[4], 3072);
  {
    const cuuint64_t dims[2] = {32, 1024}, strides[1] = {64};
    const cuuint32_t box[2] = {32, 128};
    encode(fn, &P.mwphi, d_in[5], 2, dims, strides, box, CU_TENSOR_MAP_SWIZZLE_64B);
  }
  cudaFuncSetAttribute(fused_kernel, cudaFuncAttributeMaxDynamicSharedMemorySize, SMEM_BYTES);
  fused_kernel<<<NCTA, NTHREADS, SMEM_BYTES, cudaStreamPerThread>>>(P);
}
```

```cpp
#include <cuda_runtime.h>
#include <cuda_bf16.h>
#include <cuda.h>
#include <stdint.h>

namespace {

__device__ __forceinline__ void wgmma_ss_n256(float (&d)[128], uint32_t da, uint32_t db, int sd) {
  asm volatile("{\n.reg .pred p;\n.reg .b64 a, b;\nsetp.ne.b32 p, %130, 0;\nmov.b64 a, {%128, 0x40000040};\nmov.b64 b, {%129, 0x40000040};\n"
    "wgmma.mma_async.sync.aligned.m64n256k16.f32.bf16.bf16 {%0,%1,%2,%3,%4,%5,%6,%7,%8,%9,%10,%11,%12,%13,%14,%15,%16,%17,%18,%19,%20,%21,%22,%23,%24,%25,%26,%27,%28,%29,%30,%31,%32,%33,%34,%35,%36,%37,%38,%39,%40,%41,%42,%43,%44,%45,%46,%47,%48,%49,%50,%51,%52,%53,%54,%55,%56,%57,%58,%59,%60,%61,%62,%63,%64,%65,%66,%67,%68,%69,%70,%71,%72,%73,%74,%75,%76,%77,%78,%79,%80,%81,%82,%83,%84,%85,%86,%87,%88,%89,%90,%91,%92,%93,%94,%95,%96,%97,%98,%99,%100,%101,%102,%103,%104,%105,%106,%107,%108,%109,%110,%111,%112,%113,%114,%115,%116,%117,%118,%119,%120,%121,%122,%123,%124,%125,%126,%127}, a, b, p, 1, 1, 0, 1;\n}\n"
    : "+f"(d[0]),"+f"(d[1]),"+f"(d[2]),"+f"(d[3]),"+f"(d[4]),"+f"(d[5]),"+f"(d[6]),"+f"(d[7]),"+f"(d[8]),"+f"(d[9]),"+f"(d[10]),"+f"(d[11]),"+f"(d[12]),"+f"(d[13]),"+f"(d[14]),"+f"(d[15]),"+f"(d[16]),"+f"(d[17]),"+f"(d[18]),"+f"(d[19]),"+f"(d[20]),"+f"(d[21]),"+f"(d[22]),"+f"(d[23]),"+f"(d[24]),"+f"(d[25]),"+f"(d[26]),"+f"(d[27]),"+f"(d[28]),"+f"(d[29]),"+f"(d[30]),"+f"(d[31]),"+f"(d[32]),"+f"(d[33]),"+f"(d[34]),"+f"(d[35]),"+f"(d[36]),"+f"(d[37]),"+f"(d[38]),"+f"(d[39]),"+f"(d[40]),"+f"(d[41]),"+f"(d[42]),"+f"(d[43]),"+f"(d[44]),"+f"(d[45]),"+f"(d[46]),"+f"(d[47]),"+f"(d[48]),"+f"(d[49]),"+f"(d[50]),"+f"(d[51]),"+f"(d[52]),"+f"(d[53]),"+f"(d[54]),"+f"(d[55]),"+f"(d[56]),"+f"(d[57]),"+f"(d[58]),"+f"(d[59]),"+f"(d[60]),"+f"(d[61]),"+f"(d[62]),"+f"(d[63]),"+f"(d[64]),"+f"(d[65]),"+f"(d[66]),"+f"(d[67]),"+f"(d[68]),"+f"(d[69]),"+f"(d[70]),"+f"(d[71]),"+f"(d[72]),"+f"(d[73]),"+f"(d[74]),"+f"(d[75]),"+f"(d[76]),"+f"(d[77]),"+f"(d[78]),"+f"(d[79]),"+f"(d[80]),"+f"(d[81]),"+f"(d[82]),"+f"(d[83]),"+f"(d[84]),"+f"(d[85]),"+f"(d[86]),"+f"(d[87]),"+f"(d[88]),"+f"(d[89]),"+f"(d[90]),"+f"(d[91]),"+f"(d[92]),"+f"(d[93]),"+f"(d[94]),"+f"(d[95]),"+f"(d[96]),"+f"(d[97]),"+f"(d[98]),"+f"(d[99]),"+f"(d[100]),"+f"(d[101]),"+f"(d[102]),"+f"(d[103]),"+f"(d[104]),"+f"(d[105]),"+f"(d[106]),"+f"(d[107]),"+f"(d[108]),"+f"(d[109]),"+f"(d[110]),"+f"(d[111]),"+f"(d[112]),"+f"(d[113]),"+f"(d[114]),"+f"(d[115]),"+f"(d[116]),"+f"(d[117]),"+f"(d[118]),"+f"(d[119]),"+f"(d[120]),"+f"(d[121]),"+f"(d[122]),"+f"(d[123]),"+f"(d[124]),"+f"(d[125]),"+f"(d[126]),"+f"(d[127])
    : "r"(da), "r"(db), "r"(sd));
}
__device__ __forceinline__ void wgmma_ss_n128(float (&d)[64], uint32_t da, uint32_t db, int sd) {
  asm volatile("{\n.reg .pred p;\n.reg .b64 a, b;\nsetp.ne.b32 p, %66, 0;\nmov.b64 a, {%64, 0x40000040};\nmov.b64 b, {%65, 0x40000040};\n"
    "wgmma.mma_async.sync.aligned.m64n128k16.f32.bf16.bf16 {%0,%1,%2,%3,%4,%5,%6,%7,%8,%9,%10,%11,%12,%13,%14,%15,%16,%17,%18,%19,%20,%21,%22,%23,%24,%25,%26,%27,%28,%29,%30,%31,%32,%33,%34,%35,%36,%37,%38,%39,%40,%41,%42,%43,%44,%45,%46,%47,%48,%49,%50,%51,%52,%53,%54,%55,%56,%57,%58,%59,%60,%61,%62,%63}, a, b, p, 1, 1, 0, 1;\n}\n"
    : "+f"(d[0]),"+f"(d[1]),"+f"(d[2]),"+f"(d[3]),"+f"(d[4]),"+f"(d[5]),"+f"(d[6]),"+f"(d[7]),"+f"(d[8]),"+f"(d[9]),"+f"(d[10]),"+f"(d[11]),"+f"(d[12]),"+f"(d[13]),"+f"(d[14]),"+f"(d[15]),"+f"(d[16]),"+f"(d[17]),"+f"(d[18]),"+f"(d[19]),"+f"(d[20]),"+f"(d[21]),"+f"(d[22]),"+f"(d[23]),"+f"(d[24]),"+f"(d[25]),"+f"(d[26]),"+f"(d[27]),"+f"(d[28]),"+f"(d[29]),"+f"(d[30]),"+f"(d[31]),"+f"(d[32]),"+f"(d[33]),"+f"(d[34]),"+f"(d[35]),"+f"(d[36]),"+f"(d[37]),"+f"(d[38]),"+f"(d[39]),"+f"(d[40]),"+f"(d[41]),"+f"(d[42]),"+f"(d[43]),"+f"(d[44]),"+f"(d[45]),"+f"(d[46]),"+f"(d[47]),"+f"(d[48]),"+f"(d[49]),"+f"(d[50]),"+f"(d[51]),"+f"(d[52]),"+f"(d[53]),"+f"(d[54]),"+f"(d[55]),"+f"(d[56]),"+f"(d[57]),"+f"(d[58]),"+f"(d[59]),"+f"(d[60]),"+f"(d[61]),"+f"(d[62]),"+f"(d[63])
    : "r"(da), "r"(db), "r"(sd));
}
__device__ __forceinline__ void wgmma_so_n128(float (&d)[64], uint32_t da, uint32_t db, int sd) {
  asm volatile("{\n.reg .pred p;\n.reg .b64 a, b;\nsetp.ne.b32 p, %66, 0;\nmov.b64 a, {%64, 0x80000040};\nmov.b64 b, {%65, 0x40000040};\n"
    "wgmma.mma_async.sync.aligned.m64n128k16.f32.bf16.bf16 {%0,%1,%2,%3,%4,%5,%6,%7,%8,%9,%10,%11,%12,%13,%14,%15,%16,%17,%18,%19,%20,%21,%22,%23,%24,%25,%26,%27,%28,%29,%30,%31,%32,%33,%34,%35,%36,%37,%38,%39,%40,%41,%42,%43,%44,%45,%46,%47,%48,%49,%50,%51,%52,%53,%54,%55,%56,%57,%58,%59,%60,%61,%62,%63}, a, b, p, 1, 1, 0, 1;\n}\n"
    : "+f"(d[0]),"+f"(d[1]),"+f"(d[2]),"+f"(d[3]),"+f"(d[4]),"+f"(d[5]),"+f"(d[6]),"+f"(d[7]),"+f"(d[8]),"+f"(d[9]),"+f"(d[10]),"+f"(d[11]),"+f"(d[12]),"+f"(d[13]),"+f"(d[14]),"+f"(d[15]),"+f"(d[16]),"+f"(d[17]),"+f"(d[18]),"+f"(d[19]),"+f"(d[20]),"+f"(d[21]),"+f"(d[22]),"+f"(d[23]),"+f"(d[24]),"+f"(d[25]),"+f"(d[26]),"+f"(d[27]),"+f"(d[28]),"+f"(d[29]),"+f"(d[30]),"+f"(d[31]),"+f"(d[32]),"+f"(d[33]),"+f"(d[34]),"+f"(d[35]),"+f"(d[36]),"+f"(d[37]),"+f"(d[38]),"+f"(d[39]),"+f"(d[40]),"+f"(d[41]),"+f"(d[42]),"+f"(d[43]),"+f"(d[44]),"+f"(d[45]),"+f"(d[46]),"+f"(d[47]),"+f"(d[48]),"+f"(d[49]),"+f"(d[50]),"+f"(d[51]),"+f"(d[52]),"+f"(d[53]),"+f"(d[54]),"+f"(d[55]),"+f"(d[56]),"+f"(d[57]),"+f"(d[58]),"+f"(d[59]),"+f"(d[60]),"+f"(d[61]),"+f"(d[62]),"+f"(d[63])
    : "r"(da), "r"(db), "r"(sd));
}
__device__ __forceinline__ void wgmma_ss_n40_tt(float (&d)[20], uint32_t da, uint32_t db, int sd) {
  asm volatile("{\n.reg .pred p;\n.reg .b64 a, b;\nsetp.ne.b32 p, %22, 0;\nmov.b64 a, {%20, 0x40000040};\nmov.b64 b, {%21, 0x8};\n"
    "wgmma.mma_async.sync.aligned.m64n40k16.f32.bf16.bf16 {%0,%1,%2,%3,%4,%5,%6,%7,%8,%9,%10,%11,%12,%13,%14,%15,%16,%17,%18,%19}, a, b, p, 1, 1, 1, 1;\n}\n"
    : "+f"(d[0]),"+f"(d[1]),"+f"(d[2]),"+f"(d[3]),"+f"(d[4]),"+f"(d[5]),"+f"(d[6]),"+f"(d[7]),"+f"(d[8]),"+f"(d[9]),"+f"(d[10]),"+f"(d[11]),"+f"(d[12]),"+f"(d[13]),"+f"(d[14]),"+f"(d[15]),"+f"(d[16]),"+f"(d[17]),"+f"(d[18]),"+f"(d[19])
    : "r"(da), "r"(db), "r"(sd));
}
__device__ __forceinline__ void wgmma_ss_n32(float (&d)[16], uint32_t da, uint32_t db, int sd) {
  asm volatile("{\n.reg .pred p;\n.reg .b64 a, b;\nsetp.ne.b32 p, %18, 0;\nmov.b64 a, {%16, 0x40000040};\nmov.b64 b, {%17, 0x80000020};\n"
    "wgmma.mma_async.sync.aligned.m64n32k16.f32.bf16.bf16 {%0,%1,%2,%3,%4,%5,%6,%7,%8,%9,%10,%11,%12,%13,%14,%15}, a, b, p, 1, 1, 0, 1;\n}\n"
    : "+f"(d[0]),"+f"(d[1]),"+f"(d[2]),"+f"(d[3]),"+f"(d[4]),"+f"(d[5]),"+f"(d[6]),"+f"(d[7]),"+f"(d[8]),"+f"(d[9]),"+f"(d[10]),"+f"(d[11]),"+f"(d[12]),"+f"(d[13]),"+f"(d[14]),"+f"(d[15])
    : "r"(da), "r"(db), "r"(sd));
}
__device__ __forceinline__ void wgmma_rs_n40(float (&d)[20], uint32_t a0, uint32_t a1, uint32_t a2, uint32_t a3, uint32_t db, int sd) {
  asm volatile("{\n.reg .pred p;\n.reg .b64 b;\nsetp.ne.b32 p, %25, 0;\nmov.b64 b, {%24, 0x10};\n"
    "wgmma.mma_async.sync.aligned.m64n40k16.f32.bf16.bf16 {%0,%1,%2,%3,%4,%5,%6,%7,%8,%9,%10,%11,%12,%13,%14,%15,%16,%17,%18,%19}, {%20,%21,%22,%23}, b, p, 1, 1, 1;\n}\n"
    : "+f"(d[0]),"+f"(d[1]),"+f"(d[2]),"+f"(d[3]),"+f"(d[4]),"+f"(d[5]),"+f"(d[6]),"+f"(d[7]),"+f"(d[8]),"+f"(d[9]),"+f"(d[10]),"+f"(d[11]),"+f"(d[12]),"+f"(d[13]),"+f"(d[14]),"+f"(d[15]),"+f"(d[16]),"+f"(d[17]),"+f"(d[18]),"+f"(d[19])
    : "r"(a0), "r"(a1), "r"(a2), "r"(a3), "r"(db), "r"(sd));
}
__device__ __forceinline__ void wgmma_r1_n256(float (&d)[128], uint32_t da, uint32_t db, int sd) {
  asm volatile("{\n.reg .pred p;\n.reg .b64 a, b;\nsetp.ne.b32 p, %130, 0;\nmov.b64 a, {%128, 0x8};\nmov.b64 b, {%129, 0x6};\n"
    "wgmma.mma_async.sync.aligned.m64n256k16.f32.bf16.bf16 {%0,%1,%2,%3,%4,%5,%6,%7,%8,%9,%10,%11,%12,%13,%14,%15,%16,%17,%18,%19,%20,%21,%22,%23,%24,%25,%26,%27,%28,%29,%30,%31,%32,%33,%34,%35,%36,%37,%38,%39,%40,%41,%42,%43,%44,%45,%46,%47,%48,%49,%50,%51,%52,%53,%54,%55,%56,%57,%58,%59,%60,%61,%62,%63,%64,%65,%66,%67,%68,%69,%70,%71,%72,%73,%74,%75,%76,%77,%78,%79,%80,%81,%82,%83,%84,%85,%86,%87,%88,%89,%90,%91,%92,%93,%94,%95,%96,%97,%98,%99,%100,%101,%102,%103,%104,%105,%106,%107,%108,%109,%110,%111,%112,%113,%114,%115,%116,%117,%118,%119,%120,%121,%122,%123,%124,%125,%126,%127}, a, b, p, 1, 1, 0, 1;\n}\n"
    : "+f"(d[0]),"+f"(d[1]),"+f"(d[2]),"+f"(d[3]),"+f"(d[4]),"+f"(d[5]),"+f"(d[6]),"+f"(d[7]),"+f"(d[8]),"+f"(d[9]),"+f"(d[10]),"+f"(d[11]),"+f"(d[12]),"+f"(d[13]),"+f"(d[14]),"+f"(d[15]),"+f"(d[16]),"+f"(d[17]),"+f"(d[18]),"+f"(d[19]),"+f"(d[20]),"+f"(d[21]),"+f"(d[22]),"+f"(d[23]),"+f"(d[24]),"+f"(d[25]),"+f"(d[26]),"+f"(d[27]),"+f"(d[28]),"+f"(d[29]),"+f"(d[30]),"+f"(d[31]),"+f"(d[32]),"+f"(d[33]),"+f"(d[34]),"+f"(d[35]),"+f"(d[36]),"+f"(d[37]),"+f"(d[38]),"+f"(d[39]),"+f"(d[40]),"+f"(d[41]),"+f"(d[42]),"+f"(d[43]),"+f"(d[44]),"+f"(d[45]),"+f"(d[46]),"+f"(d[47]),"+f"(d[48]),"+f"(d[49]),"+f"(d[50]),"+f"(d[51]),"+f"(d[52]),"+f"(d[53]),"+f"(d[54]),"+f"(d[55]),"+f"(d[56]),"+f"(d[57]),"+f"(d[58]),"+f"(d[59]),"+f"(d[60]),"+f"(d[61]),"+f"(d[62]),"+f"(d[63]),"+f"(d[64]),"+f"(d[65]),"+f"(d[66]),"+f"(d[67]),"+f"(d[68]),"+f"(d[69]),"+f"(d[70]),"+f"(d[71]),"+f"(d[72]),"+f"(d[73]),"+f"(d[74]),"+f"(d[75]),"+f"(d[76]),"+f"(d[77]),"+f"(d[78]),"+f"(d[79]),"+f"(d[80]),"+f"(d[81]),"+f"(d[82]),"+f"(d[83]),"+f"(d[84]),"+f"(d[85]),"+f"(d[86]),"+f"(d[87]),"+f"(d[88]),"+f"(d[89]),"+f"(d[90]),"+f"(d[91]),"+f"(d[92]),"+f"(d[93]),"+f"(d[94]),"+f"(d[95]),"+f"(d[96]),"+f"(d[97]),"+f"(d[98]),"+f"(d[99]),"+f"(d[100]),"+f"(d[101]),"+f"(d[102]),"+f"(d[103]),"+f"(d[104]),"+f"(d[105]),"+f"(d[106]),"+f"(d[107]),"+f"(d[108]),"+f"(d[109]),"+f"(d[110]),"+f"(d[111]),"+f"(d[112]),"+f"(d[113]),"+f"(d[114]),"+f"(d[115]),"+f"(d[116]),"+f"(d[117]),"+f"(d[118]),"+f"(d[119]),"+f"(d[120]),"+f"(d[121]),"+f"(d[122]),"+f"(d[123]),"+f"(d[124]),"+f"(d[125]),"+f"(d[126]),"+f"(d[127])
    : "r"(da), "r"(db), "r"(sd));
}
__device__ __forceinline__ void wgmma_r1_n128(float (&d)[64], uint32_t da, uint32_t db, int sd) {
  asm volatile("{\n.reg .pred p;\n.reg .b64 a, b;\nsetp.ne.b32 p, %66, 0;\nmov.b64 a, {%64, 0x8};\nmov.b64 b, {%65, 0x6};\n"
    "wgmma.mma_async.sync.aligned.m64n128k16.f32.bf16.bf16 {%0,%1,%2,%3,%4,%5,%6,%7,%8,%9,%10,%11,%12,%13,%14,%15,%16,%17,%18,%19,%20,%21,%22,%23,%24,%25,%26,%27,%28,%29,%30,%31,%32,%33,%34,%35,%36,%37,%38,%39,%40,%41,%42,%43,%44,%45,%46,%47,%48,%49,%50,%51,%52,%53,%54,%55,%56,%57,%58,%59,%60,%61,%62,%63}, a, b, p, 1, 1, 0, 1;\n}\n"
    : "+f"(d[0]),"+f"(d[1]),"+f"(d[2]),"+f"(d[3]),"+f"(d[4]),"+f"(d[5]),"+f"(d[6]),"+f"(d[7]),"+f"(d[8]),"+f"(d[9]),"+f"(d[10]),"+f"(d[11]),"+f"(d[12]),"+f"(d[13]),"+f"(d[14]),"+f"(d[15]),"+f"(d[16]),"+f"(d[17]),"+f"(d[18]),"+f"(d[19]),"+f"(d[20]),"+f"(d[21]),"+f"(d[22]),"+f"(d[23]),"+f"(d[24]),"+f"(d[25]),"+f"(d[26]),"+f"(d[27]),"+f"(d[28]),"+f"(d[29]),"+f"(d[30]),"+f"(d[31]),"+f"(d[32]),"+f"(d[33]),"+f"(d[34]),"+f"(d[35]),"+f"(d[36]),"+f"(d[37]),"+f"(d[38]),"+f"(d[39]),"+f"(d[40]),"+f"(d[41]),"+f"(d[42]),"+f"(d[43]),"+f"(d[44]),"+f"(d[45]),"+f"(d[46]),"+f"(d[47]),"+f"(d[48]),"+f"(d[49]),"+f"(d[50]),"+f"(d[51]),"+f"(d[52]),"+f"(d[53]),"+f"(d[54]),"+f"(d[55]),"+f"(d[56]),"+f"(d[57]),"+f"(d[58]),"+f"(d[59]),"+f"(d[60]),"+f"(d[61]),"+f"(d[62]),"+f"(d[63])
    : "r"(da), "r"(db), "r"(sd));
}

__device__ __forceinline__ uint32_t smem_u32(const void* p) { return (uint32_t)__cvta_generic_to_shared(p); }
__device__ __forceinline__ void mbar_init(uint32_t bar, uint32_t cnt) { asm volatile("mbarrier.init.shared::cta.b64 [%0], %1;" ::"r"(bar), "r"(cnt)); }
__device__ __forceinline__ void mbar_expect_tx(uint32_t bar, uint32_t bytes) { asm volatile("mbarrier.arrive.expect_tx.shared::cta.b64 _, [%0], %1;" ::"r"(bar), "r"(bytes) : "memory"); }
__device__ __forceinline__ void mbar_arrive(uint32_t bar) { asm volatile("mbarrier.arrive.shared::cta.b64 _, [%0];" ::"r"(bar) : "memory"); }
__device__ __forceinline__ void mbar_arrive_n(uint32_t bar, uint32_t n) { asm volatile("mbarrier.arrive.shared::cta.b64 _, [%0], %1;" ::"r"(bar), "r"(n) : "memory"); }
__device__ __forceinline__ void mbar_wait(uint32_t bar, uint32_t parity) {
  asm volatile("{\n.reg .pred p;\nLAB_WAIT:\nmbarrier.try_wait.parity.shared::cta.b64 p, [%0], %1;\n@p bra DONE;\nbra LAB_WAIT;\nDONE:\n}" ::"r"(bar), "r"(parity) : "memory");
}
__device__ __forceinline__ void mbar_wait2(uint32_t a, uint32_t pa, uint32_t b, uint32_t pb) {
  asm volatile("{\n.reg .pred p, q;\nLAB_WAIT:\nmbarrier.try_wait.parity.shared::cta.b64 p, [%0], %1;\nmbarrier.try_wait.parity.shared::cta.b64 q, [%2], %3;\n"
               "and.pred p, p, q;\n@p bra DONE;\nbra LAB_WAIT;\nDONE:\n}" ::"r"(a), "r"(pa), "r"(b), "r"(pb) : "memory");
}
__device__ __forceinline__ void mbar_wait3(uint32_t a, uint32_t pa, uint32_t b, uint32_t pb) {
  asm volatile("{\n.reg .pred p, q, r;\nLAB_WAIT:\nmbarrier.try_wait.parity.shared::cta.b64 p, [%0], %1;\nmbarrier.try_wait.parity.shared::cta.b64 q, [%2], %3;\n"
               "mbarrier.try_wait.parity.shared::cta.b64 r, [%2+8], %3;\nand.pred p, p, q;\nand.pred p, p, r;\n@p bra DONE;\nbra LAB_WAIT;\nDONE:\n}" ::"r"(a), "r"(pa), "r"(b), "r"(pb) : "memory");
}
__device__ __forceinline__ bool mbar_probe2(uint32_t a, uint32_t pa, uint32_t b, uint32_t pb) {
  uint32_t ok;
  asm volatile("{\n.reg .pred p, q;\nmbarrier.test_wait.parity.shared::cta.b64 p, [%1], %2;\nmbarrier.test_wait.parity.shared::cta.b64 q, [%3], %4;\n"
               "and.pred p, p, q;\nselp.u32 %0, 1, 0, p;\n}" : "=r"(ok) : "r"(a), "r"(pa), "r"(b), "r"(pb) : "memory");
  return ok != 0;
}
__device__ __forceinline__ void tma_load_3d(uint32_t dst, const CUtensorMap* tm, uint32_t bar, int c0, int c1, int c2) {
  asm volatile("cp.async.bulk.tensor.3d.shared::cluster.global.mbarrier::complete_tx::bytes [%0], [%1, {%3, %4, %5}], [%2];"
               ::"r"(dst), "l"(tm), "r"(bar), "r"(c0), "r"(c1), "r"(c2) : "memory");
}
__device__ __forceinline__ void tma_load_2d(uint32_t dst, const CUtensorMap* tm, uint32_t bar, int c0, int c1) {
  asm volatile("cp.async.bulk.tensor.2d.shared::cluster.global.mbarrier::complete_tx::bytes [%0], [%1, {%3, %4}], [%2];"
               ::"r"(dst), "l"(tm), "r"(bar), "r"(c0), "r"(c1) : "memory");
}
__device__ __forceinline__ void tma_prefetch_3d(const CUtensorMap* tm, int c0, int c1, int c2) {
  asm volatile("cp.async.bulk.prefetch.tensor.3d.L2.global [%0, {%1, %2, %3}];" ::"l"(tm), "r"(c0), "r"(c1), "r"(c2) : "memory");
}
__device__ __forceinline__ void bulk_load(uint32_t dst, const void* g, uint32_t bytes, uint32_t bar) {
  asm volatile("cp.async.bulk.shared::cluster.global.mbarrier::complete_tx::bytes [%0], [%1], %2, [%3];" ::"r"(dst), "l"(g), "r"(bytes), "r"(bar) : "memory");
}
__device__ __forceinline__ void prefetch_map(const CUtensorMap* tm) { asm volatile("prefetch.tensormap [%0];" ::"l"(tm) : "memory"); }
__device__ __forceinline__ void fence_async_smem() { asm volatile("fence.proxy.async.shared::cta;" ::: "memory"); }
__device__ __forceinline__ void fence_async_global() { asm volatile("fence.proxy.async.global;" ::: "memory"); }
__device__ __forceinline__ void fence_gpu() { asm volatile("fence.release.gpu;" ::: "memory"); }
__device__ __forceinline__ void st_flag(unsigned* p, unsigned v) { asm volatile("st.relaxed.gpu.global.u32 [%0], %1;" ::"l"(p), "r"(v) : "memory"); }
__device__ __forceinline__ unsigned ld_flag(const unsigned* p) { unsigned v; asm volatile("ld.relaxed.gpu.global.u32 %0, [%1];" : "=r"(v) : "l"(p) : "memory"); return v; }
__device__ __forceinline__ uint4 ldcg4(const void* p) { uint4 v; asm volatile("ld.global.cg.v4.u32 {%0,%1,%2,%3}, [%4];" : "=r"(v.x), "=r"(v.y), "=r"(v.z), "=r"(v.w) : "l"(p)); return v; }
__device__ __forceinline__ uint4 ld_pkt(const uint4* p) {
  uint4 v; asm volatile("{\n.reg .b128 t;\nld.relaxed.gpu.global.b128 t, [%4];\nmov.b128 {%0,%1,%2,%3}, t;\n}" : "=r"(v.x), "=r"(v.y), "=r"(v.z), "=r"(v.w) : "l"(p) : "memory"); return v;
}
__device__ __forceinline__ void st_pkt(uint4* p, uint32_t a, uint32_t b, uint32_t c, uint32_t tag) {
  asm volatile("{\n.reg .b128 t;\nmov.b128 t, {%1,%2,%3,%4};\nst.relaxed.gpu.global.b128 [%0], t;\n}" ::"l"(p), "r"(a), "r"(b), "r"(c), "r"(tag) : "memory");
}
__device__ __forceinline__ void st_v4(uint4* p, uint32_t a, uint32_t b, uint32_t c, uint32_t d) { asm volatile("st.relaxed.gpu.global.v4.u32 [%0], {%1,%2,%3,%4};" ::"l"(p), "r"(a), "r"(b), "r"(c), "r"(d) : "memory"); }
__device__ __forceinline__ void sts32(uint32_t addr, uint32_t a) { asm volatile("st.shared.u32 [%0], %1;" ::"r"(addr), "r"(a) : "memory"); }
__device__ __forceinline__ void sts64(uint32_t addr, uint32_t a, uint32_t b) { asm volatile("st.shared.v2.u32 [%0], {%1,%2};" ::"r"(addr), "r"(a), "r"(b) : "memory"); }
__device__ __forceinline__ uint32_t mul2(uint32_t a, uint32_t b) { uint32_t r; asm("mul.rn.bf16x2 %0, %1, %2;" : "=r"(r) : "r"(a), "r"(b)); return r; }
__device__ __forceinline__ uint32_t add2(uint32_t a, uint32_t b) { uint32_t r; asm("add.rn.bf16x2 %0, %1, %2;" : "=r"(r) : "r"(a), "r"(b)); return r; }
__device__ __forceinline__ bool elect() {
  uint32_t p; asm volatile("{\n.reg .pred q;\nelect.sync _|q, 0xffffffff;\nselp.u32 %0, 1, 0, q;\n}" : "=r"(p)); return p != 0;
}
__device__ __forceinline__ void wgmma_fence() { asm volatile("wgmma.fence.sync.aligned;" ::: "memory"); }
__device__ __forceinline__ void wgmma_commit() { asm volatile("wgmma.commit_group.sync.aligned;" ::: "memory"); }
template <int N> __device__ __forceinline__ void wgmma_wait() { asm volatile("wgmma.wait_group.sync.aligned %0;" ::"n"(N) : "memory"); }
template <int N> __device__ __forceinline__ void fence_regs(float (&d)[N]) {
#pragma unroll
  for (int i = 0; i < N; i++) asm volatile("" : "+f"(d[i])::"memory");
}
template <int R> __device__ __forceinline__ void reg_alloc() { asm volatile("setmaxnreg.inc.sync.aligned.u32 %0;" ::"n"(R)); }
template <int R> __device__ __forceinline__ void reg_dealloc() { asm volatile("setmaxnreg.dec.sync.aligned.u32 %0;" ::"n"(R)); }
__device__ __forceinline__ void wg_bar(int w) { asm volatile("bar.sync %0, 128;" ::"r"(w + 1) : "memory"); }
__device__ __forceinline__ constexpr uint32_t desc_lo(uint32_t addr, uint32_t lbo) { return (addr >> 4) + ((lbo >> 4) << 16); }
__device__ __forceinline__ uint32_t pack2(float lo, float hi) { uint32_t r; asm("cvt.rn.bf16x2.f32 %0, %1, %2;" : "=r"(r) : "f"(hi), "f"(lo)); return r; }
__device__ __forceinline__ float lo16(uint32_t v) { return __uint_as_float(v << 16); }
__device__ __forceinline__ float hi16(uint32_t v) { return __uint_as_float(v & 0xFFFF0000u); }
__device__ __forceinline__ float ex2(float x) { float r; asm("ex2.approx.ftz.f32 %0, %1;" : "=f"(r) : "f"(x)); return r; }
__device__ __forceinline__ float rcp(float x) { float r; asm("rcp.approx.ftz.f32 %0, %1;" : "=f"(r) : "f"(x)); return r; }
__device__ __forceinline__ uint32_t movm(uint32_t a) { uint32_t d; asm volatile("movmatrix.sync.aligned.m8n8.trans.b16 %0, %1;" : "=r"(d) : "r"(a)); return d; }
__device__ __forceinline__ void stsm4(uint32_t addr, uint32_t a, uint32_t b, uint32_t c, uint32_t d) {
  asm volatile("stmatrix.sync.aligned.m8n8.x4.shared.b16 [%0], {%1,%2,%3,%4};" ::"r"(addr), "r"(a), "r"(b), "r"(c), "r"(d) : "memory");
}
__device__ __forceinline__ void ldsm4(uint32_t addr, uint32_t (&r)[4]) {
  asm volatile("ldmatrix.sync.aligned.m8n8.x4.shared.b16 {%0,%1,%2,%3}, [%4];" : "=r"(r[0]), "=r"(r[1]), "=r"(r[2]), "=r"(r[3]) : "r"(addr) : "memory");
}
__device__ __forceinline__ void sts128(uint32_t addr, uint32_t a, uint32_t b, uint32_t c, uint32_t d) {
  asm volatile("st.shared.v4.u32 [%0], {%1,%2,%3,%4};" ::"r"(addr), "r"(a), "r"(b), "r"(c), "r"(d) : "memory");
}
__device__ __forceinline__ void lds128(uint32_t addr, uint32_t& a, uint32_t& b, uint32_t& c, uint32_t& d) {
  asm volatile("ld.shared.v4.u32 {%0,%1,%2,%3}, [%4];" : "=r"(a), "=r"(b), "=r"(c), "=r"(d) : "r"(addr) : "memory");
}
__device__ __forceinline__ float lds32f(uint32_t addr) { float v; asm volatile("ld.shared.f32 %0, [%1];" : "=f"(v) : "r"(addr) : "memory"); return v; }
__device__ __forceinline__ float2 lds64f(uint32_t addr) { float2 v; asm volatile("ld.shared.v2.f32 {%0,%1}, [%2];" : "=f"(v.x), "=f"(v.y) : "r"(addr) : "memory"); return v; }
__device__ __forceinline__ void mma16816(float (&d)[4], uint32_t a0, uint32_t a1, uint32_t a2, uint32_t a3, uint32_t b0, uint32_t b1) {
  asm("mma.sync.aligned.m16n8k16.row.col.f32.bf16.bf16.f32 {%0,%1,%2,%3}, {%4,%5,%6,%7}, {%8,%9}, {%0,%1,%2,%3};"
      : "+f"(d[0]), "+f"(d[1]), "+f"(d[2]), "+f"(d[3]) : "r"(a0), "r"(a1), "r"(a2), "r"(a3), "r"(b0), "r"(b1));
}
__device__ __forceinline__ void mma1688(float (&d)[4], uint32_t a0, uint32_t a1, uint32_t b0) {
  asm("mma.sync.aligned.m16n8k8.row.col.f32.bf16.bf16.f32 {%0,%1,%2,%3}, {%4,%5}, {%6}, {%0,%1,%2,%3};"
      : "+f"(d[0]), "+f"(d[1]), "+f"(d[2]), "+f"(d[3]) : "r"(a0), "r"(a1), "r"(b0));
}

__device__ __forceinline__ float qsum(float v) { v += __shfl_xor_sync(0xffffffffu, v, 1); v += __shfl_xor_sync(0xffffffffu, v, 2); return v; }

constexpr int NCTA = 132;
#define NB_ 6
#define NA_ 5
constexpr int NB = NB_;
constexpr int NA = NA_;
constexpr uint32_t SLOT = 16384;
constexpr uint32_t SB = 1024;
constexpr uint32_t OFF_B = 0;
constexpr uint32_t OFF_A = NB * SLOT;
constexpr uint32_t OFF_S = OFF_A + NA * SLOT;
constexpr uint32_t OFF_T = OFF_S + 20480;
constexpr uint32_t OFF_CS = OFF_T + 24576;
constexpr uint32_t OFF_MR = OFF_CS + 4640;
constexpr uint32_t OFF_BAR = OFF_MR + 512;
constexpr uint32_t OFF_MA = OFF_S, OFF_MB = OFF_CS - 2048;
constexpr uint32_t BAR_FULLB = OFF_BAR;
constexpr uint32_t BAR_FULLA = BAR_FULLB + 64;
constexpr uint32_t BAR_EMPTYB = BAR_FULLA + 64;
constexpr uint32_t BAR_EMPTYA = BAR_EMPTYB + 64;
constexpr uint32_t BAR_SIGP = BAR_EMPTYA + 64;
constexpr uint32_t BAR_SIGT = BAR_SIGP + 32;
constexpr uint32_t BAR_STAT = BAR_SIGP + 64;
constexpr uint32_t BAR_HALO = BAR_STAT + 16;
constexpr uint32_t BAR_CS = BAR_HALO + 8;
constexpr uint32_t BAR_WPHI = BAR_CS + 16;
constexpr uint32_t BAR_KV = BAR_WPHI + 8;
constexpr uint32_t BAR_STG = BAR_KV + 16;
constexpr uint32_t BAR_EPOCH = BAR_STG + 48;
constexpr uint32_t OFF_EPOCH = OFF_BAR + 7 * 64;
static_assert(BAR_EPOCH < OFF_EPOCH, "barriers");
constexpr uint32_t SMEM_BYTES = OFF_EPOCH + 8;
static_assert(SMEM_BYTES <= 232448 && NB % 2 == 0 && NB <= 8 && NA <= 6, "smem");

#define CREGS 208
#define PREGS 88
#define PF0 21
#define PFS 2
#define PRE_A 2
#define PRE_B 4
#define CSB 4
#define CSNEED 0xF003u
#define XR 2
#define PS0 2
#define PS1 2
#define PSW 0
#define STG0 0
#define QORD 1
#define KSPLIT 12
#define KEEP 16
#define NJ 3
#define LEAD 0
#define SPO 1
#define KSL 1000
#define KB 8
#define PNX 2
#define PNO 2
#define DEFER 3
#define DEFL 2
#define TSK 3
#define TSL 3
constexpr int NTHREADS = 384;

struct Params {
  CUtensorMap mx[4];
  CUtensorMap mw[2];
  CUtensorMap mwo[2];
  CUtensorMap mcs[2];
  CUtensorMap mwphi;
  uint4* xp[5];
};

__device__ __align__(256) uint4 g_o[16][16][1024];
__device__ __align__(256) uint4 g_wf[2][8][16][1024];
__device__ __align__(256) uint4 g_stats[16][2][8][32];
__device__ __align__(256) uint4 g_halo[16][8][2][256];
__device__ __align__(256) float g_cs[2][2][3072];
__device__ __align__(256) uint4 g_kvpart[8][16][2][544];
__device__ __align__(256) uint4 g_kvfin[8][16][80];
__device__ __align__(256) unsigned g_xflag[4][2][16][32];
__device__ __align__(256) unsigned g_oflag[4][2][16][32];
__device__ __align__(256) unsigned g_hflag[2][16][8][32];
__device__ __align__(256) unsigned g_kvfflag[2][8][2][32];
__device__ __align__(256) unsigned g_csflag[2][8][32];
__device__ __align__(256) unsigned g_kflag[8][32];
__device__ unsigned g_ctr;
__device__ __forceinline__ unsigned vblock() {
  unsigned s;
  asm volatile("mov.u32 %0, %%smid;" : "=r"(s));
  const unsigned r = s & 1;
  s >>= 1;
  const unsigned t = s - 32, q = (t * 37) >> 8;
  const unsigned hi = s < 60 ? 12 + (t - 7 * q) * 8 + q : (s < 62 ? s + 4 : s - 58);
  return __shfl_sync(0xffffffffu, 2 * (s < 32 ? (s & 7) * 8 + (s >> 3) : hi) + r, 0);
}
#define TS(who, id) do {} while (0)
#define TSW(id) do {} while (0)

__device__ __forceinline__ int cta_m(unsigned b) { return ((b >> 2) & 12) | (b & 3); }
__device__ __forceinline__ int cta_j(unsigned b) { return ((b >> 2) & 3) | ((b >> 4) & 4); }
struct Ring { uint32_t s, ph; };
template <int N> __device__ __forceinline__ void adv(Ring& r) { if (++r.s == N) { r.s = 0; r.ph ^= 1; } }
template <int N> __device__ __forceinline__ void rewind2(Ring& r) { if (r.s < 2) { r.s += N - 2; r.ph ^= 1; } else r.s -= 2; }
__device__ __forceinline__ int other_tile(int t, int j) { return (t == (j | 4) ? 7 : t) ^ (~j & 4); }
__device__ __forceinline__ int q_order(int i, int j) { return 2 * (i >= 14 ? j : other_tile(i >> 1, j)) + (i & 1); }
__device__ __forceinline__ int o_order(int i, int j) {
  if (i < 2) return 2 * j + i;
  const int odd = i >= 9;
  return 2 * other_tile(i - 2 - 7 * odd, j) + odd;
}
__device__ __forceinline__ int kv_order(int i, int j, int L) { return L > 0 ? o_order(i, j) : (i + 14 + 2 * (j & 4)) & 15; }

__device__ __forceinline__ unsigned poll_flags(const unsigned* f, int n, unsigned need, unsigned tag) {
  const int lane = threadIdx.x & 31;
  unsigned mask; int it = 0;
  do {
    unsigned v = lane < n ? ld_flag(f + lane) : 0u;
    mask = __ballot_sync(0xffffffffu, lane < n && v == tag);
    if (++it > (1 << 22)) __trap();
  } while ((mask & need) != need);
  fence_async_global();
  return mask;
}
template <bool WAIT = true>
__device__ __forceinline__ unsigned get_tag(uint32_t sb) {
  if (WAIT) mbar_wait(sb + BAR_EPOCH, 0);
  unsigned t; asm volatile("ld.shared.u32 %0, [%1];" : "=r"(t) : "r"(sb + OFF_EPOCH) : "memory");
  return t;
}

__device__ __forceinline__ int lane_id() { int l; asm volatile("mov.u32 %0, %%laneid;" : "=r"(l)); return l; }
__device__ __forceinline__ unsigned seq4(unsigned tag, int L) { return 8u | ((tag & 1u) << 2) | (unsigned)L; }
constexpr float LOG2E = 1.4426950408889634f;

__device__ __forceinline__ void sched_fence(uint32_t sb) { mbar_wait(sb + BAR_EPOCH, 0); }
struct Ctx {
  static constexpr uint32_t sb = SB;
  uint32_t ab, da0;
  int w, warp, lane, g, c;
  int goff;
  __device__ __forceinline__ int m() const { return goff >> 14; }
  __device__ __forceinline__ int j() const { return (goff >> 4) & 7; }
  bool elected;
  Ring ra, rb;
  uint32_t pa, pb;
  uint32_t mrow, mxor, mhi;
  __device__ __forceinline__ uint32_t aslot(uint32_t s) const { return ab + s * SLOT; }
  __device__ __forceinline__ uint32_t fullA(uint32_t s) const { return sb + BAR_FULLA + s * 8; }
  __device__ __forceinline__ uint32_t fullB(uint32_t s) const { return sb + BAR_FULLB + s * 8; }
  __device__ __forceinline__ void releaseA(uint32_t s) const { if (elected) mbar_arrive(sb + BAR_EMPTYA + s * 8); }
  __device__ __forceinline__ void releaseB(uint32_t s) const { if (elected) mbar_arrive(sb + BAR_EMPTYB + s * 8); }
  __device__ __forceinline__ uint32_t maddr(uint32_t tile, uint32_t ch) const { return tile + mrow + (((ch + mhi) ^ mxor) << 4); }
  __device__ __forceinline__ uint4* oimg(int hp) const { return &g_o[m()][2 * j() + hp][w * 512 + warp * 128]; }
  __device__ __forceinline__ uint32_t held(int i) const { return ra.s + i < 2 ? ra.s + i + NA - 2 : ra.s + i - 2; }
};

template <int N, bool FIRST, bool O = false>
__device__ __forceinline__ void gemm_issue(float (&acc)[N / 2], Ctx& x, bool ready = false) {
  if (!ready) {
    if (N == 256) mbar_wait3(x.fullA(x.ra.s), x.ra.ph, x.fullB(x.rb.s), x.rb.ph);
    else mbar_wait2(x.fullA(x.ra.s), x.ra.ph, x.fullB(x.rb.s), x.rb.ph);
  }
  const uint32_t da = x.da0 + x.ra.s * (SLOT / 16), db = desc_lo(SB + OFF_B, 8192) + x.rb.s * (SLOT / 16);
  wgmma_fence();
#pragma unroll
  for (int k = 0; k < 4; k++) {
    if constexpr (N == 256) wgmma_ss_n256(acc, da + 2 * k, db + 128 * k, !(FIRST && k == 0));
    else if constexpr (O) wgmma_so_n128(acc, da + (k >> 1) * 32 + (k & 1) * 2, db + 128 * k, 1);
    else wgmma_ss_n128(acc, da + 2 * k, db + 128 * k, !(FIRST && k == 0));
  }
  wgmma_commit();
}
template <int N>
__device__ __forceinline__ void gemm_next(Ctx& x) {
  x.pa = x.ra.s; x.pb = x.rb.s;
  if (N == 256) x.rb.s++;
  adv<NA>(x.ra); adv<NB>(x.rb);
}
template <int N>
__device__ __forceinline__ void gemm_release(Ctx& x, bool relA) {
  if (relA) x.releaseA(x.pa);
  x.releaseB(x.pb);
  if (N == 256) x.releaseB(x.pb + 1);
}
template <int N>
__device__ __forceinline__ void gemm_retire(Ctx& x, bool relA) { wgmma_wait<1>(); gemm_release<N>(x, relA); gemm_next<N>(x); }
template <bool O = false>
__device__ __forceinline__ void gemm_run(float (&acc)[64], Ctx& x, int n, int hold, int n4 = 0) {
  bool ready = false;
#pragma unroll 1
  for (; n > 0; n--) {
    gemm_issue<128, false, O>(acc, x, ready);
    const uint32_t pa = x.pa, pb = x.pb;
    gemm_next<128>(x);
    ready = mbar_probe2(x.fullA(x.ra.s), x.ra.ph, x.fullB(x.rb.s), x.rb.ph);
    wgmma_wait<1>();
    if (n > hold) x.releaseA(pa);
    x.releaseB(pb);
  }
}
__device__ __forceinline__ void gemm_end(float (&acc)[64], Ctx& x) { wgmma_wait<0>(); fence_regs(acc); gemm_release<128>(x, false); }

__device__ __forceinline__ void load_x32(float* a, uint32_t tile, uint32_t ch, const Ctx& x) {
#pragma unroll
  for (int p = 0; p < 2; p++) {
    uint32_t v[4];
    ldsm4(x.maddr(tile, ch + 2 * p), v);
#pragma unroll
    for (int i = 0; i < 4; i++) { a[8 * p + 2 * i] = lo16(v[i]); a[8 * p + 2 * i + 1] = hi16(v[i]); }
  }
}

__device__ __forceinline__ void rows_load(uint4* r, uint32_t tile, const Ctx& x) {
#pragma unroll
  for (int q = 0; q < 4; q++) {
    const uint32_t row = x.warp * 16 + 4 * q + (x.lane >> 3);
    lds128(tile + row * 128 + (((x.lane & 7) ^ (row & 7)) << 4), r[q].x, r[q].y, r[q].z, r[q].w);
  }
}
__device__ __forceinline__ void rows_store(const uint4* r, uint4* g, const Ctx& x) {
  g += (x.warp * 16 + (x.lane >> 3)) * 256 + (x.lane & 7);
#pragma unroll
  for (int q = 0; q < 4; q++) g[q * 1024] = r[q];
}
__device__ __forceinline__ void publish(int id, const Ctx& x) { __syncwarp(); if (x.lane == 0) mbar_arrive(x.sb + BAR_SIGP + id * 8); }
__device__ __forceinline__ void tile_out(uint32_t tile, uint4* g, int id, const Ctx& x) {
  uint4 r[4];
  __syncwarp();
  rows_load(r, tile, x); rows_store(r, g, x); publish(id, x);
}

template <int N>
__device__ __forceinline__ void stats_acc(const float* a, float (&t)[4]) {
#pragma unroll
  for (int i = 0; i < N; i++) { t[i & 2] += a[i]; t[(i & 2) + 1] = fmaf(a[i], a[i], t[(i & 2) + 1]); }
}
__device__ __forceinline__ void stats_send(float (&t)[4], int L, const Ctx& x) {
  const unsigned seq = seq4(get_tag<false>(x.sb), L);
#pragma unroll
  for (int q = 0; q < 4; q++) t[q] = qsum(t[q]);
  if (x.c == 0) st_pkt(&g_stats[x.m()][x.w][x.j()][x.warp * 8 + x.g], __float_as_uint(t[0]), __float_as_uint(t[1]), __float_as_uint(t[2]), (__float_as_uint(t[3]) & ~15u) | seq);
}
__device__ __forceinline__ void out_epilogue(const float (&acc)[64], uint4 (&r1)[4], uint4* g, int L, Ctx& x) {
  const uint32_t t0 = x.aslot(x.ra.s), t1 = x.aslot(x.ra.s + 1 == NA ? 0 : x.ra.s + 1);
#pragma unroll
  for (int p = 0; p < 8; p++) {
    stsm4(x.maddr(p < 4 ? t0 : t1, (p & 3) * 2), pack2(acc[8 * p], acc[8 * p + 1]), pack2(acc[8 * p + 2], acc[8 * p + 3]),
          pack2(acc[8 * p + 4], acc[8 * p + 5]), pack2(acc[8 * p + 6], acc[8 * p + 7]));
    if (p == 3) { tile_out(t0, g, 2, x); sched_fence(x.sb); }
  }
  __syncwarp();
  rows_load(r1, t1, x);
  if (L < 3) {
    float t[4] = {0.f, 0.f, 0.f, 0.f}, u[4] = {0.f, 0.f, 0.f, 0.f};
    stats_acc<32>(acc, t); stats_acc<32>(acc + 32, u);
#pragma unroll
    for (int q = 0; q < 4; q++) t[q] += u[q];
    stats_send(t, L + 1, x);
    fence_async_smem();
    asm volatile("bar.sync %0, %1;" ::"r"(L == 1 ? x.w + 1 : 3), "r"(L == 1 ? 128 : 256) : "memory");
  }
}

struct Stats { float rstd0, rstd1; };
__device__ __forceinline__ Stats load_stats(int half, const Ctx& x) {
  const float2 u = lds64f(x.sb + OFF_MR + half * 256 + (x.warp * 8 + x.g) * 8);
  return {u.x, u.y};
}

template <int NK>
__device__ __forceinline__ void hedgehog_scale(float* t, const Stats& st, const uint32_t* keep) {
#pragma unroll
  for (int q = 0; q < 16; q++) t[q] *= ((q & 2) ? st.rstd1 : st.rstd0) * LOG2E;
  float m[4];
#pragma unroll
  for (int q = 0; q < 4; q++) m[q] = fmaxf(fmaxf(fabsf(t[4 * q]), fabsf(t[4 * q + 1])), fmaxf(fabsf(t[4 * q + 2]), fabsf(t[4 * q + 3])));
  if (__builtin_expect(__any_sync(0xffffffffu, fmaxf(fmaxf(m[0], m[1]), fmaxf(m[2], m[3])) > 58.f), 0)) {
    float z[16 + NK];
#pragma unroll
    for (int q = 0; q < 16 + NK; q++) z[q] = q < 16 ? t[q & 15] : __uint_as_float(keep[q & 15]);
#pragma unroll 1
    for (int r = 0; r < 4; r += 2) {
      float hi = -INFINITY, lo = INFINITY;
#pragma unroll 1
      for (int i = 0; i < 16; i++) {
        const int k = (i & 6) * 2 + (i & 1) + r;
        const float v = z[k];
        if (i < 8) { hi = fmaxf(hi, v); lo = fminf(lo, v); }
        else z[k] = v - fminf(fmaxf(v, lo), hi);
        if (i == 7) {
#pragma unroll 1
          for (int d = 1; d <= 2; d++) { hi = fmaxf(hi, __shfl_xor_sync(0xffffffffu, hi, d)); lo = fminf(lo, __shfl_xor_sync(0xffffffffu, lo, d)); }
          const float mid = 0.5f * hi + 0.5f * lo;
          hi = fmaxf(hi - 58.f, mid); lo = fminf(lo + 58.f, mid);
        }
      }
    }
#pragma unroll
    for (int q = 0; q < 16; q++) t[q] = z[q];
  }
}
__device__ __forceinline__ void dual_exp(const float* t, uint32_t (&f)[18], int never) {
  float e[KSPLIT];
#pragma unroll
  for (int q = 0; q < KSPLIT; q++) e[q] = ex2(q < 16 ? t[q] : -t[q & 15]);
  while (never < 0) {
#pragma unroll
    for (int i = 0; i < KSPLIT; i += 4) asm volatile("ld.shared.v4.f32 {%0,%1,%2,%3}, [%4];" : "=f"(e[i]), "=f"(e[i + 1]), "=f"(e[i + 2]), "=f"(e[i + 3]) : "r"(never + i) : "memory");
    never += __float_as_int(e[0]);
  }
#pragma unroll
  for (int q = 0; q < KSPLIT; q += 2) f[q >> 1] = pack2(e[q], e[q + 1]);
#pragma unroll
  for (int q = KSPLIT; q < 32; q += 2) f[q >> 1] = q < 16 ? pack2(ex2(t[q]), ex2(t[q + 1])) : pack2(ex2(-t[q & 15]), ex2(-t[(q & 15) + 1]));
#pragma unroll
  for (int sg = 0; sg < 2; sg++) {
    const uint32_t* u = f + 8 * sg;
    const uint32_t a = add2(add2(u[0], u[2]), add2(u[4], u[6])), b = add2(add2(u[1], u[3]), add2(u[5], u[7]));
    f[16 + sg] = add2(__byte_perm(a, b, 0x5410), __byte_perm(a, b, 0x7632));
  }
}
__device__ __forceinline__ void dual_exp_rcp(const float* t, uint32_t (&f)[16]) {
#pragma unroll
  for (int q = 0; q < 8; q++) {
    const float a = ex2(t[2 * q]), b = ex2(t[2 * q + 1]), r = rcp(a * b);
    f[q] = pack2(a, b); f[8 + q] = pack2(r * b, r * a);
  }
}
__device__ __forceinline__ void cta_bar() { asm volatile("bar.sync 3, 256;" ::: "memory"); }

template <int N> __device__ __forceinline__ void pin(const uint32_t* v, uint32_t addr) {
#pragma unroll
  for (int i = 0; i < N; i += 4)
    asm volatile("{\n.reg .pred p;\nsetp.eq.u32 p, %0, 0;\n@p st.shared.v4.u32 [%0], {%1,%2,%3,%4};\n}" ::"r"(addr), "r"(v[i]), "r"(v[i + 1]), "r"(v[i + 2]), "r"(v[i + 3]) : "memory");
}

__device__ __forceinline__ void consumer(const Params& P, uint32_t sb, int w, unsigned vb) {
  Ctx x;
  x.w = w;
  x.ab = sb + OFF_A + w * 8192; x.da0 = desc_lo(SB + OFF_A, 16) + w * 512;
  x.lane = threadIdx.x & 31; x.warp = __shfl_sync(0xffffffffu, (threadIdx.x >> 5) & 3, 0); x.g = x.lane >> 2; x.c = x.lane & 3;
  x.goff = (cta_m(vb) * 128 + w) * 128 + cta_j(vb) * 16;
  asm volatile("" : "+r"(x.goff));
  x.elected = (threadIdx.x & 127) == 0;
  x.ra = {0, 0}; x.rb = {0, 0}; x.pa = x.pb = 0;
  {
    const uint32_t row = x.warp * 16 + (x.lane & 15);
    x.mrow = row * 128; x.mxor = row & 7; x.mhi = x.lane >> 4;
  }
  const int goff = x.goff;
  uint4 r1[4];
#pragma unroll
  for (int i = 0; i < 4; i++) r1[i] = make_uint4(0, 0, 0, 0);
  TSW(0);
#pragma unroll 1
  for (int L = 0; L < 4; L++) {
    float acc[64];
    constexpr uint32_t dcs = desc_lo(SB + OFF_CS, 0);
    if ((L & 1) == 0) {
    float kv[128];
    gemm_issue<256, true>(kv, x); gemm_next<256>(x);
    {
      int i = 1;
      bool rel = true;
      float t[4] = {0.f, 0.f, 0.f, 0.f};
#pragma unroll 1
      for (int seg = 0; seg < 3; seg++) {
        const int end = seg < 2 ? (L == 0 ? 3 + 2 * (x.j() & 3) + seg : 2 + seg * 2) : 14 + L;
#pragma unroll 1
        while (true) {
          gemm_issue<256, false>(kv, x);
          if (++i == end) break;
          wgmma_wait<1>();
          if (rel) gemm_release<256>(x, true);
          rel = true;
          gemm_next<256>(x);
          if (i == 5) TSW(8 + L * 12);
          if (i == 11) TSW(10 + L * 12);
        }
        if (seg < 2 && L == 0) {
          float a[32];
          const uint32_t tile = x.aslot(x.ra.s);
          load_x32(a, tile, 0, x); load_x32(a + 16, tile, 4, x);
          stats_acc<32>(a, t);
          if (seg == 1) { mbar_wait(sb + BAR_EPOCH, 0); stats_send(t, 0, x); }
          fence_async_smem();
          wg_bar(w);
        }
        if (seg == 1 && L > 0) { rows_store(r1, P.xp[L] + goff + 8, x); publish(3, x); }
        wgmma_wait<1>();
        if (rel) gemm_release<256>(x, true);
        rel = true;
        gemm_next<256>(x);
        if (seg == 0 && L > 0) { wgmma_wait<0>(); gemm_release<256>(x, true); rel = false; }
      }
    }
#pragma unroll 1
      for (int h = L; h < 2; h++) {
        float d[16];
        mbar_wait(sb + BAR_WPHI, 0);
        wgmma_fence();
#pragma unroll
        for (int q = 0; q < 2; q++) wgmma_ss_n32(d, desc_lo(SB + OFF_S + 4096, 16) + w * 512 + h * 4 + q * 2, desc_lo(SB + OFF_T + 8192, 512) + w * 256 + h * 128 + q * 64, q);
        wgmma_commit();
        gemm_issue<256, false>(kv, x);
        gemm_retire<256>(x, true);
        fence_regs(d);
        uint4* dst = &g_wf[1][x.j()][x.m()][w * 512 + (x.warp * 16 + x.g) * 8 + ((h * 4 + x.c) ^ x.g)];
        dst[0] = make_uint4(pack2(d[0], d[1]), pack2(d[4], d[5]), pack2(d[8], d[9]), pack2(d[12], d[13]));
        dst[64] = make_uint4(pack2(d[2], d[3]), pack2(d[6], d[7]), pack2(d[10], d[11]), pack2(d[14], d[15]));
      }
      const uint32_t dm = desc_lo(SB + OFF_MA, 0) + w * 64;
      mbar_wait2(sb + BAR_STAT, 0, sb + BAR_CS, 0);
      wgmma_fence();
      wgmma_r1_n256(kv, dm, dcs + 96, 1);
      wgmma_commit();
      const Stats st = load_stats(w, x);
      wgmma_wait<0>();
      fence_regs(kv);
      gemm_release<256>(x, true);
      TSW(2 + L * 12);
      uint32_t P0[32], P1[32], PH[32];
#pragma unroll
      for (int t = 0; t < 16; t++) { P0[t] = pack2(kv[4 * t] * st.rstd0, kv[4 * t + 1] * st.rstd0); P1[t] = pack2(kv[4 * t + 2] * st.rstd1, kv[4 * t + 3] * st.rstd1); }
      pin<16>(P0, x.mrow + 16);
      {
#pragma unroll
        for (int q = 0; q < 4; q++) sts128((x.warp < 3 ? sb + OFF_T + w * 12288 + x.warp * 4096 : sb + OFF_S + 4096 + w * 14336) + x.lane * 16 + q * 512, P1[4 * q], P1[4 * q + 1], P1[4 * q + 2], P1[4 * q + 3]);
      }
      wgmma_fence();
      wgmma_r1_n128(acc, dm, dcs, 0);
      gemm_issue<128, false>(acc, x); gemm_next<128>(x);
      TSW(3 + L * 12);
#pragma unroll
      for (int s = 0; s < 4; s++) {
#pragma unroll
        for (int t = 16 + 8 * (s & 1); t < 24 + 8 * (s & 1); t++) {
          if (s < 2) P1[t] = movm(pack2(kv[4 * t + 2] * st.rstd1, kv[4 * t + 3] * st.rstd1));
          else P0[t] = movm(pack2(kv[4 * t] * st.rstd0, kv[4 * t + 1] * st.rstd0));
        }
        if (s < 3) { gemm_issue<128, false>(acc, x); gemm_retire<128>(x, true); }
        if (s == 1) {
          if (x.warp < 3) {
#pragma unroll
            for (int q = 4; q < 8; q++) sts128(sb + OFF_T + w * 12288 + x.warp * 4096 + x.lane * 16 + q * 512, P1[4 * q], P1[4 * q + 1], P1[4 * q + 2], P1[4 * q + 3]);
          } else {
            uint4* dst = &g_halo[x.m()][x.j()][w][x.lane];
#pragma unroll
            for (int q = 0; q < 8; q++) dst[q * 32] = make_uint4(P1[4 * q], P1[4 * q + 1], P1[4 * q + 2], P1[4 * q + 3]);
          }
          publish(4, x);
          gemm_issue<128, false>(acc, x);
          gemm_retire<128>(x, true);
        }
      }
      TSW(4 + L * 12);
      gemm_run(acc, x, 10, 0);
      gemm_issue<128, false>(acc, x);
      {
        wg_bar(w);
        uint32_t tr = sb + OFF_T + w * 12288 + (x.warp - 1) * 4096;
        if (x.warp == 0) {
          tr = x.m() > 0 ? sb + OFF_S + 8192 + w * 4096 : tr + 4096;
          if (x.m() > 0) mbar_wait(sb + BAR_HALO, L >> 1);
        }
#pragma unroll
        for (int q = 0; q < 8; q++) lds128(tr + x.lane * 16 + q * 512, PH[4 * q], PH[4 * q + 1], PH[4 * q + 2], PH[4 * q + 3]);
      }
      gemm_retire<128>(x, false);
      gemm_end(acc, x);
      TSW(5 + L * 12);
      const bool first = (x.m() == 0) && (x.warp == 0);
      const bool hi0 = 2 * x.c > x.g, hi1 = 2 * x.c + 1 > x.g;
      const uint32_t mhi = (hi0 ? 0xFFFFu : 0u) | (hi1 ? 0xFFFF0000u : 0u);
      const float sc0 = st.rstd0 * (0.17677669529663687f * LOG2E), sc1 = st.rstd1 * (0.17677669529663687f * LOG2E);
#pragma unroll
      for (int hp = 0; hp < 2; hp++) {
        const uint32_t tile = x.aslot(x.held(hp));
        uint32_t px[2], py[2];
        float s[2][3][4];
#pragma unroll
        for (int u = 0; u < 2; u++) {
#pragma unroll
          for (int q = 0; q < 12; q++) s[u][q >> 2][q & 3] = 0.f;
#pragma unroll
          for (int ks = 0; ks < 2; ks++) {
            const int t = 8 * hp + 4 * u + 2 * ks;
            const uint32_t a0 = pack2(acc[4 * t], acc[4 * t + 1]), a1 = pack2(acc[4 * t + 2], acc[4 * t + 3]);
            const uint32_t a2 = pack2(acc[4 * t + 4], acc[4 * t + 5]), a3 = pack2(acc[4 * t + 6], acc[4 * t + 7]);
            mma16816(s[u][0], a0, a1, a2, a3, PH[t], PH[t + 1]);
            mma16816(s[u][1], a0, a1, a2, a3, P0[t], P0[t + 1]);
            mma16816(s[u][2], a0, a1, a2, a3, P1[t], P1[t + 1]);
          }
        }
        load_x32(acc + 32 * hp, tile, 0, x);
        load_x32(acc + 32 * hp + 16, tile, 4, x);
        float e[2][4], r[2][2];
#pragma unroll
        for (int u = 0; u < 2; u++) {
          e[u][0] = (hi0 ? s[u][0][0] : s[u][1][0]) * sc0; e[u][1] = (hi1 ? s[u][0][1] : s[u][1][1]) * sc0;
          e[u][2] = (hi0 ? s[u][1][2] : s[u][2][2]) * sc1; e[u][3] = (hi1 ? s[u][1][3] : s[u][2][3]) * sc1;
          if (first) { if (hi0) e[u][0] = -1e30f; if (hi1) e[u][1] = -1e30f; }
          r[u][0] = fmaxf(e[u][0], e[u][1]); r[u][1] = fmaxf(e[u][2], e[u][3]);
        }
#pragma unroll
        for (int d = 1; d <= 2; d++)
#pragma unroll
          for (int q = 0; q < 4; q++) r[q >> 1][q & 1] = fmaxf(r[q >> 1][q & 1], __shfl_xor_sync(0xffffffffu, r[q >> 1][q & 1], d));
#pragma unroll
        for (int u = 0; u < 2; u++) {
#pragma unroll
          for (int q = 0; q < 4; q++) e[u][q] = ex2(e[u][q] - r[u][q >> 1]);
          r[u][0] = e[u][0] + e[u][1]; r[u][1] = e[u][2] + e[u][3];
        }
#pragma unroll
        for (int d = 1; d <= 2; d++)
#pragma unroll
          for (int q = 0; q < 4; q++) r[q >> 1][q & 1] += __shfl_xor_sync(0xffffffffu, r[q >> 1][q & 1], d);
#pragma unroll
        for (int u = 0; u < 2; u++) {
          const float rx = rcp(r[u][0]), ry = rcp(r[u][1]);
          px[u] = pack2(e[u][0] * rx, e[u][1] * rx); py[u] = pack2(e[u][2] * ry, e[u][3] * ry);
        }
        uint32_t o[8][2];
#pragma unroll
        for (int q = 0; q < 8; q++) {
          float d[4] = {0.f, 0.f, 0.f, 0.f};
          const int t = 16 + 8 * hp + q, u = q >> 2;
          mma16816(d, px[u] & mhi, 0u, px[u] & ~mhi, py[u] & mhi, PH[t], P0[t]);
          mma1688(d, 0u, py[u] & ~mhi, P1[t]);
          o[q][0] = pack2(d[0], d[1]); o[q][1] = pack2(d[2], d[3]);
        }
#pragma unroll
        for (int q = 0; q < 4; q++)
          stsm4(tile + (x.mrow & ~1023u) + x.mxor * 64 + (q >> 1) * 512 + (((2 * (q & 1) + x.mhi) ^ (x.mxor >> 1)) << 4), o[2 * q][0], o[2 * q][1], o[2 * q + 1][0], o[2 * q + 1][1]);
        __syncwarp();
        uint4 v[4];
#pragma unroll
        for (int q = 0; q < 4; q++) lds128(tile + x.warp * 2048 + q * 512 + x.lane * 16, v[q].x, v[q].y, v[q].z, v[q].w);
#pragma unroll
        for (int q = 0; q < 4; q++) x.oimg(hp)[q * 32 + x.lane] = v[q];
        publish(hp, x);
        if (hp == 0) sched_fence(sb);
      }
    } else {
      float kv[128];
      float (&kv0)[64] = reinterpret_cast<float (&)[64]>(kv[0]);
      float (&kv1)[64] = reinterpret_cast<float (&)[64]>(kv[64]);
      auto mma8 = [&](uint32_t as, uint32_t bs, int i, bool fence) {
        const uint32_t da = desc_lo(SB + OFF_A, 16) + as * (SLOT / 16), db = desc_lo(SB + OFF_B, 8192) + bs * (SLOT / 16);
        if (fence) wgmma_fence();
#pragma unroll
        for (int k = 0; k < 4; k++) {
          wgmma_ss_n128(kv0, da + 2 * k, db + 128 * k, i + k);
          wgmma_ss_n128(kv1, da + 512 + 2 * k, db + 128 * k, i + k);
        }
        wgmma_commit();
      };
      constexpr uint32_t dm = desc_lo(SB + OFF_MB, 0);
      auto relB = [&](uint32_t s) { mbar_arrive_n(sb + BAR_EMPTYB + s * 8, 2); };
      auto skip = [&]() {
#pragma unroll
        for (int q = 0; q < 6 - NJ; q++) adv<NA>(x.ra);
        x.rb.s = w ? (2 + NJ) % 6 : 4;
        if (!w && NJ < 4) x.rb.ph ^= 1;
      };
      static_assert(NA == 5 && NB == 6, "ring arithmetic");
      mbar_wait2(x.fullA(x.ra.s), x.ra.ph, x.fullB(x.rb.s + w), x.rb.ph);
      mma8(x.ra.s, x.rb.s + w, 0, true);
      gemm_next<256>(x);
#pragma unroll 1
      for (int i = 1; i < NJ; i++) {
        mbar_wait2(x.fullA(x.ra.s), x.ra.ph, x.fullB(x.rb.s + w), x.rb.ph);
        mma8(x.ra.s, x.rb.s + w, 1, true);
        if (i == XR) { rows_store(r1, P.xp[L] + goff + 8, x); publish(3, x); }
        wgmma_wait<1>();
        if (x.elected && i != 2) { x.releaseA(x.pa); relB(x.pb + w); }
        gemm_next<256>(x);
        if (i == 1) { wgmma_wait<0>(); if (x.elected) { x.releaseA(x.pa); relB(x.pb + w); } }
      }
      if (w) {
        if (NJ > 2) { wgmma_wait<0>(); if (x.elected) { x.releaseA(x.pa); relB(x.pb + 1); } }
        if (XR >= NJ) { mbar_wait(x.fullA(x.ra.s), x.ra.ph); rows_store(r1, P.xp[L] + goff + 8, x); publish(3, x); }
        skip();
        asm volatile("bar.sync 7, 256;" ::: "memory");
      }
      TSW(8 + L * 12);
      {
        const int t = threadIdx.x & 127;
        uint32_t mask = t < 2 ? ((w ? (t ? 0xFF3Fu : 0x3FFFu) : 0xFFFFu) >> (NJ - 1)) & (w || NJ == 2 ? ~1u : ~0u) : 0u, cnt = 1 + t;
        bool ready = false;
#pragma unroll 1
        for (int i = NJ; i < 16; i++) {
          if (!ready) mbar_wait2(x.fullA(x.ra.s), x.ra.ph, x.fullB(x.rb.s), x.rb.ph);
          mma8(x.ra.s, x.rb.s, 1, true);
          if (XR >= NJ && i == NJ && !w) { rows_store(r1, P.xp[L] + goff + 8, x); publish(3, x); }
          const uint32_t bar = sb + (t ? BAR_EMPTYB + x.pb * 8 : BAR_EMPTYA + x.pa * 8);
          gemm_next<128>(x);
          if (w && (i | 4) == 15) x.rb.s = 4;
          ready = mbar_probe2(x.fullA(x.ra.s), x.ra.ph, x.fullB(x.rb.s), x.rb.ph);
          wgmma_wait<1>();
          if (mask & 1) mbar_arrive_n(bar, cnt);
          mask >>= 1; cnt = 2;
          if (i == 8 && w) asm volatile("bar.arrive 9, 256;" ::: "memory");
          if (i == 9) TSW(10 + L * 12);
        }
        mbar_wait2(sb + BAR_STAT, 1, sb + BAR_CS + 8, 0);
        wgmma_fence();
        wgmma_r1_n128(kv0, dm, dcs + 96 + 96 * w, 1);
        wgmma_r1_n128(kv1, dm + 64, dcs + 96 + 96 * w, 1);
        wgmma_commit();
        if (w == 0) asm volatile("bar.arrive 7, 256;" ::: "memory");
        wgmma_wait<1>();
        if (mask & 1) mbar_arrive_n(sb + (t ? BAR_EMPTYB + x.pb * 8 : BAR_EMPTYA + x.pa * 8), 2);
      }
      const Stats s0 = load_stats(0, x), s1 = load_stats(1, x), st = w ? s1 : s0;
      wgmma_wait<0>();
      fence_regs(kv);
      TSW(2 + L * 12);
      if (w == 0) skip();
      const uint32_t h0 = x.held(0), h1 = x.held(1);
      auto vreg = [&](int ks) { return ks < 6 ? OFF_A + (ks < 3 ? h0 * SLOT : h1 * SLOT - 15360) + ks * 5120 : OFF_S + 2048 + ks * 5120; };
      if (w == 0) {
        uint32_t f[2][18], ad[4];
#pragma unroll
        for (int q = 0; q < 18; q++) f[1][q] = 0u;
#pragma unroll
        for (int q = 0; q < 4; q++) ad[q] = x.maddr(sb + OFF_S, 2 * q);
        auto norm = [&](int un) {
          uint32_t* u = f[un & 1];
          const Stats& sn = (un & 2) ? s1 : s0;
#pragma unroll
          for (int sg = 0; sg < 2; sg++) {
            uint32_t v = u[16 + sg];
            v = add2(v, __shfl_xor_sync(0xffffffffu, v, 1)); v = add2(v, __shfl_xor_sync(0xffffffffu, v, 2));
            const float a = rcp(lo16(v)) * sn.rstd0, b = rcp(hi16(v)) * sn.rstd1;
            const uint32_t r0 = pack2(a, a), r1_ = pack2(b, b);
#pragma unroll
            for (int q = 8 * sg; q < 8 * sg + 8; q++) u[q] = mul2(u[q], (q & 1) ? r1_ : r0);
#pragma unroll
            for (int q = 2 * sg; q < 2 * sg + 2; q++) stsm4(ad[q] + (un & 1) * SLOT + (un >> 1) * 8192, u[4 * q], u[4 * q + 1], u[4 * q + 2], u[4 * q + 3]);
          }
        };
        auto unit = [&](int un) { return kv + ((un >> 1) & 1) * 64 + (un & 1) * 16 + (un >> 2) * 32; };
        hedgehog_scale<0>(kv, s0, nullptr);
#pragma unroll 1
        for (int it = 0;; it++) {
#pragma unroll
          for (int un = 0; un < 4; un++) {
            if (un == 1) {
              if (it) asm volatile("bar.sync 9, 256;" ::: "memory");
#pragma unroll
              for (int q = 0; q < 4; q++) ad[q] -= it * (OFF_S - OFF_B - 2 * SLOT);
            }
            norm((un + 3) & 3);
            dual_exp(unit(un), f[un & 1], x.goff);
            hedgehog_scale<KEEP>(unit(un + 1), ((un + 1) & 2) ? s1 : s0, f[(un + 1) & 1]);
          }
          if (it) break;
#pragma unroll
          for (int q = 0; q < 32; q++) {
            asm volatile("mov.b32 %0, %1;" : "=f"(kv[q]) : "f"(kv[q + 32]));
            asm volatile("mov.b32 %0, %1;" : "=f"(kv[q + 64]) : "f"(kv[q + 96]));
            if (q < 16) kv[32 + q] = 0.f;
          }
        }
        norm(3);
        fence_async_smem();
        TSW(3 + L * 12);
      } else {
        wg_bar(w);
#pragma unroll
        for (int hf = 0; hf < 2; hf++) {
          const uint32_t tV = sb + vreg(4 * hf + x.warp) + ((x.lane >> 3) & 1) * 2560 + (x.lane & 7) * 16;
          const float i0 = rcp(hf ? s1.rstd0 : s0.rstd0), i1 = rcp(hf ? s1.rstd1 : s0.rstd1);
          const uint32_t h = pack2(i0, i1), u0 = pack2(lo16(h), i0 - lo16(h)), u1 = pack2(hi16(h), i1 - hi16(h));
          stsm4(tV + 512 + x.mhi * 640, u0, u1, u0, u1);
          stsm4(tV + 1792 + x.mhi * 640, u0, u1, u0, u1);
#pragma unroll
          for (int q = 0; q < 8; q++) {
            const float* u = kv + 64 * hf + 8 * q;
            stsm4(tV + (q >> 1) * 640 + (2 * (q & 1) + x.mhi) * 128, pack2(u[0], u[1]), pack2(u[2], u[3]), pack2(u[4], u[5]), pack2(u[6], u[7]));
          }
        }
        TSW(3 + L * 12);
        fence_async_smem();
      }
      {
        float d[2][20];
        cta_bar();
        TSW(11 + L * 12);
        wgmma_fence();
#pragma unroll
        for (int q = 0; q < 16; q++) {
          wgmma_ss_n40_tt(d[q >> 3], desc_lo(SB + (q < 8 ? OFF_S : OFF_B + 2 * SLOT), 1024) + w * (SLOT / 16) + 128 * (q & 7), desc_lo(SB + vreg(q & 7), 2560) + (w + (q >> 3) * 2) * 40, q & 7);
          if (q == 7) wgmma_commit();
        }
        wgmma_r1_n128(acc, dm + w * 64, dcs, LEAD != 0);
        wgmma_commit();
        uint32_t pk[9];
        auto prep = [&](float (&u)[20]) {
          fence_regs(u);
#pragma unroll
          for (int q = 0; q < 8; q++) pk[q] = pack2(u[((q >> 1) & 2) + 4 * (q & 3)], u[((q >> 1) & 2) + 4 * (q & 3) + 1]);
          pk[8] = __float_as_uint((x.c & 1) ? u[18] + u[19] : u[16] + u[17]);
#pragma unroll
          for (int q = 0; q < 9; q += 4) pk[q] = (pk[q] & ~1u) | (L == 1);
        };
        uint4* dst = &g_kvpart[x.j()][w * 4 + x.warp][0][x.m() * 32 + x.lane];
        unsigned* dz = reinterpret_cast<unsigned*>(&g_kvpart[x.j()][w * 4 + x.warp][x.c & 1][512]) + x.g * 16 + x.m();
        auto send = [&](int hp) {
          st_v4(dst + hp * 16 * 544, pk[0], pk[1], pk[2], pk[3]); st_v4(dst + (hp * 16 + 1) * 544, pk[4], pk[5], pk[6], pk[7]);
          if (x.c < 2) st_flag(dz + hp * 16 * 544 * 4, pk[8]);
        };
        wgmma_wait<1>();
        prep(d[0]); send(0);
        gemm_issue<128, false>(acc, x); gemm_next<128>(x);
        wgmma_wait<1>();
        x.releaseA(h0); x.releaseA(h1); x.releaseB(2); x.releaseB(3);
        if (x.lane == 0) mbar_arrive(sb + BAR_SIGT);
        prep(d[1]);
        TSW(4 + L * 12);
#pragma unroll 1
        for (int seg = 0; seg < 2; seg++) {
          const int n0 = w ? PS1 : PS0;
          gemm_run(acc, x, seg ? 15 - LEAD * w - n0 : n0, seg, seg ? 14 : 0);
          if (seg == 0) send(1);
        }
      }
      gemm_end(acc, x);
      TSW(5 + L * 12);
      {
        float dp[2][20], dn[2][20];
        uint32_t f[4][16];
        auto expo = [&](int h) { hedgehog_scale<0>(acc + 16 * h, st, nullptr); dual_exp_rcp(acc + 16 * h, f[h]); };
        auto mma = [&](int h) {
          if (!(h & 1)) mbar_wait(sb + BAR_KV + h * 4, L >> 1);
          if (h == 0) TSW(9 + L * 12);
          const uint32_t db = desc_lo(SB + OFF_S + h * 5120, 128);
          const uint32_t (&a)[16] = f[h];
          wgmma_fence();
          wgmma_rs_n40(dp[h & 1], a[0], a[1], a[2], a[3], db, 0);
          wgmma_rs_n40(dn[h & 1], a[8], a[9], a[10], a[11], db + 160, 0);
          wgmma_rs_n40(dp[h & 1], a[4], a[5], a[6], a[7], db + 80, 1);
          wgmma_rs_n40(dn[h & 1], a[12], a[13], a[14], a[15], db + 240, 1);
          wgmma_commit();
        };
        const uint32_t oo = x.g * 4 + (x.c ^ (x.g >> 1));
        uint32_t xr[16];
        auto fin = [&](int h) {
          const uint32_t tile = x.aslot(x.held(h >> 1));
          if (!(h & 1)) {
#pragma unroll
            for (int q = 0; q < 4; q++) ldsm4(x.maddr(tile, 2 * q), reinterpret_cast<uint32_t (&)[4]>(xr[4 * q]));
          }
          float (&u)[20] = dp[h & 1];
          float (&v)[20] = dn[h & 1];
          fence_regs(u); fence_regs(v);
#pragma unroll
          for (int r = 0; r < 2; r++) {
            float cc = u[17 + 2 * r] * rcp(v[17 + 2 * r]);
            const float aa = rcp(fmaf(v[16 + 2 * r], cc, fmaf(u[17 + 2 * r], 1e-6f, u[16 + 2 * r])));
            cc *= aa;
            uint32_t o[4];
#pragma unroll
            for (int t = 0; t < 4; t++) o[t] = pack2(fmaf(u[4 * t + 2 * r], aa, v[4 * t + 2 * r] * cc), fmaf(u[4 * t + 2 * r + 1], aa, v[4 * t + 2 * r + 1] * cc));
            x.oimg(h >> 1)[r * 64 + (h & 1) * 32 + oo] = make_uint4(o[0], o[1], o[2], o[3]);
            if (r == 0 && !(h & 1)) __syncwarp();
            sts128(tile + x.warp * 2048 + r * 1024 + (h & 1) * 512 + oo * 16, o[0], o[1], o[2], o[3]);
          }
          if (h & 1) {
            publish(h >> 1, x);
#pragma unroll
            for (int q = 0; q < 16; q++) { acc[16 * (h - 1) + 2 * q] = lo16(xr[q]); acc[16 * (h - 1) + 2 * q + 1] = hi16(xr[q]); }
          }
        };
        expo(0); mma(0);
        expo(1); mma(1);
        wgmma_wait<1>(); fin(0); wgmma_wait<0>(); fin(1);
        expo(2); mma(2);
        expo(3); mma(3);
        wgmma_wait<1>(); fin(2); wgmma_wait<0>(); fin(3);
      }
    }
    fence_async_smem();
    wg_bar(w);
    TSW(6 + L * 12);
    rewind2<NA>(x.ra);
    gemm_issue<128, false, true>(acc, x); gemm_next<128>(x);
#pragma unroll 1
    for (int seg = L >= TSL ? 0 : 1; seg < 2; seg++) {
      gemm_run<true>(acc, x, L >= TSL ? (seg ? TSK : 15 - TSK) : 15, seg);
      if (L >= TSL) {
        if (seg == 0 && w == 1) asm volatile("bar.sync 6, 256;" ::: "memory");
        if (seg == 1 && w == 0) asm volatile("bar.arrive 6, 256;" ::: "memory");
      }
    }
    gemm_end(acc, x);
    TSW(7 + L * 12);
    rewind2<NA>(x.ra);
    out_epilogue(acc, r1, P.xp[L + 1] + goff, L, x);
    TSW(13 + L * 12);
  }
  rows_store(r1, P.xp[4] + goff + 8, x);
}

__device__ __forceinline__ void b_producer(const Params& P, uint32_t sb, unsigned vb) {
  const int j = cta_j(vb);
  Ring r = {PRE_B % NB, PRE_B < NB};
  auto load = [&](const CUtensorMap* tm, int kb, int part, bool folded) {
    mbar_wait(sb + BAR_EMPTYB + r.s * 8, r.ph);
    if (elect()) {
      mbar_expect_tx(sb + BAR_FULLB + r.s * 8, SLOT);
      if (folded) bulk_load(sb + OFF_B + r.s * SLOT, &g_wf[part][j][kb][0], SLOT, sb + BAR_FULLB + r.s * 8);
      else tma_load_3d(sb + OFF_B + r.s * SLOT, tm, sb + BAR_FULLB + r.s * 8, 0, kb * 64, part * 16 + 2 * j);
    }
    adv<NB>(r);
  };
#pragma unroll 1
  for (int L = 0; L < 4; L++) {
    const int wt = L & 1;
    if (L == 1) { mbar_wait(sb + BAR_WPHI, 1); fence_async_global(); }
#pragma unroll 1
    for (int i = L == 0 ? PRE_B : 0; i < 32; i++) {
      const bool solo = wt && i >= 2 * NJ;
      const int v = solo ? i >= 16 + NJ : i & 1;
      load(&P.mw[wt], kv_order(solo ? i - (v ? 16 : NJ) : i >> 1, j, L), 1 + v, wt && !v);
      if (wt && (i | 4) == 31) r.s = 4;
      if (L == 0 && (i == PF0 || i == PF0 + PFS) && elect()) tma_prefetch_3d(&P.mwo[i != PF0], 0, cta_m(vb) * 64, 2 * j);
      if (L == 0 && i < 9) TS(6, 4 + i);
      if (L == 2 && (i & 1)) TS(7, 32 + (i >> 1));
    }
    if (L == 1) { mbar_wait(sb + BAR_CS + 8, 0); fence_async_global(); }
#pragma unroll 1
    for (int i = 0; i < 32; i++) {
      if (DEFER && i == 16 && ((DEFL >> wt) & 1)) {
        Ring q = r;
        for (int u = 0; u < DEFER; u++) adv<NB>(q);
        mbar_wait(sb + BAR_EMPTYB + q.s * 8, q.ph);
      }
      load(i < 16 ? &P.mw[wt] : &P.mwo[wt], i < 16 ? q_order(i, j) : o_order(i - 16, j), 0, wt && i < 16);
    }
  }
}

__device__ __forceinline__ void a_loader(const Params& P, uint32_t sb, unsigned vb) {
  const int j = cta_j(vb), m = cta_m(vb);
  Ring r = {PRE_A % NA, PRE_A < NA};
  auto load = [&](const CUtensorMap* tm, int c0, int c1, int c2) {
    mbar_wait(sb + BAR_EMPTYA + r.s * 8, r.ph);
    if (elect()) {
      mbar_expect_tx(sb + BAR_FULLA + r.s * 8, SLOT);
      tma_load_3d(sb + OFF_A + r.s * SLOT, tm, sb + BAR_FULLA + r.s * 8, c0, c1, c2);
    }
    adv<NA>(r);
  };
#pragma unroll 1
  for (int i = PRE_A; i < 16; i++) { load(&P.mx[0], kv_order(i, j, 0) * 64, m * 64, 0); if (i < 8) TS(6, 21 + i); }
  const unsigned tag = get_tag(sb);
#pragma unroll 1
  for (int L = 0; L < 4; L++) {
#pragma unroll 1
    for (int i = (L & 1) ? NJ - 16 : 0; i < 16; i++) load(&P.mx[L], (i < 0 ? o_order(16 + i, j) : q_order(i, j)) * 64, m * 64, 0);
    if (L & 1) {
#pragma unroll 1
      for (int p = 0; p < 2; p++) {
        poll_flags(&g_kvfflag[L >> 1][j][p][0], 8, 0xFFu, tag);
        if (elect()) { mbar_expect_tx(sb + BAR_KV + p * 8, 10240); bulk_load(sb + OFF_S + p * 10240, &g_kvfin[j][8 * p][0], 10240, sb + BAR_KV + p * 8); }
      }
      TS(4, 14 + L);
    }
#pragma unroll 1
    for (int p = 0; p < (L < 3 ? 2 : 1); p++) {
      const unsigned* flags = p == 0 ? &g_oflag[L][0][m][0] : &g_xflag[L + 1][0][m][0];
      unsigned seen = 0;
#pragma unroll 1
      for (int i = 2; i < 16; i++) {
        const int c0 = o_order(i, j) * 64;
        mbar_wait(sb + BAR_EMPTYA + r.s * 8, r.ph);
        if (elect()) mbar_expect_tx(sb + BAR_FULLA + r.s * 8, SLOT);
        if (i == 2) mbar_wait(sb + BAR_SIGP + p * 16, L & 1);
        if (i == 2 || i == 9 || (i == 6 && seen != 0xFFFFFFFFu)) {
          const int lane = threadIdx.x & 31, nn = p == 1 ? PNX : PNO;
          const unsigned* f = flags + (i == 9 ? 512 : 0) + (lane & 7);
          if (i == 2) f += (((lane >> 3) & (nn - 1)) - (m & (nn - 1))) * 32;
          const unsigned need = i == 2 ? 0x0F0F0F0Fu << (~j & 4) : 0xFFFFFFFFu;
          int it = 0;
          do { seen = __ballot_sync(0xffffffffu, ld_flag(f) == tag); if (++it > (1 << 22)) __trap(); } while ((seen & need) != need);
          fence_async_global();
        }
        if (elect()) {
          if (p == 0) bulk_load(sb + OFF_A + r.s * SLOT, &g_o[m][0][c0 * 16], SLOT, sb + BAR_FULLA + r.s * 8);
          else tma_load_3d(sb + OFF_A + r.s * SLOT, &P.mx[L + 1], sb + BAR_FULLA + r.s * 8, c0, m * 64, 0);
        }
        adv<NA>(r);
        if (i == 2) TS(2, p == 0 ? 5 + L * 8 : 9 + L * 8);
        if (L == 1 && p == 1) TS(7, 16 + i);
      }
    }
  }
}

__device__ __forceinline__ void helper_bar() { asm volatile("bar.sync 4, 64;" ::: "memory"); }
__device__ __forceinline__ void helper(const Params& P, uint32_t sb, int w, unsigned vb) {
  const int j = cta_j(vb), m = cta_m(vb);
  if (w == 0) {
    if (elect()) {
      const unsigned t = atomicAdd(&g_ctr, 1u) / NCTA + 1u;
      asm volatile("st.shared.u32 [%0], %1;" ::"r"(sb + OFF_EPOCH), "r"(t) : "memory");
      mbar_arrive(sb + BAR_EPOCH);
    }
  }
  const unsigned tag = get_tag(sb);
  mbar_wait(sb + BAR_FULLB + 24, 0);
  const uint32_t stg = sb + OFF_T + w * 12288, stb = sb + BAR_STG + w * 24;
  Ring rs = {0, 0};
  if (w == 1 && elect()) { mbar_expect_tx(sb + BAR_WPHI, SLOT + 8192); tma_load_3d(sb + OFF_S + 4096, &P.mw[1], sb + BAR_WPHI, 0, m * 64, 16 + 2 * j); }
  auto cs_image = [&](int L) {
      const int lane = lane_id();
      poll_flags(&g_csflag[L][j][0], 16, L ? CSNEED : 0xFFFu, tag);
#pragma unroll
      for (int p = 0; p < 3; p++) {
        const uint4 u = ldcg4(&g_cs[L][0][p * 1024 + 128 * j + lane * 4]), v = ldcg4(&g_cs[L][1][p * 1024 + 128 * j + lane * 4]);
        const float c0 = __uint_as_float(u.x) + __uint_as_float(v.x), c1 = __uint_as_float(u.y) + __uint_as_float(v.y);
        const float c2 = __uint_as_float(u.z) + __uint_as_float(v.z), c3 = __uint_as_float(u.w) + __uint_as_float(v.w);
        const uint32_t h0 = pack2(c0, c1), h1 = pack2(c2, c3), dst = sb + OFF_CS + (p * 16 + (lane >> 1)) * 96 + L * 48 + (lane & 1) * 8;
        sts64(dst, h0, h1); sts64(dst + 16, pack2(c0 - lo16(h0), c1 - hi16(h0)), pack2(c2 - lo16(h1), c3 - hi16(h1))); sts64(dst + 32, h0, h1);
        if (L == 0) { sts64(dst + 48, 0u, 0u); sts64(dst + 64, 0u, 0u); sts64(dst + 80, 0u, 0u); }
      }
      if (L == 0 && lane < 4) sts64(sb + OFF_CS + 4608 + lane * 8, 0u, 0u);
      fence_async_smem();
      __syncwarp();
      if (elect()) mbar_arrive(sb + BAR_CS + L * 8);
      TS(4, 2 + L * 2);
  };
#pragma unroll 1
  for (int L = 0; L < 4; L++) {
    const int lane = lane_id();
    if (L == 0) {
      {
        const int wt = m >= 12, col = ((0x2021 >> (m & 12)) & 3) * 1024 + 128 * j + (m & 3) * 32;
        const CUtensorMap* tm = &P.mcs[wt];
        constexpr int nb = 8;
        float a[8] = {0.f, 0.f, 0.f, 0.f, 0.f, 0.f, 0.f, 0.f};
#pragma unroll 1
        for (int b = -3; b < nb; b++) {
          uint4 v[8];
          if (b >= 0) {
            mbar_wait(stb + rs.s * 8, rs.ph);
#pragma unroll
            for (int u = 0; u < 8; u++) lds128(stg + rs.s * 4096 + u * 512 + lane * 16, v[u].x, v[u].y, v[u].z, v[u].w);
            fence_async_smem();
            __syncwarp();
          }
          const uint32_t sl = b < 0 ? (rs.s + b + 3) % 3 : rs.s;
          if (b + 3 < nb && elect()) { mbar_expect_tx(stb + sl * 8, 4096); tma_load_2d(stg + sl * 4096, tm, stb + sl * 8, col, (w * (16 - nb) + b + 3) * 64); }
          if (b >= 0) {
            adv<3>(rs);
#pragma unroll
            for (int u = 0; u < 8; u++) {
              a[0] += lo16(v[u].x); a[1] += hi16(v[u].x); a[2] += lo16(v[u].y); a[3] += hi16(v[u].y);
              a[4] += lo16(v[u].z); a[5] += hi16(v[u].z); a[6] += lo16(v[u].w); a[7] += hi16(v[u].w);
            }
          }
        }
#pragma unroll
        for (int u = 0; u < 8; u++) {
          a[u] += __shfl_xor_sync(0xffffffffu, a[u], 4); a[u] += __shfl_xor_sync(0xffffffffu, a[u], 8); a[u] += __shfl_xor_sync(0xffffffffu, a[u], 16);
        }
        if (lane < 4) {
          float4* dst = reinterpret_cast<float4*>(&g_cs[wt][w][col + lane * 8]);
          dst[0] = make_float4(a[0], a[1], a[2], a[3]); dst[1] = make_float4(a[4], a[5], a[6], a[7]);
        }
        helper_bar();
        if (w == 0 && elect()) { fence_gpu(); st_flag(&g_csflag[wt][j][m], tag); }
      }
      if (w == 1 && elect()) tma_load_2d(sb + OFF_T + 8192, &P.mwphi, sb + BAR_WPHI, 0, 128 * j);
      if (w == 0) TS(4, 1 + L * 2);
    }
    if (w == 1) {
      if (L > 0) mbar_wait(sb + BAR_SIGP + ((L & STG0) ? 16 : 24), (L - 1) & 1);
#pragma unroll 1
      for (int p = 0; p < 2; p++) {
        uint4 v[8];
        for (int it = 0;; it++) {
          bool ok = true;
#pragma unroll
          for (int t = 0; t < 8; t++) v[t] = ld_pkt(&g_stats[m][p][t][lane]);
#pragma unroll
          for (int t = 0; t < 8; t++) ok = ok && (v[t].w & 15u) == seq4(tag, L);
          if (__all_sync(0xffffffffu, ok)) break;
          __nanosleep(200);
          if (it > (1 << 20)) __trap();
        }
        float s0 = 0.f, q0 = 0.f, s1 = 0.f, q1 = 0.f;
#pragma unroll
        for (int t = 0; t < 8; t++) { s0 += __uint_as_float(v[t].x); q0 += __uint_as_float(v[t].y); s1 += __uint_as_float(v[t].z); q1 += __uint_as_float(v[t].w & ~15u); }
        s0 *= (1.f / 1024); s1 *= (1.f / 1024);
        sts64(sb + OFF_MR + p * 256 + lane * 8, __float_as_uint(rsqrtf(fmaxf(q0 * (1.f / 1024) - s0 * s0, 0.f) + 1e-5f)),
              __float_as_uint(rsqrtf(fmaxf(q1 * (1.f / 1024) - s1 * s1, 0.f) + 1e-5f)));
#pragma unroll
        for (int r = 0; r < 2; r++) {
          const float v = -0.5f * (r ? s1 : s0);
          const uint32_t hh = pack2(v, v), hl = pack2(v, v - lo16(hh));
          const bool b = L & 1;
          sts128(sb + (b ? OFF_MB : OFF_MA) + p * 1024 + (lane >> 3) * 256 + r * 128 + (lane & 7) * 16, b ? 0u : hh, b ? hh << 16 : hl >> 16, b ? hl : 0u, 0u);
        }
      }
      fence_async_smem();
      __syncwarp();
      if (elect()) {
        mbar_arrive(sb + BAR_STAT);
      }
      TS(2, 0 + L * 8);
    }
    if (L == w) cs_image(L);
    if (L & 1) {
      const uint32_t flip = L == 1 ? 0u : 1u;
      mbar_wait(sb + BAR_SIGT, 1);
      {
        int it = 0;
        while (!__all_sync(0xffffffffu, (ld_flag(reinterpret_cast<const unsigned*>(&g_kvpart[j][m][w][512]) + (lane & 15)) ^ flip) & 1u)) { if (++it > (1 << 22)) __trap(); }
        fence_async_global();
      }
      if (w == 0) TS(4, 6 + L * 2);
      for (int it = 0;; it++) {
        if (elect()) { mbar_expect_tx(stb + rs.s * 8, 8704); bulk_load(stg, &g_kvpart[j][m][w][0], 8704, stb + rs.s * 8); }
        mbar_wait(stb + rs.s * 8, rs.ph);
        adv<3>(rs);
        float a[8] = {0.f, 0.f, 0.f, 0.f, 0.f, 0.f, 0.f, 0.f};
        uint4 z;
        lds128(stg + 8192 + lane * 16, z.x, z.y, z.z, z.w);
        uint32_t ok = (z.x ^ flip) & (z.y ^ flip) & (z.z ^ flip) & (z.w ^ flip);
#pragma unroll 1
        for (int b = 0; b < 16; b += KB) {
          uint4 v[KB];
#pragma unroll
          for (int u = 0; u < KB; u++) lds128(stg + (b + u) * 512 + lane * 16, v[u].x, v[u].y, v[u].z, v[u].w);
#pragma unroll
          for (int u = 0; u < KB; u++) {
            a[0] += lo16(v[u].x); a[1] += hi16(v[u].x); a[2] += lo16(v[u].y); a[3] += hi16(v[u].y);
            a[4] += lo16(v[u].z); a[5] += hi16(v[u].z); a[6] += lo16(v[u].w); a[7] += hi16(v[u].w);
            ok &= v[u].x ^ flip;
          }
        }
        uint4* img = &g_kvfin[j][m][w * 8 + (lane >> 2)];
        img[(lane & 3) * 16] = make_uint4(pack2(a[0], a[1]), pack2(a[2], a[3]), pack2(a[4], a[5]), pack2(a[6], a[7]));
        reinterpret_cast<uint32_t*>(img + 64)[lane & 3] = pack2(qsum((__uint_as_float(z.x) + __uint_as_float(z.y)) + (__uint_as_float(z.z) + __uint_as_float(z.w))), 1.f);
        if (__all_sync(0xffffffffu, ok & 1u)) break;
        fence_async_smem();
        if (it > (1 << 16)) __trap();
      }
      if (w == 0) TS(4, 7 + L * 2);
      helper_bar();
      if (w == 1 && elect()) { fence_gpu(); st_flag(&g_kvfflag[L >> 1][j][m >> 3][m & 7], tag); }
      if (w == 1 && L == 1) TS(4, 20);
    } else {
      mbar_wait(sb + BAR_SIGT, 0);
      if (w == 0) {
        if (elect()) { fence_gpu(); st_flag(&g_hflag[L >> 1][m][j][0], tag); st_flag(&g_kflag[j][m], tag); }
        if (L == 0) {
          __nanosleep(KSL);
          poll_flags(&g_kflag[j][0], 16, 0xFFFFu, tag);
          if (elect()) mbar_arrive(sb + BAR_WPHI);
        }
      } else if (m > 0) {
        poll_flags(&g_hflag[L >> 1][m - 1][j][0], 1, 1u, tag);
        if (elect()) { mbar_expect_tx(sb + BAR_HALO, 8192); bulk_load(sb + OFF_S + 8192, &g_halo[m - 1][j][0][0], 8192, sb + BAR_HALO); }
        TS(2, 2 + L * 8);
      }
    }
#pragma unroll 1
    for (int e = 0; e < (L < 3 && w == 0 ? 3 : 1); e++) {
      mbar_wait(sb + BAR_SIGP + (e == 0 ? w : e + 1) * 8, L & 1);
      TS(e == 2 ? 3 : 2 + w, (e ? 6 : 3) + L * 8);
      if (elect()) { fence_gpu(); st_flag(e == 0 ? &g_oflag[L][w][m][j] : &g_xflag[L + 1][e - 1][m][j], tag); }
      TS(e == 2 ? 3 : 2 + w, (e ? 7 : 4) + L * 8);
    }
  }
}

__device__ __forceinline__ void spare(const Params& P, uint32_t sb, int id) {
  const int tid = threadIdx.x & 127, w = __shfl_sync(0xffffffffu, threadIdx.x >> 7, 0), lane = tid & 31, j = 2 * id + w;
  const uint32_t ring = w * 6 * SLOT, wp = 12 * SLOT + w * 8192, bar = sb + 13 * SLOT + w * 64;
  auto part = [&](int t) { return (t >> 4) ^ SPO; };
  auto load = [&](int t, uint32_t sl) {
    mbar_expect_tx(bar + sl * 8, t == 0 ? SLOT + 8192 : SLOT);
    tma_load_3d(sb + ring + sl * SLOT, &P.mw[1], bar + sl * 8, 0, (t & 15) * 64, part(t) * 16 + 2 * j);
  };
  if (tid == 0) {
    if (w == 2) sts32(sb + OFF_EPOCH, atomicAdd(&g_ctr, 1u) / NCTA + 1u);
    else {
#pragma unroll 1
      for (int t = 0; t < 5; t++) {
        mbar_init(bar + t * 8, 1);
        asm volatile("fence.mbarrier_init.release.cluster;" ::: "memory");
        load(t, t);
      }
      tma_load_2d(sb + wp, &P.mwphi, bar, 0, 128 * j);
    }
  }
  __syncthreads();
  const unsigned tag = get_tag<false>(sb);
  if (w == 2) {
    int it = 0;
    while ((int)(ld_flag(&g_ctr) - tag * NCTA) < 0) { if (++it > (1 << 22)) __trap(); }
    return;
  }
  Ring r = {4, 1};
  float d[64] = {}, cs[32] = {};
  auto fold = [&]() {
    mbar_wait(bar + r.s * 8, r.ph);
    wgmma_fence();
#pragma unroll
    for (int q = 0; q < 8; q++)
      wgmma_ss_n32(reinterpret_cast<float (&)[16]>(d[16 * (q >> 1)]), desc_lo(SB + ring + r.s * SLOT, 16) + (q >> 2) * 512 + (q & 3) * 2, desc_lo(SB + wp, 512) + q * 64, q & 1);
    wgmma_commit();
  };
  const int row = (tid >> 5) * 16 + (lane >> 2);
#pragma unroll 1
  for (int t = -1; t < 32; t++) {
    uint32_t f[32];
#pragma unroll
    for (int i = 0; i < 32; i++) f[i] = pack2(d[2 * i], d[2 * i + 1]);
    wg_bar(w);
    if (tid == 0 && t >= 0 && t < 27) load(t + 5, r.s);
    __syncwarp();
    if (t < 31) adv<5>(r);
    fold();
    if (part(t) == 0 && t >= 0) {
#pragma unroll
      for (int q = 0; q < 8; q++)
        g_wf[0][j][t & 15][(q >> 2) * 512 + (row + 8 * (q & 1)) * 8 + (((q & 2) * 2 + (lane & 3)) ^ (lane >> 2))] =
            make_uint4(f[4 * (q & 6) + (q & 1)], f[4 * (q & 6) + (q & 1) + 2], f[4 * (q & 6) + (q & 1) + 4], f[4 * (q & 6) + (q & 1) + 6]);
    }
#pragma unroll
    for (int i = 0; i < 32; i++) { cs[i & 30] += lo16(f[i]); cs[i | 1] += hi16(f[i]); }
    wgmma_wait<0>();
    fence_regs(d);
    if ((t & 15) == 15) {
      if (t >= 0) {
        const uint32_t red = sb + ring + 5 * SLOT;
#pragma unroll
        for (int i = 0; i < 8; i++) sts128(red + (tid >> 2) * 512 + (i >> 1) * 128 + (lane & 3) * 32 + (i & 1) * 16, __float_as_uint(cs[4 * i]), __float_as_uint(cs[4 * i + 1]), __float_as_uint(cs[4 * i + 2]), __float_as_uint(cs[4 * i + 3]));
        wg_bar(w);
        float a = 0.f;
#pragma unroll 4
        for (int i = 0; i < 32; i++) a += lds32f(red + i * 512 + tid * 4);
        g_cs[1][0][part(t) * 1024 + j * 128 + tid] = a;
        wg_bar(w);
        if (tid == 0) {
          fence_gpu();
          st_flag(&g_csflag[1][j][part(t)], tag);
        }
        __syncwarp();
      }
#pragma unroll
      for (int i = 0; i < 32; i++) cs[i] = 0.f;
    }
  }
}

__global__ void __launch_bounds__(NTHREADS, 1) fused_kernel(const __grid_constant__ Params P) {
  extern __shared__ __align__(1024) uint8_t smem_raw[];
  constexpr uint32_t sb = SB;
  const int tid = threadIdx.x;
  const unsigned vb = vblock();
  if (vb >= 128) { spare(P, sb, vb - 128); return; }
  const int warp = __shfl_sync(0xffffffffu, tid >> 5, 0);
  if (elect()) {
    if (warp == 11) { prefetch_map(&P.mx[0]); prefetch_map(&P.mw[0]); if (smem_u32(smem_raw) != SB) __trap(); }
    if (warp < 7) {
#pragma unroll
      for (int i = 0; i < 8; i++) mbar_init(sb + OFF_BAR + (warp * 8 + i) * 8, warp == 2 || warp == 3 ? 2 : (warp == 4 ? 8 : 1));
    }
    asm volatile("fence.mbarrier_init.release.cluster;" ::: "memory");
    if (warp < 2) {
      const int j = cta_j(vb);
#pragma unroll 1
      for (int i = 0; i < (warp == 0 ? PRE_B : PRE_A); i++) {
        const uint32_t bar = sb + BAR_FULLB + warp * 64 + i * 8;
        mbar_expect_tx(bar, SLOT);
        if (warp == 0) tma_load_3d(sb + OFF_B + i * SLOT, &P.mw[0], bar, 0, kv_order(i >> 1, j, 0) * 64, 16 + (i & 1) * 16 + 2 * j);
        else tma_load_3d(sb + OFF_A + i * SLOT, &P.mx[0], bar, kv_order(i, j, 0) * 64, cta_m(vb) * 64, 0);
      }
    }
  }
  if (tid == 0) TS(6, 0);
  __syncthreads();
  if (tid == 0) TS(6, 2);
  if (warp < 4) {
    reg_dealloc<PREGS>();
    if (warp == 0) b_producer(P, sb, vb);
    else if (warp == 1) a_loader(P, sb, vb);
    else helper(P, sb, warp - 2, vb);
  } else {
    reg_alloc<CREGS>();
    consumer(P, sb, (warp >> 2) - 1, vb);
  }
}

typedef CUresult (*EncodeFn)(CUtensorMap*, CUtensorMapDataType, cuuint32_t, void*, const cuuint64_t*, const cuuint64_t*,
                             const cuuint32_t*, const cuuint32_t*, CUtensorMapInterleave, CUtensorMapSwizzle,
                             CUtensorMapL2promotion, CUtensorMapFloatOOBfill);

void encode(EncodeFn fn, CUtensorMap* m, const void* ptr, int rank, const cuuint64_t* dims, const cuuint64_t* strides,
            const cuuint32_t* box, CUtensorMapSwizzle swz) {
  const cuuint32_t es[3] = {1, 1, 1};
  fn(m, CU_TENSOR_MAP_DATA_TYPE_BFLOAT16, rank, const_cast<void*>(ptr), dims, strides, box, es, CU_TENSOR_MAP_INTERLEAVE_NONE,
     swz, CU_TENSOR_MAP_L2_PROMOTION_L2_256B, CU_TENSOR_MAP_FLOAT_OOB_FILL_NONE);
}
void encode_w(EncodeFn fn, CUtensorMap* m, const void* ptr, int ncols) {
  const cuuint64_t d[3] = {64, 1024, (cuuint64_t)ncols / 64}, s[2] = {(cuuint64_t)ncols * 2, 128};
  const cuuint32_t box[3] = {64, 64, 2};
  encode(fn, m, ptr, 3, d, s, box, CU_TENSOR_MAP_SWIZZLE_128B);
}

void encode_cs(EncodeFn fn, CUtensorMap* m, const void* ptr, int ncols) {
  const cuuint64_t d[2] = {(cuuint64_t)ncols, 1024}, s[1] = {(cuuint64_t)ncols * 2};
  const cuuint32_t box[2] = {32, 64};
  encode(fn, m, ptr, 2, d, s, box, CU_TENSOR_MAP_SWIZZLE_NONE);
}

}

extern "C" void kernel_launch(void* const* d_in, const int* in_sizes, int n_in, void* d_out, int out_size) {
  (void)in_sizes; (void)n_in; (void)out_size;
  void* fnp = nullptr;
  cudaDriverEntryPointQueryResult q;
  cudaGetDriverEntryPoint("cuTensorMapEncodeTiled", &fnp, cudaEnableDefault, &q);
  EncodeFn fn = (EncodeFn)fnp;
  Params P;
  {
    const cuuint64_t dims[3] = {1024, 1024, 2}, strides[2] = {4096, 2048};
    const cuuint32_t box[3] = {64, 64, 2};
    const void* xs[5] = {d_in[0], d_out, d_out, d_out, d_out};
    for (int i = 0; i < 5; i++) P.xp[i] = (uint4*)xs[i];
    for (int i = 0; i < 4; i++) encode(fn, &P.mx[i], xs[i], 3, dims, strides, box, CU_TENSOR_MAP_SWIZZLE_128B);
  }
  encode_w(fn, &P.mw[0], d_in[1], 3072);
  encode_w(fn, &P.mw[1], d_in[4], 3072);
  encode_w(fn, &P.mwo[0], d_in[2], 1024);
  encode_w(fn, &P.mwo[1], d_in[6], 1024);
  encode_cs(fn, &P.mcs[0], d_in[1], 3072);
  encode_cs(fn, &P.mcs[1], d_in[4], 3072);
  {
    const cuuint64_t dims[2] = {32, 1024}, strides[1] = {64};
    const cuuint32_t box[2] = {32, 128};
    encode(fn, &P.mwphi, d_in[5], 2, dims, strides, box, CU_TENSOR_MAP_SWIZZLE_64B);
  }
  cudaFuncSetAttribute(fused_kernel, cudaFuncAttributeMaxDynamicSharedMemorySize, SMEM_BYTES);
  fused_kernel<<<NCTA, NTHREADS, SMEM_BYTES, cudaStreamPerThread>>>(P);
}
```

```cpp
#include <cuda_runtime.h>
#include <cuda_bf16.h>
#include <cuda.h>
#include <stdint.h>

namespace {

__device__ __forceinline__ void wgmma_ss_n256(float (&d)[128], uint32_t da, uint32_t db, int sd) {
  asm volatile("{\n.reg .pred p;\n.reg .b64 a, b;\nsetp.ne.b32 p, %130, 0;\nmov.b64 a, {%128, 0x40000040};\nmov.b64 b, {%129, 0x40000040};\n"
    "wgmma.mma_async.sync.aligned.m64n256k16.f32.bf16.bf16 {%0,%1,%2,%3,%4,%5,%6,%7,%8,%9,%10,%11,%12,%13,%14,%15,%16,%17,%18,%19,%20,%21,%22,%23,%24,%25,%26,%27,%28,%29,%30,%31,%32,%33,%34,%35,%36,%37,%38,%39,%40,%41,%42,%43,%44,%45,%46,%47,%48,%49,%50,%51,%52,%53,%54,%55,%56,%57,%58,%59,%60,%61,%62,%63,%64,%65,%66,%67,%68,%69,%70,%71,%72,%73,%74,%75,%76,%77,%78,%79,%80,%81,%82,%83,%84,%85,%86,%87,%88,%89,%90,%91,%92,%93,%94,%95,%96,%97,%98,%99,%100,%101,%102,%103,%104,%105,%106,%107,%108,%109,%110,%111,%112,%113,%114,%115,%116,%117,%118,%119,%120,%121,%122,%123,%124,%125,%126,%127}, a, b, p, 1, 1, 0, 1;\n}\n"
    : "+f"(d[0]),"+f"(d[1]),"+f"(d[2]),"+f"(d[3]),"+f"(d[4]),"+f"(d[5]),"+f"(d[6]),"+f"(d[7]),"+f"(d[8]),"+f"(d[9]),"+f"(d[10]),"+f"(d[11]),"+f"(d[12]),"+f"(d[13]),"+f"(d[14]),"+f"(d[15]),"+f"(d[16]),"+f"(d[17]),"+f"(d[18]),"+f"(d[19]),"+f"(d[20]),"+f"(d[21]),"+f"(d[22]),"+f"(d[23]),"+f"(d[24]),"+f"(d[25]),"+f"(d[26]),"+f"(d[27]),"+f"(d[28]),"+f"(d[29]),"+f"(d[30]),"+f"(d[31]),"+f"(d[32]),"+f"(d[33]),"+f"(d[34]),"+f"(d[35]),"+f"(d[36]),"+f"(d[37]),"+f"(d[38]),"+f"(d[39]),"+f"(d[40]),"+f"(d[41]),"+f"(d[42]),"+f"(d[43]),"+f"(d[44]),"+f"(d[45]),"+f"(d[46]),"+f"(d[47]),"+f"(d[48]),"+f"(d[49]),"+f"(d[50]),"+f"(d[51]),"+f"(d[52]),"+f"(d[53]),"+f"(d[54]),"+f"(d[55]),"+f"(d[56]),"+f"(d[57]),"+f"(d[58]),"+f"(d[59]),"+f"(d[60]),"+f"(d[61]),"+f"(d[62]),"+f"(d[63]),"+f"(d[64]),"+f"(d[65]),"+f"(d[66]),"+f"(d[67]),"+f"(d[68]),"+f"(d[69]),"+f"(d[70]),"+f"(d[71]),"+f"(d[72]),"+f"(d[73]),"+f"(d[74]),"+f"(d[75]),"+f"(d[76]),"+f"(d[77]),"+f"(d[78]),"+f"(d[79]),"+f"(d[80]),"+f"(d[81]),"+f"(d[82]),"+f"(d[83]),"+f"(d[84]),"+f"(d[85]),"+f"(d[86]),"+f"(d[87]),"+f"(d[88]),"+f"(d[89]),"+f"(d[90]),"+f"(d[91]),"+f"(d[92]),"+f"(d[93]),"+f"(d[94]),"+f"(d[95]),"+f"(d[96]),"+f"(d[97]),"+f"(d[98]),"+f"(d[99]),"+f"(d[100]),"+f"(d[101]),"+f"(d[102]),"+f"(d[103]),"+f"(d[104]),"+f"(d[105]),"+f"(d[106]),"+f"(d[107]),"+f"(d[108]),"+f"(d[109]),"+f"(d[110]),"+f"(d[111]),"+f"(d[112]),"+f"(d[113]),"+f"(d[114]),"+f"(d[115]),"+f"(d[116]),"+f"(d[117]),"+f"(d[118]),"+f"(d[119]),"+f"(d[120]),"+f"(d[121]),"+f"(d[122]),"+f"(d[123]),"+f"(d[124]),"+f"(d[125]),"+f"(d[126]),"+f"(d[127])
    : "r"(da), "r"(db), "r"(sd));
}
__device__ __forceinline__ void wgmma_ss_n128(float (&d)[64], uint32_t da, uint32_t db, int sd) {
  asm volatile("{\n.reg .pred p;\n.reg .b64 a, b;\nsetp.ne.b32 p, %66, 0;\nmov.b64 a, {%64, 0x40000040};\nmov.b64 b, {%65, 0x40000040};\n"
    "wgmma.mma_async.sync.aligned.m64n128k16.f32.bf16.bf16 {%0,%1,%2,%3,%4,%5,%6,%7,%8,%9,%10,%11,%12,%13,%14,%15,%16,%17,%18,%19,%20,%21,%22,%23,%24,%25,%26,%27,%28,%29,%30,%31,%32,%33,%34,%35,%36,%37,%38,%39,%40,%41,%42,%43,%44,%45,%46,%47,%48,%49,%50,%51,%52,%53,%54,%55,%56,%57,%58,%59,%60,%61,%62,%63}, a, b, p, 1, 1, 0, 1;\n}\n"
    : "+f"(d[0]),"+f"(d[1]),"+f"(d[2]),"+f"(d[3]),"+f"(d[4]),"+f"(d[5]),"+f"(d[6]),"+f"(d[7]),"+f"(d[8]),"+f"(d[9]),"+f"(d[10]),"+f"(d[11]),"+f"(d[12]),"+f"(d[13]),"+f"(d[14]),"+f"(d[15]),"+f"(d[16]),"+f"(d[17]),"+f"(d[18]),"+f"(d[19]),"+f"(d[20]),"+f"(d[21]),"+f"(d[22]),"+f"(d[23]),"+f"(d[24]),"+f"(d[25]),"+f"(d[26]),"+f"(d[27]),"+f"(d[28]),"+f"(d[29]),"+f"(d[30]),"+f"(d[31]),"+f"(d[32]),"+f"(d[33]),"+f"(d[34]),"+f"(d[35]),"+f"(d[36]),"+f"(d[37]),"+f"(d[38]),"+f"(d[39]),"+f"(d[40]),"+f"(d[41]),"+f"(d[42]),"+f"(d[43]),"+f"(d[44]),"+f"(d[45]),"+f"(d[46]),"+f"(d[47]),"+f"(d[48]),"+f"(d[49]),"+f"(d[50]),"+f"(d[51]),"+f"(d[52]),"+f"(d[53]),"+f"(d[54]),"+f"(d[55]),"+f"(d[56]),"+f"(d[57]),"+f"(d[58]),"+f"(d[59]),"+f"(d[60]),"+f"(d[61]),"+f"(d[62]),"+f"(d[63])
    : "r"(da), "r"(db), "r"(sd));
}
__device__ __forceinline__ void wgmma_so_n128(float (&d)[64], uint32_t da, uint32_t db, int sd) {
  asm volatile("{\n.reg .pred p;\n.reg .b64 a, b;\nsetp.ne.b32 p, %66, 0;\nmov.b64 a, {%64, 0x80000040};\nmov.b64 b, {%65, 0x40000040};\n"
    "wgmma.mma_async.sync.aligned.m64n128k16.f32.bf16.bf16 {%0,%1,%2,%3,%4,%5,%6,%7,%8,%9,%10,%11,%12,%13,%14,%15,%16,%17,%18,%19,%20,%21,%22,%23,%24,%25,%26,%27,%28,%29,%30,%31,%32,%33,%34,%35,%36,%37,%38,%39,%40,%41,%42,%43,%44,%45,%46,%47,%48,%49,%50,%51,%52,%53,%54,%55,%56,%57,%58,%59,%60,%61,%62,%63}, a, b, p, 1, 1, 0, 1;\n}\n"
    : "+f"(d[0]),"+f"(d[1]),"+f"(d[2]),"+f"(d[3]),"+f"(d[4]),"+f"(d[5]),"+f"(d[6]),"+f"(d[7]),"+f"(d[8]),"+f"(d[9]),"+f"(d[10]),"+f"(d[11]),"+f"(d[12]),"+f"(d[13]),"+f"(d[14]),"+f"(d[15]),"+f"(d[16]),"+f"(d[17]),"+f"(d[18]),"+f"(d[19]),"+f"(d[20]),"+f"(d[21]),"+f"(d[22]),"+f"(d[23]),"+f"(d[24]),"+f"(d[25]),"+f"(d[26]),"+f"(d[27]),"+f"(d[28]),"+f"(d[29]),"+f"(d[30]),"+f"(d[31]),"+f"(d[32]),"+f"(d[33]),"+f"(d[34]),"+f"(d[35]),"+f"(d[36]),"+f"(d[37]),"+f"(d[38]),"+f"(d[39]),"+f"(d[40]),"+f"(d[41]),"+f"(d[42]),"+f"(d[43]),"+f"(d[44]),"+f"(d[45]),"+f"(d[46]),"+f"(d[47]),"+f"(d[48]),"+f"(d[49]),"+f"(d[50]),"+f"(d[51]),"+f"(d[52]),"+f"(d[53]),"+f"(d[54]),"+f"(d[55]),"+f"(d[56]),"+f"(d[57]),"+f"(d[58]),"+f"(d[59]),"+f"(d[60]),"+f"(d[61]),"+f"(d[62]),"+f"(d[63])
    : "r"(da), "r"(db), "r"(sd));
}
__device__ __forceinline__ void wgmma_ss_n40_tt(float (&d)[20], uint32_t da, uint32_t db, int sd) {
  asm volatile("{\n.reg .pred p;\n.reg .b64 a, b;\nsetp.ne.b32 p, %22, 0;\nmov.b64 a, {%20, 0x40000040};\nmov.b64 b, {%21, 0x8};\n"
    "wgmma.mma_async.sync.aligned.m64n40k16.f32.bf16.bf16 {%0,%1,%2,%3,%4,%5,%6,%7,%8,%9,%10,%11,%12,%13,%14,%15,%16,%17,%18,%19}, a, b, p, 1, 1, 1, 1;\n}\n"
    : "+f"(d[0]),"+f"(d[1]),"+f"(d[2]),"+f"(d[3]),"+f"(d[4]),"+f"(d[5]),"+f"(d[6]),"+f"(d[7]),"+f"(d[8]),"+f"(d[9]),"+f"(d[10]),"+f"(d[11]),"+f"(d[12]),"+f"(d[13]),"+f"(d[14]),"+f"(d[15]),"+f"(d[16]),"+f"(d[17]),"+f"(d[18]),"+f"(d[19])
    : "r"(da), "r"(db), "r"(sd));
}
__device__ __forceinline__ void wgmma_ss_n32(float (&d)[16], uint32_t da, uint32_t db, int sd) {
  asm volatile("{\n.reg .pred p;\n.reg .b64 a, b;\nsetp.ne.b32 p, %18, 0;\nmov.b64 a, {%16, 0x40000040};\nmov.b64 b, {%17, 0x80000020};\n"
    "wgmma.mma_async.sync.aligned.m64n32k16.f32.bf16.bf16 {%0,%1,%2,%3,%4,%5,%6,%7,%8,%9,%10,%11,%12,%13,%14,%15}, a, b, p, 1, 1, 0, 1;\n}\n"
    : "+f"(d[0]),"+f"(d[1]),"+f"(d[2]),"+f"(d[3]),"+f"(d[4]),"+f"(d[5]),"+f"(d[6]),"+f"(d[7]),"+f"(d[8]),"+f"(d[9]),"+f"(d[10]),"+f"(d[11]),"+f"(d[12]),"+f"(d[13]),"+f"(d[14]),"+f"(d[15])
    : "r"(da), "r"(db), "r"(sd));
}
__device__ __forceinline__ void wgmma_rs_n40(float (&d)[20], uint32_t a0, uint32_t a1, uint32_t a2, uint32_t a3, uint32_t db, int sd) {
  asm volatile("{\n.reg .pred p;\n.reg .b64 b;\nsetp.ne.b32 p, %25, 0;\nmov.b64 b, {%24, 0x10};\n"
    "wgmma.mma_async.sync.aligned.m64n40k16.f32.bf16.bf16 {%0,%1,%2,%3,%4,%5,%6,%7,%8,%9,%10,%11,%12,%13,%14,%15,%16,%17,%18,%19}, {%20,%21,%22,%23}, b, p, 1, 1, 1;\n}\n"
    : "+f"(d[0]),"+f"(d[1]),"+f"(d[2]),"+f"(d[3]),"+f"(d[4]),"+f"(d[5]),"+f"(d[6]),"+f"(d[7]),"+f"(d[8]),"+f"(d[9]),"+f"(d[10]),"+f"(d[11]),"+f"(d[12]),"+f"(d[13]),"+f"(d[14]),"+f"(d[15]),"+f"(d[16]),"+f"(d[17]),"+f"(d[18]),"+f"(d[19])
    : "r"(a0), "r"(a1), "r"(a2), "r"(a3), "r"(db), "r"(sd));
}
__device__ __forceinline__ void wgmma_r1_n256(float (&d)[128], uint32_t da, uint32_t db, int sd) {
  asm volatile("{\n.reg .pred p;\n.reg .b64 a, b;\nsetp.ne.b32 p, %130, 0;\nmov.b64 a, {%128, 0x8};\nmov.b64 b, {%129, 0x6};\n"
    "wgmma.mma_async.sync.aligned.m64n256k16.f32.bf16.bf16 {%0,%1,%2,%3,%4,%5,%6,%7,%8,%9,%10,%11,%12,%13,%14,%15,%16,%17,%18,%19,%20,%21,%22,%23,%24,%25,%26,%27,%28,%29,%30,%31,%32,%33,%34,%35,%36,%37,%38,%39,%40,%41,%42,%43,%44,%45,%46,%47,%48,%49,%50,%51,%52,%53,%54,%55,%56,%57,%58,%59,%60,%61,%62,%63,%64,%65,%66,%67,%68,%69,%70,%71,%72,%73,%74,%75,%76,%77,%78,%79,%80,%81,%82,%83,%84,%85,%86,%87,%88,%89,%90,%91,%92,%93,%94,%95,%96,%97,%98,%99,%100,%101,%102,%103,%104,%105,%106,%107,%108,%109,%110,%111,%112,%113,%114,%115,%116,%117,%118,%119,%120,%121,%122,%123,%124,%125,%126,%127}, a, b, p, 1, 1, 0, 1;\n}\n"
    : "+f"(d[0]),"+f"(d[1]),"+f"(d[2]),"+f"(d[3]),"+f"(d[4]),"+f"(d[5]),"+f"(d[6]),"+f"(d[7]),"+f"(d[8]),"+f"(d[9]),"+f"(d[10]),"+f"(d[11]),"+f"(d[12]),"+f"(d[13]),"+f"(d[14]),"+f"(d[15]),"+f"(d[16]),"+f"(d[17]),"+f"(d[18]),"+f"(d[19]),"+f"(d[20]),"+f"(d[21]),"+f"(d[22]),"+f"(d[23]),"+f"(d[24]),"+f"(d[25]),"+f"(d[26]),"+f"(d[27]),"+f"(d[28]),"+f"(d[29]),"+f"(d[30]),"+f"(d[31]),"+f"(d[32]),"+f"(d[33]),"+f"(d[34]),"+f"(d[35]),"+f"(d[36]),"+f"(d[37]),"+f"(d[38]),"+f"(d[39]),"+f"(d[40]),"+f"(d[41]),"+f"(d[42]),"+f"(d[43]),"+f"(d[44]),"+f"(d[45]),"+f"(d[46]),"+f"(d[47]),"+f"(d[48]),"+f"(d[49]),"+f"(d[50]),"+f"(d[51]),"+f"(d[52]),"+f"(d[53]),"+f"(d[54]),"+f"(d[55]),"+f"(d[56]),"+f"(d[57]),"+f"(d[58]),"+f"(d[59]),"+f"(d[60]),"+f"(d[61]),"+f"(d[62]),"+f"(d[63]),"+f"(d[64]),"+f"(d[65]),"+f"(d[66]),"+f"(d[67]),"+f"(d[68]),"+f"(d[69]),"+f"(d[70]),"+f"(d[71]),"+f"(d[72]),"+f"(d[73]),"+f"(d[74]),"+f"(d[75]),"+f"(d[76]),"+f"(d[77]),"+f"(d[78]),"+f"(d[79]),"+f"(d[80]),"+f"(d[81]),"+f"(d[82]),"+f"(d[83]),"+f"(d[84]),"+f"(d[85]),"+f"(d[86]),"+f"(d[87]),"+f"(d[88]),"+f"(d[89]),"+f"(d[90]),"+f"(d[91]),"+f"(d[92]),"+f"(d[93]),"+f"(d[94]),"+f"(d[95]),"+f"(d[96]),"+f"(d[97]),"+f"(d[98]),"+f"(d[99]),"+f"(d[100]),"+f"(d[101]),"+f"(d[102]),"+f"(d[103]),"+f"(d[104]),"+f"(d[105]),"+f"(d[106]),"+f"(d[107]),"+f"(d[108]),"+f"(d[109]),"+f"(d[110]),"+f"(d[111]),"+f"(d[112]),"+f"(d[113]),"+f"(d[114]),"+f"(d[115]),"+f"(d[116]),"+f"(d[117]),"+f"(d[118]),"+f"(d[119]),"+f"(d[120]),"+f"(d[121]),"+f"(d[122]),"+f"(d[123]),"+f"(d[124]),"+f"(d[125]),"+f"(d[126]),"+f"(d[127])
    : "r"(da), "r"(db), "r"(sd));
}
__device__ __forceinline__ void wgmma_r1_n128(float (&d)[64], uint32_t da, uint32_t db, int sd) {
  asm volatile("{\n.reg .pred p;\n.reg .b64 a, b;\nsetp.ne.b32 p, %66, 0;\nmov.b64 a, {%64, 0x8};\nmov.b64 b, {%65, 0x6};\n"
    "wgmma.mma_async.sync.aligned.m64n128k16.f32.bf16.bf16 {%0,%1,%2,%3,%4,%5,%6,%7,%8,%9,%10,%11,%12,%13,%14,%15,%16,%17,%18,%19,%20,%21,%22,%23,%24,%25,%26,%27,%28,%29,%30,%31,%32,%33,%34,%35,%36,%37,%38,%39,%40,%41,%42,%43,%44,%45,%46,%47,%48,%49,%50,%51,%52,%53,%54,%55,%56,%57,%58,%59,%60,%61,%62,%63}, a, b, p, 1, 1, 0, 1;\n}\n"
    : "+f"(d[0]),"+f"(d[1]),"+f"(d[2]),"+f"(d[3]),"+f"(d[4]),"+f"(d[5]),"+f"(d[6]),"+f"(d[7]),"+f"(d[8]),"+f"(d[9]),"+f"(d[10]),"+f"(d[11]),"+f"(d[12]),"+f"(d[13]),"+f"(d[14]),"+f"(d[15]),"+f"(d[16]),"+f"(d[17]),"+f"(d[18]),"+f"(d[19]),"+f"(d[20]),"+f"(d[21]),"+f"(d[22]),"+f"(d[23]),"+f"(d[24]),"+f"(d[25]),"+f"(d[26]),"+f"(d[27]),"+f"(d[28]),"+f"(d[29]),"+f"(d[30]),"+f"(d[31]),"+f"(d[32]),"+f"(d[33]),"+f"(d[34]),"+f"(d[35]),"+f"(d[36]),"+f"(d[37]),"+f"(d[38]),"+f"(d[39]),"+f"(d[40]),"+f"(d[41]),"+f"(d[42]),"+f"(d[43]),"+f"(d[44]),"+f"(d[45]),"+f"(d[46]),"+f"(d[47]),"+f"(d[48]),"+f"(d[49]),"+f"(d[50]),"+f"(d[51]),"+f"(d[52]),"+f"(d[53]),"+f"(d[54]),"+f"(d[55]),"+f"(d[56]),"+f"(d[57]),"+f"(d[58]),"+f"(d[59]),"+f"(d[60]),"+f"(d[61]),"+f"(d[62]),"+f"(d[63])
    : "r"(da), "r"(db), "r"(sd));
}

__device__ __forceinline__ uint32_t smem_u32(const void* p) { return (uint32_t)__cvta_generic_to_shared(p); }
__device__ __forceinline__ void mbar_init(uint32_t bar, uint32_t cnt) { asm volatile("mbarrier.init.shared::cta.b64 [%0], %1;" ::"r"(bar), "r"(cnt)); }
__device__ __forceinline__ void mbar_expect_tx(uint32_t bar, uint32_t bytes) { asm volatile("mbarrier.arrive.expect_tx.shared::cta.b64 _, [%0], %1;" ::"r"(bar), "r"(bytes) : "memory"); }
__device__ __forceinline__ void mbar_arrive(uint32_t bar) { asm volatile("mbarrier.arrive.shared::cta.b64 _, [%0];" ::"r"(bar) : "memory"); }
__device__ __forceinline__ void mbar_arrive_n(uint32_t bar, uint32_t n) { asm volatile("mbarrier.arrive.shared::cta.b64 _, [%0], %1;" ::"r"(bar), "r"(n) : "memory"); }
__device__ __forceinline__ void mbar_wait(uint32_t bar, uint32_t parity) {
  asm volatile("{\n.reg .pred p;\nLAB_WAIT:\nmbarrier.try_wait.parity.shared::cta.b64 p, [%0], %1;\n@p bra DONE;\nbra LAB_WAIT;\nDONE:\n}" ::"r"(bar), "r"(parity) : "memory");
}
__device__ __forceinline__ void mbar_wait2(uint32_t a, uint32_t pa, uint32_t b, uint32_t pb) {
  asm volatile("{\n.reg .pred p, q;\nLAB_WAIT:\nmbarrier.try_wait.parity.shared::cta.b64 p, [%0], %1;\nmbarrier.try_wait.parity.shared::cta.b64 q, [%2], %3;\n"
               "and.pred p, p, q;\n@p bra DONE;\nbra LAB_WAIT;\nDONE:\n}" ::"r"(a), "r"(pa), "r"(b), "r"(pb) : "memory");
}
__device__ __forceinline__ void mbar_wait3(uint32_t a, uint32_t pa, uint32_t b, uint32_t pb) {
  asm volatile("{\n.reg .pred p, q, r;\nLAB_WAIT:\nmbarrier.try_wait.parity.shared::cta.b64 p, [%0], %1;\nmbarrier.try_wait.parity.shared::cta.b64 q, [%2], %3;\n"
               "mbarrier.try_wait.parity.shared::cta.b64 r, [%2+8], %3;\nand.pred p, p, q;\nand.pred p, p, r;\n@p bra DONE;\nbra LAB_WAIT;\nDONE:\n}" ::"r"(a), "r"(pa), "r"(b), "r"(pb) : "memory");
}
__device__ __forceinline__ bool mbar_probe2(uint32_t a, uint32_t pa, uint32_t b, uint32_t pb) {
  uint32_t ok;
  asm volatile("{\n.reg .pred p, q;\nmbarrier.test_wait.parity.shared::cta.b64 p, [%1], %2;\nmbarrier.test_wait.parity.shared::cta.b64 q, [%3], %4;\n"
               "and.pred p, p, q;\nselp.u32 %0, 1, 0, p;\n}" : "=r"(ok) : "r"(a), "r"(pa), "r"(b), "r"(pb) : "memory");
  return ok != 0;
}
__device__ __forceinline__ void tma_load_3d(uint32_t dst, const CUtensorMap* tm, uint32_t bar, int c0, int c1, int c2) {
  asm volatile("cp.async.bulk.tensor.3d.shared::cluster.global.mbarrier::complete_tx::bytes [%0], [%1, {%3, %4, %5}], [%2];"
               ::"r"(dst), "l"(tm), "r"(bar), "r"(c0), "r"(c1), "r"(c2) : "memory");
}
__device__ __forceinline__ void tma_load_2d(uint32_t dst, const CUtensorMap* tm, uint32_t bar, int c0, int c1) {
  asm volatile("cp.async.bulk.tensor.2d.shared::cluster.global.mbarrier::complete_tx::bytes [%0], [%1, {%3, %4}], [%2];"
               ::"r"(dst), "l"(tm), "r"(bar), "r"(c0), "r"(c1) : "memory");
}
__device__ __forceinline__ void tma_prefetch_3d(const CUtensorMap* tm, int c0, int c1, int c2) {
  asm volatile("cp.async.bulk.prefetch.tensor.3d.L2.global [%0, {%1, %2, %3}];" ::"l"(tm), "r"(c0), "r"(c1), "r"(c2) : "memory");
}
__device__ __forceinline__ void bulk_load(uint32_t dst, const void* g, uint32_t bytes, uint32_t bar) {
  asm volatile("cp.async.bulk.shared::cluster.global.mbarrier::complete_tx::bytes [%0], [%1], %2, [%3];" ::"r"(dst), "l"(g), "r"(bytes), "r"(bar) : "memory");
}
__device__ __forceinline__ void prefetch_map(const CUtensorMap* tm) { asm volatile("prefetch.tensormap [%0];" ::"l"(tm) : "memory"); }
__device__ __forceinline__ void fence_async_smem() { asm volatile("fence.proxy.async.shared::cta;" ::: "memory"); }
__device__ __forceinline__ void fence_async_global() { asm volatile("fence.proxy.async.global;" ::: "memory"); }
__device__ __forceinline__ void fence_gpu() { asm volatile("fence.release.gpu;" ::: "memory"); }
__device__ __forceinline__ void st_flag(unsigned* p, unsigned v) { asm volatile("st.relaxed.gpu.global.u32 [%0], %1;" ::"l"(p), "r"(v) : "memory"); }
__device__ __forceinline__ unsigned ld_flag(const unsigned* p) { unsigned v; asm volatile("ld.relaxed.gpu.global.u32 %0, [%1];" : "=r"(v) : "l"(p) : "memory"); return v; }
__device__ __forceinline__ uint4 ldcg4(const void* p) { uint4 v; asm volatile("ld.global.cg.v4.u32 {%0,%1,%2,%3}, [%4];" : "=r"(v.x), "=r"(v.y), "=r"(v.z), "=r"(v.w) : "l"(p)); return v; }
__device__ __forceinline__ uint4 ld_pkt(const uint4* p) {
  uint4 v; asm volatile("{\n.reg .b128 t;\nld.relaxed.gpu.global.b128 t, [%4];\nmov.b128 {%0,%1,%2,%3}, t;\n}" : "=r"(v.x), "=r"(v.y), "=r"(v.z), "=r"(v.w) : "l"(p) : "memory"); return v;
}
__device__ __forceinline__ void st_pkt(uint4* p, uint32_t a, uint32_t b, uint32_t c, uint32_t tag) {
  asm volatile("{\n.reg .b128 t;\nmov.b128 t, {%1,%2,%3,%4};\nst.relaxed.gpu.global.b128 [%0], t;\n}" ::"l"(p), "r"(a), "r"(b), "r"(c), "r"(tag) : "memory");
}
__device__ __forceinline__ void st_v4(uint4* p, uint32_t a, uint32_t b, uint32_t c, uint32_t d) { asm volatile("st.relaxed.gpu.global.v4.u32 [%0], {%1,%2,%3,%4};" ::"l"(p), "r"(a), "r"(b), "r"(c), "r"(d) : "memory"); }
__device__ __forceinline__ void sts32(uint32_t addr, uint32_t a) { asm volatile("st.shared.u32 [%0], %1;" ::"r"(addr), "r"(a) : "memory"); }
__device__ __forceinline__ void sts64(uint32_t addr, uint32_t a, uint32_t b) { asm volatile("st.shared.v2.u32 [%0], {%1,%2};" ::"r"(addr), "r"(a), "r"(b) : "memory"); }
__device__ __forceinline__ uint32_t mul2(uint32_t a, uint32_t b) { uint32_t r; asm("mul.rn.bf16x2 %0, %1, %2;" : "=r"(r) : "r"(a), "r"(b)); return r; }
__device__ __forceinline__ uint32_t add2(uint32_t a, uint32_t b) { uint32_t r; asm("add.rn.bf16x2 %0, %1, %2;" : "=r"(r) : "r"(a), "r"(b)); return r; }
__device__ __forceinline__ bool elect() {
  uint32_t p; asm volatile("{\n.reg .pred q;\nelect.sync _|q, 0xffffffff;\nselp.u32 %0, 1, 0, q;\n}" : "=r"(p)); return p != 0;
}
__device__ __forceinline__ void wgmma_fence() { asm volatile("wgmma.fence.sync.aligned;" ::: "memory"); }
__device__ __forceinline__ void wgmma_commit() { asm volatile("wgmma.commit_group.sync.aligned;" ::: "memory"); }
template <int N> __device__ __forceinline__ void wgmma_wait() { asm volatile("wgmma.wait_group.sync.aligned %0;" ::"n"(N) : "memory"); }
template <int N> __device__ __forceinline__ void fence_regs(float (&d)[N]) {
#pragma unroll
  for (int i = 0; i < N; i++) asm volatile("" : "+f"(d[i])::"memory");
}
template <int R> __device__ __forceinline__ void reg_alloc() { asm volatile("setmaxnreg.inc.sync.aligned.u32 %0;" ::"n"(R)); }
template <int R> __device__ __forceinline__ void reg_dealloc() { asm volatile("setmaxnreg.dec.sync.aligned.u32 %0;" ::"n"(R)); }
__device__ __forceinline__ void wg_bar(int w) { asm volatile("bar.sync %0, 128;" ::"r"(w + 1) : "memory"); }
__device__ __forceinline__ constexpr uint32_t desc_lo(uint32_t addr, uint32_t lbo) { return (addr >> 4) + ((lbo >> 4) << 16); }
__device__ __forceinline__ uint32_t pack2(float lo, float hi) { uint32_t r; asm("cvt.rn.bf16x2.f32 %0, %1, %2;" : "=r"(r) : "f"(hi), "f"(lo)); return r; }
__device__ __forceinline__ float lo16(uint32_t v) { return __uint_as_float(v << 16); }
__device__ __forceinline__ float hi16(uint32_t v) { return __uint_as_float(v & 0xFFFF0000u); }
__device__ __forceinline__ float ex2(float x) { float r; asm("ex2.approx.ftz.f32 %0, %1;" : "=f"(r) : "f"(x)); return r; }
__device__ __forceinline__ float rcp(float x) { float r; asm("rcp.approx.ftz.f32 %0, %1;" : "=f"(r) : "f"(x)); return r; }
__device__ __forceinline__ uint32_t movm(uint32_t a) { uint32_t d; asm volatile("movmatrix.sync.aligned.m8n8.trans.b16 %0, %1;" : "=r"(d) : "r"(a)); return d; }
__device__ __forceinline__ void stsm4(uint32_t addr, uint32_t a, uint32_t b, uint32_t c, uint32_t d) {
  asm volatile("stmatrix.sync.aligned.m8n8.x4.shared.b16 [%0], {%1,%2,%3,%4};" ::"r"(addr), "r"(a), "r"(b), "r"(c), "r"(d) : "memory");
}
__device__ __forceinline__ void ldsm4(uint32_t addr, uint32_t (&r)[4]) {
  asm volatile("ldmatrix.sync.aligned.m8n8.x4.shared.b16 {%0,%1,%2,%3}, [%4];" : "=r"(r[0]), "=r"(r[1]), "=r"(r[2]), "=r"(r[3]) : "r"(addr) : "memory");
}
__device__ __forceinline__ void sts128(uint32_t addr, uint32_t a, uint32_t b, uint32_t c, uint32_t d) {
  asm volatile("st.shared.v4.u32 [%0], {%1,%2,%3,%4};" ::"r"(addr), "r"(a), "r"(b), "r"(c), "r"(d) : "memory");
}
__device__ __forceinline__ void lds128(uint32_t addr, uint32_t& a, uint32_t& b, uint32_t& c, uint32_t& d) {
  asm volatile("ld.shared.v4.u32 {%0,%1,%2,%3}, [%4];" : "=r"(a), "=r"(b), "=r"(c), "=r"(d) : "r"(addr) : "memory");
}
__device__ __forceinline__ float lds32f(uint32_t addr) { float v; asm volatile("ld.shared.f32 %0, [%1];" : "=f"(v) : "r"(addr) : "memory"); return v; }
__device__ __forceinline__ float2 lds64f(uint32_t addr) { float2 v; asm volatile("ld.shared.v2.f32 {%0,%1}, [%2];" : "=f"(v.x), "=f"(v.y) : "r"(addr) : "memory"); return v; }
__device__ __forceinline__ void mma16816(float (&d)[4], uint32_t a0, uint32_t a1, uint32_t a2, uint32_t a3, uint32_t b0, uint32_t b1) {
  asm("mma.sync.aligned.m16n8k16.row.col.f32.bf16.bf16.f32 {%0,%1,%2,%3}, {%4,%5,%6,%7}, {%8,%9}, {%0,%1,%2,%3};"
      : "+f"(d[0]), "+f"(d[1]), "+f"(d[2]), "+f"(d[3]) : "r"(a0), "r"(a1), "r"(a2), "r"(a3), "r"(b0), "r"(b1));
}
__device__ __forceinline__ void mma1688(float (&d)[4], uint32_t a0, uint32_t a1, uint32_t b0) {
  asm("mma.sync.aligned.m16n8k8.row.col.f32.bf16.bf16.f32 {%0,%1,%2,%3}, {%4,%5}, {%6}, {%0,%1,%2,%3};"
      : "+f"(d[0]), "+f"(d[1]), "+f"(d[2]), "+f"(d[3]) : "r"(a0), "r"(a1), "r"(b0));
}

__device__ __forceinline__ float qsum(float v) { v += __shfl_xor_sync(0xffffffffu, v, 1); v += __shfl_xor_sync(0xffffffffu, v, 2); return v; }

constexpr int NCTA = 132;
#define NB_ 6
#define NA_ 5
constexpr int NB = NB_;
constexpr int NA = NA_;
constexpr uint32_t SLOT = 16384;
constexpr uint32_t SB = 1024;
constexpr uint32_t OFF_B = 0;
constexpr uint32_t OFF_A = NB * SLOT;
constexpr uint32_t OFF_S = OFF_A + NA * SLOT;
constexpr uint32_t OFF_T = OFF_S + 20480;
constexpr uint32_t OFF_CS = OFF_T + 24576;
constexpr uint32_t OFF_MR = OFF_CS + 4640;
constexpr uint32_t OFF_BAR = OFF_MR + 512;
constexpr uint32_t OFF_MA = OFF_S, OFF_MB = OFF_CS - 2048;
constexpr uint32_t BAR_FULLB = OFF_BAR;
constexpr uint32_t BAR_FULLA = BAR_FULLB + 64;
constexpr uint32_t BAR_EMPTYB = BAR_FULLA + 64;
constexpr uint32_t BAR_EMPTYA = BAR_EMPTYB + 64;
constexpr uint32_t BAR_SIGP = BAR_EMPTYA + 64;
constexpr uint32_t BAR_SIGT = BAR_SIGP + 32;
constexpr uint32_t BAR_STAT = BAR_SIGP + 64;
constexpr uint32_t BAR_HALO = BAR_STAT + 16;
constexpr uint32_t BAR_CS = BAR_HALO + 8;
constexpr uint32_t BAR_WPHI = BAR_CS + 16;
constexpr uint32_t BAR_KV = BAR_WPHI + 8;
constexpr uint32_t BAR_STG = BAR_KV + 16;
constexpr uint32_t BAR_EPOCH = BAR_STG + 48;
constexpr uint32_t OFF_EPOCH = OFF_BAR + 7 * 64;
static_assert(BAR_EPOCH < OFF_EPOCH, "barriers");
constexpr uint32_t SMEM_BYTES = OFF_EPOCH + 8;
static_assert(SMEM_BYTES <= 232448 && NB % 2 == 0 && NB <= 8 && NA <= 6, "smem");

#define CREGS 208
#define PREGS 88
#define PF0 14
#define PFS 8
#define PRE_A 2
#define PRE_B 4
#define CSB 4
#define CSNEED 0xF003u
#define XR 2
#define PS0 2
#define PS1 2
#define PSW 0
#define STG0 0
#define QORD 1
#define KSPLIT 12
#define KEEP 16
#define NJ 3
#define LEAD 0
#define KSL 1000
#define PSL 0
#define KVS 10
#define RH 0
#define D2 2000
#define D3 1500
#define KB 8
#define PNX 2
#define PNO 2
#define DEFER 3
#define DEFL 2
#define TSK 3
#define TSL 3
constexpr int NTHREADS = 384;

struct Params {
  CUtensorMap mx[4];
  CUtensorMap mw[2];
  CUtensorMap mwo[2];
  CUtensorMap mcs[2];
  CUtensorMap mwphi;
  uint4* xp[5];
};

__device__ __align__(256) uint4 g_o[16][16][1024];
__device__ __align__(256) uint4 g_wf[2][8][16][1024];
__device__ __align__(256) uint4 g_stats[16][2][8][32];
__device__ __align__(256) uint4 g_halo[16][8][2][256];
__device__ __align__(256) float g_cs[2][2][3072];
__device__ __align__(256) uint4 g_kvpart[8][16][2][544];
__device__ __align__(256) uint4 g_kvfin[8][16][80];
__device__ __align__(256) unsigned g_xflag[4][2][16][32];
__device__ __align__(256) unsigned g_oflag[4][2][16][32];
__device__ __align__(256) unsigned g_hflag[2][16][8][32];
__device__ __align__(256) unsigned g_kvfflag[2][8][2][32];
__device__ __align__(256) unsigned g_csflag[2][8][32];
__device__ __align__(256) unsigned g_kflag[8][32];
__device__ unsigned g_ctr;
__device__ __forceinline__ unsigned vblock() {
  unsigned s;
  asm volatile("mov.u32 %0, %%smid;" : "=r"(s));
  const unsigned r = s & 1;
  s >>= 1;
  const unsigned t = s - 32, q = (t * 37) >> 8;
  const unsigned hi = s < 60 ? 12 + (t - 7 * q) * 8 + q : (s < 62 ? s + 4 : s - 58);
  return __shfl_sync(0xffffffffu, 2 * (s < 32 ? (s & 7) * 8 + (s >> 3) : hi) + r, 0);
}
#define TS(who, id) do {} while (0)
#define TSW(id) do {} while (0)

__device__ __forceinline__ int cta_m(unsigned b) { return ((b >> 2) & 12) | (b & 3); }
__device__ __forceinline__ int cta_j(unsigned b) { return ((b >> 2) & 3) | ((b >> 4) & 4); }
struct Ring { uint32_t s, ph; };
template <int N> __device__ __forceinline__ void adv(Ring& r) { if (++r.s == N) { r.s = 0; r.ph ^= 1; } }
template <int N> __device__ __forceinline__ void rewind2(Ring& r) { if (r.s < 2) { r.s += N - 2; r.ph ^= 1; } else r.s -= 2; }
__device__ __forceinline__ int other_tile(int t, int j) { return (t == (j | 4) ? 7 : t) ^ (~j & 4); }
__device__ __forceinline__ int q_order(int i, int j) { return 2 * (i >= 14 ? j : other_tile(i >> 1, j)) + (i & 1); }
__device__ __forceinline__ int o_order(int i, int j) {
  if (i < 2) return 2 * j + i;
  const int odd = i >= 9;
  return 2 * other_tile(i - 2 - 7 * odd, j) + odd;
}
__device__ __forceinline__ int kv_order(int i, int j, int L) { return L > 0 ? o_order(i, j) : (i + 14 + 2 * (j & 4)) & 15; }

__device__ __forceinline__ unsigned poll_flags(const unsigned* f, int n, unsigned need, unsigned tag) {
  const int lane = threadIdx.x & 31;
  unsigned mask; int it = 0;
  do {
    unsigned v = lane < n ? ld_flag(f + lane) : 0u;
    mask = __ballot_sync(0xffffffffu, lane < n && v == tag);
    if (++it > (1 << 22)) __trap();
  } while ((mask & need) != need);
  fence_async_global();
  return mask;
}
template <bool WAIT = true>
__device__ __forceinline__ unsigned get_tag(uint32_t sb) {
  if (WAIT) mbar_wait(sb + BAR_EPOCH, 0);
  unsigned t; asm volatile("ld.shared.u32 %0, [%1];" : "=r"(t) : "r"(sb + OFF_EPOCH) : "memory");
  return t;
}

__device__ __forceinline__ int lane_id() { int l; asm volatile("mov.u32 %0, %%laneid;" : "=r"(l)); return l; }
__device__ __forceinline__ unsigned seq4(unsigned tag, int L) { return 8u | ((tag & 1u) << 2) | (unsigned)L; }
constexpr float LOG2E = 1.4426950408889634f;

__device__ __forceinline__ void sched_fence(uint32_t sb) { mbar_wait(sb + BAR_EPOCH, 0); }
struct Ctx {
  static constexpr uint32_t sb = SB;
  uint32_t ab, da0;
  int w, warp, lane, g, c;
  int goff;
  __device__ __forceinline__ int m() const { return goff >> 14; }
  __device__ __forceinline__ int j() const { return (goff >> 4) & 7; }
  bool elected;
  Ring ra, rb;
  uint32_t pa, pb;
  uint32_t mrow, mxor, mhi;
  __device__ __forceinline__ uint32_t aslot(uint32_t s) const { return ab + s * SLOT; }
  __device__ __forceinline__ uint32_t fullA(uint32_t s) const { return sb + BAR_FULLA + s * 8; }
  __device__ __forceinline__ uint32_t fullB(uint32_t s) const { return sb + BAR_FULLB + s * 8; }
  __device__ __forceinline__ void releaseA(uint32_t s) const { if (elected) mbar_arrive(sb + BAR_EMPTYA + s * 8); }
  __device__ __forceinline__ void releaseB(uint32_t s) const { if (elected) mbar_arrive(sb + BAR_EMPTYB + s * 8); }
  __device__ __forceinline__ uint32_t maddr(uint32_t tile, uint32_t ch) const { return tile + mrow + (((ch + mhi) ^ mxor) << 4); }
  __device__ __forceinline__ uint4* oimg(int hp) const { return &g_o[m()][2 * j() + hp][w * 512 + warp * 128]; }
  __device__ __forceinline__ uint32_t held(int i) const { return ra.s + i < 2 ? ra.s + i + NA - 2 : ra.s + i - 2; }
};

template <int N, bool FIRST, bool O = false>
__device__ __forceinline__ void gemm_issue(float (&acc)[N / 2], Ctx& x, bool ready = false) {
  if (!ready) {
    if (N == 256) mbar_wait3(x.fullA(x.ra.s), x.ra.ph, x.fullB(x.rb.s), x.rb.ph);
    else mbar_wait2(x.fullA(x.ra.s), x.ra.ph, x.fullB(x.rb.s), x.rb.ph);
  }
  const uint32_t da = x.da0 + x.ra.s * (SLOT / 16), db = desc_lo(SB + OFF_B, 8192) + x.rb.s * (SLOT / 16);
  wgmma_fence();
#pragma unroll
  for (int k = 0; k < 4; k++) {
    if constexpr (N == 256) wgmma_ss_n256(acc, da + 2 * k, db + 128 * k, !(FIRST && k == 0));
    else if constexpr (O) wgmma_so_n128(acc, da + (k >> 1) * 32 + (k & 1) * 2, db + 128 * k, 1);
    else wgmma_ss_n128(acc, da + 2 * k, db + 128 * k, !(FIRST && k == 0));
  }
  wgmma_commit();
}
template <int N>
__device__ __forceinline__ void gemm_next(Ctx& x) {
  x.pa = x.ra.s; x.pb = x.rb.s;
  if (N == 256) x.rb.s++;
  adv<NA>(x.ra); adv<NB>(x.rb);
}
template <int N>
__device__ __forceinline__ void gemm_release(Ctx& x, bool relA) {
  if (relA) x.releaseA(x.pa);
  x.releaseB(x.pb);
  if (N == 256) x.releaseB(x.pb + 1);
}
template <int N>
__device__ __forceinline__ void gemm_retire(Ctx& x, bool relA) { wgmma_wait<1>(); gemm_release<N>(x, relA); gemm_next<N>(x); }
template <bool O = false>
__device__ __forceinline__ void gemm_run(float (&acc)[64], Ctx& x, int n, int hold, int n4 = 0) {
  bool ready = false;
#pragma unroll 1
  for (; n > 0; n--) {
    gemm_issue<128, false, O>(acc, x, ready);
    const uint32_t pa = x.pa, pb = x.pb;
    gemm_next<128>(x);
    ready = mbar_probe2(x.fullA(x.ra.s), x.ra.ph, x.fullB(x.rb.s), x.rb.ph);
    wgmma_wait<1>();
    if (n > hold) x.releaseA(pa);
    x.releaseB(pb);
  }
}
__device__ __forceinline__ void gemm_end(float (&acc)[64], Ctx& x) { wgmma_wait<0>(); fence_regs(acc); gemm_release<128>(x, false); }

__device__ __forceinline__ void load_x32(float* a, uint32_t tile, uint32_t ch, const Ctx& x) {
#pragma unroll
  for (int p = 0; p < 2; p++) {
    uint32_t v[4];
    ldsm4(x.maddr(tile, ch + 2 * p), v);
#pragma unroll
    for (int i = 0; i < 4; i++) { a[8 * p + 2 * i] = lo16(v[i]); a[8 * p + 2 * i + 1] = hi16(v[i]); }
  }
}

__device__ __forceinline__ void rows_load(uint4* r, uint32_t tile, const Ctx& x) {
#pragma unroll
  for (int q = 0; q < 4; q++) {
    const uint32_t row = x.warp * 16 + 4 * q + (x.lane >> 3);
    lds128(tile + row * 128 + (((x.lane & 7) ^ (row & 7)) << 4), r[q].x, r[q].y, r[q].z, r[q].w);
  }
}
__device__ __forceinline__ void rows_store(const uint4* r, uint4* g, const Ctx& x) {
  g += (x.warp * 16 + (x.lane >> 3)) * 256 + (x.lane & 7);
#pragma unroll
  for (int q = 0; q < 4; q++) g[q * 1024] = r[q];
}
__device__ __forceinline__ void publish(int id, const Ctx& x) { __syncwarp(); if (x.lane == 0) mbar_arrive(x.sb + BAR_SIGP + id * 8); }
__device__ __forceinline__ void tile_out(uint32_t tile, uint4* g, int id, const Ctx& x) {
  uint4 r[4];
  __syncwarp();
  rows_load(r, tile, x); rows_store(r, g, x); publish(id, x);
}

template <int N>
__device__ __forceinline__ void stats_acc(const float* a, float (&t)[4]) {
#pragma unroll
  for (int i = 0; i < N; i++) { t[i & 2] += a[i]; t[(i & 2) + 1] = fmaf(a[i], a[i], t[(i & 2) + 1]); }
}
__device__ __forceinline__ void stats_send(float (&t)[4], int L, const Ctx& x) {
  const unsigned seq = seq4(get_tag<false>(x.sb), L);
#pragma unroll
  for (int q = 0; q < 4; q++) t[q] = qsum(t[q]);
  if (x.c == 0) st_pkt(&g_stats[x.m()][x.w][x.j()][x.warp * 8 + x.g], __float_as_uint(t[0]), __float_as_uint(t[1]), __float_as_uint(t[2]), (__float_as_uint(t[3]) & ~15u) | seq);
}
__device__ __forceinline__ void out_epilogue(const float (&acc)[64], uint4 (&r1)[4], uint4* g, int L, Ctx& x) {
  const uint32_t t0 = x.aslot(x.ra.s), t1 = x.aslot(x.ra.s + 1 == NA ? 0 : x.ra.s + 1);
#pragma unroll
  for (int p = 0; p < 8; p++) {
    stsm4(x.maddr(p < 4 ? t0 : t1, (p & 3) * 2), pack2(acc[8 * p], acc[8 * p + 1]), pack2(acc[8 * p + 2], acc[8 * p + 3]),
          pack2(acc[8 * p + 4], acc[8 * p + 5]), pack2(acc[8 * p + 6], acc[8 * p + 7]));
    if (p == 3) { tile_out(t0, g, 2, x); sched_fence(x.sb); }
  }
  __syncwarp();
  rows_load(r1, t1, x);
  if (L < 3) {
    float t[4] = {0.f, 0.f, 0.f, 0.f}, u[4] = {0.f, 0.f, 0.f, 0.f};
    stats_acc<32>(acc, t); stats_acc<32>(acc + 32, u);
#pragma unroll
    for (int q = 0; q < 4; q++) t[q] += u[q];
    stats_send(t, L + 1, x);
    fence_async_smem();
    asm volatile("bar.sync %0, %1;" ::"r"(L == 1 ? x.w + 1 : 3), "r"(L == 1 ? 128 : 256) : "memory");
  }
}

struct Stats { float rstd0, rstd1; };
__device__ __forceinline__ Stats load_stats(int half, const Ctx& x) {
  const float2 u = lds64f(x.sb + OFF_MR + half * 256 + (x.warp * 8 + x.g) * 8);
  return {u.x, u.y};
}

template <int NK>
__device__ __forceinline__ void hedgehog_scale(float* t, const Stats& st, const uint32_t* keep) {
#pragma unroll
  for (int q = 0; q < 16; q++) t[q] *= ((q & 2) ? st.rstd1 : st.rstd0) * LOG2E;
  float m[4];
#pragma unroll
  for (int q = 0; q < 4; q++) m[q] = fmaxf(fmaxf(fabsf(t[4 * q]), fabsf(t[4 * q + 1])), fmaxf(fabsf(t[4 * q + 2]), fabsf(t[4 * q + 3])));
  if (__builtin_expect(__any_sync(0xffffffffu, fmaxf(fmaxf(m[0], m[1]), fmaxf(m[2], m[3])) > 58.f), 0)) {
    float z[16 + NK];
#pragma unroll
    for (int q = 0; q < 16 + NK; q++) z[q] = q < 16 ? t[q & 15] : __uint_as_float(keep[q & 15]);
#pragma unroll 1
    for (int r = 0; r < 4; r += 2) {
      float hi = -INFINITY, lo = INFINITY;
#pragma unroll 1
      for (int i = 0; i < 16; i++) {
        const int k = (i & 6) * 2 + (i & 1) + r;
        const float v = z[k];
        if (i < 8) { hi = fmaxf(hi, v); lo = fminf(lo, v); }
        else z[k] = v - fminf(fmaxf(v, lo), hi);
        if (i == 7) {
#pragma unroll 1
          for (int d = 1; d <= 2; d++) { hi = fmaxf(hi, __shfl_xor_sync(0xffffffffu, hi, d)); lo = fminf(lo, __shfl_xor_sync(0xffffffffu, lo, d)); }
          const float mid = 0.5f * hi + 0.5f * lo;
          hi = fmaxf(hi - 58.f, mid); lo = fminf(lo + 58.f, mid);
        }
      }
    }
#pragma unroll
    for (int q = 0; q < 16; q++) t[q] = z[q];
  }
}
__device__ __forceinline__ void dual_exp(const float* t, uint32_t (&f)[18], int never) {
  float e[KSPLIT];
#pragma unroll
  for (int q = 0; q < KSPLIT; q++) e[q] = ex2(q < 16 ? t[q] : -t[q & 15]);
  while (never < 0) {
#pragma unroll
    for (int i = 0; i < KSPLIT; i += 4) asm volatile("ld.shared.v4.f32 {%0,%1,%2,%3}, [%4];" : "=f"(e[i]), "=f"(e[i + 1]), "=f"(e[i + 2]), "=f"(e[i + 3]) : "r"(never + i) : "memory");
    never += __float_as_int(e[0]);
  }
#pragma unroll
  for (int q = 0; q < KSPLIT; q += 2) f[q >> 1] = pack2(e[q], e[q + 1]);
#pragma unroll
  for (int q = KSPLIT; q < 32; q += 2) f[q >> 1] = q < 16 ? pack2(ex2(t[q]), ex2(t[q + 1])) : pack2(ex2(-t[q & 15]), ex2(-t[(q & 15) + 1]));
#pragma unroll
  for (int sg = 0; sg < 2; sg++) {
    const uint32_t* u = f + 8 * sg;
    const uint32_t a = add2(add2(u[0], u[2]), add2(u[4], u[6])), b = add2(add2(u[1], u[3]), add2(u[5], u[7]));
    f[16 + sg] = add2(__byte_perm(a, b, 0x5410), __byte_perm(a, b, 0x7632));
  }
}
__device__ __forceinline__ void dual_exp_rcp(const float* t, uint32_t (&f)[16]) {
#pragma unroll
  for (int q = 0; q < 8; q++) {
    const float a = ex2(t[2 * q]), b = ex2(t[2 * q + 1]), r = rcp(a * b);
    f[q] = pack2(a, b); f[8 + q] = pack2(r * b, r * a);
  }
}
__device__ __forceinline__ void cta_bar() { asm volatile("bar.sync 3, 256;" ::: "memory"); }

template <int N> __device__ __forceinline__ void pin(const uint32_t* v, uint32_t addr) {
#pragma unroll
  for (int i = 0; i < N; i += 4)
    asm volatile("{\n.reg .pred p;\nsetp.eq.u32 p, %0, 0;\n@p st.shared.v4.u32 [%0], {%1,%2,%3,%4};\n}" ::"r"(addr), "r"(v[i]), "r"(v[i + 1]), "r"(v[i + 2]), "r"(v[i + 3]) : "memory");
}

__device__ __forceinline__ void consumer(const Params& P, uint32_t sb, int w, unsigned vb) {
  Ctx x;
  x.w = w;
  x.ab = sb + OFF_A + w * 8192; x.da0 = desc_lo(SB + OFF_A, 16) + w * 512;
  x.lane = threadIdx.x & 31; x.warp = __shfl_sync(0xffffffffu, (threadIdx.x >> 5) & 3, 0); x.g = x.lane >> 2; x.c = x.lane & 3;
  x.goff = (cta_m(vb) * 128 + w) * 128 + cta_j(vb) * 16;
  asm volatile("" : "+r"(x.goff));
  x.elected = (threadIdx.x & 127) == 0;
  x.ra = {0, 0}; x.rb = {0, 0}; x.pa = x.pb = 0;
  {
    const uint32_t row = x.warp * 16 + (x.lane & 15);
    x.mrow = row * 128; x.mxor = row & 7; x.mhi = x.lane >> 4;
  }
  const int goff = x.goff;
  uint4 r1[4];
#pragma unroll
  for (int i = 0; i < 4; i++) r1[i] = make_uint4(0, 0, 0, 0);
  TSW(0);
#pragma unroll 1
  for (int L = 0; L < 4; L++) {
    float acc[64];
    constexpr uint32_t dcs = desc_lo(SB + OFF_CS, 0);
    if ((L & 1) == 0) {
    float kv[128];
    gemm_issue<256, true>(kv, x); gemm_next<256>(x);
    {
      int i = 1;
      bool rel = true;
      float t[4] = {0.f, 0.f, 0.f, 0.f};
#pragma unroll 1
      for (int seg = 0; seg < 3; seg++) {
        const int end = seg < 2 ? (L == 0 ? 3 + 2 * (x.j() & 3) + seg : 2 + seg * 2) : 14 + L;
#pragma unroll 1
        while (true) {
          gemm_issue<256, false>(kv, x);
          if (++i == end) break;
          wgmma_wait<1>();
          if (rel) gemm_release<256>(x, true);
          rel = true;
          gemm_next<256>(x);
          if (i == 5) TSW(8 + L * 12);
          if (i == 11) TSW(10 + L * 12);
        }
        if (seg < 2 && L == 0) {
          float a[32];
          const uint32_t tile = x.aslot(x.ra.s);
          load_x32(a, tile, 0, x); load_x32(a + 16, tile, 4, x);
          stats_acc<32>(a, t);
          if (seg == 1) { mbar_wait(sb + BAR_EPOCH, 0); stats_send(t, 0, x); }
          fence_async_smem();
          wg_bar(w);
        }
        if (seg == 1 && L > 0) { rows_store(r1, P.xp[L] + goff + 8, x); publish(3, x); }
        wgmma_wait<1>();
        if (rel) gemm_release<256>(x, true);
        rel = true;
        gemm_next<256>(x);
        if (seg == 0 && L > 0) { wgmma_wait<0>(); gemm_release<256>(x, true); rel = false; }
      }
    }
      const Ring kt = x.ra;
      if (L == 0) adv<NA>(x.ra);
#pragma unroll 1
      for (int h = L; h < 2; h++) {
        float d[16];
        mbar_wait2(x.fullA(kt.s), kt.ph, sb + BAR_WPHI, 0);
        wgmma_fence();
#pragma unroll
        for (int q = 0; q < 2; q++) wgmma_ss_n32(d, x.da0 + kt.s * (SLOT / 16) + h * 4 + q * 2, desc_lo(SB + OFF_S + 4096, 512) + w * 256 + h * 128 + q * 64, q);
        wgmma_commit();
        gemm_issue<256, false>(kv, x);
        gemm_retire<256>(x, true);
        if (h) x.releaseA(kt.s);
        fence_regs(d);
        uint4* dst = &g_wf[1][x.j()][x.m()][w * 512 + (x.warp * 16 + x.g) * 8 + ((h * 4 + x.c) ^ x.g)];
        dst[0] = make_uint4(pack2(d[0], d[1]), pack2(d[4], d[5]), pack2(d[8], d[9]), pack2(d[12], d[13]));
        dst[64] = make_uint4(pack2(d[2], d[3]), pack2(d[6], d[7]), pack2(d[10], d[11]), pack2(d[14], d[15]));
      }
      const uint32_t dm = desc_lo(SB + OFF_MA, 0) + w * 64;
      mbar_wait2(sb + BAR_STAT, 0, sb + BAR_CS, 0);
      wgmma_fence();
      wgmma_r1_n256(kv, dm, dcs + 96, 1);
      wgmma_commit();
      const Stats st = load_stats(w, x);
      wgmma_wait<0>();
      fence_regs(kv);
      gemm_release<256>(x, true);
      TSW(2 + L * 12);
      uint32_t P0[32], P1[32], PH[32];
#pragma unroll
      for (int t = 0; t < 16; t++) { P0[t] = pack2(kv[4 * t] * st.rstd0, kv[4 * t + 1] * st.rstd0); P1[t] = pack2(kv[4 * t + 2] * st.rstd1, kv[4 * t + 3] * st.rstd1); }
      pin<16>(P0, x.mrow + 16);
      {
#pragma unroll
        for (int q = 0; q < 4; q++) sts128((x.warp < 3 ? sb + OFF_T + w * 12288 + x.warp * 4096 : sb + OFF_S + 16384 + w * 2048) + x.lane * 16 + q * 512, P1[4 * q], P1[4 * q + 1], P1[4 * q + 2], P1[4 * q + 3]);
      }
      wgmma_fence();
      wgmma_r1_n128(acc, dm, dcs, 0);
      gemm_issue<128, false>(acc, x); gemm_next<128>(x);
      TSW(3 + L * 12);
#pragma unroll
      for (int s = 0; s < 4; s++) {
#pragma unroll
        for (int t = 16 + 8 * (s & 1); t < 24 + 8 * (s & 1); t++) {
          if (s < 2) P1[t] = movm(pack2(kv[4 * t + 2] * st.rstd1, kv[4 * t + 3] * st.rstd1));
          else P0[t] = movm(pack2(kv[4 * t] * st.rstd0, kv[4 * t + 1] * st.rstd0));
        }
        if (s < 3) { gemm_issue<128, false>(acc, x); gemm_retire<128>(x, true); }
        if (s == 1) {
          if (x.warp < 3) {
#pragma unroll
            for (int q = 4; q < 8; q++) sts128(sb + OFF_T + w * 12288 + x.warp * 4096 + x.lane * 16 + q * 512, P1[4 * q], P1[4 * q + 1], P1[4 * q + 2], P1[4 * q + 3]);
          } else {
            uint4* dst = &g_halo[x.m()][x.j()][w][x.lane];
#pragma unroll
            for (int q = 0; q < 8; q++) dst[q * 32] = make_uint4(P1[4 * q], P1[4 * q + 1], P1[4 * q + 2], P1[4 * q + 3]);
          }
          publish(4, x);
          gemm_issue<128, false>(acc, x);
          gemm_retire<128>(x, true);
        }
      }
      TSW(4 + L * 12);
      gemm_run(acc, x, 10, 0);
      gemm_issue<128, false>(acc, x);
      {
        wg_bar(w);
        uint32_t tr = sb + OFF_T + w * 12288 + (x.warp - 1) * 4096;
        if (x.warp == 0) {
          tr = x.m() > 0 ? sb + OFF_S + 8192 + w * 4096 : tr + 4096;
          if (x.m() > 0) mbar_wait(sb + BAR_HALO, L >> 1);
        }
#pragma unroll
        for (int q = 0; q < 8; q++) lds128(tr + x.lane * 16 + q * 512, PH[4 * q], PH[4 * q + 1], PH[4 * q + 2], PH[4 * q + 3]);
      }
      gemm_retire<128>(x, false);
      gemm_end(acc, x);
      TSW(5 + L * 12);
      const bool first = (x.m() == 0) && (x.warp == 0);
      const bool hi0 = 2 * x.c > x.g, hi1 = 2 * x.c + 1 > x.g;
      const uint32_t mhi = (hi0 ? 0xFFFFu : 0u) | (hi1 ? 0xFFFF0000u : 0u);
      const float sc0 = st.rstd0 * (0.17677669529663687f * LOG2E), sc1 = st.rstd1 * (0.17677669529663687f * LOG2E);
#pragma unroll
      for (int hp = 0; hp < 2; hp++) {
        const uint32_t tile = x.aslot(x.held(hp));
        uint32_t px[2], py[2];
        float s[2][3][4];
#pragma unroll
        for (int u = 0; u < 2; u++) {
#pragma unroll
          for (int q = 0; q < 12; q++) s[u][q >> 2][q & 3] = 0.f;
#pragma unroll
          for (int ks = 0; ks < 2; ks++) {
            const int t = 8 * hp + 4 * u + 2 * ks;
            const uint32_t a0 = pack2(acc[4 * t], acc[4 * t + 1]), a1 = pack2(acc[4 * t + 2], acc[4 * t + 3]);
            const uint32_t a2 = pack2(acc[4 * t + 4], acc[4 * t + 5]), a3 = pack2(acc[4 * t + 6], acc[4 * t + 7]);
            mma16816(s[u][0], a0, a1, a2, a3, PH[t], PH[t + 1]);
            mma16816(s[u][1], a0, a1, a2, a3, P0[t], P0[t + 1]);
            mma16816(s[u][2], a0, a1, a2, a3, P1[t], P1[t + 1]);
          }
        }
        load_x32(acc + 32 * hp, tile, 0, x);
        load_x32(acc + 32 * hp + 16, tile, 4, x);
        float e[2][4], r[2][2];
#pragma unroll
        for (int u = 0; u < 2; u++) {
          e[u][0] = (hi0 ? s[u][0][0] : s[u][1][0]) * sc0; e[u][1] = (hi1 ? s[u][0][1] : s[u][1][1]) * sc0;
          e[u][2] = (hi0 ? s[u][1][2] : s[u][2][2]) * sc1; e[u][3] = (hi1 ? s[u][1][3] : s[u][2][3]) * sc1;
          if (first) { if (hi0) e[u][0] = -1e30f; if (hi1) e[u][1] = -1e30f; }
          r[u][0] = fmaxf(e[u][0], e[u][1]); r[u][1] = fmaxf(e[u][2], e[u][3]);
        }
#pragma unroll
        for (int d = 1; d <= 2; d++)
#pragma unroll
          for (int q = 0; q < 4; q++) r[q >> 1][q & 1] = fmaxf(r[q >> 1][q & 1], __shfl_xor_sync(0xffffffffu, r[q >> 1][q & 1], d));
#pragma unroll
        for (int u = 0; u < 2; u++) {
#pragma unroll
          for (int q = 0; q < 4; q++) e[u][q] = ex2(e[u][q] - r[u][q >> 1]);
          r[u][0] = e[u][0] + e[u][1]; r[u][1] = e[u][2] + e[u][3];
        }
#pragma unroll
        for (int d = 1; d <= 2; d++)
#pragma unroll
          for (int q = 0; q < 4; q++) r[q >> 1][q & 1] += __shfl_xor_sync(0xffffffffu, r[q >> 1][q & 1], d);
#pragma unroll
        for (int u = 0; u < 2; u++) {
          const float rx = rcp(r[u][0]), ry = rcp(r[u][1]);
          px[u] = pack2(e[u][0] * rx, e[u][1] * rx); py[u] = pack2(e[u][2] * ry, e[u][3] * ry);
        }
        uint32_t o[8][2];
#pragma unroll
        for (int q = 0; q < 8; q++) {
          float d[4] = {0.f, 0.f, 0.f, 0.f};
          const int t = 16 + 8 * hp + q, u = q >> 2;
          mma16816(d, px[u] & mhi, 0u, px[u] & ~mhi, py[u] & mhi, PH[t], P0[t]);
          mma1688(d, 0u, py[u] & ~mhi, P1[t]);
          o[q][0] = pack2(d[0], d[1]); o[q][1] = pack2(d[2], d[3]);
        }
#pragma unroll
        for (int q = 0; q < 4; q++)
          stsm4(tile + (x.mrow & ~1023u) + x.mxor * 64 + (q >> 1) * 512 + (((2 * (q & 1) + x.mhi) ^ (x.mxor >> 1)) << 4), o[2 * q][0], o[2 * q][1], o[2 * q + 1][0], o[2 * q + 1][1]);
        __syncwarp();
        uint4 v[4];
#pragma unroll
        for (int q = 0; q < 4; q++) lds128(tile + x.warp * 2048 + q * 512 + x.lane * 16, v[q].x, v[q].y, v[q].z, v[q].w);
#pragma unroll
        for (int q = 0; q < 4; q++) x.oimg(hp)[q * 32 + x.lane] = v[q];
        publish(hp, x);
        if (hp == 0) sched_fence(sb);
      }
    } else {
      float kv[128];
      float (&kv0)[64] = reinterpret_cast<float (&)[64]>(kv[0]);
      float (&kv1)[64] = reinterpret_cast<float (&)[64]>(kv[64]);
      auto mma8 = [&](uint32_t as, uint32_t bs, int i, bool fence) {
        const uint32_t da = desc_lo(SB + OFF_A, 16) + as * (SLOT / 16), db = desc_lo(SB + OFF_B, 8192) + bs * (SLOT / 16);
        if (fence) wgmma_fence();
#pragma unroll
        for (int k = 0; k < 4; k++) {
          wgmma_ss_n128(kv0, da + 2 * k, db + 128 * k, i + k);
          wgmma_ss_n128(kv1, da + 512 + 2 * k, db + 128 * k, i + k);
        }
        wgmma_commit();
      };
      constexpr uint32_t dm = desc_lo(SB + OFF_MB, 0);
      auto relB = [&](uint32_t s) { mbar_arrive_n(sb + BAR_EMPTYB + s * 8, 2); };
      auto skip = [&]() {
#pragma unroll
        for (int q = 0; q < 6 - NJ; q++) adv<NA>(x.ra);
        x.rb.s = w ? (2 + NJ) % 6 : 4;
        if (!w && NJ < 4) x.rb.ph ^= 1;
      };
      static_assert(NA == 5 && NB == 6, "ring arithmetic");
      mbar_wait2(x.fullA(x.ra.s), x.ra.ph, x.fullB(x.rb.s + w), x.rb.ph);
      mma8(x.ra.s, x.rb.s + w, 0, true);
      gemm_next<256>(x);
#pragma unroll 1
      for (int i = 1; i < NJ; i++) {
        mbar_wait2(x.fullA(x.ra.s), x.ra.ph, x.fullB(x.rb.s + w), x.rb.ph);
        mma8(x.ra.s, x.rb.s + w, 1, true);
        if (i == XR) { rows_store(r1, P.xp[L] + goff + 8, x); publish(3, x); }
        wgmma_wait<1>();
        if (x.elected && i != 2) { x.releaseA(x.pa); relB(x.pb + w); }
        gemm_next<256>(x);
        if (i == 1) { wgmma_wait<0>(); if (x.elected) { x.releaseA(x.pa); relB(x.pb + w); } }
      }
      if (w) {
        if (NJ > 2) { wgmma_wait<0>(); if (x.elected) { x.releaseA(x.pa); relB(x.pb + 1); } }
        if (XR >= NJ) { mbar_wait(x.fullA(x.ra.s), x.ra.ph); rows_store(r1, P.xp[L] + goff + 8, x); publish(3, x); }
        skip();
        asm volatile("bar.sync 7, 256;" ::: "memory");
      }
      TSW(8 + L * 12);
      {
        const int t = threadIdx.x & 127;
        uint32_t mask = t < 2 ? ((w ? (t ? 0xFF3Fu : 0x3FFFu) : 0xFFFFu) >> (NJ - 1)) & (w || NJ == 2 ? ~1u : ~0u) : 0u, cnt = 1 + t;
        bool ready = false;
#pragma unroll 1
        for (int i = NJ; i < 16; i++) {
          if (!ready) mbar_wait2(x.fullA(x.ra.s), x.ra.ph, x.fullB(x.rb.s), x.rb.ph);
          mma8(x.ra.s, x.rb.s, 1, true);
          if (XR >= NJ && i == NJ && !w) { rows_store(r1, P.xp[L] + goff + 8, x); publish(3, x); }
          const uint32_t bar = sb + (t ? BAR_EMPTYB + x.pb * 8 : BAR_EMPTYA + x.pa * 8);
          gemm_next<128>(x);
          if (w && (i | 4) == 15) x.rb.s = 4;
          ready = mbar_probe2(x.fullA(x.ra.s), x.ra.ph, x.fullB(x.rb.s), x.rb.ph);
          wgmma_wait<1>();
          if (mask & 1) mbar_arrive_n(bar, cnt);
          mask >>= 1; cnt = 2;
          if (i == 8 && w) asm volatile("bar.arrive 9, 256;" ::: "memory");
          if (i == 9) TSW(10 + L * 12);
        }
        mbar_wait2(sb + BAR_STAT, 1, sb + BAR_CS + 8, 0);
        wgmma_fence();
        wgmma_r1_n128(kv0, dm, dcs + 96 + 96 * w, 1);
        wgmma_r1_n128(kv1, dm + 64, dcs + 96 + 96 * w, 1);
        wgmma_commit();
        if (w == 0) asm volatile("bar.arrive 7, 256;" ::: "memory");
        wgmma_wait<1>();
        if (mask & 1) mbar_arrive_n(sb + (t ? BAR_EMPTYB + x.pb * 8 : BAR_EMPTYA + x.pa * 8), 2);
      }
      const Stats s0 = load_stats(0, x), s1 = load_stats(1, x), st = w ? s1 : s0;
      wgmma_wait<0>();
      fence_regs(kv);
      TSW(2 + L * 12);
      if (w == 0) skip();
      const uint32_t h0 = x.held(0), h1 = x.held(1);
      auto vreg = [&](int ks) { return ks < 6 ? OFF_A + (ks < 3 ? h0 * SLOT : h1 * SLOT - 15360) + ks * 5120 : OFF_S + 2048 + ks * 5120; };
      if (w == 0) {
        uint32_t f[2][18], ad[4];
#pragma unroll
        for (int q = 0; q < 18; q++) f[1][q] = 0u;
#pragma unroll
        for (int q = 0; q < 4; q++) ad[q] = x.maddr(sb + OFF_S, 2 * q);
        auto norm = [&](int un) {
          uint32_t* u = f[un & 1];
          const Stats& sn = (un & 2) ? s1 : s0;
#pragma unroll
          for (int sg = 0; sg < 2; sg++) {
            uint32_t v = u[16 + sg];
            v = add2(v, __shfl_xor_sync(0xffffffffu, v, 1)); v = add2(v, __shfl_xor_sync(0xffffffffu, v, 2));
            const float a = rcp(lo16(v)) * sn.rstd0, b = rcp(hi16(v)) * sn.rstd1;
            const uint32_t r0 = pack2(a, a), r1_ = pack2(b, b);
#pragma unroll
            for (int q = 8 * sg; q < 8 * sg + 8; q++) u[q] = mul2(u[q], (q & 1) ? r1_ : r0);
#pragma unroll
            for (int q = 2 * sg; q < 2 * sg + 2; q++) stsm4(ad[q] + (un & 1) * SLOT + (un >> 1) * 8192, u[4 * q], u[4 * q + 1], u[4 * q + 2], u[4 * q + 3]);
          }
        };
        auto unit = [&](int un) { return kv + ((un >> 1) & 1) * 64 + (un & 1) * 16 + (un >> 2) * 32; };
        hedgehog_scale<0>(kv, s0, nullptr);
#pragma unroll 1
        for (int it = 0;; it++) {
#pragma unroll
          for (int un = 0; un < 4; un++) {
            if (un == 1) {
              if (it) asm volatile("bar.sync 9, 256;" ::: "memory");
#pragma unroll
              for (int q = 0; q < 4; q++) ad[q] -= it * (OFF_S - OFF_B - 2 * SLOT);
            }
            norm((un + 3) & 3);
            dual_exp(unit(un), f[un & 1], x.goff);
            hedgehog_scale<KEEP>(unit(un + 1), ((un + 1) & 2) ? s1 : s0, f[(un + 1) & 1]);
          }
          if (it) break;
#pragma unroll
          for (int q = 0; q < 32; q++) {
            asm volatile("mov.b32 %0, %1;" : "=f"(kv[q]) : "f"(kv[q + 32]));
            asm volatile("mov.b32 %0, %1;" : "=f"(kv[q + 64]) : "f"(kv[q + 96]));
            if (q < 16) kv[32 + q] = 0.f;
          }
        }
        norm(3);
        fence_async_smem();
        TSW(3 + L * 12);
      } else {
        wg_bar(w);
#pragma unroll
        for (int hf = 0; hf < 2; hf++) {
          const uint32_t tV = sb + vreg(4 * hf + x.warp) + ((x.lane >> 3) & 1) * 2560 + (x.lane & 7) * 16;
          const float i0 = rcp(hf ? s1.rstd0 : s0.rstd0), i1 = rcp(hf ? s1.rstd1 : s0.rstd1);
          const uint32_t h = pack2(i0, i1), u0 = pack2(lo16(h), i0 - lo16(h)), u1 = pack2(hi16(h), i1 - hi16(h));
          stsm4(tV + 512 + x.mhi * 640, u0, u1, u0, u1);
          stsm4(tV + 1792 + x.mhi * 640, u0, u1, u0, u1);
#pragma unroll
          for (int q = 0; q < 8; q++) {
            const float* u = kv + 64 * hf + 8 * q;
            stsm4(tV + (q >> 1) * 640 + (2 * (q & 1) + x.mhi) * 128, pack2(u[0], u[1]), pack2(u[2], u[3]), pack2(u[4], u[5]), pack2(u[6], u[7]));
          }
        }
        TSW(3 + L * 12);
        fence_async_smem();
      }
      {
        float d[2][20];
        cta_bar();
        TSW(11 + L * 12);
        uint32_t pk[9];
        auto prep = [&](float (&u)[20]) {
          fence_regs(u);
#pragma unroll
          for (int q = 0; q < 8; q++) pk[q] = pack2(u[((q >> 1) & 2) + 4 * (q & 3)], u[((q >> 1) & 2) + 4 * (q & 3) + 1]);
          pk[8] = __float_as_uint((x.c & 1) ? u[18] + u[19] : u[16] + u[17]);
#pragma unroll
          for (int q = 0; q < 9; q += 4) pk[q] = (pk[q] & ~1u) | (L == 1);
        };
        uint4* dst = &g_kvpart[x.j()][w * 4 + x.warp][0][x.m() * 32 + x.lane];
        unsigned* dz = reinterpret_cast<unsigned*>(&g_kvpart[x.j()][w * 4 + x.warp][x.c & 1][512]) + x.m() * 8 + x.g;
        auto send = [&](int hp) {
          st_v4(dst + hp * 16 * 544, pk[0], pk[1], pk[2], pk[3]); st_v4(dst + (hp * 16 + 1) * 544, pk[4], pk[5], pk[6], pk[7]);
          if (x.c < 2) st_flag(dz + hp * 16 * 544 * 4, pk[8]);
        };
        wgmma_fence();
#pragma unroll
        for (int q = 0; q < 17; q++) {
          if (q < 16) wgmma_ss_n40_tt(d[q >> 3], desc_lo(SB + (q < 8 ? OFF_S : OFF_B + 2 * SLOT), 1024) + w * (SLOT / 16) + 128 * (q & 7), desc_lo(SB + vreg(q & 7), 2560) + (w + (q >> 3) * 2) * 40, q & 7);
          else wgmma_r1_n128(acc, dm + w * 64, dcs, LEAD != 0);
          if (q == 7 || q == KVS || q == 16) wgmma_commit();
          if (q == KVS) { wgmma_wait<1>(); prep(d[0]); send(0); wgmma_fence(); }
        }
        gemm_issue<128, false>(acc, x); gemm_next<128>(x);
        wgmma_wait<1>();
        x.releaseA(h0); x.releaseA(h1); x.releaseB(2); x.releaseB(3);
        if (x.lane == 0) mbar_arrive(sb + BAR_SIGT);
        prep(d[1]);
        TSW(4 + L * 12);
#pragma unroll 1
        for (int seg = 0; seg < 2; seg++) {
          const int n0 = w ? PS1 : PS0;
          gemm_run(acc, x, seg ? 15 - LEAD * w - n0 : n0, seg, seg ? L : 0);
          if (seg == 0) send(1);
        }
      }
      gemm_end(acc, x);
      TSW(5 + L * 12);
      {
        float dp[2][20], dn[2][20];
        uint32_t f[4][16];
        auto expo = [&](int h) { hedgehog_scale<0>(acc + 16 * h, st, nullptr); dual_exp_rcp(acc + 16 * h, f[h]); };
        auto mma = [&](int h) {
          if (!(h & 1)) mbar_wait(sb + BAR_KV + h * 4, L >> 1);
          if (h == 0) TSW(9 + L * 12);
          const uint32_t db = desc_lo(SB + OFF_S + h * 5120, 128);
          const uint32_t (&a)[16] = f[h];
          wgmma_fence();
          wgmma_rs_n40(dp[h & 1], a[0], a[1], a[2], a[3], db, 0);
          wgmma_rs_n40(dn[h & 1], a[8], a[9], a[10], a[11], db + 160, 0);
          wgmma_rs_n40(dp[h & 1], a[4], a[5], a[6], a[7], db + 80, 1);
          wgmma_rs_n40(dn[h & 1], a[12], a[13], a[14], a[15], db + 240, 1);
          wgmma_commit();
        };
        const uint32_t oo = x.g * 4 + (x.c ^ (x.g >> 1));
        uint32_t xr[16];
        auto fin = [&](int h) {
          const uint32_t tile = x.aslot(x.held(h >> 1));
          if (!(h & 1)) {
#pragma unroll
            for (int q = 0; q < 4; q++) ldsm4(x.maddr(tile, 2 * q), reinterpret_cast<uint32_t (&)[4]>(xr[4 * q]));
          }
          float (&u)[20] = dp[h & 1];
          float (&v)[20] = dn[h & 1];
          fence_regs(u); fence_regs(v);
#pragma unroll
          for (int r = 0; r < 2; r++) {
            float cc = u[17 + 2 * r] * rcp(v[17 + 2 * r]);
            const float aa = rcp(fmaf(v[16 + 2 * r], cc, fmaf(u[17 + 2 * r], 1e-6f, u[16 + 2 * r])));
            cc *= aa;
            uint32_t o[4];
#pragma unroll
            for (int t = 0; t < 4; t++) o[t] = pack2(fmaf(u[4 * t + 2 * r], aa, v[4 * t + 2 * r] * cc), fmaf(u[4 * t + 2 * r + 1], aa, v[4 * t + 2 * r + 1] * cc));
            x.oimg(h >> 1)[r * 64 + (h & 1) * 32 + oo] = make_uint4(o[0], o[1], o[2], o[3]);
            if (r == 0 && !(h & 1)) __syncwarp();
            sts128(tile + x.warp * 2048 + r * 1024 + (h & 1) * 512 + oo * 16, o[0], o[1], o[2], o[3]);
          }
          if (h & 1) {
            publish(h >> 1, x);
#pragma unroll
            for (int q = 0; q < 16; q++) { acc[16 * (h - 1) + 2 * q] = lo16(xr[q]); acc[16 * (h - 1) + 2 * q + 1] = hi16(xr[q]); }
          }
        };
        expo(0); mma(0);
        expo(1); mma(1);
        wgmma_wait<1>(); fin(0); wgmma_wait<0>(); fin(1);
        expo(2); mma(2);
        expo(3); mma(3);
        wgmma_wait<1>(); fin(2); wgmma_wait<0>(); fin(3);
      }
    }
    fence_async_smem();
    wg_bar(w);
    TSW(6 + L * 12);
    rewind2<NA>(x.ra);
    gemm_issue<128, false, true>(acc, x); gemm_next<128>(x);
#pragma unroll 1
    for (int seg = L >= TSL ? 0 : 1; seg < 2; seg++) {
      gemm_run<true>(acc, x, L >= TSL ? (seg ? TSK : 15 - TSK) : 15, seg);
      if (L >= TSL) {
        if (seg == 0 && w == 1) asm volatile("bar.sync 6, 256;" ::: "memory");
        if (seg == 1 && w == 0) asm volatile("bar.arrive 6, 256;" ::: "memory");
      }
    }
    gemm_end(acc, x);
    TSW(7 + L * 12);
    rewind2<NA>(x.ra);
    out_epilogue(acc, r1, P.xp[L + 1] + goff, L, x);
    TSW(13 + L * 12);
  }
  rows_store(r1, P.xp[4] + goff + 8, x);
}

__device__ __forceinline__ void b_producer(const Params& P, uint32_t sb, unsigned vb) {
  const int j = cta_j(vb);
  Ring r = {PRE_B % NB, PRE_B < NB};
  auto load = [&](const CUtensorMap* tm, int kb, int part, bool folded) {
    mbar_wait(sb + BAR_EMPTYB + r.s * 8, r.ph);
    if (elect()) {
      mbar_expect_tx(sb + BAR_FULLB + r.s * 8, SLOT);
      if (folded) bulk_load(sb + OFF_B + r.s * SLOT, &g_wf[part][j][kb][0], SLOT, sb + BAR_FULLB + r.s * 8);
      else tma_load_3d(sb + OFF_B + r.s * SLOT, tm, sb + BAR_FULLB + r.s * 8, 0, kb * 64, part * 16 + 2 * j);
    }
    adv<NB>(r);
  };
#pragma unroll 1
  for (int L = 0; L < 4; L++) {
    const int wt = L & 1;
    if (L == 1) { mbar_wait(sb + BAR_WPHI, 1); fence_async_global(); }
#pragma unroll 1
    for (int i = L == 0 ? PRE_B : 0; i < 32; i++) {
      const bool solo = wt && i >= 2 * NJ;
      const int v = solo ? i >= 16 + NJ : i & 1;
      load(&P.mw[wt], kv_order(solo ? i - (v ? 16 : NJ) : i >> 1, j, L), 1 + v, wt && !v);
      if (wt && (i | 4) == 31) r.s = 4;
      if (L == 0 && i >= PF0 && (i - PF0) % PFS == 0 && elect()) {
        const int p = (i - PF0) / PFS;
        if (p < 3) tma_prefetch_3d(p ? &P.mwo[p - 1] : &P.mw[1], 0, cta_m(vb) * 64, (p ? 0 : 16) + 2 * j);
      }
      if (L == 0 && i < 9) TS(6, 4 + i);
      if (L == 2 && (i & 1)) TS(7, 32 + (i >> 1));
    }
    if (L == 1) { mbar_wait(sb + BAR_CS + 8, 0); fence_async_global(); }
#pragma unroll 1
    for (int i = 0; i < 32; i++) {
      if (DEFER && i == 16 && ((DEFL >> wt) & 1)) {
        Ring q = r;
        for (int u = 0; u < DEFER; u++) adv<NB>(q);
        mbar_wait(sb + BAR_EMPTYB + q.s * 8, q.ph);
      }
      load(i < 16 ? &P.mw[wt] : &P.mwo[wt], i < 16 ? q_order(i, j) : o_order(i - 16, j), 0, wt && i < 16);
    }
  }
}

__device__ __forceinline__ void a_loader(const Params& P, uint32_t sb, unsigned vb) {
  const int j = cta_j(vb), m = cta_m(vb);
  Ring r = {PRE_A % NA, PRE_A < NA};
  auto load = [&](const CUtensorMap* tm, int c0, int c1, int c2) {
    mbar_wait(sb + BAR_EMPTYA + r.s * 8, r.ph);
    if (elect()) {
      mbar_expect_tx(sb + BAR_FULLA + r.s * 8, SLOT);
      tma_load_3d(sb + OFF_A + r.s * SLOT, tm, sb + BAR_FULLA + r.s * 8, c0, c1, c2);
    }
    adv<NA>(r);
  };
#pragma unroll 1
  for (int i = PRE_A; i < 17; i++) {
    load(i == 14 ? &P.mw[1] : &P.mx[0], i == 14 ? 0 : kv_order(i - (i > 14), j, 0) * 64, m * 64, i == 14 ? 16 + 2 * j : 0);
    if (i == 14 && elect()) { mbar_expect_tx(sb + BAR_WPHI, 8192); tma_load_2d(sb + OFF_S + 4096, &P.mwphi, sb + BAR_WPHI, 0, 128 * j); }
    if (i < 8) TS(6, 21 + i);
  }
  const unsigned tag = get_tag(sb);
#pragma unroll 1
  for (int L = 0; L < 4; L++) {
#pragma unroll 1
    for (int i = (L & 1) ? NJ - 16 : 0; i < 16; i++) load(&P.mx[L], (i < 0 ? o_order(16 + i, j) : q_order(i, j)) * 64, m * 64, 0);
    if (L & 1) {
#pragma unroll 1
      for (int p = 0; p < 2; p++) {
        poll_flags(&g_kvfflag[L >> 1][j][p][0], 8, 0xFFu, tag);
        if (elect()) { mbar_expect_tx(sb + BAR_KV + p * 8, 10240); bulk_load(sb + OFF_S + p * 10240, &g_kvfin[j][8 * p][0], 10240, sb + BAR_KV + p * 8); }
      }
      TS(4, 14 + L);
    }
#pragma unroll 1
    for (int p = 0; p < (L < 3 ? 2 : 1); p++) {
      const unsigned* flags = p == 0 ? &g_oflag[L][0][m][0] : &g_xflag[L + 1][0][m][0];
      unsigned seen = 0;
#pragma unroll 1
      for (int i = 2; i < 16; i++) {
        const int c0 = o_order(i, j) * 64;
        mbar_wait(sb + BAR_EMPTYA + r.s * 8, r.ph);
        if (elect()) mbar_expect_tx(sb + BAR_FULLA + r.s * 8, SLOT);
        if (i == 2) mbar_wait(sb + BAR_SIGP + p * 16, L & 1);
        if (i == 2 || i == 9 || (i == 6 && seen != 0xFFFFFFFFu)) {
          const int lane = threadIdx.x & 31, nn = p == 1 ? PNX : PNO;
          const unsigned* f = flags + (i == 9 ? 512 : 0) + (lane & 7);
          if (i == 2) f += (((lane >> 3) & (nn - 1)) - (m & (nn - 1))) * 32;
          const unsigned need = i == 2 ? 0x0F0F0F0Fu << (~j & 4) : 0xFFFFFFFFu;
          int it = 0;
          do { seen = __ballot_sync(0xffffffffu, ld_flag(f) == tag); if (++it > (1 << 22)) __trap(); } while ((seen & need) != need);
          fence_async_global();
        }
        if (elect()) {
          if (p == 0) bulk_load(sb + OFF_A + r.s * SLOT, &g_o[m][0][c0 * 16], SLOT, sb + BAR_FULLA + r.s * 8);
          else tma_load_3d(sb + OFF_A + r.s * SLOT, &P.mx[L + 1], sb + BAR_FULLA + r.s * 8, c0, m * 64, 0);
        }
        adv<NA>(r);
        if (i == 2) TS(2, p == 0 ? 5 + L * 8 : 9 + L * 8);
        if (L == 1 && p == 1) TS(7, 16 + i);
      }
    }
  }
}

__device__ __forceinline__ void helper_bar() { asm volatile("bar.sync 4, 64;" ::: "memory"); }
__device__ __forceinline__ void helper(const Params& P, uint32_t sb, int w, unsigned vb) {
  const int j = cta_j(vb), m = cta_m(vb);
  if (w == 0) {
    if (elect()) {
      const unsigned t = atomicAdd(&g_ctr, 1u) / NCTA + 1u;
      asm volatile("st.shared.u32 [%0], %1;" ::"r"(sb + OFF_EPOCH), "r"(t) : "memory");
      mbar_arrive(sb + BAR_EPOCH);
    }
  }
  const unsigned tag = get_tag(sb);
  mbar_wait(sb + BAR_FULLB + 24, 0);
  const uint32_t stg = sb + OFF_T + w * 12288, stb = sb + BAR_STG + w * 24;
  Ring rs = {0, 0};
  auto cs_image = [&](int L) {
      const int lane = lane_id();
      poll_flags(&g_csflag[L][j][0], 16, L ? CSNEED : 0xFFFu, tag);
#pragma unroll
      for (int p = 0; p < 3; p++) {
        const uint4 u = ldcg4(&g_cs[L][0][p * 1024 + 128 * j + lane * 4]), v = ldcg4(&g_cs[L][1][p * 1024 + 128 * j + lane * 4]);
        const float c0 = __uint_as_float(u.x) + __uint_as_float(v.x), c1 = __uint_as_float(u.y) + __uint_as_float(v.y);
        const float c2 = __uint_as_float(u.z) + __uint_as_float(v.z), c3 = __uint_as_float(u.w) + __uint_as_float(v.w);
        const uint32_t h0 = pack2(c0, c1), h1 = pack2(c2, c3), dst = sb + OFF_CS + (p * 16 + (lane >> 1)) * 96 + L * 48 + (lane & 1) * 8;
        sts64(dst, h0, h1); sts64(dst + 16, pack2(c0 - lo16(h0), c1 - hi16(h0)), pack2(c2 - lo16(h1), c3 - hi16(h1))); sts64(dst + 32, h0, h1);
        if (L == 0) { sts64(dst + 48, 0u, 0u); sts64(dst + 64, 0u, 0u); sts64(dst + 80, 0u, 0u); }
      }
      if (L == 0 && lane < 4) sts64(sb + OFF_CS + 4608 + lane * 8, 0u, 0u);
      fence_async_smem();
      __syncwarp();
      if (elect()) mbar_arrive(sb + BAR_CS + L * 8);
      TS(4, 2 + L * 2);
  };
#pragma unroll 1
  for (int L = 0; L < 4; L++) {
    const int lane = lane_id();
    if (L == 0) {
      {
        const int wt = m >= 12, col = ((0x2021 >> (m & 12)) & 3) * 1024 + 128 * j + (m & 3) * 32;
        const CUtensorMap* tm = &P.mcs[wt];
        if (D2 && wt) __nanosleep(D2);
        constexpr int nb = 8;
        float a[8] = {0.f, 0.f, 0.f, 0.f, 0.f, 0.f, 0.f, 0.f};
#pragma unroll 1
        for (int b = -3; b < nb; b++) {
          uint4 v[8];
          if (b >= 0) {
            mbar_wait(stb + rs.s * 8, rs.ph);
#pragma unroll
            for (int u = 0; u < 8; u++) lds128(stg + rs.s * 4096 + u * 512 + lane * 16, v[u].x, v[u].y, v[u].z, v[u].w);
            fence_async_smem();
            __syncwarp();
          }
          const uint32_t sl = b < 0 ? (rs.s + b + 3) % 3 : rs.s;
          if (b + 3 < nb && elect()) { mbar_expect_tx(stb + sl * 8, 4096); tma_load_2d(stg + sl * 4096, tm, stb + sl * 8, col, (w * (16 - nb) + b + 3) * 64); }
          if (b >= 0) {
            adv<3>(rs);
#pragma unroll
            for (int u = 0; u < 8; u++) {
              a[0] += lo16(v[u].x); a[1] += hi16(v[u].x); a[2] += lo16(v[u].y); a[3] += hi16(v[u].y);
              a[4] += lo16(v[u].z); a[5] += hi16(v[u].z); a[6] += lo16(v[u].w); a[7] += hi16(v[u].w);
            }
          }
        }
#pragma unroll
        for (int u = 0; u < 8; u++) {
          a[u] += __shfl_xor_sync(0xffffffffu, a[u], 4); a[u] += __shfl_xor_sync(0xffffffffu, a[u], 8); a[u] += __shfl_xor_sync(0xffffffffu, a[u], 16);
        }
        if (lane < 4) {
          float4* dst = reinterpret_cast<float4*>(&g_cs[wt][w][col + lane * 8]);
          dst[0] = make_float4(a[0], a[1], a[2], a[3]); dst[1] = make_float4(a[4], a[5], a[6], a[7]);
        }
        helper_bar();
        if (w == 0 && elect()) { fence_gpu(); st_flag(&g_csflag[wt][j][m], tag); }
      }
      if (w == 0) TS(4, 1 + L * 2);
    }
    if (w == 1) {
      if (L > 0) mbar_wait(sb + BAR_SIGP + ((L & STG0) ? 16 : 24), (L - 1) & 1);
#pragma unroll 1
      for (int p = 0; p < 2; p++) {
        uint4 v[8];
        for (int it = 0;; it++) {
          bool ok = true;
#pragma unroll
          for (int t = 0; t < 8; t++) v[t] = ld_pkt(&g_stats[m][p][t][lane]);
#pragma unroll
          for (int t = 0; t < 8; t++) ok = ok && (v[t].w & 15u) == seq4(tag, L);
          if (__all_sync(0xffffffffu, ok)) break;
          __nanosleep(200);
          if (it > (1 << 20)) __trap();
        }
        float s0 = 0.f, q0 = 0.f, s1 = 0.f, q1 = 0.f;
#pragma unroll
        for (int t = 0; t < 8; t++) { s0 += __uint_as_float(v[t].x); q0 += __uint_as_float(v[t].y); s1 += __uint_as_float(v[t].z); q1 += __uint_as_float(v[t].w & ~15u); }
        s0 *= (1.f / 1024); s1 *= (1.f / 1024);
        sts64(sb + OFF_MR + p * 256 + lane * 8, __float_as_uint(rsqrtf(fmaxf(q0 * (1.f / 1024) - s0 * s0, 0.f) + 1e-5f)),
              __float_as_uint(rsqrtf(fmaxf(q1 * (1.f / 1024) - s1 * s1, 0.f) + 1e-5f)));
#pragma unroll
        for (int r = 0; r < 2; r++) {
          const float v = -0.5f * (r ? s1 : s0);
          const uint32_t hh = pack2(v, v), hl = pack2(v, v - lo16(hh));
          const bool b = L & 1;
          sts128(sb + (b ? OFF_MB : OFF_MA) + p * 1024 + (lane >> 3) * 256 + r * 128 + (lane & 7) * 16, b ? 0u : hh, b ? hh << 16 : hl >> 16, b ? hl : 0u, 0u);
        }
      }
      fence_async_smem();
      __syncwarp();
      if (elect()) {
        mbar_arrive(sb + BAR_STAT);
      }
      TS(2, 0 + L * 8);
    }
    if (L == w) cs_image(L);
    if (L & 1) {
      const uint32_t flip = L == 1 ? 0u : 1u;
      mbar_wait(sb + BAR_SIGT, 1);
      {
        int it = 0;
        if (PSL) __nanosleep(m < 8 ? PSL : PSL + 600);
        while (!__all_sync(0xffffffffu, (ld_flag(reinterpret_cast<const unsigned*>(&g_kvpart[j][m][w][512]) + (lane & 15) * 8) ^ flip) & 1u)) { if (PSL) __nanosleep(100); if (++it > (1 << 22)) __trap(); }
        fence_async_global();
      }
      if (w == 0) TS(4, 6 + L * 2);
      for (int it = 0;; it++) {
        if (elect()) { mbar_expect_tx(stb + rs.s * 8, 8704); bulk_load(stg, &g_kvpart[j][m][w][0], 8704, stb + rs.s * 8); }
        mbar_wait(stb + rs.s * 8, rs.ph);
        adv<3>(rs);
        float a[8] = {0.f, 0.f, 0.f, 0.f, 0.f, 0.f, 0.f, 0.f};
        float z = 0.f;
        uint32_t ok = 1u;
#pragma unroll
        for (int u = 0; u < 4; u++) { const float v = lds32f(stg + 8192 + u * 128 + (lane & 3) * 32 + (lane >> 2) * 4); z += v; ok &= __float_as_uint(v) ^ flip; }
#pragma unroll 1
        for (int b = 0; b < 16; b += KB) {
          uint4 v[KB];
#pragma unroll
          for (int u = 0; u < KB; u++) lds128(stg + (b + u) * 512 + lane * 16, v[u].x, v[u].y, v[u].z, v[u].w);
#pragma unroll
          for (int u = 0; u < KB; u++) {
            ok &= v[u].x ^ flip;
            if (RH && !(u & 1)) continue;
            if (RH) { v[u].x = add2(v[u].x, v[u - 1].x); v[u].y = add2(v[u].y, v[u - 1].y); v[u].z = add2(v[u].z, v[u - 1].z); v[u].w = add2(v[u].w, v[u - 1].w); }
            a[0] += lo16(v[u].x); a[1] += hi16(v[u].x); a[2] += lo16(v[u].y); a[3] += hi16(v[u].y);
            a[4] += lo16(v[u].z); a[5] += hi16(v[u].z); a[6] += lo16(v[u].w); a[7] += hi16(v[u].w);
          }
        }
        uint4* img = &g_kvfin[j][m][w * 8 + (lane >> 2)];
        img[(lane & 3) * 16] = make_uint4(pack2(a[0], a[1]), pack2(a[2], a[3]), pack2(a[4], a[5]), pack2(a[6], a[7]));
        reinterpret_cast<uint32_t*>(img + 64)[lane & 3] = pack2(qsum(z), 1.f);
        if (__all_sync(0xffffffffu, ok & 1u)) break;
        fence_async_smem();
        if (it > (1 << 16)) __trap();
      }
      if (w == 0) TS(4, 7 + L * 2);
      helper_bar();
      if (w == 1 && elect()) { fence_gpu(); st_flag(&g_kvfflag[L >> 1][j][m >> 3][m & 7], tag); }
      if (w == 1 && L == 1) TS(4, 20);
    } else {
      mbar_wait(sb + BAR_SIGT, 0);
      if (w == 0) {
        if (elect()) { fence_gpu(); st_flag(&g_hflag[L >> 1][m][j][0], tag); st_flag(&g_kflag[j][m], tag); }
        if (L == 0) {
          __nanosleep(KSL);
          poll_flags(&g_kflag[j][0], 16, 0xFFFFu, tag);
          if (elect()) mbar_arrive(sb + BAR_WPHI);
        }
      } else if (m > 0) {
        poll_flags(&g_hflag[L >> 1][m - 1][j][0], 1, 1u, tag);
        if (elect()) { mbar_expect_tx(sb + BAR_HALO, 8192); bulk_load(sb + OFF_S + 8192, &g_halo[m - 1][j][0][0], 8192, sb + BAR_HALO); }
        TS(2, 2 + L * 8);
      }
    }
#pragma unroll 1
    for (int e = 0; e < (L < 3 && w == 0 ? 3 : 1); e++) {
      mbar_wait(sb + BAR_SIGP + (e == 0 ? w : e + 1) * 8, L & 1);
      TS(e == 2 ? 3 : 2 + w, (e ? 6 : 3) + L * 8);
      if (elect()) { fence_gpu(); st_flag(e == 0 ? &g_oflag[L][w][m][j] : &g_xflag[L + 1][e - 1][m][j], tag); }
      TS(e == 2 ? 3 : 2 + w, (e ? 7 : 4) + L * 8);
    }
  }
}

__device__ __forceinline__ void spare(const Params& P, uint32_t sb, int id) {
  const int tid = threadIdx.x & 127, w = __shfl_sync(0xffffffffu, threadIdx.x >> 7, 0), lane = tid & 31, j = 2 * id + w;
  const uint32_t ring = w * 6 * SLOT, wp = 12 * SLOT + w * 8192, bar = sb + 13 * SLOT + w * 64;
  auto part = [&](int t) { return (t >> 4) ^ w; };
  auto load = [&](int t, uint32_t sl) {
    mbar_expect_tx(bar + sl * 8, t == 0 ? SLOT + 8192 : SLOT);
    tma_load_3d(sb + ring + sl * SLOT, &P.mw[1], bar + sl * 8, 0, (t & 15) * 64, part(t) * 16 + 2 * j);
  };
  if (tid == 0) {
    if (w == 2) sts32(sb + OFF_EPOCH, atomicAdd(&g_ctr, 1u) / NCTA + 1u);
    else {
      __nanosleep(D3);
#pragma unroll 1
      for (int t = 0; t < 5; t++) {
        mbar_init(bar + t * 8, 1);
        asm volatile("fence.mbarrier_init.release.cluster;" ::: "memory");
        load(t, t);
      }
      tma_load_2d(sb + wp, &P.mwphi, bar, 0, 128 * j);
    }
  }
  __syncthreads();
  const unsigned tag = get_tag<false>(sb);
  if (w == 2) {
    int it = 0;
    while ((int)(ld_flag(&g_ctr) - tag * NCTA) < 0) { if (++it > (1 << 22)) __trap(); }
    return;
  }
  Ring r = {4, 1};
  float d[64] = {}, cs[32] = {};
  auto fold = [&]() {
    mbar_wait(bar + r.s * 8, r.ph);
    wgmma_fence();
#pragma unroll
    for (int q = 0; q < 8; q++)
      wgmma_ss_n32(reinterpret_cast<float (&)[16]>(d[16 * (q >> 1)]), desc_lo(SB + ring + r.s * SLOT, 16) + (q >> 2) * 512 + (q & 3) * 2, desc_lo(SB + wp, 512) + q * 64, q & 1);
    wgmma_commit();
  };
  const int row = (tid >> 5) * 16 + (lane >> 2);
#pragma unroll 1
  for (int t = -1; t < 32; t++) {
    uint32_t f[32];
#pragma unroll
    for (int i = 0; i < 32; i++) { f[i] = pack2(d[2 * i], d[2 * i + 1]); cs[i & 30] += d[2 * i]; cs[i | 1] += d[2 * i + 1]; }
    wg_bar(w);
    if (tid == 0 && t >= 0 && t < 27) load(t + 5, r.s);
    __syncwarp();
    if (t < 31) adv<5>(r);
    fold();
    if (part(t) == 0 && t >= 0) {
#pragma unroll
      for (int q = 0; q < 8; q++)
        g_wf[0][j][t & 15][(q >> 2) * 512 + (row + 8 * (q & 1)) * 8 + (((q & 2) * 2 + (lane & 3)) ^ (lane >> 2))] =
            make_uint4(f[4 * (q & 6) + (q & 1)], f[4 * (q & 6) + (q & 1) + 2], f[4 * (q & 6) + (q & 1) + 4], f[4 * (q & 6) + (q & 1) + 6]);
    }
    wgmma_wait<0>();
    fence_regs(d);
    if ((t & 15) == 15) {
      if (t >= 0) {
        const uint32_t red = sb + ring + 5 * SLOT;
#pragma unroll
        for (int i = 0; i < 8; i++) sts128(red + (tid >> 2) * 512 + (i >> 1) * 128 + (lane & 3) * 32 + (i & 1) * 16, __float_as_uint(cs[4 * i]), __float_as_uint(cs[4 * i + 1]), __float_as_uint(cs[4 * i + 2]), __float_as_uint(cs[4 * i + 3]));
        wg_bar(w);
        float a = 0.f;
#pragma unroll 4
        for (int i = 0; i < 32; i++) a += lds32f(red + i * 512 + tid * 4);
        g_cs[1][0][part(t) * 1024 + j * 128 + tid] = a;
        wg_bar(w);
        if (tid == 0) {
          fence_gpu();
          st_flag(&g_csflag[1][j][part(t)], tag);
        }
        __syncwarp();
      }
#pragma unroll
      for (int i = 0; i < 32; i++) cs[i] = 0.f;
    }
  }
}

__global__ void __launch_bounds__(NTHREADS, 1) fused_kernel(const __grid_constant__ Params P) {
  extern __shared__ __align__(1024) uint8_t smem_raw[];
  constexpr uint32_t sb = SB;
  const int tid = threadIdx.x;
  const unsigned vb = vblock();
  if (vb >= 128) { spare(P, sb, vb - 128); return; }
  const int warp = __shfl_sync(0xffffffffu, tid >> 5, 0);
  if (elect()) {
    if (warp == 11) { prefetch_map(&P.mx[0]); prefetch_map(&P.mw[0]); if (smem_u32(smem_raw) != SB) __trap(); }
    if (warp < 7) {
#pragma unroll
      for (int i = 0; i < 8; i++) mbar_init(sb + OFF_BAR + (warp * 8 + i) * 8, warp == 2 || warp == 3 ? 2 : (warp == 4 ? 8 : 1));
    }
    asm volatile("fence.mbarrier_init.release.cluster;" ::: "memory");
    if (warp < 2) {
      const int j = cta_j(vb);
#pragma unroll 1
      for (int i = 0; i < (warp == 0 ? PRE_B : PRE_A); i++) {
        const uint32_t bar = sb + BAR_FULLB + warp * 64 + i * 8;
        mbar_expect_tx(bar, SLOT);
        if (warp == 0) tma_load_3d(sb + OFF_B + i * SLOT, &P.mw[0], bar, 0, kv_order(i >> 1, j, 0) * 64, 16 + (i & 1) * 16 + 2 * j);
        else tma_load_3d(sb + OFF_A + i * SLOT, &P.mx[0], bar, kv_order(i, j, 0) * 64, cta_m(vb) * 64, 0);
      }
    }
  }
  if (tid == 0) TS(6, 0);
  __syncthreads();
  if (tid == 0) TS(6, 2);
  if (warp < 4) {
    reg_dealloc<PREGS>();
    if (warp == 0) b_producer(P, sb, vb);
    else if (warp == 1) a_loader(P, sb, vb);
    else helper(P, sb, warp - 2, vb);
  } else {
    reg_alloc<CREGS>();
    consumer(P, sb, (warp >> 2) - 1, vb);
  }
}

typedef CUresult (*EncodeFn)(CUtensorMap*, CUtensorMapDataType, cuuint32_t, void*, const cuuint64_t*, const cuuint64_t*,
                             const cuuint32_t*, const cuuint32_t*, CUtensorMapInterleave, CUtensorMapSwizzle,
                             CUtensorMapL2promotion, CUtensorMapFloatOOBfill);

void encode(EncodeFn fn, CUtensorMap* m, const void* ptr, int rank, const cuuint64_t* dims, const cuuint64_t* strides,
            const cuuint32_t* box, CUtensorMapSwizzle swz) {
  const cuuint32_t es[3] = {1, 1, 1};
  fn(m, CU_TENSOR_MAP_DATA_TYPE_BFLOAT16, rank, const_cast<void*>(ptr), dims, strides, box, es, CU_TENSOR_MAP_INTERLEAVE_NONE,
     swz, CU_TENSOR_MAP_L2_PROMOTION_L2_256B, CU_TENSOR_MAP_FLOAT_OOB_FILL_NONE);
}
void encode_w(EncodeFn fn, CUtensorMap* m, const void* ptr, int ncols) {
  const cuuint64_t d[3] = {64, 1024, (cuuint64_t)ncols / 64}, s[2] = {(cuuint64_t)ncols * 2, 128};
  const cuuint32_t box[3] = {64, 64, 2};
  encode(fn, m, ptr, 3, d, s, box, CU_TENSOR_MAP_SWIZZLE_128B);
}

void encode_cs(EncodeFn fn, CUtensorMap* m, const void* ptr, int ncols) {
  const cuuint64_t d[2] = {(cuuint64_t)ncols, 1024}, s[1] = {(cuuint64_t)ncols * 2};
  const cuuint32_t box[2] = {32, 64};
  encode(fn, m, ptr, 2, d, s, box, CU_TENSOR_MAP_SWIZZLE_NONE);
}

}

extern "C" void kernel_launch(void* const* d_in, const int* in_sizes, int n_in, void* d_out, int out_size) {
  (void)in_sizes; (void)n_in; (void)out_size;
  void* fnp = nullptr;
  cudaDriverEntryPointQueryResult q;
  cudaGetDriverEntryPoint("cuTensorMapEncodeTiled", &fnp, cudaEnableDefault, &q);
  EncodeFn fn = (EncodeFn)fnp;
  Params P;
  {
    const cuuint64_t dims[3] = {1024, 1024, 2}, strides[2] = {4096, 2048};
    const cuuint32_t box[3] = {64, 64, 2};
    const void* xs[5] = {d_in[0], d_out, d_out, d_out, d_out};
    for (int i = 0; i < 5; i++) P.xp[i] = (uint4*)xs[i];
    for (int i = 0; i < 4; i++) encode(fn, &P.mx[i], xs[i], 3, dims, strides, box, CU_TENSOR_MAP_SWIZZLE_128B);
  }
  encode_w(fn, &P.mw[0], d_in[1], 3072);
  encode_w(fn, &P.mw[1], d_in[4], 3072);
  encode_w(fn, &P.mwo[0], d_in[2], 1024);
  encode_w(fn, &P.mwo[1], d_in[6], 1024);
  encode_cs(fn, &P.mcs[0], d_in[1], 3072);
  encode_cs(fn, &P.mcs[1], d_in[4], 3072);
  {
    const cuuint64_t dims[2] = {32, 1024}, strides[1] = {64};
    const cuuint32_t box[2] = {32, 128};
    encode(fn, &P.mwphi, d_in[5], 2, dims, strides, box, CU_TENSOR_MAP_SWIZZLE_64B);
  }
  cudaFuncSetAttribute(fused_kernel, cudaFuncAttributeMaxDynamicSharedMemorySize, SMEM_BYTES);
  fused_kernel<<<NCTA, NTHREADS, SMEM_BYTES, cudaStreamPerThread>>>(P);
}
```

```cpp
#include <cuda_runtime.h>
#include <cuda_bf16.h>
#include <cuda.h>
#include <stdint.h>

namespace {

__device__ __forceinline__ void wgmma_ss_n256(float (&d)[128], uint32_t da, uint32_t ha, uint32_t db, int sd) {
  asm volatile("{\n.reg .pred p;\n.reg .b64 a, b;\nsetp.ne.b32 p, %130, 0;\nmov.b64 a, {%128, %131};\nmov.b64 b, {%129, 0x40000040};\n"
    "wgmma.mma_async.sync.aligned.m64n256k16.f32.bf16.bf16 {%0,%1,%2,%3,%4,%5,%6,%7,%8,%9,%10,%11,%12,%13,%14,%15,%16,%17,%18,%19,%20,%21,%22,%23,%24,%25,%26,%27,%28,%29,%30,%31,%32,%33,%34,%35,%36,%37,%38,%39,%40,%41,%42,%43,%44,%45,%46,%47,%48,%49,%50,%51,%52,%53,%54,%55,%56,%57,%58,%59,%60,%61,%62,%63,%64,%65,%66,%67,%68,%69,%70,%71,%72,%73,%74,%75,%76,%77,%78,%79,%80,%81,%82,%83,%84,%85,%86,%87,%88,%89,%90,%91,%92,%93,%94,%95,%96,%97,%98,%99,%100,%101,%102,%103,%104,%105,%106,%107,%108,%109,%110,%111,%112,%113,%114,%115,%116,%117,%118,%119,%120,%121,%122,%123,%124,%125,%126,%127}, a, b, p, 1, 1, 0, 1;\n}\n"
    : "+f"(d[0]),"+f"(d[1]),"+f"(d[2]),"+f"(d[3]),"+f"(d[4]),"+f"(d[5]),"+f"(d[6]),"+f"(d[7]),"+f"(d[8]),"+f"(d[9]),"+f"(d[10]),"+f"(d[11]),"+f"(d[12]),"+f"(d[13]),"+f"(d[14]),"+f"(d[15]),"+f"(d[16]),"+f"(d[17]),"+f"(d[18]),"+f"(d[19]),"+f"(d[20]),"+f"(d[21]),"+f"(d[22]),"+f"(d[23]),"+f"(d[24]),"+f"(d[25]),"+f"(d[26]),"+f"(d[27]),"+f"(d[28]),"+f"(d[29]),"+f"(d[30]),"+f"(d[31]),"+f"(d[32]),"+f"(d[33]),"+f"(d[34]),"+f"(d[35]),"+f"(d[36]),"+f"(d[37]),"+f"(d[38]),"+f"(d[39]),"+f"(d[40]),"+f"(d[41]),"+f"(d[42]),"+f"(d[43]),"+f"(d[44]),"+f"(d[45]),"+f"(d[46]),"+f"(d[47]),"+f"(d[48]),"+f"(d[49]),"+f"(d[50]),"+f"(d[51]),"+f"(d[52]),"+f"(d[53]),"+f"(d[54]),"+f"(d[55]),"+f"(d[56]),"+f"(d[57]),"+f"(d[58]),"+f"(d[59]),"+f"(d[60]),"+f"(d[61]),"+f"(d[62]),"+f"(d[63]),"+f"(d[64]),"+f"(d[65]),"+f"(d[66]),"+f"(d[67]),"+f"(d[68]),"+f"(d[69]),"+f"(d[70]),"+f"(d[71]),"+f"(d[72]),"+f"(d[73]),"+f"(d[74]),"+f"(d[75]),"+f"(d[76]),"+f"(d[77]),"+f"(d[78]),"+f"(d[79]),"+f"(d[80]),"+f"(d[81]),"+f"(d[82]),"+f"(d[83]),"+f"(d[84]),"+f"(d[85]),"+f"(d[86]),"+f"(d[87]),"+f"(d[88]),"+f"(d[89]),"+f"(d[90]),"+f"(d[91]),"+f"(d[92]),"+f"(d[93]),"+f"(d[94]),"+f"(d[95]),"+f"(d[96]),"+f"(d[97]),"+f"(d[98]),"+f"(d[99]),"+f"(d[100]),"+f"(d[101]),"+f"(d[102]),"+f"(d[103]),"+f"(d[104]),"+f"(d[105]),"+f"(d[106]),"+f"(d[107]),"+f"(d[108]),"+f"(d[109]),"+f"(d[110]),"+f"(d[111]),"+f"(d[112]),"+f"(d[113]),"+f"(d[114]),"+f"(d[115]),"+f"(d[116]),"+f"(d[117]),"+f"(d[118]),"+f"(d[119]),"+f"(d[120]),"+f"(d[121]),"+f"(d[122]),"+f"(d[123]),"+f"(d[124]),"+f"(d[125]),"+f"(d[126]),"+f"(d[127])
    : "r"(da), "r"(db), "r"(sd), "r"(ha));
}
__device__ __forceinline__ void wgmma_ss_n128(float (&d)[64], uint32_t da, uint32_t ha, uint32_t db, int sd) {
  asm volatile("{\n.reg .pred p;\n.reg .b64 a, b;\nsetp.ne.b32 p, %66, 0;\nmov.b64 a, {%64, %67};\nmov.b64 b, {%65, 0x40000040};\n"
    "wgmma.mma_async.sync.aligned.m64n128k16.f32.bf16.bf16 {%0,%1,%2,%3,%4,%5,%6,%7,%8,%9,%10,%11,%12,%13,%14,%15,%16,%17,%18,%19,%20,%21,%22,%23,%24,%25,%26,%27,%28,%29,%30,%31,%32,%33,%34,%35,%36,%37,%38,%39,%40,%41,%42,%43,%44,%45,%46,%47,%48,%49,%50,%51,%52,%53,%54,%55,%56,%57,%58,%59,%60,%61,%62,%63}, a, b, p, 1, 1, 0, 1;\n}\n"
    : "+f"(d[0]),"+f"(d[1]),"+f"(d[2]),"+f"(d[3]),"+f"(d[4]),"+f"(d[5]),"+f"(d[6]),"+f"(d[7]),"+f"(d[8]),"+f"(d[9]),"+f"(d[10]),"+f"(d[11]),"+f"(d[12]),"+f"(d[13]),"+f"(d[14]),"+f"(d[15]),"+f"(d[16]),"+f"(d[17]),"+f"(d[18]),"+f"(d[19]),"+f"(d[20]),"+f"(d[21]),"+f"(d[22]),"+f"(d[23]),"+f"(d[24]),"+f"(d[25]),"+f"(d[26]),"+f"(d[27]),"+f"(d[28]),"+f"(d[29]),"+f"(d[30]),"+f"(d[31]),"+f"(d[32]),"+f"(d[33]),"+f"(d[34]),"+f"(d[35]),"+f"(d[36]),"+f"(d[37]),"+f"(d[38]),"+f"(d[39]),"+f"(d[40]),"+f"(d[41]),"+f"(d[42]),"+f"(d[43]),"+f"(d[44]),"+f"(d[45]),"+f"(d[46]),"+f"(d[47]),"+f"(d[48]),"+f"(d[49]),"+f"(d[50]),"+f"(d[51]),"+f"(d[52]),"+f"(d[53]),"+f"(d[54]),"+f"(d[55]),"+f"(d[56]),"+f"(d[57]),"+f"(d[58]),"+f"(d[59]),"+f"(d[60]),"+f"(d[61]),"+f"(d[62]),"+f"(d[63])
    : "r"(da), "r"(db), "r"(sd), "r"(ha));
}
__device__ __forceinline__ void wgmma_ss_n40_tt(float (&d)[20], uint32_t da, uint32_t db, int sd) {
  asm volatile("{\n.reg .pred p;\n.reg .b64 a, b;\nsetp.ne.b32 p, %22, 0;\nmov.b64 a, {%20, 0x40000040};\nmov.b64 b, {%21, 0x8};\n"
    "wgmma.mma_async.sync.aligned.m64n40k16.f32.bf16.bf16 {%0,%1,%2,%3,%4,%5,%6,%7,%8,%9,%10,%11,%12,%13,%14,%15,%16,%17,%18,%19}, a, b, p, 1, 1, 1, 1;\n}\n"
    : "+f"(d[0]),"+f"(d[1]),"+f"(d[2]),"+f"(d[3]),"+f"(d[4]),"+f"(d[5]),"+f"(d[6]),"+f"(d[7]),"+f"(d[8]),"+f"(d[9]),"+f"(d[10]),"+f"(d[11]),"+f"(d[12]),"+f"(d[13]),"+f"(d[14]),"+f"(d[15]),"+f"(d[16]),"+f"(d[17]),"+f"(d[18]),"+f"(d[19])
    : "r"(da), "r"(db), "r"(sd));
}
__device__ __forceinline__ void wgmma_ss_n32(float (&d)[16], uint32_t da, uint32_t db, int sd) {
  asm volatile("{\n.reg .pred p;\n.reg .b64 a, b;\nsetp.ne.b32 p, %18, 0;\nmov.b64 a, {%16, 0x40000040};\nmov.b64 b, {%17, 0x80000020};\n"
    "wgmma.mma_async.sync.aligned.m64n32k16.f32.bf16.bf16 {%0,%1,%2,%3,%4,%5,%6,%7,%8,%9,%10,%11,%12,%13,%14,%15}, a, b, p, 1, 1, 0, 1;\n}\n"
    : "+f"(d[0]),"+f"(d[1]),"+f"(d[2]),"+f"(d[3]),"+f"(d[4]),"+f"(d[5]),"+f"(d[6]),"+f"(d[7]),"+f"(d[8]),"+f"(d[9]),"+f"(d[10]),"+f"(d[11]),"+f"(d[12]),"+f"(d[13]),"+f"(d[14]),"+f"(d[15])
    : "r"(da), "r"(db), "r"(sd));
}
__device__ __forceinline__ void wgmma_rs_n40(float (&d)[20], uint32_t a0, uint32_t a1, uint32_t a2, uint32_t a3, uint32_t db, int sd) {
  asm volatile("{\n.reg .pred p;\n.reg .b64 b;\nsetp.ne.b32 p, %25, 0;\nmov.b64 b, {%24, 0x10};\n"
    "wgmma.mma_async.sync.aligned.m64n40k16.f32.bf16.bf16 {%0,%1,%2,%3,%4,%5,%6,%7,%8,%9,%10,%11,%12,%13,%14,%15,%16,%17,%18,%19}, {%20,%21,%22,%23}, b, p, 1, 1, 1;\n}\n"
    : "+f"(d[0]),"+f"(d[1]),"+f"(d[2]),"+f"(d[3]),"+f"(d[4]),"+f"(d[5]),"+f"(d[6]),"+f"(d[7]),"+f"(d[8]),"+f"(d[9]),"+f"(d[10]),"+f"(d[11]),"+f"(d[12]),"+f"(d[13]),"+f"(d[14]),"+f"(d[15]),"+f"(d[16]),"+f"(d[17]),"+f"(d[18]),"+f"(d[19])
    : "r"(a0), "r"(a1), "r"(a2), "r"(a3), "r"(db), "r"(sd));
}
__device__ __forceinline__ void wgmma_r1_n256(float (&d)[128], uint32_t da, uint32_t db, int sd) {
  asm volatile("{\n.reg .pred p;\n.reg .b64 a, b;\nsetp.ne.b32 p, %130, 0;\nmov.b64 a, {%128, 0x8};\nmov.b64 b, {%129, 0x6};\n"
    "wgmma.mma_async.sync.aligned.m64n256k16.f32.bf16.bf16 {%0,%1,%2,%3,%4,%5,%6,%7,%8,%9,%10,%11,%12,%13,%14,%15,%16,%17,%18,%19,%20,%21,%22,%23,%24,%25,%26,%27,%28,%29,%30,%31,%32,%33,%34,%35,%36,%37,%38,%39,%40,%41,%42,%43,%44,%45,%46,%47,%48,%49,%50,%51,%52,%53,%54,%55,%56,%57,%58,%59,%60,%61,%62,%63,%64,%65,%66,%67,%68,%69,%70,%71,%72,%73,%74,%75,%76,%77,%78,%79,%80,%81,%82,%83,%84,%85,%86,%87,%88,%89,%90,%91,%92,%93,%94,%95,%96,%97,%98,%99,%100,%101,%102,%103,%104,%105,%106,%107,%108,%109,%110,%111,%112,%113,%114,%115,%116,%117,%118,%119,%120,%121,%122,%123,%124,%125,%126,%127}, a, b, p, 1, 1, 0, 1;\n}\n"
    : "+f"(d[0]),"+f"(d[1]),"+f"(d[2]),"+f"(d[3]),"+f"(d[4]),"+f"(d[5]),"+f"(d[6]),"+f"(d[7]),"+f"(d[8]),"+f"(d[9]),"+f"(d[10]),"+f"(d[11]),"+f"(d[12]),"+f"(d[13]),"+f"(d[14]),"+f"(d[15]),"+f"(d[16]),"+f"(d[17]),"+f"(d[18]),"+f"(d[19]),"+f"(d[20]),"+f"(d[21]),"+f"(d[22]),"+f"(d[23]),"+f"(d[24]),"+f"(d[25]),"+f"(d[26]),"+f"(d[27]),"+f"(d[28]),"+f"(d[29]),"+f"(d[30]),"+f"(d[31]),"+f"(d[32]),"+f"(d[33]),"+f"(d[34]),"+f"(d[35]),"+f"(d[36]),"+f"(d[37]),"+f"(d[38]),"+f"(d[39]),"+f"(d[40]),"+f"(d[41]),"+f"(d[42]),"+f"(d[43]),"+f"(d[44]),"+f"(d[45]),"+f"(d[46]),"+f"(d[47]),"+f"(d[48]),"+f"(d[49]),"+f"(d[50]),"+f"(d[51]),"+f"(d[52]),"+f"(d[53]),"+f"(d[54]),"+f"(d[55]),"+f"(d[56]),"+f"(d[57]),"+f"(d[58]),"+f"(d[59]),"+f"(d[60]),"+f"(d[61]),"+f"(d[62]),"+f"(d[63]),"+f"(d[64]),"+f"(d[65]),"+f"(d[66]),"+f"(d[67]),"+f"(d[68]),"+f"(d[69]),"+f"(d[70]),"+f"(d[71]),"+f"(d[72]),"+f"(d[73]),"+f"(d[74]),"+f"(d[75]),"+f"(d[76]),"+f"(d[77]),"+f"(d[78]),"+f"(d[79]),"+f"(d[80]),"+f"(d[81]),"+f"(d[82]),"+f"(d[83]),"+f"(d[84]),"+f"(d[85]),"+f"(d[86]),"+f"(d[87]),"+f"(d[88]),"+f"(d[89]),"+f"(d[90]),"+f"(d[91]),"+f"(d[92]),"+f"(d[93]),"+f"(d[94]),"+f"(d[95]),"+f"(d[96]),"+f"(d[97]),"+f"(d[98]),"+f"(d[99]),"+f"(d[100]),"+f"(d[101]),"+f"(d[102]),"+f"(d[103]),"+f"(d[104]),"+f"(d[105]),"+f"(d[106]),"+f"(d[107]),"+f"(d[108]),"+f"(d[109]),"+f"(d[110]),"+f"(d[111]),"+f"(d[112]),"+f"(d[113]),"+f"(d[114]),"+f"(d[115]),"+f"(d[116]),"+f"(d[117]),"+f"(d[118]),"+f"(d[119]),"+f"(d[120]),"+f"(d[121]),"+f"(d[122]),"+f"(d[123]),"+f"(d[124]),"+f"(d[125]),"+f"(d[126]),"+f"(d[127])
    : "r"(da), "r"(db), "r"(sd));
}
__device__ __forceinline__ void wgmma_r1_n128(float (&d)[64], uint32_t da, uint32_t db, int sd) {
  asm volatile("{\n.reg .pred p;\n.reg .b64 a, b;\nsetp.ne.b32 p, %66, 0;\nmov.b64 a, {%64, 0x8};\nmov.b64 b, {%65, 0x6};\n"
    "wgmma.mma_async.sync.aligned.m64n128k16.f32.bf16.bf16 {%0,%1,%2,%3,%4,%5,%6,%7,%8,%9,%10,%11,%12,%13,%14,%15,%16,%17,%18,%19,%20,%21,%22,%23,%24,%25,%26,%27,%28,%29,%30,%31,%32,%33,%34,%35,%36,%37,%38,%39,%40,%41,%42,%43,%44,%45,%46,%47,%48,%49,%50,%51,%52,%53,%54,%55,%56,%57,%58,%59,%60,%61,%62,%63}, a, b, p, 1, 1, 0, 1;\n}\n"
    : "+f"(d[0]),"+f"(d[1]),"+f"(d[2]),"+f"(d[3]),"+f"(d[4]),"+f"(d[5]),"+f"(d[6]),"+f"(d[7]),"+f"(d[8]),"+f"(d[9]),"+f"(d[10]),"+f"(d[11]),"+f"(d[12]),"+f"(d[13]),"+f"(d[14]),"+f"(d[15]),"+f"(d[16]),"+f"(d[17]),"+f"(d[18]),"+f"(d[19]),"+f"(d[20]),"+f"(d[21]),"+f"(d[22]),"+f"(d[23]),"+f"(d[24]),"+f"(d[25]),"+f"(d[26]),"+f"(d[27]),"+f"(d[28]),"+f"(d[29]),"+f"(d[30]),"+f"(d[31]),"+f"(d[32]),"+f"(d[33]),"+f"(d[34]),"+f"(d[35]),"+f"(d[36]),"+f"(d[37]),"+f"(d[38]),"+f"(d[39]),"+f"(d[40]),"+f"(d[41]),"+f"(d[42]),"+f"(d[43]),"+f"(d[44]),"+f"(d[45]),"+f"(d[46]),"+f"(d[47]),"+f"(d[48]),"+f"(d[49]),"+f"(d[50]),"+f"(d[51]),"+f"(d[52]),"+f"(d[53]),"+f"(d[54]),"+f"(d[55]),"+f"(d[56]),"+f"(d[57]),"+f"(d[58]),"+f"(d[59]),"+f"(d[60]),"+f"(d[61]),"+f"(d[62]),"+f"(d[63])
    : "r"(da), "r"(db), "r"(sd));
}

__device__ __forceinline__ uint32_t smem_u32(const void* p) { return (uint32_t)__cvta_generic_to_shared(p); }
__device__ __forceinline__ void mbar_init(uint32_t bar, uint32_t cnt) { asm volatile("mbarrier.init.shared::cta.b64 [%0], %1;" ::"r"(bar), "r"(cnt)); }
__device__ __forceinline__ void mbar_expect_tx(uint32_t bar, uint32_t bytes) { asm volatile("mbarrier.arrive.expect_tx.shared::cta.b64 _, [%0], %1;" ::"r"(bar), "r"(bytes) : "memory"); }
__device__ __forceinline__ void mbar_arrive(uint32_t bar) { asm volatile("mbarrier.arrive.shared::cta.b64 _, [%0];" ::"r"(bar) : "memory"); }
__device__ __forceinline__ void mbar_arrive_n(uint32_t bar, uint32_t n) { asm volatile("mbarrier.arrive.shared::cta.b64 _, [%0], %1;" ::"r"(bar), "r"(n) : "memory"); }
__device__ __forceinline__ void mbar_wait(uint32_t bar, uint32_t parity) {
  asm volatile("{\n.reg .pred p;\nLAB_WAIT:\nmbarrier.try_wait.parity.shared::cta.b64 p, [%0], %1;\n@p bra DONE;\nbra LAB_WAIT;\nDONE:\n}" ::"r"(bar), "r"(parity) : "memory");
}
__device__ __forceinline__ void mbar_wait2(uint32_t a, uint32_t pa, uint32_t b, uint32_t pb) {
  asm volatile("{\n.reg .pred p, q;\nLAB_WAIT:\nmbarrier.try_wait.parity.shared::cta.b64 p, [%0], %1;\nmbarrier.try_wait.parity.shared::cta.b64 q, [%2], %3;\n"
               "and.pred p, p, q;\n@p bra DONE;\nbra LAB_WAIT;\nDONE:\n}" ::"r"(a), "r"(pa), "r"(b), "r"(pb) : "memory");
}
__device__ __forceinline__ void mbar_wait3(uint32_t a, uint32_t pa, uint32_t b, uint32_t pb) {
  asm volatile("{\n.reg .pred p, q, r;\nLAB_WAIT:\nmbarrier.try_wait.parity.shared::cta.b64 p, [%0], %1;\nmbarrier.try_wait.parity.shared::cta.b64 q, [%2], %3;\n"
               "mbarrier.try_wait.parity.shared::cta.b64 r, [%2+8], %3;\nand.pred p, p, q;\nand.pred p, p, r;\n@p bra DONE;\nbra LAB_WAIT;\nDONE:\n}" ::"r"(a), "r"(pa), "r"(b), "r"(pb) : "memory");
}
__device__ __forceinline__ bool mbar_probe2(uint32_t a, uint32_t pa, uint32_t b, uint32_t pb) {
  uint32_t ok;
  asm volatile("{\n.reg .pred p, q;\nmbarrier.test_wait.parity.shared::cta.b64 p, [%1], %2;\nmbarrier.test_wait.parity.shared::cta.b64 q, [%3], %4;\n"
               "and.pred p, p, q;\nselp.u32 %0, 1, 0, p;\n}" : "=r"(ok) : "r"(a), "r"(pa), "r"(b), "r"(pb) : "memory");
  return ok != 0;
}
__device__ __forceinline__ void tma_load_3d(uint32_t dst, const CUtensorMap* tm, uint32_t bar, int c0, int c1, int c2) {
  asm volatile("cp.async.bulk.tensor.3d.shared::cluster.global.mbarrier::complete_tx::bytes [%0], [%1, {%3, %4, %5}], [%2];"
               ::"r"(dst), "l"(tm), "r"(bar), "r"(c0), "r"(c1), "r"(c2) : "memory");
}
__device__ __forceinline__ void tma_load_2d(uint32_t dst, const CUtensorMap* tm, uint32_t bar, int c0, int c1) {
  asm volatile("cp.async.bulk.tensor.2d.shared::cluster.global.mbarrier::complete_tx::bytes [%0], [%1, {%3, %4}], [%2];"
               ::"r"(dst), "l"(tm), "r"(bar), "r"(c0), "r"(c1) : "memory");
}
__device__ __forceinline__ void tma_load_w(uint32_t dst, const CUtensorMap* tm, uint32_t bar, int col, int kb) {
#pragma unroll
  for (int q = 0; q < 2; q++)
    asm volatile("cp.async.bulk.tensor.5d.shared::cluster.global.mbarrier::complete_tx::bytes [%0], [%1, {%3, %4, %4, %4, %5}], [%2];"
                 ::"r"(dst + q * 8192), "l"(tm), "r"(bar), "r"(col + q * 64), "r"(0), "r"(2 * kb) : "memory");
}
__device__ __forceinline__ void tma_prefetch_w(const CUtensorMap* tm, int col, int kb) {
#pragma unroll
  for (int q = 0; q < 2; q++)
    asm volatile("cp.async.bulk.prefetch.tensor.5d.L2.global [%0, {%1, %2, %2, %2, %3}];" ::"l"(tm), "r"(col + q * 64), "r"(0), "r"(2 * kb) : "memory");
}
__device__ __forceinline__ void bulk_load(uint32_t dst, const void* g, uint32_t bytes, uint32_t bar) {
  asm volatile("cp.async.bulk.shared::cluster.global.mbarrier::complete_tx::bytes [%0], [%1], %2, [%3];" ::"r"(dst), "l"(g), "r"(bytes), "r"(bar) : "memory");
}
__device__ __forceinline__ void prefetch_map(const CUtensorMap* tm) { asm volatile("prefetch.tensormap [%0];" ::"l"(tm) : "memory"); }
__device__ __forceinline__ void fence_async_smem() { asm volatile("fence.proxy.async.shared::cta;" ::: "memory"); }
__device__ __forceinline__ void fence_async_global() { asm volatile("fence.proxy.async.global;" ::: "memory"); }
__device__ __forceinline__ void fence_gpu() { asm volatile("fence.release.gpu;" ::: "memory"); }
__device__ __forceinline__ void st_flag(unsigned* p, unsigned v) { asm volatile("st.relaxed.gpu.global.u32 [%0], %1;" ::"l"(p), "r"(v) : "memory"); }
__device__ __forceinline__ unsigned ld_flag(const unsigned* p) { unsigned v; asm volatile("ld.relaxed.gpu.global.u32 %0, [%1];" : "=r"(v) : "l"(p) : "memory"); return v; }
__device__ __forceinline__ uint4 ldcg4(const void* p) { uint4 v; asm volatile("ld.global.cg.v4.u32 {%0,%1,%2,%3}, [%4];" : "=r"(v.x), "=r"(v.y), "=r"(v.z), "=r"(v.w) : "l"(p)); return v; }
__device__ __forceinline__ uint4 ld_pkt(const uint4* p) {
  uint4 v; asm volatile("{\n.reg .b128 t;\nld.relaxed.gpu.global.b128 t, [%4];\nmov.b128 {%0,%1,%2,%3}, t;\n}" : "=r"(v.x), "=r"(v.y), "=r"(v.z), "=r"(v.w) : "l"(p) : "memory"); return v;
}
__device__ __forceinline__ void st_pkt(uint4* p, uint32_t a, uint32_t b, uint32_t c, uint32_t tag) {
  asm volatile("{\n.reg .b128 t;\nmov.b128 t, {%1,%2,%3,%4};\nst.relaxed.gpu.global.b128 [%0], t;\n}" ::"l"(p), "r"(a), "r"(b), "r"(c), "r"(tag) : "memory");
}
__device__ __forceinline__ void st_v4(uint4* p, uint32_t a, uint32_t b, uint32_t c, uint32_t d) { asm volatile("st.relaxed.gpu.global.v4.u32 [%0], {%1,%2,%3,%4};" ::"l"(p), "r"(a), "r"(b), "r"(c), "r"(d) : "memory"); }
__device__ __forceinline__ void sts32(uint32_t addr, uint32_t a) { asm volatile("st.shared.u32 [%0], %1;" ::"r"(addr), "r"(a) : "memory"); }
__device__ __forceinline__ void sts64(uint32_t addr, uint32_t a, uint32_t b) { asm volatile("st.shared.v2.u32 [%0], {%1,%2};" ::"r"(addr), "r"(a), "r"(b) : "memory"); }
__device__ __forceinline__ uint32_t mul2(uint32_t a, uint32_t b) { uint32_t r; asm("mul.rn.bf16x2 %0, %1, %2;" : "=r"(r) : "r"(a), "r"(b)); return r; }
__device__ __forceinline__ uint32_t add2(uint32_t a, uint32_t b) { uint32_t r; asm("add.rn.bf16x2 %0, %1, %2;" : "=r"(r) : "r"(a), "r"(b)); return r; }
__device__ __forceinline__ bool elect() {
  uint32_t p; asm volatile("{\n.reg .pred q;\nelect.sync _|q, 0xffffffff;\nselp.u32 %0, 1, 0, q;\n}" : "=r"(p)); return p != 0;
}
__device__ __forceinline__ void wgmma_fence() { asm volatile("wgmma.fence.sync.aligned;" ::: "memory"); }
__device__ __forceinline__ void wgmma_commit() { asm volatile("wgmma.commit_group.sync.aligned;" ::: "memory"); }
template <int N> __device__ __forceinline__ void wgmma_wait() { asm volatile("wgmma.wait_group.sync.aligned %0;" ::"n"(N) : "memory"); }
template <int N> __device__ __forceinline__ void fence_regs(float (&d)[N]) {
#pragma unroll
  for (int i = 0; i < N; i++) asm volatile("" : "+f"(d[i])::"memory");
}
template <int R> __device__ __forceinline__ void reg_alloc() { asm volatile("setmaxnreg.inc.sync.aligned.u32 %0;" ::"n"(R)); }
template <int R> __device__ __forceinline__ void reg_dealloc() { asm volatile("setmaxnreg.dec.sync.aligned.u32 %0;" ::"n"(R)); }
__device__ __forceinline__ void wg_bar(int w) { asm volatile("bar.sync %0, 128;" ::"r"(w + 1) : "memory"); }
__device__ __forceinline__ constexpr uint32_t desc_lo(uint32_t addr, uint32_t lbo) { return (addr >> 4) + ((lbo >> 4) << 16); }
__device__ __forceinline__ uint32_t pack2(float lo, float hi) { uint32_t r; asm("cvt.rn.bf16x2.f32 %0, %1, %2;" : "=r"(r) : "f"(hi), "f"(lo)); return r; }
__device__ __forceinline__ float lo16(uint32_t v) { return __uint_as_float(v << 16); }
__device__ __forceinline__ float hi16(uint32_t v) { return __uint_as_float(v & 0xFFFF0000u); }
__device__ __forceinline__ float ex2(float x) { float r; asm("ex2.approx.ftz.f32 %0, %1;" : "=f"(r) : "f"(x)); return r; }
__device__ __forceinline__ float rcp(float x) { float r; asm("rcp.approx.ftz.f32 %0, %1;" : "=f"(r) : "f"(x)); return r; }
__device__ __forceinline__ uint32_t movm(uint32_t a) { uint32_t d; asm volatile("movmatrix.sync.aligned.m8n8.trans.b16 %0, %1;" : "=r"(d) : "r"(a)); return d; }
__device__ __forceinline__ void stsm4(uint32_t addr, uint32_t a, uint32_t b, uint32_t c, uint32_t d) {
  asm volatile("stmatrix.sync.aligned.m8n8.x4.shared.b16 [%0], {%1,%2,%3,%4};" ::"r"(addr), "r"(a), "r"(b), "r"(c), "r"(d) : "memory");
}
__device__ __forceinline__ void ldsm4(uint32_t addr, uint32_t (&r)[4]) {
  asm volatile("ldmatrix.sync.aligned.m8n8.x4.shared.b16 {%0,%1,%2,%3}, [%4];" : "=r"(r[0]), "=r"(r[1]), "=r"(r[2]), "=r"(r[3]) : "r"(addr) : "memory");
}
__device__ __forceinline__ void sts128(uint32_t addr, uint32_t a, uint32_t b, uint32_t c, uint32_t d) {
  asm volatile("st.shared.v4.u32 [%0], {%1,%2,%3,%4};" ::"r"(addr), "r"(a), "r"(b), "r"(c), "r"(d) : "memory");
}
__device__ __forceinline__ void lds128(uint32_t addr, uint32_t& a, uint32_t& b, uint32_t& c, uint32_t& d) {
  asm volatile("ld.shared.v4.u32 {%0,%1,%2,%3}, [%4];" : "=r"(a), "=r"(b), "=r"(c), "=r"(d) : "r"(addr) : "memory");
}
__device__ __forceinline__ float lds32f(uint32_t addr) { float v; asm volatile("ld.shared.f32 %0, [%1];" : "=f"(v) : "r"(addr) : "memory"); return v; }
__device__ __forceinline__ float2 lds64f(uint32_t addr) { float2 v; asm volatile("ld.shared.v2.f32 {%0,%1}, [%2];" : "=f"(v.x), "=f"(v.y) : "r"(addr) : "memory"); return v; }
__device__ __forceinline__ void mma16816(float (&d)[4], uint32_t a0, uint32_t a1, uint32_t a2, uint32_t a3, uint32_t b0, uint32_t b1) {
  asm("mma.sync.aligned.m16n8k16.row.col.f32.bf16.bf16.f32 {%0,%1,%2,%3}, {%4,%5,%6,%7}, {%8,%9}, {%0,%1,%2,%3};"
      : "+f"(d[0]), "+f"(d[1]), "+f"(d[2]), "+f"(d[3]) : "r"(a0), "r"(a1), "r"(a2), "r"(a3), "r"(b0), "r"(b1));
}
__device__ __forceinline__ void mma1688(float (&d)[4], uint32_t a0, uint32_t a1, uint32_t b0) {
  asm("mma.sync.aligned.m16n8k8.row.col.f32.bf16.bf16.f32 {%0,%1,%2,%3}, {%4,%5}, {%6}, {%0,%1,%2,%3};"
      : "+f"(d[0]), "+f"(d[1]), "+f"(d[2]), "+f"(d[3]) : "r"(a0), "r"(a1), "r"(b0));
}

__device__ __forceinline__ float qsum(float v) { v += __shfl_xor_sync(0xffffffffu, v, 1); v += __shfl_xor_sync(0xffffffffu, v, 2); return v; }

constexpr int NCTA = 132;
#define NB_ 6
#define NA_ 5
constexpr int NB = NB_;
constexpr int NA = NA_;
constexpr uint32_t SLOT = 16384;
constexpr uint32_t SB = 1024;
constexpr uint32_t OFF_B = 0;
constexpr uint32_t OFF_A = NB * SLOT;
constexpr uint32_t OFF_S = OFF_A + NA * SLOT;
constexpr uint32_t OFF_T = OFF_S + 20480;
constexpr uint32_t OFF_CS = OFF_T + 24576;
constexpr uint32_t OFF_MR = OFF_CS + 4640;
constexpr uint32_t OFF_BAR = OFF_MR + 512;
constexpr uint32_t OFF_MA = OFF_S, OFF_MB = OFF_CS - 2048;
constexpr uint32_t BAR_FULLB = OFF_BAR;
constexpr uint32_t BAR_FULLA = BAR_FULLB + 64;
constexpr uint32_t BAR_EMPTYB = BAR_FULLA + 64;
constexpr uint32_t BAR_EMPTYA = BAR_EMPTYB + 64;
constexpr uint32_t BAR_SIGP = BAR_EMPTYA + 64;
constexpr uint32_t BAR_SIGT = BAR_SIGP + 32;
constexpr uint32_t BAR_STAT = BAR_SIGP + 64;
constexpr uint32_t BAR_HALO = BAR_STAT + 16;
constexpr uint32_t BAR_CS = BAR_HALO + 8;
constexpr uint32_t BAR_WPHI = BAR_CS + 16;
constexpr uint32_t BAR_KV = BAR_WPHI + 8;
constexpr uint32_t BAR_STG = BAR_KV + 16;
constexpr uint32_t BAR_EPOCH = BAR_STG + 48;
constexpr uint32_t OFF_EPOCH = OFF_BAR + 7 * 64;
static_assert(BAR_EPOCH < OFF_EPOCH, "barriers");
constexpr uint32_t SMEM_BYTES = OFF_EPOCH + 8;
static_assert(SMEM_BYTES <= 232448 && NB % 2 == 0 && NB <= 8 && NA <= 6, "smem");

#define CREGS 208
#define PREGS 88
#define PF0 9
#define PF1 13
#define PF2 17
#define PRE_A 2
#define PRE_B 4
#define CSB 4
#define CSNEED 0xF003u
#define XR 2
#define PS0 2
#define PS1 2
#define PSW 0
#define STG0 0
#define QORD 1
#define KSPLIT 12
#define KEEP 16
#define NJ 3
#define LEAD 0
#define KSL 1000
#define PSL 0
#define KVS 10
#define RH 0
#define D2 2000
#define D3 1500
#define G0 50
#define G3 50
#define G1 0
#define G4 0
#define KB 8
#define PNX 2
#define PNO 2
#define DEFER 3
#define DEFL 2
#define TSK 3
#define TSL 3
constexpr int NTHREADS = 384;

struct Params {
  CUtensorMap mx;
  CUtensorMap mw[3];
  CUtensorMap mwo[2];
  CUtensorMap mcs[2];
  CUtensorMap mwphi;
  uint4* out;
};

#define XBUF(L) 1
__device__ __align__(256) uint4 g_img[XBUF(3) + 1][16][16][1024];
__device__ __align__(256) uint4 g_wf[2][8][16][1024];
__device__ __align__(256) uint4 g_stats[16][2][8][32];
__device__ __align__(256) uint4 g_halo[16][8][2][256];
__device__ __align__(256) float g_cs[2][2][3072];
__device__ __align__(256) uint4 g_kvpart[8][16][2][544];
__device__ __align__(256) uint4 g_kvfin[8][16][80];
__device__ __align__(256) unsigned g_xflag[4][2][16][32];
__device__ __align__(256) unsigned g_oflag[4][2][16][32];
__device__ __align__(256) unsigned g_hflag[2][16][8][32];
__device__ __align__(256) unsigned g_kvfflag[2][8][2][32];
__device__ __align__(256) unsigned g_csflag[2][8][32];
__device__ __align__(256) unsigned g_kflag[8][32];
__device__ unsigned g_ctr;
__device__ __forceinline__ unsigned vblock() {
  unsigned s;
  asm volatile("mov.u32 %0, %%smid;" : "=r"(s));
  const unsigned r = s & 1;
  s >>= 1;
  const unsigned t = s - 32, q = (t * 37) >> 8;
  const unsigned hi = s < 60 ? 12 + (t - 7 * q) * 8 + q : (s < 62 ? s + 4 : s - 58);
  return __shfl_sync(0xffffffffu, 2 * (s < 32 ? (s & 7) * 8 + (s >> 3) : hi) + r, 0);
}
#define TS(who, id) do {} while (0)
#define TSW(id) do {} while (0)

__device__ __forceinline__ int cta_m(unsigned b) { return ((b >> 2) & 12) | (b & 3); }
__device__ __forceinline__ int cta_j(unsigned b) { return ((b >> 2) & 3) | ((b >> 4) & 4); }
struct Ring { uint32_t s, ph; };
template <int N> __device__ __forceinline__ void adv(Ring& r) { if (++r.s == N) { r.s = 0; r.ph ^= 1; } }
template <int N> __device__ __forceinline__ void rewind2(Ring& r) { if (r.s < 2) { r.s += N - 2; r.ph ^= 1; } else r.s -= 2; }
__device__ __forceinline__ int other_tile(int t, int j) { return (t == (j | 4) ? 7 : t) ^ (~j & 4); }
__device__ __forceinline__ int q_order(int i, int j) { return 2 * (i >= 14 ? j : other_tile(i >> 1, j)) + (i & 1); }
__device__ __forceinline__ int o_order(int i, int j) {
  if (i < 2) return 2 * j + i;
  const int odd = i >= 9;
  return 2 * other_tile(i - 2 - 7 * odd, j) + odd;
}
__device__ __forceinline__ int kv_order(int i, int j, int L) { return L > 0 ? o_order(i, j) : (i + 14 + 2 * (j & 4)) & 15; }

__device__ __forceinline__ unsigned poll_flags(const unsigned* f, int n, unsigned need, unsigned tag) {
  const int lane = threadIdx.x & 31;
  unsigned mask; int it = 0;
  do {
    unsigned v = lane < n ? ld_flag(f + lane) : 0u;
    mask = __ballot_sync(0xffffffffu, lane < n && v == tag);
    if (++it > (1 << 22)) __trap();
  } while ((mask & need) != need);
  fence_async_global();
  return mask;
}
template <bool WAIT = true>
__device__ __forceinline__ unsigned get_tag(uint32_t sb) {
  if (WAIT) mbar_wait(sb + BAR_EPOCH, 0);
  unsigned t; asm volatile("ld.shared.u32 %0, [%1];" : "=r"(t) : "r"(sb + OFF_EPOCH) : "memory");
  return t;
}

__device__ __forceinline__ int lane_id() { int l; asm volatile("mov.u32 %0, %%laneid;" : "=r"(l)); return l; }
__device__ __forceinline__ unsigned seq4(unsigned tag, int L) { return 8u | ((tag & 1u) << 2) | (unsigned)L; }
constexpr float LOG2E = 1.4426950408889634f;

__device__ __forceinline__ void sched_fence(uint32_t sb) { mbar_wait(sb + BAR_EPOCH, 0); }
constexpr uint32_t HA128 = 0x40000040u, HA64 = 0x80000040u;
struct Ctx {
  static constexpr uint32_t sb = SB;
  uint32_t ab, da0;
  int w, warp, lane, g, c;
  int goff;
  __device__ __forceinline__ int m() const { return goff >> 14; }
  __device__ __forceinline__ int j() const { return (goff >> 4) & 7; }
  bool elected;
  Ring ra, rb;
  uint32_t pa, pb;
  uint32_t ha, k2;
  uint32_t mrow, mxor, mhi;
  __device__ __forceinline__ uint32_t aslot(uint32_t s) const { return ab + s * SLOT; }
  __device__ __forceinline__ uint32_t fullA(uint32_t s) const { return sb + BAR_FULLA + s * 8; }
  __device__ __forceinline__ uint32_t fullB(uint32_t s) const { return sb + BAR_FULLB + s * 8; }
  __device__ __forceinline__ void releaseA(uint32_t s) const { if (elected) mbar_arrive(sb + BAR_EMPTYA + s * 8); }
  __device__ __forceinline__ void releaseB(uint32_t s) const { if (elected) mbar_arrive(sb + BAR_EMPTYB + s * 8); }
  __device__ __forceinline__ uint32_t maddr(uint32_t tile, uint32_t ch) const { return tile + mrow + (((ch + mhi) ^ mxor) << 4); }
  __device__ __forceinline__ uint32_t oo() const { return warp * 128 + g * 4 + (c ^ (g >> 1)); }
  __device__ __forceinline__ uint4* img(int b, int hp) const { return &g_img[b][m()][2 * j() + hp][w * 512 + oo()]; }
  __device__ __forceinline__ uint32_t held(int i) const { return ra.s + i < 2 ? ra.s + i + NA - 2 : ra.s + i - 2; }
};

template <int N, bool FIRST, bool O = true>
__device__ __forceinline__ void gemm_issue(float (&acc)[N / 2], Ctx& x, bool ready = false) {
  if (!ready) {
    if (N == 256) mbar_wait3(x.fullA(x.ra.s), x.ra.ph, x.fullB(x.rb.s), x.rb.ph);
    else mbar_wait2(x.fullA(x.ra.s), x.ra.ph, x.fullB(x.rb.s), x.rb.ph);
  }
  const uint32_t da = x.da0 + x.ra.s * (SLOT / 16), db = desc_lo(SB + OFF_B, 8192) + x.rb.s * (SLOT / 16);
  wgmma_fence();
#pragma unroll
  for (int k = 0; k < 4; k++) {
    const uint32_t a = da + (k >> 1) * (O ? 32 : x.k2) + (k & 1) * 2, ha = O ? HA64 : x.ha;
    if constexpr (N == 256) wgmma_ss_n256(acc, a, ha, db + 128 * k, !(FIRST && k == 0));
    else wgmma_ss_n128(acc, a, ha, db + 128 * k, !(FIRST && k == 0));
  }
  wgmma_commit();
}
template <int N>
__device__ __forceinline__ void gemm_next(Ctx& x) {
  x.pa = x.ra.s; x.pb = x.rb.s;
  if (N == 256) x.rb.s++;
  adv<NA>(x.ra); adv<NB>(x.rb);
}
template <int N>
__device__ __forceinline__ void gemm_release(Ctx& x, bool relA) {
  if (relA) x.releaseA(x.pa);
  x.releaseB(x.pb);
  if (N == 256) x.releaseB(x.pb + 1);
}
template <int N>
__device__ __forceinline__ void gemm_retire(Ctx& x, bool relA) { wgmma_wait<1>(); gemm_release<N>(x, relA); gemm_next<N>(x); }
template <bool O = true>
__device__ __forceinline__ void gemm_run(float (&acc)[64], Ctx& x, int n, int hold, int n4 = 0) {
  bool ready = false;
#pragma unroll 1
  for (; n > 0; n--) {
    gemm_issue<128, false, O>(acc, x, ready);
    const uint32_t pa = x.pa, pb = x.pb;
    gemm_next<128>(x);
    ready = mbar_probe2(x.fullA(x.ra.s), x.ra.ph, x.fullB(x.rb.s), x.rb.ph);
    wgmma_wait<1>();
    if (n > hold) x.releaseA(pa);
    x.releaseB(pb);
  }
}
__device__ __forceinline__ void gemm_end(float (&acc)[64], Ctx& x) { wgmma_wait<0>(); fence_regs(acc); gemm_release<128>(x, false); }

__device__ __forceinline__ void load_x32(float* a, uint32_t tile, uint32_t ch, const Ctx& x) {
#pragma unroll
  for (int p = 0; p < 2; p++) {
    uint32_t v[4];
    ldsm4(x.maddr(tile, ch + 2 * p), v);
#pragma unroll
    for (int i = 0; i < 4; i++) { a[8 * p + 2 * i] = lo16(v[i]); a[8 * p + 2 * i + 1] = hi16(v[i]); }
  }
}

__device__ __forceinline__ void rows_load(uint4* r, uint32_t tile, const Ctx& x) {
#pragma unroll
  for (int q = 0; q < 4; q++) {
    const uint32_t row = x.warp * 16 + 4 * q + (x.lane >> 3);
    lds128(tile + row * 128 + (((x.lane & 7) ^ (row & 7)) << 4), r[q].x, r[q].y, r[q].z, r[q].w);
  }
}
__device__ __forceinline__ void rows_store(const uint4* r, uint4* g, const Ctx& x) {
  g += (x.warp * 16 + (x.lane >> 3)) * 256 + (x.lane & 7);
#pragma unroll
  for (int q = 0; q < 4; q++) g[q * 1024] = r[q];
}
__device__ __forceinline__ void publish(int id, const Ctx& x) { __syncwarp(); if (x.lane == 0) mbar_arrive(x.sb + BAR_SIGP + id * 8); }
__device__ __forceinline__ void img_store(const uint4 (&r)[4], uint4* g) {
#pragma unroll
  for (int q = 0; q < 4; q++) g[q * 32] = r[q];
}
__device__ __forceinline__ void img_sts(const uint4 (&r)[4], uint32_t tile, const Ctx& x) {
#pragma unroll
  for (int q = 0; q < 4; q++) sts128(tile + x.oo() * 16 + q * 512, r[q].x, r[q].y, r[q].z, r[q].w);
}
__device__ __forceinline__ void img_load(uint32_t (&v)[16], uint32_t tile, const Ctx& x) {
#pragma unroll
  for (int q = 0; q < 4; q++) lds128(tile + x.oo() * 16 + q * 512, v[4 * q], v[4 * q + 1], v[4 * q + 2], v[4 * q + 3]);
}
__device__ __forceinline__ void img_unpack(float* a, const uint32_t (&v)[16]) {
#pragma unroll
  for (int q = 0; q < 16; q++) { a[4 * (q & 7) + 2 * (q >> 3)] = lo16(v[q]); a[4 * (q & 7) + 2 * (q >> 3) + 1] = hi16(v[q]); }
}

template <int N>
__device__ __forceinline__ void stats_acc(const float* a, float (&t)[4]) {
#pragma unroll
  for (int i = 0; i < N; i++) { t[i & 2] += a[i]; t[(i & 2) + 1] = fmaf(a[i], a[i], t[(i & 2) + 1]); }
}
__device__ __forceinline__ void stats_send(float (&t)[4], int L, const Ctx& x) {
  const unsigned seq = seq4(get_tag<false>(x.sb), L);
#pragma unroll
  for (int q = 0; q < 4; q++) t[q] = qsum(t[q]);
  if (x.c == 0) st_pkt(&g_stats[x.m()][x.w][x.j()][x.warp * 8 + x.g], __float_as_uint(t[0]), __float_as_uint(t[1]), __float_as_uint(t[2]), (__float_as_uint(t[3]) & ~15u) | seq);
}
__device__ __forceinline__ void out_epilogue(const float (&acc)[64], uint4 (&r1)[4], uint4* g, int L, Ctx& x) {
  const uint32_t t0 = x.aslot(x.ra.s), t1 = x.aslot(x.ra.s + 1 == NA ? 0 : x.ra.s + 1);
  if (L == 3) {
#pragma unroll
    for (int p = 0; p < 8; p++) {
      stsm4(x.maddr(p < 4 ? t0 : t1, (p & 3) * 2), pack2(acc[8 * p], acc[8 * p + 1]), pack2(acc[8 * p + 2], acc[8 * p + 3]),
            pack2(acc[8 * p + 4], acc[8 * p + 5]), pack2(acc[8 * p + 6], acc[8 * p + 7]));
      if ((p & 3) == 3) { uint4 r[4]; __syncwarp(); rows_load(r, p < 4 ? t0 : t1, x); rows_store(r, g + (p >> 2) * 8, x); }
    }
  } else {
    auto pack16 = [&](uint4 (&r)[4], const float* a) {
#pragma unroll
      for (int q = 0; q < 4; q++) { const float* u = a + 16 * (q & 1) + (q & 2); r[q] = make_uint4(pack2(u[0], u[1]), pack2(u[4], u[5]), pack2(u[8], u[9]), pack2(u[12], u[13])); }
    };
    uint4 r0[4];
    pack16(r0, acc);
    img_store(r0, x.img(XBUF(L + 1), 0));
    publish(2, x);
    img_sts(r0, t0, x);
    sched_fence(x.sb);
    pack16(r1, acc + 32);
    img_sts(r1, t1, x);
    float t[4] = {0.f, 0.f, 0.f, 0.f}, u[4] = {0.f, 0.f, 0.f, 0.f};
    stats_acc<32>(acc, t); stats_acc<32>(acc + 32, u);
#pragma unroll
    for (int q = 0; q < 4; q++) t[q] += u[q];
    stats_send(t, L + 1, x);
    fence_async_smem();
    asm volatile("bar.sync %0, %1;" ::"r"(L == 1 ? x.w + 1 : 3), "r"(L == 1 ? 128 : 256) : "memory");
  }
}

struct Stats { float rstd0, rstd1; };
__device__ __forceinline__ Stats load_stats(int half, const Ctx& x) {
  const float2 u = lds64f(x.sb + OFF_MR + half * 256 + (x.warp * 8 + x.g) * 8);
  return {u.x, u.y};
}

template <int NK>
__device__ __forceinline__ void hedgehog_scale(float* t, const Stats& st, const uint32_t* keep) {
#pragma unroll
  for (int q = 0; q < 16; q++) t[q] *= ((q & 2) ? st.rstd1 : st.rstd0) * LOG2E;
  float m[4];
#pragma unroll
  for (int q = 0; q < 4; q++) m[q] = fmaxf(fmaxf(fabsf(t[4 * q]), fabsf(t[4 * q + 1])), fmaxf(fabsf(t[4 * q + 2]), fabsf(t[4 * q + 3])));
  if (__builtin_expect(__any_sync(0xffffffffu, fmaxf(fmaxf(m[0], m[1]), fmaxf(m[2], m[3])) > 58.f), 0)) {
    float z[16 + NK];
#pragma unroll
    for (int q = 0; q < 16 + NK; q++) z[q] = q < 16 ? t[q & 15] : __uint_as_float(keep[q & 15]);
#pragma unroll 1
    for (int r = 0; r < 4; r += 2) {
      float hi = -INFINITY, lo = INFINITY;
#pragma unroll 1
      for (int i = 0; i < 16; i++) {
        const int k = (i & 6) * 2 + (i & 1) + r;
        const float v = z[k];
        if (i < 8) { hi = fmaxf(hi, v); lo = fminf(lo, v); }
        else z[k] = v - fminf(fmaxf(v, lo), hi);
        if (i == 7) {
#pragma unroll 1
          for (int d = 1; d <= 2; d++) { hi = fmaxf(hi, __shfl_xor_sync(0xffffffffu, hi, d)); lo = fminf(lo, __shfl_xor_sync(0xffffffffu, lo, d)); }
          const float mid = 0.5f * hi + 0.5f * lo;
          hi = fmaxf(hi - 58.f, mid); lo = fminf(lo + 58.f, mid);
        }
      }
    }
#pragma unroll
    for (int q = 0; q < 16; q++) t[q] = z[q];
  }
}
__device__ __forceinline__ void dual_exp(const float* t, uint32_t (&f)[18], int never) {
  float e[KSPLIT];
#pragma unroll
  for (int q = 0; q < KSPLIT; q++) e[q] = ex2(q < 16 ? t[q] : -t[q & 15]);
  while (never < 0) {
#pragma unroll
    for (int i = 0; i < KSPLIT; i += 4) asm volatile("ld.shared.v4.f32 {%0,%1,%2,%3}, [%4];" : "=f"(e[i]), "=f"(e[i + 1]), "=f"(e[i + 2]), "=f"(e[i + 3]) : "r"(never + i) : "memory");
    never += __float_as_int(e[0]);
  }
#pragma unroll
  for (int q = 0; q < KSPLIT; q += 2) f[q >> 1] = pack2(e[q], e[q + 1]);
#pragma unroll
  for (int q = KSPLIT; q < 32; q += 2) f[q >> 1] = q < 16 ? pack2(ex2(t[q]), ex2(t[q + 1])) : pack2(ex2(-t[q & 15]), ex2(-t[(q & 15) + 1]));
#pragma unroll
  for (int sg = 0; sg < 2; sg++) {
    const uint32_t* u = f + 8 * sg;
    const uint32_t a = add2(add2(u[0], u[2]), add2(u[4], u[6])), b = add2(add2(u[1], u[3]), add2(u[5], u[7]));
    f[16 + sg] = add2(__byte_perm(a, b, 0x5410), __byte_perm(a, b, 0x7632));
  }
}
__device__ __forceinline__ void dual_exp_rcp(const float* t, uint32_t (&f)[16]) {
#pragma unroll
  for (int q = 0; q < 8; q++) {
    const float a = ex2(t[2 * q]), b = ex2(t[2 * q + 1]), r = rcp(a * b);
    f[q] = pack2(a, b); f[8 + q] = pack2(r * b, r * a);
  }
}
__device__ __forceinline__ void cta_bar() { asm volatile("bar.sync 3, 256;" ::: "memory"); }

template <int N> __device__ __forceinline__ void pin(const uint32_t* v, uint32_t addr) {
#pragma unroll
  for (int i = 0; i < N; i += 4)
    asm volatile("{\n.reg .pred p;\nsetp.eq.u32 p, %0, 0;\n@p st.shared.v4.u32 [%0], {%1,%2,%3,%4};\n}" ::"r"(addr), "r"(v[i]), "r"(v[i + 1]), "r"(v[i + 2]), "r"(v[i + 3]) : "memory");
}

__device__ __forceinline__ void consumer(const Params& P, uint32_t sb, int w, unsigned vb) {
  Ctx x;
  x.w = w;
  x.ab = sb + OFF_A + w * 8192; x.da0 = desc_lo(SB + OFF_A, 16) + w * 512;
  x.lane = threadIdx.x & 31; x.warp = __shfl_sync(0xffffffffu, (threadIdx.x >> 5) & 3, 0); x.g = x.lane >> 2; x.c = x.lane & 3;
  x.goff = (cta_m(vb) * 128 + w) * 128 + cta_j(vb) * 16;
  asm volatile("" : "+r"(x.goff));
  x.elected = (threadIdx.x & 127) == 0;
  x.ra = {0, 0}; x.rb = {0, 0}; x.pa = x.pb = 0;
  {
    const uint32_t row = x.warp * 16 + (x.lane & 15);
    x.mrow = row * 128; x.mxor = row & 7; x.mhi = x.lane >> 4;
  }
  const int goff = x.goff;
  uint4 r1[4];
#pragma unroll
  for (int i = 0; i < 4; i++) r1[i] = make_uint4(0, 0, 0, 0);
  TSW(0);
#pragma unroll 1
  for (int L = 0; L < 4; L++) {
    float acc[64];
    constexpr uint32_t dcs = desc_lo(SB + OFF_CS, 0);
    if ((L & 1) == 0) {
    float kv[128];
    x.ha = L ? HA64 : HA128; x.k2 = L ? 32 : 4;
    gemm_issue<256, true, false>(kv, x); gemm_next<256>(x);
    {
      int i = 1;
      bool rel = true;
      float t[4] = {0.f, 0.f, 0.f, 0.f};
#pragma unroll 1
      for (int seg = 0; seg < 3; seg++) {
        const int end = seg < 2 ? (L == 0 ? 3 + 2 * (x.j() & 3) + seg : 2 + seg * 2) : 14 + L;
#pragma unroll 1
        while (true) {
          gemm_issue<256, false, false>(kv, x);
          if (++i == end) break;
          wgmma_wait<1>();
          if (rel) gemm_release<256>(x, true);
          rel = true;
          gemm_next<256>(x);
          if (i == 5) TSW(8 + L * 12);
          if (i == 11) TSW(10 + L * 12);
        }
        if (seg < 2 && L == 0) {
          float a[32];
          const uint32_t tile = x.aslot(x.ra.s);
          load_x32(a, tile, 0, x); load_x32(a + 16, tile, 4, x);
          stats_acc<32>(a, t);
          if (seg == 1) { mbar_wait(sb + BAR_EPOCH, 0); stats_send(t, 0, x); }
          fence_async_smem();
          wg_bar(w);
        }
        if (seg == 1 && L > 0) { img_store(r1, x.img(XBUF(L), 1)); publish(3, x); }
        wgmma_wait<1>();
        if (rel) gemm_release<256>(x, true);
        rel = true;
        gemm_next<256>(x);
        if (seg == 0 && L > 0) { wgmma_wait<0>(); gemm_release<256>(x, true); rel = false; }
      }
    }
      const Ring kt = x.ra;
      if (L == 0) adv<NA>(x.ra);
#pragma unroll 1
      for (int h = L; h < 2; h++) {
        float d[16];
        mbar_wait2(x.fullA(kt.s), kt.ph, sb + BAR_WPHI, 0);
        wgmma_fence();
#pragma unroll
        for (int q = 0; q < 2; q++) wgmma_ss_n32(d, x.da0 + kt.s * (SLOT / 16) + h * 4 + q * 2, desc_lo(SB + OFF_S + 4096, 512) + w * 256 + h * 128 + q * 64, q);
        wgmma_commit();
        gemm_issue<256, false, false>(kv, x);
        gemm_retire<256>(x, true);
        if (h) x.releaseA(kt.s);
        fence_regs(d);
        uint4* dst = &g_wf[1][x.j()][x.m()][w * 512 + (x.warp * 16 + x.g) * 8 + ((h * 4 + x.c) ^ x.g)];
        dst[0] = make_uint4(pack2(d[0], d[1]), pack2(d[4], d[5]), pack2(d[8], d[9]), pack2(d[12], d[13]));
        dst[64] = make_uint4(pack2(d[2], d[3]), pack2(d[6], d[7]), pack2(d[10], d[11]), pack2(d[14], d[15]));
      }
      const uint32_t dm = desc_lo(SB + OFF_MA, 0) + w * 64;
      mbar_wait2(sb + BAR_STAT, 0, sb + BAR_CS, 0);
      wgmma_fence();
      wgmma_r1_n256(kv, dm, dcs + 96, 1);
      wgmma_commit();
      const Stats st = load_stats(w, x);
      wgmma_wait<0>();
      fence_regs(kv);
      gemm_release<256>(x, true);
      TSW(2 + L * 12);
      uint32_t P0[32], P1[32], PH[32];
#pragma unroll
      for (int t = 0; t < 16; t++) { P0[t] = pack2(kv[4 * t] * st.rstd0, kv[4 * t + 1] * st.rstd0); P1[t] = pack2(kv[4 * t + 2] * st.rstd1, kv[4 * t + 3] * st.rstd1); }
      pin<16>(P0, x.mrow + 16);
      {
#pragma unroll
        for (int q = 0; q < 4; q++) sts128((x.warp < 3 ? sb + OFF_T + w * 12288 + x.warp * 4096 : sb + OFF_S + 16384 + w * 2048) + x.lane * 16 + q * 512, P1[4 * q], P1[4 * q + 1], P1[4 * q + 2], P1[4 * q + 3]);
      }
      wgmma_fence();
      wgmma_r1_n128(acc, dm, dcs, 0);
      gemm_issue<128, false, false>(acc, x); gemm_next<128>(x);
      TSW(3 + L * 12);
#pragma unroll
      for (int s = 0; s < 4; s++) {
#pragma unroll
        for (int t = 16 + 8 * (s & 1); t < 24 + 8 * (s & 1); t++) {
          if (s < 2) P1[t] = movm(pack2(kv[4 * t + 2] * st.rstd1, kv[4 * t + 3] * st.rstd1));
          else P0[t] = movm(pack2(kv[4 * t] * st.rstd0, kv[4 * t + 1] * st.rstd0));
        }
        if (s < 3) { gemm_issue<128, false, false>(acc, x); gemm_retire<128>(x, true); }
        if (s == 1) {
          if (x.warp < 3) {
#pragma unroll
            for (int q = 4; q < 8; q++) sts128(sb + OFF_T + w * 12288 + x.warp * 4096 + x.lane * 16 + q * 512, P1[4 * q], P1[4 * q + 1], P1[4 * q + 2], P1[4 * q + 3]);
          } else {
            uint4* dst = &g_halo[x.m()][x.j()][w][x.lane];
#pragma unroll
            for (int q = 0; q < 8; q++) dst[q * 32] = make_uint4(P1[4 * q], P1[4 * q + 1], P1[4 * q + 2], P1[4 * q + 3]);
          }
          publish(4, x);
          gemm_issue<128, false, false>(acc, x);
          gemm_retire<128>(x, true);
        }
      }
      TSW(4 + L * 12);
      gemm_run<false>(acc, x, 10, 0);
      gemm_issue<128, false, false>(acc, x);
      {
        wg_bar(w);
        uint32_t tr = sb + OFF_T + w * 12288 + (x.warp - 1) * 4096;
        if (x.warp == 0) {
          tr = x.m() > 0 ? sb + OFF_S + 8192 + w * 4096 : tr + 4096;
          if (x.m() > 0) mbar_wait(sb + BAR_HALO, L >> 1);
        }
#pragma unroll
        for (int q = 0; q < 8; q++) lds128(tr + x.lane * 16 + q * 512, PH[4 * q], PH[4 * q + 1], PH[4 * q + 2], PH[4 * q + 3]);
      }
      gemm_retire<128>(x, false);
      gemm_end(acc, x);
      TSW(5 + L * 12);
      const bool first = (x.m() == 0) && (x.warp == 0);
      const bool hi0 = 2 * x.c > x.g, hi1 = 2 * x.c + 1 > x.g;
      const uint32_t mhi = (hi0 ? 0xFFFFu : 0u) | (hi1 ? 0xFFFF0000u : 0u);
      const float sc0 = st.rstd0 * (0.17677669529663687f * LOG2E), sc1 = st.rstd1 * (0.17677669529663687f * LOG2E);
#pragma unroll
      for (int hp = 0; hp < 2; hp++) {
        const uint32_t tile = x.aslot(x.held(hp));
        uint32_t px[2], py[2];
        float s[2][3][4];
#pragma unroll
        for (int u = 0; u < 2; u++) {
#pragma unroll
          for (int q = 0; q < 12; q++) s[u][q >> 2][q & 3] = 0.f;
#pragma unroll
          for (int ks = 0; ks < 2; ks++) {
            const int t = 8 * hp + 4 * u + 2 * ks;
            const uint32_t a0 = pack2(acc[4 * t], acc[4 * t + 1]), a1 = pack2(acc[4 * t + 2], acc[4 * t + 3]);
            const uint32_t a2 = pack2(acc[4 * t + 4], acc[4 * t + 5]), a3 = pack2(acc[4 * t + 6], acc[4 * t + 7]);
            mma16816(s[u][0], a0, a1, a2, a3, PH[t], PH[t + 1]);
            mma16816(s[u][1], a0, a1, a2, a3, P0[t], P0[t + 1]);
            mma16816(s[u][2], a0, a1, a2, a3, P1[t], P1[t + 1]);
          }
        }
        float e[2][4], r[2][2];
#pragma unroll
        for (int u = 0; u < 2; u++) {
          e[u][0] = (hi0 ? s[u][0][0] : s[u][1][0]) * sc0; e[u][1] = (hi1 ? s[u][0][1] : s[u][1][1]) * sc0;
          e[u][2] = (hi0 ? s[u][1][2] : s[u][2][2]) * sc1; e[u][3] = (hi1 ? s[u][1][3] : s[u][2][3]) * sc1;
          if (first) { if (hi0) e[u][0] = -1e30f; if (hi1) e[u][1] = -1e30f; }
          r[u][0] = fmaxf(e[u][0], e[u][1]); r[u][1] = fmaxf(e[u][2], e[u][3]);
        }
#pragma unroll
        for (int d = 1; d <= 2; d++)
#pragma unroll
          for (int q = 0; q < 4; q++) r[q >> 1][q & 1] = fmaxf(r[q >> 1][q & 1], __shfl_xor_sync(0xffffffffu, r[q >> 1][q & 1], d));
#pragma unroll
        for (int u = 0; u < 2; u++) {
#pragma unroll
          for (int q = 0; q < 4; q++) e[u][q] = ex2(e[u][q] - r[u][q >> 1]);
          r[u][0] = e[u][0] + e[u][1]; r[u][1] = e[u][2] + e[u][3];
        }
#pragma unroll
        for (int d = 1; d <= 2; d++)
#pragma unroll
          for (int q = 0; q < 4; q++) r[q >> 1][q & 1] += __shfl_xor_sync(0xffffffffu, r[q >> 1][q & 1], d);
#pragma unroll
        for (int u = 0; u < 2; u++) {
          const float rx = rcp(r[u][0]), ry = rcp(r[u][1]);
          px[u] = pack2(e[u][0] * rx, e[u][1] * rx); py[u] = pack2(e[u][2] * ry, e[u][3] * ry);
        }
        uint32_t o[8][2];
        uint4 ro[4];
#pragma unroll
        for (int q = 0; q < 8; q++) {
          float d[4] = {0.f, 0.f, 0.f, 0.f};
          const int t = 16 + 8 * hp + q, u = q >> 2;
          mma16816(d, px[u] & mhi, 0u, px[u] & ~mhi, py[u] & mhi, PH[t], P0[t]);
          mma1688(d, 0u, py[u] & ~mhi, P1[t]);
          o[q][0] = pack2(d[0], d[1]); o[q][1] = pack2(d[2], d[3]);
        }
#pragma unroll
        for (int q = 0; q < 4; q++) ro[q] = make_uint4(o[4 * (q & 1)][q >> 1], o[4 * (q & 1) + 1][q >> 1], o[4 * (q & 1) + 2][q >> 1], o[4 * (q & 1) + 3][q >> 1]);
        img_store(ro, x.img(0, hp));
        publish(hp, x);
        uint32_t xr[16];
        if (L) img_load(xr, tile, x);
        else {
#pragma unroll
          for (int q = 0; q < 4; q++) {
            uint32_t v[4];
            ldsm4(x.maddr(tile, 2 * q), v);
            xr[2 * q] = v[0]; xr[8 + 2 * q] = v[1]; xr[2 * q + 1] = v[2]; xr[9 + 2 * q] = v[3];
          }
          __syncwarp();
        }
        img_sts(ro, tile, x);
        img_unpack(acc + 32 * hp, xr);
      }
    } else {
      float kv[128];
      float (&kv0)[64] = reinterpret_cast<float (&)[64]>(kv[0]);
      float (&kv1)[64] = reinterpret_cast<float (&)[64]>(kv[64]);
      auto mma8 = [&](uint32_t as, uint32_t bs, int i, bool fence) {
        const uint32_t da = desc_lo(SB + OFF_A, 16) + as * (SLOT / 16), db = desc_lo(SB + OFF_B, 8192) + bs * (SLOT / 16);
        if (fence) wgmma_fence();
#pragma unroll
        for (int k = 0; k < 4; k++) {
          wgmma_ss_n128(kv0, da + (k >> 1) * 32 + (k & 1) * 2, HA64, db + 128 * k, i + k);
          wgmma_ss_n128(kv1, da + 512 + (k >> 1) * 32 + (k & 1) * 2, HA64, db + 128 * k, i + k);
        }
        wgmma_commit();
      };
      constexpr uint32_t dm = desc_lo(SB + OFF_MB, 0);
      auto relB = [&](uint32_t s) { mbar_arrive_n(sb + BAR_EMPTYB + s * 8, 2); };
      auto skip = [&]() {
#pragma unroll
        for (int q = 0; q < 6 - NJ; q++) adv<NA>(x.ra);
        x.rb.s = w ? (2 + NJ) % 6 : 4;
        if (!w && NJ < 4) x.rb.ph ^= 1;
      };
      static_assert(NA == 5 && NB == 6, "ring arithmetic");
      mbar_wait2(x.fullA(x.ra.s), x.ra.ph, x.fullB(x.rb.s + w), x.rb.ph);
      mma8(x.ra.s, x.rb.s + w, 0, true);
      gemm_next<256>(x);
#pragma unroll 1
      for (int i = 1; i < NJ; i++) {
        mbar_wait2(x.fullA(x.ra.s), x.ra.ph, x.fullB(x.rb.s + w), x.rb.ph);
        mma8(x.ra.s, x.rb.s + w, 1, true);
        if (i == XR) { img_store(r1, x.img(XBUF(L), 1)); publish(3, x); }
        wgmma_wait<1>();
        if (x.elected && i != 2) { x.releaseA(x.pa); relB(x.pb + w); }
        gemm_next<256>(x);
        if (i == 1) { wgmma_wait<0>(); if (x.elected) { x.releaseA(x.pa); relB(x.pb + w); } }
      }
      if (w) {
        if (NJ > 2) { wgmma_wait<0>(); if (x.elected) { x.releaseA(x.pa); relB(x.pb + 1); } }
        if (XR >= NJ) { mbar_wait(x.fullA(x.ra.s), x.ra.ph); img_store(r1, x.img(XBUF(L), 1)); publish(3, x); }
        skip();
        asm volatile("bar.sync 7, 256;" ::: "memory");
      }
      TSW(8 + L * 12);
      {
        const int t = lane_id() + 32 * x.warp;
        uint32_t mask = t < 2 ? ((w ? (t ? 0xFF3Fu : 0x3FFFu) : 0xFFFFu) >> (NJ - 1)) & (w || NJ == 2 ? ~1u : ~0u) : 0u, cnt = 1 + t;
        bool ready = false;
#pragma unroll 1
        for (int i = NJ; i < 16; i++) {
          if (!ready) mbar_wait2(x.fullA(x.ra.s), x.ra.ph, x.fullB(x.rb.s), x.rb.ph);
          mma8(x.ra.s, x.rb.s, 1, true);
          if (XR >= NJ && i == NJ && !w) { img_store(r1, x.img(XBUF(L), 1)); publish(3, x); }
          const uint32_t bar = sb + (t ? BAR_EMPTYB + x.pb * 8 : BAR_EMPTYA + x.pa * 8);
          gemm_next<128>(x);
          if (w && (i | 4) == 15) x.rb.s = 4;
          ready = mbar_probe2(x.fullA(x.ra.s), x.ra.ph, x.fullB(x.rb.s), x.rb.ph);
          wgmma_wait<1>();
          if (mask & 1) mbar_arrive_n(bar, cnt);
          mask >>= 1; cnt = 2;
          if (i == 8 && w) asm volatile("bar.arrive 9, 256;" ::: "memory");
          if (i == 9) TSW(10 + L * 12);
        }
        mbar_wait2(sb + BAR_STAT, 1, sb + BAR_CS + 8, 0);
        wgmma_fence();
        wgmma_r1_n128(kv0, dm, dcs + 96 + 96 * w, 1);
        wgmma_r1_n128(kv1, dm + 64, dcs + 96 + 96 * w, 1);
        wgmma_commit();
        if (w == 0) asm volatile("bar.arrive 7, 256;" ::: "memory");
        wgmma_wait<1>();
        if (mask & 1) mbar_arrive_n(sb + (t ? BAR_EMPTYB + x.pb * 8 : BAR_EMPTYA + x.pa * 8), 2);
      }
      const Stats s0 = load_stats(0, x), s1 = load_stats(1, x), st = w ? s1 : s0;
      wgmma_wait<0>();
      fence_regs(kv);
      TSW(2 + L * 12);
      if (w == 0) skip();
      const uint32_t h0 = x.held(0), h1 = x.held(1);
      auto vreg = [&](int ks) { return ks < 6 ? OFF_A + (ks < 3 ? h0 * SLOT : h1 * SLOT - 15360) + ks * 5120 : OFF_S + 2048 + ks * 5120; };
      if (w == 0) {
        uint32_t f[2][18], ad[4];
#pragma unroll
        for (int q = 0; q < 18; q++) f[1][q] = 0u;
#pragma unroll
        for (int q = 0; q < 4; q++) ad[q] = x.maddr(sb + OFF_S, 2 * q);
        auto norm = [&](int un) {
          uint32_t* u = f[un & 1];
          const Stats& sn = (un & 2) ? s1 : s0;
#pragma unroll
          for (int sg = 0; sg < 2; sg++) {
            uint32_t v = u[16 + sg];
            v = add2(v, __shfl_xor_sync(0xffffffffu, v, 1)); v = add2(v, __shfl_xor_sync(0xffffffffu, v, 2));
            const float a = rcp(lo16(v)) * sn.rstd0, b = rcp(hi16(v)) * sn.rstd1;
            const uint32_t r0 = pack2(a, a), r1_ = pack2(b, b);
#pragma unroll
            for (int q = 8 * sg; q < 8 * sg + 8; q++) u[q] = mul2(u[q], (q & 1) ? r1_ : r0);
#pragma unroll
            for (int q = 2 * sg; q < 2 * sg + 2; q++) stsm4(ad[q] + (un & 1) * SLOT + (un >> 1) * 8192, u[4 * q], u[4 * q + 1], u[4 * q + 2], u[4 * q + 3]);
          }
        };
        auto unit = [&](int un) { return kv + ((un >> 1) & 1) * 64 + (un & 1) * 16 + (un >> 2) * 32; };
        hedgehog_scale<0>(kv, s0, nullptr);
#pragma unroll 1
        for (int it = 0;; it++) {
#pragma unroll
          for (int un = 0; un < 4; un++) {
            if (un == 1) {
              if (it) asm volatile("bar.sync 9, 256;" ::: "memory");
#pragma unroll
              for (int q = 0; q < 4; q++) ad[q] -= it * (OFF_S - OFF_B - 2 * SLOT);
            }
            norm((un + 3) & 3);
            dual_exp(unit(un), f[un & 1], x.goff);
            hedgehog_scale<KEEP>(unit(un + 1), ((un + 1) & 2) ? s1 : s0, f[(un + 1) & 1]);
          }
          if (it) break;
#pragma unroll
          for (int q = 0; q < 32; q++) {
            asm volatile("mov.b32 %0, %1;" : "=f"(kv[q]) : "f"(kv[q + 32]));
            asm volatile("mov.b32 %0, %1;" : "=f"(kv[q + 64]) : "f"(kv[q + 96]));
            if (q < 16) kv[32 + q] = 0.f;
          }
        }
        norm(3);
        fence_async_smem();
        TSW(3 + L * 12);
      } else {
        wg_bar(w);
#pragma unroll
        for (int hf = 0; hf < 2; hf++) {
          const uint32_t tV = sb + vreg(4 * hf + x.warp) + ((x.lane >> 3) & 1) * 2560 + (x.lane & 7) * 16;
          const float i0 = rcp(hf ? s1.rstd0 : s0.rstd0), i1 = rcp(hf ? s1.rstd1 : s0.rstd1);
          const uint32_t h = pack2(i0, i1), u0 = pack2(lo16(h), i0 - lo16(h)), u1 = pack2(hi16(h), i1 - hi16(h));
          stsm4(tV + 512 + x.mhi * 640, u0, u1, u0, u1);
          stsm4(tV + 1792 + x.mhi * 640, u0, u1, u0, u1);
#pragma unroll
          for (int q = 0; q < 8; q++) {
            const float* u = kv + 64 * hf + 8 * q;
            stsm4(tV + (q >> 1) * 640 + (2 * (q & 1) + x.mhi) * 128, pack2(u[0], u[1]), pack2(u[2], u[3]), pack2(u[4], u[5]), pack2(u[6], u[7]));
          }
        }
        TSW(3 + L * 12);
        fence_async_smem();
      }
      {
        float d[2][20];
        cta_bar();
        TSW(11 + L * 12);
        uint32_t pk[9];
        auto prep = [&](float (&u)[20]) {
          fence_regs(u);
#pragma unroll
          for (int q = 0; q < 8; q++) pk[q] = pack2(u[((q >> 1) & 2) + 4 * (q & 3)], u[((q >> 1) & 2) + 4 * (q & 3) + 1]);
          pk[8] = __float_as_uint((x.c & 1) ? u[18] + u[19] : u[16] + u[17]);
#pragma unroll
          for (int q = 0; q < 9; q += 4) pk[q] = (pk[q] & ~1u) | (L == 1);
        };
        uint4* dst = &g_kvpart[x.j()][w * 4 + x.warp][0][x.m() * 32 + x.lane];
        unsigned* dz = reinterpret_cast<unsigned*>(&g_kvpart[x.j()][w * 4 + x.warp][x.c & 1][512]) + x.m() * 8 + x.g;
        auto send = [&](int hp) {
          st_v4(dst + hp * 16 * 544, pk[0], pk[1], pk[2], pk[3]); st_v4(dst + (hp * 16 + 1) * 544, pk[4], pk[5], pk[6], pk[7]);
          if (x.c < 2) st_flag(dz + hp * 16 * 544 * 4, pk[8]);
        };
        wgmma_fence();
#pragma unroll
        for (int q = 0; q < 17; q++) {
          if (q < 16) wgmma_ss_n40_tt(d[q >> 3], desc_lo(SB + (q < 8 ? OFF_S : OFF_B + 2 * SLOT), 1024) + w * (SLOT / 16) + 128 * (q & 7), desc_lo(SB + vreg(q & 7), 2560) + (w + (q >> 3) * 2) * 40, q & 7);
          else wgmma_r1_n128(acc, dm + w * 64, dcs, LEAD != 0);
          if (q == 7 || q == KVS || q == 16) wgmma_commit();
          if (q == KVS) { wgmma_wait<1>(); prep(d[0]); send(0); wgmma_fence(); }
        }
        gemm_issue<128, false>(acc, x); gemm_next<128>(x);
        wgmma_wait<1>();
        x.releaseA(h0); x.releaseA(h1); x.releaseB(2); x.releaseB(3);
        if (x.lane == 0) mbar_arrive(sb + BAR_SIGT);
        prep(d[1]);
        TSW(4 + L * 12);
#pragma unroll 1
        for (int seg = 0; seg < 2; seg++) {
          const int n0 = w ? PS1 : PS0;
          gemm_run(acc, x, seg ? 15 - LEAD * w - n0 : n0, seg, seg ? L : 0);
          if (seg == 0) send(1);
        }
      }
      gemm_end(acc, x);
      TSW(5 + L * 12);
      {
        float dp[2][20], dn[2][20];
        uint32_t f[4][16];
        auto expo = [&](int h) { hedgehog_scale<0>(acc + 16 * h, st, nullptr); dual_exp_rcp(acc + 16 * h, f[h]); };
        auto mma = [&](int h) {
          if (!(h & 1)) mbar_wait(sb + BAR_KV + h * 4, L >> 1);
          if (h == 0) TSW(9 + L * 12);
          const uint32_t db = desc_lo(SB + OFF_S + h * 5120, 128);
          const uint32_t (&a)[16] = f[h];
          wgmma_fence();
          wgmma_rs_n40(dp[h & 1], a[0], a[1], a[2], a[3], db, 0);
          wgmma_rs_n40(dn[h & 1], a[8], a[9], a[10], a[11], db + 160, 0);
          wgmma_rs_n40(dp[h & 1], a[4], a[5], a[6], a[7], db + 80, 1);
          wgmma_rs_n40(dn[h & 1], a[12], a[13], a[14], a[15], db + 240, 1);
          wgmma_commit();
        };
        uint32_t xr[16];
        auto fin = [&](int h) {
          const uint32_t tile = x.aslot(x.held(h >> 1));
          if (!(h & 1)) img_load(xr, tile, x);
          float (&u)[20] = dp[h & 1];
          float (&v)[20] = dn[h & 1];
          fence_regs(u); fence_regs(v);
#pragma unroll
          for (int r = 0; r < 2; r++) {
            float cc = u[17 + 2 * r] * rcp(v[17 + 2 * r]);
            const float aa = rcp(fmaf(v[16 + 2 * r], cc, fmaf(u[17 + 2 * r], 1e-6f, u[16 + 2 * r])));
            cc *= aa;
            uint32_t o[4];
#pragma unroll
            for (int t = 0; t < 4; t++) o[t] = pack2(fmaf(u[4 * t + 2 * r], aa, v[4 * t + 2 * r] * cc), fmaf(u[4 * t + 2 * r + 1], aa, v[4 * t + 2 * r + 1] * cc));
            x.img(0, h >> 1)[r * 64 + (h & 1) * 32] = make_uint4(o[0], o[1], o[2], o[3]);
            sts128(tile + r * 1024 + (h & 1) * 512 + x.oo() * 16, o[0], o[1], o[2], o[3]);
          }
          if (h & 1) { publish(h >> 1, x); img_unpack(acc + 16 * (h - 1), xr); }
        };
        expo(0); mma(0);
        expo(1); mma(1);
        wgmma_wait<1>(); fin(0); wgmma_wait<0>(); fin(1);
        expo(2); mma(2);
        expo(3); mma(3);
        wgmma_wait<1>(); fin(2); wgmma_wait<0>(); fin(3);
      }
    }
    fence_async_smem();
    wg_bar(w);
    TSW(6 + L * 12);
    rewind2<NA>(x.ra);
    gemm_issue<128, false>(acc, x); gemm_next<128>(x);
#pragma unroll 1
    for (int seg = L >= TSL ? 0 : 1; seg < 2; seg++) {
      gemm_run(acc, x, L >= TSL ? (seg ? TSK : 15 - TSK) : 15, seg);
      if (L >= TSL) {
        if (seg == 0 && w == 1) asm volatile("bar.sync 6, 256;" ::: "memory");
        if (seg == 1 && w == 0) asm volatile("bar.arrive 6, 256;" ::: "memory");
      }
    }
    gemm_end(acc, x);
    TSW(7 + L * 12);
    rewind2<NA>(x.ra);
    out_epilogue(acc, r1, P.out + goff, L, x);
    TSW(13 + L * 12);
  }
}

typedef unsigned long long u64;
__device__ __forceinline__ void pause(uint32_t GAP) {
  if (GAP) { uint32_t t0, t; asm volatile("mov.u32 %0, %%clock;" : "=r"(t0)); do { asm volatile("mov.u32 %0, %%clock;" : "=r"(t)); } while (t - t0 < GAP); }
}
__device__ __forceinline__ u64 order_table(int kind, int j) {
  const int i = threadIdx.x & 15;
  const unsigned v = (unsigned)(kind == 2 ? q_order(i, j) : kv_order(i, j, kind)) << (4 * (i & 7));
  return (u64)__reduce_or_sync(0xffffffffu, i < 8 ? 0u : v) << 32 | __reduce_or_sync(0xffffffffu, i < 8 ? v : 0u);
}

__device__ __forceinline__ void b_producer(const Params& P, uint32_t sb, unsigned vb) {
  const int j = cta_j(vb);
  const u64 t0 = order_table(0, j), t1 = order_table(1, j), t2 = order_table(2, j);
  Ring r = {PRE_B % NB, PRE_B < NB};
#pragma unroll 1
  for (int sg = 0; sg < 20; sg++) {
    const int L = sg / 5, p = sg - 5 * L, wt = L & 1;
    int n = p >= 3 ? 16 : (wt ? (p ? 16 - NJ : 2 * NJ) : (p ? 0 : (L ? 32 : 32 - PRE_B)));
    u64 tab = p == 3 ? t2 : (sg == 0 ? t0 >> (2 * PRE_B) : (p == 1 || p == 2 ? t1 >> (4 * NJ) : t1));
    const CUtensorMap* tm = p == 4 ? &P.mwo[wt] : &P.mw[wt ? 1 : L];
    const uint4* img = &g_wf[p != 3][j][0][0];
    int col = (p >= 3 ? 0 : (p == 2 ? 2048 : 1024)) + 128 * j;
    const int flip = p == 0 ? 3072 : 0;
    const bool fold = wt && p != 4;
    if (sg == 5 || sg == 8) { mbar_wait(sb + (sg == 5 ? BAR_WPHI : BAR_CS + 8), sg == 5); fence_async_global(); }
    if (DEFER && p == 4 && ((DEFL >> wt) & 1)) {
      Ring q = r;
      for (int u = 0; u < DEFER; u++) adv<NB>(q);
      mbar_wait(sb + BAR_EMPTYB + q.s * 8, q.ph);
    }
#pragma unroll 1
    for (; n > 0; n--) {
      const int kb = (int)tab & 15;
      mbar_wait(sb + BAR_EMPTYB + r.s * 8, r.ph);
      if (elect()) {
        mbar_expect_tx(sb + BAR_FULLB + r.s * 8, SLOT);
        if (fold && col < 2048) bulk_load(sb + OFF_B + r.s * SLOT, img + kb * 1024, SLOT, sb + BAR_FULLB + r.s * 8);
        else tma_load_w(sb + OFF_B + r.s * SLOT, tm, sb + BAR_FULLB + r.s * 8, col, kb);
      }
      adv<NB>(r);
      if (p == 2 && (n | 4) == 5) r.s = 4;
      col ^= flip;
      if (!(col & flip & 2048)) tab >>= 4;
    }
  }
}

__device__ __forceinline__ void a_loader(const Params& P, uint32_t sb, unsigned vb) {
  const int j = cta_j(vb), m = cta_m(vb);
  const u64 t1 = order_table(1, j), t2 = order_table(2, j);
  Ring r = {PRE_A % NA, PRE_A < NA};
  {
    u64 tab = order_table(0, j) >> (4 * PRE_A);
#pragma unroll 1
    for (int i = PRE_A; i < 33; i++) {
      if (i == 17) tab = t2;
      mbar_wait(sb + BAR_EMPTYA + r.s * 8, r.ph);
      if (elect()) {
        mbar_expect_tx(sb + BAR_FULLA + r.s * 8, SLOT);
        if (i != 14) tma_load_3d(sb + OFF_A + r.s * SLOT, &P.mx, sb + BAR_FULLA + r.s * 8, ((int)tab & 15) * 64, m * 64, 0);
        else {
          tma_load_w(sb + OFF_A + r.s * SLOT, &P.mw[1], sb + BAR_FULLA + r.s * 8, 1024 + 128 * j, m);
          mbar_expect_tx(sb + BAR_WPHI, 8192); tma_load_2d(sb + OFF_S + 4096, &P.mwphi, sb + BAR_WPHI, 0, 128 * j);
        }
        if (i == PF0 || i == PF1 || i == PF2)
          tma_prefetch_w(i == PF0 ? &P.mw[1] : &P.mwo[i == PF2], (i == PF0 ? 1024 : 0) + 128 * j, m);
      }
      adv<NA>(r);
      if (i != 14) tab >>= 4;
    }
  }
  const unsigned tag = get_tag(sb);
  unsigned seen = 0;
#pragma unroll 1
  for (int sg = 0; sg < 27; sg++) {
    const int L = sg >> 3, p = sg & 7, q = p >= 3 ? p - 3 : p;
    if (p == 0 && (L & 1)) {
#pragma unroll 1
      for (int h = 0; h < 2; h++) {
        poll_flags(&g_kvfflag[L >> 1][j][h][0], 8, 0xFFu, tag);
        if (elect()) { mbar_expect_tx(sb + BAR_KV + h * 8, 10240); bulk_load(sb + OFF_S + h * 10240, &g_kvfin[j][8 * h][0], 10240, sb + BAR_KV + h * 8); }
      }
      TS(4, 14 + L);
    }
    int n = q == 0 ? 4 : (q == 1 ? 3 : (q == 2 ? 7 : (q == 3 ? ((L & 1) ? 0 : 16 - NJ) : 16)));
    u64 tab = q == 4 ? t2 : t1 >> (q == 0 ? 8 : (q == 1 ? 24 : (q == 2 ? 36 : 4 * NJ)));
    const uint4* img = &g_img[p >= 3 ? XBUF(L + 1) : 0][m][0][0];
    const uint32_t gap = p == 0 ? G0 : (p == 3 ? G3 : (q < 3 ? G1 : G4));
    bool poll = q == 0 || q == 2 || (q == 1 && seen != 0xFFFFFFFFu);
#pragma unroll 1
    for (; n > 0; n--) {
      const uint4* src = img + ((int)tab & 15) * 1024;
      mbar_wait(sb + BAR_EMPTYA + r.s * 8, r.ph);
      if (elect()) mbar_expect_tx(sb + BAR_FULLA + r.s * 8, SLOT);
      if (poll) {
        const int lane = threadIdx.x & 31, nn = p >= 3 ? PNX : PNO;
        const unsigned* f = (p >= 3 ? &g_xflag[L + 1][0][m][0] : &g_oflag[L][0][m][0]) + (q == 2 ? 512 : 0) + (lane & 7);
        if (q == 0) f += (((lane >> 3) & (nn - 1)) - (m & (nn - 1))) * 32;
        const unsigned need = q == 0 ? 0x0F0F0F0Fu << (~j & 4) : 0xFFFFFFFFu;
        if (q == 0) mbar_wait(sb + BAR_SIGP + (p ? 16 : 0), L & 1);
        int it = 0;
        do { seen = __ballot_sync(0xffffffffu, ld_flag(f) == tag); if (++it > (1 << 22)) __trap(); } while ((seen & need) != need);
        fence_async_global();
        if (q == 0) TS(2, p == 0 ? 5 + L * 8 : 9 + L * 8);
        poll = false;
      }
      if (elect()) bulk_load(sb + OFF_A + r.s * SLOT, src, SLOT, sb + BAR_FULLA + r.s * 8);
      adv<NA>(r);
      tab >>= 4;
      pause(gap);
    }
  }
}

__device__ __forceinline__ void helper_bar() { asm volatile("bar.sync 4, 64;" ::: "memory"); }
__device__ __forceinline__ void helper(const Params& P, uint32_t sb, int w, unsigned vb) {
  const int j = cta_j(vb), m = cta_m(vb);
  if (w == 0) {
    if (elect()) {
      const unsigned t = atomicAdd(&g_ctr, 1u) / NCTA + 1u;
      asm volatile("st.shared.u32 [%0], %1;" ::"r"(sb + OFF_EPOCH), "r"(t) : "memory");
      mbar_arrive(sb + BAR_EPOCH);
    }
  }
  const unsigned tag = get_tag(sb);
  mbar_wait(sb + BAR_FULLB + 24, 0);
  const uint32_t stg = sb + OFF_T + w * 12288, stb = sb + BAR_STG + w * 24;
  Ring rs = {0, 0};
  auto cs_image = [&](int L) {
      const int lane = lane_id();
      poll_flags(&g_csflag[L][j][0], 16, L ? CSNEED : 0xFFFu, tag);
#pragma unroll
      for (int p = 0; p < 3; p++) {
        const uint4 u = ldcg4(&g_cs[L][0][p * 1024 + 128 * j + lane * 4]), v = ldcg4(&g_cs[L][1][p * 1024 + 128 * j + lane * 4]);
        const float c0 = __uint_as_float(u.x) + __uint_as_float(v.x), c1 = __uint_as_float(u.y) + __uint_as_float(v.y);
        const float c2 = __uint_as_float(u.z) + __uint_as_float(v.z), c3 = __uint_as_float(u.w) + __uint_as_float(v.w);
        const uint32_t h0 = pack2(c0, c1), h1 = pack2(c2, c3), dst = sb + OFF_CS + (p * 16 + (lane >> 1)) * 96 + L * 48 + (lane & 1) * 8;
        sts64(dst, h0, h1); sts64(dst + 16, pack2(c0 - lo16(h0), c1 - hi16(h0)), pack2(c2 - lo16(h1), c3 - hi16(h1))); sts64(dst + 32, h0, h1);
        if (L == 0) { sts64(dst + 48, 0u, 0u); sts64(dst + 64, 0u, 0u); sts64(dst + 80, 0u, 0u); }
      }
      if (L == 0 && lane < 4) sts64(sb + OFF_CS + 4608 + lane * 8, 0u, 0u);
      fence_async_smem();
      __syncwarp();
      if (elect()) mbar_arrive(sb + BAR_CS + L * 8);
      TS(4, 2 + L * 2);
  };
#pragma unroll 1
  for (int L = 0; L < 4; L++) {
    const int lane = lane_id();
    if (L == 0) {
      {
        const int wt = m >= 12, col = ((0x2021 >> (m & 12)) & 3) * 1024 + 128 * j + (m & 3) * 32;
        const CUtensorMap* tm = &P.mcs[wt];
        if (D2 && wt) __nanosleep(D2);
        constexpr int nb = 8;
        float a[8] = {0.f, 0.f, 0.f, 0.f, 0.f, 0.f, 0.f, 0.f};
#pragma unroll 1
        for (int b = -3; b < nb; b++) {
          uint4 v[8];
          if (b >= 0) {
            mbar_wait(stb + rs.s * 8, rs.ph);
#pragma unroll
            for (int u = 0; u < 8; u++) lds128(stg + rs.s * 4096 + u * 512 + lane * 16, v[u].x, v[u].y, v[u].z, v[u].w);
            fence_async_smem();
            __syncwarp();
          }
          const uint32_t sl = b < 0 ? (rs.s + b + 3) % 3 : rs.s;
          if (b + 3 < nb && elect()) { mbar_expect_tx(stb + sl * 8, 4096); tma_load_2d(stg + sl * 4096, tm, stb + sl * 8, col, (w * (16 - nb) + b + 3) * 64); }
          if (b >= 0) {
            adv<3>(rs);
#pragma unroll
            for (int u = 0; u < 8; u++) {
              a[0] += lo16(v[u].x); a[1] += hi16(v[u].x); a[2] += lo16(v[u].y); a[3] += hi16(v[u].y);
              a[4] += lo16(v[u].z); a[5] += hi16(v[u].z); a[6] += lo16(v[u].w); a[7] += hi16(v[u].w);
            }
          }
        }
#pragma unroll
        for (int u = 0; u < 8; u++) {
          a[u] += __shfl_xor_sync(0xffffffffu, a[u], 4); a[u] += __shfl_xor_sync(0xffffffffu, a[u], 8); a[u] += __shfl_xor_sync(0xffffffffu, a[u], 16);
        }
        if (lane < 4) {
          float4* dst = reinterpret_cast<float4*>(&g_cs[wt][w][col + lane * 8]);
          dst[0] = make_float4(a[0], a[1], a[2], a[3]); dst[1] = make_float4(a[4], a[5], a[6], a[7]);
        }
        helper_bar();
        if (w == 0 && elect()) { fence_gpu(); st_flag(&g_csflag[wt][j][m], tag); }
      }
      if (w == 0) TS(4, 1 + L * 2);
    }
    if (w == 1) {
      if (L > 0) mbar_wait(sb + BAR_SIGP + ((L & STG0) ? 16 : 24), (L - 1) & 1);
#pragma unroll 1
      for (int p = 0; p < 2; p++) {
        uint4 v[8];
        for (int it = 0;; it++) {
          bool ok = true;
#pragma unroll
          for (int t = 0; t < 8; t++) v[t] = ld_pkt(&g_stats[m][p][t][lane]);
#pragma unroll
          for (int t = 0; t < 8; t++) ok = ok && (v[t].w & 15u) == seq4(tag, L);
          if (__all_sync(0xffffffffu, ok)) break;
          __nanosleep(200);
          if (it > (1 << 20)) __trap();
        }
        float s0 = 0.f, q0 = 0.f, s1 = 0.f, q1 = 0.f;
#pragma unroll
        for (int t = 0; t < 8; t++) { s0 += __uint_as_float(v[t].x); q0 += __uint_as_float(v[t].y); s1 += __uint_as_float(v[t].z); q1 += __uint_as_float(v[t].w & ~15u); }
        s0 *= (1.f / 1024); s1 *= (1.f / 1024);
        sts64(sb + OFF_MR + p * 256 + lane * 8, __float_as_uint(rsqrtf(fmaxf(q0 * (1.f / 1024) - s0 * s0, 0.f) + 1e-5f)),
              __float_as_uint(rsqrtf(fmaxf(q1 * (1.f / 1024) - s1 * s1, 0.f) + 1e-5f)));
#pragma unroll
        for (int r = 0; r < 2; r++) {
          const float v = -0.5f * (r ? s1 : s0);
          const uint32_t hh = pack2(v, v), hl = pack2(v, v - lo16(hh));
          const bool b = L & 1;
          sts128(sb + (b ? OFF_MB : OFF_MA) + p * 1024 + (lane >> 3) * 256 + r * 128 + (lane & 7) * 16, b ? 0u : hh, b ? hh << 16 : hl >> 16, b ? hl : 0u, 0u);
        }
      }
      fence_async_smem();
      __syncwarp();
      if (elect()) {
        mbar_arrive(sb + BAR_STAT);
      }
      TS(2, 0 + L * 8);
    }
    if (L == w) cs_image(L);
    if (L & 1) {
      const uint32_t flip = L == 1 ? 0u : 1u;
      mbar_wait(sb + BAR_SIGT, 1);
      {
        int it = 0;
        if (PSL) __nanosleep(m < 8 ? PSL : PSL + 600);
        while (!__all_sync(0xffffffffu, (ld_flag(reinterpret_cast<const unsigned*>(&g_kvpart[j][m][w][512]) + (lane & 15) * 8) ^ flip) & 1u)) { if (PSL) __nanosleep(100); if (++it > (1 << 22)) __trap(); }
        fence_async_global();
      }
      if (w == 0) TS(4, 6 + L * 2);
      for (int it = 0;; it++) {
        if (elect()) { mbar_expect_tx(stb + rs.s * 8, 8704); bulk_load(stg, &g_kvpart[j][m][w][0], 8704, stb + rs.s * 8); }
        mbar_wait(stb + rs.s * 8, rs.ph);
        adv<3>(rs);
        float a[8] = {0.f, 0.f, 0.f, 0.f, 0.f, 0.f, 0.f, 0.f};
        float z = 0.f;
        uint32_t ok = 1u;
#pragma unroll
        for (int u = 0; u < 4; u++) { const float v = lds32f(stg + 8192 + u * 128 + (lane & 3) * 32 + (lane >> 2) * 4); z += v; ok &= __float_as_uint(v) ^ flip; }
#pragma unroll 1
        for (int b = 0; b < 16; b += KB) {
          uint4 v[KB];
#pragma unroll
          for (int u = 0; u < KB; u++) lds128(stg + (b + u) * 512 + lane * 16, v[u].x, v[u].y, v[u].z, v[u].w);
#pragma unroll
          for (int u = 0; u < KB; u++) {
            ok &= v[u].x ^ flip;
            if (RH && !(u & 1)) continue;
            if (RH) { v[u].x = add2(v[u].x, v[u - 1].x); v[u].y = add2(v[u].y, v[u - 1].y); v[u].z = add2(v[u].z, v[u - 1].z); v[u].w = add2(v[u].w, v[u - 1].w); }
            a[0] += lo16(v[u].x); a[1] += hi16(v[u].x); a[2] += lo16(v[u].y); a[3] += hi16(v[u].y);
            a[4] += lo16(v[u].z); a[5] += hi16(v[u].z); a[6] += lo16(v[u].w); a[7] += hi16(v[u].w);
          }
        }
        uint4* img = &g_kvfin[j][m][w * 8 + (lane >> 2)];
        img[(lane & 3) * 16] = make_uint4(pack2(a[0], a[1]), pack2(a[2], a[3]), pack2(a[4], a[5]), pack2(a[6], a[7]));
        reinterpret_cast<uint32_t*>(img + 64)[lane & 3] = pack2(qsum(z), 1.f);
        if (__all_sync(0xffffffffu, ok & 1u)) break;
        fence_async_smem();
        if (it > (1 << 16)) __trap();
      }
      if (w == 0) TS(4, 7 + L * 2);
      helper_bar();
      if (w == 1 && elect()) { fence_gpu(); st_flag(&g_kvfflag[L >> 1][j][m >> 3][m & 7], tag); }
      if (w == 1 && L == 1) TS(4, 20);
    } else {
      mbar_wait(sb + BAR_SIGT, 0);
      if (w == 0) {
        if (elect()) { fence_gpu(); st_flag(&g_hflag[L >> 1][m][j][0], tag); st_flag(&g_kflag[j][m], tag); }
        if (L == 0) {
          __nanosleep(KSL);
          poll_flags(&g_kflag[j][0], 16, 0xFFFFu, tag);
          if (elect()) mbar_arrive(sb + BAR_WPHI);
        }
      } else if (m > 0) {
        poll_flags(&g_hflag[L >> 1][m - 1][j][0], 1, 1u, tag);
        if (elect()) { mbar_expect_tx(sb + BAR_HALO, 8192); bulk_load(sb + OFF_S + 8192, &g_halo[m - 1][j][0][0], 8192, sb + BAR_HALO); }
        TS(2, 2 + L * 8);
      }
    }
#pragma unroll 1
    for (int e = 0; e < (L < 3 && w == 0 ? 3 : 1); e++) {
      mbar_wait(sb + BAR_SIGP + (e == 0 ? w : e + 1) * 8, L & 1);
      TS(e == 2 ? 3 : 2 + w, (e ? 6 : 3) + L * 8);
      if (elect()) { fence_gpu(); st_flag(e == 0 ? &g_oflag[L][w][m][j] : &g_xflag[L + 1][e - 1][m][j], tag); }
      TS(e == 2 ? 3 : 2 + w, (e ? 7 : 4) + L * 8);
    }
  }
}

__device__ __forceinline__ void spare(const Params& P, uint32_t sb, int id) {
  const int tid = threadIdx.x & 127, w = __shfl_sync(0xffffffffu, threadIdx.x >> 7, 0), lane = tid & 31, j = 2 * id + w;
  const uint32_t ring = w * 6 * SLOT, wp = 12 * SLOT + w * 8192, bar = sb + 13 * SLOT + w * 64;
  auto part = [&](int t) { return (t >> 4) ^ w; };
  auto load = [&](int t, uint32_t sl) {
    mbar_expect_tx(bar + sl * 8, t == 0 ? SLOT + 8192 : SLOT);
    tma_load_w(sb + ring + sl * SLOT, &P.mw[1], bar + sl * 8, part(t) * 1024 + 128 * j, t & 15);
  };
  if (tid == 0) {
    if (w == 2) sts32(sb + OFF_EPOCH, atomicAdd(&g_ctr, 1u) / NCTA + 1u);
    else {
      __nanosleep(D3);
#pragma unroll 1
      for (int t = 0; t < 5; t++) {
        mbar_init(bar + t * 8, 1);
        asm volatile("fence.mbarrier_init.release.cluster;" ::: "memory");
        load(t, t);
      }
      tma_load_2d(sb + wp, &P.mwphi, bar, 0, 128 * j);
    }
  }
  __syncthreads();
  const unsigned tag = get_tag<false>(sb);
  if (w == 2) {
    int it = 0;
    while ((int)(ld_flag(&g_ctr) - tag * NCTA) < 0) { if (++it > (1 << 22)) __trap(); }
    return;
  }
  Ring r = {4, 1};
  float d[64] = {}, cs[32] = {};
  auto fold = [&]() {
    mbar_wait(bar + r.s * 8, r.ph);
    wgmma_fence();
#pragma unroll
    for (int q = 0; q < 8; q++)
      wgmma_ss_n32(reinterpret_cast<float (&)[16]>(d[16 * (q >> 1)]), desc_lo(SB + ring + r.s * SLOT, 16) + (q >> 2) * 512 + (q & 3) * 2, desc_lo(SB + wp, 512) + q * 64, q & 1);
    wgmma_commit();
  };
  const int row = (tid >> 5) * 16 + (lane >> 2);
#pragma unroll 1
  for (int t = -1; t < 32; t++) {
    uint32_t f[32];
#pragma unroll
    for (int i = 0; i < 32; i++) { f[i] = pack2(d[2 * i], d[2 * i + 1]); cs[i & 30] += d[2 * i]; cs[i | 1] += d[2 * i + 1]; }
    wg_bar(w);
    if (tid == 0 && t >= 0 && t < 27) load(t + 5, r.s);
    __syncwarp();
    if (t < 31) adv<5>(r);
    fold();
    if (part(t) == 0 && t >= 0) {
#pragma unroll
      for (int q = 0; q < 8; q++)
        g_wf[0][j][t & 15][(q >> 2) * 512 + (row + 8 * (q & 1)) * 8 + (((q & 2) * 2 + (lane & 3)) ^ (lane >> 2))] =
            make_uint4(f[4 * (q & 6) + (q & 1)], f[4 * (q & 6) + (q & 1) + 2], f[4 * (q & 6) + (q & 1) + 4], f[4 * (q & 6) + (q & 1) + 6]);
    }
    wgmma_wait<0>();
    fence_regs(d);
    if ((t & 15) == 15) {
      if (t >= 0) {
        const uint32_t red = sb + ring + 5 * SLOT;
#pragma unroll
        for (int i = 0; i < 8; i++) sts128(red + (tid >> 2) * 512 + (i >> 1) * 128 + (lane & 3) * 32 + (i & 1) * 16, __float_as_uint(cs[4 * i]), __float_as_uint(cs[4 * i + 1]), __float_as_uint(cs[4 * i + 2]), __float_as_uint(cs[4 * i + 3]));
        wg_bar(w);
        float a = 0.f;
#pragma unroll 4
        for (int i = 0; i < 32; i++) a += lds32f(red + i * 512 + tid * 4);
        g_cs[1][0][part(t) * 1024 + j * 128 + tid] = a;
        wg_bar(w);
        if (tid == 0) {
          fence_gpu();
          st_flag(&g_csflag[1][j][part(t)], tag);
        }
        __syncwarp();
      }
#pragma unroll
      for (int i = 0; i < 32; i++) cs[i] = 0.f;
    }
  }
}

__global__ void __launch_bounds__(NTHREADS, 1) fused_kernel(const __grid_constant__ Params P) {
  extern __shared__ __align__(1024) uint8_t smem_raw[];
  constexpr uint32_t sb = SB;
  const int tid = threadIdx.x;
  const unsigned vb = vblock();
  if (vb >= 128) { spare(P, sb, vb - 128); return; }
  const int warp = __shfl_sync(0xffffffffu, tid >> 5, 0);
  if (elect()) {
    if (warp == 11) { prefetch_map(&P.mx); prefetch_map(&P.mw[0]); if (smem_u32(smem_raw) != SB) __trap(); }
    if (warp < 7) {
#pragma unroll
      for (int i = 0; i < 8; i++) mbar_init(sb + OFF_BAR + (warp * 8 + i) * 8, warp == 2 || warp == 3 ? 2 : (warp == 4 ? 8 : 1));
    }
    asm volatile("fence.mbarrier_init.release.cluster;" ::: "memory");
    if (warp < 2) {
      const int j = cta_j(vb);
#pragma unroll 1
      for (int i = 0; i < (warp == 0 ? PRE_B : PRE_A); i++) {
        const uint32_t bar = sb + BAR_FULLB + warp * 64 + i * 8;
        mbar_expect_tx(bar, SLOT);
        if (warp == 0) tma_load_w(sb + OFF_B + i * SLOT, &P.mw[0], bar, 1024 + (i & 1) * 1024 + 128 * j, kv_order(i >> 1, j, 0));
        else tma_load_3d(sb + OFF_A + i * SLOT, &P.mx, bar, kv_order(i, j, 0) * 64, cta_m(vb) * 64, 0);
      }
    }
  }
  if (tid == 0) TS(6, 0);
  __syncthreads();
  if (tid == 0) TS(6, 2);
  if (warp < 4) {
    reg_dealloc<PREGS>();
    if (warp == 0) b_producer(P, sb, vb);
    else if (warp == 1) a_loader(P, sb, vb);
    else helper(P, sb, warp - 2, vb);
  } else {
    reg_alloc<CREGS>();
    consumer(P, sb, (warp >> 2) - 1, vb);
  }
}

typedef CUresult (*EncodeFn)(CUtensorMap*, CUtensorMapDataType, cuuint32_t, void*, const cuuint64_t*, const cuuint64_t*,
                             const cuuint32_t*, const cuuint32_t*, CUtensorMapInterleave, CUtensorMapSwizzle,
                             CUtensorMapL2promotion, CUtensorMapFloatOOBfill);

void encode(EncodeFn fn, CUtensorMap* m, const void* ptr, int rank, const cuuint64_t* dims, const cuuint64_t* strides,
            const cuuint32_t* box, CUtensorMapSwizzle swz) {
  const cuuint32_t es[5] = {1, 1, 1, 1, 1};
  fn(m, CU_TENSOR_MAP_DATA_TYPE_BFLOAT16, rank, const_cast<void*>(ptr), dims, strides, box, es, CU_TENSOR_MAP_INTERLEAVE_NONE,
     swz, CU_TENSOR_MAP_L2_PROMOTION_L2_256B, CU_TENSOR_MAP_FLOAT_OOB_FILL_NONE);
}
void encode_w(EncodeFn fn, CUtensorMap* m, const void* ptr, int ncols, bool perm) {
  const cuuint64_t p = (cuuint64_t)ncols * 2, d[5] = {(cuuint64_t)ncols, 2, 4, 4, 32}, s[4] = {p, (perm ? 8 : 2) * p, (perm ? 2 : 8) * p, 32 * p};
  const cuuint32_t box[5] = {64, 2, 4, 4, 2};
  encode(fn, m, ptr, 5, d, s, box, CU_TENSOR_MAP_SWIZZLE_128B);
}

void encode_cs(EncodeFn fn, CUtensorMap* m, const void* ptr, int ncols) {
  const cuuint64_t d[2] = {(cuuint64_t)ncols, 1024}, s[1] = {(cuuint64_t)ncols * 2};
  const cuuint32_t box[2] = {32, 64};
  encode(fn, m, ptr, 2, d, s, box, CU_TENSOR_MAP_SWIZZLE_NONE);
}

}

extern "C" void kernel_launch(void* const* d_in, const int* in_sizes, int n_in, void* d_out, int out_size) {
  (void)in_sizes; (void)n_in; (void)out_size;
  void* fnp = nullptr;
  cudaDriverEntryPointQueryResult q;
  cudaGetDriverEntryPoint("cuTensorMapEncodeTiled", &fnp, cudaEnableDefault, &q);
  EncodeFn fn = (EncodeFn)fnp;
  Params P;
  {
    const cuuint64_t dims[3] = {1024, 1024, 2}, strides[2] = {4096, 2048};
    const cuuint32_t box[3] = {64, 64, 2};
    encode(fn, &P.mx, d_in[0], 3, dims, strides, box, CU_TENSOR_MAP_SWIZZLE_128B);
  }
  P.out = (uint4*)d_out;
  encode_w(fn, &P.mw[0], d_in[1], 3072, false);
  encode_w(fn, &P.mw[1], d_in[4], 3072, true);
  encode_w(fn, &P.mw[2], d_in[1], 3072, true);
  encode_w(fn, &P.mwo[0], d_in[2], 1024, true);
  encode_w(fn, &P.mwo[1], d_in[6], 1024, false);
  encode_cs(fn, &P.mcs[0], d_in[1], 3072);
  encode_cs(fn, &P.mcs[1], d_in[4], 3072);
  {
    const cuuint64_t dims[2] = {32, 1024}, strides[1] = {64};
    const cuuint32_t box[2] = {32, 128};
    encode(fn, &P.mwphi, d_in[5], 2, dims, strides, box, CU_TENSOR_MAP_SWIZZLE_64B);
  }
  cudaFuncSetAttribute(fused_kernel, cudaFuncAttributeMaxDynamicSharedMemorySize, SMEM_BYTES);
  fused_kernel<<<NCTA, NTHREADS, SMEM_BYTES, cudaStreamPerThread>>>(P);
}
```

```cpp
#include <cuda_runtime.h>
#include <cuda_bf16.h>
#include <cuda.h>
#include <stdint.h>

namespace {

__device__ __forceinline__ void wgmma_ss_n256(float (&d)[128], uint32_t da, uint32_t ha, uint32_t db, int sd) {
  asm volatile("{\n.reg .pred p;\n.reg .b64 a, b;\nsetp.ne.b32 p, %130, 0;\nmov.b64 a, {%128, %131};\nmov.b64 b, {%129, 0x40000040};\n"
    "wgmma.mma_async.sync.aligned.m64n256k16.f32.bf16.bf16 {%0,%1,%2,%3,%4,%5,%6,%7,%8,%9,%10,%11,%12,%13,%14,%15,%16,%17,%18,%19,%20,%21,%22,%23,%24,%25,%26,%27,%28,%29,%30,%31,%32,%33,%34,%35,%36,%37,%38,%39,%40,%41,%42,%43,%44,%45,%46,%47,%48,%49,%50,%51,%52,%53,%54,%55,%56,%57,%58,%59,%60,%61,%62,%63,%64,%65,%66,%67,%68,%69,%70,%71,%72,%73,%74,%75,%76,%77,%78,%79,%80,%81,%82,%83,%84,%85,%86,%87,%88,%89,%90,%91,%92,%93,%94,%95,%96,%97,%98,%99,%100,%101,%102,%103,%104,%105,%106,%107,%108,%109,%110,%111,%112,%113,%114,%115,%116,%117,%118,%119,%120,%121,%122,%123,%124,%125,%126,%127}, a, b, p, 1, 1, 0, 1;\n}\n"
    : "+f"(d[0]),"+f"(d[1]),"+f"(d[2]),"+f"(d[3]),"+f"(d[4]),"+f"(d[5]),"+f"(d[6]),"+f"(d[7]),"+f"(d[8]),"+f"(d[9]),"+f"(d[10]),"+f"(d[11]),"+f"(d[12]),"+f"(d[13]),"+f"(d[14]),"+f"(d[15]),"+f"(d[16]),"+f"(d[17]),"+f"(d[18]),"+f"(d[19]),"+f"(d[20]),"+f"(d[21]),"+f"(d[22]),"+f"(d[23]),"+f"(d[24]),"+f"(d[25]),"+f"(d[26]),"+f"(d[27]),"+f"(d[28]),"+f"(d[29]),"+f"(d[30]),"+f"(d[31]),"+f"(d[32]),"+f"(d[33]),"+f"(d[34]),"+f"(d[35]),"+f"(d[36]),"+f"(d[37]),"+f"(d[38]),"+f"(d[39]),"+f"(d[40]),"+f"(d[41]),"+f"(d[42]),"+f"(d[43]),"+f"(d[44]),"+f"(d[45]),"+f"(d[46]),"+f"(d[47]),"+f"(d[48]),"+f"(d[49]),"+f"(d[50]),"+f"(d[51]),"+f"(d[52]),"+f"(d[53]),"+f"(d[54]),"+f"(d[55]),"+f"(d[56]),"+f"(d[57]),"+f"(d[58]),"+f"(d[59]),"+f"(d[60]),"+f"(d[61]),"+f"(d[62]),"+f"(d[63]),"+f"(d[64]),"+f"(d[65]),"+f"(d[66]),"+f"(d[67]),"+f"(d[68]),"+f"(d[69]),"+f"(d[70]),"+f"(d[71]),"+f"(d[72]),"+f"(d[73]),"+f"(d[74]),"+f"(d[75]),"+f"(d[76]),"+f"(d[77]),"+f"(d[78]),"+f"(d[79]),"+f"(d[80]),"+f"(d[81]),"+f"(d[82]),"+f"(d[83]),"+f"(d[84]),"+f"(d[85]),"+f"(d[86]),"+f"(d[87]),"+f"(d[88]),"+f"(d[89]),"+f"(d[90]),"+f"(d[91]),"+f"(d[92]),"+f"(d[93]),"+f"(d[94]),"+f"(d[95]),"+f"(d[96]),"+f"(d[97]),"+f"(d[98]),"+f"(d[99]),"+f"(d[100]),"+f"(d[101]),"+f"(d[102]),"+f"(d[103]),"+f"(d[104]),"+f"(d[105]),"+f"(d[106]),"+f"(d[107]),"+f"(d[108]),"+f"(d[109]),"+f"(d[110]),"+f"(d[111]),"+f"(d[112]),"+f"(d[113]),"+f"(d[114]),"+f"(d[115]),"+f"(d[116]),"+f"(d[117]),"+f"(d[118]),"+f"(d[119]),"+f"(d[120]),"+f"(d[121]),"+f"(d[122]),"+f"(d[123]),"+f"(d[124]),"+f"(d[125]),"+f"(d[126]),"+f"(d[127])
    : "r"(da), "r"(db), "r"(sd), "r"(ha));
}
__device__ __forceinline__ void wgmma_ss_n128(float (&d)[64], uint32_t da, uint32_t ha, uint32_t db, int sd) {
  asm volatile("{\n.reg .pred p;\n.reg .b64 a, b;\nsetp.ne.b32 p, %66, 0;\nmov.b64 a, {%64, %67};\nmov.b64 b, {%65, 0x40000040};\n"
    "wgmma.mma_async.sync.aligned.m64n128k16.f32.bf16.bf16 {%0,%1,%2,%3,%4,%5,%6,%7,%8,%9,%10,%11,%12,%13,%14,%15,%16,%17,%18,%19,%20,%21,%22,%23,%24,%25,%26,%27,%28,%29,%30,%31,%32,%33,%34,%35,%36,%37,%38,%39,%40,%41,%42,%43,%44,%45,%46,%47,%48,%49,%50,%51,%52,%53,%54,%55,%56,%57,%58,%59,%60,%61,%62,%63}, a, b, p, 1, 1, 0, 1;\n}\n"
    : "+f"(d[0]),"+f"(d[1]),"+f"(d[2]),"+f"(d[3]),"+f"(d[4]),"+f"(d[5]),"+f"(d[6]),"+f"(d[7]),"+f"(d[8]),"+f"(d[9]),"+f"(d[10]),"+f"(d[11]),"+f"(d[12]),"+f"(d[13]),"+f"(d[14]),"+f"(d[15]),"+f"(d[16]),"+f"(d[17]),"+f"(d[18]),"+f"(d[19]),"+f"(d[20]),"+f"(d[21]),"+f"(d[22]),"+f"(d[23]),"+f"(d[24]),"+f"(d[25]),"+f"(d[26]),"+f"(d[27]),"+f"(d[28]),"+f"(d[29]),"+f"(d[30]),"+f"(d[31]),"+f"(d[32]),"+f"(d[33]),"+f"(d[34]),"+f"(d[35]),"+f"(d[36]),"+f"(d[37]),"+f"(d[38]),"+f"(d[39]),"+f"(d[40]),"+f"(d[41]),"+f"(d[42]),"+f"(d[43]),"+f"(d[44]),"+f"(d[45]),"+f"(d[46]),"+f"(d[47]),"+f"(d[48]),"+f"(d[49]),"+f"(d[50]),"+f"(d[51]),"+f"(d[52]),"+f"(d[53]),"+f"(d[54]),"+f"(d[55]),"+f"(d[56]),"+f"(d[57]),"+f"(d[58]),"+f"(d[59]),"+f"(d[60]),"+f"(d[61]),"+f"(d[62]),"+f"(d[63])
    : "r"(da), "r"(db), "r"(sd), "r"(ha));
}
__device__ __forceinline__ void wgmma_ss_n40_tt(float (&d)[20], uint32_t da, uint32_t db, int sd) {
  asm volatile("{\n.reg .pred p;\n.reg .b64 a, b;\nsetp.ne.b32 p, %22, 0;\nmov.b64 a, {%20, 0x40000040};\nmov.b64 b, {%21, 0x8};\n"
    "wgmma.mma_async.sync.aligned.m64n40k16.f32.bf16.bf16 {%0,%1,%2,%3,%4,%5,%6,%7,%8,%9,%10,%11,%12,%13,%14,%15,%16,%17,%18,%19}, a, b, p, 1, 1, 1, 1;\n}\n"
    : "+f"(d[0]),"+f"(d[1]),"+f"(d[2]),"+f"(d[3]),"+f"(d[4]),"+f"(d[5]),"+f"(d[6]),"+f"(d[7]),"+f"(d[8]),"+f"(d[9]),"+f"(d[10]),"+f"(d[11]),"+f"(d[12]),"+f"(d[13]),"+f"(d[14]),"+f"(d[15]),"+f"(d[16]),"+f"(d[17]),"+f"(d[18]),"+f"(d[19])
    : "r"(da), "r"(db), "r"(sd));
}
__device__ __forceinline__ void wgmma_ss_n32(float (&d)[16], uint32_t da, uint32_t db, int sd) {
  asm volatile("{\n.reg .pred p;\n.reg .b64 a, b;\nsetp.ne.b32 p, %18, 0;\nmov.b64 a, {%16, 0x40000040};\nmov.b64 b, {%17, 0x80000020};\n"
    "wgmma.mma_async.sync.aligned.m64n32k16.f32.bf16.bf16 {%0,%1,%2,%3,%4,%5,%6,%7,%8,%9,%10,%11,%12,%13,%14,%15}, a, b, p, 1, 1, 0, 1;\n}\n"
    : "+f"(d[0]),"+f"(d[1]),"+f"(d[2]),"+f"(d[3]),"+f"(d[4]),"+f"(d[5]),"+f"(d[6]),"+f"(d[7]),"+f"(d[8]),"+f"(d[9]),"+f"(d[10]),"+f"(d[11]),"+f"(d[12]),"+f"(d[13]),"+f"(d[14]),"+f"(d[15])
    : "r"(da), "r"(db), "r"(sd));
}
__device__ __forceinline__ void wgmma_rs_n40(float (&d)[20], uint32_t a0, uint32_t a1, uint32_t a2, uint32_t a3, uint32_t db, int sd) {
  asm volatile("{\n.reg .pred p;\n.reg .b64 b;\nsetp.ne.b32 p, %25, 0;\nmov.b64 b, {%24, 0x10};\n"
    "wgmma.mma_async.sync.aligned.m64n40k16.f32.bf16.bf16 {%0,%1,%2,%3,%4,%5,%6,%7,%8,%9,%10,%11,%12,%13,%14,%15,%16,%17,%18,%19}, {%20,%21,%22,%23}, b, p, 1, 1, 1;\n}\n"
    : "+f"(d[0]),"+f"(d[1]),"+f"(d[2]),"+f"(d[3]),"+f"(d[4]),"+f"(d[5]),"+f"(d[6]),"+f"(d[7]),"+f"(d[8]),"+f"(d[9]),"+f"(d[10]),"+f"(d[11]),"+f"(d[12]),"+f"(d[13]),"+f"(d[14]),"+f"(d[15]),"+f"(d[16]),"+f"(d[17]),"+f"(d[18]),"+f"(d[19])
    : "r"(a0), "r"(a1), "r"(a2), "r"(a3), "r"(db), "r"(sd));
}
__device__ __forceinline__ void wgmma_r1_n256(float (&d)[128], uint32_t da, uint32_t db, int sd) {
  asm volatile("{\n.reg .pred p;\n.reg .b64 a, b;\nsetp.ne.b32 p, %130, 0;\nmov.b64 a, {%128, 0x8};\nmov.b64 b, {%129, 0x6};\n"
    "wgmma.mma_async.sync.aligned.m64n256k16.f32.bf16.bf16 {%0,%1,%2,%3,%4,%5,%6,%7,%8,%9,%10,%11,%12,%13,%14,%15,%16,%17,%18,%19,%20,%21,%22,%23,%24,%25,%26,%27,%28,%29,%30,%31,%32,%33,%34,%35,%36,%37,%38,%39,%40,%41,%42,%43,%44,%45,%46,%47,%48,%49,%50,%51,%52,%53,%54,%55,%56,%57,%58,%59,%60,%61,%62,%63,%64,%65,%66,%67,%68,%69,%70,%71,%72,%73,%74,%75,%76,%77,%78,%79,%80,%81,%82,%83,%84,%85,%86,%87,%88,%89,%90,%91,%92,%93,%94,%95,%96,%97,%98,%99,%100,%101,%102,%103,%104,%105,%106,%107,%108,%109,%110,%111,%112,%113,%114,%115,%116,%117,%118,%119,%120,%121,%122,%123,%124,%125,%126,%127}, a, b, p, 1, 1, 0, 1;\n}\n"
    : "+f"(d[0]),"+f"(d[1]),"+f"(d[2]),"+f"(d[3]),"+f"(d[4]),"+f"(d[5]),"+f"(d[6]),"+f"(d[7]),"+f"(d[8]),"+f"(d[9]),"+f"(d[10]),"+f"(d[11]),"+f"(d[12]),"+f"(d[13]),"+f"(d[14]),"+f"(d[15]),"+f"(d[16]),"+f"(d[17]),"+f"(d[18]),"+f"(d[19]),"+f"(d[20]),"+f"(d[21]),"+f"(d[22]),"+f"(d[23]),"+f"(d[24]),"+f"(d[25]),"+f"(d[26]),"+f"(d[27]),"+f"(d[28]),"+f"(d[29]),"+f"(d[30]),"+f"(d[31]),"+f"(d[32]),"+f"(d[33]),"+f"(d[34]),"+f"(d[35]),"+f"(d[36]),"+f"(d[37]),"+f"(d[38]),"+f"(d[39]),"+f"(d[40]),"+f"(d[41]),"+f"(d[42]),"+f"(d[43]),"+f"(d[44]),"+f"(d[45]),"+f"(d[46]),"+f"(d[47]),"+f"(d[48]),"+f"(d[49]),"+f"(d[50]),"+f"(d[51]),"+f"(d[52]),"+f"(d[53]),"+f"(d[54]),"+f"(d[55]),"+f"(d[56]),"+f"(d[57]),"+f"(d[58]),"+f"(d[59]),"+f"(d[60]),"+f"(d[61]),"+f"(d[62]),"+f"(d[63]),"+f"(d[64]),"+f"(d[65]),"+f"(d[66]),"+f"(d[67]),"+f"(d[68]),"+f"(d[69]),"+f"(d[70]),"+f"(d[71]),"+f"(d[72]),"+f"(d[73]),"+f"(d[74]),"+f"(d[75]),"+f"(d[76]),"+f"(d[77]),"+f"(d[78]),"+f"(d[79]),"+f"(d[80]),"+f"(d[81]),"+f"(d[82]),"+f"(d[83]),"+f"(d[84]),"+f"(d[85]),"+f"(d[86]),"+f"(d[87]),"+f"(d[88]),"+f"(d[89]),"+f"(d[90]),"+f"(d[91]),"+f"(d[92]),"+f"(d[93]),"+f"(d[94]),"+f"(d[95]),"+f"(d[96]),"+f"(d[97]),"+f"(d[98]),"+f"(d[99]),"+f"(d[100]),"+f"(d[101]),"+f"(d[102]),"+f"(d[103]),"+f"(d[104]),"+f"(d[105]),"+f"(d[106]),"+f"(d[107]),"+f"(d[108]),"+f"(d[109]),"+f"(d[110]),"+f"(d[111]),"+f"(d[112]),"+f"(d[113]),"+f"(d[114]),"+f"(d[115]),"+f"(d[116]),"+f"(d[117]),"+f"(d[118]),"+f"(d[119]),"+f"(d[120]),"+f"(d[121]),"+f"(d[122]),"+f"(d[123]),"+f"(d[124]),"+f"(d[125]),"+f"(d[126]),"+f"(d[127])
    : "r"(da), "r"(db), "r"(sd));
}
__device__ __forceinline__ void wgmma_r1_n128(float (&d)[64], uint32_t da, uint32_t db, int sd) {
  asm volatile("{\n.reg .pred p;\n.reg .b64 a, b;\nsetp.ne.b32 p, %66, 0;\nmov.b64 a, {%64, 0x8};\nmov.b64 b, {%65, 0x6};\n"
    "wgmma.mma_async.sync.aligned.m64n128k16.f32.bf16.bf16 {%0,%1,%2,%3,%4,%5,%6,%7,%8,%9,%10,%11,%12,%13,%14,%15,%16,%17,%18,%19,%20,%21,%22,%23,%24,%25,%26,%27,%28,%29,%30,%31,%32,%33,%34,%35,%36,%37,%38,%39,%40,%41,%42,%43,%44,%45,%46,%47,%48,%49,%50,%51,%52,%53,%54,%55,%56,%57,%58,%59,%60,%61,%62,%63}, a, b, p, 1, 1, 0, 1;\n}\n"
    : "+f"(d[0]),"+f"(d[1]),"+f"(d[2]),"+f"(d[3]),"+f"(d[4]),"+f"(d[5]),"+f"(d[6]),"+f"(d[7]),"+f"(d[8]),"+f"(d[9]),"+f"(d[10]),"+f"(d[11]),"+f"(d[12]),"+f"(d[13]),"+f"(d[14]),"+f"(d[15]),"+f"(d[16]),"+f"(d[17]),"+f"(d[18]),"+f"(d[19]),"+f"(d[20]),"+f"(d[21]),"+f"(d[22]),"+f"(d[23]),"+f"(d[24]),"+f"(d[25]),"+f"(d[26]),"+f"(d[27]),"+f"(d[28]),"+f"(d[29]),"+f"(d[30]),"+f"(d[31]),"+f"(d[32]),"+f"(d[33]),"+f"(d[34]),"+f"(d[35]),"+f"(d[36]),"+f"(d[37]),"+f"(d[38]),"+f"(d[39]),"+f"(d[40]),"+f"(d[41]),"+f"(d[42]),"+f"(d[43]),"+f"(d[44]),"+f"(d[45]),"+f"(d[46]),"+f"(d[47]),"+f"(d[48]),"+f"(d[49]),"+f"(d[50]),"+f"(d[51]),"+f"(d[52]),"+f"(d[53]),"+f"(d[54]),"+f"(d[55]),"+f"(d[56]),"+f"(d[57]),"+f"(d[58]),"+f"(d[59]),"+f"(d[60]),"+f"(d[61]),"+f"(d[62]),"+f"(d[63])
    : "r"(da), "r"(db), "r"(sd));
}

__device__ __forceinline__ uint32_t smem_u32(const void* p) { return (uint32_t)__cvta_generic_to_shared(p); }
__device__ __forceinline__ void mbar_init(uint32_t bar, uint32_t cnt) { asm volatile("mbarrier.init.shared::cta.b64 [%0], %1;" ::"r"(bar), "r"(cnt)); }
__device__ __forceinline__ void mbar_expect_tx(uint32_t bar, uint32_t bytes) { asm volatile("mbarrier.arrive.expect_tx.shared::cta.b64 _, [%0], %1;" ::"r"(bar), "r"(bytes) : "memory"); }
__device__ __forceinline__ void mbar_arrive(uint32_t bar) { asm volatile("mbarrier.arrive.shared::cta.b64 _, [%0];" ::"r"(bar) : "memory"); }
__device__ __forceinline__ void mbar_arrive_n(uint32_t bar, uint32_t n) { asm volatile("mbarrier.arrive.shared::cta.b64 _, [%0], %1;" ::"r"(bar), "r"(n) : "memory"); }
__device__ __forceinline__ void mbar_wait(uint32_t bar, uint32_t parity) {
  asm volatile("{\n.reg .pred p;\nLAB_WAIT:\nmbarrier.try_wait.parity.shared::cta.b64 p, [%0], %1;\n@p bra DONE;\nbra LAB_WAIT;\nDONE:\n}" ::"r"(bar), "r"(parity) : "memory");
}
__device__ __forceinline__ void mbar_wait2(uint32_t a, uint32_t pa, uint32_t b, uint32_t pb) {
  asm volatile("{\n.reg .pred p, q;\nLAB_WAIT:\nmbarrier.try_wait.parity.shared::cta.b64 p, [%0], %1;\nmbarrier.try_wait.parity.shared::cta.b64 q, [%2], %3;\n"
               "and.pred p, p, q;\n@p bra DONE;\nbra LAB_WAIT;\nDONE:\n}" ::"r"(a), "r"(pa), "r"(b), "r"(pb) : "memory");
}
__device__ __forceinline__ void mbar_wait3(uint32_t a, uint32_t pa, uint32_t b, uint32_t pb) {
  asm volatile("{\n.reg .pred p, q, r;\nLAB_WAIT:\nmbarrier.try_wait.parity.shared::cta.b64 p, [%0], %1;\nmbarrier.try_wait.parity.shared::cta.b64 q, [%2], %3;\n"
               "mbarrier.try_wait.parity.shared::cta.b64 r, [%2+8], %3;\nand.pred p, p, q;\nand.pred p, p, r;\n@p bra DONE;\nbra LAB_WAIT;\nDONE:\n}" ::"r"(a), "r"(pa), "r"(b), "r"(pb) : "memory");
}
__device__ __forceinline__ bool mbar_probe2(uint32_t a, uint32_t pa, uint32_t b, uint32_t pb) {
  uint32_t ok;
  asm volatile("{\n.reg .pred p, q;\nmbarrier.test_wait.parity.shared::cta.b64 p, [%1], %2;\nmbarrier.test_wait.parity.shared::cta.b64 q, [%3], %4;\n"
               "and.pred p, p, q;\nselp.u32 %0, 1, 0, p;\n}" : "=r"(ok) : "r"(a), "r"(pa), "r"(b), "r"(pb) : "memory");
  return ok != 0;
}
__device__ __forceinline__ void tma_load_3d(uint32_t dst, const CUtensorMap* tm, uint32_t bar, int c0, int c1, int c2) {
  asm volatile("cp.async.bulk.tensor.3d.shared::cluster.global.mbarrier::complete_tx::bytes [%0], [%1, {%3, %4, %5}], [%2];"
               ::"r"(dst), "l"(tm), "r"(bar), "r"(c0), "r"(c1), "r"(c2) : "memory");
}
__device__ __forceinline__ void tma_load_2d(uint32_t dst, const CUtensorMap* tm, uint32_t bar, int c0, int c1) {
  asm volatile("cp.async.bulk.tensor.2d.shared::cluster.global.mbarrier::complete_tx::bytes [%0], [%1, {%3, %4}], [%2];"
               ::"r"(dst), "l"(tm), "r"(bar), "r"(c0), "r"(c1) : "memory");
}
__device__ __forceinline__ void tma_load_w(uint32_t dst, const CUtensorMap* tm, uint32_t bar, int col, int kb) {
#pragma unroll
  for (int q = 0; q < 2; q++)
    asm volatile("cp.async.bulk.tensor.5d.shared::cluster.global.mbarrier::complete_tx::bytes [%0], [%1, {%3, %4, %4, %4, %5}], [%2];"
                 ::"r"(dst + q * 8192), "l"(tm), "r"(bar), "r"(col + q * 64), "r"(0), "r"(2 * kb) : "memory");
}
__device__ __forceinline__ void tma_prefetch_w(const CUtensorMap* tm, int col, int kb) {
#pragma unroll
  for (int q = 0; q < 2; q++)
    asm volatile("cp.async.bulk.prefetch.tensor.5d.L2.global [%0, {%1, %2, %2, %2, %3}];" ::"l"(tm), "r"(col + q * 64), "r"(0), "r"(2 * kb) : "memory");
}
__device__ __forceinline__ void bulk_load(uint32_t dst, const void* g, uint32_t bytes, uint32_t bar) {
  asm volatile("cp.async.bulk.shared::cluster.global.mbarrier::complete_tx::bytes [%0], [%1], %2, [%3];" ::"r"(dst), "l"(g), "r"(bytes), "r"(bar) : "memory");
}
__device__ __forceinline__ void prefetch_map(const CUtensorMap* tm) { asm volatile("prefetch.tensormap [%0];" ::"l"(tm) : "memory"); }
__device__ __forceinline__ void fence_async_smem() { asm volatile("fence.proxy.async.shared::cta;" ::: "memory"); }
__device__ __forceinline__ void fence_async_global() { asm volatile("fence.proxy.async.global;" ::: "memory"); }
__device__ __forceinline__ void fence_gpu() { asm volatile("fence.release.gpu;" ::: "memory"); }
__device__ __forceinline__ void st_flag(unsigned* p, unsigned v) { asm volatile("st.relaxed.gpu.global.u32 [%0], %1;" ::"l"(p), "r"(v) : "memory"); }
__device__ __forceinline__ unsigned ld_flag(const unsigned* p) { unsigned v; asm volatile("ld.relaxed.gpu.global.u32 %0, [%1];" : "=r"(v) : "l"(p) : "memory"); return v; }
__device__ __forceinline__ uint4 ldcg4(const void* p) { uint4 v; asm volatile("ld.global.cg.v4.u32 {%0,%1,%2,%3}, [%4];" : "=r"(v.x), "=r"(v.y), "=r"(v.z), "=r"(v.w) : "l"(p)); return v; }
__device__ __forceinline__ uint4 ld_pkt(const uint4* p) {
  uint4 v; asm volatile("{\n.reg .b128 t;\nld.relaxed.gpu.global.b128 t, [%4];\nmov.b128 {%0,%1,%2,%3}, t;\n}" : "=r"(v.x), "=r"(v.y), "=r"(v.z), "=r"(v.w) : "l"(p) : "memory"); return v;
}
__device__ __forceinline__ void st_pkt(uint4* p, uint32_t a, uint32_t b, uint32_t c, uint32_t tag) {
  asm volatile("{\n.reg .b128 t;\nmov.b128 t, {%1,%2,%3,%4};\nst.relaxed.gpu.global.b128 [%0], t;\n}" ::"l"(p), "r"(a), "r"(b), "r"(c), "r"(tag) : "memory");
}
__device__ __forceinline__ void st_v4(uint4* p, uint32_t a, uint32_t b, uint32_t c, uint32_t d) { asm volatile("st.relaxed.gpu.global.v4.u32 [%0], {%1,%2,%3,%4};" ::"l"(p), "r"(a), "r"(b), "r"(c), "r"(d) : "memory"); }
__device__ __forceinline__ void sts32(uint32_t addr, uint32_t a) { asm volatile("st.shared.u32 [%0], %1;" ::"r"(addr), "r"(a) : "memory"); }
__device__ __forceinline__ void sts64(uint32_t addr, uint32_t a, uint32_t b) { asm volatile("st.shared.v2.u32 [%0], {%1,%2};" ::"r"(addr), "r"(a), "r"(b) : "memory"); }
__device__ __forceinline__ uint32_t mul2(uint32_t a, uint32_t b) { uint32_t r; asm("mul.rn.bf16x2 %0, %1, %2;" : "=r"(r) : "r"(a), "r"(b)); return r; }
__device__ __forceinline__ uint32_t add2(uint32_t a, uint32_t b) { uint32_t r; asm("add.rn.bf16x2 %0, %1, %2;" : "=r"(r) : "r"(a), "r"(b)); return r; }
__device__ __forceinline__ bool elect() {
  uint32_t p; asm volatile("{\n.reg .pred q;\nelect.sync _|q, 0xffffffff;\nselp.u32 %0, 1, 0, q;\n}" : "=r"(p)); return p != 0;
}
__device__ __forceinline__ void wgmma_fence() { asm volatile("wgmma.fence.sync.aligned;" ::: "memory"); }
__device__ __forceinline__ void wgmma_commit() { asm volatile("wgmma.commit_group.sync.aligned;" ::: "memory"); }
template <int N> __device__ __forceinline__ void wgmma_wait() { asm volatile("wgmma.wait_group.sync.aligned %0;" ::"n"(N) : "memory"); }
template <int N> __device__ __forceinline__ void fence_regs(float (&d)[N]) {
#pragma unroll
  for (int i = 0; i < N; i++) asm volatile("" : "+f"(d[i])::"memory");
}
template <int R> __device__ __forceinline__ void reg_alloc() { asm volatile("setmaxnreg.inc.sync.aligned.u32 %0;" ::"n"(R)); }
template <int R> __device__ __forceinline__ void reg_dealloc() { asm volatile("setmaxnreg.dec.sync.aligned.u32 %0;" ::"n"(R)); }
__device__ __forceinline__ void wg_bar(int w) { asm volatile("bar.sync %0, 128;" ::"r"(w + 1) : "memory"); }
__device__ __forceinline__ constexpr uint32_t desc_lo(uint32_t addr, uint32_t lbo) { return (addr >> 4) + ((lbo >> 4) << 16); }
__device__ __forceinline__ uint32_t pack2(float lo, float hi) { uint32_t r; asm("cvt.rn.bf16x2.f32 %0, %1, %2;" : "=r"(r) : "f"(hi), "f"(lo)); return r; }
__device__ __forceinline__ float lo16(uint32_t v) { return __uint_as_float(v << 16); }
__device__ __forceinline__ float hi16(uint32_t v) { return __uint_as_float(v & 0xFFFF0000u); }
__device__ __forceinline__ float ex2(float x) { float r; asm("ex2.approx.ftz.f32 %0, %1;" : "=f"(r) : "f"(x)); return r; }
__device__ __forceinline__ float rcp(float x) { float r; asm("rcp.approx.ftz.f32 %0, %1;" : "=f"(r) : "f"(x)); return r; }
__device__ __forceinline__ uint32_t movm(uint32_t a) { uint32_t d; asm volatile("movmatrix.sync.aligned.m8n8.trans.b16 %0, %1;" : "=r"(d) : "r"(a)); return d; }
__device__ __forceinline__ void stsm4(uint32_t addr, uint32_t a, uint32_t b, uint32_t c, uint32_t d) {
  asm volatile("stmatrix.sync.aligned.m8n8.x4.shared.b16 [%0], {%1,%2,%3,%4};" ::"r"(addr), "r"(a), "r"(b), "r"(c), "r"(d) : "memory");
}
__device__ __forceinline__ void ldsm4(uint32_t addr, uint32_t (&r)[4]) {
  asm volatile("ldmatrix.sync.aligned.m8n8.x4.shared.b16 {%0,%1,%2,%3}, [%4];" : "=r"(r[0]), "=r"(r[1]), "=r"(r[2]), "=r"(r[3]) : "r"(addr) : "memory");
}
__device__ __forceinline__ void sts128(uint32_t addr, uint32_t a, uint32_t b, uint32_t c, uint32_t d) {
  asm volatile("st.shared.v4.u32 [%0], {%1,%2,%3,%4};" ::"r"(addr), "r"(a), "r"(b), "r"(c), "r"(d) : "memory");
}
__device__ __forceinline__ void lds128(uint32_t addr, uint32_t& a, uint32_t& b, uint32_t& c, uint32_t& d) {
  asm volatile("ld.shared.v4.u32 {%0,%1,%2,%3}, [%4];" : "=r"(a), "=r"(b), "=r"(c), "=r"(d) : "r"(addr) : "memory");
}
__device__ __forceinline__ float lds32f(uint32_t addr) { float v; asm volatile("ld.shared.f32 %0, [%1];" : "=f"(v) : "r"(addr) : "memory"); return v; }
__device__ __forceinline__ float2 lds64f(uint32_t addr) { float2 v; asm volatile("ld.shared.v2.f32 {%0,%1}, [%2];" : "=f"(v.x), "=f"(v.y) : "r"(addr) : "memory"); return v; }
__device__ __forceinline__ void mma16816(float (&d)[4], uint32_t a0, uint32_t a1, uint32_t a2, uint32_t a3, uint32_t b0, uint32_t b1) {
  asm("mma.sync.aligned.m16n8k16.row.col.f32.bf16.bf16.f32 {%0,%1,%2,%3}, {%4,%5,%6,%7}, {%8,%9}, {%0,%1,%2,%3};"
      : "+f"(d[0]), "+f"(d[1]), "+f"(d[2]), "+f"(d[3]) : "r"(a0), "r"(a1), "r"(a2), "r"(a3), "r"(b0), "r"(b1));
}
__device__ __forceinline__ void mma1688(float (&d)[4], uint32_t a0, uint32_t a1, uint32_t b0) {
  asm("mma.sync.aligned.m16n8k8.row.col.f32.bf16.bf16.f32 {%0,%1,%2,%3}, {%4,%5}, {%6}, {%0,%1,%2,%3};"
      : "+f"(d[0]), "+f"(d[1]), "+f"(d[2]), "+f"(d[3]) : "r"(a0), "r"(a1), "r"(b0));
}

__device__ __forceinline__ float qsum(float v) { v += __shfl_xor_sync(0xffffffffu, v, 1); v += __shfl_xor_sync(0xffffffffu, v, 2); return v; }

constexpr int NCTA = 132;
#define NB_ 6
#define NA_ 5
constexpr int NB = NB_;
constexpr int NA = NA_;
constexpr uint32_t SLOT = 16384;
constexpr uint32_t SB = 1024;
constexpr uint32_t OFF_B = 0;
constexpr uint32_t OFF_A = NB * SLOT;
constexpr uint32_t OFF_S = OFF_A + NA * SLOT;
constexpr uint32_t OFF_T = OFF_S + 20480;
constexpr uint32_t OFF_CS = OFF_T + 24576;
constexpr uint32_t OFF_MR = OFF_CS + 4640;
constexpr uint32_t OFF_BAR = OFF_MR + 512;
constexpr uint32_t OFF_MA = OFF_S, OFF_MB = OFF_CS - 2048;
constexpr uint32_t BAR_FULLB = OFF_BAR;
constexpr uint32_t BAR_FULLA = BAR_FULLB + 64;
constexpr uint32_t BAR_EMPTYB = BAR_FULLA + 64;
constexpr uint32_t BAR_EMPTYA = BAR_EMPTYB + 64;
constexpr uint32_t BAR_SIGP = BAR_EMPTYA + 64;
constexpr uint32_t BAR_SIGT = BAR_SIGP + 32;
constexpr uint32_t BAR_STAT = BAR_SIGP + 64;
constexpr uint32_t BAR_HALO = BAR_STAT + 16;
constexpr uint32_t BAR_CS = BAR_HALO + 8;
constexpr uint32_t BAR_WPHI = BAR_CS + 16;
constexpr uint32_t BAR_KV = BAR_WPHI + 8;
constexpr uint32_t BAR_STG = BAR_KV + 16;
constexpr uint32_t BAR_EPOCH = BAR_STG + 48;
constexpr uint32_t OFF_EPOCH = OFF_BAR + 7 * 64;
static_assert(BAR_EPOCH < OFF_EPOCH, "barriers");
constexpr uint32_t SMEM_BYTES = OFF_EPOCH + 8;
static_assert(SMEM_BYTES <= 232448 && NB % 2 == 0 && NB <= 8 && NA <= 6, "smem");

#define CREGS 208
#define PREGS 88
#define PF0 9
#define PF1 13
#define PF2 17
#define PRE_A 2
#define PRE_B 4
#define CSB 4
#define CSNEED 0xF003u
#define XR 2
#define PS0 2
#define PS1 2
#define PSW 0
#define STG0 0
#define QORD 2
#define KSPLIT 12
#define KEEP 16
#define NJ 3
#define KSL 1000
#define PSL 0
#define KVS 12
#define RH 0
#define D2 2000
#define D3 1500
#define G0 50
#define G3 50
#define G1 0
#define G4 0
#define MAP 3
#define PMAP 0x76321450u
#define PW 1
#define KB 8
#define PNX 2
#define PNO 2
#define DEFER 3
#define DEFL 2
#define TSK 3
#define TSL 3
constexpr int NTHREADS = 384;

struct Params {
  CUtensorMap mx;
  CUtensorMap mw[3];
  CUtensorMap mwo[2];
  CUtensorMap mcs[2];
  CUtensorMap mwphi;
  uint4* out;
};

#define XBUF(L) 1
__device__ __align__(256) uint4 g_img[XBUF(3) + 1][16][16][1024];
__device__ __align__(256) uint4 g_wf[2][8][16][1024];
__device__ __align__(256) uint4 g_stats[16][2][8][32];
__device__ __align__(256) uint4 g_halo[16][8][2][256];
__device__ __align__(256) float g_cs[2][2][3072];
__device__ __align__(256) uint4 g_kvpart[8][16][2][544];
__device__ __align__(256) uint4 g_kvfin[8][16][80];
__device__ __align__(256) unsigned g_xflag[4][2][16][32];
__device__ __align__(256) unsigned g_oflag[4][2][16][32];
__device__ __align__(256) unsigned g_hflag[2][16][8][32];
__device__ __align__(256) unsigned g_kvfflag[2][8][2][32];
__device__ __align__(256) unsigned g_csflag[2][8][32];
__device__ __align__(256) unsigned g_kflag[8][32];
__device__ unsigned g_ctr;
__device__ __forceinline__ unsigned vblock() {
  unsigned s;
  asm volatile("mov.u32 %0, %%smid;" : "=r"(s));
  const unsigned r = s & 1;
  s >>= 1;
  const unsigned t = s - 32, q = (t * 37) >> 8;
  const unsigned hi = s < 60 ? 12 + (t - 7 * q) * 8 + q : (s < 62 ? s + 4 : s - 58);
  unsigned b = 2 * (s < 32 ? (s & 7) * 8 + (s >> 3) : hi) + r;
  if (b < 128) b = (b & 15) | ((PMAP >> ((b >> 4) * 4)) & 7) << 4;
  if (s >= 62) b = 8 + 4 * r + s - 62;
  return __shfl_sync(0xffffffffu, b, 0);
}
#define TS(who, id) do {} while (0)
#define TSW(id) do {} while (0)

__device__ __forceinline__ int cta_m(unsigned b) { return ((b >> 2) & 12) | (b & 3); }
__device__ __forceinline__ int cta_j(unsigned b) { return ((b >> 2) & 3) | ((b >> 4) & 4); }
struct Ring { uint32_t s, ph; };
template <int N> __device__ __forceinline__ void adv(Ring& r) { if (++r.s == N) { r.s = 0; r.ph ^= 1; } }
template <int N> __device__ __forceinline__ void rewind2(Ring& r) { if (r.s < 2) { r.s += N - 2; r.ph ^= 1; } else r.s -= 2; }
__device__ __forceinline__ int other_tile(int t, int j) { return (t == (j | 4) ? 7 : t) ^ (~j & 4); }
__device__ __forceinline__ int q_order(int i, int j) { return 2 * (i >= 14 ? j : other_tile(i >> 1, j)) + (i & 1); }
__device__ __forceinline__ int o_order(int i, int j) {
  if (i < 2) return 2 * j + i;
  const int odd = i >= 9;
  return 2 * other_tile(i - 2 - 7 * odd, j) + odd;
}
__device__ __forceinline__ int kv_order(int i, int j, int L) { return L > 0 ? o_order(i, j) : (i + 14 + 2 * (j & 4)) & 15; }

__device__ __forceinline__ unsigned poll_flags(const unsigned* f, int n, unsigned need, unsigned tag) {
  const int lane = threadIdx.x & 31;
  unsigned mask; int it = 0;
  do {
    unsigned v = lane < n ? ld_flag(f + lane) : 0u;
    mask = __ballot_sync(0xffffffffu, lane < n && v == tag);
    if (++it > (1 << 22)) __trap();
  } while ((mask & need) != need);
  fence_async_global();
  return mask;
}
template <bool WAIT = true>
__device__ __forceinline__ unsigned get_tag(uint32_t sb) {
  if (WAIT) mbar_wait(sb + BAR_EPOCH, 0);
  unsigned t; asm volatile("ld.shared.u32 %0, [%1];" : "=r"(t) : "r"(sb + OFF_EPOCH) : "memory");
  return t;
}

__device__ __forceinline__ int lane_id() { int l; asm volatile("mov.u32 %0, %%laneid;" : "=r"(l)); return l; }
__device__ __forceinline__ unsigned seq4(unsigned tag, int L) { return 8u | ((tag & 1u) << 2) | (unsigned)L; }
constexpr float LOG2E = 1.4426950408889634f;

__device__ __forceinline__ void sched_fence(uint32_t sb) { mbar_wait(sb + BAR_EPOCH, 0); }
constexpr uint32_t HA128 = 0x40000040u, HA64 = 0x80000040u;
struct Ctx {
  static constexpr uint32_t sb = SB;
  uint32_t ab, da0;
  int w, warp, lane, g, c;
  int goff;
  __device__ __forceinline__ int m() const { return goff >> 14; }
  __device__ __forceinline__ int j() const { return (goff >> 4) & 7; }
  bool elected;
  Ring ra, rb;
  uint32_t pa, pb;
  uint32_t ha, k2;
  uint32_t mrow, mxor, mhi;
  __device__ __forceinline__ uint32_t aslot(uint32_t s) const { return ab + s * SLOT; }
  __device__ __forceinline__ uint32_t fullA(uint32_t s) const { return sb + BAR_FULLA + s * 8; }
  __device__ __forceinline__ uint32_t fullB(uint32_t s) const { return sb + BAR_FULLB + s * 8; }
  __device__ __forceinline__ void releaseA(uint32_t s) const { if (elected) mbar_arrive(sb + BAR_EMPTYA + s * 8); }
  __device__ __forceinline__ void releaseB(uint32_t s) const { if (elected) mbar_arrive(sb + BAR_EMPTYB + s * 8); }
  __device__ __forceinline__ uint32_t maddr(uint32_t tile, uint32_t ch) const { return tile + mrow + (((ch + mhi) ^ mxor) << 4); }
  __device__ __forceinline__ uint32_t oo() const { return warp * 128 + g * 4 + (c ^ (g >> 1)); }
  __device__ __forceinline__ uint4* img(int b, int hp) const { return &g_img[b][m()][2 * j() + hp][w * 512 + oo()]; }
  __device__ __forceinline__ uint32_t held(int i) const { return ra.s + i < 2 ? ra.s + i + NA - 2 : ra.s + i - 2; }
};

template <int N, bool FIRST, bool O = true>
__device__ __forceinline__ void gemm_issue(float (&acc)[N / 2], Ctx& x, bool ready = false) {
  if (!ready) {
    if (N == 256) mbar_wait3(x.fullA(x.ra.s), x.ra.ph, x.fullB(x.rb.s), x.rb.ph);
    else mbar_wait2(x.fullA(x.ra.s), x.ra.ph, x.fullB(x.rb.s), x.rb.ph);
  }
  const uint32_t da = x.da0 + x.ra.s * (SLOT / 16), db = desc_lo(SB + OFF_B, 8192) + x.rb.s * (SLOT / 16);
  wgmma_fence();
#pragma unroll
  for (int k = 0; k < 4; k++) {
    const uint32_t a = da + (k >> 1) * (O ? 32 : x.k2) + (k & 1) * 2, ha = O ? HA64 : x.ha;
    if constexpr (N == 256) wgmma_ss_n256(acc, a, ha, db + 128 * k, !(FIRST && k == 0));
    else wgmma_ss_n128(acc, a, ha, db + 128 * k, !(FIRST && k == 0));
  }
  wgmma_commit();
}
template <int N>
__device__ __forceinline__ void gemm_next(Ctx& x) {
  x.pa = x.ra.s; x.pb = x.rb.s;
  if (N == 256) x.rb.s++;
  adv<NA>(x.ra); adv<NB>(x.rb);
}
template <int N>
__device__ __forceinline__ void gemm_release(Ctx& x, bool relA) {
  if (relA) x.releaseA(x.pa);
  x.releaseB(x.pb);
  if (N == 256) x.releaseB(x.pb + 1);
}
template <int N>
__device__ __forceinline__ void gemm_retire(Ctx& x, bool relA) { wgmma_wait<1>(); gemm_release<N>(x, relA); gemm_next<N>(x); }
template <bool O = true>
__device__ __forceinline__ void gemm_run(float (&acc)[64], Ctx& x, int n, int hold, int n4 = 0) {
  bool ready = false;
#pragma unroll 1
  for (; n > 0; n--) {
    gemm_issue<128, false, O>(acc, x, ready);
    const uint32_t pa = x.pa, pb = x.pb;
    gemm_next<128>(x);
    ready = mbar_probe2(x.fullA(x.ra.s), x.ra.ph, x.fullB(x.rb.s), x.rb.ph);
    wgmma_wait<1>();
    if (n > hold) x.releaseA(pa);
    x.releaseB(pb);
  }
}
__device__ __forceinline__ void gemm_end(float (&acc)[64], Ctx& x) { wgmma_wait<0>(); fence_regs(acc); gemm_release<128>(x, false); }

__device__ __forceinline__ void load_x32(float* a, uint32_t tile, uint32_t ch, const Ctx& x) {
#pragma unroll
  for (int p = 0; p < 2; p++) {
    uint32_t v[4];
    ldsm4(x.maddr(tile, ch + 2 * p), v);
#pragma unroll
    for (int i = 0; i < 4; i++) { a[8 * p + 2 * i] = lo16(v[i]); a[8 * p + 2 * i + 1] = hi16(v[i]); }
  }
}

__device__ __forceinline__ void rows_load(uint4* r, uint32_t tile, const Ctx& x) {
#pragma unroll
  for (int q = 0; q < 4; q++) {
    const uint32_t row = x.warp * 16 + 4 * q + (x.lane >> 3);
    lds128(tile + row * 128 + (((x.lane & 7) ^ (row & 7)) << 4), r[q].x, r[q].y, r[q].z, r[q].w);
  }
}
__device__ __forceinline__ void rows_store(const uint4* r, uint4* g, const Ctx& x) {
  g += (x.warp * 16 + (x.lane >> 3)) * 256 + (x.lane & 7);
#pragma unroll
  for (int q = 0; q < 4; q++) g[q * 1024] = r[q];
}
__device__ __forceinline__ void publish(int id, const Ctx& x) { __syncwarp(); if (x.lane == 0) mbar_arrive(x.sb + BAR_SIGP + id * 8); }
__device__ __forceinline__ void img_store(const uint4 (&r)[4], uint4* g) {
#pragma unroll
  for (int q = 0; q < 4; q++) g[q * 32] = r[q];
}
__device__ __forceinline__ void img_sts(const uint4 (&r)[4], uint32_t tile, const Ctx& x) {
#pragma unroll
  for (int q = 0; q < 4; q++) sts128(tile + x.oo() * 16 + q * 512, r[q].x, r[q].y, r[q].z, r[q].w);
}
__device__ __forceinline__ void img_load(uint32_t (&v)[16], uint32_t tile, const Ctx& x) {
#pragma unroll
  for (int q = 0; q < 4; q++) lds128(tile + x.oo() * 16 + q * 512, v[4 * q], v[4 * q + 1], v[4 * q + 2], v[4 * q + 3]);
}
__device__ __forceinline__ void img_unpack(float* a, const uint32_t (&v)[16]) {
#pragma unroll
  for (int q = 0; q < 16; q++) { a[4 * (q & 7) + 2 * (q >> 3)] = lo16(v[q]); a[4 * (q & 7) + 2 * (q >> 3) + 1] = hi16(v[q]); }
}

template <int N>
__device__ __forceinline__ void stats_acc(const float* a, float (&t)[4]) {
#pragma unroll
  for (int i = 0; i < N; i++) { t[i & 2] += a[i]; t[(i & 2) + 1] = fmaf(a[i], a[i], t[(i & 2) + 1]); }
}
__device__ __forceinline__ void stats_send(float (&t)[4], int L, const Ctx& x) {
  const unsigned seq = seq4(get_tag<false>(x.sb), L);
#pragma unroll
  for (int q = 0; q < 4; q++) t[q] = qsum(t[q]);
  if (x.c == 0) st_pkt(&g_stats[x.m()][x.w][x.j()][x.warp * 8 + x.g], __float_as_uint(t[0]), __float_as_uint(t[1]), __float_as_uint(t[2]), (__float_as_uint(t[3]) & ~15u) | seq);
}
__device__ __forceinline__ void out_epilogue(const float (&acc)[64], uint4 (&r1)[4], uint4* g, int L, Ctx& x) {
  const uint32_t t0 = x.aslot(x.ra.s), t1 = x.aslot(x.ra.s + 1 == NA ? 0 : x.ra.s + 1);
  if (L == 3) {
#pragma unroll
    for (int p = 0; p < 8; p++) {
      stsm4(x.maddr(p < 4 ? t0 : t1, (p & 3) * 2), pack2(acc[8 * p], acc[8 * p + 1]), pack2(acc[8 * p + 2], acc[8 * p + 3]),
            pack2(acc[8 * p + 4], acc[8 * p + 5]), pack2(acc[8 * p + 6], acc[8 * p + 7]));
      if ((p & 3) == 3) { uint4 r[4]; __syncwarp(); rows_load(r, p < 4 ? t0 : t1, x); rows_store(r, g + (p >> 2) * 8, x); }
    }
  } else {
    auto pack16 = [&](uint4 (&r)[4], const float* a) {
#pragma unroll
      for (int q = 0; q < 4; q++) { const float* u = a + 16 * (q & 1) + (q & 2); r[q] = make_uint4(pack2(u[0], u[1]), pack2(u[4], u[5]), pack2(u[8], u[9]), pack2(u[12], u[13])); }
    };
    uint4 r0[4];
    pack16(r0, acc);
    img_store(r0, x.img(XBUF(L + 1), 0));
    publish(2, x);
    img_sts(r0, t0, x);
    sched_fence(x.sb);
    pack16(r1, acc + 32);
    img_sts(r1, t1, x);
    float t[4] = {0.f, 0.f, 0.f, 0.f}, u[4] = {0.f, 0.f, 0.f, 0.f};
    stats_acc<32>(acc, t); stats_acc<32>(acc + 32, u);
#pragma unroll
    for (int q = 0; q < 4; q++) t[q] += u[q];
    stats_send(t, L + 1, x);
    mbar_wait2(x.fullB(x.rb.s), x.rb.ph, x.fullB(x.rb.s + 1), x.rb.ph);
    fence_async_smem();
    asm volatile("bar.sync %0, %1;" ::"r"(L == 1 ? x.w + 1 : 3), "r"(L == 1 ? 128 : 256) : "memory");
  }
}

struct Stats { float rstd0, rstd1; };
__device__ __forceinline__ Stats load_stats(int half, const Ctx& x) {
  const float2 u = lds64f(x.sb + OFF_MR + half * 256 + (x.warp * 8 + x.g) * 8);
  return {u.x, u.y};
}

template <int NK>
__device__ __forceinline__ void hedgehog_scale(float* t, const Stats& st, const uint32_t* keep) {
#pragma unroll
  for (int q = 0; q < 16; q++) t[q] *= ((q & 2) ? st.rstd1 : st.rstd0) * LOG2E;
  float m[4];
#pragma unroll
  for (int q = 0; q < 4; q++) m[q] = fmaxf(fmaxf(fabsf(t[4 * q]), fabsf(t[4 * q + 1])), fmaxf(fabsf(t[4 * q + 2]), fabsf(t[4 * q + 3])));
  if (__builtin_expect(__any_sync(0xffffffffu, fmaxf(fmaxf(m[0], m[1]), fmaxf(m[2], m[3])) > 58.f), 0)) {
    float z[16 + NK];
#pragma unroll
    for (int q = 0; q < 16 + NK; q++) z[q] = q < 16 ? t[q & 15] : __uint_as_float(keep[q & 15]);
#pragma unroll 1
    for (int r = 0; r < 4; r += 2) {
      float hi = -INFINITY, lo = INFINITY;
#pragma unroll 1
      for (int i = 0; i < 16; i++) {
        const int k = (i & 6) * 2 + (i & 1) + r;
        const float v = z[k];
        if (i < 8) { hi = fmaxf(hi, v); lo = fminf(lo, v); }
        else z[k] = v - fminf(fmaxf(v, lo), hi);
        if (i == 7) {
#pragma unroll 1
          for (int d = 1; d <= 2; d++) { hi = fmaxf(hi, __shfl_xor_sync(0xffffffffu, hi, d)); lo = fminf(lo, __shfl_xor_sync(0xffffffffu, lo, d)); }
          const float mid = 0.5f * hi + 0.5f * lo;
          hi = fmaxf(hi - 58.f, mid); lo = fminf(lo + 58.f, mid);
        }
      }
    }
#pragma unroll
    for (int q = 0; q < 16; q++) t[q] = z[q];
  }
}
__device__ __forceinline__ void dual_exp(const float* t, uint32_t (&f)[18], int never) {
  float e[KSPLIT];
#pragma unroll
  for (int q = 0; q < KSPLIT; q++) e[q] = ex2(q < 16 ? t[q] : -t[q & 15]);
  while (never < 0) {
#pragma unroll
    for (int i = 0; i < KSPLIT; i += 4) asm volatile("ld.shared.v4.f32 {%0,%1,%2,%3}, [%4];" : "=f"(e[i]), "=f"(e[i + 1]), "=f"(e[i + 2]), "=f"(e[i + 3]) : "r"(never + i) : "memory");
    never += __float_as_int(e[0]);
  }
#pragma unroll
  for (int q = 0; q < KSPLIT; q += 2) f[q >> 1] = pack2(e[q], e[q + 1]);
#pragma unroll
  for (int q = KSPLIT; q < 32; q += 2) f[q >> 1] = q < 16 ? pack2(ex2(t[q]), ex2(t[q + 1])) : pack2(ex2(-t[q & 15]), ex2(-t[(q & 15) + 1]));
#pragma unroll
  for (int sg = 0; sg < 2; sg++) {
    const uint32_t* u = f + 8 * sg;
    const uint32_t a = add2(add2(u[0], u[2]), add2(u[4], u[6])), b = add2(add2(u[1], u[3]), add2(u[5], u[7]));
    f[16 + sg] = add2(__byte_perm(a, b, 0x5410), __byte_perm(a, b, 0x7632));
  }
}
__device__ __forceinline__ void dual_exp_rcp(const float* t, uint32_t (&f)[16]) {
#pragma unroll
  for (int q = 0; q < 8; q++) {
    const float a = ex2(t[2 * q]), b = ex2(t[2 * q + 1]), r = rcp(a * b);
    f[q] = pack2(a, b); f[8 + q] = pack2(r * b, r * a);
  }
}
__device__ __forceinline__ void cta_bar() { asm volatile("bar.sync 3, 256;" ::: "memory"); }

template <int N> __device__ __forceinline__ void pin(const uint32_t* v, uint32_t addr) {
#pragma unroll
  for (int i = 0; i < N; i += 4)
    asm volatile("{\n.reg .pred p;\nsetp.eq.u32 p, %0, 0;\n@p st.shared.v4.u32 [%0], {%1,%2,%3,%4};\n}" ::"r"(addr), "r"(v[i]), "r"(v[i + 1]), "r"(v[i + 2]), "r"(v[i + 3]) : "memory");
}

__device__ __forceinline__ void consumer(const Params& P, uint32_t sb, int w, unsigned vb) {
  Ctx x;
  x.w = w;
  x.ab = sb + OFF_A + w * 8192; x.da0 = desc_lo(SB + OFF_A, 16) + w * 512;
  x.lane = threadIdx.x & 31; x.warp = __shfl_sync(0xffffffffu, (threadIdx.x >> 5) & 3, 0); x.g = x.lane >> 2; x.c = x.lane & 3;
  x.goff = (cta_m(vb) * 128 + w) * 128 + cta_j(vb) * 16;
  asm volatile("" : "+r"(x.goff));
  x.elected = (threadIdx.x & 127) == 0;
  x.ra = {0, 0}; x.rb = {0, 0}; x.pa = x.pb = 0;
  {
    const uint32_t row = x.warp * 16 + (x.lane & 15);
    x.mrow = row * 128; x.mxor = row & 7; x.mhi = x.lane >> 4;
  }
  const int goff = x.goff;
  uint4 r1[4];
#pragma unroll
  for (int i = 0; i < 4; i++) r1[i] = make_uint4(0, 0, 0, 0);
  TSW(0);
  mbar_wait3(x.fullA(0), 0, x.fullB(0), 0);
#pragma unroll 1
  for (int L = 0; L < 4; L++) {
    float acc[64];
    constexpr uint32_t dcs = desc_lo(SB + OFF_CS, 0);
    if ((L & 1) == 0) {
    float kv[128];
    x.ha = L ? HA64 : HA128; x.k2 = L ? 32 : 4;
    gemm_issue<256, true, false>(kv, x, true); gemm_next<256>(x);
    {
      int i = 1;
      bool rel = true;
      float t[4] = {0.f, 0.f, 0.f, 0.f};
#pragma unroll 1
      for (int seg = 0; seg < 3; seg++) {
        const int end = seg < 2 ? (L == 0 ? 3 + 2 * (x.j() & 3) + seg : 2 + seg * 2) : 14 + L;
#pragma unroll 1
        while (true) {
          gemm_issue<256, false, false>(kv, x);
          if (++i == end) break;
          wgmma_wait<1>();
          if (rel) gemm_release<256>(x, true);
          rel = true;
          gemm_next<256>(x);
          if (i == 5) TSW(8 + L * 12);
          if (i == 11) TSW(10 + L * 12);
        }
        if (seg < 2 && L == 0) {
          float a[32];
          const uint32_t tile = x.aslot(x.ra.s);
          load_x32(a, tile, 0, x); load_x32(a + 16, tile, 4, x);
          stats_acc<32>(a, t);
          if (seg == 1) { mbar_wait(sb + BAR_EPOCH, 0); stats_send(t, 0, x); }
          fence_async_smem();
          wg_bar(w);
        }
        if (seg == 1 && L > 0) { img_store(r1, x.img(XBUF(L), 1)); publish(3, x); }
        wgmma_wait<1>();
        if (rel) gemm_release<256>(x, true);
        rel = true;
        gemm_next<256>(x);
        if (seg == 0 && L > 0) { wgmma_wait<0>(); gemm_release<256>(x, true); rel = false; }
      }
    }
      const Ring kt = x.ra;
      if (L == 0) adv<NA>(x.ra);
#pragma unroll 1
      for (int h = L; h < 2; h++) {
        float d[16];
        mbar_wait2(x.fullA(kt.s), kt.ph, sb + BAR_WPHI, 0);
        wgmma_fence();
#pragma unroll
        for (int q = 0; q < 2; q++) wgmma_ss_n32(d, x.da0 + kt.s * (SLOT / 16) + h * 4 + q * 2, desc_lo(SB + OFF_S + 4096, 512) + w * 256 + h * 128 + q * 64, q);
        wgmma_commit();
        gemm_issue<256, false, false>(kv, x);
        gemm_retire<256>(x, true);
        if (h) x.releaseA(kt.s);
        fence_regs(d);
        uint4* dst = &g_wf[1][x.j()][x.m()][w * 512 + (x.warp * 16 + x.g) * 8 + ((h * 4 + x.c) ^ x.g)];
        dst[0] = make_uint4(pack2(d[0], d[1]), pack2(d[4], d[5]), pack2(d[8], d[9]), pack2(d[12], d[13]));
        dst[64] = make_uint4(pack2(d[2], d[3]), pack2(d[6], d[7]), pack2(d[10], d[11]), pack2(d[14], d[15]));
      }
      const uint32_t dm = desc_lo(SB + OFF_MA, 0) + w * 64;
      mbar_wait2(sb + BAR_STAT, 0, sb + BAR_CS, 0);
      wgmma_fence();
      wgmma_r1_n256(kv, dm, dcs + 96, 1);
      wgmma_commit();
      const Stats st = load_stats(w, x);
      if (PW & 1) mbar_wait2(x.fullA(x.ra.s), x.ra.ph, x.fullB(x.rb.s), x.rb.ph);
      wgmma_wait<0>();
      fence_regs(kv);
      gemm_release<256>(x, true);
      TSW(2 + L * 12);
      uint32_t P0[32], P1[32], PH[32];
#pragma unroll
      for (int t = 0; t < 16; t++) { P0[t] = pack2(kv[4 * t] * st.rstd0, kv[4 * t + 1] * st.rstd0); P1[t] = pack2(kv[4 * t + 2] * st.rstd1, kv[4 * t + 3] * st.rstd1); }
      pin<16>(P0, x.mrow + 16);
      {
#pragma unroll
        for (int q = 0; q < 4; q++) sts128((x.warp < 3 ? sb + OFF_T + w * 12288 + x.warp * 4096 : sb + OFF_S + 16384 + w * 2048) + x.lane * 16 + q * 512, P1[4 * q], P1[4 * q + 1], P1[4 * q + 2], P1[4 * q + 3]);
      }
      wgmma_fence();
      wgmma_r1_n128(acc, dm, dcs, 0);
      gemm_issue<128, false, false>(acc, x, PW & 1); gemm_next<128>(x);
      TSW(3 + L * 12);
#pragma unroll
      for (int s = 0; s < 4; s++) {
#pragma unroll
        for (int t = 16 + 8 * (s & 1); t < 24 + 8 * (s & 1); t++) {
          if (s < 2) P1[t] = movm(pack2(kv[4 * t + 2] * st.rstd1, kv[4 * t + 3] * st.rstd1));
          else P0[t] = movm(pack2(kv[4 * t] * st.rstd0, kv[4 * t + 1] * st.rstd0));
        }
        if (s < 3) { gemm_issue<128, false, false>(acc, x); gemm_retire<128>(x, true); }
        if (s == 1) {
          if (x.warp < 3) {
#pragma unroll
            for (int q = 4; q < 8; q++) sts128(sb + OFF_T + w * 12288 + x.warp * 4096 + x.lane * 16 + q * 512, P1[4 * q], P1[4 * q + 1], P1[4 * q + 2], P1[4 * q + 3]);
          } else {
            uint4* dst = &g_halo[x.m()][x.j()][w][x.lane];
#pragma unroll
            for (int q = 0; q < 8; q++) dst[q * 32] = make_uint4(P1[4 * q], P1[4 * q + 1], P1[4 * q + 2], P1[4 * q + 3]);
          }
          publish(4, x);
          gemm_issue<128, false, false>(acc, x);
          gemm_retire<128>(x, true);
        }
      }
      TSW(4 + L * 12);
      gemm_run<false>(acc, x, 10, 0);
      gemm_issue<128, false, false>(acc, x);
      {
        wg_bar(w);
        uint32_t tr = sb + OFF_T + w * 12288 + (x.warp - 1) * 4096;
        if (x.warp == 0) {
          tr = x.m() > 0 ? sb + OFF_S + 8192 + w * 4096 : tr + 4096;
          if (x.m() > 0) mbar_wait(sb + BAR_HALO, L >> 1);
        }
#pragma unroll
        for (int q = 0; q < 8; q++) lds128(tr + x.lane * 16 + q * 512, PH[4 * q], PH[4 * q + 1], PH[4 * q + 2], PH[4 * q + 3]);
      }
      gemm_retire<128>(x, false);
      gemm_end(acc, x);
      TSW(5 + L * 12);
      const bool first = (x.m() == 0) && (x.warp == 0);
      const bool hi0 = 2 * x.c > x.g, hi1 = 2 * x.c + 1 > x.g;
      const uint32_t mhi = (hi0 ? 0xFFFFu : 0u) | (hi1 ? 0xFFFF0000u : 0u);
      const float sc0 = st.rstd0 * (0.17677669529663687f * LOG2E), sc1 = st.rstd1 * (0.17677669529663687f * LOG2E);
#pragma unroll
      for (int hp = 0; hp < 2; hp++) {
        const uint32_t tile = x.aslot(x.held(hp));
        uint32_t px[2], py[2];
        float s[2][3][4];
#pragma unroll
        for (int u = 0; u < 2; u++) {
#pragma unroll
          for (int q = 0; q < 12; q++) s[u][q >> 2][q & 3] = 0.f;
#pragma unroll
          for (int ks = 0; ks < 2; ks++) {
            const int t = 8 * hp + 4 * u + 2 * ks;
            const uint32_t a0 = pack2(acc[4 * t], acc[4 * t + 1]), a1 = pack2(acc[4 * t + 2], acc[4 * t + 3]);
            const uint32_t a2 = pack2(acc[4 * t + 4], acc[4 * t + 5]), a3 = pack2(acc[4 * t + 6], acc[4 * t + 7]);
            mma16816(s[u][0], a0, a1, a2, a3, PH[t], PH[t + 1]);
            mma16816(s[u][1], a0, a1, a2, a3, P0[t], P0[t + 1]);
            mma16816(s[u][2], a0, a1, a2, a3, P1[t], P1[t + 1]);
          }
        }
        float e[2][4], r[2][2];
#pragma unroll
        for (int u = 0; u < 2; u++) {
          e[u][0] = (hi0 ? s[u][0][0] : s[u][1][0]) * sc0; e[u][1] = (hi1 ? s[u][0][1] : s[u][1][1]) * sc0;
          e[u][2] = (hi0 ? s[u][1][2] : s[u][2][2]) * sc1; e[u][3] = (hi1 ? s[u][1][3] : s[u][2][3]) * sc1;
          if (first) { if (hi0) e[u][0] = -1e30f; if (hi1) e[u][1] = -1e30f; }
          r[u][0] = fmaxf(e[u][0], e[u][1]); r[u][1] = fmaxf(e[u][2], e[u][3]);
        }
#pragma unroll
        for (int d = 1; d <= 2; d++)
#pragma unroll
          for (int q = 0; q < 4; q++) r[q >> 1][q & 1] = fmaxf(r[q >> 1][q & 1], __shfl_xor_sync(0xffffffffu, r[q >> 1][q & 1], d));
#pragma unroll
        for (int u = 0; u < 2; u++) {
#pragma unroll
          for (int q = 0; q < 4; q++) e[u][q] = ex2(e[u][q] - r[u][q >> 1]);
          r[u][0] = e[u][0] + e[u][1]; r[u][1] = e[u][2] + e[u][3];
        }
#pragma unroll
        for (int d = 1; d <= 2; d++)
#pragma unroll
          for (int q = 0; q < 4; q++) r[q >> 1][q & 1] += __shfl_xor_sync(0xffffffffu, r[q >> 1][q & 1], d);
#pragma unroll
        for (int u = 0; u < 2; u++) {
          const float rx = rcp(r[u][0]), ry = rcp(r[u][1]);
          px[u] = pack2(e[u][0] * rx, e[u][1] * rx); py[u] = pack2(e[u][2] * ry, e[u][3] * ry);
        }
        uint32_t o[8][2];
        uint4 ro[4];
#pragma unroll
        for (int q = 0; q < 8; q++) {
          float d[4] = {0.f, 0.f, 0.f, 0.f};
          const int t = 16 + 8 * hp + q, u = q >> 2;
          mma16816(d, px[u] & mhi, 0u, px[u] & ~mhi, py[u] & mhi, PH[t], P0[t]);
          mma1688(d, 0u, py[u] & ~mhi, P1[t]);
          o[q][0] = pack2(d[0], d[1]); o[q][1] = pack2(d[2], d[3]);
        }
#pragma unroll
        for (int q = 0; q < 4; q++) ro[q] = make_uint4(o[4 * (q & 1)][q >> 1], o[4 * (q & 1) + 1][q >> 1], o[4 * (q & 1) + 2][q >> 1], o[4 * (q & 1) + 3][q >> 1]);
        img_store(ro, x.img(0, hp));
        publish(hp, x);
        uint32_t xr[16];
        if (L) img_load(xr, tile, x);
        else {
#pragma unroll
          for (int q = 0; q < 4; q++) {
            uint32_t v[4];
            ldsm4(x.maddr(tile, 2 * q), v);
            xr[2 * q] = v[0]; xr[8 + 2 * q] = v[1]; xr[2 * q + 1] = v[2]; xr[9 + 2 * q] = v[3];
          }
          __syncwarp();
        }
        img_sts(ro, tile, x);
        img_unpack(acc + 32 * hp, xr);
      }
    } else {
      float kv[128];
      float (&kv0)[64] = reinterpret_cast<float (&)[64]>(kv[0]);
      float (&kv1)[64] = reinterpret_cast<float (&)[64]>(kv[64]);
      auto mma8 = [&](uint32_t as, uint32_t bs, int i, bool fence) {
        const uint32_t da = desc_lo(SB + OFF_A, 16) + as * (SLOT / 16), db = desc_lo(SB + OFF_B, 8192) + bs * (SLOT / 16);
        if (fence) wgmma_fence();
#pragma unroll
        for (int k = 0; k < 4; k++) {
          wgmma_ss_n128(kv0, da + (k >> 1) * 32 + (k & 1) * 2, HA64, db + 128 * k, i + k);
          wgmma_ss_n128(kv1, da + 512 + (k >> 1) * 32 + (k & 1) * 2, HA64, db + 128 * k, i + k);
        }
        wgmma_commit();
      };
      constexpr uint32_t dm = desc_lo(SB + OFF_MB, 0);
      auto relB = [&](uint32_t s) { mbar_arrive_n(sb + BAR_EMPTYB + s * 8, 2); };
      auto skip = [&]() {
#pragma unroll
        for (int q = 0; q < 6 - NJ; q++) adv<NA>(x.ra);
        x.rb.s = w ? (2 + NJ) % 6 : 4;
        if (!w && NJ < 4) x.rb.ph ^= 1;
      };
      static_assert(NA == 5 && NB == 6, "ring arithmetic");
      mma8(x.ra.s, x.rb.s + w, 0, true);
      gemm_next<256>(x);
#pragma unroll 1
      for (int i = 1; i < NJ; i++) {
        mbar_wait2(x.fullA(x.ra.s), x.ra.ph, x.fullB(x.rb.s + w), x.rb.ph);
        mma8(x.ra.s, x.rb.s + w, 1, true);
        if (i == XR) { img_store(r1, x.img(XBUF(L), 1)); publish(3, x); }
        wgmma_wait<1>();
        if (x.elected && i != 2) { x.releaseA(x.pa); relB(x.pb + w); }
        gemm_next<256>(x);
        if (i == 1) { wgmma_wait<0>(); if (x.elected) { x.releaseA(x.pa); relB(x.pb + w); } }
      }
      if (w) {
        if (NJ > 2) { wgmma_wait<0>(); if (x.elected) { x.releaseA(x.pa); relB(x.pb + 1); } }
        if (XR >= NJ) { mbar_wait(x.fullA(x.ra.s), x.ra.ph); img_store(r1, x.img(XBUF(L), 1)); publish(3, x); }
        skip();
        asm volatile("bar.sync 7, 256;" ::: "memory");
      }
      TSW(8 + L * 12);
      {
        const int t = lane_id() + 32 * x.warp;
        uint32_t mask = t < 2 ? ((w ? (t ? 0xFF3Fu : 0x3FFFu) : 0xFFFFu) >> (NJ - 1)) & (w || NJ == 2 ? ~1u : ~0u) : 0u, cnt = 1 + t;
        bool ready = false;
#pragma unroll 1
        for (int i = NJ; i < 16; i++) {
          if (!ready) mbar_wait2(x.fullA(x.ra.s), x.ra.ph, x.fullB(x.rb.s), x.rb.ph);
          mma8(x.ra.s, x.rb.s, 1, true);
          if (XR >= NJ && i == NJ && !w) { img_store(r1, x.img(XBUF(L), 1)); publish(3, x); }
          const uint32_t bar = sb + (t ? BAR_EMPTYB + x.pb * 8 : BAR_EMPTYA + x.pa * 8);
          gemm_next<128>(x);
          if (w && (i | 4) == 15) x.rb.s = 4;
          ready = mbar_probe2(x.fullA(x.ra.s), x.ra.ph, x.fullB(x.rb.s), x.rb.ph);
          wgmma_wait<1>();
          if (mask & 1) mbar_arrive_n(bar, cnt);
          mask >>= 1; cnt = 2;
          if (i == 8 && w) asm volatile("bar.arrive 9, 256;" ::: "memory");
          if (i == 9) TSW(10 + L * 12);
        }
        mbar_wait2(sb + BAR_STAT, 1, sb + BAR_CS + 8, 0);
        wgmma_fence();
        wgmma_r1_n128(kv0, dm, dcs + 96 + 96 * w, 1);
        wgmma_r1_n128(kv1, dm + 64, dcs + 96 + 96 * w, 1);
        wgmma_commit();
        if (w == 0) asm volatile("bar.arrive 7, 256;" ::: "memory");
        wgmma_wait<1>();
        if (mask & 1) mbar_arrive_n(sb + (t ? BAR_EMPTYB + x.pb * 8 : BAR_EMPTYA + x.pa * 8), 2);
      }
      const Stats s0 = load_stats(0, x), s1 = load_stats(1, x), st = w ? s1 : s0;
      if (w == 0) skip();
      const uint32_t h0 = x.held(0), h1 = x.held(1);
      auto vreg = [&](int ks) { return ks < 6 ? OFF_A + (ks < 3 ? h0 * SLOT : h1 * SLOT - 15360) + ks * 5120 : OFF_S + 2048 + ks * 5120; };
      uint32_t tV[2], uu[4];
#pragma unroll
      for (int hf = 0; hf < 2; hf++) {
        tV[hf] = sb + vreg(4 * hf + x.warp) + ((x.lane >> 3) & 1) * 2560 + (x.lane & 7) * 16 + x.mhi * 128;
        const float i0 = rcp(hf ? s1.rstd0 : s0.rstd0), i1 = rcp(hf ? s1.rstd1 : s0.rstd1);
        const uint32_t h = pack2(i0, i1);
        uu[2 * hf] = pack2(lo16(h), i0 - lo16(h)); uu[2 * hf + 1] = pack2(hi16(h), i1 - hi16(h));
        asm volatile("" : "+r"(tV[hf]), "+r"(uu[2 * hf]), "+r"(uu[2 * hf + 1])::"memory");
      }
      wgmma_wait<0>();
      fence_regs(kv);
      TSW(2 + L * 12);
      if (w == 0) {
        uint32_t f[2][18], ad[4];
#pragma unroll
        for (int q = 0; q < 18; q++) f[1][q] = 0u;
#pragma unroll
        for (int q = 0; q < 4; q++) ad[q] = x.maddr(sb + OFF_S, 2 * q);
        auto norm = [&](int un) {
          uint32_t* u = f[un & 1];
          const Stats& sn = (un & 2) ? s1 : s0;
#pragma unroll
          for (int sg = 0; sg < 2; sg++) {
            uint32_t v = u[16 + sg];
            v = add2(v, __shfl_xor_sync(0xffffffffu, v, 1)); v = add2(v, __shfl_xor_sync(0xffffffffu, v, 2));
            const float a = rcp(lo16(v)) * sn.rstd0, b = rcp(hi16(v)) * sn.rstd1;
            const uint32_t r0 = pack2(a, a), r1_ = pack2(b, b);
#pragma unroll
            for (int q = 8 * sg; q < 8 * sg + 8; q++) u[q] = mul2(u[q], (q & 1) ? r1_ : r0);
#pragma unroll
            for (int q = 2 * sg; q < 2 * sg + 2; q++) stsm4(ad[q] + (un & 1) * SLOT + (un >> 1) * 8192, u[4 * q], u[4 * q + 1], u[4 * q + 2], u[4 * q + 3]);
          }
        };
        auto unit = [&](int un) { return kv + ((un >> 1) & 1) * 64 + (un & 1) * 16 + (un >> 2) * 32; };
        hedgehog_scale<0>(kv, s0, nullptr);
#pragma unroll 1
        for (int it = 0;; it++) {
#pragma unroll
          for (int un = 0; un < 4; un++) {
            if (un == 1) {
              if (it) asm volatile("bar.sync 9, 256;" ::: "memory");
#pragma unroll
              for (int q = 0; q < 4; q++) ad[q] -= it * (OFF_S - OFF_B - 2 * SLOT);
            }
            norm((un + 3) & 3);
            dual_exp(unit(un), f[un & 1], x.goff);
            hedgehog_scale<KEEP>(unit(un + 1), ((un + 1) & 2) ? s1 : s0, f[(un + 1) & 1]);
          }
          if (it) break;
#pragma unroll
          for (int q = 0; q < 32; q++) {
            asm volatile("mov.b32 %0, %1;" : "=f"(kv[q]) : "f"(kv[q + 32]));
            asm volatile("mov.b32 %0, %1;" : "=f"(kv[q + 64]) : "f"(kv[q + 96]));
            if (q < 16) kv[32 + q] = 0.f;
          }
        }
        norm(3);
        TSW(3 + L * 12);
      } else {
        wg_bar(w);
#pragma unroll
        for (int hf = 0; hf < 2; hf++) {
          stsm4(tV[hf] + 512 + x.mhi * 512, uu[2 * hf], uu[2 * hf + 1], uu[2 * hf], uu[2 * hf + 1]);
          stsm4(tV[hf] + 1792 + x.mhi * 512, uu[2 * hf], uu[2 * hf + 1], uu[2 * hf], uu[2 * hf + 1]);
#pragma unroll
          for (int q = 0; q < 8; q++) {
            const float* u = kv + 64 * hf + 8 * q;
            stsm4(tV[hf] + (q >> 1) * 640 + (q & 1) * 256, pack2(u[0], u[1]), pack2(u[2], u[3]), pack2(u[4], u[5]), pack2(u[6], u[7]));
          }
        }
        TSW(3 + L * 12);
      }
      {
        float d[2][20];
        uint4* dst = &g_kvpart[x.j()][w * 4 + x.warp][0][x.m() * 32 + x.lane];
        unsigned* dz = reinterpret_cast<unsigned*>(&g_kvpart[x.j()][w * 4 + x.warp][x.c & 1][512]) + x.m() * 8 + x.g;
        asm volatile("" : "+l"(dst), "+l"(dz)::"memory");
        fence_async_smem();
        cta_bar();
        TSW(11 + L * 12);
        uint32_t pk[9];
        auto prep = [&](float (&u)[20]) {
          fence_regs(u);
#pragma unroll
          for (int q = 0; q < 8; q++) pk[q] = pack2(u[((q >> 1) & 2) + 4 * (q & 3)], u[((q >> 1) & 2) + 4 * (q & 3) + 1]);
          pk[8] = __float_as_uint((x.c & 1) ? u[18] + u[19] : u[16] + u[17]);
#pragma unroll
          for (int q = 0; q < 9; q += 4) pk[q] = (pk[q] & ~1u) | (L == 1);
        };
        auto send = [&](int hp) {
          st_v4(dst + hp * 16 * 544, pk[0], pk[1], pk[2], pk[3]); st_v4(dst + (hp * 16 + 1) * 544, pk[4], pk[5], pk[6], pk[7]);
          st_flag(dz + hp * 16 * 544 * 4, pk[8]);
        };
        wgmma_fence();
#pragma unroll
        for (int q = 0; q < 17; q++) {
          if (q < 16) wgmma_ss_n40_tt(d[q >> 3], desc_lo(SB + (q < 8 ? OFF_S : OFF_B + 2 * SLOT), 1024) + w * (SLOT / 16) + 128 * (q & 7), desc_lo(SB + vreg(q & 7), 2560) + (w + (q >> 3) * 2) * 40, q & 7);
          else wgmma_r1_n128(acc, dm + w * 64, dcs, 0);
          if (q == 7 || q == KVS || q == 16) wgmma_commit();
          if (q == KVS) { wgmma_wait<1>(); prep(d[0]); send(0); mbar_wait2(x.fullA(x.ra.s), x.ra.ph, x.fullB(x.rb.s), x.rb.ph); wgmma_fence(); }
        }
        gemm_issue<128, false>(acc, x, true); gemm_next<128>(x);
        wgmma_wait<1>();
        x.releaseA(h0); x.releaseA(h1); x.releaseB(2); x.releaseB(3);
        if (x.lane == 0) mbar_arrive(sb + BAR_SIGT);
        prep(d[1]);
        TSW(4 + L * 12);
#pragma unroll 1
        for (int seg = 0; seg < 2; seg++) {
          const int n0 = w ? PS1 : PS0;
          gemm_run(acc, x, seg ? 15 - n0 : n0, seg, seg ? L : 0);
          if (seg == 0) send(1);
        }
      }
      gemm_end(acc, x);
      TSW(5 + L * 12);
      {
        float dp[2][20], dn[2][20];
        uint32_t f[4][16];
        auto mma = [&](int h) {
          if (!(h & 1)) mbar_wait(sb + BAR_KV + h * 4, L >> 1);
          if (h == 0) TSW(9 + L * 12);
          const uint32_t db = desc_lo(SB + OFF_S + h * 5120, 128);
          const uint32_t (&a)[16] = f[h];
          wgmma_fence();
          wgmma_rs_n40(dp[h & 1], a[0], a[1], a[2], a[3], db, 0);
          wgmma_rs_n40(dn[h & 1], a[8], a[9], a[10], a[11], db + 160, 0);
          wgmma_rs_n40(dp[h & 1], a[4], a[5], a[6], a[7], db + 80, 1);
          wgmma_rs_n40(dn[h & 1], a[12], a[13], a[14], a[15], db + 240, 1);
          wgmma_commit();
        };
        uint32_t xr[16];
        auto fin = [&](int h) {
          const uint32_t tile = x.aslot(x.held(h >> 1));
          if (!(h & 1)) img_load(xr, tile, x);
          float (&u)[20] = dp[h & 1];
          float (&v)[20] = dn[h & 1];
          fence_regs(u); fence_regs(v);
#pragma unroll
          for (int r = 0; r < 2; r++) {
            float cc = u[17 + 2 * r] * rcp(v[17 + 2 * r]);
            const float aa = rcp(fmaf(v[16 + 2 * r], cc, fmaf(u[17 + 2 * r], 1e-6f, u[16 + 2 * r])));
            cc *= aa;
            uint32_t o[4];
#pragma unroll
            for (int t = 0; t < 4; t++) o[t] = pack2(fmaf(u[4 * t + 2 * r], aa, v[4 * t + 2 * r] * cc), fmaf(u[4 * t + 2 * r + 1], aa, v[4 * t + 2 * r + 1] * cc));
            x.img(0, h >> 1)[r * 64 + (h & 1) * 32] = make_uint4(o[0], o[1], o[2], o[3]);
            sts128(tile + r * 1024 + (h & 1) * 512 + x.oo() * 16, o[0], o[1], o[2], o[3]);
          }
          if (h & 1) { publish(h >> 1, x); img_unpack(acc + 16 * (h - 1), xr); }
        };
        auto scale = [&](int h) { hedgehog_scale<0>(acc + 16 * h, st, nullptr); };
        auto ex = [&](int h) { dual_exp_rcp(acc + 16 * h, f[h]); };
        scale(0);
        ex(0); scale(1); mma(0);
        ex(1); wgmma_wait<0>(); fin(0); scale(2); mma(1);
        ex(2); wgmma_wait<0>(); fin(1); scale(3); mma(2);
        ex(3); wgmma_wait<0>(); fin(2); mma(3);
        wgmma_wait<0>(); fin(3);
      }
    }
    if (PW & 2) { mbar_wait(x.fullB(x.rb.s), x.rb.ph); fence_regs(acc); }
    fence_async_smem();
    wg_bar(w);
    TSW(6 + L * 12);
    rewind2<NA>(x.ra);
    gemm_issue<128, false>(acc, x, PW & 2); gemm_next<128>(x);
#pragma unroll 1
    for (int seg = L >= TSL ? 0 : 1; seg < 2; seg++) {
      gemm_run(acc, x, L >= TSL ? (seg ? TSK : 15 - TSK) : 15, seg);
      if (L >= TSL) {
        if (seg == 0 && w == 1) asm volatile("bar.sync 6, 256;" ::: "memory");
        if (seg == 1 && w == 0) asm volatile("bar.arrive 6, 256;" ::: "memory");
      }
    }
    gemm_end(acc, x);
    TSW(7 + L * 12);
    rewind2<NA>(x.ra);
    out_epilogue(acc, r1, P.out + goff, L, x);
    TSW(13 + L * 12);
  }
}

typedef unsigned long long u64;
__device__ __forceinline__ void pause(uint32_t GAP) {
  if (GAP) { uint32_t t0, t; asm volatile("mov.u32 %0, %%clock;" : "=r"(t0)); do { asm volatile("mov.u32 %0, %%clock;" : "=r"(t)); } while (t - t0 < GAP); }
}
__device__ __forceinline__ u64 order_table(int kind, int j) {
  const int i = threadIdx.x & 15;
  const unsigned v = (unsigned)(kind == 2 ? q_order(i, j) : kv_order(i, j, kind)) << (4 * (i & 7));
  return (u64)__reduce_or_sync(0xffffffffu, i < 8 ? 0u : v) << 32 | __reduce_or_sync(0xffffffffu, i < 8 ? v : 0u);
}

__device__ __forceinline__ void b_producer(const Params& P, uint32_t sb, unsigned vb) {
  const int j = cta_j(vb);
  const u64 t0 = order_table(0, j), t1 = order_table(1, j), t2 = order_table(2, j);
  Ring r = {PRE_B % NB, PRE_B < NB};
#pragma unroll 1
  for (int sg = 0; sg < 20; sg++) {
    const int L = sg / 5, p = sg - 5 * L, wt = L & 1;
    int n = p >= 3 ? 16 : (wt ? (p ? 16 - NJ : 2 * NJ) : (p ? 0 : (L ? 32 : 32 - PRE_B)));
    u64 tab = p == 3 ? t2 : (sg == 0 ? t0 >> (2 * PRE_B) : (p == 1 || p == 2 ? t1 >> (4 * NJ) : t1));
    const CUtensorMap* tm = p == 4 ? &P.mwo[wt] : &P.mw[wt ? 1 : L];
    const uint4* img = &g_wf[p != 3][j][0][0];
    int col = (p >= 3 ? 0 : (p == 2 ? 2048 : 1024)) + 128 * j;
    const int flip = p == 0 ? 3072 : 0;
    const bool fold = wt && p != 4;
    if (sg == 5 || sg == 8) { mbar_wait(sb + (sg == 5 ? BAR_WPHI : BAR_CS + 8), sg == 5); fence_async_global(); }
    if (DEFER && p == 4 && ((DEFL >> wt) & 1)) {
      Ring q = r;
      for (int u = 0; u < DEFER; u++) adv<NB>(q);
      mbar_wait(sb + BAR_EMPTYB + q.s * 8, q.ph);
    }
#pragma unroll 1
    for (; n > 0; n--) {
      const int kb = (int)tab & 15;
      mbar_wait(sb + BAR_EMPTYB + r.s * 8, r.ph);
      if (elect()) {
        mbar_expect_tx(sb + BAR_FULLB + r.s * 8, SLOT);
        if (fold && col < 2048) bulk_load(sb + OFF_B + r.s * SLOT, img + kb * 1024, SLOT, sb + BAR_FULLB + r.s * 8);
        else tma_load_w(sb + OFF_B + r.s * SLOT, tm, sb + BAR_FULLB + r.s * 8, col, kb);
      }
      adv<NB>(r);
      if (p == 2 && (n | 4) == 5) r.s = 4;
      col ^= flip;
      if (!(col & flip & 2048)) tab >>= 4;
    }
  }
}

__device__ __forceinline__ void a_loader(const Params& P, uint32_t sb, unsigned vb) {
  const int j = cta_j(vb), m = cta_m(vb);
  const u64 t1 = order_table(1, j), t2 = order_table(2, j);
  Ring r = {PRE_A % NA, PRE_A < NA};
  {
    u64 tab = order_table(0, j) >> (4 * PRE_A);
#pragma unroll 1
    for (int i = PRE_A; i < 33; i++) {
      if (i == 17) tab = t2;
      mbar_wait(sb + BAR_EMPTYA + r.s * 8, r.ph);
      if (elect()) {
        mbar_expect_tx(sb + BAR_FULLA + r.s * 8, SLOT);
        if (i != 14) tma_load_3d(sb + OFF_A + r.s * SLOT, &P.mx, sb + BAR_FULLA + r.s * 8, ((int)tab & 15) * 64, m * 64, 0);
        else {
          tma_load_w(sb + OFF_A + r.s * SLOT, &P.mw[1], sb + BAR_FULLA + r.s * 8, 1024 + 128 * j, m);
          mbar_expect_tx(sb + BAR_WPHI, 8192); tma_load_2d(sb + OFF_S + 4096, &P.mwphi, sb + BAR_WPHI, 0, 128 * j);
        }
        if (i == PF0 || i == PF1 || i == PF2)
          tma_prefetch_w(i == PF0 ? &P.mw[1] : &P.mwo[i == PF2], (i == PF0 ? 1024 : 0) + 128 * j, m);
      }
      adv<NA>(r);
      if (i != 14) tab >>= 4;
    }
  }
  const unsigned tag = get_tag(sb);
  unsigned seen = 0;
#pragma unroll 1
  for (int sg = 0; sg < 27; sg++) {
    const int L = sg >> 3, p = sg & 7, q = p >= 3 ? p - 3 : p;
    if (p == 0 && (L & 1)) {
#pragma unroll 1
      for (int h = 0; h < 2; h++) {
        poll_flags(&g_kvfflag[L >> 1][j][h][0], 8, 0xFFu, tag);
        if (elect()) { mbar_expect_tx(sb + BAR_KV + h * 8, 10240); bulk_load(sb + OFF_S + h * 10240, &g_kvfin[j][8 * h][0], 10240, sb + BAR_KV + h * 8); }
      }
      TS(4, 14 + L);
    }
    int n = q == 0 ? 4 : (q == 1 ? 3 : (q == 2 ? 7 : (q == 3 ? ((L & 1) ? 0 : 16 - NJ) : 16)));
    u64 tab = q == 4 ? t2 : t1 >> (q == 0 ? 8 : (q == 1 ? 24 : (q == 2 ? 36 : 4 * NJ)));
    const uint4* img = &g_img[p >= 3 ? XBUF(L + 1) : 0][m][0][0];
    const uint32_t gap = p == 0 ? G0 : (p == 3 ? G3 : (q < 3 ? G1 : G4));
    bool poll = q == 0 || q == 2 || (q == 1 && seen != 0xFFFFFFFFu);
#pragma unroll 1
    for (; n > 0; n--) {
      const uint4* src = img + ((int)tab & 15) * 1024;
      mbar_wait(sb + BAR_EMPTYA + r.s * 8, r.ph);
      if (elect()) mbar_expect_tx(sb + BAR_FULLA + r.s * 8, SLOT);
      if (poll) {
        const int lane = threadIdx.x & 31, nn = p >= 3 ? PNX : PNO;
        const unsigned* f = (p >= 3 ? &g_xflag[L + 1][0][m][0] : &g_oflag[L][0][m][0]) + (q == 2 ? 512 : 0) + (lane & 7);
        if (q == 0) f += (((lane >> 3) & (nn - 1)) - (m & (nn - 1))) * 32;
        const unsigned need = q == 0 ? 0x0F0F0F0Fu << (~j & 4) : 0xFFFFFFFFu;
        if (q == 0) mbar_wait(sb + BAR_SIGP + (p ? 16 : 0), L & 1);
        int it = 0;
        do { seen = __ballot_sync(0xffffffffu, ld_flag(f) == tag); if (++it > (1 << 22)) __trap(); } while ((seen & need) != need);
        fence_async_global();
        if (q == 0) TS(2, p == 0 ? 5 + L * 8 : 9 + L * 8);
        poll = false;
      }
      if (elect()) bulk_load(sb + OFF_A + r.s * SLOT, src, SLOT, sb + BAR_FULLA + r.s * 8);
      adv<NA>(r);
      tab >>= 4;
      pause(gap);
    }
  }
}

__device__ __forceinline__ void helper_bar() { asm volatile("bar.sync 4, 64;" ::: "memory"); }
__device__ __forceinline__ void helper(const Params& P, uint32_t sb, int w, unsigned vb) {
  const int j = cta_j(vb), m = cta_m(vb);
  if (w == 0) {
    if (elect()) {
      const unsigned t = atomicAdd(&g_ctr, 1u) / NCTA + 1u;
      asm volatile("st.shared.u32 [%0], %1;" ::"r"(sb + OFF_EPOCH), "r"(t) : "memory");
      mbar_arrive(sb + BAR_EPOCH);
    }
  }
  const unsigned tag = get_tag(sb);
  mbar_wait(sb + BAR_FULLB + 24, 0);
  const uint32_t stg = sb + OFF_T + w * 12288, stb = sb + BAR_STG + w * 24;
  Ring rs = {0, 0};
  auto cs_image = [&](int L) {
      const int lane = lane_id();
      poll_flags(&g_csflag[L][j][0], 16, L ? CSNEED : 0xFFFu, tag);
#pragma unroll
      for (int p = 0; p < 3; p++) {
        const uint4 u = ldcg4(&g_cs[L][0][p * 1024 + 128 * j + lane * 4]), v = ldcg4(&g_cs[L][1][p * 1024 + 128 * j + lane * 4]);
        const float c0 = __uint_as_float(u.x) + __uint_as_float(v.x), c1 = __uint_as_float(u.y) + __uint_as_float(v.y);
        const float c2 = __uint_as_float(u.z) + __uint_as_float(v.z), c3 = __uint_as_float(u.w) + __uint_as_float(v.w);
        const uint32_t h0 = pack2(c0, c1), h1 = pack2(c2, c3), dst = sb + OFF_CS + (p * 16 + (lane >> 1)) * 96 + L * 48 + (lane & 1) * 8;
        sts64(dst, h0, h1); sts64(dst + 16, pack2(c0 - lo16(h0), c1 - hi16(h0)), pack2(c2 - lo16(h1), c3 - hi16(h1))); sts64(dst + 32, h0, h1);
        if (L == 0) { sts64(dst + 48, 0u, 0u); sts64(dst + 64, 0u, 0u); sts64(dst + 80, 0u, 0u); }
      }
      if (L == 0 && lane < 4) sts64(sb + OFF_CS + 4608 + lane * 8, 0u, 0u);
      fence_async_smem();
      __syncwarp();
      if (elect()) mbar_arrive(sb + BAR_CS + L * 8);
      TS(4, 2 + L * 2);
  };
#pragma unroll 1
  for (int L = 0; L < 4; L++) {
    const int lane = lane_id();
    if (L == 0) {
      {
        const int wt = m >= 12, col = ((0x2021 >> (m & 12)) & 3) * 1024 + 128 * j + (m & 3) * 32;
        const CUtensorMap* tm = &P.mcs[wt];
        if (D2 && wt) __nanosleep(D2);
        constexpr int nb = 8;
        float a[8] = {0.f, 0.f, 0.f, 0.f, 0.f, 0.f, 0.f, 0.f};
#pragma unroll 1
        for (int b = -3; b < nb; b++) {
          uint4 v[8];
          if (b >= 0) {
            mbar_wait(stb + rs.s * 8, rs.ph);
#pragma unroll
            for (int u = 0; u < 8; u++) lds128(stg + rs.s * 4096 + u * 512 + lane * 16, v[u].x, v[u].y, v[u].z, v[u].w);
            fence_async_smem();
            __syncwarp();
          }
          const uint32_t sl = b < 0 ? (rs.s + b + 3) % 3 : rs.s;
          if (b + 3 < nb && elect()) { mbar_expect_tx(stb + sl * 8, 4096); tma_load_2d(stg + sl * 4096, tm, stb + sl * 8, col, (w * (16 - nb) + b + 3) * 64); }
          if (b >= 0) {
            adv<3>(rs);
#pragma unroll
            for (int u = 0; u < 8; u++) {
              a[0] += lo16(v[u].x); a[1] += hi16(v[u].x); a[2] += lo16(v[u].y); a[3] += hi16(v[u].y);
              a[4] += lo16(v[u].z); a[5] += hi16(v[u].z); a[6] += lo16(v[u].w); a[7] += hi16(v[u].w);
            }
          }
        }
#pragma unroll
        for (int u = 0; u < 8; u++) {
          a[u] += __shfl_xor_sync(0xffffffffu, a[u], 4); a[u] += __shfl_xor_sync(0xffffffffu, a[u], 8); a[u] += __shfl_xor_sync(0xffffffffu, a[u], 16);
        }
        if (lane < 4) {
          float4* dst = reinterpret_cast<float4*>(&g_cs[wt][w][col + lane * 8]);
          dst[0] = make_float4(a[0], a[1], a[2], a[3]); dst[1] = make_float4(a[4], a[5], a[6], a[7]);
        }
        helper_bar();
        if (w == 0 && elect()) { fence_gpu(); st_flag(&g_csflag[wt][j][m], tag); }
      }
      if (w == 0) TS(4, 1 + L * 2);
    }
    if (w == 1) {
      if (L > 0) mbar_wait(sb + BAR_SIGP + ((L & STG0) ? 16 : 24), (L - 1) & 1);
#pragma unroll 1
      for (int p = 0; p < 2; p++) {
        uint4 v[8];
        for (int it = 0;; it++) {
          bool ok = true;
#pragma unroll
          for (int t = 0; t < 8; t++) v[t] = ld_pkt(&g_stats[m][p][t][lane]);
#pragma unroll
          for (int t = 0; t < 8; t++) ok = ok && (v[t].w & 15u) == seq4(tag, L);
          if (__all_sync(0xffffffffu, ok)) break;
          __nanosleep(200);
          if (it > (1 << 20)) __trap();
        }
        float s0 = 0.f, q0 = 0.f, s1 = 0.f, q1 = 0.f;
#pragma unroll
        for (int t = 0; t < 8; t++) { s0 += __uint_as_float(v[t].x); q0 += __uint_as_float(v[t].y); s1 += __uint_as_float(v[t].z); q1 += __uint_as_float(v[t].w & ~15u); }
        s0 *= (1.f / 1024); s1 *= (1.f / 1024);
        sts64(sb + OFF_MR + p * 256 + lane * 8, __float_as_uint(rsqrtf(fmaxf(q0 * (1.f / 1024) - s0 * s0, 0.f) + 1e-5f)),
              __float_as_uint(rsqrtf(fmaxf(q1 * (1.f / 1024) - s1 * s1, 0.f) + 1e-5f)));
#pragma unroll
        for (int r = 0; r < 2; r++) {
          const float v = -0.5f * (r ? s1 : s0);
          const uint32_t hh = pack2(v, v), hl = pack2(v, v - lo16(hh));
          const bool b = L & 1;
          sts128(sb + (b ? OFF_MB : OFF_MA) + p * 1024 + (lane >> 3) * 256 + r * 128 + (lane & 7) * 16, b ? 0u : hh, b ? hh << 16 : hl >> 16, b ? hl : 0u, 0u);
        }
      }
      fence_async_smem();
      __syncwarp();
      if (elect()) {
        mbar_arrive(sb + BAR_STAT);
      }
      TS(2, 0 + L * 8);
    }
    if (L == w) cs_image(L);
    if (L & 1) {
      const uint32_t flip = L == 1 ? 0u : 1u;
      mbar_wait(sb + BAR_SIGT, 1);
      {
        int it = 0;
        if (PSL) __nanosleep(m < 8 ? PSL : PSL + 600);
        while (!__all_sync(0xffffffffu, (ld_flag(reinterpret_cast<const unsigned*>(&g_kvpart[j][m][w][512]) + (lane & 15) * 8) ^ flip) & 1u)) { if (PSL) __nanosleep(100); if (++it > (1 << 22)) __trap(); }
        fence_async_global();
      }
      if (w == 0) TS(4, 6 + L * 2);
      for (int it = 0;; it++) {
        if (elect()) { mbar_expect_tx(stb + rs.s * 8, 8704); bulk_load(stg, &g_kvpart[j][m][w][0], 8704, stb + rs.s * 8); }
        mbar_wait(stb + rs.s * 8, rs.ph);
        adv<3>(rs);
        float a[8] = {0.f, 0.f, 0.f, 0.f, 0.f, 0.f, 0.f, 0.f};
        float z = 0.f;
        uint32_t ok = 1u;
#pragma unroll
        for (int u = 0; u < 4; u++) { const float v = lds32f(stg + 8192 + u * 128 + (lane & 3) * 32 + (lane >> 2) * 4); z += v; ok &= __float_as_uint(v) ^ flip; }
#pragma unroll 1
        for (int b = 0; b < 16; b += KB) {
          uint4 v[KB];
#pragma unroll
          for (int u = 0; u < KB; u++) lds128(stg + (b + u) * 512 + lane * 16, v[u].x, v[u].y, v[u].z, v[u].w);
#pragma unroll
          for (int u = 0; u < KB; u++) {
            ok &= v[u].x ^ flip;
            if (RH && !(u & 1)) continue;
            if (RH) { v[u].x = add2(v[u].x, v[u - 1].x); v[u].y = add2(v[u].y, v[u - 1].y); v[u].z = add2(v[u].z, v[u - 1].z); v[u].w = add2(v[u].w, v[u - 1].w); }
            a[0] += lo16(v[u].x); a[1] += hi16(v[u].x); a[2] += lo16(v[u].y); a[3] += hi16(v[u].y);
            a[4] += lo16(v[u].z); a[5] += hi16(v[u].z); a[6] += lo16(v[u].w); a[7] += hi16(v[u].w);
          }
        }
        uint4* img = &g_kvfin[j][m][w * 8 + (lane >> 2)];
        img[(lane & 3) * 16] = make_uint4(pack2(a[0], a[1]), pack2(a[2], a[3]), pack2(a[4], a[5]), pack2(a[6], a[7]));
        reinterpret_cast<uint32_t*>(img + 64)[lane & 3] = pack2(qsum(z), 1.f);
        if (__all_sync(0xffffffffu, ok & 1u)) break;
        fence_async_smem();
        if (it > (1 << 16)) __trap();
      }
      if (w == 0) TS(4, 7 + L * 2);
      helper_bar();
      if (w == 1 && elect()) { fence_gpu(); st_flag(&g_kvfflag[L >> 1][j][m >> 3][m & 7], tag); }
      if (w == 1 && L == 1) TS(4, 20);
    } else {
      mbar_wait(sb + BAR_SIGT, 0);
      if (w == 0) {
        if (elect()) { fence_gpu(); st_flag(&g_hflag[L >> 1][m][j][0], tag); st_flag(&g_kflag[j][m], tag); }
        if (L == 0) {
          __nanosleep(KSL);
          poll_flags(&g_kflag[j][0], 16, 0xFFFFu, tag);
          if (elect()) mbar_arrive(sb + BAR_WPHI);
        }
      } else if (m > 0) {
        poll_flags(&g_hflag[L >> 1][m - 1][j][0], 1, 1u, tag);
        if (elect()) { mbar_expect_tx(sb + BAR_HALO, 8192); bulk_load(sb + OFF_S + 8192, &g_halo[m - 1][j][0][0], 8192, sb + BAR_HALO); }
        TS(2, 2 + L * 8);
      }
    }
#pragma unroll 1
    for (int e = 0; e < (L < 3 && w == 0 ? 3 : 1); e++) {
      mbar_wait(sb + BAR_SIGP + (e == 0 ? w : e + 1) * 8, L & 1);
      TS(e == 2 ? 3 : 2 + w, (e ? 6 : 3) + L * 8);
      if (elect()) { fence_gpu(); st_flag(e == 0 ? &g_oflag[L][w][m][j] : &g_xflag[L + 1][e - 1][m][j], tag); }
      TS(e == 2 ? 3 : 2 + w, (e ? 7 : 4) + L * 8);
    }
  }
}

__device__ __forceinline__ void spare(const Params& P, uint32_t sb, int id) {
  const int tid = threadIdx.x & 127, w = __shfl_sync(0xffffffffu, threadIdx.x >> 7, 0), lane = tid & 31, j = 2 * id + w;
  const uint32_t ring = w * 6 * SLOT, wp = 12 * SLOT + w * 8192, bar = sb + 13 * SLOT + w * 64;
  auto part = [&](int t) { return (t >> 4) ^ w; };
  auto load = [&](int t, uint32_t sl) {
    mbar_expect_tx(bar + sl * 8, t == 0 ? SLOT + 8192 : SLOT);
    tma_load_w(sb + ring + sl * SLOT, &P.mw[1], bar + sl * 8, part(t) * 1024 + 128 * j, t & 15);
  };
  if (tid == 0) {
    if (w == 2) sts32(sb + OFF_EPOCH, atomicAdd(&g_ctr, 1u) / NCTA + 1u);
    else {
      __nanosleep(D3);
#pragma unroll 1
      for (int t = 0; t < 5; t++) {
        mbar_init(bar + t * 8, 1);
        asm volatile("fence.mbarrier_init.release.cluster;" ::: "memory");
        load(t, t);
      }
      tma_load_2d(sb + wp, &P.mwphi, bar, 0, 128 * j);
    }
  }
  __syncthreads();
  const unsigned tag = get_tag<false>(sb);
  if (w == 2) {
    int it = 0;
    while ((int)(ld_flag(&g_ctr) - tag * NCTA) < 0) { if (++it > (1 << 22)) __trap(); }
    return;
  }
  Ring r = {4, 1};
  float d[64] = {}, cs[32] = {};
  auto fold = [&]() {
    mbar_wait(bar + r.s * 8, r.ph);
    wgmma_fence();
#pragma unroll
    for (int q = 0; q < 8; q++)
      wgmma_ss_n32(reinterpret_cast<float (&)[16]>(d[16 * (q >> 1)]), desc_lo(SB + ring + r.s * SLOT, 16) + (q >> 2) * 512 + (q & 3) * 2, desc_lo(SB + wp, 512) + q * 64, q & 1);
    wgmma_commit();
  };
  const int row = (tid >> 5) * 16 + (lane >> 2);
#pragma unroll 1
  for (int t = -1; t < 32; t++) {
    uint32_t f[32];
#pragma unroll
    for (int i = 0; i < 32; i++) { f[i] = pack2(d[2 * i], d[2 * i + 1]); cs[i & 30] += d[2 * i]; cs[i | 1] += d[2 * i + 1]; }
    wg_bar(w);
    if (tid == 0 && t >= 0 && t < 27) load(t + 5, r.s);
    __syncwarp();
    if (t < 31) adv<5>(r);
    fold();
    if (part(t) == 0 && t >= 0) {
#pragma unroll
      for (int q = 0; q < 8; q++)
        g_wf[0][j][t & 15][(q >> 2) * 512 + (row + 8 * (q & 1)) * 8 + (((q & 2) * 2 + (lane & 3)) ^ (lane >> 2))] =
            make_uint4(f[4 * (q & 6) + (q & 1)], f[4 * (q & 6) + (q & 1) + 2], f[4 * (q & 6) + (q & 1) + 4], f[4 * (q & 6) + (q & 1) + 6]);
    }
    wgmma_wait<0>();
    fence_regs(d);
    if ((t & 15) == 15) {
      if (t >= 0) {
        const uint32_t red = sb + ring + 5 * SLOT;
#pragma unroll
        for (int i = 0; i < 8; i++) sts128(red + (tid >> 2) * 512 + (i >> 1) * 128 + (lane & 3) * 32 + (i & 1) * 16, __float_as_uint(cs[4 * i]), __float_as_uint(cs[4 * i + 1]), __float_as_uint(cs[4 * i + 2]), __float_as_uint(cs[4 * i + 3]));
        wg_bar(w);
        float a = 0.f;
#pragma unroll 4
        for (int i = 0; i < 32; i++) a += lds32f(red + i * 512 + tid * 4);
        g_cs[1][0][part(t) * 1024 + j * 128 + tid] = a;
        wg_bar(w);
        if (tid == 0) {
          fence_gpu();
          st_flag(&g_csflag[1][j][part(t)], tag);
        }
        __syncwarp();
      }
#pragma unroll
      for (int i = 0; i < 32; i++) cs[i] = 0.f;
    }
  }
}

__global__ void __launch_bounds__(NTHREADS, 1) fused_kernel(const __grid_constant__ Params P) {
  extern __shared__ __align__(1024) uint8_t smem_raw[];
  constexpr uint32_t sb = SB;
  const int tid = threadIdx.x;
  const unsigned vb = vblock();
  if (vb >= 128) { spare(P, sb, vb - 128); return; }
  const int warp = __shfl_sync(0xffffffffu, tid >> 5, 0);
  if (elect()) {
    if (warp == 11) { prefetch_map(&P.mx); prefetch_map(&P.mw[0]); if (smem_u32(smem_raw) != SB) __trap(); }
    if (warp < 7) {
#pragma unroll
      for (int i = 0; i < 8; i++) mbar_init(sb + OFF_BAR + (warp * 8 + i) * 8, warp == 2 || warp == 3 ? 2 : (warp == 4 ? 8 : 1));
    }
    asm volatile("fence.mbarrier_init.release.cluster;" ::: "memory");
    if (warp < 2) {
      const int j = cta_j(vb);
#pragma unroll 1
      for (int i = 0; i < (warp == 0 ? PRE_B : PRE_A); i++) {
        const uint32_t bar = sb + BAR_FULLB + warp * 64 + i * 8;
        mbar_expect_tx(bar, SLOT);
        if (warp == 0) tma_load_w(sb + OFF_B + i * SLOT, &P.mw[0], bar, 1024 + (i & 1) * 1024 + 128 * j, kv_order(i >> 1, j, 0));
        else tma_load_3d(sb + OFF_A + i * SLOT, &P.mx, bar, kv_order(i, j, 0) * 64, cta_m(vb) * 64, 0);
      }
    }
  }
  if (tid == 0) TS(6, 0);
  __syncthreads();
  if (tid == 0) TS(6, 2);
  if (warp < 4) {
    reg_dealloc<PREGS>();
    if (warp == 0) b_producer(P, sb, vb);
    else if (warp == 1) a_loader(P, sb, vb);
    else helper(P, sb, warp - 2, vb);
  } else {
    reg_alloc<CREGS>();
    consumer(P, sb, (warp >> 2) - 1, vb);
  }
}

typedef CUresult (*EncodeFn)(CUtensorMap*, CUtensorMapDataType, cuuint32_t, void*, const cuuint64_t*, const cuuint64_t*,
                             const cuuint32_t*, const cuuint32_t*, CUtensorMapInterleave, CUtensorMapSwizzle,
                             CUtensorMapL2promotion, CUtensorMapFloatOOBfill);

void encode(EncodeFn fn, CUtensorMap* m, const void* ptr, int rank, const cuuint64_t* dims, const cuuint64_t* strides,
            const cuuint32_t* box, CUtensorMapSwizzle swz) {
  const cuuint32_t es[5] = {1, 1, 1, 1, 1};
  fn(m, CU_TENSOR_MAP_DATA_TYPE_BFLOAT16, rank, const_cast<void*>(ptr), dims, strides, box, es, CU_TENSOR_MAP_INTERLEAVE_NONE,
     swz, CU_TENSOR_MAP_L2_PROMOTION_L2_256B, CU_TENSOR_MAP_FLOAT_OOB_FILL_NONE);
}
void encode_w(EncodeFn fn, CUtensorMap* m, const void* ptr, int ncols, bool perm) {
  const cuuint64_t p = (cuuint64_t)ncols * 2, d[5] = {(cuuint64_t)ncols, 2, 4, 4, 32}, s[4] = {p, (perm ? 8 : 2) * p, (perm ? 2 : 8) * p, 32 * p};
  const cuuint32_t box[5] = {64, 2, 4, 4, 2};
  encode(fn, m, ptr, 5, d, s, box, CU_TENSOR_MAP_SWIZZLE_128B);
}

void encode_cs(EncodeFn fn, CUtensorMap* m, const void* ptr, int ncols) {
  const cuuint64_t d[2] = {(cuuint64_t)ncols, 1024}, s[1] = {(cuuint64_t)ncols * 2};
  const cuuint32_t box[2] = {32, 64};
  encode(fn, m, ptr, 2, d, s, box, CU_TENSOR_MAP_SWIZZLE_NONE);
}

}

extern "C" void kernel_launch(void* const* d_in, const int* in_sizes, int n_in, void* d_out, int out_size) {
  (void)in_sizes; (void)n_in; (void)out_size;
  void* fnp = nullptr;
  cudaDriverEntryPointQueryResult q;
  cudaGetDriverEntryPoint("cuTensorMapEncodeTiled", &fnp, cudaEnableDefault, &q);
  EncodeFn fn = (EncodeFn)fnp;
  Params P;
  {
    const cuuint64_t dims[3] = {1024, 1024, 2}, strides[2] = {4096, 2048};
    const cuuint32_t box[3] = {64, 64, 2};
    encode(fn, &P.mx, d_in[0], 3, dims, strides, box, CU_TENSOR_MAP_SWIZZLE_128B);
  }
  P.out = (uint4*)d_out;
  encode_w(fn, &P.mw[0], d_in[1], 3072, false);
  encode_w(fn, &P.mw[1], d_in[4], 3072, true);
  encode_w(fn, &P.mw[2], d_in[1], 3072, true);
  encode_w(fn, &P.mwo[0], d_in[2], 1024, true);
  encode_w(fn, &P.mwo[1], d_in[6], 1024, false);
  encode_cs(fn, &P.mcs[0], d_in[1], 3072);
  encode_cs(fn, &P.mcs[1], d_in[4], 3072);
  {
    const cuuint64_t dims[2] = {32, 1024}, strides[1] = {64};
    const cuuint32_t box[2] = {32, 128};
    encode(fn, &P.mwphi, d_in[5], 2, dims, strides, box, CU_TENSOR_MAP_SWIZZLE_64B);
  }
  cudaFuncSetAttribute(fused_kernel, cudaFuncAttributeMaxDynamicSharedMemorySize, SMEM_BYTES);
  fused_kernel<<<NCTA, NTHREADS, SMEM_BYTES, cudaStreamPerThread>>>(P);
}
```

```cpp
#include <cuda_runtime.h>
#include <cuda_bf16.h>
#include <cuda.h>
#include <stdint.h>

namespace {

__device__ __forceinline__ void wgmma_ss_n256(float (&d)[128], uint32_t da, uint32_t ha, uint32_t db, int sd) {
  asm volatile("{\n.reg .pred p;\n.reg .b64 a, b;\nsetp.ne.b32 p, %130, 0;\nmov.b64 a, {%128, %131};\nmov.b64 b, {%129, 0x40000040};\n"
    "wgmma.mma_async.sync.aligned.m64n256k16.f32.bf16.bf16 {%0,%1,%2,%3,%4,%5,%6,%7,%8,%9,%10,%11,%12,%13,%14,%15,%16,%17,%18,%19,%20,%21,%22,%23,%24,%25,%26,%27,%28,%29,%30,%31,%32,%33,%34,%35,%36,%37,%38,%39,%40,%41,%42,%43,%44,%45,%46,%47,%48,%49,%50,%51,%52,%53,%54,%55,%56,%57,%58,%59,%60,%61,%62,%63,%64,%65,%66,%67,%68,%69,%70,%71,%72,%73,%74,%75,%76,%77,%78,%79,%80,%81,%82,%83,%84,%85,%86,%87,%88,%89,%90,%91,%92,%93,%94,%95,%96,%97,%98,%99,%100,%101,%102,%103,%104,%105,%106,%107,%108,%109,%110,%111,%112,%113,%114,%115,%116,%117,%118,%119,%120,%121,%122,%123,%124,%125,%126,%127}, a, b, p, 1, 1, 0, 1;\n}\n"
    : "+f"(d[0]),"+f"(d[1]),"+f"(d[2]),"+f"(d[3]),"+f"(d[4]),"+f"(d[5]),"+f"(d[6]),"+f"(d[7]),"+f"(d[8]),"+f"(d[9]),"+f"(d[10]),"+f"(d[11]),"+f"(d[12]),"+f"(d[13]),"+f"(d[14]),"+f"(d[15]),"+f"(d[16]),"+f"(d[17]),"+f"(d[18]),"+f"(d[19]),"+f"(d[20]),"+f"(d[21]),"+f"(d[22]),"+f"(d[23]),"+f"(d[24]),"+f"(d[25]),"+f"(d[26]),"+f"(d[27]),"+f"(d[28]),"+f"(d[29]),"+f"(d[30]),"+f"(d[31]),"+f"(d[32]),"+f"(d[33]),"+f"(d[34]),"+f"(d[35]),"+f"(d[36]),"+f"(d[37]),"+f"(d[38]),"+f"(d[39]),"+f"(d[40]),"+f"(d[41]),"+f"(d[42]),"+f"(d[43]),"+f"(d[44]),"+f"(d[45]),"+f"(d[46]),"+f"(d[47]),"+f"(d[48]),"+f"(d[49]),"+f"(d[50]),"+f"(d[51]),"+f"(d[52]),"+f"(d[53]),"+f"(d[54]),"+f"(d[55]),"+f"(d[56]),"+f"(d[57]),"+f"(d[58]),"+f"(d[59]),"+f"(d[60]),"+f"(d[61]),"+f"(d[62]),"+f"(d[63]),"+f"(d[64]),"+f"(d[65]),"+f"(d[66]),"+f"(d[67]),"+f"(d[68]),"+f"(d[69]),"+f"(d[70]),"+f"(d[71]),"+f"(d[72]),"+f"(d[73]),"+f"(d[74]),"+f"(d[75]),"+f"(d[76]),"+f"(d[77]),"+f"(d[78]),"+f"(d[79]),"+f"(d[80]),"+f"(d[81]),"+f"(d[82]),"+f"(d[83]),"+f"(d[84]),"+f"(d[85]),"+f"(d[86]),"+f"(d[87]),"+f"(d[88]),"+f"(d[89]),"+f"(d[90]),"+f"(d[91]),"+f"(d[92]),"+f"(d[93]),"+f"(d[94]),"+f"(d[95]),"+f"(d[96]),"+f"(d[97]),"+f"(d[98]),"+f"(d[99]),"+f"(d[100]),"+f"(d[101]),"+f"(d[102]),"+f"(d[103]),"+f"(d[104]),"+f"(d[105]),"+f"(d[106]),"+f"(d[107]),"+f"(d[108]),"+f"(d[109]),"+f"(d[110]),"+f"(d[111]),"+f"(d[112]),"+f"(d[113]),"+f"(d[114]),"+f"(d[115]),"+f"(d[116]),"+f"(d[117]),"+f"(d[118]),"+f"(d[119]),"+f"(d[120]),"+f"(d[121]),"+f"(d[122]),"+f"(d[123]),"+f"(d[124]),"+f"(d[125]),"+f"(d[126]),"+f"(d[127])
    : "r"(da), "r"(db), "r"(sd), "r"(ha));
}
__device__ __forceinline__ void wgmma_ss_n128(float (&d)[64], uint32_t da, uint32_t ha, uint32_t db, int sd) {
  asm volatile("{\n.reg .pred p;\n.reg .b64 a, b;\nsetp.ne.b32 p, %66, 0;\nmov.b64 a, {%64, %67};\nmov.b64 b, {%65, 0x40000040};\n"
    "wgmma.mma_async.sync.aligned.m64n128k16.f32.bf16.bf16 {%0,%1,%2,%3,%4,%5,%6,%7,%8,%9,%10,%11,%12,%13,%14,%15,%16,%17,%18,%19,%20,%21,%22,%23,%24,%25,%26,%27,%28,%29,%30,%31,%32,%33,%34,%35,%36,%37,%38,%39,%40,%41,%42,%43,%44,%45,%46,%47,%48,%49,%50,%51,%52,%53,%54,%55,%56,%57,%58,%59,%60,%61,%62,%63}, a, b, p, 1, 1, 0, 1;\n}\n"
    : "+f"(d[0]),"+f"(d[1]),"+f"(d[2]),"+f"(d[3]),"+f"(d[4]),"+f"(d[5]),"+f"(d[6]),"+f"(d[7]),"+f"(d[8]),"+f"(d[9]),"+f"(d[10]),"+f"(d[11]),"+f"(d[12]),"+f"(d[13]),"+f"(d[14]),"+f"(d[15]),"+f"(d[16]),"+f"(d[17]),"+f"(d[18]),"+f"(d[19]),"+f"(d[20]),"+f"(d[21]),"+f"(d[22]),"+f"(d[23]),"+f"(d[24]),"+f"(d[25]),"+f"(d[26]),"+f"(d[27]),"+f"(d[28]),"+f"(d[29]),"+f"(d[30]),"+f"(d[31]),"+f"(d[32]),"+f"(d[33]),"+f"(d[34]),"+f"(d[35]),"+f"(d[36]),"+f"(d[37]),"+f"(d[38]),"+f"(d[39]),"+f"(d[40]),"+f"(d[41]),"+f"(d[42]),"+f"(d[43]),"+f"(d[44]),"+f"(d[45]),"+f"(d[46]),"+f"(d[47]),"+f"(d[48]),"+f"(d[49]),"+f"(d[50]),"+f"(d[51]),"+f"(d[52]),"+f"(d[53]),"+f"(d[54]),"+f"(d[55]),"+f"(d[56]),"+f"(d[57]),"+f"(d[58]),"+f"(d[59]),"+f"(d[60]),"+f"(d[61]),"+f"(d[62]),"+f"(d[63])
    : "r"(da), "r"(db), "r"(sd), "r"(ha));
}
__device__ __forceinline__ void wgmma_ss_n40_tt(float (&d)[20], uint32_t da, uint32_t db, int sd) {
  asm volatile("{\n.reg .pred p;\n.reg .b64 a, b;\nsetp.ne.b32 p, %22, 0;\nmov.b64 a, {%20, 0x40000040};\nmov.b64 b, {%21, 0x8};\n"
    "wgmma.mma_async.sync.aligned.m64n40k16.f32.bf16.bf16 {%0,%1,%2,%3,%4,%5,%6,%7,%8,%9,%10,%11,%12,%13,%14,%15,%16,%17,%18,%19}, a, b, p, 1, 1, 1, 1;\n}\n"
    : "+f"(d[0]),"+f"(d[1]),"+f"(d[2]),"+f"(d[3]),"+f"(d[4]),"+f"(d[5]),"+f"(d[6]),"+f"(d[7]),"+f"(d[8]),"+f"(d[9]),"+f"(d[10]),"+f"(d[11]),"+f"(d[12]),"+f"(d[13]),"+f"(d[14]),"+f"(d[15]),"+f"(d[16]),"+f"(d[17]),"+f"(d[18]),"+f"(d[19])
    : "r"(da), "r"(db), "r"(sd));
}
__device__ __forceinline__ void wgmma_ss_n32(float (&d)[16], uint32_t da, uint32_t db, int sd) {
  asm volatile("{\n.reg .pred p;\n.reg .b64 a, b;\nsetp.ne.b32 p, %18, 0;\nmov.b64 a, {%16, 0x40000040};\nmov.b64 b, {%17, 0x80000020};\n"
    "wgmma.mma_async.sync.aligned.m64n32k16.f32.bf16.bf16 {%0,%1,%2,%3,%4,%5,%6,%7,%8,%9,%10,%11,%12,%13,%14,%15}, a, b, p, 1, 1, 0, 1;\n}\n"
    : "+f"(d[0]),"+f"(d[1]),"+f"(d[2]),"+f"(d[3]),"+f"(d[4]),"+f"(d[5]),"+f"(d[6]),"+f"(d[7]),"+f"(d[8]),"+f"(d[9]),"+f"(d[10]),"+f"(d[11]),"+f"(d[12]),"+f"(d[13]),"+f"(d[14]),"+f"(d[15])
    : "r"(da), "r"(db), "r"(sd));
}
__device__ __forceinline__ void wgmma_rs_n40(float (&d)[20], uint32_t a0, uint32_t a1, uint32_t a2, uint32_t a3, uint32_t db, int sd) {
  asm volatile("{\n.reg .pred p;\n.reg .b64 b;\nsetp.ne.b32 p, %25, 0;\nmov.b64 b, {%24, 0x10};\n"
    "wgmma.mma_async.sync.aligned.m64n40k16.f32.bf16.bf16 {%0,%1,%2,%3,%4,%5,%6,%7,%8,%9,%10,%11,%12,%13,%14,%15,%16,%17,%18,%19}, {%20,%21,%22,%23}, b, p, 1, 1, 1;\n}\n"
    : "+f"(d[0]),"+f"(d[1]),"+f"(d[2]),"+f"(d[3]),"+f"(d[4]),"+f"(d[5]),"+f"(d[6]),"+f"(d[7]),"+f"(d[8]),"+f"(d[9]),"+f"(d[10]),"+f"(d[11]),"+f"(d[12]),"+f"(d[13]),"+f"(d[14]),"+f"(d[15]),"+f"(d[16]),"+f"(d[17]),"+f"(d[18]),"+f"(d[19])
    : "r"(a0), "r"(a1), "r"(a2), "r"(a3), "r"(db), "r"(sd));
}
__device__ __forceinline__ void wgmma_r1_n256(float (&d)[128], uint32_t da, uint32_t db, int sd) {
  asm volatile("{\n.reg .pred p;\n.reg .b64 a, b;\nsetp.ne.b32 p, %130, 0;\nmov.b64 a, {%128, 0x8};\nmov.b64 b, {%129, 0x6};\n"
    "wgmma.mma_async.sync.aligned.m64n256k16.f32.bf16.bf16 {%0,%1,%2,%3,%4,%5,%6,%7,%8,%9,%10,%11,%12,%13,%14,%15,%16,%17,%18,%19,%20,%21,%22,%23,%24,%25,%26,%27,%28,%29,%30,%31,%32,%33,%34,%35,%36,%37,%38,%39,%40,%41,%42,%43,%44,%45,%46,%47,%48,%49,%50,%51,%52,%53,%54,%55,%56,%57,%58,%59,%60,%61,%62,%63,%64,%65,%66,%67,%68,%69,%70,%71,%72,%73,%74,%75,%76,%77,%78,%79,%80,%81,%82,%83,%84,%85,%86,%87,%88,%89,%90,%91,%92,%93,%94,%95,%96,%97,%98,%99,%100,%101,%102,%103,%104,%105,%106,%107,%108,%109,%110,%111,%112,%113,%114,%115,%116,%117,%118,%119,%120,%121,%122,%123,%124,%125,%126,%127}, a, b, p, 1, 1, 0, 1;\n}\n"
    : "+f"(d[0]),"+f"(d[1]),"+f"(d[2]),"+f"(d[3]),"+f"(d[4]),"+f"(d[5]),"+f"(d[6]),"+f"(d[7]),"+f"(d[8]),"+f"(d[9]),"+f"(d[10]),"+f"(d[11]),"+f"(d[12]),"+f"(d[13]),"+f"(d[14]),"+f"(d[15]),"+f"(d[16]),"+f"(d[17]),"+f"(d[18]),"+f"(d[19]),"+f"(d[20]),"+f"(d[21]),"+f"(d[22]),"+f"(d[23]),"+f"(d[24]),"+f"(d[25]),"+f"(d[26]),"+f"(d[27]),"+f"(d[28]),"+f"(d[29]),"+f"(d[30]),"+f"(d[31]),"+f"(d[32]),"+f"(d[33]),"+f"(d[34]),"+f"(d[35]),"+f"(d[36]),"+f"(d[37]),"+f"(d[38]),"+f"(d[39]),"+f"(d[40]),"+f"(d[41]),"+f"(d[42]),"+f"(d[43]),"+f"(d[44]),"+f"(d[45]),"+f"(d[46]),"+f"(d[47]),"+f"(d[48]),"+f"(d[49]),"+f"(d[50]),"+f"(d[51]),"+f"(d[52]),"+f"(d[53]),"+f"(d[54]),"+f"(d[55]),"+f"(d[56]),"+f"(d[57]),"+f"(d[58]),"+f"(d[59]),"+f"(d[60]),"+f"(d[61]),"+f"(d[62]),"+f"(d[63]),"+f"(d[64]),"+f"(d[65]),"+f"(d[66]),"+f"(d[67]),"+f"(d[68]),"+f"(d[69]),"+f"(d[70]),"+f"(d[71]),"+f"(d[72]),"+f"(d[73]),"+f"(d[74]),"+f"(d[75]),"+f"(d[76]),"+f"(d[77]),"+f"(d[78]),"+f"(d[79]),"+f"(d[80]),"+f"(d[81]),"+f"(d[82]),"+f"(d[83]),"+f"(d[84]),"+f"(d[85]),"+f"(d[86]),"+f"(d[87]),"+f"(d[88]),"+f"(d[89]),"+f"(d[90]),"+f"(d[91]),"+f"(d[92]),"+f"(d[93]),"+f"(d[94]),"+f"(d[95]),"+f"(d[96]),"+f"(d[97]),"+f"(d[98]),"+f"(d[99]),"+f"(d[100]),"+f"(d[101]),"+f"(d[102]),"+f"(d[103]),"+f"(d[104]),"+f"(d[105]),"+f"(d[106]),"+f"(d[107]),"+f"(d[108]),"+f"(d[109]),"+f"(d[110]),"+f"(d[111]),"+f"(d[112]),"+f"(d[113]),"+f"(d[114]),"+f"(d[115]),"+f"(d[116]),"+f"(d[117]),"+f"(d[118]),"+f"(d[119]),"+f"(d[120]),"+f"(d[121]),"+f"(d[122]),"+f"(d[123]),"+f"(d[124]),"+f"(d[125]),"+f"(d[126]),"+f"(d[127])
    : "r"(da), "r"(db), "r"(sd));
}
__device__ __forceinline__ void wgmma_r1_n128(float (&d)[64], uint32_t da, uint32_t db, int sd) {
  asm volatile("{\n.reg .pred p;\n.reg .b64 a, b;\nsetp.ne.b32 p, %66, 0;\nmov.b64 a, {%64, 0x8};\nmov.b64 b, {%65, 0x6};\n"
    "wgmma.mma_async.sync.aligned.m64n128k16.f32.bf16.bf16 {%0,%1,%2,%3,%4,%5,%6,%7,%8,%9,%10,%11,%12,%13,%14,%15,%16,%17,%18,%19,%20,%21,%22,%23,%24,%25,%26,%27,%28,%29,%30,%31,%32,%33,%34,%35,%36,%37,%38,%39,%40,%41,%42,%43,%44,%45,%46,%47,%48,%49,%50,%51,%52,%53,%54,%55,%56,%57,%58,%59,%60,%61,%62,%63}, a, b, p, 1, 1, 0, 1;\n}\n"
    : "+f"(d[0]),"+f"(d[1]),"+f"(d[2]),"+f"(d[3]),"+f"(d[4]),"+f"(d[5]),"+f"(d[6]),"+f"(d[7]),"+f"(d[8]),"+f"(d[9]),"+f"(d[10]),"+f"(d[11]),"+f"(d[12]),"+f"(d[13]),"+f"(d[14]),"+f"(d[15]),"+f"(d[16]),"+f"(d[17]),"+f"(d[18]),"+f"(d[19]),"+f"(d[20]),"+f"(d[21]),"+f"(d[22]),"+f"(d[23]),"+f"(d[24]),"+f"(d[25]),"+f"(d[26]),"+f"(d[27]),"+f"(d[28]),"+f"(d[29]),"+f"(d[30]),"+f"(d[31]),"+f"(d[32]),"+f"(d[33]),"+f"(d[34]),"+f"(d[35]),"+f"(d[36]),"+f"(d[37]),"+f"(d[38]),"+f"(d[39]),"+f"(d[40]),"+f"(d[41]),"+f"(d[42]),"+f"(d[43]),"+f"(d[44]),"+f"(d[45]),"+f"(d[46]),"+f"(d[47]),"+f"(d[48]),"+f"(d[49]),"+f"(d[50]),"+f"(d[51]),"+f"(d[52]),"+f"(d[53]),"+f"(d[54]),"+f"(d[55]),"+f"(d[56]),"+f"(d[57]),"+f"(d[58]),"+f"(d[59]),"+f"(d[60]),"+f"(d[61]),"+f"(d[62]),"+f"(d[63])
    : "r"(da), "r"(db), "r"(sd));
}

__device__ __forceinline__ uint32_t smem_u32(const void* p) { return (uint32_t)__cvta_generic_to_shared(p); }
__device__ __forceinline__ void mbar_init(uint32_t bar, uint32_t cnt) { asm volatile("mbarrier.init.shared::cta.b64 [%0], %1;" ::"r"(bar), "r"(cnt)); }
__device__ __forceinline__ void mbar_expect_tx(uint32_t bar, uint32_t bytes) { asm volatile("mbarrier.arrive.expect_tx.shared::cta.b64 _, [%0], %1;" ::"r"(bar), "r"(bytes) : "memory"); }
__device__ __forceinline__ void mbar_arrive(uint32_t bar) { asm volatile("mbarrier.arrive.shared::cta.b64 _, [%0];" ::"r"(bar) : "memory"); }
__device__ __forceinline__ void mbar_arrive_n(uint32_t bar, uint32_t n) { asm volatile("mbarrier.arrive.shared::cta.b64 _, [%0], %1;" ::"r"(bar), "r"(n) : "memory"); }
__device__ __forceinline__ void mbar_wait(uint32_t bar, uint32_t parity) {
  asm volatile("{\n.reg .pred p;\nLAB_WAIT:\nmbarrier.try_wait.parity.shared::cta.b64 p, [%0], %1;\n@p bra DONE;\nbra LAB_WAIT;\nDONE:\n}" ::"r"(bar), "r"(parity) : "memory");
}
__device__ __forceinline__ void mbar_wait2(uint32_t a, uint32_t pa, uint32_t b, uint32_t pb) {
  asm volatile("{\n.reg .pred p, q;\nLAB_WAIT:\nmbarrier.try_wait.parity.shared::cta.b64 p, [%0], %1;\nmbarrier.try_wait.parity.shared::cta.b64 q, [%2], %3;\n"
               "and.pred p, p, q;\n@p bra DONE;\nbra LAB_WAIT;\nDONE:\n}" ::"r"(a), "r"(pa), "r"(b), "r"(pb) : "memory");
}
__device__ __forceinline__ void mbar_wait3(uint32_t a, uint32_t pa, uint32_t b, uint32_t pb) {
  asm volatile("{\n.reg .pred p, q, r;\nLAB_WAIT:\nmbarrier.try_wait.parity.shared::cta.b64 p, [%0], %1;\nmbarrier.try_wait.parity.shared::cta.b64 q, [%2], %3;\n"
               "mbarrier.try_wait.parity.shared::cta.b64 r, [%2+8], %3;\nand.pred p, p, q;\nand.pred p, p, r;\n@p bra DONE;\nbra LAB_WAIT;\nDONE:\n}" ::"r"(a), "r"(pa), "r"(b), "r"(pb) : "memory");
}
__device__ __forceinline__ bool mbar_probe2(uint32_t a, uint32_t pa, uint32_t b, uint32_t pb) {
  uint32_t ok;
  asm volatile("{\n.reg .pred p, q;\nmbarrier.test_wait.parity.shared::cta.b64 p, [%1], %2;\nmbarrier.test_wait.parity.shared::cta.b64 q, [%3], %4;\n"
               "and.pred p, p, q;\nselp.u32 %0, 1, 0, p;\n}" : "=r"(ok) : "r"(a), "r"(pa), "r"(b), "r"(pb) : "memory");
  return ok != 0;
}
__device__ __forceinline__ void tma_load_3d(uint32_t dst, const CUtensorMap* tm, uint32_t bar, int c0, int c1, int c2) {
  asm volatile("cp.async.bulk.tensor.3d.shared::cluster.global.mbarrier::complete_tx::bytes [%0], [%1, {%3, %4, %5}], [%2];"
               ::"r"(dst), "l"(tm), "r"(bar), "r"(c0), "r"(c1), "r"(c2) : "memory");
}
__device__ __forceinline__ void tma_load_2d(uint32_t dst, const CUtensorMap* tm, uint32_t bar, int c0, int c1) {
  asm volatile("cp.async.bulk.tensor.2d.shared::cluster.global.mbarrier::complete_tx::bytes [%0], [%1, {%3, %4}], [%2];"
               ::"r"(dst), "l"(tm), "r"(bar), "r"(c0), "r"(c1) : "memory");
}
__device__ __forceinline__ void tma_load_w(uint32_t dst, const CUtensorMap* tm, uint32_t bar, int col, int kb) {
#pragma unroll
  for (int q = 0; q < 2; q++)
    asm volatile("cp.async.bulk.tensor.5d.shared::cluster.global.mbarrier::complete_tx::bytes [%0], [%1, {%3, %4, %4, %4, %5}], [%2];"
                 ::"r"(dst + q * 8192), "l"(tm), "r"(bar), "r"(col + q * 64), "r"(0), "r"(2 * kb) : "memory");
}
__device__ __forceinline__ void tma_prefetch_w(const CUtensorMap* tm, int col, int kb) {
#pragma unroll
  for (int q = 0; q < 2; q++)
    asm volatile("cp.async.bulk.prefetch.tensor.5d.L2.global [%0, {%1, %2, %2, %2, %3}];" ::"l"(tm), "r"(col + q * 64), "r"(0), "r"(2 * kb) : "memory");
}
__device__ __forceinline__ void bulk_load(uint32_t dst, const void* g, uint32_t bytes, uint32_t bar) {
  asm volatile("cp.async.bulk.shared::cluster.global.mbarrier::complete_tx::bytes [%0], [%1], %2, [%3];" ::"r"(dst), "l"(g), "r"(bytes), "r"(bar) : "memory");
}
__device__ __forceinline__ void prefetch_map(const CUtensorMap* tm) { asm volatile("prefetch.tensormap [%0];" ::"l"(tm) : "memory"); }
__device__ __forceinline__ void fence_async_smem() { asm volatile("fence.proxy.async.shared::cta;" ::: "memory"); }
__device__ __forceinline__ void fence_async_global() { asm volatile("fence.proxy.async.global;" ::: "memory"); }
__device__ __forceinline__ void fence_gpu() { asm volatile("fence.release.gpu;" ::: "memory"); }
__device__ __forceinline__ void st_flag(unsigned* p, unsigned v) { asm volatile("st.relaxed.gpu.global.u32 [%0], %1;" ::"l"(p), "r"(v) : "memory"); }
__device__ __forceinline__ unsigned ld_flag(const unsigned* p) { unsigned v; asm volatile("ld.relaxed.gpu.global.u32 %0, [%1];" : "=r"(v) : "l"(p) : "memory"); return v; }
__device__ __forceinline__ uint4 ldcg4(const void* p) { uint4 v; asm volatile("ld.global.cg.v4.u32 {%0,%1,%2,%3}, [%4];" : "=r"(v.x), "=r"(v.y), "=r"(v.z), "=r"(v.w) : "l"(p)); return v; }
__device__ __forceinline__ uint4 ld_pkt(const uint4* p) {
  uint4 v; asm volatile("{\n.reg .b128 t;\nld.relaxed.gpu.global.b128 t, [%4];\nmov.b128 {%0,%1,%2,%3}, t;\n}" : "=r"(v.x), "=r"(v.y), "=r"(v.z), "=r"(v.w) : "l"(p) : "memory"); return v;
}
__device__ __forceinline__ void st_pkt(uint4* p, uint32_t a, uint32_t b, uint32_t c, uint32_t tag) {
  asm volatile("{\n.reg .b128 t;\nmov.b128 t, {%1,%2,%3,%4};\nst.relaxed.gpu.global.b128 [%0], t;\n}" ::"l"(p), "r"(a), "r"(b), "r"(c), "r"(tag) : "memory");
}
__device__ __forceinline__ void st_v4(uint4* p, uint32_t a, uint32_t b, uint32_t c, uint32_t d) { asm volatile("st.relaxed.gpu.global.v4.u32 [%0], {%1,%2,%3,%4};" ::"l"(p), "r"(a), "r"(b), "r"(c), "r"(d) : "memory"); }
__device__ __forceinline__ void sts32(uint32_t addr, uint32_t a) { asm volatile("st.shared.u32 [%0], %1;" ::"r"(addr), "r"(a) : "memory"); }
__device__ __forceinline__ void sts64(uint32_t addr, uint32_t a, uint32_t b) { asm volatile("st.shared.v2.u32 [%0], {%1,%2};" ::"r"(addr), "r"(a), "r"(b) : "memory"); }
__device__ __forceinline__ uint32_t mul2(uint32_t a, uint32_t b) { uint32_t r; asm("mul.rn.bf16x2 %0, %1, %2;" : "=r"(r) : "r"(a), "r"(b)); return r; }
__device__ __forceinline__ uint32_t add2(uint32_t a, uint32_t b) { uint32_t r; asm("add.rn.bf16x2 %0, %1, %2;" : "=r"(r) : "r"(a), "r"(b)); return r; }
__device__ __forceinline__ bool elect() {
  uint32_t p; asm volatile("{\n.reg .pred q;\nelect.sync _|q, 0xffffffff;\nselp.u32 %0, 1, 0, q;\n}" : "=r"(p)); return p != 0;
}
__device__ __forceinline__ void wgmma_fence() { asm volatile("wgmma.fence.sync.aligned;" ::: "memory"); }
__device__ __forceinline__ void wgmma_commit() { asm volatile("wgmma.commit_group.sync.aligned;" ::: "memory"); }
template <int N> __device__ __forceinline__ void wgmma_wait() { asm volatile("wgmma.wait_group.sync.aligned %0;" ::"n"(N) : "memory"); }
template <int N> __device__ __forceinline__ void fence_regs(float (&d)[N]) {
#pragma unroll
  for (int i = 0; i < N; i++) asm volatile("" : "+f"(d[i])::"memory");
}
template <int R> __device__ __forceinline__ void reg_alloc() { asm volatile("setmaxnreg.inc.sync.aligned.u32 %0;" ::"n"(R)); }
template <int R> __device__ __forceinline__ void reg_dealloc() { asm volatile("setmaxnreg.dec.sync.aligned.u32 %0;" ::"n"(R)); }
__device__ __forceinline__ void wg_bar(int w) { asm volatile("bar.sync %0, 128;" ::"r"(w + 1) : "memory"); }
__device__ __forceinline__ constexpr uint32_t desc_lo(uint32_t addr, uint32_t lbo) { return (addr >> 4) + ((lbo >> 4) << 16); }
__device__ __forceinline__ uint32_t pack2(float lo, float hi) { uint32_t r; asm("cvt.rn.bf16x2.f32 %0, %1, %2;" : "=r"(r) : "f"(hi), "f"(lo)); return r; }
__device__ __forceinline__ float lo16(uint32_t v) { return __uint_as_float(v << 16); }
__device__ __forceinline__ float hi16(uint32_t v) { return __uint_as_float(v & 0xFFFF0000u); }
__device__ __forceinline__ float ex2(float x) { float r; asm("ex2.approx.ftz.f32 %0, %1;" : "=f"(r) : "f"(x)); return r; }
__device__ __forceinline__ float rcp(float x) { float r; asm("rcp.approx.ftz.f32 %0, %1;" : "=f"(r) : "f"(x)); return r; }
__device__ __forceinline__ uint32_t movm(uint32_t a) { uint32_t d; asm volatile("movmatrix.sync.aligned.m8n8.trans.b16 %0, %1;" : "=r"(d) : "r"(a)); return d; }
__device__ __forceinline__ void stsm4(uint32_t addr, uint32_t a, uint32_t b, uint32_t c, uint32_t d) {
  asm volatile("stmatrix.sync.aligned.m8n8.x4.shared.b16 [%0], {%1,%2,%3,%4};" ::"r"(addr), "r"(a), "r"(b), "r"(c), "r"(d) : "memory");
}
__device__ __forceinline__ void ldsm4(uint32_t addr, uint32_t (&r)[4]) {
  asm volatile("ldmatrix.sync.aligned.m8n8.x4.shared.b16 {%0,%1,%2,%3}, [%4];" : "=r"(r[0]), "=r"(r[1]), "=r"(r[2]), "=r"(r[3]) : "r"(addr) : "memory");
}
__device__ __forceinline__ void sts128(uint32_t addr, uint32_t a, uint32_t b, uint32_t c, uint32_t d) {
  asm volatile("st.shared.v4.u32 [%0], {%1,%2,%3,%4};" ::"r"(addr), "r"(a), "r"(b), "r"(c), "r"(d) : "memory");
}
__device__ __forceinline__ void lds128(uint32_t addr, uint32_t& a, uint32_t& b, uint32_t& c, uint32_t& d) {
  asm volatile("ld.shared.v4.u32 {%0,%1,%2,%3}, [%4];" : "=r"(a), "=r"(b), "=r"(c), "=r"(d) : "r"(addr) : "memory");
}
__device__ __forceinline__ float lds32f(uint32_t addr) { float v; asm volatile("ld.shared.f32 %0, [%1];" : "=f"(v) : "r"(addr) : "memory"); return v; }
__device__ __forceinline__ float2 lds64f(uint32_t addr) { float2 v; asm volatile("ld.shared.v2.f32 {%0,%1}, [%2];" : "=f"(v.x), "=f"(v.y) : "r"(addr) : "memory"); return v; }
__device__ __forceinline__ void mma16816(float (&d)[4], uint32_t a0, uint32_t a1, uint32_t a2, uint32_t a3, uint32_t b0, uint32_t b1) {
  asm("mma.sync.aligned.m16n8k16.row.col.f32.bf16.bf16.f32 {%0,%1,%2,%3}, {%4,%5,%6,%7}, {%8,%9}, {%0,%1,%2,%3};"
      : "+f"(d[0]), "+f"(d[1]), "+f"(d[2]), "+f"(d[3]) : "r"(a0), "r"(a1), "r"(a2), "r"(a3), "r"(b0), "r"(b1));
}
__device__ __forceinline__ void mma1688(float (&d)[4], uint32_t a0, uint32_t a1, uint32_t b0) {
  asm("mma.sync.aligned.m16n8k8.row.col.f32.bf16.bf16.f32 {%0,%1,%2,%3}, {%4,%5}, {%6}, {%0,%1,%2,%3};"
      : "+f"(d[0]), "+f"(d[1]), "+f"(d[2]), "+f"(d[3]) : "r"(a0), "r"(a1), "r"(b0));
}

__device__ __forceinline__ float qsum(float v) { v += __shfl_xor_sync(0xffffffffu, v, 1); v += __shfl_xor_sync(0xffffffffu, v, 2); return v; }

constexpr int NCTA = 132;
#define NB_ 6
#define NA_ 5
constexpr int NB = NB_;
constexpr int NA = NA_;
constexpr uint32_t SLOT = 16384;
constexpr uint32_t SB = 1024;
constexpr uint32_t OFF_B = 0;
constexpr uint32_t OFF_A = NB * SLOT;
constexpr uint32_t OFF_S = OFF_A + NA * SLOT;
constexpr uint32_t OFF_T = OFF_S + 20480;
constexpr uint32_t OFF_CS = OFF_T + 24576;
constexpr uint32_t OFF_MR = OFF_CS + 4640;
constexpr uint32_t OFF_BAR = OFF_MR + 512;
constexpr uint32_t OFF_MA = OFF_S, OFF_MB = OFF_CS - 2048;
constexpr uint32_t BAR_FULLB = OFF_BAR;
constexpr uint32_t BAR_FULLA = BAR_FULLB + 64;
constexpr uint32_t BAR_EMPTYB = BAR_FULLA + 64;
constexpr uint32_t BAR_EMPTYA = BAR_EMPTYB + 64;
constexpr uint32_t BAR_SIGP = BAR_EMPTYA + 64;
constexpr uint32_t BAR_SIGT = BAR_SIGP + 32;
constexpr uint32_t BAR_STAT = BAR_SIGP + 64;
constexpr uint32_t BAR_HALO = BAR_STAT + 16;
constexpr uint32_t BAR_CS = BAR_HALO + 8;
constexpr uint32_t BAR_WPHI = BAR_CS + 16;
constexpr uint32_t BAR_KV = BAR_WPHI + 8;
constexpr uint32_t BAR_STG = BAR_KV + 16;
constexpr uint32_t BAR_EPOCH = BAR_STG + 48;
constexpr uint32_t OFF_EPOCH = OFF_BAR + 7 * 64;
static_assert(BAR_EPOCH < OFF_EPOCH, "barriers");
constexpr uint32_t SMEM_BYTES = OFF_EPOCH + 8;
static_assert(SMEM_BYTES <= 232448 && NB % 2 == 0 && NB <= 8 && NA <= 6, "smem");

#define CREGS 224
#define PREGS 56
#define PF0 9
#define PF1 13
#define PF2 17
#define PRE_A 2
#define PRE_B 4
#define CSB 4
#define CSNEED 0xF003u
#define XR 2
#define PS0 2
#define PS1 2
#define PSW 0
#define STG0 0
#define QORD 2
#define KSPLIT 12
#define KEEP 16
#define NJ 3
#define KSL 1000
#define PSL 0
#define KVS 12
#define D2 2000
#define D3 1500
#define G0 50
#define G3 50
#define G1 0
#define G4 0
#define MAP 3
#define PMAP 0x76321450u
#define PW 1
#define PN2 0
#define KB 8
#define PNX 2
#define PNO 2
#define DEFER 3
#define DEFL 2
#define TSK 3
#define TSL 3
constexpr int NTHREADS = 384;

struct Params {
  CUtensorMap mx;
  CUtensorMap mw[3];
  CUtensorMap mwo[2];
  CUtensorMap mcs[2];
  CUtensorMap mwphi;
  uint4* out;
};

#define XBUF(L) 1
__device__ __align__(256) uint4 g_img[XBUF(3) + 1][16][16][1024];
__device__ __align__(256) uint4 g_wf[2][8][16][1024];
__device__ __align__(256) uint4 g_stats[16][2][8][32];
__device__ __align__(256) uint4 g_halo[16][8][2][256];
__device__ __align__(256) float g_cs[2][2][3072];
__device__ __align__(256) uint4 g_kvpart[8][16][2][544];
__device__ __align__(256) uint4 g_kvfin[8][16][80];
__device__ __align__(256) unsigned g_xflag[4][2][16][32];
__device__ __align__(256) unsigned g_oflag[4][2][16][32];
__device__ __align__(256) unsigned g_hflag[2][16][8][32];
__device__ __align__(256) unsigned g_kvfflag[2][8][2][32];
__device__ __align__(256) unsigned g_csflag[2][8][32];
__device__ __align__(256) unsigned g_kflag[8][32];
__device__ unsigned g_ctr;
__device__ __forceinline__ unsigned vblock() {
  unsigned s;
  asm volatile("mov.u32 %0, %%smid;" : "=r"(s));
  const unsigned r = s & 1;
  s >>= 1;
  const unsigned t = s - 32, q = (t * 37) >> 8;
  const unsigned hi = s < 60 ? 12 + (t - 7 * q) * 8 + q : (s < 62 ? s + 4 : s - 58);
  unsigned b = 2 * (s < 32 ? (s & 7) * 8 + (s >> 3) : hi) + r;
  if (b < 128) b = (b & 15) | ((PMAP >> ((b >> 4) * 4)) & 7) << 4;
  if (s >= 62) b = 8 + 4 * r + s - 62;
  return __shfl_sync(0xffffffffu, b, 0);
}
#define TS(who, id) do {} while (0)
#define TSW(id) do {} while (0)

#define TSMASK 0xFFFF
#define TSL_(a) do { if ((TSMASK >> (a)) & 1) TSW((a) + L * 12); } while (0)
__device__ __forceinline__ int cta_m(unsigned b) { return ((b >> 2) & 12) | (b & 3); }
__device__ __forceinline__ int cta_j(unsigned b) { return ((b >> 2) & 3) | ((b >> 4) & 4); }
struct Ring { uint32_t s, ph; };
template <int N> __device__ __forceinline__ void adv(Ring& r) { if (++r.s == N) { r.s = 0; r.ph ^= 1; } }
template <int N> __device__ __forceinline__ void rewind2(Ring& r) { if (r.s < 2) { r.s += N - 2; r.ph ^= 1; } else r.s -= 2; }
__device__ __forceinline__ int other_tile(int t, int j) { return (t == (j | 4) ? 7 : t) ^ (~j & 4); }
__device__ __forceinline__ int q_order(int i, int j) { return 2 * (i >= 14 ? j : other_tile(i >> 1, j)) + (i & 1); }
__device__ __forceinline__ int o_order(int i, int j) {
  if (i < 2) return 2 * j + i;
  const int odd = i >= 9;
  return 2 * other_tile(i - 2 - 7 * odd, j) + odd;
}
__device__ __forceinline__ int kv_order(int i, int j, int L) { return L > 0 ? o_order(i, j) : (i + 14 + 2 * (j & 4)) & 15; }

__device__ __forceinline__ unsigned poll_flags(const unsigned* f, int n, unsigned need, unsigned tag) {
  const int lane = threadIdx.x & 31;
  unsigned mask; int it = 0;
  do {
    unsigned v = lane < n ? ld_flag(f + lane) : 0u;
    mask = __ballot_sync(0xffffffffu, lane < n && v == tag);
    if (++it > (1 << 22)) __trap();
  } while ((mask & need) != need);
  fence_async_global();
  return mask;
}
template <bool WAIT = true>
__device__ __forceinline__ unsigned get_tag(uint32_t sb) {
  if (WAIT) mbar_wait(sb + BAR_EPOCH, 0);
  unsigned t; asm volatile("ld.shared.u32 %0, [%1];" : "=r"(t) : "r"(sb + OFF_EPOCH) : "memory");
  return t;
}

__device__ __forceinline__ int lane_id() { int l; asm volatile("mov.u32 %0, %%laneid;" : "=r"(l)); return l; }
__device__ __forceinline__ unsigned seq4(unsigned tag, int L) { return 8u | ((tag & 1u) << 2) | (unsigned)L; }
constexpr float LOG2E = 1.4426950408889634f;

__device__ __forceinline__ void sched_fence(uint32_t sb) { mbar_wait(sb + BAR_EPOCH, 0); }
constexpr uint32_t HA128 = 0x40000040u, HA64 = 0x80000040u;
struct Ctx {
  static constexpr uint32_t sb = SB;
  uint32_t ab, da0;
  int w, warp, lane, g, c;
  int goff;
  __device__ __forceinline__ int m() const { return goff >> 14; }
  __device__ __forceinline__ int j() const { return (goff >> 4) & 7; }
  bool elected;
  Ring ra, rb;
  uint32_t pa, pb;
  uint32_t ha, k2;
  uint32_t mrow, mxor, mhi;
  __device__ __forceinline__ uint32_t aslot(uint32_t s) const { return ab + s * SLOT; }
  __device__ __forceinline__ uint32_t fullA(uint32_t s) const { return sb + BAR_FULLA + s * 8; }
  __device__ __forceinline__ uint32_t fullB(uint32_t s) const { return sb + BAR_FULLB + s * 8; }
  __device__ __forceinline__ void releaseA(uint32_t s) const { if (elected) mbar_arrive(sb + BAR_EMPTYA + s * 8); }
  __device__ __forceinline__ void releaseB(uint32_t s) const { if (elected) mbar_arrive(sb + BAR_EMPTYB + s * 8); }
  __device__ __forceinline__ uint32_t maddr(uint32_t tile, uint32_t ch) const { return tile + mrow + (((ch + mhi) ^ mxor) << 4); }
  __device__ __forceinline__ uint32_t oo() const { return warp * 128 + g * 4 + (c ^ (g >> 1)); }
  __device__ __forceinline__ uint4* img(int b, int hp) const { return &g_img[b][m()][2 * j() + hp][w * 512 + oo()]; }
  __device__ __forceinline__ uint32_t held(int i) const { return ra.s + i < 2 ? ra.s + i + NA - 2 : ra.s + i - 2; }
};

template <int N, bool FIRST, bool O = true>
__device__ __forceinline__ void gemm_issue(float (&acc)[N / 2], Ctx& x, bool ready = false) {
  if (!ready) {
    if (N == 256) mbar_wait3(x.fullA(x.ra.s), x.ra.ph, x.fullB(x.rb.s), x.rb.ph);
    else mbar_wait2(x.fullA(x.ra.s), x.ra.ph, x.fullB(x.rb.s), x.rb.ph);
  }
  const uint32_t da = x.da0 + x.ra.s * (SLOT / 16), db = desc_lo(SB + OFF_B, 8192) + x.rb.s * (SLOT / 16);
  wgmma_fence();
#pragma unroll
  for (int k = 0; k < 4; k++) {
    const uint32_t a = da + (k >> 1) * (O ? 32 : x.k2) + (k & 1) * 2, ha = O ? HA64 : x.ha;
    if constexpr (N == 256) wgmma_ss_n256(acc, a, ha, db + 128 * k, !(FIRST && k == 0));
    else wgmma_ss_n128(acc, a, ha, db + 128 * k, !(FIRST && k == 0));
  }
  wgmma_commit();
}
template <int N>
__device__ __forceinline__ void gemm_next(Ctx& x) {
  x.pa = x.ra.s; x.pb = x.rb.s;
  if (N == 256) x.rb.s++;
  adv<NA>(x.ra); adv<NB>(x.rb);
}
template <int N>
__device__ __forceinline__ void gemm_release(Ctx& x, bool relA) {
  if (relA) x.releaseA(x.pa);
  x.releaseB(x.pb);
  if (N == 256) x.releaseB(x.pb + 1);
}
template <int N>
__device__ __forceinline__ void gemm_retire(Ctx& x, bool relA) { wgmma_wait<1>(); gemm_release<N>(x, relA); gemm_next<N>(x); }
template <bool O = true>
__device__ __forceinline__ void gemm_run(float (&acc)[64], Ctx& x, int n, int hold, int n4 = 0) {
  bool ready = false;
#pragma unroll 1
  for (; n > 0; n--) {
    gemm_issue<128, false, O>(acc, x, ready);
    const uint32_t pa = x.pa, pb = x.pb;
    gemm_next<128>(x);
    ready = mbar_probe2(x.fullA(x.ra.s), x.ra.ph, x.fullB(x.rb.s), x.rb.ph);
    wgmma_wait<1>();
    if (n > hold) x.releaseA(pa);
    x.releaseB(pb);
  }
}
__device__ __forceinline__ void gemm_end(float (&acc)[64], Ctx& x) { wgmma_wait<0>(); fence_regs(acc); gemm_release<128>(x, false); }

__device__ __forceinline__ void load_x32(float* a, uint32_t tile, uint32_t ch, const Ctx& x) {
#pragma unroll
  for (int p = 0; p < 2; p++) {
    uint32_t v[4];
    ldsm4(x.maddr(tile, ch + 2 * p), v);
#pragma unroll
    for (int i = 0; i < 4; i++) { a[8 * p + 2 * i] = lo16(v[i]); a[8 * p + 2 * i + 1] = hi16(v[i]); }
  }
}

__device__ __forceinline__ void rows_load(uint4* r, uint32_t tile, const Ctx& x) {
#pragma unroll
  for (int q = 0; q < 4; q++) {
    const uint32_t row = x.warp * 16 + 4 * q + (x.lane >> 3);
    lds128(tile + row * 128 + (((x.lane & 7) ^ (row & 7)) << 4), r[q].x, r[q].y, r[q].z, r[q].w);
  }
}
__device__ __forceinline__ void rows_store(const uint4* r, uint4* g, const Ctx& x) {
  g += (x.warp * 16 + (x.lane >> 3)) * 256 + (x.lane & 7);
#pragma unroll
  for (int q = 0; q < 4; q++) g[q * 1024] = r[q];
}
__device__ __forceinline__ void publish(int id, const Ctx& x) { __syncwarp(); if (x.lane == 0) mbar_arrive(x.sb + BAR_SIGP + id * 8); }
__device__ __forceinline__ void img_store(const uint4 (&r)[4], uint4* g) {
#pragma unroll
  for (int q = 0; q < 4; q++) g[q * 32] = r[q];
}
__device__ __forceinline__ void img_sts(const uint4 (&r)[4], uint32_t tile, const Ctx& x) {
#pragma unroll
  for (int q = 0; q < 4; q++) sts128(tile + x.oo() * 16 + q * 512, r[q].x, r[q].y, r[q].z, r[q].w);
}
__device__ __forceinline__ void img_load(uint32_t (&v)[16], uint32_t tile, const Ctx& x) {
#pragma unroll
  for (int q = 0; q < 4; q++) lds128(tile + x.oo() * 16 + q * 512, v[4 * q], v[4 * q + 1], v[4 * q + 2], v[4 * q + 3]);
}
__device__ __forceinline__ void img_unpack(float* a, const uint32_t (&v)[16]) {
#pragma unroll
  for (int q = 0; q < 16; q++) { a[4 * (q & 7) + 2 * (q >> 3)] = lo16(v[q]); a[4 * (q & 7) + 2 * (q >> 3) + 1] = hi16(v[q]); }
}

template <int N>
__device__ __forceinline__ void stats_acc(const float* a, float (&t)[4]) {
#pragma unroll
  for (int i = 0; i < N; i++) { t[i & 2] += a[i]; t[(i & 2) + 1] = fmaf(a[i], a[i], t[(i & 2) + 1]); }
}
__device__ __forceinline__ void stats_send(float (&t)[4], int L, const Ctx& x) {
  const unsigned seq = seq4(get_tag<false>(x.sb), L);
#pragma unroll
  for (int q = 0; q < 4; q++) t[q] = qsum(t[q]);
  if (x.c == 0) st_pkt(&g_stats[x.m()][x.w][x.j()][x.warp * 8 + x.g], __float_as_uint(t[0]), __float_as_uint(t[1]), __float_as_uint(t[2]), (__float_as_uint(t[3]) & ~15u) | seq);
}
__device__ __forceinline__ void out_epilogue(const float (&acc)[64], uint4 (&r1)[4], uint4* g, int L, Ctx& x) {
  const uint32_t t0 = x.aslot(x.ra.s), t1 = x.aslot(x.ra.s + 1 == NA ? 0 : x.ra.s + 1);
  if (L == 3) {
#pragma unroll
    for (int p = 0; p < 8; p++) {
      stsm4(x.maddr(p < 4 ? t0 : t1, (p & 3) * 2), pack2(acc[8 * p], acc[8 * p + 1]), pack2(acc[8 * p + 2], acc[8 * p + 3]),
            pack2(acc[8 * p + 4], acc[8 * p + 5]), pack2(acc[8 * p + 6], acc[8 * p + 7]));
      if ((p & 3) == 3) { uint4 r[4]; __syncwarp(); rows_load(r, p < 4 ? t0 : t1, x); rows_store(r, g + (p >> 2) * 8, x); }
    }
  } else {
    auto pack16 = [&](uint4 (&r)[4], const float* a) {
#pragma unroll
      for (int q = 0; q < 4; q++) { const float* u = a + 16 * (q & 1) + (q & 2); r[q] = make_uint4(pack2(u[0], u[1]), pack2(u[4], u[5]), pack2(u[8], u[9]), pack2(u[12], u[13])); }
    };
    uint4 r0[4];
    pack16(r0, acc);
    img_store(r0, x.img(XBUF(L + 1), 0));
    publish(2, x);
    img_sts(r0, t0, x);
    sched_fence(x.sb);
    pack16(r1, acc + 32);
    img_sts(r1, t1, x);
    float t[4] = {0.f, 0.f, 0.f, 0.f}, u[4] = {0.f, 0.f, 0.f, 0.f};
    stats_acc<32>(acc, t); stats_acc<32>(acc + 32, u);
#pragma unroll
    for (int q = 0; q < 4; q++) t[q] += u[q];
    stats_send(t, L + 1, x);
    mbar_wait2(x.fullB(x.rb.s), x.rb.ph, x.fullB(x.rb.s + 1), x.rb.ph);
    fence_async_smem();
    asm volatile("bar.sync %0, %1;" ::"r"(L == 1 ? x.w + 1 : 3), "r"(L == 1 ? 128 : 256) : "memory");
  }
}

struct Stats { float rstd0, rstd1; };
__device__ __forceinline__ Stats load_stats(int half, const Ctx& x) {
  const float2 u = lds64f(x.sb + OFF_MR + half * 256 + (x.warp * 8 + x.g) * 8);
  return {u.x, u.y};
}

template <int NK>
__device__ __forceinline__ void hedgehog_scale(float* t, const Stats& st, const uint32_t* keep) {
#pragma unroll
  for (int q = 0; q < 16; q++) t[q] *= ((q & 2) ? st.rstd1 : st.rstd0) * LOG2E;
  float m[4];
#pragma unroll
  for (int q = 0; q < 4; q++) m[q] = fmaxf(fmaxf(fabsf(t[4 * q]), fabsf(t[4 * q + 1])), fmaxf(fabsf(t[4 * q + 2]), fabsf(t[4 * q + 3])));
  if (__builtin_expect(__any_sync(0xffffffffu, fmaxf(fmaxf(m[0], m[1]), fmaxf(m[2], m[3])) > 58.f), 0)) {
    float z[16 + NK];
#pragma unroll
    for (int q = 0; q < 16 + NK; q++) z[q] = q < 16 ? t[q & 15] : __uint_as_float(keep[q & 15]);
#pragma unroll 1
    for (int r = 0; r < 4; r += 2) {
      float hi = -INFINITY, lo = INFINITY;
#pragma unroll 1
      for (int i = 0; i < 16; i++) {
        const int k = (i & 6) * 2 + (i & 1) + r;
        const float v = z[k];
        if (i < 8) { hi = fmaxf(hi, v); lo = fminf(lo, v); }
        else z[k] = v - fminf(fmaxf(v, lo), hi);
        if (i == 7) {
#pragma unroll 1
          for (int d = 1; d <= 2; d++) { hi = fmaxf(hi, __shfl_xor_sync(0xffffffffu, hi, d)); lo = fminf(lo, __shfl_xor_sync(0xffffffffu, lo, d)); }
          const float mid = 0.5f * hi + 0.5f * lo;
          hi = fmaxf(hi - 58.f, mid); lo = fminf(lo + 58.f, mid);
        }
      }
    }
#pragma unroll
    for (int q = 0; q < 16; q++) t[q] = z[q];
  }
}
__device__ __forceinline__ void dual_exp(const float* t, uint32_t (&f)[18], int never) {
  float e[KSPLIT];
#pragma unroll
  for (int q = 0; q < KSPLIT; q++) e[q] = ex2(q < 16 ? t[q] : -t[q & 15]);
  while (never < 0) {
#pragma unroll
    for (int i = 0; i < KSPLIT; i += 4) asm volatile("ld.shared.v4.f32 {%0,%1,%2,%3}, [%4];" : "=f"(e[i]), "=f"(e[i + 1]), "=f"(e[i + 2]), "=f"(e[i + 3]) : "r"(never + i) : "memory");
    never += __float_as_int(e[0]);
  }
#pragma unroll
  for (int q = 0; q < KSPLIT; q += 2) f[q >> 1] = pack2(e[q], e[q + 1]);
#pragma unroll
  for (int q = KSPLIT; q < 32; q += 2) f[q >> 1] = q < 16 ? pack2(ex2(t[q]), ex2(t[q + 1])) : pack2(ex2(-t[q & 15]), ex2(-t[(q & 15) + 1]));
#pragma unroll
  for (int sg = 0; sg < 2; sg++) {
    const uint32_t* u = f + 8 * sg;
    const uint32_t a = add2(add2(u[0], u[2]), add2(u[4], u[6])), b = add2(add2(u[1], u[3]), add2(u[5], u[7]));
    f[16 + sg] = add2(__byte_perm(a, b, 0x5410), __byte_perm(a, b, 0x7632));
  }
}
__device__ __forceinline__ void dual_exp_rcp(const float* t, uint32_t (&f)[16]) {
#pragma unroll
  for (int q = 0; q < 8; q++) {
    const float a = ex2(t[2 * q]), b = ex2(t[2 * q + 1]), r = rcp(a * b);
    f[q] = pack2(a, b); f[8 + q] = pack2(r * b, r * a);
  }
}
__device__ __forceinline__ void cta_bar() { asm volatile("bar.sync 3, 256;" ::: "memory"); }

template <int N> __device__ __forceinline__ void pin(const uint32_t* v, uint32_t addr) {
#pragma unroll
  for (int i = 0; i < N; i += 4)
    asm volatile("{\n.reg .pred p;\nsetp.eq.u32 p, %0, 0;\n@p st.shared.v4.u32 [%0], {%1,%2,%3,%4};\n}" ::"r"(addr), "r"(v[i]), "r"(v[i + 1]), "r"(v[i + 2]), "r"(v[i + 3]) : "memory");
}

__device__ __forceinline__ void consumer(const Params& P, uint32_t sb, int w, unsigned vb) {
  Ctx x;
  x.w = w;
  x.ab = sb + OFF_A + w * 8192; x.da0 = desc_lo(SB + OFF_A, 16) + w * 512;
  x.lane = threadIdx.x & 31; x.warp = __shfl_sync(0xffffffffu, (threadIdx.x >> 5) & 3, 0); x.g = x.lane >> 2; x.c = x.lane & 3;
  x.goff = (cta_m(vb) * 128 + w) * 128 + cta_j(vb) * 16;
  asm volatile("" : "+r"(x.goff));
  x.elected = (threadIdx.x & 127) == 0;
  x.ra = {0, 0}; x.rb = {0, 0}; x.pa = x.pb = 0;
  {
    const uint32_t row = x.warp * 16 + (x.lane & 15);
    x.mrow = row * 128; x.mxor = row & 7; x.mhi = x.lane >> 4;
  }
  const int goff = x.goff;
  uint4 r1[4];
#pragma unroll
  for (int i = 0; i < 4; i++) r1[i] = make_uint4(0, 0, 0, 0);
  TSW(0);
  mbar_wait3(x.fullA(0), 0, x.fullB(0), 0);
#pragma unroll 1
  for (int L = 0; L < 4; L++) {
    float acc[64];
    constexpr uint32_t dcs = desc_lo(SB + OFF_CS, 0);
    if ((L & 1) == 0) {
    float kv[128];
    x.ha = L ? HA64 : HA128; x.k2 = L ? 32 : 4;
    gemm_issue<256, true, false>(kv, x, true); gemm_next<256>(x);
    {
      int i = 1;
      bool rel = true;
      float t[4] = {0.f, 0.f, 0.f, 0.f};
#pragma unroll 1
      for (int seg = 0; seg < 3; seg++) {
        const int end = seg < 2 ? (L == 0 ? 3 + 2 * (x.j() & 3) + seg : 2 + seg * 2) : 14 + L;
#pragma unroll 1
        while (true) {
          gemm_issue<256, false, false>(kv, x);
          if (++i == end) break;
          wgmma_wait<1>();
          if (rel) gemm_release<256>(x, true);
          rel = true;
          gemm_next<256>(x);
          if (i == 5) TSL_(8);
          if (i == 11) TSL_(10);
        }
        if (seg < 2 && L == 0) {
          float a[32];
          const uint32_t tile = x.aslot(x.ra.s);
          load_x32(a, tile, 0, x); load_x32(a + 16, tile, 4, x);
          stats_acc<32>(a, t);
          if (seg == 1) { mbar_wait(sb + BAR_EPOCH, 0); stats_send(t, 0, x); }
          fence_async_smem();
          wg_bar(w);
        }
        if (seg == 1 && L > 0) { img_store(r1, x.img(XBUF(L), 1)); publish(3, x); }
        wgmma_wait<1>();
        if (rel) gemm_release<256>(x, true);
        rel = true;
        gemm_next<256>(x);
        if (seg == 0 && L > 0) { wgmma_wait<0>(); gemm_release<256>(x, true); rel = false; }
      }
    }
      const Ring kt = x.ra;
      if (L == 0) adv<NA>(x.ra);
#pragma unroll 1
      for (int h = L; h < 2; h++) {
        float d[16];
        mbar_wait2(x.fullA(kt.s), kt.ph, sb + BAR_WPHI, 0);
        wgmma_fence();
#pragma unroll
        for (int q = 0; q < 2; q++) wgmma_ss_n32(d, x.da0 + kt.s * (SLOT / 16) + h * 4 + q * 2, desc_lo(SB + OFF_S + 4096, 512) + w * 256 + h * 128 + q * 64, q);
        wgmma_commit();
        gemm_issue<256, false, false>(kv, x);
        gemm_retire<256>(x, true);
        if (h) x.releaseA(kt.s);
        fence_regs(d);
        uint4* dst = &g_wf[1][x.j()][x.m()][w * 512 + (x.warp * 16 + x.g) * 8 + ((h * 4 + x.c) ^ x.g)];
        dst[0] = make_uint4(pack2(d[0], d[1]), pack2(d[4], d[5]), pack2(d[8], d[9]), pack2(d[12], d[13]));
        dst[64] = make_uint4(pack2(d[2], d[3]), pack2(d[6], d[7]), pack2(d[10], d[11]), pack2(d[14], d[15]));
      }
      const uint32_t dm = desc_lo(SB + OFF_MA, 0) + w * 64;
      mbar_wait2(sb + BAR_STAT, 0, sb + BAR_CS, 0);
      wgmma_fence();
      wgmma_r1_n256(kv, dm, dcs + 96, 1);
      wgmma_commit();
      const Stats st = load_stats(w, x);
      if (PW & 1) mbar_wait2(x.fullA(x.ra.s), x.ra.ph, x.fullB(x.rb.s), x.rb.ph);
      wgmma_wait<0>();
      fence_regs(kv);
      gemm_release<256>(x, true);
      TSL_(2);
      uint32_t P0[32], P1[32], PH[32];
#pragma unroll
      for (int t = 0; t < 16; t++) { P0[t] = pack2(kv[4 * t] * st.rstd0, kv[4 * t + 1] * st.rstd0); P1[t] = pack2(kv[4 * t + 2] * st.rstd1, kv[4 * t + 3] * st.rstd1); }
      pin<16>(P0, x.mrow + 16);
      {
#pragma unroll
        for (int q = 0; q < 4; q++) sts128((x.warp < 3 ? sb + OFF_T + w * 12288 + x.warp * 4096 : sb + OFF_S + 16384 + w * 2048) + x.lane * 16 + q * 512, P1[4 * q], P1[4 * q + 1], P1[4 * q + 2], P1[4 * q + 3]);
      }
      wgmma_fence();
      wgmma_r1_n128(acc, dm, dcs, 0);
      gemm_issue<128, false, false>(acc, x, PW & 1); gemm_next<128>(x);
      TSL_(3);
#pragma unroll
      for (int s = 0; s < 4; s++) {
#pragma unroll
        for (int t = 16 + 8 * (s & 1); t < 24 + 8 * (s & 1); t++) {
          if (s < 2) P1[t] = movm(pack2(kv[4 * t + 2] * st.rstd1, kv[4 * t + 3] * st.rstd1));
          else P0[t] = movm(pack2(kv[4 * t] * st.rstd0, kv[4 * t + 1] * st.rstd0));
        }
        if (s < 3) { gemm_issue<128, false, false>(acc, x); gemm_retire<128>(x, true); }
        if (s == 1) {
          if (x.warp < 3) {
#pragma unroll
            for (int q = 4; q < 8; q++) sts128(sb + OFF_T + w * 12288 + x.warp * 4096 + x.lane * 16 + q * 512, P1[4 * q], P1[4 * q + 1], P1[4 * q + 2], P1[4 * q + 3]);
          } else {
            uint4* dst = &g_halo[x.m()][x.j()][w][x.lane];
#pragma unroll
            for (int q = 0; q < 8; q++) dst[q * 32] = make_uint4(P1[4 * q], P1[4 * q + 1], P1[4 * q + 2], P1[4 * q + 3]);
          }
          publish(4, x);
          gemm_issue<128, false, false>(acc, x);
          gemm_retire<128>(x, true);
        }
      }
      TSL_(4);
      gemm_run<false>(acc, x, 10, 0);
      gemm_issue<128, false, false>(acc, x);
      {
        wg_bar(w);
        uint32_t tr = sb + OFF_T + w * 12288 + (x.warp - 1) * 4096;
        if (x.warp == 0) {
          tr = x.m() > 0 ? sb + OFF_S + 8192 + w * 4096 : tr + 4096;
          if (x.m() > 0) mbar_wait(sb + BAR_HALO, L >> 1);
        }
#pragma unroll
        for (int q = 0; q < 8; q++) lds128(tr + x.lane * 16 + q * 512, PH[4 * q], PH[4 * q + 1], PH[4 * q + 2], PH[4 * q + 3]);
      }
      gemm_retire<128>(x, false);
      gemm_end(acc, x);
      TSL_(5);
      const bool first = (x.m() == 0) && (x.warp == 0);
      const bool hi0 = 2 * x.c > x.g, hi1 = 2 * x.c + 1 > x.g;
      const uint32_t mhi = (hi0 ? 0xFFFFu : 0u) | (hi1 ? 0xFFFF0000u : 0u);
      const float sc0 = st.rstd0 * (0.17677669529663687f * LOG2E), sc1 = st.rstd1 * (0.17677669529663687f * LOG2E);
#pragma unroll
      for (int hp = 0; hp < 2; hp++) {
        const uint32_t tile = x.aslot(x.held(hp));
        uint32_t px[2], py[2];
        float s[2][3][4];
#pragma unroll
        for (int u = 0; u < 2; u++) {
#pragma unroll
          for (int q = 0; q < 12; q++) s[u][q >> 2][q & 3] = 0.f;
#pragma unroll
          for (int ks = 0; ks < 2; ks++) {
            const int t = 8 * hp + 4 * u + 2 * ks;
            const uint32_t a0 = pack2(acc[4 * t], acc[4 * t + 1]), a1 = pack2(acc[4 * t + 2], acc[4 * t + 3]);
            const uint32_t a2 = pack2(acc[4 * t + 4], acc[4 * t + 5]), a3 = pack2(acc[4 * t + 6], acc[4 * t + 7]);
            mma16816(s[u][0], a0, a1, a2, a3, PH[t], PH[t + 1]);
            mma16816(s[u][1], a0, a1, a2, a3, P0[t], P0[t + 1]);
            mma16816(s[u][2], a0, a1, a2, a3, P1[t], P1[t + 1]);
          }
        }
        float e[2][4], r[2][2];
#pragma unroll
        for (int u = 0; u < 2; u++) {
          e[u][0] = (hi0 ? s[u][0][0] : s[u][1][0]) * sc0; e[u][1] = (hi1 ? s[u][0][1] : s[u][1][1]) * sc0;
          e[u][2] = (hi0 ? s[u][1][2] : s[u][2][2]) * sc1; e[u][3] = (hi1 ? s[u][1][3] : s[u][2][3]) * sc1;
          if (first) { if (hi0) e[u][0] = -1e30f; if (hi1) e[u][1] = -1e30f; }
          r[u][0] = fmaxf(e[u][0], e[u][1]); r[u][1] = fmaxf(e[u][2], e[u][3]);
        }
#pragma unroll
        for (int d = 1; d <= 2; d++)
#pragma unroll
          for (int q = 0; q < 4; q++) r[q >> 1][q & 1] = fmaxf(r[q >> 1][q & 1], __shfl_xor_sync(0xffffffffu, r[q >> 1][q & 1], d));
#pragma unroll
        for (int u = 0; u < 2; u++) {
#pragma unroll
          for (int q = 0; q < 4; q++) e[u][q] = ex2(e[u][q] - r[u][q >> 1]);
          r[u][0] = e[u][0] + e[u][1]; r[u][1] = e[u][2] + e[u][3];
        }
#pragma unroll
        for (int d = 1; d <= 2; d++)
#pragma unroll
          for (int q = 0; q < 4; q++) r[q >> 1][q & 1] += __shfl_xor_sync(0xffffffffu, r[q >> 1][q & 1], d);
#pragma unroll
        for (int u = 0; u < 2; u++) {
          const float rx = rcp(r[u][0]), ry = rcp(r[u][1]);
          px[u] = pack2(e[u][0] * rx, e[u][1] * rx); py[u] = pack2(e[u][2] * ry, e[u][3] * ry);
        }
        uint32_t o[8][2];
        uint4 ro[4];
#pragma unroll
        for (int q = 0; q < 8; q++) {
          float d[4] = {0.f, 0.f, 0.f, 0.f};
          const int t = 16 + 8 * hp + q, u = q >> 2;
          mma16816(d, px[u] & mhi, 0u, px[u] & ~mhi, py[u] & mhi, PH[t], P0[t]);
          mma1688(d, 0u, py[u] & ~mhi, P1[t]);
          o[q][0] = pack2(d[0], d[1]); o[q][1] = pack2(d[2], d[3]);
        }
#pragma unroll
        for (int q = 0; q < 4; q++) ro[q] = make_uint4(o[4 * (q & 1)][q >> 1], o[4 * (q & 1) + 1][q >> 1], o[4 * (q & 1) + 2][q >> 1], o[4 * (q & 1) + 3][q >> 1]);
        img_store(ro, x.img(0, hp));
        publish(hp, x);
        uint32_t xr[16];
        if (L) img_load(xr, tile, x);
        else {
#pragma unroll
          for (int q = 0; q < 4; q++) {
            uint32_t v[4];
            ldsm4(x.maddr(tile, 2 * q), v);
            xr[2 * q] = v[0]; xr[8 + 2 * q] = v[1]; xr[2 * q + 1] = v[2]; xr[9 + 2 * q] = v[3];
          }
          __syncwarp();
        }
        img_sts(ro, tile, x);
        img_unpack(acc + 32 * hp, xr);
      }
    } else {
      float kv[128];
      float (&kv0)[64] = reinterpret_cast<float (&)[64]>(kv[0]);
      float (&kv1)[64] = reinterpret_cast<float (&)[64]>(kv[64]);
      auto mma8 = [&](uint32_t as, uint32_t bs, int i, bool fence) {
        const uint32_t da = desc_lo(SB + OFF_A, 16) + as * (SLOT / 16), db = desc_lo(SB + OFF_B, 8192) + bs * (SLOT / 16);
        if (fence) wgmma_fence();
#pragma unroll
        for (int k = 0; k < 4; k++) {
          wgmma_ss_n128(kv0, da + (k >> 1) * 32 + (k & 1) * 2, HA64, db + 128 * k, i + k);
          wgmma_ss_n128(kv1, da + 512 + (k >> 1) * 32 + (k & 1) * 2, HA64, db + 128 * k, i + k);
        }
        wgmma_commit();
      };
      constexpr uint32_t dm = desc_lo(SB + OFF_MB, 0);
      auto relB = [&](uint32_t s) { mbar_arrive_n(sb + BAR_EMPTYB + s * 8, 2); };
      auto skip = [&]() {
#pragma unroll
        for (int q = 0; q < 6 - NJ; q++) adv<NA>(x.ra);
        x.rb.s = w ? (2 + NJ) % 6 : 4;
        if (!w && NJ < 4) x.rb.ph ^= 1;
      };
      static_assert(NA == 5 && NB == 6, "ring arithmetic");
      mma8(x.ra.s, x.rb.s + w, 0, true);
      gemm_next<256>(x);
#pragma unroll 1
      for (int i = 1; i < NJ; i++) {
        mbar_wait2(x.fullA(x.ra.s), x.ra.ph, x.fullB(x.rb.s + w), x.rb.ph);
        mma8(x.ra.s, x.rb.s + w, 1, true);
        if (i == XR) { img_store(r1, x.img(XBUF(L), 1)); publish(3, x); }
        wgmma_wait<1>();
        if (x.elected && i != 2) { x.releaseA(x.pa); relB(x.pb + w); }
        gemm_next<256>(x);
        if (i == 1) { wgmma_wait<0>(); if (x.elected) { x.releaseA(x.pa); relB(x.pb + w); } }
      }
      if (w) {
        if (NJ > 2) { wgmma_wait<0>(); if (x.elected) { x.releaseA(x.pa); relB(x.pb + 1); } }
        if (XR >= NJ) { mbar_wait(x.fullA(x.ra.s), x.ra.ph); img_store(r1, x.img(XBUF(L), 1)); publish(3, x); }
        skip();
        asm volatile("bar.sync 7, 256;" ::: "memory");
      }
      TSL_(8);
      {
        const int t = lane_id() + 32 * x.warp;
        uint32_t mask = t < 2 ? ((w ? (t ? 0xFF3Fu : 0x3FFFu) : 0xFFFFu) >> (NJ - 1)) & (w || NJ == 2 ? ~1u : ~0u) : 0u, cnt = 1 + t;
        bool ready = false;
#pragma unroll 1
        for (int i = NJ; i < 16; i++) {
          if (!ready) mbar_wait2(x.fullA(x.ra.s), x.ra.ph, x.fullB(x.rb.s), x.rb.ph);
          mma8(x.ra.s, x.rb.s, 1, true);
          if (XR >= NJ && i == NJ && !w) { img_store(r1, x.img(XBUF(L), 1)); publish(3, x); }
          const uint32_t bar = sb + (t ? BAR_EMPTYB + x.pb * 8 : BAR_EMPTYA + x.pa * 8);
          gemm_next<128>(x);
          if (w && (i | 4) == 15) x.rb.s = 4;
          ready = mbar_probe2(x.fullA(x.ra.s), x.ra.ph, x.fullB(x.rb.s), x.rb.ph);
          wgmma_wait<1>();
          if (mask & 1) mbar_arrive_n(bar, cnt);
          mask >>= 1; cnt = 2;
          if (i == 8 && w) asm volatile("bar.arrive 9, 256;" ::: "memory");
          if (i == 9) TSL_(10);
        }
        mbar_wait2(sb + BAR_STAT, 1, sb + BAR_CS + 8, 0);
        wgmma_fence();
        wgmma_r1_n128(kv0, dm, dcs + 96 + 96 * w, 1);
        wgmma_r1_n128(kv1, dm + 64, dcs + 96 + 96 * w, 1);
        wgmma_commit();
        if (w == 0) asm volatile("bar.arrive 7, 256;" ::: "memory");
        wgmma_wait<1>();
        if (mask & 1) mbar_arrive_n(sb + (t ? BAR_EMPTYB + x.pb * 8 : BAR_EMPTYA + x.pa * 8), 2);
      }
      const Stats s0 = load_stats(0, x), s1 = load_stats(1, x), st = w ? s1 : s0;
      if (w == 0) skip();
      const uint32_t h0 = x.held(0), h1 = x.held(1);
      auto vreg = [&](int ks) { return ks < 6 ? OFF_A + (ks < 3 ? h0 * SLOT : h1 * SLOT - 15360) + ks * 5120 : OFF_S + 2048 + ks * 5120; };
      uint32_t tV[2], uu[4];
#pragma unroll
      for (int hf = 0; hf < 2; hf++) {
        tV[hf] = sb + vreg(4 * hf + x.warp) + ((x.lane >> 3) & 1) * 2560 + (x.lane & 7) * 16 + x.mhi * 128;
        const float i0 = rcp(hf ? s1.rstd0 : s0.rstd0), i1 = rcp(hf ? s1.rstd1 : s0.rstd1);
        const uint32_t h = pack2(i0, i1);
        uu[2 * hf] = pack2(lo16(h), i0 - lo16(h)); uu[2 * hf + 1] = pack2(hi16(h), i1 - hi16(h));
        asm volatile("" : "+r"(tV[hf]), "+r"(uu[2 * hf]), "+r"(uu[2 * hf + 1])::"memory");
      }
      wgmma_wait<0>();
      fence_regs(kv);
      TSL_(2);
      if (w == 0) {
        uint32_t f[2][18], ad[4];
#pragma unroll
        for (int q = 0; q < 18; q++) f[1][q] = 0u;
#pragma unroll
        for (int q = 0; q < 4; q++) ad[q] = x.maddr(sb + OFF_S, 2 * q);
        auto norm = [&](int un) {
          uint32_t* u = f[un & 1];
          const Stats& sn = (un & 2) ? s1 : s0;
#pragma unroll
          for (int sg = 0; sg < 2; sg++) {
            uint32_t v = u[16 + sg];
            v = add2(v, __shfl_xor_sync(0xffffffffu, v, 1)); v = add2(v, __shfl_xor_sync(0xffffffffu, v, 2));
            const float a = rcp(lo16(v)) * sn.rstd0, b = rcp(hi16(v)) * sn.rstd1;
            const uint32_t r0 = pack2(a, a), r1_ = pack2(b, b);
#pragma unroll
            for (int q = 8 * sg; q < 8 * sg + 8; q++) u[q] = mul2(u[q], (q & 1) ? r1_ : r0);
#pragma unroll
            for (int q = 2 * sg; q < 2 * sg + 2; q++) stsm4(ad[q] + (un & 1) * SLOT + (un >> 1) * 8192, u[4 * q], u[4 * q + 1], u[4 * q + 2], u[4 * q + 3]);
          }
        };
        auto unit = [&](int un) { return kv + ((un >> 1) & 1) * 64 + (un & 1) * 16 + (un >> 2) * 32; };
        hedgehog_scale<0>(kv, s0, nullptr);
#pragma unroll 1
        for (int it = 0;; it++) {
#pragma unroll
          for (int un = 0; un < 4; un++) {
            if (un == 1) {
              if (it) asm volatile("bar.sync 9, 256;" ::: "memory");
#pragma unroll
              for (int q = 0; q < 4; q++) ad[q] -= it * (OFF_S - OFF_B - 2 * SLOT);
            }
            norm((un + 3) & 3);
            dual_exp(unit(un), f[un & 1], x.goff);
            hedgehog_scale<KEEP>(unit(un + 1), ((un + 1) & 2) ? s1 : s0, f[(un + 1) & 1]);
          }
          if (it) break;
#pragma unroll
          for (int q = 0; q < 32; q++) {
            asm volatile("mov.b32 %0, %1;" : "=f"(kv[q]) : "f"(kv[q + 32]));
            asm volatile("mov.b32 %0, %1;" : "=f"(kv[q + 64]) : "f"(kv[q + 96]));
            if (q < 16) kv[32 + q] = 0.f;
          }
        }
        norm(3);
        TSL_(3);
      } else {
        wg_bar(w);
#pragma unroll
        for (int hf = 0; hf < 2; hf++) {
          stsm4(tV[hf] + 512 + x.mhi * 512, uu[2 * hf], uu[2 * hf + 1], uu[2 * hf], uu[2 * hf + 1]);
          stsm4(tV[hf] + 1792 + x.mhi * 512, uu[2 * hf], uu[2 * hf + 1], uu[2 * hf], uu[2 * hf + 1]);
#pragma unroll
          for (int q = 0; q < 8; q++) {
            const float* u = kv + 64 * hf + 8 * q;
            stsm4(tV[hf] + (q >> 1) * 640 + (q & 1) * 256, pack2(u[0], u[1]), pack2(u[2], u[3]), pack2(u[4], u[5]), pack2(u[6], u[7]));
          }
        }
        TSL_(3);
      }
      {
        float d[2][20];
        uint4* dst = &g_kvpart[x.j()][w * 4 + x.warp][0][x.m() * 32 + x.lane];
        unsigned* dz = reinterpret_cast<unsigned*>(&g_kvpart[x.j()][w * 4 + x.warp][x.c & 1][512]) + x.m() * 8 + x.g;
        asm volatile("" : "+l"(dst), "+l"(dz)::"memory");
        fence_async_smem();
        cta_bar();
        TSL_(11);
        uint32_t pk[9];
        auto prep = [&](float (&u)[20]) {
          fence_regs(u);
#pragma unroll
          for (int q = 0; q < 8; q++) pk[q] = pack2(u[((q >> 1) & 2) + 4 * (q & 3)], u[((q >> 1) & 2) + 4 * (q & 3) + 1]);
          pk[8] = __float_as_uint((x.c & 1) ? u[18] + u[19] : u[16] + u[17]);
#pragma unroll
          for (int q = 0; q < 9; q += 4) pk[q] = (pk[q] & ~1u) | (L == 1);
        };
        auto send = [&](int hp) {
          st_v4(dst + hp * 16 * 544, pk[0], pk[1], pk[2], pk[3]); st_v4(dst + (hp * 16 + 1) * 544, pk[4], pk[5], pk[6], pk[7]);
          st_flag(dz + hp * 16 * 544 * 4, pk[8]);
        };
        wgmma_fence();
#pragma unroll
        for (int q = 0; q < 17; q++) {
          if (q < 16) wgmma_ss_n40_tt(d[q >> 3], desc_lo(SB + (q < 8 ? OFF_S : OFF_B + 2 * SLOT), 1024) + w * (SLOT / 16) + 128 * (q & 7), desc_lo(SB + vreg(q & 7), 2560) + (w + (q >> 3) * 2) * 40, q & 7);
          else wgmma_r1_n128(acc, dm + w * 64, dcs, 0);
          if (q == 7 || q == KVS || q == 16) wgmma_commit();
          if (q == KVS) { wgmma_wait<1>(); prep(d[0]); send(0); mbar_wait2(x.fullA(x.ra.s), x.ra.ph, x.fullB(x.rb.s), x.rb.ph); wgmma_fence(); }
        }
        gemm_issue<128, false>(acc, x, true); gemm_next<128>(x);
        wgmma_wait<1>();
        x.releaseA(h0); x.releaseA(h1); x.releaseB(2); x.releaseB(3);
        if (x.lane == 0) mbar_arrive(sb + BAR_SIGT);
        prep(d[1]);
        TSL_(4);
#pragma unroll 1
        for (int seg = 0; seg < 2; seg++) {
          const int n0 = w ? PS1 : PS0;
          gemm_run(acc, x, seg ? 15 - n0 : n0, seg, seg ? L : 0);
          if (seg == 0) send(1);
        }
      }
      gemm_end(acc, x);
      TSL_(5);
      {
        float dp[2][20], dn[2][20];
        uint32_t f[4][16];
        auto mma = [&](int h) {
          if (!(h & 1)) mbar_wait(sb + BAR_KV + h * 4, L >> 1);
          if (h == 0) TSL_(9);
          const uint32_t db = desc_lo(SB + OFF_S + h * 5120, 128);
          const uint32_t (&a)[16] = f[h];
          wgmma_fence();
          wgmma_rs_n40(dp[h & 1], a[0], a[1], a[2], a[3], db, 0);
          wgmma_rs_n40(dn[h & 1], a[8], a[9], a[10], a[11], db + 160, 0);
          wgmma_rs_n40(dp[h & 1], a[4], a[5], a[6], a[7], db + 80, 1);
          wgmma_rs_n40(dn[h & 1], a[12], a[13], a[14], a[15], db + 240, 1);
          wgmma_commit();
        };
        uint32_t xr[16];
        auto fin = [&](int h) {
          const uint32_t tile = x.aslot(x.held(h >> 1));
          if (!(h & 1)) img_load(xr, tile, x);
          float (&u)[20] = dp[h & 1];
          float (&v)[20] = dn[h & 1];
          fence_regs(u); fence_regs(v);
#pragma unroll
          for (int r = 0; r < 2; r++) {
            float cc = u[17 + 2 * r] * rcp(v[17 + 2 * r]);
            const float aa = rcp(fmaf(v[16 + 2 * r], cc, fmaf(u[17 + 2 * r], 1e-6f, u[16 + 2 * r])));
            cc *= aa;
            uint32_t o[4];
#pragma unroll
            for (int t = 0; t < 4; t++) o[t] = pack2(fmaf(u[4 * t + 2 * r], aa, v[4 * t + 2 * r] * cc), fmaf(u[4 * t + 2 * r + 1], aa, v[4 * t + 2 * r + 1] * cc));
            x.img(0, h >> 1)[r * 64 + (h & 1) * 32] = make_uint4(o[0], o[1], o[2], o[3]);
            sts128(tile + r * 1024 + (h & 1) * 512 + x.oo() * 16, o[0], o[1], o[2], o[3]);
          }
          if (h & 1) { publish(h >> 1, x); img_unpack(acc + 16 * (h - 1), xr); }
        };
        auto scale = [&](int h) { hedgehog_scale<0>(acc + 16 * h, st, nullptr); };
        auto ex = [&](int h) { dual_exp_rcp(acc + 16 * h, f[h]); };
        scale(0);
        ex(0); scale(1); mma(0);
        ex(1); wgmma_wait<0>(); fin(0); scale(2); mma(1);
        ex(2); wgmma_wait<0>(); fin(1); scale(3); mma(2);
        ex(3); wgmma_wait<0>(); fin(2); mma(3);
        wgmma_wait<0>(); fin(3);
      }
    }
    if (PW & 2) { mbar_wait(x.fullB(x.rb.s), x.rb.ph); fence_regs(acc); }
    fence_async_smem();
    wg_bar(w);
    TSL_(6);
    rewind2<NA>(x.ra);
    gemm_issue<128, false>(acc, x, PW & 2); gemm_next<128>(x);
#pragma unroll 1
    for (int seg = L >= TSL ? 0 : 1; seg < 2; seg++) {
      gemm_run(acc, x, L >= TSL ? (seg ? TSK : 15 - TSK) : 15, seg);
      if (L >= TSL) {
        if (seg == 0 && w == 1) asm volatile("bar.sync 6, 256;" ::: "memory");
        if (seg == 1 && w == 0) asm volatile("bar.arrive 6, 256;" ::: "memory");
      }
    }
    gemm_end(acc, x);
    TSL_(7);
    rewind2<NA>(x.ra);
    out_epilogue(acc, r1, P.out + goff, L, x);
    TSL_(13);
  }
}

typedef unsigned long long u64;
template <class T> __device__ __forceinline__ T* early(T* p) { return (T*)__shfl_xor_sync(0xffffffffu, (u64)p, 1); }
__device__ __forceinline__ void pause(uint32_t GAP) {
  if (GAP) { uint32_t t0, t; asm volatile("mov.u32 %0, %%clock;" : "=r"(t0)); do { asm volatile("mov.u32 %0, %%clock;" : "=r"(t)); } while (t - t0 < GAP); }
}
__device__ __forceinline__ u64 order_table(int kind, int j) {
  const int i = threadIdx.x & 15;
  const unsigned v = (unsigned)(kind == 2 ? q_order(i, j) : kv_order(i, j, kind)) << (4 * (i & 7));
  return (u64)__reduce_or_sync(0xffffffffu, i < 8 ? 0u : v) << 32 | __reduce_or_sync(0xffffffffu, i < 8 ? v : 0u);
}

__device__ __forceinline__ void b_producer(const Params& P, uint32_t sb, unsigned vb) {
  const int j = cta_j(vb);
  const u64 t0 = order_table(0, j), t1 = order_table(1, j), t2 = order_table(2, j);
  Ring r = {PRE_B % NB, PRE_B < NB};
#pragma unroll 1
  for (int sg = 0; sg < 20; sg++) {
    const int L = sg / 5, p = sg - 5 * L, wt = L & 1;
    int n = p >= 3 ? 16 : (wt ? (p ? 16 - NJ : 2 * NJ) : (p ? 0 : (L ? 32 : 32 - PRE_B)));
    u64 tab = p == 3 ? t2 : (sg == 0 ? t0 >> (2 * PRE_B) : (p == 1 || p == 2 ? t1 >> (4 * NJ) : t1));
    const CUtensorMap* tm = p == 4 ? &P.mwo[wt] : &P.mw[wt ? 1 : L];
    const uint4* img = &g_wf[p != 3][j][0][0];
    int col = (p >= 3 ? 0 : (p == 2 ? 2048 : 1024)) + 128 * j;
    const int flip = p == 0 ? 3072 : 0;
    const bool fold = wt && p != 4;
    if (sg == 5 || sg == 8) { mbar_wait(sb + (sg == 5 ? BAR_WPHI : BAR_CS + 8), sg == 5); fence_async_global(); }
    if (DEFER && p == 4 && ((DEFL >> wt) & 1)) {
      Ring q = r;
      for (int u = 0; u < DEFER; u++) adv<NB>(q);
      mbar_wait(sb + BAR_EMPTYB + q.s * 8, q.ph);
    }
#pragma unroll 1
    for (; n > 0; n--) {
      const int kb = (int)tab & 15;
      mbar_wait(sb + BAR_EMPTYB + r.s * 8, r.ph);
      if (elect()) {
        mbar_expect_tx(sb + BAR_FULLB + r.s * 8, SLOT);
        if (fold && col < 2048) bulk_load(sb + OFF_B + r.s * SLOT, img + kb * 1024, SLOT, sb + BAR_FULLB + r.s * 8);
        else tma_load_w(sb + OFF_B + r.s * SLOT, tm, sb + BAR_FULLB + r.s * 8, col, kb);
      }
      adv<NB>(r);
      if (p == 2 && (n | 4) == 5) r.s = 4;
      col ^= flip;
      if (!(col & flip & 2048)) tab >>= 4;
    }
  }
}

__device__ __forceinline__ void a_loader(const Params& P, uint32_t sb, unsigned vb) {
  const int j = cta_j(vb), m = cta_m(vb);
  const u64 t1 = order_table(1, j), t2 = order_table(2, j);
  Ring r = {PRE_A % NA, PRE_A < NA};
  {
    u64 tab = order_table(0, j) >> (4 * PRE_A);
#pragma unroll 1
    for (int i = PRE_A; i < 33; i++) {
      if (i == 17) tab = t2;
      mbar_wait(sb + BAR_EMPTYA + r.s * 8, r.ph);
      if (elect()) {
        mbar_expect_tx(sb + BAR_FULLA + r.s * 8, SLOT);
        if (i != 14) tma_load_3d(sb + OFF_A + r.s * SLOT, &P.mx, sb + BAR_FULLA + r.s * 8, ((int)tab & 15) * 64, m * 64, 0);
        else {
          tma_load_w(sb + OFF_A + r.s * SLOT, &P.mw[1], sb + BAR_FULLA + r.s * 8, 1024 + 128 * j, m);
          mbar_expect_tx(sb + BAR_WPHI, 8192); tma_load_2d(sb + OFF_S + 4096, &P.mwphi, sb + BAR_WPHI, 0, 128 * j);
        }
        if (i == PF0 || i == PF1 || i == PF2)
          tma_prefetch_w(i == PF0 ? &P.mw[1] : &P.mwo[i == PF2], (i == PF0 ? 1024 : 0) + 128 * j, m);
      }
      adv<NA>(r);
      if (i != 14) tab >>= 4;
    }
  }
  const unsigned tag = get_tag(sb);
  unsigned seen = 0;
#pragma unroll 1
  for (int sg = 0; sg < 27; sg++) {
    const int L = sg >> 3, p = sg & 7, q = p >= 3 ? p - 3 : p;
    if (p == 0 && (L & 1)) {
#pragma unroll 1
      for (int h = 0; h < 2; h++) {
        poll_flags(&g_kvfflag[L >> 1][j][h][0], 8, 0xFFu, tag);
        if (elect()) { mbar_expect_tx(sb + BAR_KV + h * 8, 10240); bulk_load(sb + OFF_S + h * 10240, &g_kvfin[j][8 * h][0], 10240, sb + BAR_KV + h * 8); }
      }
      TS(4, 14 + L);
    }
    int n = q == 0 ? 4 : (q == 1 ? 3 : (q == 2 ? 7 : (q == 3 ? ((L & 1) ? 0 : 16 - NJ) : 16)));
    u64 tab = q == 4 ? t2 : t1 >> (q == 0 ? 8 : (q == 1 ? 24 : (q == 2 ? 36 : 4 * NJ)));
    const uint4* img = &g_img[p >= 3 ? XBUF(L + 1) : 0][m][0][0];
    const uint32_t gap = p == 0 ? G0 : (p == 3 ? G3 : (q < 3 ? G1 : G4));
    bool poll = q == 0 || q == 2 || (q == 1 && seen != 0xFFFFFFFFu);
#pragma unroll 1
    for (; n > 0; n--) {
      const uint4* src = img + ((int)tab & 15) * 1024;
      src = early(src);
      mbar_wait(sb + BAR_EMPTYA + r.s * 8, r.ph);
      if (elect()) mbar_expect_tx(sb + BAR_FULLA + r.s * 8, SLOT);
      if (poll) {
        const int lane = threadIdx.x & 31, nn = p >= 3 ? PNX : PNO;
        const unsigned* f = (p >= 3 ? &g_xflag[L + 1][0][m][0] : &g_oflag[L][0][m][0]) + (q == 2 ? 512 : 0) + (lane & 7);
        if (q == 0 || (PN2 && q == 2)) f += (((lane >> 3) & (nn - 1)) - (m & (nn - 1))) * 32;
        const unsigned need = q == 0 ? 0x0F0F0F0Fu << (~j & 4) : 0xFFFFFFFFu;
        if (q == 0) mbar_wait(sb + BAR_SIGP + (p ? 16 : 0), L & 1);
        int it = 0;
        do { seen = __ballot_sync(0xffffffffu, ld_flag(f) == tag); if (++it > (1 << 22)) __trap(); } while ((seen & need) != need);
        if (q == 0) TS(2, p == 0 ? 5 + L * 8 : 9 + L * 8);
        poll = false;
      }
      if (elect()) bulk_load(sb + OFF_A + r.s * SLOT, src, SLOT, sb + BAR_FULLA + r.s * 8);
      adv<NA>(r);
      tab >>= 4;
      pause(gap);
    }
  }
}

__device__ __forceinline__ uint2 sum_packets(float (&a)[8], uint32_t addr, int n) {
  uint2 ok = make_uint2(~0u, 0u);
#pragma unroll 1
  for (int b = 0; b < n; b += KB) {
    uint4 v[KB];
#pragma unroll
    for (int u = 0; u < KB; u++) lds128(addr + (b + u) * 512, v[u].x, v[u].y, v[u].z, v[u].w);
#pragma unroll
    for (int u = 0; u < KB; u++) {
      ok.x &= v[u].x; ok.y |= v[u].x;
      a[0] += lo16(v[u].x); a[1] += hi16(v[u].x); a[2] += lo16(v[u].y); a[3] += hi16(v[u].y);
      a[4] += lo16(v[u].z); a[5] += hi16(v[u].z); a[6] += lo16(v[u].w); a[7] += hi16(v[u].w);
    }
  }
  return ok;
}
__device__ __forceinline__ void helper_bar() { asm volatile("bar.sync 4, 64;" ::: "memory"); }
__device__ __forceinline__ void helper(const Params& P, uint32_t sb, int w, unsigned vb) {
  const int j = cta_j(vb), m = cta_m(vb);
  if (w == 0) {
    if (elect()) {
      const unsigned t = atomicAdd(&g_ctr, 1u) / NCTA + 1u;
      asm volatile("st.shared.u32 [%0], %1;" ::"r"(sb + OFF_EPOCH), "r"(t) : "memory");
      mbar_arrive(sb + BAR_EPOCH);
    }
  }
  const unsigned tag = get_tag(sb);
  mbar_wait(sb + BAR_FULLB + 24, 0);
  const uint32_t stg = sb + OFF_T + w * 12288, stb = sb + BAR_STG + w * 24;
  Ring rs = {0, 0};
  auto cs_image = [&](int L) {
      const int lane = lane_id();
      poll_flags(&g_csflag[L][j][0], 16, L ? CSNEED : 0xFFFu, tag);
#pragma unroll
      for (int p = 0; p < 3; p++) {
        const uint4 u = ldcg4(&g_cs[L][0][p * 1024 + 128 * j + lane * 4]), v = ldcg4(&g_cs[L][1][p * 1024 + 128 * j + lane * 4]);
        const float c0 = __uint_as_float(u.x) + __uint_as_float(v.x), c1 = __uint_as_float(u.y) + __uint_as_float(v.y);
        const float c2 = __uint_as_float(u.z) + __uint_as_float(v.z), c3 = __uint_as_float(u.w) + __uint_as_float(v.w);
        const uint32_t h0 = pack2(c0, c1), h1 = pack2(c2, c3), dst = sb + OFF_CS + (p * 16 + (lane >> 1)) * 96 + L * 48 + (lane & 1) * 8;
        sts64(dst, h0, h1); sts64(dst + 16, pack2(c0 - lo16(h0), c1 - hi16(h0)), pack2(c2 - lo16(h1), c3 - hi16(h1))); sts64(dst + 32, h0, h1);
        if (L == 0) { sts64(dst + 48, 0u, 0u); sts64(dst + 64, 0u, 0u); sts64(dst + 80, 0u, 0u); }
      }
      if (L == 0 && lane < 4) sts64(sb + OFF_CS + 4608 + lane * 8, 0u, 0u);
      fence_async_smem();
      __syncwarp();
      if (elect()) mbar_arrive(sb + BAR_CS + L * 8);
      TS(4, 2 + L * 2);
  };
#pragma unroll 1
  for (int L = 0; L < 4; L++) {
    const int lane = lane_id();
    if (L == 0) {
      {
        const int wt = m >= 12, col = ((0x2021 >> (m & 12)) & 3) * 1024 + 128 * j + (m & 3) * 32;
        const CUtensorMap* tm = &P.mcs[wt];
        if (D2 && wt) __nanosleep(D2);
        constexpr int nb = 8;
        float a[8] = {0.f, 0.f, 0.f, 0.f, 0.f, 0.f, 0.f, 0.f};
#pragma unroll 1
        for (int b = -3; b < nb; b++) {
          if (b >= 0) {
            mbar_wait(stb + rs.s * 8, rs.ph);
            sum_packets(a, stg + rs.s * 4096 + lane * 16, 8);
            fence_async_smem();
            __syncwarp();
          }
          const uint32_t sl = b < 0 ? (rs.s + b + 3) % 3 : rs.s;
          if (b + 3 < nb && elect()) { mbar_expect_tx(stb + sl * 8, 4096); tma_load_2d(stg + sl * 4096, tm, stb + sl * 8, col, (w * (16 - nb) + b + 3) * 64); }
          if (b >= 0) adv<3>(rs);
        }
#pragma unroll
        for (int u = 0; u < 8; u++) {
          a[u] += __shfl_xor_sync(0xffffffffu, a[u], 4); a[u] += __shfl_xor_sync(0xffffffffu, a[u], 8); a[u] += __shfl_xor_sync(0xffffffffu, a[u], 16);
        }
        if (lane < 4) {
          float4* dst = reinterpret_cast<float4*>(&g_cs[wt][w][col + lane * 8]);
          dst[0] = make_float4(a[0], a[1], a[2], a[3]); dst[1] = make_float4(a[4], a[5], a[6], a[7]);
        }
        helper_bar();
        if (w == 0 && elect()) { fence_gpu(); st_flag(&g_csflag[wt][j][m], tag); }
      }
      if (w == 0) TS(4, 1 + L * 2);
    }
    if (w == 1) {
      if (L > 0) mbar_wait(sb + BAR_SIGP + ((L & STG0) ? 16 : 24), (L - 1) & 1);
#pragma unroll 1
      for (int p = 0; p < 2; p++) {
        uint4 v[8];
        for (int it = 0;; it++) {
          bool ok = true;
#pragma unroll
          for (int t = 0; t < 8; t++) v[t] = ld_pkt(&g_stats[m][p][t][lane]);
#pragma unroll
          for (int t = 0; t < 8; t++) ok = ok && (v[t].w & 15u) == seq4(tag, L);
          if (__all_sync(0xffffffffu, ok)) break;
          __nanosleep(200);
          if (it > (1 << 20)) __trap();
        }
        float s0 = 0.f, q0 = 0.f, s1 = 0.f, q1 = 0.f;
#pragma unroll
        for (int t = 0; t < 8; t++) { s0 += __uint_as_float(v[t].x); q0 += __uint_as_float(v[t].y); s1 += __uint_as_float(v[t].z); q1 += __uint_as_float(v[t].w & ~15u); }
        s0 *= (1.f / 1024); s1 *= (1.f / 1024);
        sts64(sb + OFF_MR + p * 256 + lane * 8, __float_as_uint(rsqrtf(fmaxf(q0 * (1.f / 1024) - s0 * s0, 0.f) + 1e-5f)),
              __float_as_uint(rsqrtf(fmaxf(q1 * (1.f / 1024) - s1 * s1, 0.f) + 1e-5f)));
#pragma unroll
        for (int r = 0; r < 2; r++) {
          const float v = -0.5f * (r ? s1 : s0);
          const uint32_t hh = pack2(v, v), hl = pack2(v, v - lo16(hh));
          const bool b = L & 1;
          sts128(sb + (b ? OFF_MB : OFF_MA) + p * 1024 + (lane >> 3) * 256 + r * 128 + (lane & 7) * 16, b ? 0u : hh, b ? hh << 16 : hl >> 16, b ? hl : 0u, 0u);
        }
      }
      fence_async_smem();
      __syncwarp();
      if (elect()) {
        mbar_arrive(sb + BAR_STAT);
      }
      TS(2, 0 + L * 8);
    }
    if (L == w) cs_image(L);
    if (L & 1) {
      const uint32_t flip = L == 1 ? 0u : 1u;
      mbar_wait(sb + BAR_SIGT, 1);
      {
        int it = 0;
        if (PSL) __nanosleep(m < 8 ? PSL : PSL + 600);
        while (!__all_sync(0xffffffffu, (ld_flag(reinterpret_cast<const unsigned*>(&g_kvpart[j][m][w][512]) + (lane & 15) * 8) ^ flip) & 1u)) { if (PSL) __nanosleep(100); if (++it > (1 << 22)) __trap(); }
        fence_async_global();
      }
      if (w == 0) TS(4, 6 + L * 2);
      for (int it = 0;; it++) {
        if (elect()) { mbar_expect_tx(stb + rs.s * 8, 8704); bulk_load(stg, &g_kvpart[j][m][w][0], 8704, stb + rs.s * 8); }
        mbar_wait(stb + rs.s * 8, rs.ph);
        adv<3>(rs);
        float a[8] = {0.f, 0.f, 0.f, 0.f, 0.f, 0.f, 0.f, 0.f};
        float z = 0.f;
        uint32_t ok = 1u;
#pragma unroll
        for (int u = 0; u < 4; u++) { const float v = lds32f(stg + 8192 + u * 128 + (lane & 3) * 32 + (lane >> 2) * 4); z += v; ok &= __float_as_uint(v) ^ flip; }
        const uint2 tg = sum_packets(a, stg + lane * 16, 16);
        ok &= flip ? ~tg.y : tg.x;
        uint4* img = &g_kvfin[j][m][w * 8 + (lane >> 2)];
        img[(lane & 3) * 16] = make_uint4(pack2(a[0], a[1]), pack2(a[2], a[3]), pack2(a[4], a[5]), pack2(a[6], a[7]));
        reinterpret_cast<uint32_t*>(img + 64)[lane & 3] = pack2(qsum(z), 1.f);
        if (__all_sync(0xffffffffu, ok & 1u)) break;
        fence_async_smem();
        if (it > (1 << 16)) __trap();
      }
      if (w == 0) TS(4, 7 + L * 2);
      helper_bar();
      if (w == 1 && elect()) { fence_gpu(); st_flag(&g_kvfflag[L >> 1][j][m >> 3][m & 7], tag); }
      if (w == 1 && L == 1) TS(4, 20);
    } else {
      mbar_wait(sb + BAR_SIGT, 0);
      if (w == 0) {
        if (elect()) { fence_gpu(); st_flag(&g_hflag[L >> 1][m][j][0], tag); st_flag(&g_kflag[j][m], tag); }
        if (L == 0) {
          __nanosleep(KSL);
          poll_flags(&g_kflag[j][0], 16, 0xFFFFu, tag);
          if (elect()) mbar_arrive(sb + BAR_WPHI);
        }
      } else if (m > 0) {
        poll_flags(&g_hflag[L >> 1][m - 1][j][0], 1, 1u, tag);
        if (elect()) { mbar_expect_tx(sb + BAR_HALO, 8192); bulk_load(sb + OFF_S + 8192, &g_halo[m - 1][j][0][0], 8192, sb + BAR_HALO); }
        TS(2, 2 + L * 8);
      }
    }
#pragma unroll 1
    for (int e = 0; e < (L < 3 && w == 0 ? 3 : 1); e++) {
      unsigned* flag = e == 0 ? &g_oflag[L][w][m][j] : &g_xflag[L + 1][e - 1][m][j];
      flag = early(flag);
      mbar_wait(sb + BAR_SIGP + (e == 0 ? w : e + 1) * 8, L & 1);
      TS(e == 2 ? 3 : 2 + w, (e ? 6 : 3) + L * 8);
      if (elect()) { fence_async_global(); fence_gpu(); st_flag(flag, tag); }
      TS(e == 2 ? 3 : 2 + w, (e ? 7 : 4) + L * 8);
    }
  }
}

__device__ __forceinline__ void spare(const Params& P, uint32_t sb, int id) {
  const int tid = threadIdx.x & 127, w = __shfl_sync(0xffffffffu, threadIdx.x >> 7, 0), lane = tid & 31, j = 2 * id + w;
  const uint32_t ring = w * 6 * SLOT, wp = 12 * SLOT + w * 8192, bar = sb + 13 * SLOT + w * 64;
  auto part = [&](int t) { return (t >> 4) ^ w; };
  auto load = [&](int t, uint32_t sl) {
    mbar_expect_tx(bar + sl * 8, t == 0 ? SLOT + 8192 : SLOT);
    tma_load_w(sb + ring + sl * SLOT, &P.mw[1], bar + sl * 8, part(t) * 1024 + 128 * j, t & 15);
  };
  if (tid == 0) {
    if (w == 2) sts32(sb + OFF_EPOCH, atomicAdd(&g_ctr, 1u) / NCTA + 1u);
    else {
      __nanosleep(D3);
#pragma unroll 1
      for (int t = 0; t < 5; t++) {
        mbar_init(bar + t * 8, 1);
        asm volatile("fence.mbarrier_init.release.cluster;" ::: "memory");
        load(t, t);
      }
      tma_load_2d(sb + wp, &P.mwphi, bar, 0, 128 * j);
    }
  }
  __syncthreads();
  const unsigned tag = get_tag<false>(sb);
  if (w == 2) {
    int it = 0;
    while ((int)(ld_flag(&g_ctr) - tag * NCTA) < 0) { if (++it > (1 << 22)) __trap(); }
    return;
  }
  Ring r = {4, 1};
  float d[64] = {}, cs[32] = {};
  auto fold = [&]() {
    mbar_wait(bar + r.s * 8, r.ph);
    wgmma_fence();
#pragma unroll
    for (int q = 0; q < 8; q++)
      wgmma_ss_n32(reinterpret_cast<float (&)[16]>(d[16 * (q >> 1)]), desc_lo(SB + ring + r.s * SLOT, 16) + (q >> 2) * 512 + (q & 3) * 2, desc_lo(SB + wp, 512) + q * 64, q & 1);
    wgmma_commit();
  };
  const int row = (tid >> 5) * 16 + (lane >> 2);
#pragma unroll 1
  for (int t = -1; t < 32; t++) {
    uint32_t f[32];
#pragma unroll
    for (int i = 0; i < 32; i++) { f[i] = pack2(d[2 * i], d[2 * i + 1]); cs[i & 30] += d[2 * i]; cs[i | 1] += d[2 * i + 1]; }
    wg_bar(w);
    if (tid == 0 && t >= 0 && t < 27) load(t + 5, r.s);
    __syncwarp();
    if (t < 31) adv<5>(r);
    fold();
    if (part(t) == 0 && t >= 0) {
#pragma unroll
      for (int q = 0; q < 8; q++)
        g_wf[0][j][t & 15][(q >> 2) * 512 + (row + 8 * (q & 1)) * 8 + (((q & 2) * 2 + (lane & 3)) ^ (lane >> 2))] =
            make_uint4(f[4 * (q & 6) + (q & 1)], f[4 * (q & 6) + (q & 1) + 2], f[4 * (q & 6) + (q & 1) + 4], f[4 * (q & 6) + (q & 1) + 6]);
    }
    wgmma_wait<0>();
    fence_regs(d);
    if ((t & 15) == 15) {
      if (t >= 0) {
        const uint32_t red = sb + ring + 5 * SLOT;
#pragma unroll
        for (int i = 0; i < 8; i++) sts128(red + (tid >> 2) * 512 + (i >> 1) * 128 + (lane & 3) * 32 + (i & 1) * 16, __float_as_uint(cs[4 * i]), __float_as_uint(cs[4 * i + 1]), __float_as_uint(cs[4 * i + 2]), __float_as_uint(cs[4 * i + 3]));
        wg_bar(w);
        float a = 0.f;
#pragma unroll 4
        for (int i = 0; i < 32; i++) a += lds32f(red + i * 512 + tid * 4);
        g_cs[1][0][part(t) * 1024 + j * 128 + tid] = a;
        wg_bar(w);
        if (tid == 0) {
          fence_gpu();
          st_flag(&g_csflag[1][j][part(t)], tag);
        }
        __syncwarp();
      }
#pragma unroll
      for (int i = 0; i < 32; i++) cs[i] = 0.f;
    }
  }
}

__global__ void __launch_bounds__(NTHREADS, 1) fused_kernel(const __grid_constant__ Params P) {
  extern __shared__ __align__(1024) uint8_t smem_raw[];
  constexpr uint32_t sb = SB;
  const int tid = threadIdx.x;
  const unsigned vb = vblock();
  if (vb >= 128) { spare(P, sb, vb - 128); return; }
  const int warp = __shfl_sync(0xffffffffu, tid >> 5, 0);
  if (elect()) {
    if (warp == 11) { prefetch_map(&P.mx); prefetch_map(&P.mw[0]); if (smem_u32(smem_raw) != SB) __trap(); }
    if (warp < 7) {
#pragma unroll
      for (int i = 0; i < 8; i++) mbar_init(sb + OFF_BAR + (warp * 8 + i) * 8, warp == 2 || warp == 3 ? 2 : (warp == 4 ? 8 : 1));
    }
    asm volatile("fence.mbarrier_init.release.cluster;" ::: "memory");
    if (warp < 2) {
      const int j = cta_j(vb);
#pragma unroll 1
      for (int i = 0; i < (warp == 0 ? PRE_B : PRE_A); i++) {
        const uint32_t bar = sb + BAR_FULLB + warp * 64 + i * 8;
        mbar_expect_tx(bar, SLOT);
        if (warp == 0) tma_load_w(sb + OFF_B + i * SLOT, &P.mw[0], bar, 1024 + (i & 1) * 1024 + 128 * j, kv_order(i >> 1, j, 0));
        else tma_load_3d(sb + OFF_A + i * SLOT, &P.mx, bar, kv_order(i, j, 0) * 64, cta_m(vb) * 64, 0);
      }
    }
  }
  if (tid == 0) TS(6, 0);
  __syncthreads();
  if (tid == 0) TS(6, 2);
  if (warp < 4) {
    reg_dealloc<PREGS>();
    if (warp == 0) b_producer(P, sb, vb);
    else if (warp == 1) a_loader(P, sb, vb);
    else helper(P, sb, warp - 2, vb);
  } else {
    reg_alloc<CREGS>();
    consumer(P, sb, (warp >> 2) - 1, vb);
  }
}

typedef CUresult (*EncodeFn)(CUtensorMap*, CUtensorMapDataType, cuuint32_t, void*, const cuuint64_t*, const cuuint64_t*,
                             const cuuint32_t*, const cuuint32_t*, CUtensorMapInterleave, CUtensorMapSwizzle,
                             CUtensorMapL2promotion, CUtensorMapFloatOOBfill);

void encode(EncodeFn fn, CUtensorMap* m, const void* ptr, int rank, const cuuint64_t* dims, const cuuint64_t* strides,
            const cuuint32_t* box, CUtensorMapSwizzle swz) {
  const cuuint32_t es[5] = {1, 1, 1, 1, 1};
  fn(m, CU_TENSOR_MAP_DATA_TYPE_BFLOAT16, rank, const_cast<void*>(ptr), dims, strides, box, es, CU_TENSOR_MAP_INTERLEAVE_NONE,
     swz, CU_TENSOR_MAP_L2_PROMOTION_L2_256B, CU_TENSOR_MAP_FLOAT_OOB_FILL_NONE);
}
void encode_w(EncodeFn fn, CUtensorMap* m, const void* ptr, int ncols, bool perm) {
  const cuuint64_t p = (cuuint64_t)ncols * 2, d[5] = {(cuuint64_t)ncols, 2, 4, 4, 32}, s[4] = {p, (perm ? 8 : 2) * p, (perm ? 2 : 8) * p, 32 * p};
  const cuuint32_t box[5] = {64, 2, 4, 4, 2};
  encode(fn, m, ptr, 5, d, s, box, CU_TENSOR_MAP_SWIZZLE_128B);
}

void encode_cs(EncodeFn fn, CUtensorMap* m, const void* ptr, int ncols) {
  const cuuint64_t d[2] = {(cuuint64_t)ncols, 1024}, s[1] = {(cuuint64_t)ncols * 2};
  const cuuint32_t box[2] = {32, 64};
  encode(fn, m, ptr, 2, d, s, box, CU_TENSOR_MAP_SWIZZLE_NONE);
}

}

extern "C" void kernel_launch(void* const* d_in, const int* in_sizes, int n_in, void* d_out, int out_size) {
  (void)in_sizes; (void)n_in; (void)out_size;
  void* fnp = nullptr;
  cudaDriverEntryPointQueryResult q;
  cudaGetDriverEntryPoint("cuTensorMapEncodeTiled", &fnp, cudaEnableDefault, &q);
  EncodeFn fn = (EncodeFn)fnp;
  Params P;
  {
    const cuuint64_t dims[3] = {1024, 1024, 2}, strides[2] = {4096, 2048};
    const cuuint32_t box[3] = {64, 64, 2};
    encode(fn, &P.mx, d_in[0], 3, dims, strides, box, CU_TENSOR_MAP_SWIZZLE_128B);
  }
  P.out = (uint4*)d_out;
  encode_w(fn, &P.mw[0], d_in[1], 3072, false);
  encode_w(fn, &P.mw[1], d_in[4], 3072, true);
  encode_w(fn, &P.mw[2], d_in[1], 3072, true);
  encode_w(fn, &P.mwo[0], d_in[2], 1024, true);
  encode_w(fn, &P.mwo[1], d_in[6], 1024, false);
  encode_cs(fn, &P.mcs[0], d_in[1], 3072);
  encode_cs(fn, &P.mcs[1], d_in[4], 3072);
  {
    const cuuint64_t dims[2] = {32, 1024}, strides[1] = {64};
    const cuuint32_t box[2] = {32, 128};
    encode(fn, &P.mwphi, d_in[5], 2, dims, strides, box, CU_TENSOR_MAP_SWIZZLE_64B);
  }
  cudaFuncSetAttribute(fused_kernel, cudaFuncAttributeMaxDynamicSharedMemorySize, SMEM_BYTES);
  fused_kernel<<<NCTA, NTHREADS, SMEM_BYTES, cudaStreamPerThread>>>(P);
}
```

```cpp
#include <cuda_runtime.h>
#include <cuda_bf16.h>
#include <cuda.h>
#include <stdint.h>

namespace {

__device__ __forceinline__ void wgmma_ss_n256(float (&d)[128], uint32_t da, uint32_t ha, uint32_t db, int sd) {
  asm volatile("{\n.reg .pred p;\n.reg .b64 a, b;\nsetp.ne.b32 p, %130, 0;\nmov.b64 a, {%128, %131};\nmov.b64 b, {%129, 0x40000040};\n"
    "wgmma.mma_async.sync.aligned.m64n256k16.f32.bf16.bf16 {%0,%1,%2,%3,%4,%5,%6,%7,%8,%9,%10,%11,%12,%13,%14,%15,%16,%17,%18,%19,%20,%21,%22,%23,%24,%25,%26,%27,%28,%29,%30,%31,%32,%33,%34,%35,%36,%37,%38,%39,%40,%41,%42,%43,%44,%45,%46,%47,%48,%49,%50,%51,%52,%53,%54,%55,%56,%57,%58,%59,%60,%61,%62,%63,%64,%65,%66,%67,%68,%69,%70,%71,%72,%73,%74,%75,%76,%77,%78,%79,%80,%81,%82,%83,%84,%85,%86,%87,%88,%89,%90,%91,%92,%93,%94,%95,%96,%97,%98,%99,%100,%101,%102,%103,%104,%105,%106,%107,%108,%109,%110,%111,%112,%113,%114,%115,%116,%117,%118,%119,%120,%121,%122,%123,%124,%125,%126,%127}, a, b, p, 1, 1, 0, 1;\n}\n"
    : "+f"(d[0]),"+f"(d[1]),"+f"(d[2]),"+f"(d[3]),"+f"(d[4]),"+f"(d[5]),"+f"(d[6]),"+f"(d[7]),"+f"(d[8]),"+f"(d[9]),"+f"(d[10]),"+f"(d[11]),"+f"(d[12]),"+f"(d[13]),"+f"(d[14]),"+f"(d[15]),"+f"(d[16]),"+f"(d[17]),"+f"(d[18]),"+f"(d[19]),"+f"(d[20]),"+f"(d[21]),"+f"(d[22]),"+f"(d[23]),"+f"(d[24]),"+f"(d[25]),"+f"(d[26]),"+f"(d[27]),"+f"(d[28]),"+f"(d[29]),"+f"(d[30]),"+f"(d[31]),"+f"(d[32]),"+f"(d[33]),"+f"(d[34]),"+f"(d[35]),"+f"(d[36]),"+f"(d[37]),"+f"(d[38]),"+f"(d[39]),"+f"(d[40]),"+f"(d[41]),"+f"(d[42]),"+f"(d[43]),"+f"(d[44]),"+f"(d[45]),"+f"(d[46]),"+f"(d[47]),"+f"(d[48]),"+f"(d[49]),"+f"(d[50]),"+f"(d[51]),"+f"(d[52]),"+f"(d[53]),"+f"(d[54]),"+f"(d[55]),"+f"(d[56]),"+f"(d[57]),"+f"(d[58]),"+f"(d[59]),"+f"(d[60]),"+f"(d[61]),"+f"(d[62]),"+f"(d[63]),"+f"(d[64]),"+f"(d[65]),"+f"(d[66]),"+f"(d[67]),"+f"(d[68]),"+f"(d[69]),"+f"(d[70]),"+f"(d[71]),"+f"(d[72]),"+f"(d[73]),"+f"(d[74]),"+f"(d[75]),"+f"(d[76]),"+f"(d[77]),"+f"(d[78]),"+f"(d[79]),"+f"(d[80]),"+f"(d[81]),"+f"(d[82]),"+f"(d[83]),"+f"(d[84]),"+f"(d[85]),"+f"(d[86]),"+f"(d[87]),"+f"(d[88]),"+f"(d[89]),"+f"(d[90]),"+f"(d[91]),"+f"(d[92]),"+f"(d[93]),"+f"(d[94]),"+f"(d[95]),"+f"(d[96]),"+f"(d[97]),"+f"(d[98]),"+f"(d[99]),"+f"(d[100]),"+f"(d[101]),"+f"(d[102]),"+f"(d[103]),"+f"(d[104]),"+f"(d[105]),"+f"(d[106]),"+f"(d[107]),"+f"(d[108]),"+f"(d[109]),"+f"(d[110]),"+f"(d[111]),"+f"(d[112]),"+f"(d[113]),"+f"(d[114]),"+f"(d[115]),"+f"(d[116]),"+f"(d[117]),"+f"(d[118]),"+f"(d[119]),"+f"(d[120]),"+f"(d[121]),"+f"(d[122]),"+f"(d[123]),"+f"(d[124]),"+f"(d[125]),"+f"(d[126]),"+f"(d[127])
    : "r"(da), "r"(db), "r"(sd), "r"(ha));
}
__device__ __forceinline__ void wgmma_ss_n128(float (&d)[64], uint32_t da, uint32_t ha, uint32_t db, int sd) {
  asm volatile("{\n.reg .pred p;\n.reg .b64 a, b;\nsetp.ne.b32 p, %66, 0;\nmov.b64 a, {%64, %67};\nmov.b64 b, {%65, 0x40000040};\n"
    "wgmma.mma_async.sync.aligned.m64n128k16.f32.bf16.bf16 {%0,%1,%2,%3,%4,%5,%6,%7,%8,%9,%10,%11,%12,%13,%14,%15,%16,%17,%18,%19,%20,%21,%22,%23,%24,%25,%26,%27,%28,%29,%30,%31,%32,%33,%34,%35,%36,%37,%38,%39,%40,%41,%42,%43,%44,%45,%46,%47,%48,%49,%50,%51,%52,%53,%54,%55,%56,%57,%58,%59,%60,%61,%62,%63}, a, b, p, 1, 1, 0, 1;\n}\n"
    : "+f"(d[0]),"+f"(d[1]),"+f"(d[2]),"+f"(d[3]),"+f"(d[4]),"+f"(d[5]),"+f"(d[6]),"+f"(d[7]),"+f"(d[8]),"+f"(d[9]),"+f"(d[10]),"+f"(d[11]),"+f"(d[12]),"+f"(d[13]),"+f"(d[14]),"+f"(d[15]),"+f"(d[16]),"+f"(d[17]),"+f"(d[18]),"+f"(d[19]),"+f"(d[20]),"+f"(d[21]),"+f"(d[22]),"+f"(d[23]),"+f"(d[24]),"+f"(d[25]),"+f"(d[26]),"+f"(d[27]),"+f"(d[28]),"+f"(d[29]),"+f"(d[30]),"+f"(d[31]),"+f"(d[32]),"+f"(d[33]),"+f"(d[34]),"+f"(d[35]),"+f"(d[36]),"+f"(d[37]),"+f"(d[38]),"+f"(d[39]),"+f"(d[40]),"+f"(d[41]),"+f"(d[42]),"+f"(d[43]),"+f"(d[44]),"+f"(d[45]),"+f"(d[46]),"+f"(d[47]),"+f"(d[48]),"+f"(d[49]),"+f"(d[50]),"+f"(d[51]),"+f"(d[52]),"+f"(d[53]),"+f"(d[54]),"+f"(d[55]),"+f"(d[56]),"+f"(d[57]),"+f"(d[58]),"+f"(d[59]),"+f"(d[60]),"+f"(d[61]),"+f"(d[62]),"+f"(d[63])
    : "r"(da), "r"(db), "r"(sd), "r"(ha));
}
__device__ __forceinline__ void wgmma_ss_n40_tt(float (&d)[20], uint32_t da, uint32_t db, int sd) {
  asm volatile("{\n.reg .pred p;\n.reg .b64 a, b;\nsetp.ne.b32 p, %22, 0;\nmov.b64 a, {%20, 0x40000040};\nmov.b64 b, {%21, 0x8};\n"
    "wgmma.mma_async.sync.aligned.m64n40k16.f32.bf16.bf16 {%0,%1,%2,%3,%4,%5,%6,%7,%8,%9,%10,%11,%12,%13,%14,%15,%16,%17,%18,%19}, a, b, p, 1, 1, 1, 1;\n}\n"
    : "+f"(d[0]),"+f"(d[1]),"+f"(d[2]),"+f"(d[3]),"+f"(d[4]),"+f"(d[5]),"+f"(d[6]),"+f"(d[7]),"+f"(d[8]),"+f"(d[9]),"+f"(d[10]),"+f"(d[11]),"+f"(d[12]),"+f"(d[13]),"+f"(d[14]),"+f"(d[15]),"+f"(d[16]),"+f"(d[17]),"+f"(d[18]),"+f"(d[19])
    : "r"(da), "r"(db), "r"(sd));
}
__device__ __forceinline__ void wgmma_ss_n32(float (&d)[16], uint32_t da, uint32_t db, int sd) {
  asm volatile("{\n.reg .pred p;\n.reg .b64 a, b;\nsetp.ne.b32 p, %18, 0;\nmov.b64 a, {%16, 0x40000040};\nmov.b64 b, {%17, 0x80000020};\n"
    "wgmma.mma_async.sync.aligned.m64n32k16.f32.bf16.bf16 {%0,%1,%2,%3,%4,%5,%6,%7,%8,%9,%10,%11,%12,%13,%14,%15}, a, b, p, 1, 1, 0, 1;\n}\n"
    : "+f"(d[0]),"+f"(d[1]),"+f"(d[2]),"+f"(d[3]),"+f"(d[4]),"+f"(d[5]),"+f"(d[6]),"+f"(d[7]),"+f"(d[8]),"+f"(d[9]),"+f"(d[10]),"+f"(d[11]),"+f"(d[12]),"+f"(d[13]),"+f"(d[14]),"+f"(d[15])
    : "r"(da), "r"(db), "r"(sd));
}
__device__ __forceinline__ void wgmma_rs_n40(float (&d)[20], uint32_t a0, uint32_t a1, uint32_t a2, uint32_t a3, uint32_t db, int sd) {
  asm volatile("{\n.reg .pred p;\n.reg .b64 b;\nsetp.ne.b32 p, %25, 0;\nmov.b64 b, {%24, 0x10};\n"
    "wgmma.mma_async.sync.aligned.m64n40k16.f32.bf16.bf16 {%0,%1,%2,%3,%4,%5,%6,%7,%8,%9,%10,%11,%12,%13,%14,%15,%16,%17,%18,%19}, {%20,%21,%22,%23}, b, p, 1, 1, 1;\n}\n"
    : "+f"(d[0]),"+f"(d[1]),"+f"(d[2]),"+f"(d[3]),"+f"(d[4]),"+f"(d[5]),"+f"(d[6]),"+f"(d[7]),"+f"(d[8]),"+f"(d[9]),"+f"(d[10]),"+f"(d[11]),"+f"(d[12]),"+f"(d[13]),"+f"(d[14]),"+f"(d[15]),"+f"(d[16]),"+f"(d[17]),"+f"(d[18]),"+f"(d[19])
    : "r"(a0), "r"(a1), "r"(a2), "r"(a3), "r"(db), "r"(sd));
}
__device__ __forceinline__ void wgmma_r1_n256(float (&d)[128], uint32_t da, uint32_t db, int sd) {
  asm volatile("{\n.reg .pred p;\n.reg .b64 a, b;\nsetp.ne.b32 p, %130, 0;\nmov.b64 a, {%128, 0x8};\nmov.b64 b, {%129, 0x6};\n"
    "wgmma.mma_async.sync.aligned.m64n256k16.f32.bf16.bf16 {%0,%1,%2,%3,%4,%5,%6,%7,%8,%9,%10,%11,%12,%13,%14,%15,%16,%17,%18,%19,%20,%21,%22,%23,%24,%25,%26,%27,%28,%29,%30,%31,%32,%33,%34,%35,%36,%37,%38,%39,%40,%41,%42,%43,%44,%45,%46,%47,%48,%49,%50,%51,%52,%53,%54,%55,%56,%57,%58,%59,%60,%61,%62,%63,%64,%65,%66,%67,%68,%69,%70,%71,%72,%73,%74,%75,%76,%77,%78,%79,%80,%81,%82,%83,%84,%85,%86,%87,%88,%89,%90,%91,%92,%93,%94,%95,%96,%97,%98,%99,%100,%101,%102,%103,%104,%105,%106,%107,%108,%109,%110,%111,%112,%113,%114,%115,%116,%117,%118,%119,%120,%121,%122,%123,%124,%125,%126,%127}, a, b, p, 1, 1, 0, 1;\n}\n"
    : "+f"(d[0]),"+f"(d[1]),"+f"(d[2]),"+f"(d[3]),"+f"(d[4]),"+f"(d[5]),"+f"(d[6]),"+f"(d[7]),"+f"(d[8]),"+f"(d[9]),"+f"(d[10]),"+f"(d[11]),"+f"(d[12]),"+f"(d[13]),"+f"(d[14]),"+f"(d[15]),"+f"(d[16]),"+f"(d[17]),"+f"(d[18]),"+f"(d[19]),"+f"(d[20]),"+f"(d[21]),"+f"(d[22]),"+f"(d[23]),"+f"(d[24]),"+f"(d[25]),"+f"(d[26]),"+f"(d[27]),"+f"(d[28]),"+f"(d[29]),"+f"(d[30]),"+f"(d[31]),"+f"(d[32]),"+f"(d[33]),"+f"(d[34]),"+f"(d[35]),"+f"(d[36]),"+f"(d[37]),"+f"(d[38]),"+f"(d[39]),"+f"(d[40]),"+f"(d[41]),"+f"(d[42]),"+f"(d[43]),"+f"(d[44]),"+f"(d[45]),"+f"(d[46]),"+f"(d[47]),"+f"(d[48]),"+f"(d[49]),"+f"(d[50]),"+f"(d[51]),"+f"(d[52]),"+f"(d[53]),"+f"(d[54]),"+f"(d[55]),"+f"(d[56]),"+f"(d[57]),"+f"(d[58]),"+f"(d[59]),"+f"(d[60]),"+f"(d[61]),"+f"(d[62]),"+f"(d[63]),"+f"(d[64]),"+f"(d[65]),"+f"(d[66]),"+f"(d[67]),"+f"(d[68]),"+f"(d[69]),"+f"(d[70]),"+f"(d[71]),"+f"(d[72]),"+f"(d[73]),"+f"(d[74]),"+f"(d[75]),"+f"(d[76]),"+f"(d[77]),"+f"(d[78]),"+f"(d[79]),"+f"(d[80]),"+f"(d[81]),"+f"(d[82]),"+f"(d[83]),"+f"(d[84]),"+f"(d[85]),"+f"(d[86]),"+f"(d[87]),"+f"(d[88]),"+f"(d[89]),"+f"(d[90]),"+f"(d[91]),"+f"(d[92]),"+f"(d[93]),"+f"(d[94]),"+f"(d[95]),"+f"(d[96]),"+f"(d[97]),"+f"(d[98]),"+f"(d[99]),"+f"(d[100]),"+f"(d[101]),"+f"(d[102]),"+f"(d[103]),"+f"(d[104]),"+f"(d[105]),"+f"(d[106]),"+f"(d[107]),"+f"(d[108]),"+f"(d[109]),"+f"(d[110]),"+f"(d[111]),"+f"(d[112]),"+f"(d[113]),"+f"(d[114]),"+f"(d[115]),"+f"(d[116]),"+f"(d[117]),"+f"(d[118]),"+f"(d[119]),"+f"(d[120]),"+f"(d[121]),"+f"(d[122]),"+f"(d[123]),"+f"(d[124]),"+f"(d[125]),"+f"(d[126]),"+f"(d[127])
    : "r"(da), "r"(db), "r"(sd));
}
__device__ __forceinline__ void wgmma_r1_n128(float (&d)[64], uint32_t da, uint32_t db, int sd) {
  asm volatile("{\n.reg .pred p;\n.reg .b64 a, b;\nsetp.ne.b32 p, %66, 0;\nmov.b64 a, {%64, 0x8};\nmov.b64 b, {%65, 0x6};\n"
    "wgmma.mma_async.sync.aligned.m64n128k16.f32.bf16.bf16 {%0,%1,%2,%3,%4,%5,%6,%7,%8,%9,%10,%11,%12,%13,%14,%15,%16,%17,%18,%19,%20,%21,%22,%23,%24,%25,%26,%27,%28,%29,%30,%31,%32,%33,%34,%35,%36,%37,%38,%39,%40,%41,%42,%43,%44,%45,%46,%47,%48,%49,%50,%51,%52,%53,%54,%55,%56,%57,%58,%59,%60,%61,%62,%63}, a, b, p, 1, 1, 0, 1;\n}\n"
    : "+f"(d[0]),"+f"(d[1]),"+f"(d[2]),"+f"(d[3]),"+f"(d[4]),"+f"(d[5]),"+f"(d[6]),"+f"(d[7]),"+f"(d[8]),"+f"(d[9]),"+f"(d[10]),"+f"(d[11]),"+f"(d[12]),"+f"(d[13]),"+f"(d[14]),"+f"(d[15]),"+f"(d[16]),"+f"(d[17]),"+f"(d[18]),"+f"(d[19]),"+f"(d[20]),"+f"(d[21]),"+f"(d[22]),"+f"(d[23]),"+f"(d[24]),"+f"(d[25]),"+f"(d[26]),"+f"(d[27]),"+f"(d[28]),"+f"(d[29]),"+f"(d[30]),"+f"(d[31]),"+f"(d[32]),"+f"(d[33]),"+f"(d[34]),"+f"(d[35]),"+f"(d[36]),"+f"(d[37]),"+f"(d[38]),"+f"(d[39]),"+f"(d[40]),"+f"(d[41]),"+f"(d[42]),"+f"(d[43]),"+f"(d[44]),"+f"(d[45]),"+f"(d[46]),"+f"(d[47]),"+f"(d[48]),"+f"(d[49]),"+f"(d[50]),"+f"(d[51]),"+f"(d[52]),"+f"(d[53]),"+f"(d[54]),"+f"(d[55]),"+f"(d[56]),"+f"(d[57]),"+f"(d[58]),"+f"(d[59]),"+f"(d[60]),"+f"(d[61]),"+f"(d[62]),"+f"(d[63])
    : "r"(da), "r"(db), "r"(sd));
}

__device__ __forceinline__ uint32_t smem_u32(const void* p) { return (uint32_t)__cvta_generic_to_shared(p); }
__device__ __forceinline__ void mbar_init(uint32_t bar, uint32_t cnt) { asm volatile("mbarrier.init.shared::cta.b64 [%0], %1;" ::"r"(bar), "r"(cnt)); }
__device__ __forceinline__ void mbar_expect_tx(uint32_t bar, uint32_t bytes) { asm volatile("mbarrier.arrive.expect_tx.shared::cta.b64 _, [%0], %1;" ::"r"(bar), "r"(bytes) : "memory"); }
__device__ __forceinline__ void mbar_arrive(uint32_t bar) { asm volatile("mbarrier.arrive.shared::cta.b64 _, [%0];" ::"r"(bar) : "memory"); }
__device__ __forceinline__ void mbar_arrive_n(uint32_t bar, uint32_t n) { asm volatile("mbarrier.arrive.shared::cta.b64 _, [%0], %1;" ::"r"(bar), "r"(n) : "memory"); }
__device__ __forceinline__ void mbar_wait(uint32_t bar, uint32_t parity) {
  asm volatile("{\n.reg .pred p;\nLAB_WAIT:\nmbarrier.try_wait.parity.shared::cta.b64 p, [%0], %1;\n@p bra DONE;\nbra LAB_WAIT;\nDONE:\n}" ::"r"(bar), "r"(parity) : "memory");
}
__device__ __forceinline__ void mbar_wait2(uint32_t a, uint32_t pa, uint32_t b, uint32_t pb) {
  asm volatile("{\n.reg .pred p, q;\nLAB_WAIT:\nmbarrier.try_wait.parity.shared::cta.b64 p, [%0], %1;\nmbarrier.try_wait.parity.shared::cta.b64 q, [%2], %3;\n"
               "and.pred p, p, q;\n@p bra DONE;\nbra LAB_WAIT;\nDONE:\n}" ::"r"(a), "r"(pa), "r"(b), "r"(pb) : "memory");
}
__device__ __forceinline__ void mbar_wait3(uint32_t a, uint32_t pa, uint32_t b, uint32_t pb) {
  asm volatile("{\n.reg .pred p, q, r;\nLAB_WAIT:\nmbarrier.try_wait.parity.shared::cta.b64 p, [%0], %1;\nmbarrier.try_wait.parity.shared::cta.b64 q, [%2], %3;\n"
               "mbarrier.try_wait.parity.shared::cta.b64 r, [%2+8], %3;\nand.pred p, p, q;\nand.pred p, p, r;\n@p bra DONE;\nbra LAB_WAIT;\nDONE:\n}" ::"r"(a), "r"(pa), "r"(b), "r"(pb) : "memory");
}
__device__ __forceinline__ bool mbar_probe2(uint32_t a, uint32_t pa, uint32_t b, uint32_t pb) {
  uint32_t ok;
  asm volatile("{\n.reg .pred p, q;\nmbarrier.test_wait.parity.shared::cta.b64 p, [%1], %2;\nmbarrier.test_wait.parity.shared::cta.b64 q, [%3], %4;\n"
               "and.pred p, p, q;\nselp.u32 %0, 1, 0, p;\n}" : "=r"(ok) : "r"(a), "r"(pa), "r"(b), "r"(pb) : "memory");
  return ok != 0;
}
__device__ __forceinline__ void tma_load_3d(uint32_t dst, const CUtensorMap* tm, uint32_t bar, int c0, int c1, int c2) {
  asm volatile("cp.async.bulk.tensor.3d.shared::cluster.global.mbarrier::complete_tx::bytes [%0], [%1, {%3, %4, %5}], [%2];"
               ::"r"(dst), "l"(tm), "r"(bar), "r"(c0), "r"(c1), "r"(c2) : "memory");
}
__device__ __forceinline__ void tma_load_2d(uint32_t dst, const CUtensorMap* tm, uint32_t bar, int c0, int c1) {
  asm volatile("cp.async.bulk.tensor.2d.shared::cluster.global.mbarrier::complete_tx::bytes [%0], [%1, {%3, %4}], [%2];"
               ::"r"(dst), "l"(tm), "r"(bar), "r"(c0), "r"(c1) : "memory");
}
__device__ __forceinline__ void tma_load_w(uint32_t dst, const CUtensorMap* tm, uint32_t bar, int col, int kb) {
#pragma unroll
  for (int q = 0; q < 2; q++)
    asm volatile("cp.async.bulk.tensor.5d.shared::cluster.global.mbarrier::complete_tx::bytes [%0], [%1, {%3, %4, %4, %4, %5}], [%2];"
                 ::"r"(dst + q * 8192), "l"(tm), "r"(bar), "r"(col + q * 64), "r"(0), "r"(2 * kb) : "memory");
}
__device__ __forceinline__ void tma_prefetch_w(const CUtensorMap* tm, int col, int kb) {
#pragma unroll
  for (int q = 0; q < 2; q++)
    asm volatile("cp.async.bulk.prefetch.tensor.5d.L2.global [%0, {%1, %2, %2, %2, %3}];" ::"l"(tm), "r"(col + q * 64), "r"(0), "r"(2 * kb) : "memory");
}
__device__ __forceinline__ void bulk_load(uint32_t dst, const void* g, uint32_t bytes, uint32_t bar) {
  asm volatile("cp.async.bulk.shared::cluster.global.mbarrier::complete_tx::bytes [%0], [%1], %2, [%3];" ::"r"(dst), "l"(g), "r"(bytes), "r"(bar) : "memory");
}
__device__ __forceinline__ void prefetch_map(const CUtensorMap* tm) { asm volatile("prefetch.tensormap [%0];" ::"l"(tm) : "memory"); }
__device__ __forceinline__ void fence_async_smem() { asm volatile("fence.proxy.async.shared::cta;" ::: "memory"); }
__device__ __forceinline__ void fence_async_global() { asm volatile("fence.proxy.async.global;" ::: "memory"); }
__device__ __forceinline__ void fence_gpu() { asm volatile("fence.release.gpu;" ::: "memory"); }
__device__ __forceinline__ void st_flag(unsigned* p, unsigned v) { asm volatile("st.relaxed.gpu.global.u32 [%0], %1;" ::"l"(p), "r"(v) : "memory"); }
__device__ __forceinline__ unsigned ld_flag(const unsigned* p) { unsigned v; asm volatile("ld.relaxed.gpu.global.u32 %0, [%1];" : "=r"(v) : "l"(p) : "memory"); return v; }
__device__ __forceinline__ uint4 ldcg4(const void* p) { uint4 v; asm volatile("ld.global.cg.v4.u32 {%0,%1,%2,%3}, [%4];" : "=r"(v.x), "=r"(v.y), "=r"(v.z), "=r"(v.w) : "l"(p)); return v; }
__device__ __forceinline__ uint4 ld_pkt(const uint4* p) {
  uint4 v; asm volatile("{\n.reg .b128 t;\nld.relaxed.gpu.global.b128 t, [%4];\nmov.b128 {%0,%1,%2,%3}, t;\n}" : "=r"(v.x), "=r"(v.y), "=r"(v.z), "=r"(v.w) : "l"(p) : "memory"); return v;
}
__device__ __forceinline__ void st_pkt(uint4* p, uint32_t a, uint32_t b, uint32_t c, uint32_t tag) {
  asm volatile("{\n.reg .b128 t;\nmov.b128 t, {%1,%2,%3,%4};\nst.relaxed.gpu.global.b128 [%0], t;\n}" ::"l"(p), "r"(a), "r"(b), "r"(c), "r"(tag) : "memory");
}
__device__ __forceinline__ void st_v4(uint4* p, uint32_t a, uint32_t b, uint32_t c, uint32_t d) { asm volatile("st.relaxed.gpu.global.v4.u32 [%0], {%1,%2,%3,%4};" ::"l"(p), "r"(a), "r"(b), "r"(c), "r"(d) : "memory"); }
__device__ __forceinline__ void sts32(uint32_t addr, uint32_t a) { asm volatile("st.shared.u32 [%0], %1;" ::"r"(addr), "r"(a) : "memory"); }
__device__ __forceinline__ void sts64(uint32_t addr, uint32_t a, uint32_t b) { asm volatile("st.shared.v2.u32 [%0], {%1,%2};" ::"r"(addr), "r"(a), "r"(b) : "memory"); }
__device__ __forceinline__ uint32_t mul2(uint32_t a, uint32_t b) { uint32_t r; asm("mul.rn.bf16x2 %0, %1, %2;" : "=r"(r) : "r"(a), "r"(b)); return r; }
__device__ __forceinline__ uint32_t add2(uint32_t a, uint32_t b) { uint32_t r; asm("add.rn.bf16x2 %0, %1, %2;" : "=r"(r) : "r"(a), "r"(b)); return r; }
__device__ __forceinline__ bool elect() {
  uint32_t p; asm volatile("{\n.reg .pred q;\nelect.sync _|q, 0xffffffff;\nselp.u32 %0, 1, 0, q;\n}" : "=r"(p)); return p != 0;
}
__device__ __forceinline__ void wgmma_fence() { asm volatile("wgmma.fence.sync.aligned;" ::: "memory"); }
__device__ __forceinline__ void wgmma_commit() { asm volatile("wgmma.commit_group.sync.aligned;" ::: "memory"); }
template <int N> __device__ __forceinline__ void wgmma_wait() { asm volatile("wgmma.wait_group.sync.aligned %0;" ::"n"(N) : "memory"); }
template <int N> __device__ __forceinline__ void fence_regs(float (&d)[N]) {
#pragma unroll
  for (int i = 0; i < N; i++) asm volatile("" : "+f"(d[i])::"memory");
}
template <int R> __device__ __forceinline__ void reg_alloc() { asm volatile("setmaxnreg.inc.sync.aligned.u32 %0;" ::"n"(R)); }
template <int R> __device__ __forceinline__ void reg_dealloc() { asm volatile("setmaxnreg.dec.sync.aligned.u32 %0;" ::"n"(R)); }
__device__ __forceinline__ void wg_bar(int w) { asm volatile("bar.sync %0, 128;" ::"r"(w + 1) : "memory"); }
__device__ __forceinline__ constexpr uint32_t desc_lo(uint32_t addr, uint32_t lbo) { return (addr >> 4) + ((lbo >> 4) << 16); }
__device__ __forceinline__ uint32_t pack2(float lo, float hi) { uint32_t r; asm("cvt.rn.bf16x2.f32 %0, %1, %2;" : "=r"(r) : "f"(hi), "f"(lo)); return r; }
__device__ __forceinline__ float lo16(uint32_t v) { return __uint_as_float(v << 16); }
__device__ __forceinline__ float hi16(uint32_t v) { return __uint_as_float(v & 0xFFFF0000u); }
__device__ __forceinline__ float ex2(float x) { float r; asm("ex2.approx.ftz.f32 %0, %1;" : "=f"(r) : "f"(x)); return r; }
__device__ __forceinline__ float rcp(float x) { float r; asm("rcp.approx.ftz.f32 %0, %1;" : "=f"(r) : "f"(x)); return r; }
__device__ __forceinline__ uint32_t movm(uint32_t a) { uint32_t d; asm volatile("movmatrix.sync.aligned.m8n8.trans.b16 %0, %1;" : "=r"(d) : "r"(a)); return d; }
__device__ __forceinline__ void stsm4(uint32_t addr, uint32_t a, uint32_t b, uint32_t c, uint32_t d) {
  asm volatile("stmatrix.sync.aligned.m8n8.x4.shared.b16 [%0], {%1,%2,%3,%4};" ::"r"(addr), "r"(a), "r"(b), "r"(c), "r"(d) : "memory");
}
__device__ __forceinline__ void ldsm4(uint32_t addr, uint32_t (&r)[4]) {
  asm volatile("ldmatrix.sync.aligned.m8n8.x4.shared.b16 {%0,%1,%2,%3}, [%4];" : "=r"(r[0]), "=r"(r[1]), "=r"(r[2]), "=r"(r[3]) : "r"(addr) : "memory");
}
__device__ __forceinline__ void sts128(uint32_t addr, uint32_t a, uint32_t b, uint32_t c, uint32_t d) {
  asm volatile("st.shared.v4.u32 [%0], {%1,%2,%3,%4};" ::"r"(addr), "r"(a), "r"(b), "r"(c), "r"(d) : "memory");
}
__device__ __forceinline__ void lds128(uint32_t addr, uint32_t& a, uint32_t& b, uint32_t& c, uint32_t& d) {
  asm volatile("ld.shared.v4.u32 {%0,%1,%2,%3}, [%4];" : "=r"(a), "=r"(b), "=r"(c), "=r"(d) : "r"(addr) : "memory");
}
__device__ __forceinline__ float lds32f(uint32_t addr) { float v; asm volatile("ld.shared.f32 %0, [%1];" : "=f"(v) : "r"(addr) : "memory"); return v; }
__device__ __forceinline__ float2 lds64f(uint32_t addr) { float2 v; asm volatile("ld.shared.v2.f32 {%0,%1}, [%2];" : "=f"(v.x), "=f"(v.y) : "r"(addr) : "memory"); return v; }
__device__ __forceinline__ void mma16816(float (&d)[4], uint32_t a0, uint32_t a1, uint32_t a2, uint32_t a3, uint32_t b0, uint32_t b1) {
  asm("mma.sync.aligned.m16n8k16.row.col.f32.bf16.bf16.f32 {%0,%1,%2,%3}, {%4,%5,%6,%7}, {%8,%9}, {%0,%1,%2,%3};"
      : "+f"(d[0]), "+f"(d[1]), "+f"(d[2]), "+f"(d[3]) : "r"(a0), "r"(a1), "r"(a2), "r"(a3), "r"(b0), "r"(b1));
}
__device__ __forceinline__ void mma1688(float (&d)[4], uint32_t a0, uint32_t a1, uint32_t b0) {
  asm("mma.sync.aligned.m16n8k8.row.col.f32.bf16.bf16.f32 {%0,%1,%2,%3}, {%4,%5}, {%6}, {%0,%1,%2,%3};"
      : "+f"(d[0]), "+f"(d[1]), "+f"(d[2]), "+f"(d[3]) : "r"(a0), "r"(a1), "r"(b0));
}

__device__ __forceinline__ float qsum(float v) { v += __shfl_xor_sync(0xffffffffu, v, 1); v += __shfl_xor_sync(0xffffffffu, v, 2); return v; }

constexpr int NCTA = 132;
#define NB_ 6
#define NA_ 5
constexpr int NB = NB_;
constexpr int NA = NA_;
constexpr uint32_t SLOT = 16384;
constexpr uint32_t SB = 1024;
constexpr uint32_t OFF_B = 0;
constexpr uint32_t OFF_A = NB * SLOT;
constexpr uint32_t OFF_S = OFF_A + NA * SLOT;
constexpr uint32_t OFF_T = OFF_S + 20480;
constexpr uint32_t OFF_CS = OFF_T + 24576;
constexpr uint32_t OFF_MR = OFF_CS + 4640;
constexpr uint32_t OFF_BAR = OFF_MR + 512;
constexpr uint32_t OFF_MA = OFF_S, OFF_MB = OFF_CS - 2048;
constexpr uint32_t BAR_FULLB = OFF_BAR;
constexpr uint32_t BAR_FULLA = BAR_FULLB + 64;
constexpr uint32_t BAR_EMPTYB = BAR_FULLA + 64;
constexpr uint32_t BAR_EMPTYA = BAR_EMPTYB + 64;
constexpr uint32_t BAR_SIGP = BAR_EMPTYA + 64;
constexpr uint32_t BAR_SIGT = BAR_SIGP + 32;
constexpr uint32_t BAR_STAT = BAR_SIGP + 64;
constexpr uint32_t BAR_HALO = BAR_STAT + 16;
constexpr uint32_t BAR_CS = BAR_HALO + 8;
constexpr uint32_t BAR_WPHI = BAR_CS + 16;
constexpr uint32_t BAR_KV = BAR_WPHI + 8;
constexpr uint32_t BAR_STG = BAR_KV + 16;
constexpr uint32_t BAR_EPOCH = BAR_STG + 48;
constexpr uint32_t OFF_EPOCH = OFF_BAR + 7 * 64;
static_assert(BAR_EPOCH < OFF_EPOCH, "barriers");
constexpr uint32_t SMEM_BYTES = OFF_EPOCH + 8;
static_assert(SMEM_BYTES <= 232448 && NB % 2 == 0 && NB <= 8 && NA <= 6, "smem");

#define CREGS 224
#define PREGS 56
#define PF0 9
#define PF1 13
#define PF2 17
#define PRE_A 2
#define PRE_B 4
#define CSB 4
#define CSNEED 0xF003u
#define XR 1
#define PS0 2
#define PS1 2
#define PSW 0
#define STG0 0
#define QORD 2
#define KSPLIT 12
#define KEEP 16
#define NJ 3
#define KSL 1000
#define PSL 0
#define KVS 12
#define D2 2000
#define D3 1500
#define G0 50
#define G3 50
#define G1 0
#define G4 0
#define MAP 3
#define PMAP 0x76321450u
#define PW 1
#define PN2 0
#define XA 3
#define KB 8
#define PNX 2
#define PNO 2
#define DEFER 3
#define DEFL 2
#define TSK 3
#define TSL 3
constexpr int NTHREADS = 384;

struct Params {
  CUtensorMap mx;
  CUtensorMap mw[3];
  CUtensorMap mwo[2];
  CUtensorMap mcs[2];
  CUtensorMap mwphi;
  uint4* out;
};

#define XBUF(L) 1
__device__ __align__(256) uint4 g_img[XBUF(3) + 1][16][16][1024];
__device__ __align__(256) uint4 g_wf[2][8][16][1024];
__device__ __align__(256) uint4 g_stats[16][2][8][32];
__device__ __align__(256) uint4 g_halo[16][8][2][256];
__device__ __align__(256) float g_cs[2][2][3072];
__device__ __align__(256) uint4 g_kvpart[8][16][2][544];
__device__ __align__(256) uint4 g_kvfin[8][16][80];
__device__ __align__(256) unsigned g_xflag[4][2][16][32];
__device__ __align__(256) unsigned g_oflag[4][2][16][32];
__device__ __align__(256) unsigned g_hflag[2][16][8][32];
__device__ __align__(256) unsigned g_kvfflag[2][8][2][32];
__device__ __align__(256) unsigned g_csflag[2][8][32];
__device__ __align__(256) unsigned g_kflag[8][32];
__device__ unsigned g_ctr;
__device__ __forceinline__ unsigned vblock() {
  unsigned s;
  asm volatile("mov.u32 %0, %%smid;" : "=r"(s));
  const unsigned r = s & 1;
  s >>= 1;
  const unsigned t = s - 32, q = (t * 37) >> 8;
  const unsigned hi = s < 60 ? 12 + (t - 7 * q) * 8 + q : (s < 62 ? s + 4 : s - 58);
  unsigned b = 2 * (s < 32 ? (s & 7) * 8 + (s >> 3) : hi) + r;
  if (b < 128) b = (b & 15) | ((PMAP >> ((b >> 4) * 4)) & 7) << 4;
  if (s >= 62) b = 8 + 4 * r + s - 62;
  return __shfl_sync(0xffffffffu, b, 0);
}
#define TS(who, id) do {} while (0)
#define TSW(id) do {} while (0)

#define TSMASK 0xFFFF
#define TSL_(a) do { if ((TSMASK >> (a)) & 1) TSW((a) + L * 12); } while (0)
__device__ __forceinline__ int cta_m(unsigned b) { return ((b >> 2) & 12) | (b & 3); }
__device__ __forceinline__ int cta_j(unsigned b) { return ((b >> 2) & 3) | ((b >> 4) & 4); }
struct Ring { uint32_t s, ph; };
template <int N> __device__ __forceinline__ void adv(Ring& r) { if (++r.s == N) { r.s = 0; r.ph ^= 1; } }
template <int N> __device__ __forceinline__ void rewind2(Ring& r) { if (r.s < 2) { r.s += N - 2; r.ph ^= 1; } else r.s -= 2; }
__device__ __forceinline__ int other_tile(int t, int j) { return (t == (j | 4) ? 7 : t) ^ (~j & 4); }
__device__ __forceinline__ int q_order(int i, int j) { return 2 * (i >= 14 ? j : other_tile(i >> 1, j)) + (i & 1); }
__device__ __forceinline__ int o_order(int i, int j) {
  if (i < 2) return 2 * j + i;
  const int odd = i >= 9;
  return 2 * other_tile(i - 2 - 7 * odd, j) + odd;
}
__device__ __forceinline__ int kv_order(int i, int j, int L) { return L > 0 ? o_order(i, j) : (i + 14 + 2 * (j & 4)) & 15; }

__device__ __forceinline__ unsigned poll_flags(const unsigned* f, int n, unsigned need, unsigned tag) {
  const int lane = threadIdx.x & 31;
  unsigned mask; int it = 0;
  do {
    unsigned v = lane < n ? ld_flag(f + lane) : 0u;
    mask = __ballot_sync(0xffffffffu, lane < n && v == tag);
    if (++it > (1 << 22)) __trap();
  } while ((mask & need) != need);
  fence_async_global();
  return mask;
}
template <bool WAIT = true>
__device__ __forceinline__ unsigned get_tag(uint32_t sb) {
  if (WAIT) mbar_wait(sb + BAR_EPOCH, 0);
  unsigned t; asm volatile("ld.shared.u32 %0, [%1];" : "=r"(t) : "r"(sb + OFF_EPOCH) : "memory");
  return t;
}

__device__ __forceinline__ int lane_id() { int l; asm volatile("mov.u32 %0, %%laneid;" : "=r"(l)); return l; }
__device__ __forceinline__ unsigned seq4(unsigned tag, int L) { return 8u | ((tag & 1u) << 2) | (unsigned)L; }
constexpr float LOG2E = 1.4426950408889634f;

__device__ __forceinline__ void sched_fence(uint32_t sb) { mbar_wait(sb + BAR_EPOCH, 0); }
constexpr uint32_t HA128 = 0x40000040u, HA64 = 0x80000040u;
struct Ctx {
  static constexpr uint32_t sb = SB;
  uint32_t ab, da0;
  int w, warp, lane, g, c;
  int goff;
  __device__ __forceinline__ int m() const { return goff >> 14; }
  __device__ __forceinline__ int j() const { return (goff >> 4) & 7; }
  bool elected;
  Ring ra, rb;
  uint32_t pa, pb;
  uint32_t ha, k2;
  uint32_t mrow, mxor, mhi;
  __device__ __forceinline__ uint32_t aslot(uint32_t s) const { return ab + s * SLOT; }
  __device__ __forceinline__ uint32_t fullA(uint32_t s) const { return sb + BAR_FULLA + s * 8; }
  __device__ __forceinline__ uint32_t fullB(uint32_t s) const { return sb + BAR_FULLB + s * 8; }
  __device__ __forceinline__ void releaseA(uint32_t s) const { if (elected) mbar_arrive(sb + BAR_EMPTYA + s * 8); }
  __device__ __forceinline__ void releaseB(uint32_t s) const { if (elected) mbar_arrive(sb + BAR_EMPTYB + s * 8); }
  __device__ __forceinline__ uint32_t maddr(uint32_t tile, uint32_t ch) const { return tile + mrow + (((ch + mhi) ^ mxor) << 4); }
  __device__ __forceinline__ uint32_t oo() const { return warp * 128 + g * 4 + (c ^ (g >> 1)); }
  __device__ __forceinline__ uint4* img(int b, int hp) const { return &g_img[b][m()][2 * j() + hp][w * 512 + oo()]; }
  __device__ __forceinline__ uint32_t held(int i) const { return ra.s + i < 2 ? ra.s + i + NA - 2 : ra.s + i - 2; }
};

template <int N, bool FIRST, bool O = true>
__device__ __forceinline__ void gemm_issue(float (&acc)[N / 2], Ctx& x, bool ready = false) {
  if (!ready) {
    if (N == 256) mbar_wait3(x.fullA(x.ra.s), x.ra.ph, x.fullB(x.rb.s), x.rb.ph);
    else mbar_wait2(x.fullA(x.ra.s), x.ra.ph, x.fullB(x.rb.s), x.rb.ph);
  }
  const uint32_t da = x.da0 + x.ra.s * (SLOT / 16), db = desc_lo(SB + OFF_B, 8192) + x.rb.s * (SLOT / 16);
  wgmma_fence();
#pragma unroll
  for (int k = 0; k < 4; k++) {
    const uint32_t a = da + (k >> 1) * (O ? 32 : x.k2) + (k & 1) * 2, ha = O ? HA64 : x.ha;
    if constexpr (N == 256) wgmma_ss_n256(acc, a, ha, db + 128 * k, !(FIRST && k == 0));
    else wgmma_ss_n128(acc, a, ha, db + 128 * k, !(FIRST && k == 0));
  }
  wgmma_commit();
}
template <int N>
__device__ __forceinline__ void gemm_next(Ctx& x) {
  x.pa = x.ra.s; x.pb = x.rb.s;
  if (N == 256) x.rb.s++;
  adv<NA>(x.ra); adv<NB>(x.rb);
}
template <int N>
__device__ __forceinline__ void gemm_release(Ctx& x, bool relA) {
  if (relA) x.releaseA(x.pa);
  x.releaseB(x.pb);
  if (N == 256) x.releaseB(x.pb + 1);
}
template <int N>
__device__ __forceinline__ void gemm_retire(Ctx& x, bool relA) { wgmma_wait<1>(); gemm_release<N>(x, relA); gemm_next<N>(x); }
template <bool O = true>
__device__ __forceinline__ void gemm_run(float (&acc)[64], Ctx& x, int n, int hold, int n4 = 0) {
  bool ready = false;
#pragma unroll 1
  for (; n > 0; n--) {
    gemm_issue<128, false, O>(acc, x, ready);
    const uint32_t pa = x.pa, pb = x.pb;
    gemm_next<128>(x);
    ready = mbar_probe2(x.fullA(x.ra.s), x.ra.ph, x.fullB(x.rb.s), x.rb.ph);
    wgmma_wait<1>();
    if (n > hold) x.releaseA(pa);
    x.releaseB(pb);
  }
}
__device__ __forceinline__ void gemm_end(float (&acc)[64], Ctx& x) { wgmma_wait<0>(); fence_regs(acc); gemm_release<128>(x, false); }

__device__ __forceinline__ void load_x32(float* a, uint32_t tile, uint32_t ch, const Ctx& x) {
#pragma unroll
  for (int p = 0; p < 2; p++) {
    uint32_t v[4];
    ldsm4(x.maddr(tile, ch + 2 * p), v);
#pragma unroll
    for (int i = 0; i < 4; i++) { a[8 * p + 2 * i] = lo16(v[i]); a[8 * p + 2 * i + 1] = hi16(v[i]); }
  }
}

__device__ __forceinline__ void rows_load(uint4* r, uint32_t tile, const Ctx& x) {
#pragma unroll
  for (int q = 0; q < 4; q++) {
    const uint32_t row = x.warp * 16 + 4 * q + (x.lane >> 3);
    lds128(tile + row * 128 + (((x.lane & 7) ^ (row & 7)) << 4), r[q].x, r[q].y, r[q].z, r[q].w);
  }
}
__device__ __forceinline__ void rows_store(const uint4* r, uint4* g, const Ctx& x) {
  g += (x.warp * 16 + (x.lane >> 3)) * 256 + (x.lane & 7);
#pragma unroll
  for (int q = 0; q < 4; q++) g[q * 1024] = r[q];
}
__device__ __forceinline__ void publish(int id, const Ctx& x) { __syncwarp(); if (x.lane == 0) mbar_arrive(x.sb + BAR_SIGP + id * 8); }
__device__ __forceinline__ void img_store(const uint4 (&r)[4], uint4* g) {
#pragma unroll
  for (int q = 0; q < 4; q++) g[q * 32] = r[q];
}
__device__ __forceinline__ void img_sts(const uint4 (&r)[4], uint32_t tile, const Ctx& x) {
#pragma unroll
  for (int q = 0; q < 4; q++) sts128(tile + x.oo() * 16 + q * 512, r[q].x, r[q].y, r[q].z, r[q].w);
}
__device__ __forceinline__ void img_load(uint32_t (&v)[16], uint32_t tile, const Ctx& x) {
#pragma unroll
  for (int q = 0; q < 4; q++) lds128(tile + x.oo() * 16 + q * 512, v[4 * q], v[4 * q + 1], v[4 * q + 2], v[4 * q + 3]);
}
__device__ __forceinline__ void img_unpack(float* a, const uint32_t (&v)[16]) {
#pragma unroll
  for (int q = 0; q < 16; q++) { a[4 * (q & 7) + 2 * (q >> 3)] = lo16(v[q]); a[4 * (q & 7) + 2 * (q >> 3) + 1] = hi16(v[q]); }
}

template <int N>
__device__ __forceinline__ void stats_acc(const float* a, float (&t)[4]) {
#pragma unroll
  for (int i = 0; i < N; i++) { t[i & 2] += a[i]; t[(i & 2) + 1] = fmaf(a[i], a[i], t[(i & 2) + 1]); }
}
__device__ __forceinline__ void stats_send(float (&t)[4], int L, const Ctx& x) {
  const unsigned seq = seq4(get_tag<false>(x.sb), L);
#pragma unroll
  for (int q = 0; q < 4; q++) t[q] = qsum(t[q]);
  if (x.c == 0) st_pkt(&g_stats[x.m()][x.w][x.j()][x.warp * 8 + x.g], __float_as_uint(t[0]), __float_as_uint(t[1]), __float_as_uint(t[2]), (__float_as_uint(t[3]) & ~15u) | seq);
}
__device__ __forceinline__ void out_epilogue(const float (&acc)[64], uint4 (&r1)[4], uint4* g, int L, Ctx& x) {
  const uint32_t t0 = x.aslot(x.ra.s), t1 = x.aslot(x.ra.s + 1 == NA ? 0 : x.ra.s + 1);
  if (L == 3) {
#pragma unroll
    for (int p = 0; p < 8; p++) {
      stsm4(x.maddr(p < 4 ? t0 : t1, (p & 3) * 2), pack2(acc[8 * p], acc[8 * p + 1]), pack2(acc[8 * p + 2], acc[8 * p + 3]),
            pack2(acc[8 * p + 4], acc[8 * p + 5]), pack2(acc[8 * p + 6], acc[8 * p + 7]));
      if ((p & 3) == 3) { uint4 r[4]; __syncwarp(); rows_load(r, p < 4 ? t0 : t1, x); rows_store(r, g + (p >> 2) * 8, x); }
    }
  } else {
    auto pack16 = [&](uint4 (&r)[4], const float* a) {
#pragma unroll
      for (int q = 0; q < 4; q++) { const float* u = a + 16 * (q & 1) + (q & 2); r[q] = make_uint4(pack2(u[0], u[1]), pack2(u[4], u[5]), pack2(u[8], u[9]), pack2(u[12], u[13])); }
    };
    uint4 r0[4];
    pack16(r0, acc);
    img_store(r0, x.img(XBUF(L + 1), 0));
    publish(2, x);
    img_sts(r0, t0, x);
    sched_fence(x.sb);
    pack16(r1, acc + 32);
    img_sts(r1, t1, x);
    float t[4] = {0.f, 0.f, 0.f, 0.f}, u[4] = {0.f, 0.f, 0.f, 0.f};
    stats_acc<32>(acc, t); stats_acc<32>(acc + 32, u);
#pragma unroll
    for (int q = 0; q < 4; q++) t[q] += u[q];
    stats_send(t, L + 1, x);
    mbar_wait2(x.fullB(x.rb.s), x.rb.ph, x.fullB(x.rb.s + 1), x.rb.ph);
    fence_async_smem();
    asm volatile("bar.sync %0, %1;" ::"r"(L == 1 ? x.w + 1 : 3), "r"(L == 1 ? 128 : 256) : "memory");
  }
}

struct Stats { float rstd0, rstd1; };
__device__ __forceinline__ Stats load_stats(int half, const Ctx& x) {
  const float2 u = lds64f(x.sb + OFF_MR + half * 256 + (x.warp * 8 + x.g) * 8);
  return {u.x, u.y};
}

template <int NK>
__device__ __forceinline__ void hedgehog_scale(float* t, const Stats& st, const uint32_t* keep) {
#pragma unroll
  for (int q = 0; q < 16; q++) t[q] *= ((q & 2) ? st.rstd1 : st.rstd0) * LOG2E;
  float m[4];
#pragma unroll
  for (int q = 0; q < 4; q++) m[q] = fmaxf(fmaxf(fabsf(t[4 * q]), fabsf(t[4 * q + 1])), fmaxf(fabsf(t[4 * q + 2]), fabsf(t[4 * q + 3])));
  if (__builtin_expect(__any_sync(0xffffffffu, fmaxf(fmaxf(m[0], m[1]), fmaxf(m[2], m[3])) > 58.f), 0)) {
    float z[16 + NK];
#pragma unroll
    for (int q = 0; q < 16 + NK; q++) z[q] = q < 16 ? t[q & 15] : __uint_as_float(keep[q & 15]);
#pragma unroll 1
    for (int r = 0; r < 4; r += 2) {
      float hi = -INFINITY, lo = INFINITY;
#pragma unroll 1
      for (int i = 0; i < 16; i++) {
        const int k = (i & 6) * 2 + (i & 1) + r;
        const float v = z[k];
        if (i < 8) { hi = fmaxf(hi, v); lo = fminf(lo, v); }
        else z[k] = v - fminf(fmaxf(v, lo), hi);
        if (i == 7) {
#pragma unroll 1
          for (int d = 1; d <= 2; d++) { hi = fmaxf(hi, __shfl_xor_sync(0xffffffffu, hi, d)); lo = fminf(lo, __shfl_xor_sync(0xffffffffu, lo, d)); }
          const float mid = 0.5f * hi + 0.5f * lo;
          hi = fmaxf(hi - 58.f, mid); lo = fminf(lo + 58.f, mid);
        }
      }
    }
#pragma unroll
    for (int q = 0; q < 16; q++) t[q] = z[q];
  }
}
__device__ __forceinline__ void dual_exp(const float* t, uint32_t (&f)[18], int never) {
  float e[KSPLIT];
#pragma unroll
  for (int q = 0; q < KSPLIT; q++) e[q] = ex2(q < 16 ? t[q] : -t[q & 15]);
  while (never < 0) {
#pragma unroll
    for (int i = 0; i < KSPLIT; i += 4) asm volatile("ld.shared.v4.f32 {%0,%1,%2,%3}, [%4];" : "=f"(e[i]), "=f"(e[i + 1]), "=f"(e[i + 2]), "=f"(e[i + 3]) : "r"(never + i) : "memory");
    never += __float_as_int(e[0]);
  }
#pragma unroll
  for (int q = 0; q < KSPLIT; q += 2) f[q >> 1] = pack2(e[q], e[q + 1]);
#pragma unroll
  for (int q = KSPLIT; q < 32; q += 2) f[q >> 1] = q < 16 ? pack2(ex2(t[q]), ex2(t[q + 1])) : pack2(ex2(-t[q & 15]), ex2(-t[(q & 15) + 1]));
#pragma unroll
  for (int sg = 0; sg < 2; sg++) {
    const uint32_t* u = f + 8 * sg;
    const uint32_t a = add2(add2(u[0], u[2]), add2(u[4], u[6])), b = add2(add2(u[1], u[3]), add2(u[5], u[7]));
    f[16 + sg] = add2(__byte_perm(a, b, 0x5410), __byte_perm(a, b, 0x7632));
  }
}
__device__ __forceinline__ void dual_exp_rcp(const float* t, uint32_t (&f)[16]) {
#pragma unroll
  for (int q = 0; q < 8; q++) {
    const float a = ex2(t[2 * q]), b = ex2(t[2 * q + 1]), r = rcp(a * b);
    f[q] = pack2(a, b); f[8 + q] = pack2(r * b, r * a);
  }
}
__device__ __forceinline__ void cta_bar() { asm volatile("bar.sync 3, 256;" ::: "memory"); }

template <int N> __device__ __forceinline__ void pin(const uint32_t* v, uint32_t addr) {
#pragma unroll
  for (int i = 0; i < N; i += 4)
    asm volatile("{\n.reg .pred p;\nsetp.eq.u32 p, %0, 0;\n@p st.shared.v4.u32 [%0], {%1,%2,%3,%4};\n}" ::"r"(addr), "r"(v[i]), "r"(v[i + 1]), "r"(v[i + 2]), "r"(v[i + 3]) : "memory");
}

__device__ __forceinline__ void consumer(const Params& P, uint32_t sb, int w, unsigned vb) {
  Ctx x;
  x.w = w;
  x.ab = sb + OFF_A + w * 8192; x.da0 = desc_lo(SB + OFF_A, 16) + w * 512;
  x.lane = threadIdx.x & 31; x.warp = __shfl_sync(0xffffffffu, (threadIdx.x >> 5) & 3, 0); x.g = x.lane >> 2; x.c = x.lane & 3;
  x.goff = (cta_m(vb) * 128 + w) * 128 + cta_j(vb) * 16;
  asm volatile("" : "+r"(x.goff));
  x.elected = (threadIdx.x & 127) == 0;
  x.ra = {0, 0}; x.rb = {0, 0}; x.pa = x.pb = 0;
  {
    const uint32_t row = x.warp * 16 + (x.lane & 15);
    x.mrow = row * 128; x.mxor = row & 7; x.mhi = x.lane >> 4;
  }
  const int goff = x.goff;
  uint4 r1[4];
#pragma unroll
  for (int i = 0; i < 4; i++) r1[i] = make_uint4(0, 0, 0, 0);
  TSW(0);
  mbar_wait3(x.fullA(0), 0, x.fullB(0), 0);
#pragma unroll 1
  for (int L = 0; L < 4; L++) {
    float acc[64];
    constexpr uint32_t dcs = desc_lo(SB + OFF_CS, 0);
    if ((L & 1) == 0) {
    float kv[128];
    x.ha = L ? HA64 : HA128; x.k2 = L ? 32 : 4;
    gemm_issue<256, true, false>(kv, x, true); gemm_next<256>(x);
    {
      int i = 1;
      float t[4] = {0.f, 0.f, 0.f, 0.f};
#pragma unroll 1
      for (int seg = L >> 1; seg < 3; seg++) {
        const int end = seg < 2 ? (L == 0 ? 3 + 2 * (x.j() & 3) + seg : XA + 1) : 14 + L;
#pragma unroll 1
        while (true) {
          gemm_issue<256, false, false>(kv, x);
          if (++i == end) break;
          gemm_retire<256>(x, true);
          if (i == 5) TSL_(8);
          if (i == 11) TSL_(10);
        }
        if (seg < 2 && L == 0) {
          float a[32];
          const uint32_t tile = x.aslot(x.ra.s);
          load_x32(a, tile, 0, x); load_x32(a + 16, tile, 4, x);
          stats_acc<32>(a, t);
          if (seg == 1) { mbar_wait(sb + BAR_EPOCH, 0); stats_send(t, 0, x); }
          fence_async_smem();
          wg_bar(w);
        }
        if (seg == 1 && L > 0) { img_store(r1, x.img(XBUF(L), 1)); publish(3, x); }
        gemm_retire<256>(x, true);
      }
    }
      const Ring kt = x.ra;
      if (L == 0) adv<NA>(x.ra);
#pragma unroll 1
      for (int h = L; h < 2; h++) {
        float d[16];
        mbar_wait2(x.fullA(kt.s), kt.ph, sb + BAR_WPHI, 0);
        wgmma_fence();
#pragma unroll
        for (int q = 0; q < 2; q++) wgmma_ss_n32(d, x.da0 + kt.s * (SLOT / 16) + h * 4 + q * 2, desc_lo(SB + OFF_S + 4096, 512) + w * 256 + h * 128 + q * 64, q);
        wgmma_commit();
        gemm_issue<256, false, false>(kv, x);
        gemm_retire<256>(x, true);
        if (h) x.releaseA(kt.s);
        fence_regs(d);
        uint4* dst = &g_wf[1][x.j()][x.m()][w * 512 + (x.warp * 16 + x.g) * 8 + ((h * 4 + x.c) ^ x.g)];
        dst[0] = make_uint4(pack2(d[0], d[1]), pack2(d[4], d[5]), pack2(d[8], d[9]), pack2(d[12], d[13]));
        dst[64] = make_uint4(pack2(d[2], d[3]), pack2(d[6], d[7]), pack2(d[10], d[11]), pack2(d[14], d[15]));
      }
      const uint32_t dm = desc_lo(SB + OFF_MA, 0) + w * 64;
      mbar_wait2(sb + BAR_STAT, 0, sb + BAR_CS, 0);
      wgmma_fence();
      wgmma_r1_n256(kv, dm, dcs + 96, 1);
      wgmma_commit();
      const Stats st = load_stats(w, x);
      if (PW & 1) mbar_wait2(x.fullA(x.ra.s), x.ra.ph, x.fullB(x.rb.s), x.rb.ph);
      wgmma_wait<0>();
      fence_regs(kv);
      gemm_release<256>(x, true);
      TSL_(2);
      uint32_t P0[32], P1[32], PH[32];
#pragma unroll
      for (int t = 0; t < 16; t++) { P0[t] = pack2(kv[4 * t] * st.rstd0, kv[4 * t + 1] * st.rstd0); P1[t] = pack2(kv[4 * t + 2] * st.rstd1, kv[4 * t + 3] * st.rstd1); }
      pin<16>(P0, x.mrow + 16);
      {
#pragma unroll
        for (int q = 0; q < 4; q++) sts128((x.warp < 3 ? sb + OFF_T + w * 12288 + x.warp * 4096 : sb + OFF_S + 16384 + w * 2048) + x.lane * 16 + q * 512, P1[4 * q], P1[4 * q + 1], P1[4 * q + 2], P1[4 * q + 3]);
      }
      wgmma_fence();
      wgmma_r1_n128(acc, dm, dcs, 0);
      gemm_issue<128, false, false>(acc, x, PW & 1); gemm_next<128>(x);
      TSL_(3);
#pragma unroll
      for (int s = 0; s < 4; s++) {
#pragma unroll
        for (int t = 16 + 8 * (s & 1); t < 24 + 8 * (s & 1); t++) {
          if (s < 2) P1[t] = movm(pack2(kv[4 * t + 2] * st.rstd1, kv[4 * t + 3] * st.rstd1));
          else P0[t] = movm(pack2(kv[4 * t] * st.rstd0, kv[4 * t + 1] * st.rstd0));
        }
        if (s < 3) { gemm_issue<128, false, false>(acc, x); gemm_retire<128>(x, true); }
        if (s == 1) {
          if (x.warp < 3) {
#pragma unroll
            for (int q = 4; q < 8; q++) sts128(sb + OFF_T + w * 12288 + x.warp * 4096 + x.lane * 16 + q * 512, P1[4 * q], P1[4 * q + 1], P1[4 * q + 2], P1[4 * q + 3]);
          } else {
            uint4* dst = &g_halo[x.m()][x.j()][w][x.lane];
#pragma unroll
            for (int q = 0; q < 8; q++) dst[q * 32] = make_uint4(P1[4 * q], P1[4 * q + 1], P1[4 * q + 2], P1[4 * q + 3]);
          }
          publish(4, x);
          gemm_issue<128, false, false>(acc, x);
          gemm_retire<128>(x, true);
        }
      }
      TSL_(4);
      gemm_run<false>(acc, x, 10, 0);
      gemm_issue<128, false, false>(acc, x);
      {
        wg_bar(w);
        uint32_t tr = sb + OFF_T + w * 12288 + (x.warp - 1) * 4096;
        if (x.warp == 0) {
          tr = x.m() > 0 ? sb + OFF_S + 8192 + w * 4096 : tr + 4096;
          if (x.m() > 0) mbar_wait(sb + BAR_HALO, L >> 1);
        }
#pragma unroll
        for (int q = 0; q < 8; q++) lds128(tr + x.lane * 16 + q * 512, PH[4 * q], PH[4 * q + 1], PH[4 * q + 2], PH[4 * q + 3]);
      }
      gemm_retire<128>(x, false);
      gemm_end(acc, x);
      TSL_(5);
      const bool first = (x.m() == 0) && (x.warp == 0);
      const bool hi0 = 2 * x.c > x.g, hi1 = 2 * x.c + 1 > x.g;
      const uint32_t mhi = (hi0 ? 0xFFFFu : 0u) | (hi1 ? 0xFFFF0000u : 0u);
      const float sc0 = st.rstd0 * (0.17677669529663687f * LOG2E), sc1 = st.rstd1 * (0.17677669529663687f * LOG2E);
#pragma unroll
      for (int hp = 0; hp < 2; hp++) {
        const uint32_t tile = x.aslot(x.held(hp));
        uint32_t px[2], py[2];
        float s[2][3][4];
#pragma unroll
        for (int u = 0; u < 2; u++) {
#pragma unroll
          for (int q = 0; q < 12; q++) s[u][q >> 2][q & 3] = 0.f;
#pragma unroll
          for (int ks = 0; ks < 2; ks++) {
            const int t = 8 * hp + 4 * u + 2 * ks;
            const uint32_t a0 = pack2(acc[4 * t], acc[4 * t + 1]), a1 = pack2(acc[4 * t + 2], acc[4 * t + 3]);
            const uint32_t a2 = pack2(acc[4 * t + 4], acc[4 * t + 5]), a3 = pack2(acc[4 * t + 6], acc[4 * t + 7]);
            mma16816(s[u][0], a0, a1, a2, a3, PH[t], PH[t + 1]);
            mma16816(s[u][1], a0, a1, a2, a3, P0[t], P0[t + 1]);
            mma16816(s[u][2], a0, a1, a2, a3, P1[t], P1[t + 1]);
          }
        }
        float e[2][4], r[2][2];
#pragma unroll
        for (int u = 0; u < 2; u++) {
          e[u][0] = (hi0 ? s[u][0][0] : s[u][1][0]) * sc0; e[u][1] = (hi1 ? s[u][0][1] : s[u][1][1]) * sc0;
          e[u][2] = (hi0 ? s[u][1][2] : s[u][2][2]) * sc1; e[u][3] = (hi1 ? s[u][1][3] : s[u][2][3]) * sc1;
          if (first) { if (hi0) e[u][0] = -1e30f; if (hi1) e[u][1] = -1e30f; }
          r[u][0] = fmaxf(e[u][0], e[u][1]); r[u][1] = fmaxf(e[u][2], e[u][3]);
        }
#pragma unroll
        for (int d = 1; d <= 2; d++)
#pragma unroll
          for (int q = 0; q < 4; q++) r[q >> 1][q & 1] = fmaxf(r[q >> 1][q & 1], __shfl_xor_sync(0xffffffffu, r[q >> 1][q & 1], d));
#pragma unroll
        for (int u = 0; u < 2; u++) {
#pragma unroll
          for (int q = 0; q < 4; q++) e[u][q] = ex2(e[u][q] - r[u][q >> 1]);
          r[u][0] = e[u][0] + e[u][1]; r[u][1] = e[u][2] + e[u][3];
        }
#pragma unroll
        for (int d = 1; d <= 2; d++)
#pragma unroll
          for (int q = 0; q < 4; q++) r[q >> 1][q & 1] += __shfl_xor_sync(0xffffffffu, r[q >> 1][q & 1], d);
#pragma unroll
        for (int u = 0; u < 2; u++) {
          const float rx = rcp(r[u][0]), ry = rcp(r[u][1]);
          px[u] = pack2(e[u][0] * rx, e[u][1] * rx); py[u] = pack2(e[u][2] * ry, e[u][3] * ry);
        }
        uint32_t o[8][2];
        uint4 ro[4];
#pragma unroll
        for (int q = 0; q < 8; q++) {
          float d[4] = {0.f, 0.f, 0.f, 0.f};
          const int t = 16 + 8 * hp + q, u = q >> 2;
          mma16816(d, px[u] & mhi, 0u, px[u] & ~mhi, py[u] & mhi, PH[t], P0[t]);
          mma1688(d, 0u, py[u] & ~mhi, P1[t]);
          o[q][0] = pack2(d[0], d[1]); o[q][1] = pack2(d[2], d[3]);
        }
#pragma unroll
        for (int q = 0; q < 4; q++) ro[q] = make_uint4(o[4 * (q & 1)][q >> 1], o[4 * (q & 1) + 1][q >> 1], o[4 * (q & 1) + 2][q >> 1], o[4 * (q & 1) + 3][q >> 1]);
        img_store(ro, x.img(0, hp));
        publish(hp, x);
        uint32_t xr[16];
        if (L) img_load(xr, tile, x);
        else {
#pragma unroll
          for (int q = 0; q < 4; q++) {
            uint32_t v[4];
            ldsm4(x.maddr(tile, 2 * q), v);
            xr[2 * q] = v[0]; xr[8 + 2 * q] = v[1]; xr[2 * q + 1] = v[2]; xr[9 + 2 * q] = v[3];
          }
          __syncwarp();
        }
        img_sts(ro, tile, x);
        img_unpack(acc + 32 * hp, xr);
      }
    } else {
      float kv[128];
      float (&kv0)[64] = reinterpret_cast<float (&)[64]>(kv[0]);
      float (&kv1)[64] = reinterpret_cast<float (&)[64]>(kv[64]);
      auto mma8 = [&](uint32_t as, uint32_t bs, int i, bool fence) {
        const uint32_t da = desc_lo(SB + OFF_A, 16) + as * (SLOT / 16), db = desc_lo(SB + OFF_B, 8192) + bs * (SLOT / 16);
        if (fence) wgmma_fence();
#pragma unroll
        for (int k = 0; k < 4; k++) {
          wgmma_ss_n128(kv0, da + (k >> 1) * 32 + (k & 1) * 2, HA64, db + 128 * k, i + k);
          wgmma_ss_n128(kv1, da + 512 + (k >> 1) * 32 + (k & 1) * 2, HA64, db + 128 * k, i + k);
        }
        wgmma_commit();
      };
      constexpr uint32_t dm = desc_lo(SB + OFF_MB, 0);
      auto relB = [&](uint32_t s) { mbar_arrive_n(sb + BAR_EMPTYB + s * 8, 2); };
      auto skip = [&]() {
#pragma unroll
        for (int q = 0; q < 6 - NJ; q++) adv<NA>(x.ra);
        x.rb.s = w ? (2 + NJ) % 6 : 4;
        if (!w && NJ < 4) x.rb.ph ^= 1;
      };
      static_assert(NA == 5 && NB == 6, "ring arithmetic");
      mma8(x.ra.s, x.rb.s + w, 0, true);
      if (XR == 0) { img_store(r1, x.img(XBUF(L), 1)); publish(3, x); }
      gemm_next<256>(x);
#pragma unroll 1
      for (int i = 1; i < NJ; i++) {
        mbar_wait2(x.fullA(x.ra.s), x.ra.ph, x.fullB(x.rb.s + w), x.rb.ph);
        mma8(x.ra.s, x.rb.s + w, 1, true);
        if (i == XR) { img_store(r1, x.img(XBUF(L), 1)); publish(3, x); }
        wgmma_wait<1>();
        if (x.elected) { x.releaseA(x.pa); relB(x.pb + w); }
        gemm_next<256>(x);
      }
      if (w) {
        wgmma_wait<0>();
        if (x.elected) { x.releaseA(x.pa); relB(x.pb + 1); }
        skip();
        asm volatile("bar.sync 7, 256;" ::: "memory");
      }
      TSL_(8);
      {
        const int t = lane_id() + 32 * x.warp;
        uint32_t mask = t < 2 ? ((w ? (t ? 0xFF3Fu : 0x3FFFu) : 0xFFFFu) >> (NJ - 1)) & (w ? ~1u : ~0u) : 0u, cnt = 1 + t;
        bool ready = false;
#pragma unroll 1
        for (int i = NJ; i < 16; i++) {
          if (!ready) mbar_wait2(x.fullA(x.ra.s), x.ra.ph, x.fullB(x.rb.s), x.rb.ph);
          mma8(x.ra.s, x.rb.s, 1, true);
          const uint32_t bar = sb + (t ? BAR_EMPTYB + x.pb * 8 : BAR_EMPTYA + x.pa * 8);
          gemm_next<128>(x);
          if (w && (i | 4) == 15) x.rb.s = 4;
          ready = mbar_probe2(x.fullA(x.ra.s), x.ra.ph, x.fullB(x.rb.s), x.rb.ph);
          wgmma_wait<1>();
          if (mask & 1) mbar_arrive_n(bar, cnt);
          mask >>= 1; cnt = 2;
          if (i == 8 && w) asm volatile("bar.arrive 9, 256;" ::: "memory");
          if (i == 9) TSL_(10);
        }
        mbar_wait2(sb + BAR_STAT, 1, sb + BAR_CS + 8, 0);
        wgmma_fence();
        wgmma_r1_n128(kv0, dm, dcs + 96 + 96 * w, 1);
        wgmma_r1_n128(kv1, dm + 64, dcs + 96 + 96 * w, 1);
        wgmma_commit();
        if (w == 0) asm volatile("bar.arrive 7, 256;" ::: "memory");
        wgmma_wait<1>();
        if (mask & 1) mbar_arrive_n(sb + (t ? BAR_EMPTYB + x.pb * 8 : BAR_EMPTYA + x.pa * 8), 2);
      }
      const Stats s0 = load_stats(0, x), s1 = load_stats(1, x), st = w ? s1 : s0;
      if (w == 0) skip();
      const uint32_t h0 = x.held(0), h1 = x.held(1);
      auto vreg = [&](int ks) { return ks < 6 ? OFF_A + (ks < 3 ? h0 * SLOT : h1 * SLOT - 15360) + ks * 5120 : OFF_S + 2048 + ks * 5120; };
      uint32_t tV[2], uu[4];
#pragma unroll
      for (int hf = 0; hf < 2; hf++) {
        tV[hf] = sb + vreg(4 * hf + x.warp) + ((x.lane >> 3) & 1) * 2560 + (x.lane & 7) * 16 + x.mhi * 128;
        const float i0 = rcp(hf ? s1.rstd0 : s0.rstd0), i1 = rcp(hf ? s1.rstd1 : s0.rstd1);
        const uint32_t h = pack2(i0, i1);
        uu[2 * hf] = pack2(lo16(h), i0 - lo16(h)); uu[2 * hf + 1] = pack2(hi16(h), i1 - hi16(h));
        asm volatile("" : "+r"(tV[hf]), "+r"(uu[2 * hf]), "+r"(uu[2 * hf + 1])::"memory");
      }
      wgmma_wait<0>();
      fence_regs(kv);
      TSL_(2);
      if (w == 0) {
        uint32_t f[2][18], ad[4];
#pragma unroll
        for (int q = 0; q < 18; q++) f[1][q] = 0u;
#pragma unroll
        for (int q = 0; q < 4; q++) ad[q] = x.maddr(sb + OFF_S, 2 * q);
        auto norm = [&](int un) {
          uint32_t* u = f[un & 1];
          const Stats& sn = (un & 2) ? s1 : s0;
#pragma unroll
          for (int sg = 0; sg < 2; sg++) {
            uint32_t v = u[16 + sg];
            v = add2(v, __shfl_xor_sync(0xffffffffu, v, 1)); v = add2(v, __shfl_xor_sync(0xffffffffu, v, 2));
            const float a = rcp(lo16(v)) * sn.rstd0, b = rcp(hi16(v)) * sn.rstd1;
            const uint32_t r0 = pack2(a, a), r1_ = pack2(b, b);
#pragma unroll
            for (int q = 8 * sg; q < 8 * sg + 8; q++) u[q] = mul2(u[q], (q & 1) ? r1_ : r0);
#pragma unroll
            for (int q = 2 * sg; q < 2 * sg + 2; q++) stsm4(ad[q] + (un & 1) * SLOT + (un >> 1) * 8192, u[4 * q], u[4 * q + 1], u[4 * q + 2], u[4 * q + 3]);
          }
        };
        auto unit = [&](int un) { return kv + ((un >> 1) & 1) * 64 + (un & 1) * 16 + (un >> 2) * 32; };
        hedgehog_scale<0>(kv, s0, nullptr);
#pragma unroll 1
        for (int it = 0;; it++) {
#pragma unroll
          for (int un = 0; un < 4; un++) {
            if (un == 1) {
              if (it) asm volatile("bar.sync 9, 256;" ::: "memory");
#pragma unroll
              for (int q = 0; q < 4; q++) ad[q] -= it * (OFF_S - OFF_B - 2 * SLOT);
            }
            norm((un + 3) & 3);
            dual_exp(unit(un), f[un & 1], x.goff);
            hedgehog_scale<KEEP>(unit(un + 1), ((un + 1) & 2) ? s1 : s0, f[(un + 1) & 1]);
          }
          if (it) break;
#pragma unroll
          for (int q = 0; q < 32; q++) {
            asm volatile("mov.b32 %0, %1;" : "=f"(kv[q]) : "f"(kv[q + 32]));
            asm volatile("mov.b32 %0, %1;" : "=f"(kv[q + 64]) : "f"(kv[q + 96]));
            if (q < 16) kv[32 + q] = 0.f;
          }
        }
        norm(3);
        TSL_(3);
      } else {
        wg_bar(w);
#pragma unroll
        for (int hf = 0; hf < 2; hf++) {
          stsm4(tV[hf] + 512 + x.mhi * 512, uu[2 * hf], uu[2 * hf + 1], uu[2 * hf], uu[2 * hf + 1]);
          stsm4(tV[hf] + 1792 + x.mhi * 512, uu[2 * hf], uu[2 * hf + 1], uu[2 * hf], uu[2 * hf + 1]);
#pragma unroll
          for (int q = 0; q < 8; q++) {
            const float* u = kv + 64 * hf + 8 * q;
            stsm4(tV[hf] + (q >> 1) * 640 + (q & 1) * 256, pack2(u[0], u[1]), pack2(u[2], u[3]), pack2(u[4], u[5]), pack2(u[6], u[7]));
          }
        }
        TSL_(3);
      }
      {
        float d[2][20];
        uint4* dst = &g_kvpart[x.j()][w * 4 + x.warp][0][x.m() * 32 + x.lane];
        unsigned* dz = reinterpret_cast<unsigned*>(&g_kvpart[x.j()][w * 4 + x.warp][x.c & 1][512]) + x.m() * 8 + x.g;
        asm volatile("" : "+l"(dst), "+l"(dz)::"memory");
        fence_async_smem();
        cta_bar();
        TSL_(11);
        uint32_t pk[9];
        auto prep = [&](float (&u)[20]) {
          fence_regs(u);
#pragma unroll
          for (int q = 0; q < 8; q++) pk[q] = pack2(u[((q >> 1) & 2) + 4 * (q & 3)], u[((q >> 1) & 2) + 4 * (q & 3) + 1]);
          pk[8] = __float_as_uint((x.c & 1) ? u[18] + u[19] : u[16] + u[17]);
#pragma unroll
          for (int q = 0; q < 9; q += 4) pk[q] = (pk[q] & ~1u) | (L == 1);
        };
        auto send = [&](int hp) {
          st_v4(dst + hp * 16 * 544, pk[0], pk[1], pk[2], pk[3]); st_v4(dst + (hp * 16 + 1) * 544, pk[4], pk[5], pk[6], pk[7]);
          st_flag(dz + hp * 16 * 544 * 4, pk[8]);
        };
        wgmma_fence();
#pragma unroll
        for (int q = 0; q < 17; q++) {
          if (q < 16) wgmma_ss_n40_tt(d[q >> 3], desc_lo(SB + (q < 8 ? OFF_S : OFF_B + 2 * SLOT), 1024) + w * (SLOT / 16) + 128 * (q & 7), desc_lo(SB + vreg(q & 7), 2560) + (w + (q >> 3) * 2) * 40, q & 7);
          else wgmma_r1_n128(acc, dm + w * 64, dcs, 0);
          if (q == 7 || q == KVS || q == 16) wgmma_commit();
          if (q == KVS) { wgmma_wait<1>(); prep(d[0]); send(0); mbar_wait2(x.fullA(x.ra.s), x.ra.ph, x.fullB(x.rb.s), x.rb.ph); wgmma_fence(); }
        }
        gemm_issue<128, false>(acc, x, true); gemm_next<128>(x);
        wgmma_wait<1>();
        x.releaseA(h0); x.releaseA(h1); x.releaseB(2); x.releaseB(3);
        if (x.lane == 0) mbar_arrive(sb + BAR_SIGT);
        prep(d[1]);
        TSL_(4);
#pragma unroll 1
        for (int seg = 0; seg < 2; seg++) {
          const int n0 = w ? PS1 : PS0;
          gemm_run(acc, x, seg ? 15 - n0 : n0, seg, seg ? L : 0);
          if (seg == 0) send(1);
        }
      }
      gemm_end(acc, x);
      TSL_(5);
      {
        float dp[2][20], dn[2][20];
        uint32_t f[4][16];
        auto mma = [&](int h) {
          if (!(h & 1)) mbar_wait(sb + BAR_KV + h * 4, L >> 1);
          if (h == 0) TSL_(9);
          const uint32_t db = desc_lo(SB + OFF_S + h * 5120, 128);
          const uint32_t (&a)[16] = f[h];
          wgmma_fence();
          wgmma_rs_n40(dp[h & 1], a[0], a[1], a[2], a[3], db, 0);
          wgmma_rs_n40(dn[h & 1], a[8], a[9], a[10], a[11], db + 160, 0);
          wgmma_rs_n40(dp[h & 1], a[4], a[5], a[6], a[7], db + 80, 1);
          wgmma_rs_n40(dn[h & 1], a[12], a[13], a[14], a[15], db + 240, 1);
          wgmma_commit();
        };
        uint32_t xr[16];
        auto fin = [&](int h) {
          const uint32_t tile = x.aslot(x.held(h >> 1));
          if (!(h & 1)) img_load(xr, tile, x);
          float (&u)[20] = dp[h & 1];
          float (&v)[20] = dn[h & 1];
          fence_regs(u); fence_regs(v);
#pragma unroll
          for (int r = 0; r < 2; r++) {
            float cc = u[17 + 2 * r] * rcp(v[17 + 2 * r]);
            const float aa = rcp(fmaf(v[16 + 2 * r], cc, fmaf(u[17 + 2 * r], 1e-6f, u[16 + 2 * r])));
            cc *= aa;
            uint32_t o[4];
#pragma unroll
            for (int t = 0; t < 4; t++) o[t] = pack2(fmaf(u[4 * t + 2 * r], aa, v[4 * t + 2 * r] * cc), fmaf(u[4 * t + 2 * r + 1], aa, v[4 * t + 2 * r + 1] * cc));
            x.img(0, h >> 1)[r * 64 + (h & 1) * 32] = make_uint4(o[0], o[1], o[2], o[3]);
            sts128(tile + r * 1024 + (h & 1) * 512 + x.oo() * 16, o[0], o[1], o[2], o[3]);
          }
          if (h & 1) { publish(h >> 1, x); img_unpack(acc + 16 * (h - 1), xr); }
        };
        auto scale = [&](int h) { hedgehog_scale<0>(acc + 16 * h, st, nullptr); };
        auto ex = [&](int h) { dual_exp_rcp(acc + 16 * h, f[h]); };
        scale(0);
        ex(0); scale(1); mma(0);
        ex(1); wgmma_wait<0>(); fin(0); scale(2); mma(1);
        ex(2); wgmma_wait<0>(); fin(1); scale(3); mma(2);
        ex(3); wgmma_wait<0>(); fin(2); mma(3);
        wgmma_wait<0>(); fin(3);
      }
    }
    if (PW & 2) { mbar_wait(x.fullB(x.rb.s), x.rb.ph); fence_regs(acc); }
    fence_async_smem();
    wg_bar(w);
    TSL_(6);
    rewind2<NA>(x.ra);
    gemm_issue<128, false>(acc, x, PW & 2); gemm_next<128>(x);
#pragma unroll 1
    for (int seg = L >= TSL ? 0 : 1; seg < 2; seg++) {
      gemm_run(acc, x, L >= TSL ? (seg ? TSK : 15 - TSK) : 15, seg);
      if (L >= TSL) {
        if (seg == 0 && w == 1) asm volatile("bar.sync 6, 256;" ::: "memory");
        if (seg == 1 && w == 0) asm volatile("bar.arrive 6, 256;" ::: "memory");
      }
    }
    gemm_end(acc, x);
    TSL_(7);
    rewind2<NA>(x.ra);
    out_epilogue(acc, r1, P.out + goff, L, x);
    TSL_(13);
  }
}

typedef unsigned long long u64;
template <class T> __device__ __forceinline__ T* early(T* p) { return (T*)__shfl_xor_sync(0xffffffffu, (u64)p, 1); }
__device__ __forceinline__ void pause(uint32_t GAP) {
  if (GAP) { uint32_t t0, t; asm volatile("mov.u32 %0, %%clock;" : "=r"(t0)); do { asm volatile("mov.u32 %0, %%clock;" : "=r"(t)); } while (t - t0 < GAP); }
}
__device__ __forceinline__ u64 order_table(int kind, int j) {
  const int i = threadIdx.x & 15;
  const unsigned v = (unsigned)(kind == 2 ? q_order(i, j) : kv_order(i, j, kind)) << (4 * (i & 7));
  return (u64)__reduce_or_sync(0xffffffffu, i < 8 ? 0u : v) << 32 | __reduce_or_sync(0xffffffffu, i < 8 ? v : 0u);
}

__device__ __forceinline__ void b_producer(const Params& P, uint32_t sb, unsigned vb) {
  const int j = cta_j(vb);
  const u64 t0 = order_table(0, j), t1 = order_table(1, j), t2 = order_table(2, j);
  Ring r = {PRE_B % NB, PRE_B < NB};
#pragma unroll 1
  for (int sg = 0; sg < 20; sg++) {
    const int L = sg / 5, p = sg - 5 * L, wt = L & 1;
    int n = p >= 3 ? 16 : (wt ? (p ? 16 - NJ : 2 * NJ) : (p ? 0 : (L ? 32 : 32 - PRE_B)));
    u64 tab = p == 3 ? t2 : (sg == 0 ? t0 >> (2 * PRE_B) : (p == 1 || p == 2 ? t1 >> (4 * NJ) : t1));
    const CUtensorMap* tm = p == 4 ? &P.mwo[wt] : &P.mw[wt ? 1 : L];
    const uint4* img = &g_wf[p != 3][j][0][0];
    int col = (p >= 3 ? 0 : (p == 2 ? 2048 : 1024)) + 128 * j;
    const int flip = p == 0 ? 3072 : 0;
    const bool fold = wt && p != 4;
    if (sg == 5 || sg == 8) { mbar_wait(sb + (sg == 5 ? BAR_WPHI : BAR_CS + 8), sg == 5); fence_async_global(); }
    if (DEFER && p == 4 && ((DEFL >> wt) & 1)) {
      Ring q = r;
      for (int u = 0; u < DEFER; u++) adv<NB>(q);
      mbar_wait(sb + BAR_EMPTYB + q.s * 8, q.ph);
    }
#pragma unroll 1
    for (; n > 0; n--) {
      const int kb = (int)tab & 15;
      mbar_wait(sb + BAR_EMPTYB + r.s * 8, r.ph);
      if (elect()) {
        mbar_expect_tx(sb + BAR_FULLB + r.s * 8, SLOT);
        if (fold && col < 2048) bulk_load(sb + OFF_B + r.s * SLOT, img + kb * 1024, SLOT, sb + BAR_FULLB + r.s * 8);
        else tma_load_w(sb + OFF_B + r.s * SLOT, tm, sb + BAR_FULLB + r.s * 8, col, kb);
      }
      adv<NB>(r);
      if (p == 2 && (n | 4) == 5) r.s = 4;
      col ^= flip;
      if (!(col & flip & 2048)) tab >>= 4;
    }
  }
}

__device__ __forceinline__ void a_loader(const Params& P, uint32_t sb, unsigned vb) {
  const int j = cta_j(vb), m = cta_m(vb);
  const u64 t1 = order_table(1, j), t2 = order_table(2, j);
  Ring r = {PRE_A % NA, PRE_A < NA};
  {
    u64 tab = order_table(0, j) >> (4 * PRE_A);
#pragma unroll 1
    for (int i = PRE_A; i < 33; i++) {
      if (i == 17) tab = t2;
      mbar_wait(sb + BAR_EMPTYA + r.s * 8, r.ph);
      if (elect()) {
        mbar_expect_tx(sb + BAR_FULLA + r.s * 8, SLOT);
        if (i != 14) tma_load_3d(sb + OFF_A + r.s * SLOT, &P.mx, sb + BAR_FULLA + r.s * 8, ((int)tab & 15) * 64, m * 64, 0);
        else {
          tma_load_w(sb + OFF_A + r.s * SLOT, &P.mw[1], sb + BAR_FULLA + r.s * 8, 1024 + 128 * j, m);
          mbar_expect_tx(sb + BAR_WPHI, 8192); tma_load_2d(sb + OFF_S + 4096, &P.mwphi, sb + BAR_WPHI, 0, 128 * j);
        }
        if (i == PF0 || i == PF1 || i == PF2)
          tma_prefetch_w(i == PF0 ? &P.mw[1] : &P.mwo[i == PF2], (i == PF0 ? 1024 : 0) + 128 * j, m);
      }
      adv<NA>(r);
      if (i != 14) tab >>= 4;
    }
  }
  const unsigned tag = get_tag(sb);
  unsigned seen = 0;
#pragma unroll 1
  for (int sg = 0; sg < 27; sg++) {
    const int L = sg >> 3, p = sg & 7, q = p >= 3 ? p - 3 : p;
    if (p == 0 && (L & 1)) {
#pragma unroll 1
      for (int h = 0; h < 2; h++) {
        poll_flags(&g_kvfflag[L >> 1][j][h][0], 8, 0xFFu, tag);
        if (elect()) { mbar_expect_tx(sb + BAR_KV + h * 8, 10240); bulk_load(sb + OFF_S + h * 10240, &g_kvfin[j][8 * h][0], 10240, sb + BAR_KV + h * 8); }
      }
      TS(4, 14 + L);
    }
    int n = q == 0 ? 4 : (q == 1 ? 3 : (q == 2 ? 7 : (q == 3 ? ((L & 1) ? 0 : 16 - NJ) : 16)));
    u64 tab = q == 4 ? t2 : t1 >> (q == 0 ? 8 : (q == 1 ? 24 : (q == 2 ? 36 : 4 * NJ)));
    const uint4* img = &g_img[p >= 3 ? XBUF(L + 1) : 0][m][0][0];
    const uint32_t gap = p == 0 ? G0 : (p == 3 ? G3 : (q < 3 ? G1 : G4));
    bool poll = q == 0 || q == 2 || (q == 1 && seen != 0xFFFFFFFFu);
#pragma unroll 1
    for (; n > 0; n--) {
      const uint4* src = img + ((int)tab & 15) * 1024;
      src = early(src);
      mbar_wait(sb + BAR_EMPTYA + r.s * 8, r.ph);
      if (elect()) mbar_expect_tx(sb + BAR_FULLA + r.s * 8, SLOT);
      if (poll) {
        const int lane = threadIdx.x & 31, nn = p >= 3 ? PNX : PNO;
        const unsigned* f = (p >= 3 ? &g_xflag[L + 1][0][m][0] : &g_oflag[L][0][m][0]) + (q == 2 ? 512 : 0) + (lane & 7);
        if (q == 0 || (PN2 && q == 2)) f += (((lane >> 3) & (nn - 1)) - (m & (nn - 1))) * 32;
        const unsigned need = q == 0 ? 0x0F0F0F0Fu << (~j & 4) : 0xFFFFFFFFu;
        if (q == 0) mbar_wait(sb + BAR_SIGP + (p ? 16 : 0), L & 1);
        int it = 0;
        do { seen = __ballot_sync(0xffffffffu, ld_flag(f) == tag); if (++it > (1 << 22)) __trap(); } while ((seen & need) != need);
        if (q == 0) TS(2, p == 0 ? 5 + L * 8 : 9 + L * 8);
        poll = false;
      }
      if (elect()) bulk_load(sb + OFF_A + r.s * SLOT, src, SLOT, sb + BAR_FULLA + r.s * 8);
      adv<NA>(r);
      tab >>= 4;
      pause(gap);
    }
  }
}

__device__ __forceinline__ uint2 sum_packets(float (&a)[8], uint32_t addr, int n) {
  uint2 ok = make_uint2(~0u, 0u);
#pragma unroll 1
  for (int b = 0; b < n; b += KB) {
    uint4 v[KB];
#pragma unroll
    for (int u = 0; u < KB; u++) lds128(addr + (b + u) * 512, v[u].x, v[u].y, v[u].z, v[u].w);
#pragma unroll
    for (int u = 0; u < KB; u++) {
      ok.x &= v[u].x; ok.y |= v[u].x;
      a[0] += lo16(v[u].x); a[1] += hi16(v[u].x); a[2] += lo16(v[u].y); a[3] += hi16(v[u].y);
      a[4] += lo16(v[u].z); a[5] += hi16(v[u].z); a[6] += lo16(v[u].w); a[7] += hi16(v[u].w);
    }
  }
  return ok;
}
__device__ __forceinline__ void helper_bar() { asm volatile("bar.sync 4, 64;" ::: "memory"); }
__device__ __forceinline__ void helper(const Params& P, uint32_t sb, int w, unsigned vb) {
  const int j = cta_j(vb), m = cta_m(vb);
  if (w == 0) {
    if (elect()) {
      const unsigned t = atomicAdd(&g_ctr, 1u) / NCTA + 1u;
      asm volatile("st.shared.u32 [%0], %1;" ::"r"(sb + OFF_EPOCH), "r"(t) : "memory");
      mbar_arrive(sb + BAR_EPOCH);
    }
  }
  const unsigned tag = get_tag(sb);
  mbar_wait(sb + BAR_FULLB + 24, 0);
  const uint32_t stg = sb + OFF_T + w * 12288, stb = sb + BAR_STG + w * 24;
  Ring rs = {0, 0};
  auto cs_image = [&](int L) {
      const int lane = lane_id();
      poll_flags(&g_csflag[L][j][0], 16, L ? CSNEED : 0xFFFu, tag);
#pragma unroll
      for (int p = 0; p < 3; p++) {
        const uint4 u = ldcg4(&g_cs[L][0][p * 1024 + 128 * j + lane * 4]), v = ldcg4(&g_cs[L][1][p * 1024 + 128 * j + lane * 4]);
        const float c0 = __uint_as_float(u.x) + __uint_as_float(v.x), c1 = __uint_as_float(u.y) + __uint_as_float(v.y);
        const float c2 = __uint_as_float(u.z) + __uint_as_float(v.z), c3 = __uint_as_float(u.w) + __uint_as_float(v.w);
        const uint32_t h0 = pack2(c0, c1), h1 = pack2(c2, c3), dst = sb + OFF_CS + (p * 16 + (lane >> 1)) * 96 + L * 48 + (lane & 1) * 8;
        sts64(dst, h0, h1); sts64(dst + 16, pack2(c0 - lo16(h0), c1 - hi16(h0)), pack2(c2 - lo16(h1), c3 - hi16(h1))); sts64(dst + 32, h0, h1);
        if (L == 0) { sts64(dst + 48, 0u, 0u); sts64(dst + 64, 0u, 0u); sts64(dst + 80, 0u, 0u); }
      }
      if (L == 0 && lane < 4) sts64(sb + OFF_CS + 4608 + lane * 8, 0u, 0u);
      fence_async_smem();
      __syncwarp();
      if (elect()) mbar_arrive(sb + BAR_CS + L * 8);
      TS(4, 2 + L * 2);
  };
#pragma unroll 1
  for (int L = 0; L < 4; L++) {
    const int lane = lane_id();
    if (L == 0) {
      {
        const int wt = m >= 12, col = ((0x2021 >> (m & 12)) & 3) * 1024 + 128 * j + (m & 3) * 32;
        const CUtensorMap* tm = &P.mcs[wt];
        if (D2 && wt) __nanosleep(D2);
        constexpr int nb = 8;
        float a[8] = {0.f, 0.f, 0.f, 0.f, 0.f, 0.f, 0.f, 0.f};
#pragma unroll 1
        for (int b = -3; b < nb; b++) {
          if (b >= 0) {
            mbar_wait(stb + rs.s * 8, rs.ph);
            sum_packets(a, stg + rs.s * 4096 + lane * 16, 8);
            fence_async_smem();
            __syncwarp();
          }
          const uint32_t sl = b < 0 ? (rs.s + b + 3) % 3 : rs.s;
          if (b + 3 < nb && elect()) { mbar_expect_tx(stb + sl * 8, 4096); tma_load_2d(stg + sl * 4096, tm, stb + sl * 8, col, (w * (16 - nb) + b + 3) * 64); }
          if (b >= 0) adv<3>(rs);
        }
#pragma unroll
        for (int u = 0; u < 8; u++) {
          a[u] += __shfl_xor_sync(0xffffffffu, a[u], 4); a[u] += __shfl_xor_sync(0xffffffffu, a[u], 8); a[u] += __shfl_xor_sync(0xffffffffu, a[u], 16);
        }
        if (lane < 4) {
          float4* dst = reinterpret_cast<float4*>(&g_cs[wt][w][col + lane * 8]);
          dst[0] = make_float4(a[0], a[1], a[2], a[3]); dst[1] = make_float4(a[4], a[5], a[6], a[7]);
        }
        helper_bar();
        if (w == 0 && elect()) { fence_gpu(); st_flag(&g_csflag[wt][j][m], tag); }
      }
      if (w == 0) TS(4, 1 + L * 2);
    }
    if (w == 1) {
      if (L > 0) mbar_wait(sb + BAR_SIGP + ((L & STG0) ? 16 : 24), (L - 1) & 1);
#pragma unroll 1
      for (int p = 0; p < 2; p++) {
        uint4 v[8];
        for (int it = 0;; it++) {
          bool ok = true;
#pragma unroll
          for (int t = 0; t < 8; t++) v[t] = ld_pkt(&g_stats[m][p][t][lane]);
#pragma unroll
          for (int t = 0; t < 8; t++) ok = ok && (v[t].w & 15u) == seq4(tag, L);
          if (__all_sync(0xffffffffu, ok)) break;
          __nanosleep(200);
          if (it > (1 << 20)) __trap();
        }
        float s0 = 0.f, q0 = 0.f, s1 = 0.f, q1 = 0.f;
#pragma unroll
        for (int t = 0; t < 8; t++) { s0 += __uint_as_float(v[t].x); q0 += __uint_as_float(v[t].y); s1 += __uint_as_float(v[t].z); q1 += __uint_as_float(v[t].w & ~15u); }
        s0 *= (1.f / 1024); s1 *= (1.f / 1024);
        sts64(sb + OFF_MR + p * 256 + lane * 8, __float_as_uint(rsqrtf(fmaxf(q0 * (1.f / 1024) - s0 * s0, 0.f) + 1e-5f)),
              __float_as_uint(rsqrtf(fmaxf(q1 * (1.f / 1024) - s1 * s1, 0.f) + 1e-5f)));
#pragma unroll
        for (int r = 0; r < 2; r++) {
          const float v = -0.5f * (r ? s1 : s0);
          const uint32_t hh = pack2(v, v), hl = pack2(v, v - lo16(hh));
          const bool b = L & 1;
          sts128(sb + (b ? OFF_MB : OFF_MA) + p * 1024 + (lane >> 3) * 256 + r * 128 + (lane & 7) * 16, b ? 0u : hh, b ? hh << 16 : hl >> 16, b ? hl : 0u, 0u);
        }
      }
      fence_async_smem();
      __syncwarp();
      if (elect()) {
        mbar_arrive(sb + BAR_STAT);
      }
      TS(2, 0 + L * 8);
    }
    if (L == w) cs_image(L);
    if (L & 1) {
      const uint32_t flip = L == 1 ? 0u : 1u;
      mbar_wait(sb + BAR_SIGT, 1);
      {
        int it = 0;
        if (PSL) __nanosleep(m < 8 ? PSL : PSL + 600);
        while (!__all_sync(0xffffffffu, (ld_flag(reinterpret_cast<const unsigned*>(&g_kvpart[j][m][w][512]) + (lane & 15) * 8) ^ flip) & 1u)) { if (PSL) __nanosleep(100); if (++it > (1 << 22)) __trap(); }
        fence_async_global();
      }
      if (w == 0) TS(4, 6 + L * 2);
      for (int it = 0;; it++) {
        if (elect()) { mbar_expect_tx(stb + rs.s * 8, 8704); bulk_load(stg, &g_kvpart[j][m][w][0], 8704, stb + rs.s * 8); }
        mbar_wait(stb + rs.s * 8, rs.ph);
        adv<3>(rs);
        float a[8] = {0.f, 0.f, 0.f, 0.f, 0.f, 0.f, 0.f, 0.f};
        float z = 0.f;
        uint32_t ok = 1u;
#pragma unroll
        for (int u = 0; u < 4; u++) { const float v = lds32f(stg + 8192 + u * 128 + (lane & 3) * 32 + (lane >> 2) * 4); z += v; ok &= __float_as_uint(v) ^ flip; }
        const uint2 tg = sum_packets(a, stg + lane * 16, 16);
        ok &= flip ? ~tg.y : tg.x;
        uint4* img = &g_kvfin[j][m][w * 8 + (lane >> 2)];
        img[(lane & 3) * 16] = make_uint4(pack2(a[0], a[1]), pack2(a[2], a[3]), pack2(a[4], a[5]), pack2(a[6], a[7]));
        reinterpret_cast<uint32_t*>(img + 64)[lane & 3] = pack2(qsum(z), 1.f);
        if (__all_sync(0xffffffffu, ok & 1u)) break;
        fence_async_smem();
        if (it > (1 << 16)) __trap();
      }
      if (w == 0) TS(4, 7 + L * 2);
      helper_bar();
      if (w == 1 && elect()) { fence_gpu(); st_flag(&g_kvfflag[L >> 1][j][m >> 3][m & 7], tag); }
      if (w == 1 && L == 1) TS(4, 20);
    } else {
      mbar_wait(sb + BAR_SIGT, 0);
      if (w == 0) {
        if (elect()) { fence_gpu(); st_flag(&g_hflag[L >> 1][m][j][0], tag); st_flag(&g_kflag[j][m], tag); }
        if (L == 0) {
          __nanosleep(KSL);
          poll_flags(&g_kflag[j][0], 16, 0xFFFFu, tag);
          if (elect()) mbar_arrive(sb + BAR_WPHI);
        }
      } else if (m > 0) {
        poll_flags(&g_hflag[L >> 1][m - 1][j][0], 1, 1u, tag);
        if (elect()) { mbar_expect_tx(sb + BAR_HALO, 8192); bulk_load(sb + OFF_S + 8192, &g_halo[m - 1][j][0][0], 8192, sb + BAR_HALO); }
        TS(2, 2 + L * 8);
      }
    }
#pragma unroll 1
    for (int e = 0; e < (L < 3 && w == 0 ? 3 : 1); e++) {
      unsigned* flag = e == 0 ? &g_oflag[L][w][m][j] : &g_xflag[L + 1][e - 1][m][j];
      flag = early(flag);
      mbar_wait(sb + BAR_SIGP + (e == 0 ? w : e + 1) * 8, L & 1);
      TS(e == 2 ? 3 : 2 + w, (e ? 6 : 3) + L * 8);
      if (elect()) { fence_async_global(); fence_gpu(); st_flag(flag, tag); }
      TS(e == 2 ? 3 : 2 + w, (e ? 7 : 4) + L * 8);
    }
  }
}

__device__ __forceinline__ void spare(const Params& P, uint32_t sb, int id) {
  const int tid = threadIdx.x & 127, w = __shfl_sync(0xffffffffu, threadIdx.x >> 7, 0), lane = tid & 31, j = 2 * id + w;
  const uint32_t ring = w * 6 * SLOT, wp = 12 * SLOT + w * 8192, bar = sb + 13 * SLOT + w * 64;
  auto part = [&](int t) { return (t >> 4) ^ w; };
  auto load = [&](int t, uint32_t sl) {
    mbar_expect_tx(bar + sl * 8, t == 0 ? SLOT + 8192 : SLOT);
    tma_load_w(sb + ring + sl * SLOT, &P.mw[1], bar + sl * 8, part(t) * 1024 + 128 * j, t & 15);
  };
  if (tid == 0) {
    if (w == 2) sts32(sb + OFF_EPOCH, atomicAdd(&g_ctr, 1u) / NCTA + 1u);
    else {
      __nanosleep(D3);
#pragma unroll 1
      for (int t = 0; t < 5; t++) {
        mbar_init(bar + t * 8, 1);
        asm volatile("fence.mbarrier_init.release.cluster;" ::: "memory");
        load(t, t);
      }
      tma_load_2d(sb + wp, &P.mwphi, bar, 0, 128 * j);
    }
  }
  __syncthreads();
  const unsigned tag = get_tag<false>(sb);
  if (w == 2) {
    int it = 0;
    while ((int)(ld_flag(&g_ctr) - tag * NCTA) < 0) { if (++it > (1 << 22)) __trap(); }
    return;
  }
  Ring r = {4, 1};
  float d[64] = {}, cs[32] = {};
  auto fold = [&]() {
    mbar_wait(bar + r.s * 8, r.ph);
    wgmma_fence();
#pragma unroll
    for (int q = 0; q < 8; q++)
      wgmma_ss_n32(reinterpret_cast<float (&)[16]>(d[16 * (q >> 1)]), desc_lo(SB + ring + r.s * SLOT, 16) + (q >> 2) * 512 + (q & 3) * 2, desc_lo(SB + wp, 512) + q * 64, q & 1);
    wgmma_commit();
  };
  const int row = (tid >> 5) * 16 + (lane >> 2);
#pragma unroll 1
  for (int t = -1; t < 32; t++) {
    uint32_t f[32];
#pragma unroll
    for (int i = 0; i < 32; i++) { f[i] = pack2(d[2 * i], d[2 * i + 1]); cs[i & 30] += d[2 * i]; cs[i | 1] += d[2 * i + 1]; }
    wg_bar(w);
    if (tid == 0 && t >= 0 && t < 27) load(t + 5, r.s);
    __syncwarp();
    if (t < 31) adv<5>(r);
    fold();
    if (part(t) == 0 && t >= 0) {
#pragma unroll
      for (int q = 0; q < 8; q++)
        g_wf[0][j][t & 15][(q >> 2) * 512 + (row + 8 * (q & 1)) * 8 + (((q & 2) * 2 + (lane & 3)) ^ (lane >> 2))] =
            make_uint4(f[4 * (q & 6) + (q & 1)], f[4 * (q & 6) + (q & 1) + 2], f[4 * (q & 6) + (q & 1) + 4], f[4 * (q & 6) + (q & 1) + 6]);
    }
    wgmma_wait<0>();
    fence_regs(d);
    if ((t & 15) == 15) {
      if (t >= 0) {
        const uint32_t red = sb + ring + 5 * SLOT;
#pragma unroll
        for (int i = 0; i < 8; i++) sts128(red + (tid >> 2) * 512 + (i >> 1) * 128 + (lane & 3) * 32 + (i & 1) * 16, __float_as_uint(cs[4 * i]), __float_as_uint(cs[4 * i + 1]), __float_as_uint(cs[4 * i + 2]), __float_as_uint(cs[4 * i + 3]));
        wg_bar(w);
        float a = 0.f;
#pragma unroll 4
        for (int i = 0; i < 32; i++) a += lds32f(red + i * 512 + tid * 4);
        g_cs[1][0][part(t) * 1024 + j * 128 + tid] = a;
        wg_bar(w);
        if (tid == 0) {
          fence_gpu();
          st_flag(&g_csflag[1][j][part(t)], tag);
        }
        __syncwarp();
      }
#pragma unroll
      for (int i = 0; i < 32; i++) cs[i] = 0.f;
    }
  }
}

__global__ void __launch_bounds__(NTHREADS, 1) fused_kernel(const __grid_constant__ Params P) {
  extern __shared__ __align__(1024) uint8_t smem_raw[];
  constexpr uint32_t sb = SB;
  const int tid = threadIdx.x;
  const unsigned vb = vblock();
  if (vb >= 128) { spare(P, sb, vb - 128); return; }
  const int warp = __shfl_sync(0xffffffffu, tid >> 5, 0);
  if (elect()) {
    if (warp == 11) { prefetch_map(&P.mx); prefetch_map(&P.mw[0]); if (smem_u32(smem_raw) != SB) __trap(); }
    if (warp < 7) {
#pragma unroll
      for (int i = 0; i < 8; i++) mbar_init(sb + OFF_BAR + (warp * 8 + i) * 8, warp == 2 || warp == 3 ? 2 : (warp == 4 ? 8 : 1));
    }
    asm volatile("fence.mbarrier_init.release.cluster;" ::: "memory");
    if (warp < 2) {
      const int j = cta_j(vb);
#pragma unroll 1
      for (int i = 0; i < (warp == 0 ? PRE_B : PRE_A); i++) {
        const uint32_t bar = sb + BAR_FULLB + warp * 64 + i * 8;
        mbar_expect_tx(bar, SLOT);
        if (warp == 0) tma_load_w(sb + OFF_B + i * SLOT, &P.mw[0], bar, 1024 + (i & 1) * 1024 + 128 * j, kv_order(i >> 1, j, 0));
        else tma_load_3d(sb + OFF_A + i * SLOT, &P.mx, bar, kv_order(i, j, 0) * 64, cta_m(vb) * 64, 0);
      }
    }
  }
  if (tid == 0) TS(6, 0);
  __syncthreads();
  if (tid == 0) TS(6, 2);
  if (warp < 4) {
    reg_dealloc<PREGS>();
    if (warp == 0) b_producer(P, sb, vb);
    else if (warp == 1) a_loader(P, sb, vb);
    else helper(P, sb, warp - 2, vb);
  } else {
    reg_alloc<CREGS>();
    consumer(P, sb, (warp >> 2) - 1, vb);
  }
}

typedef CUresult (*EncodeFn)(CUtensorMap*, CUtensorMapDataType, cuuint32_t, void*, const cuuint64_t*, const cuuint64_t*,
                             const cuuint32_t*, const cuuint32_t*, CUtensorMapInterleave, CUtensorMapSwizzle,
                             CUtensorMapL2promotion, CUtensorMapFloatOOBfill);

void encode(EncodeFn fn, CUtensorMap* m, const void* ptr, int rank, const cuuint64_t* dims, const cuuint64_t* strides,
            const cuuint32_t* box, CUtensorMapSwizzle swz) {
  const cuuint32_t es[5] = {1, 1, 1, 1, 1};
  fn(m, CU_TENSOR_MAP_DATA_TYPE_BFLOAT16, rank, const_cast<void*>(ptr), dims, strides, box, es, CU_TENSOR_MAP_INTERLEAVE_NONE,
     swz, CU_TENSOR_MAP_L2_PROMOTION_L2_256B, CU_TENSOR_MAP_FLOAT_OOB_FILL_NONE);
}
void encode_w(EncodeFn fn, CUtensorMap* m, const void* ptr, int ncols, bool perm) {
  const cuuint64_t p = (cuuint64_t)ncols * 2, d[5] = {(cuuint64_t)ncols, 2, 4, 4, 32}, s[4] = {p, (perm ? 8 : 2) * p, (perm ? 2 : 8) * p, 32 * p};
  const cuuint32_t box[5] = {64, 2, 4, 4, 2};
  encode(fn, m, ptr, 5, d, s, box, CU_TENSOR_MAP_SWIZZLE_128B);
}

void encode_cs(EncodeFn fn, CUtensorMap* m, const void* ptr, int ncols) {
  const cuuint64_t d[2] = {(cuuint64_t)ncols, 1024}, s[1] = {(cuuint64_t)ncols * 2};
  const cuuint32_t box[2] = {32, 64};
  encode(fn, m, ptr, 2, d, s, box, CU_TENSOR_MAP_SWIZZLE_NONE);
}

}

extern "C" void kernel_launch(void* const* d_in, const int* in_sizes, int n_in, void* d_out, int out_size) {
  (void)in_sizes; (void)n_in; (void)out_size;
  void* fnp = nullptr;
  cudaDriverEntryPointQueryResult q;
  cudaGetDriverEntryPoint("cuTensorMapEncodeTiled", &fnp, cudaEnableDefault, &q);
  EncodeFn fn = (EncodeFn)fnp;
  Params P;
  {
    const cuuint64_t dims[3] = {1024, 1024, 2}, strides[2] = {4096, 2048};
    const cuuint32_t box[3] = {64, 64, 2};
    encode(fn, &P.mx, d_in[0], 3, dims, strides, box, CU_TENSOR_MAP_SWIZZLE_128B);
  }
  P.out = (uint4*)d_out;
  encode_w(fn, &P.mw[0], d_in[1], 3072, false);
  encode_w(fn, &P.mw[1], d_in[4], 3072, true);
  encode_w(fn, &P.mw[2], d_in[1], 3072, true);
  encode_w(fn, &P.mwo[0], d_in[2], 1024, true);
  encode_w(fn, &P.mwo[1], d_in[6], 1024, false);
  encode_cs(fn, &P.mcs[0], d_in[1], 3072);
  encode_cs(fn, &P.mcs[1], d_in[4], 3072);
  {
    const cuuint64_t dims[2] = {32, 1024}, strides[1] = {64};
    const cuuint32_t box[2] = {32, 128};
    encode(fn, &P.mwphi, d_in[5], 2, dims, strides, box, CU_TENSOR_MAP_SWIZZLE_64B);
  }
  cudaFuncSetAttribute(fused_kernel, cudaFuncAttributeMaxDynamicSharedMemorySize, SMEM_BYTES);
  fused_kernel<<<NCTA, NTHREADS, SMEM_BYTES, cudaStreamPerThread>>>(P);
}
```

```cpp
#include <cuda_runtime.h>
#include <cuda_bf16.h>
#include <cuda.h>
#include <stdint.h>

namespace {

__device__ __forceinline__ void wgmma_ss_n256(float (&d)[128], uint32_t da, uint32_t ha, uint32_t db, int sd) {
  asm volatile("{\n.reg .pred p;\n.reg .b64 a, b;\nsetp.ne.b32 p, %130, 0;\nmov.b64 a, {%128, %131};\nmov.b64 b, {%129, 0x40000040};\n"
    "wgmma.mma_async.sync.aligned.m64n256k16.f32.bf16.bf16 {%0,%1,%2,%3,%4,%5,%6,%7,%8,%9,%10,%11,%12,%13,%14,%15,%16,%17,%18,%19,%20,%21,%22,%23,%24,%25,%26,%27,%28,%29,%30,%31,%32,%33,%34,%35,%36,%37,%38,%39,%40,%41,%42,%43,%44,%45,%46,%47,%48,%49,%50,%51,%52,%53,%54,%55,%56,%57,%58,%59,%60,%61,%62,%63,%64,%65,%66,%67,%68,%69,%70,%71,%72,%73,%74,%75,%76,%77,%78,%79,%80,%81,%82,%83,%84,%85,%86,%87,%88,%89,%90,%91,%92,%93,%94,%95,%96,%97,%98,%99,%100,%101,%102,%103,%104,%105,%106,%107,%108,%109,%110,%111,%112,%113,%114,%115,%116,%117,%118,%119,%120,%121,%122,%123,%124,%125,%126,%127}, a, b, p, 1, 1, 0, 1;\n}\n"
    : "+f"(d[0]),"+f"(d[1]),"+f"(d[2]),"+f"(d[3]),"+f"(d[4]),"+f"(d[5]),"+f"(d[6]),"+f"(d[7]),"+f"(d[8]),"+f"(d[9]),"+f"(d[10]),"+f"(d[11]),"+f"(d[12]),"+f"(d[13]),"+f"(d[14]),"+f"(d[15]),"+f"(d[16]),"+f"(d[17]),"+f"(d[18]),"+f"(d[19]),"+f"(d[20]),"+f"(d[21]),"+f"(d[22]),"+f"(d[23]),"+f"(d[24]),"+f"(d[25]),"+f"(d[26]),"+f"(d[27]),"+f"(d[28]),"+f"(d[29]),"+f"(d[30]),"+f"(d[31]),"+f"(d[32]),"+f"(d[33]),"+f"(d[34]),"+f"(d[35]),"+f"(d[36]),"+f"(d[37]),"+f"(d[38]),"+f"(d[39]),"+f"(d[40]),"+f"(d[41]),"+f"(d[42]),"+f"(d[43]),"+f"(d[44]),"+f"(d[45]),"+f"(d[46]),"+f"(d[47]),"+f"(d[48]),"+f"(d[49]),"+f"(d[50]),"+f"(d[51]),"+f"(d[52]),"+f"(d[53]),"+f"(d[54]),"+f"(d[55]),"+f"(d[56]),"+f"(d[57]),"+f"(d[58]),"+f"(d[59]),"+f"(d[60]),"+f"(d[61]),"+f"(d[62]),"+f"(d[63]),"+f"(d[64]),"+f"(d[65]),"+f"(d[66]),"+f"(d[67]),"+f"(d[68]),"+f"(d[69]),"+f"(d[70]),"+f"(d[71]),"+f"(d[72]),"+f"(d[73]),"+f"(d[74]),"+f"(d[75]),"+f"(d[76]),"+f"(d[77]),"+f"(d[78]),"+f"(d[79]),"+f"(d[80]),"+f"(d[81]),"+f"(d[82]),"+f"(d[83]),"+f"(d[84]),"+f"(d[85]),"+f"(d[86]),"+f"(d[87]),"+f"(d[88]),"+f"(d[89]),"+f"(d[90]),"+f"(d[91]),"+f"(d[92]),"+f"(d[93]),"+f"(d[94]),"+f"(d[95]),"+f"(d[96]),"+f"(d[97]),"+f"(d[98]),"+f"(d[99]),"+f"(d[100]),"+f"(d[101]),"+f"(d[102]),"+f"(d[103]),"+f"(d[104]),"+f"(d[105]),"+f"(d[106]),"+f"(d[107]),"+f"(d[108]),"+f"(d[109]),"+f"(d[110]),"+f"(d[111]),"+f"(d[112]),"+f"(d[113]),"+f"(d[114]),"+f"(d[115]),"+f"(d[116]),"+f"(d[117]),"+f"(d[118]),"+f"(d[119]),"+f"(d[120]),"+f"(d[121]),"+f"(d[122]),"+f"(d[123]),"+f"(d[124]),"+f"(d[125]),"+f"(d[126]),"+f"(d[127])
    : "r"(da), "r"(db), "r"(sd), "r"(ha));
}
__device__ __forceinline__ void wgmma_ss_n128(float (&d)[64], uint32_t da, uint32_t ha, uint32_t db, int sd) {
  asm volatile("{\n.reg .pred p;\n.reg .b64 a, b;\nsetp.ne.b32 p, %66, 0;\nmov.b64 a, {%64, %67};\nmov.b64 b, {%65, 0x40000040};\n"
    "wgmma.mma_async.sync.aligned.m64n128k16.f32.bf16.bf16 {%0,%1,%2,%3,%4,%5,%6,%7,%8,%9,%10,%11,%12,%13,%14,%15,%16,%17,%18,%19,%20,%21,%22,%23,%24,%25,%26,%27,%28,%29,%30,%31,%32,%33,%34,%35,%36,%37,%38,%39,%40,%41,%42,%43,%44,%45,%46,%47,%48,%49,%50,%51,%52,%53,%54,%55,%56,%57,%58,%59,%60,%61,%62,%63}, a, b, p, 1, 1, 0, 1;\n}\n"
    : "+f"(d[0]),"+f"(d[1]),"+f"(d[2]),"+f"(d[3]),"+f"(d[4]),"+f"(d[5]),"+f"(d[6]),"+f"(d[7]),"+f"(d[8]),"+f"(d[9]),"+f"(d[10]),"+f"(d[11]),"+f"(d[12]),"+f"(d[13]),"+f"(d[14]),"+f"(d[15]),"+f"(d[16]),"+f"(d[17]),"+f"(d[18]),"+f"(d[19]),"+f"(d[20]),"+f"(d[21]),"+f"(d[22]),"+f"(d[23]),"+f"(d[24]),"+f"(d[25]),"+f"(d[26]),"+f"(d[27]),"+f"(d[28]),"+f"(d[29]),"+f"(d[30]),"+f"(d[31]),"+f"(d[32]),"+f"(d[33]),"+f"(d[34]),"+f"(d[35]),"+f"(d[36]),"+f"(d[37]),"+f"(d[38]),"+f"(d[39]),"+f"(d[40]),"+f"(d[41]),"+f"(d[42]),"+f"(d[43]),"+f"(d[44]),"+f"(d[45]),"+f"(d[46]),"+f"(d[47]),"+f"(d[48]),"+f"(d[49]),"+f"(d[50]),"+f"(d[51]),"+f"(d[52]),"+f"(d[53]),"+f"(d[54]),"+f"(d[55]),"+f"(d[56]),"+f"(d[57]),"+f"(d[58]),"+f"(d[59]),"+f"(d[60]),"+f"(d[61]),"+f"(d[62]),"+f"(d[63])
    : "r"(da), "r"(db), "r"(sd), "r"(ha));
}
__device__ __forceinline__ void wgmma_ss_n40_tt(float (&d)[20], uint32_t da, uint32_t db, int sd) {
  asm volatile("{\n.reg .pred p;\n.reg .b64 a, b;\nsetp.ne.b32 p, %22, 0;\nmov.b64 a, {%20, 0x40000040};\nmov.b64 b, {%21, 0x8};\n"
    "wgmma.mma_async.sync.aligned.m64n40k16.f32.bf16.bf16 {%0,%1,%2,%3,%4,%5,%6,%7,%8,%9,%10,%11,%12,%13,%14,%15,%16,%17,%18,%19}, a, b, p, 1, 1, 1, 1;\n}\n"
    : "+f"(d[0]),"+f"(d[1]),"+f"(d[2]),"+f"(d[3]),"+f"(d[4]),"+f"(d[5]),"+f"(d[6]),"+f"(d[7]),"+f"(d[8]),"+f"(d[9]),"+f"(d[10]),"+f"(d[11]),"+f"(d[12]),"+f"(d[13]),"+f"(d[14]),"+f"(d[15]),"+f"(d[16]),"+f"(d[17]),"+f"(d[18]),"+f"(d[19])
    : "r"(da), "r"(db), "r"(sd));
}
__device__ __forceinline__ void wgmma_ss_n32(float (&d)[16], uint32_t da, uint32_t db, int sd) {
  asm volatile("{\n.reg .pred p;\n.reg .b64 a, b;\nsetp.ne.b32 p, %18, 0;\nmov.b64 a, {%16, 0x40000040};\nmov.b64 b, {%17, 0x80000020};\n"
    "wgmma.mma_async.sync.aligned.m64n32k16.f32.bf16.bf16 {%0,%1,%2,%3,%4,%5,%6,%7,%8,%9,%10,%11,%12,%13,%14,%15}, a, b, p, 1, 1, 0, 1;\n}\n"
    : "+f"(d[0]),"+f"(d[1]),"+f"(d[2]),"+f"(d[3]),"+f"(d[4]),"+f"(d[5]),"+f"(d[6]),"+f"(d[7]),"+f"(d[8]),"+f"(d[9]),"+f"(d[10]),"+f"(d[11]),"+f"(d[12]),"+f"(d[13]),"+f"(d[14]),"+f"(d[15])
    : "r"(da), "r"(db), "r"(sd));
}
__device__ __forceinline__ void wgmma_rs_n40(float (&d)[20], uint32_t a0, uint32_t a1, uint32_t a2, uint32_t a3, uint32_t db, int sd) {
  asm volatile("{\n.reg .pred p;\n.reg .b64 b;\nsetp.ne.b32 p, %25, 0;\nmov.b64 b, {%24, 0x10};\n"
    "wgmma.mma_async.sync.aligned.m64n40k16.f32.bf16.bf16 {%0,%1,%2,%3,%4,%5,%6,%7,%8,%9,%10,%11,%12,%13,%14,%15,%16,%17,%18,%19}, {%20,%21,%22,%23}, b, p, 1, 1, 1;\n}\n"
    : "+f"(d[0]),"+f"(d[1]),"+f"(d[2]),"+f"(d[3]),"+f"(d[4]),"+f"(d[5]),"+f"(d[6]),"+f"(d[7]),"+f"(d[8]),"+f"(d[9]),"+f"(d[10]),"+f"(d[11]),"+f"(d[12]),"+f"(d[13]),"+f"(d[14]),"+f"(d[15]),"+f"(d[16]),"+f"(d[17]),"+f"(d[18]),"+f"(d[19])
    : "r"(a0), "r"(a1), "r"(a2), "r"(a3), "r"(db), "r"(sd));
}
__device__ __forceinline__ void wgmma_r1_n256(float (&d)[128], uint32_t da, uint32_t db, int sd) {
  asm volatile("{\n.reg .pred p;\n.reg .b64 a, b;\nsetp.ne.b32 p, %130, 0;\nmov.b64 a, {%128, 0x8};\nmov.b64 b, {%129, 0x6};\n"
    "wgmma.mma_async.sync.aligned.m64n256k16.f32.bf16.bf16 {%0,%1,%2,%3,%4,%5,%6,%7,%8,%9,%10,%11,%12,%13,%14,%15,%16,%17,%18,%19,%20,%21,%22,%23,%24,%25,%26,%27,%28,%29,%30,%31,%32,%33,%34,%35,%36,%37,%38,%39,%40,%41,%42,%43,%44,%45,%46,%47,%48,%49,%50,%51,%52,%53,%54,%55,%56,%57,%58,%59,%60,%61,%62,%63,%64,%65,%66,%67,%68,%69,%70,%71,%72,%73,%74,%75,%76,%77,%78,%79,%80,%81,%82,%83,%84,%85,%86,%87,%88,%89,%90,%91,%92,%93,%94,%95,%96,%97,%98,%99,%100,%101,%102,%103,%104,%105,%106,%107,%108,%109,%110,%111,%112,%113,%114,%115,%116,%117,%118,%119,%120,%121,%122,%123,%124,%125,%126,%127}, a, b, p, 1, 1, 0, 1;\n}\n"
    : "+f"(d[0]),"+f"(d[1]),"+f"(d[2]),"+f"(d[3]),"+f"(d[4]),"+f"(d[5]),"+f"(d[6]),"+f"(d[7]),"+f"(d[8]),"+f"(d[9]),"+f"(d[10]),"+f"(d[11]),"+f"(d[12]),"+f"(d[13]),"+f"(d[14]),"+f"(d[15]),"+f"(d[16]),"+f"(d[17]),"+f"(d[18]),"+f"(d[19]),"+f"(d[20]),"+f"(d[21]),"+f"(d[22]),"+f"(d[23]),"+f"(d[24]),"+f"(d[25]),"+f"(d[26]),"+f"(d[27]),"+f"(d[28]),"+f"(d[29]),"+f"(d[30]),"+f"(d[31]),"+f"(d[32]),"+f"(d[33]),"+f"(d[34]),"+f"(d[35]),"+f"(d[36]),"+f"(d[37]),"+f"(d[38]),"+f"(d[39]),"+f"(d[40]),"+f"(d[41]),"+f"(d[42]),"+f"(d[43]),"+f"(d[44]),"+f"(d[45]),"+f"(d[46]),"+f"(d[47]),"+f"(d[48]),"+f"(d[49]),"+f"(d[50]),"+f"(d[51]),"+f"(d[52]),"+f"(d[53]),"+f"(d[54]),"+f"(d[55]),"+f"(d[56]),"+f"(d[57]),"+f"(d[58]),"+f"(d[59]),"+f"(d[60]),"+f"(d[61]),"+f"(d[62]),"+f"(d[63]),"+f"(d[64]),"+f"(d[65]),"+f"(d[66]),"+f"(d[67]),"+f"(d[68]),"+f"(d[69]),"+f"(d[70]),"+f"(d[71]),"+f"(d[72]),"+f"(d[73]),"+f"(d[74]),"+f"(d[75]),"+f"(d[76]),"+f"(d[77]),"+f"(d[78]),"+f"(d[79]),"+f"(d[80]),"+f"(d[81]),"+f"(d[82]),"+f"(d[83]),"+f"(d[84]),"+f"(d[85]),"+f"(d[86]),"+f"(d[87]),"+f"(d[88]),"+f"(d[89]),"+f"(d[90]),"+f"(d[91]),"+f"(d[92]),"+f"(d[93]),"+f"(d[94]),"+f"(d[95]),"+f"(d[96]),"+f"(d[97]),"+f"(d[98]),"+f"(d[99]),"+f"(d[100]),"+f"(d[101]),"+f"(d[102]),"+f"(d[103]),"+f"(d[104]),"+f"(d[105]),"+f"(d[106]),"+f"(d[107]),"+f"(d[108]),"+f"(d[109]),"+f"(d[110]),"+f"(d[111]),"+f"(d[112]),"+f"(d[113]),"+f"(d[114]),"+f"(d[115]),"+f"(d[116]),"+f"(d[117]),"+f"(d[118]),"+f"(d[119]),"+f"(d[120]),"+f"(d[121]),"+f"(d[122]),"+f"(d[123]),"+f"(d[124]),"+f"(d[125]),"+f"(d[126]),"+f"(d[127])
    : "r"(da), "r"(db), "r"(sd));
}
__device__ __forceinline__ void wgmma_r1_n128(float (&d)[64], uint32_t da, uint32_t db, int sd) {
  asm volatile("{\n.reg .pred p;\n.reg .b64 a, b;\nsetp.ne.b32 p, %66, 0;\nmov.b64 a, {%64, 0x8};\nmov.b64 b, {%65, 0x6};\n"
    "wgmma.mma_async.sync.aligned.m64n128k16.f32.bf16.bf16 {%0,%1,%2,%3,%4,%5,%6,%7,%8,%9,%10,%11,%12,%13,%14,%15,%16,%17,%18,%19,%20,%21,%22,%23,%24,%25,%26,%27,%28,%29,%30,%31,%32,%33,%34,%35,%36,%37,%38,%39,%40,%41,%42,%43,%44,%45,%46,%47,%48,%49,%50,%51,%52,%53,%54,%55,%56,%57,%58,%59,%60,%61,%62,%63}, a, b, p, 1, 1, 0, 1;\n}\n"
    : "+f"(d[0]),"+f"(d[1]),"+f"(d[2]),"+f"(d[3]),"+f"(d[4]),"+f"(d[5]),"+f"(d[6]),"+f"(d[7]),"+f"(d[8]),"+f"(d[9]),"+f"(d[10]),"+f"(d[11]),"+f"(d[12]),"+f"(d[13]),"+f"(d[14]),"+f"(d[15]),"+f"(d[16]),"+f"(d[17]),"+f"(d[18]),"+f"(d[19]),"+f"(d[20]),"+f"(d[21]),"+f"(d[22]),"+f"(d[23]),"+f"(d[24]),"+f"(d[25]),"+f"(d[26]),"+f"(d[27]),"+f"(d[28]),"+f"(d[29]),"+f"(d[30]),"+f"(d[31]),"+f"(d[32]),"+f"(d[33]),"+f"(d[34]),"+f"(d[35]),"+f"(d[36]),"+f"(d[37]),"+f"(d[38]),"+f"(d[39]),"+f"(d[40]),"+f"(d[41]),"+f"(d[42]),"+f"(d[43]),"+f"(d[44]),"+f"(d[45]),"+f"(d[46]),"+f"(d[47]),"+f"(d[48]),"+f"(d[49]),"+f"(d[50]),"+f"(d[51]),"+f"(d[52]),"+f"(d[53]),"+f"(d[54]),"+f"(d[55]),"+f"(d[56]),"+f"(d[57]),"+f"(d[58]),"+f"(d[59]),"+f"(d[60]),"+f"(d[61]),"+f"(d[62]),"+f"(d[63])
    : "r"(da), "r"(db), "r"(sd));
}

__device__ __forceinline__ uint32_t smem_u32(const void* p) { return (uint32_t)__cvta_generic_to_shared(p); }
__device__ __forceinline__ void mbar_init(uint32_t bar, uint32_t cnt) { asm volatile("mbarrier.init.shared::cta.b64 [%0], %1;" ::"r"(bar), "r"(cnt)); }
__device__ __forceinline__ void mbar_expect_tx(uint32_t bar, uint32_t bytes) { asm volatile("mbarrier.arrive.expect_tx.shared::cta.b64 _, [%0], %1;" ::"r"(bar), "r"(bytes) : "memory"); }
__device__ __forceinline__ void mbar_arrive(uint32_t bar) { asm volatile("mbarrier.arrive.shared::cta.b64 _, [%0];" ::"r"(bar) : "memory"); }
__device__ __forceinline__ void mbar_arrive_n(uint32_t bar, uint32_t n) { asm volatile("mbarrier.arrive.shared::cta.b64 _, [%0], %1;" ::"r"(bar), "r"(n) : "memory"); }
__device__ __forceinline__ void mbar_wait(uint32_t bar, uint32_t parity) {
  asm volatile("{\n.reg .pred p;\nLAB_WAIT:\nmbarrier.try_wait.parity.shared::cta.b64 p, [%0], %1;\n@p bra DONE;\nbra LAB_WAIT;\nDONE:\n}" ::"r"(bar), "r"(parity) : "memory");
}
__device__ __forceinline__ void mbar_wait2(uint32_t a, uint32_t pa, uint32_t b, uint32_t pb) {
  asm volatile("{\n.reg .pred p, q;\nLAB_WAIT:\nmbarrier.try_wait.parity.shared::cta.b64 p, [%0], %1;\nmbarrier.try_wait.parity.shared::cta.b64 q, [%2], %3;\n"
               "and.pred p, p, q;\n@p bra DONE;\nbra LAB_WAIT;\nDONE:\n}" ::"r"(a), "r"(pa), "r"(b), "r"(pb) : "memory");
}
__device__ __forceinline__ void mbar_wait3(uint32_t a, uint32_t pa, uint32_t b, uint32_t pb) {
  asm volatile("{\n.reg .pred p, q, r;\nLAB_WAIT:\nmbarrier.try_wait.parity.shared::cta.b64 p, [%0], %1;\nmbarrier.try_wait.parity.shared::cta.b64 q, [%2], %3;\n"
               "mbarrier.try_wait.parity.shared::cta.b64 r, [%2+8], %3;\nand.pred p, p, q;\nand.pred p, p, r;\n@p bra DONE;\nbra LAB_WAIT;\nDONE:\n}" ::"r"(a), "r"(pa), "r"(b), "r"(pb) : "memory");
}
__device__ __forceinline__ bool mbar_probe2(uint32_t a, uint32_t pa, uint32_t b, uint32_t pb) {
  uint32_t ok;
  asm volatile("{\n.reg .pred p, q;\nmbarrier.test_wait.parity.shared::cta.b64 p, [%1], %2;\nmbarrier.test_wait.parity.shared::cta.b64 q, [%3], %4;\n"
               "and.pred p, p, q;\nselp.u32 %0, 1, 0, p;\n}" : "=r"(ok) : "r"(a), "r"(pa), "r"(b), "r"(pb) : "memory");
  return ok != 0;
}
__device__ __forceinline__ void tma_load_3d(uint32_t dst, const CUtensorMap* tm, uint32_t bar, int c0, int c1, int c2) {
  asm volatile("cp.async.bulk.tensor.3d.shared::cluster.global.mbarrier::complete_tx::bytes [%0], [%1, {%3, %4, %5}], [%2];"
               ::"r"(dst), "l"(tm), "r"(bar), "r"(c0), "r"(c1), "r"(c2) : "memory");
}
__device__ __forceinline__ void tma_load_2d(uint32_t dst, const CUtensorMap* tm, uint32_t bar, int c0, int c1) {
  asm volatile("cp.async.bulk.tensor.2d.shared::cluster.global.mbarrier::complete_tx::bytes [%0], [%1, {%3, %4}], [%2];"
               ::"r"(dst), "l"(tm), "r"(bar), "r"(c0), "r"(c1) : "memory");
}
__device__ __forceinline__ void tma_load_w(uint32_t dst, const CUtensorMap* tm, uint32_t bar, int col, int kb) {
#pragma unroll
  for (int q = 0; q < 2; q++)
    asm volatile("cp.async.bulk.tensor.5d.shared::cluster.global.mbarrier::complete_tx::bytes [%0], [%1, {%3, %4, %4, %4, %5}], [%2];"
                 ::"r"(dst + q * 8192), "l"(tm), "r"(bar), "r"(col + q * 64), "r"(0), "r"(2 * kb) : "memory");
}
__device__ __forceinline__ void tma_prefetch_w(const CUtensorMap* tm, int col, int kb) {
#pragma unroll
  for (int q = 0; q < 2; q++)
    asm volatile("cp.async.bulk.prefetch.tensor.5d.L2.global [%0, {%1, %2, %2, %2, %3}];" ::"l"(tm), "r"(col + q * 64), "r"(0), "r"(2 * kb) : "memory");
}
__device__ __forceinline__ void bulk_load(uint32_t dst, const void* g, uint32_t bytes, uint32_t bar) {
  asm volatile("cp.async.bulk.shared::cluster.global.mbarrier::complete_tx::bytes [%0], [%1], %2, [%3];" ::"r"(dst), "l"(g), "r"(bytes), "r"(bar) : "memory");
}
__device__ __forceinline__ void prefetch_map(const CUtensorMap* tm) { asm volatile("prefetch.tensormap [%0];" ::"l"(tm) : "memory"); }
__device__ __forceinline__ void fence_async_smem() { asm volatile("fence.proxy.async.shared::cta;" ::: "memory"); }
__device__ __forceinline__ void fence_async_global() { asm volatile("fence.proxy.async.global;" ::: "memory"); }
__device__ __forceinline__ void fence_gpu() { asm volatile("fence.release.gpu;" ::: "memory"); }
__device__ __forceinline__ void st_flag(unsigned* p, unsigned v) { asm volatile("st.relaxed.gpu.global.u32 [%0], %1;" ::"l"(p), "r"(v) : "memory"); }
__device__ __forceinline__ unsigned ld_flag(const unsigned* p) { unsigned v; asm volatile("ld.relaxed.gpu.global.u32 %0, [%1];" : "=r"(v) : "l"(p) : "memory"); return v; }
__device__ __forceinline__ uint4 ldcg4(const void* p) { uint4 v; asm volatile("ld.global.cg.v4.u32 {%0,%1,%2,%3}, [%4];" : "=r"(v.x), "=r"(v.y), "=r"(v.z), "=r"(v.w) : "l"(p)); return v; }
__device__ __forceinline__ uint4 ld_pkt(const uint4* p) {
  uint4 v; asm volatile("{\n.reg .b128 t;\nld.relaxed.gpu.global.b128 t, [%4];\nmov.b128 {%0,%1,%2,%3}, t;\n}" : "=r"(v.x), "=r"(v.y), "=r"(v.z), "=r"(v.w) : "l"(p) : "memory"); return v;
}
__device__ __forceinline__ void st_pkt(uint4* p, uint32_t a, uint32_t b, uint32_t c, uint32_t tag) {
  asm volatile("{\n.reg .b128 t;\nmov.b128 t, {%1,%2,%3,%4};\nst.relaxed.gpu.global.b128 [%0], t;\n}" ::"l"(p), "r"(a), "r"(b), "r"(c), "r"(tag) : "memory");
}
__device__ __forceinline__ void st_v4(uint4* p, uint32_t a, uint32_t b, uint32_t c, uint32_t d) { asm volatile("st.relaxed.gpu.global.v4.u32 [%0], {%1,%2,%3,%4};" ::"l"(p), "r"(a), "r"(b), "r"(c), "r"(d) : "memory"); }
__device__ __forceinline__ void sts32(uint32_t addr, uint32_t a) { asm volatile("st.shared.u32 [%0], %1;" ::"r"(addr), "r"(a) : "memory"); }
__device__ __forceinline__ void sts64(uint32_t addr, uint32_t a, uint32_t b) { asm volatile("st.shared.v2.u32 [%0], {%1,%2};" ::"r"(addr), "r"(a), "r"(b) : "memory"); }
__device__ __forceinline__ uint32_t mul2(uint32_t a, uint32_t b) { uint32_t r; asm("mul.rn.bf16x2 %0, %1, %2;" : "=r"(r) : "r"(a), "r"(b)); return r; }
__device__ __forceinline__ uint32_t add2(uint32_t a, uint32_t b) { uint32_t r; asm("add.rn.bf16x2 %0, %1, %2;" : "=r"(r) : "r"(a), "r"(b)); return r; }
__device__ __forceinline__ bool elect() {
  uint32_t p; asm volatile("{\n.reg .pred q;\nelect.sync _|q, 0xffffffff;\nselp.u32 %0, 1, 0, q;\n}" : "=r"(p)); return p != 0;
}
__device__ __forceinline__ void wgmma_fence() { asm volatile("wgmma.fence.sync.aligned;" ::: "memory"); }
__device__ __forceinline__ void wgmma_commit() { asm volatile("wgmma.commit_group.sync.aligned;" ::: "memory"); }
template <int N> __device__ __forceinline__ void wgmma_wait() { asm volatile("wgmma.wait_group.sync.aligned %0;" ::"n"(N) : "memory"); }
template <int N> __device__ __forceinline__ void fence_regs(float (&d)[N]) {
#pragma unroll
  for (int i = 0; i < N; i++) asm volatile("" : "+f"(d[i])::"memory");
}
template <int R> __device__ __forceinline__ void reg_alloc() { asm volatile("setmaxnreg.inc.sync.aligned.u32 %0;" ::"n"(R)); }
template <int R> __device__ __forceinline__ void reg_dealloc() { asm volatile("setmaxnreg.dec.sync.aligned.u32 %0;" ::"n"(R)); }
__device__ __forceinline__ void wg_bar(int w) { asm volatile("bar.sync %0, 128;" ::"r"(w + 1) : "memory"); }
__device__ __forceinline__ constexpr uint32_t desc_lo(uint32_t addr, uint32_t lbo) { return (addr >> 4) + ((lbo >> 4) << 16); }
__device__ __forceinline__ uint32_t pack2(float lo, float hi) { uint32_t r; asm("cvt.rn.bf16x2.f32 %0, %1, %2;" : "=r"(r) : "f"(hi), "f"(lo)); return r; }
__device__ __forceinline__ float lo16(uint32_t v) { return __uint_as_float(v << 16); }
__device__ __forceinline__ float hi16(uint32_t v) { return __uint_as_float(v & 0xFFFF0000u); }
__device__ __forceinline__ float ex2(float x) { float r; asm("ex2.approx.ftz.f32 %0, %1;" : "=f"(r) : "f"(x)); return r; }
__device__ __forceinline__ float rcp(float x) { float r; asm("rcp.approx.ftz.f32 %0, %1;" : "=f"(r) : "f"(x)); return r; }
__device__ __forceinline__ uint32_t movm(uint32_t a) { uint32_t d; asm volatile("movmatrix.sync.aligned.m8n8.trans.b16 %0, %1;" : "=r"(d) : "r"(a)); return d; }
__device__ __forceinline__ void stsm4(uint32_t addr, uint32_t a, uint32_t b, uint32_t c, uint32_t d) {
  asm volatile("stmatrix.sync.aligned.m8n8.x4.shared.b16 [%0], {%1,%2,%3,%4};" ::"r"(addr), "r"(a), "r"(b), "r"(c), "r"(d) : "memory");
}
__device__ __forceinline__ void ldsm4(uint32_t addr, uint32_t (&r)[4]) {
  asm volatile("ldmatrix.sync.aligned.m8n8.x4.shared.b16 {%0,%1,%2,%3}, [%4];" : "=r"(r[0]), "=r"(r[1]), "=r"(r[2]), "=r"(r[3]) : "r"(addr) : "memory");
}
__device__ __forceinline__ void sts128(uint32_t addr, uint32_t a, uint32_t b, uint32_t c, uint32_t d) {
  asm volatile("st.shared.v4.u32 [%0], {%1,%2,%3,%4};" ::"r"(addr), "r"(a), "r"(b), "r"(c), "r"(d) : "memory");
}
__device__ __forceinline__ void lds128(uint32_t addr, uint32_t& a, uint32_t& b, uint32_t& c, uint32_t& d) {
  asm volatile("ld.shared.v4.u32 {%0,%1,%2,%3}, [%4];" : "=r"(a), "=r"(b), "=r"(c), "=r"(d) : "r"(addr) : "memory");
}
__device__ __forceinline__ float lds32f(uint32_t addr) { float v; asm volatile("ld.shared.f32 %0, [%1];" : "=f"(v) : "r"(addr) : "memory"); return v; }
__device__ __forceinline__ float2 lds64f(uint32_t addr) { float2 v; asm volatile("ld.shared.v2.f32 {%0,%1}, [%2];" : "=f"(v.x), "=f"(v.y) : "r"(addr) : "memory"); return v; }
__device__ __forceinline__ void mma16816(float (&d)[4], uint32_t a0, uint32_t a1, uint32_t a2, uint32_t a3, uint32_t b0, uint32_t b1) {
  asm("mma.sync.aligned.m16n8k16.row.col.f32.bf16.bf16.f32 {%0,%1,%2,%3}, {%4,%5,%6,%7}, {%8,%9}, {%0,%1,%2,%3};"
      : "+f"(d[0]), "+f"(d[1]), "+f"(d[2]), "+f"(d[3]) : "r"(a0), "r"(a1), "r"(a2), "r"(a3), "r"(b0), "r"(b1));
}
__device__ __forceinline__ void mma1688(float (&d)[4], uint32_t a0, uint32_t a1, uint32_t b0) {
  asm("mma.sync.aligned.m16n8k8.row.col.f32.bf16.bf16.f32 {%0,%1,%2,%3}, {%4,%5}, {%6}, {%0,%1,%2,%3};"
      : "+f"(d[0]), "+f"(d[1]), "+f"(d[2]), "+f"(d[3]) : "r"(a0), "r"(a1), "r"(b0));
}

__device__ __forceinline__ float qsum(float v) { v += __shfl_xor_sync(0xffffffffu, v, 1); v += __shfl_xor_sync(0xffffffffu, v, 2); return v; }

constexpr int NCTA = 132;
#define NB_ 6
#define NA_ 5
constexpr int NB = NB_;
constexpr int NA = NA_;
constexpr uint32_t SLOT = 16384;
constexpr uint32_t SB = 1024;
constexpr uint32_t OFF_B = 0;
constexpr uint32_t OFF_A = NB * SLOT;
constexpr uint32_t OFF_S = OFF_A + NA * SLOT;
constexpr uint32_t OFF_T = OFF_S + 20480;
constexpr uint32_t OFF_CS = OFF_T + 24576;
constexpr uint32_t OFF_MR = OFF_CS + 4640;
constexpr uint32_t OFF_BAR = OFF_MR + 512;
constexpr uint32_t OFF_MA = OFF_S, OFF_MB = OFF_CS - 2048;
constexpr uint32_t BAR_FULLB = OFF_BAR;
constexpr uint32_t BAR_FULLA = BAR_FULLB + 64;
constexpr uint32_t BAR_EMPTYB = BAR_FULLA + 64;
constexpr uint32_t BAR_EMPTYA = BAR_EMPTYB + 64;
constexpr uint32_t BAR_SIGP = BAR_EMPTYA + 64;
constexpr uint32_t BAR_SIGT = BAR_SIGP + 32;
constexpr uint32_t BAR_STAT = BAR_SIGP + 64;
constexpr uint32_t BAR_HALO = BAR_STAT + 16;
constexpr uint32_t BAR_CS = BAR_HALO + 8;
constexpr uint32_t BAR_WPHI = BAR_CS + 16;
constexpr uint32_t BAR_KV = BAR_WPHI + 8;
constexpr uint32_t BAR_STG = BAR_KV + 16;
constexpr uint32_t BAR_EPOCH = BAR_STG + 48;
constexpr uint32_t OFF_EPOCH = OFF_BAR + 7 * 64;
static_assert(BAR_EPOCH < OFF_EPOCH, "barriers");
constexpr uint32_t SMEM_BYTES = OFF_EPOCH + 8;
static_assert(SMEM_BYTES <= 232448 && NB % 2 == 0 && NB <= 8 && NA <= 6, "smem");

#define CREGS 224
#define PREGS 56
#define PF0 9
#define PF1 13
#define PF2 17
#define PRE_A 2
#define PRE_B 4
#define CSB 4
#define CSNEED 0xF003u
#define XR 1
#define PS0 1
#define PS1 3
#define PSW 0
#define SD 1000
#define QORD 2
#define KSPLIT 12
#define KEEP 16
#define NJ 3
#define KSL 1000
#define PSL 0
#define KVS 12
#define D2 2000
#define D3 1500
#define G0 50
#define G3 50
#define G1 0
#define G4 0
#define MAP 3
#define PMAP 0x76321450u
#define PW 1
#define PN2 0
#define XA 3
#define XS 1
#define KB 8
#define PNX 2
#define PNO 2
#define DEFER 3
#define DEFL 2
#define TSK 3
#define TSL 3
constexpr int NTHREADS = 384;

struct Params {
  CUtensorMap mx;
  CUtensorMap mw[3];
  CUtensorMap mwo[2];
  CUtensorMap mcs[2];
  CUtensorMap mwphi;
  uint4* out;
};

#define XBUF(L) 1
__device__ __align__(256) uint4 g_img[XBUF(3) + 1][16][16][1024];
__device__ __align__(256) uint4 g_wf[2][8][16][1024];
__device__ __align__(256) uint4 g_stats[16][2][8][32];
__device__ __align__(256) uint4 g_halo[16][8][2][256];
__device__ __align__(256) float g_cs[2][2][3072];
__device__ __align__(256) uint4 g_kvpart[8][16][2][544];
__device__ __align__(256) uint4 g_kvfin[8][16][80];
__device__ __align__(256) unsigned g_xflag[4][2][16][32];
__device__ __align__(256) unsigned g_oflag[4][2][16][32];
__device__ __align__(256) unsigned g_hflag[2][16][8][32];
__device__ __align__(256) unsigned g_kvfflag[2][8][2][32];
__device__ __align__(256) unsigned g_csflag[2][8][32];
__device__ __align__(256) unsigned g_kflag[8][32];
__device__ unsigned g_ctr;
__device__ __forceinline__ unsigned vblock() {
  unsigned s;
  asm volatile("mov.u32 %0, %%smid;" : "=r"(s));
  const unsigned r = s & 1;
  s >>= 1;
  const unsigned t = s - 32, q = (t * 37) >> 8;
  const unsigned hi = s < 60 ? 12 + (t - 7 * q) * 8 + q : (s < 62 ? s + 4 : s - 58);
  unsigned b = 2 * (s < 32 ? (s & 7) * 8 + (s >> 3) : hi) + r;
  if (b < 128) b = (b & 15) | ((PMAP >> ((b >> 4) * 4)) & 7) << 4;
  if (s >= 62) b = 8 + 4 * r + s - 62;
  return __shfl_sync(0xffffffffu, b, 0);
}
#define TS(who, id) do {} while (0)
#define TSW(id) do {} while (0)

#define TSMASK 0xFFFF
#define TSL_(a) do { if ((TSMASK >> (a)) & 1) TSW((a) + L * 12); } while (0)
__device__ __forceinline__ int cta_m(unsigned b) { return ((b >> 2) & 12) | (b & 3); }
__device__ __forceinline__ int cta_j(unsigned b) { return ((b >> 2) & 3) | ((b >> 4) & 4); }
struct Ring { uint32_t s, ph; };
template <int N> __device__ __forceinline__ void adv(Ring& r) { if (++r.s == N) { r.s = 0; r.ph ^= 1; } }
template <int N> __device__ __forceinline__ void rewind2(Ring& r) { if (r.s < 2) { r.s += N - 2; r.ph ^= 1; } else r.s -= 2; }
__device__ __forceinline__ int other_tile(int t, int j) { return (t == (j | 4) ? 7 : t) ^ (~j & 4); }
__device__ __forceinline__ int q_order(int i, int j) { return 2 * (i >= 14 ? j : other_tile(i >> 1, j)) + (i & 1); }
__device__ __forceinline__ int o_order(int i, int j) {
  if (i < 2) return 2 * j + i;
  const int odd = i >= 9;
  return 2 * other_tile(i - 2 - 7 * odd, j) + odd;
}
__device__ __forceinline__ int kv_order(int i, int j, int L) { return L > 0 ? o_order(i, j) : (i + 14 + 2 * (j & 4)) & 15; }

__device__ __forceinline__ unsigned poll_flags(const unsigned* f, int n, unsigned need, unsigned tag) {
  const int lane = threadIdx.x & 31;
  unsigned mask; int it = 0;
  do {
    unsigned v = lane < n ? ld_flag(f + lane) : 0u;
    mask = __ballot_sync(0xffffffffu, lane < n && v == tag);
    if (++it > (1 << 22)) __trap();
  } while ((mask & need) != need);
  fence_async_global();
  return mask;
}
template <bool WAIT = true>
__device__ __forceinline__ unsigned get_tag(uint32_t sb) {
  if (WAIT) mbar_wait(sb + BAR_EPOCH, 0);
  unsigned t; asm volatile("ld.shared.u32 %0, [%1];" : "=r"(t) : "r"(sb + OFF_EPOCH) : "memory");
  return t;
}

__device__ __forceinline__ int lane_id() { int l; asm volatile("mov.u32 %0, %%laneid;" : "=r"(l)); return l; }
__device__ __forceinline__ unsigned seq4(unsigned tag, int L) { return 8u | ((tag & 1u) << 2) | (unsigned)L; }
constexpr float LOG2E = 1.4426950408889634f;

__device__ __forceinline__ void sched_fence(uint32_t sb) { mbar_wait(sb + BAR_EPOCH, 0); }
constexpr uint32_t HA128 = 0x40000040u, HA64 = 0x80000040u;
struct Ctx {
  static constexpr uint32_t sb = SB;
  uint32_t ab, da0;
  int w, warp, lane, g, c;
  int goff;
  __device__ __forceinline__ int m() const { return goff >> 14; }
  __device__ __forceinline__ int j() const { return (goff >> 4) & 7; }
  bool elected;
  Ring ra, rb;
  uint32_t pa, pb;
  uint32_t ha, k2;
  uint32_t mrow, mxor, mhi;
  __device__ __forceinline__ uint32_t aslot(uint32_t s) const { return ab + s * SLOT; }
  __device__ __forceinline__ uint32_t fullA(uint32_t s) const { return sb + BAR_FULLA + s * 8; }
  __device__ __forceinline__ uint32_t fullB(uint32_t s) const { return sb + BAR_FULLB + s * 8; }
  __device__ __forceinline__ void releaseA(uint32_t s) const { if (elected) mbar_arrive(sb + BAR_EMPTYA + s * 8); }
  __device__ __forceinline__ void releaseB(uint32_t s) const { if (elected) mbar_arrive(sb + BAR_EMPTYB + s * 8); }
  __device__ __forceinline__ uint32_t maddr(uint32_t tile, uint32_t ch) const { return tile + mrow + (((ch + mhi) ^ mxor) << 4); }
  __device__ __forceinline__ uint32_t oo() const { return warp * 128 + g * 4 + (c ^ (g >> 1)); }
  __device__ __forceinline__ uint4* img(int b, int hp) const { return &g_img[b][m()][2 * j() + hp][w * 512 + oo()]; }
  __device__ __forceinline__ uint32_t held(int i) const { return ra.s + i < 2 ? ra.s + i + NA - 2 : ra.s + i - 2; }
};

template <int N, bool FIRST, bool O = true>
__device__ __forceinline__ void gemm_issue(float (&acc)[N / 2], Ctx& x, bool ready = false) {
  if (!ready) {
    if (N == 256) mbar_wait3(x.fullA(x.ra.s), x.ra.ph, x.fullB(x.rb.s), x.rb.ph);
    else mbar_wait2(x.fullA(x.ra.s), x.ra.ph, x.fullB(x.rb.s), x.rb.ph);
  }
  const uint32_t da = x.da0 + x.ra.s * (SLOT / 16), db = desc_lo(SB + OFF_B, 8192) + x.rb.s * (SLOT / 16);
  wgmma_fence();
#pragma unroll
  for (int k = 0; k < 4; k++) {
    const uint32_t a = da + (k >> 1) * (O ? 32 : x.k2) + (k & 1) * 2, ha = O ? HA64 : x.ha;
    if constexpr (N == 256) wgmma_ss_n256(acc, a, ha, db + 128 * k, !(FIRST && k == 0));
    else wgmma_ss_n128(acc, a, ha, db + 128 * k, !(FIRST && k == 0));
  }
  wgmma_commit();
}
template <int N>
__device__ __forceinline__ void gemm_next(Ctx& x) {
  x.pa = x.ra.s; x.pb = x.rb.s;
  if (N == 256) x.rb.s++;
  adv<NA>(x.ra); adv<NB>(x.rb);
}
template <int N>
__device__ __forceinline__ void gemm_release(Ctx& x, bool relA) {
  if (relA) x.releaseA(x.pa);
  x.releaseB(x.pb);
  if (N == 256) x.releaseB(x.pb + 1);
}
template <int N>
__device__ __forceinline__ void gemm_retire(Ctx& x, bool relA) { wgmma_wait<1>(); gemm_release<N>(x, relA); gemm_next<N>(x); }
template <bool O = true>
__device__ __forceinline__ void gemm_run(float (&acc)[64], Ctx& x, int n, int hold, int n4 = 0) {
  bool ready = false;
#pragma unroll 1
  for (; n > 0; n--) {
    gemm_issue<128, false, O>(acc, x, ready);
    const uint32_t pa = x.pa, pb = x.pb;
    gemm_next<128>(x);
    ready = mbar_probe2(x.fullA(x.ra.s), x.ra.ph, x.fullB(x.rb.s), x.rb.ph);
    wgmma_wait<1>();
    if (n > hold) x.releaseA(pa);
    x.releaseB(pb);
  }
}
__device__ __forceinline__ void gemm_end(float (&acc)[64], Ctx& x) { wgmma_wait<0>(); fence_regs(acc); gemm_release<128>(x, false); }

__device__ __forceinline__ void load_x32(float* a, uint32_t tile, uint32_t ch, const Ctx& x) {
#pragma unroll
  for (int p = 0; p < 2; p++) {
    uint32_t v[4];
    ldsm4(x.maddr(tile, ch + 2 * p), v);
#pragma unroll
    for (int i = 0; i < 4; i++) { a[8 * p + 2 * i] = lo16(v[i]); a[8 * p + 2 * i + 1] = hi16(v[i]); }
  }
}

__device__ __forceinline__ void rows_load(uint4* r, uint32_t tile, const Ctx& x) {
#pragma unroll
  for (int q = 0; q < 4; q++) {
    const uint32_t row = x.warp * 16 + 4 * q + (x.lane >> 3);
    lds128(tile + row * 128 + (((x.lane & 7) ^ (row & 7)) << 4), r[q].x, r[q].y, r[q].z, r[q].w);
  }
}
__device__ __forceinline__ void rows_store(const uint4* r, uint4* g, const Ctx& x) {
  g += (x.warp * 16 + (x.lane >> 3)) * 256 + (x.lane & 7);
#pragma unroll
  for (int q = 0; q < 4; q++) g[q * 1024] = r[q];
}
__device__ __forceinline__ void publish(int id, const Ctx& x) { __syncwarp(); if (x.lane == 0) mbar_arrive(x.sb + BAR_SIGP + id * 8); }
__device__ __forceinline__ void img_store(const uint4 (&r)[4], uint4* g) {
#pragma unroll
  for (int q = 0; q < 4; q++) g[q * 32] = r[q];
}
__device__ __forceinline__ void img_sts(const uint4 (&r)[4], uint32_t tile, const Ctx& x) {
#pragma unroll
  for (int q = 0; q < 4; q++) sts128(tile + x.oo() * 16 + q * 512, r[q].x, r[q].y, r[q].z, r[q].w);
}
__device__ __forceinline__ void img_load(uint32_t (&v)[16], uint32_t tile, const Ctx& x) {
#pragma unroll
  for (int q = 0; q < 4; q++) lds128(tile + x.oo() * 16 + q * 512, v[4 * q], v[4 * q + 1], v[4 * q + 2], v[4 * q + 3]);
}
__device__ __forceinline__ void img_unpack(float* a, const uint32_t (&v)[16]) {
#pragma unroll
  for (int q = 0; q < 16; q++) { a[4 * (q & 7) + 2 * (q >> 3)] = lo16(v[q]); a[4 * (q & 7) + 2 * (q >> 3) + 1] = hi16(v[q]); }
}

template <int N>
__device__ __forceinline__ void stats_acc(const float* a, float (&t)[4]) {
#pragma unroll
  for (int i = 0; i < N; i++) { t[i & 2] += a[i]; t[(i & 2) + 1] = fmaf(a[i], a[i], t[(i & 2) + 1]); }
}
__device__ __forceinline__ void stats_send(float (&t)[4], int L, const Ctx& x) {
  const unsigned seq = seq4(get_tag<false>(x.sb), L);
#pragma unroll
  for (int q = 0; q < 4; q++) t[q] = qsum(t[q]);
  if (x.c == 0) st_pkt(&g_stats[x.m()][x.w][x.j()][x.warp * 8 + x.g], __float_as_uint(t[0]), __float_as_uint(t[1]), __float_as_uint(t[2]), (__float_as_uint(t[3]) & ~15u) | seq);
}
__device__ __forceinline__ void out_epilogue(const float (&acc)[64], uint4 (&r1)[4], float (&t)[4], uint4* g, int L, Ctx& x) {
  const uint32_t t0 = x.aslot(x.ra.s), t1 = x.aslot(x.ra.s + 1 == NA ? 0 : x.ra.s + 1);
  if (L == 3) {
#pragma unroll
    for (int p = 0; p < 8; p++) {
      stsm4(x.maddr(p < 4 ? t0 : t1, (p & 3) * 2), pack2(acc[8 * p], acc[8 * p + 1]), pack2(acc[8 * p + 2], acc[8 * p + 3]),
            pack2(acc[8 * p + 4], acc[8 * p + 5]), pack2(acc[8 * p + 6], acc[8 * p + 7]));
      if ((p & 3) == 3) { uint4 r[4]; __syncwarp(); rows_load(r, p < 4 ? t0 : t1, x); rows_store(r, g + (p >> 2) * 8, x); }
    }
  } else {
    auto pack16 = [&](uint4 (&r)[4], const float* a) {
#pragma unroll
      for (int q = 0; q < 4; q++) { const float* u = a + 16 * (q & 1) + (q & 2); r[q] = make_uint4(pack2(u[0], u[1]), pack2(u[4], u[5]), pack2(u[8], u[9]), pack2(u[12], u[13])); }
    };
    uint4 r0[4];
    pack16(r0, acc);
    img_store(r0, x.img(XBUF(L + 1), 0));
    publish(2, x);
    img_sts(r0, t0, x);
    sched_fence(x.sb);
    pack16(r1, acc + 32);
    img_sts(r1, t1, x);
    float u[4] = {0.f, 0.f, 0.f, 0.f}, v[4] = {0.f, 0.f, 0.f, 0.f};
    stats_acc<32>(acc, v); stats_acc<32>(acc + 32, u);
#pragma unroll
    for (int q = 0; q < 4; q++) t[q] = u[q] + v[q];
    mbar_wait2(x.fullB(x.rb.s), x.rb.ph, x.fullB(x.rb.s + 1), x.rb.ph);
    fence_async_smem();
    asm volatile("bar.sync %0, %1;" ::"r"(L == 1 ? x.w + 1 : 3), "r"(L == 1 ? 128 : 256) : "memory");
  }
}

struct Stats { float rstd0, rstd1; };
__device__ __forceinline__ Stats load_stats(int half, const Ctx& x) {
  const float2 u = lds64f(x.sb + OFF_MR + half * 256 + (x.warp * 8 + x.g) * 8);
  return {u.x, u.y};
}

template <int NK>
__device__ __forceinline__ void hedgehog_scale(float* t, const Stats& st, const uint32_t* keep) {
#pragma unroll
  for (int q = 0; q < 16; q++) t[q] *= ((q & 2) ? st.rstd1 : st.rstd0) * LOG2E;
  float m[4];
#pragma unroll
  for (int q = 0; q < 4; q++) m[q] = fmaxf(fmaxf(fabsf(t[4 * q]), fabsf(t[4 * q + 1])), fmaxf(fabsf(t[4 * q + 2]), fabsf(t[4 * q + 3])));
  if (__builtin_expect(__any_sync(0xffffffffu, fmaxf(fmaxf(m[0], m[1]), fmaxf(m[2], m[3])) > 58.f), 0)) {
    float z[16 + NK];
#pragma unroll
    for (int q = 0; q < 16 + NK; q++) z[q] = q < 16 ? t[q & 15] : __uint_as_float(keep[q & 15]);
#pragma unroll 1
    for (int r = 0; r < 4; r += 2) {
      float hi = -INFINITY, lo = INFINITY;
#pragma unroll 1
      for (int i = 0; i < 16; i++) {
        const int k = (i & 6) * 2 + (i & 1) + r;
        const float v = z[k];
        if (i < 8) { hi = fmaxf(hi, v); lo = fminf(lo, v); }
        else z[k] = v - fminf(fmaxf(v, lo), hi);
        if (i == 7) {
#pragma unroll 1
          for (int d = 1; d <= 2; d++) { hi = fmaxf(hi, __shfl_xor_sync(0xffffffffu, hi, d)); lo = fminf(lo, __shfl_xor_sync(0xffffffffu, lo, d)); }
          const float mid = 0.5f * hi + 0.5f * lo;
          hi = fmaxf(hi - 58.f, mid); lo = fminf(lo + 58.f, mid);
        }
      }
    }
#pragma unroll
    for (int q = 0; q < 16; q++) t[q] = z[q];
  }
}
__device__ __forceinline__ void dual_exp(const float* t, uint32_t (&f)[18], int never) {
  float e[KSPLIT];
#pragma unroll
  for (int q = 0; q < KSPLIT; q++) e[q] = ex2(q < 16 ? t[q] : -t[q & 15]);
  while (never < 0) {
#pragma unroll
    for (int i = 0; i < KSPLIT; i += 4) asm volatile("ld.shared.v4.f32 {%0,%1,%2,%3}, [%4];" : "=f"(e[i]), "=f"(e[i + 1]), "=f"(e[i + 2]), "=f"(e[i + 3]) : "r"(never + i) : "memory");
    never += __float_as_int(e[0]);
  }
#pragma unroll
  for (int q = 0; q < KSPLIT; q += 2) f[q >> 1] = pack2(e[q], e[q + 1]);
#pragma unroll
  for (int q = KSPLIT; q < 32; q += 2) f[q >> 1] = q < 16 ? pack2(ex2(t[q]), ex2(t[q + 1])) : pack2(ex2(-t[q & 15]), ex2(-t[(q & 15) + 1]));
#pragma unroll
  for (int sg = 0; sg < 2; sg++) {
    const uint32_t* u = f + 8 * sg;
    const uint32_t a = add2(add2(u[0], u[2]), add2(u[4], u[6])), b = add2(add2(u[1], u[3]), add2(u[5], u[7]));
    f[16 + sg] = add2(__byte_perm(a, b, 0x5410), __byte_perm(a, b, 0x7632));
  }
}
__device__ __forceinline__ void dual_exp_rcp(const float* t, uint32_t (&f)[16]) {
#pragma unroll
  for (int q = 0; q < 8; q++) {
    const float a = ex2(t[2 * q]), b = ex2(t[2 * q + 1]), r = rcp(a * b);
    f[q] = pack2(a, b); f[8 + q] = pack2(r * b, r * a);
  }
}
__device__ __forceinline__ void cta_bar() { asm volatile("bar.sync 3, 256;" ::: "memory"); }

template <int N> __device__ __forceinline__ void pin(const uint32_t* v, uint32_t addr) {
#pragma unroll
  for (int i = 0; i < N; i += 4)
    asm volatile("{\n.reg .pred p;\nsetp.eq.u32 p, %0, 0;\n@p st.shared.v4.u32 [%0], {%1,%2,%3,%4};\n}" ::"r"(addr), "r"(v[i]), "r"(v[i + 1]), "r"(v[i + 2]), "r"(v[i + 3]) : "memory");
}

__device__ __forceinline__ void consumer(const Params& P, uint32_t sb, int w, unsigned vb) {
  Ctx x;
  x.w = w;
  x.ab = sb + OFF_A + w * 8192; x.da0 = desc_lo(SB + OFF_A, 16) + w * 512;
  x.lane = threadIdx.x & 31; x.warp = __shfl_sync(0xffffffffu, (threadIdx.x >> 5) & 3, 0); x.g = x.lane >> 2; x.c = x.lane & 3;
  x.goff = (cta_m(vb) * 128 + w) * 128 + cta_j(vb) * 16;
  asm volatile("" : "+r"(x.goff));
  x.elected = (threadIdx.x & 127) == 0;
  x.ra = {0, 0}; x.rb = {0, 0}; x.pa = x.pb = 0;
  {
    const uint32_t row = x.warp * 16 + (x.lane & 15);
    x.mrow = row * 128; x.mxor = row & 7; x.mhi = x.lane >> 4;
  }
  const int goff = x.goff;
  uint4 r1[4];
  float ts[4] = {0.f, 0.f, 0.f, 0.f};
#pragma unroll
  for (int i = 0; i < 4; i++) r1[i] = make_uint4(0, 0, 0, 0);
  TSW(0);
  mbar_wait3(x.fullA(0), 0, x.fullB(0), 0);
#pragma unroll 1
  for (int L = 0; L < 4; L++) {
    float acc[64];
    constexpr uint32_t dcs = desc_lo(SB + OFF_CS, 0);
    if ((L & 1) == 0) {
    float kv[128];
    x.ha = L ? HA64 : HA128; x.k2 = L ? 32 : 4;
    gemm_issue<256, true, false>(kv, x, true); gemm_next<256>(x);
    {
      int i = 1;
#pragma unroll 1
      for (int seg = L >> 1; seg < 3; seg++) {
        const int end = seg < 2 ? (L == 0 ? 3 + 2 * (x.j() & 3) + seg : XA + 1) : 14 + L;
#pragma unroll 1
        while (true) {
          gemm_issue<256, false, false>(kv, x);
          if (++i == end) break;
          gemm_retire<256>(x, true);
          if (i == 5) TSL_(8);
          if (i == 11) TSL_(10);
        }
        if (seg < 2 && L == 0) {
          float a[32];
          const uint32_t tile = x.aslot(x.ra.s);
          load_x32(a, tile, 0, x); load_x32(a + 16, tile, 4, x);
          stats_acc<32>(a, ts);
          fence_async_smem();
          wg_bar(w);
        }
        if (seg == 1) {
          if (L > 0) { img_store(r1, x.img(XBUF(L), 1)); publish(3, x); }
          mbar_wait(sb + BAR_EPOCH, 0);
          stats_send(ts, L, x);
        }
        gemm_retire<256>(x, true);
      }
    }
      const Ring kt = x.ra;
      if (L == 0) adv<NA>(x.ra);
#pragma unroll 1
      for (int h = L; h < 2; h++) {
        float d[16];
        mbar_wait2(x.fullA(kt.s), kt.ph, sb + BAR_WPHI, 0);
        wgmma_fence();
#pragma unroll
        for (int q = 0; q < 2; q++) wgmma_ss_n32(d, x.da0 + kt.s * (SLOT / 16) + h * 4 + q * 2, desc_lo(SB + OFF_S + 4096, 512) + w * 256 + h * 128 + q * 64, q);
        wgmma_commit();
        gemm_issue<256, false, false>(kv, x);
        gemm_retire<256>(x, true);
        if (h) x.releaseA(kt.s);
        fence_regs(d);
        uint4* dst = &g_wf[1][x.j()][x.m()][w * 512 + (x.warp * 16 + x.g) * 8 + ((h * 4 + x.c) ^ x.g)];
        dst[0] = make_uint4(pack2(d[0], d[1]), pack2(d[4], d[5]), pack2(d[8], d[9]), pack2(d[12], d[13]));
        dst[64] = make_uint4(pack2(d[2], d[3]), pack2(d[6], d[7]), pack2(d[10], d[11]), pack2(d[14], d[15]));
      }
      const uint32_t dm = desc_lo(SB + OFF_MA, 0) + w * 64;
      mbar_wait2(sb + BAR_STAT, 0, sb + BAR_CS, 0);
      wgmma_fence();
      wgmma_r1_n256(kv, dm, dcs + 96, 1);
      wgmma_commit();
      const Stats st = load_stats(w, x);
      if (PW & 1) mbar_wait2(x.fullA(x.ra.s), x.ra.ph, x.fullB(x.rb.s), x.rb.ph);
      wgmma_wait<0>();
      fence_regs(kv);
      gemm_release<256>(x, true);
      TSL_(2);
      uint32_t P0[32], P1[32], PH[32];
#pragma unroll
      for (int t = 0; t < 16; t++) { P0[t] = pack2(kv[4 * t] * st.rstd0, kv[4 * t + 1] * st.rstd0); P1[t] = pack2(kv[4 * t + 2] * st.rstd1, kv[4 * t + 3] * st.rstd1); }
      pin<16>(P0, x.mrow + 16);
      {
#pragma unroll
        for (int q = 0; q < 4; q++) sts128((x.warp < 3 ? sb + OFF_T + w * 12288 + x.warp * 4096 : sb + OFF_S + 16384 + w * 2048) + x.lane * 16 + q * 512, P1[4 * q], P1[4 * q + 1], P1[4 * q + 2], P1[4 * q + 3]);
      }
      wgmma_fence();
      wgmma_r1_n128(acc, dm, dcs, 0);
      gemm_issue<128, false, false>(acc, x, PW & 1); gemm_next<128>(x);
      TSL_(3);
#pragma unroll
      for (int s = 0; s < 4; s++) {
#pragma unroll
        for (int t = 16 + 8 * (s & 1); t < 24 + 8 * (s & 1); t++) {
          if (s < 2) P1[t] = movm(pack2(kv[4 * t + 2] * st.rstd1, kv[4 * t + 3] * st.rstd1));
          else P0[t] = movm(pack2(kv[4 * t] * st.rstd0, kv[4 * t + 1] * st.rstd0));
        }
        if (s < 3) { gemm_issue<128, false, false>(acc, x); gemm_retire<128>(x, true); }
        if (s == 1) {
          if (x.warp < 3) {
#pragma unroll
            for (int q = 4; q < 8; q++) sts128(sb + OFF_T + w * 12288 + x.warp * 4096 + x.lane * 16 + q * 512, P1[4 * q], P1[4 * q + 1], P1[4 * q + 2], P1[4 * q + 3]);
          } else {
            uint4* dst = &g_halo[x.m()][x.j()][w][x.lane];
#pragma unroll
            for (int q = 0; q < 8; q++) dst[q * 32] = make_uint4(P1[4 * q], P1[4 * q + 1], P1[4 * q + 2], P1[4 * q + 3]);
          }
          publish(4, x);
          gemm_issue<128, false, false>(acc, x);
          gemm_retire<128>(x, true);
        }
      }
      TSL_(4);
      gemm_run<false>(acc, x, 10, 0);
      gemm_issue<128, false, false>(acc, x);
      {
        wg_bar(w);
        uint32_t tr = sb + OFF_T + w * 12288 + (x.warp - 1) * 4096;
        if (x.warp == 0) {
          tr = x.m() > 0 ? sb + OFF_S + 8192 + w * 4096 : tr + 4096;
          if (x.m() > 0) mbar_wait(sb + BAR_HALO, L >> 1);
        }
#pragma unroll
        for (int q = 0; q < 8; q++) lds128(tr + x.lane * 16 + q * 512, PH[4 * q], PH[4 * q + 1], PH[4 * q + 2], PH[4 * q + 3]);
      }
      gemm_retire<128>(x, false);
      gemm_end(acc, x);
      TSL_(5);
      const bool first = (x.m() == 0) && (x.warp == 0);
      const bool hi0 = 2 * x.c > x.g, hi1 = 2 * x.c + 1 > x.g;
      const uint32_t mhi = (hi0 ? 0xFFFFu : 0u) | (hi1 ? 0xFFFF0000u : 0u);
      const float sc0 = st.rstd0 * (0.17677669529663687f * LOG2E), sc1 = st.rstd1 * (0.17677669529663687f * LOG2E);
#pragma unroll
      for (int hp = 0; hp < 2; hp++) {
        const uint32_t tile = x.aslot(x.held(hp));
        uint32_t px[2], py[2];
        float s[2][3][4];
#pragma unroll
        for (int u = 0; u < 2; u++) {
#pragma unroll
          for (int q = 0; q < 12; q++) s[u][q >> 2][q & 3] = 0.f;
#pragma unroll
          for (int ks = 0; ks < 2; ks++) {
            const int t = 8 * hp + 4 * u + 2 * ks;
            const uint32_t a0 = pack2(acc[4 * t], acc[4 * t + 1]), a1 = pack2(acc[4 * t + 2], acc[4 * t + 3]);
            const uint32_t a2 = pack2(acc[4 * t + 4], acc[4 * t + 5]), a3 = pack2(acc[4 * t + 6], acc[4 * t + 7]);
            mma16816(s[u][0], a0, a1, a2, a3, PH[t], PH[t + 1]);
            mma16816(s[u][1], a0, a1, a2, a3, P0[t], P0[t + 1]);
            mma16816(s[u][2], a0, a1, a2, a3, P1[t], P1[t + 1]);
          }
        }
        float e[2][4], r[2][2];
#pragma unroll
        for (int u = 0; u < 2; u++) {
          e[u][0] = (hi0 ? s[u][0][0] : s[u][1][0]) * sc0; e[u][1] = (hi1 ? s[u][0][1] : s[u][1][1]) * sc0;
          e[u][2] = (hi0 ? s[u][1][2] : s[u][2][2]) * sc1; e[u][3] = (hi1 ? s[u][1][3] : s[u][2][3]) * sc1;
          if (first) { if (hi0) e[u][0] = -1e30f; if (hi1) e[u][1] = -1e30f; }
          r[u][0] = fmaxf(e[u][0], e[u][1]); r[u][1] = fmaxf(e[u][2], e[u][3]);
        }
#pragma unroll
        for (int d = 1; d <= 2; d++)
#pragma unroll
          for (int q = 0; q < 4; q++) r[q >> 1][q & 1] = fmaxf(r[q >> 1][q & 1], __shfl_xor_sync(0xffffffffu, r[q >> 1][q & 1], d));
#pragma unroll
        for (int u = 0; u < 2; u++) {
#pragma unroll
          for (int q = 0; q < 4; q++) e[u][q] = ex2(e[u][q] - r[u][q >> 1]);
          r[u][0] = e[u][0] + e[u][1]; r[u][1] = e[u][2] + e[u][3];
        }
#pragma unroll
        for (int d = 1; d <= 2; d++)
#pragma unroll
          for (int q = 0; q < 4; q++) r[q >> 1][q & 1] += __shfl_xor_sync(0xffffffffu, r[q >> 1][q & 1], d);
#pragma unroll
        for (int u = 0; u < 2; u++) {
          const float rx = rcp(r[u][0]), ry = rcp(r[u][1]);
          px[u] = pack2(e[u][0] * rx, e[u][1] * rx); py[u] = pack2(e[u][2] * ry, e[u][3] * ry);
        }
        uint32_t o[8][2];
        uint4 ro[4];
#pragma unroll
        for (int q = 0; q < 8; q++) {
          float d[4] = {0.f, 0.f, 0.f, 0.f};
          const int t = 16 + 8 * hp + q, u = q >> 2;
          mma16816(d, px[u] & mhi, 0u, px[u] & ~mhi, py[u] & mhi, PH[t], P0[t]);
          mma1688(d, 0u, py[u] & ~mhi, P1[t]);
          o[q][0] = pack2(d[0], d[1]); o[q][1] = pack2(d[2], d[3]);
        }
#pragma unroll
        for (int q = 0; q < 4; q++) ro[q] = make_uint4(o[4 * (q & 1)][q >> 1], o[4 * (q & 1) + 1][q >> 1], o[4 * (q & 1) + 2][q >> 1], o[4 * (q & 1) + 3][q >> 1]);
        img_store(ro, x.img(0, hp));
        publish(hp, x);
        uint32_t xr[16];
        if (L) img_load(xr, tile, x);
        else {
#pragma unroll
          for (int q = 0; q < 4; q++) {
            uint32_t v[4];
            ldsm4(x.maddr(tile, 2 * q), v);
            xr[2 * q] = v[0]; xr[8 + 2 * q] = v[1]; xr[2 * q + 1] = v[2]; xr[9 + 2 * q] = v[3];
          }
          __syncwarp();
        }
        img_sts(ro, tile, x);
        img_unpack(acc + 32 * hp, xr);
      }
    } else {
      float kv[128];
      float (&kv0)[64] = reinterpret_cast<float (&)[64]>(kv[0]);
      float (&kv1)[64] = reinterpret_cast<float (&)[64]>(kv[64]);
      auto mma8 = [&](uint32_t as, uint32_t bs, int i, bool fence) {
        const uint32_t da = desc_lo(SB + OFF_A, 16) + as * (SLOT / 16), db = desc_lo(SB + OFF_B, 8192) + bs * (SLOT / 16);
        if (fence) wgmma_fence();
#pragma unroll
        for (int k = 0; k < 4; k++) {
          wgmma_ss_n128(kv0, da + (k >> 1) * 32 + (k & 1) * 2, HA64, db + 128 * k, i + k);
          wgmma_ss_n128(kv1, da + 512 + (k >> 1) * 32 + (k & 1) * 2, HA64, db + 128 * k, i + k);
        }
        wgmma_commit();
      };
      constexpr uint32_t dm = desc_lo(SB + OFF_MB, 0);
      auto relB = [&](uint32_t s) { mbar_arrive_n(sb + BAR_EMPTYB + s * 8, 2); };
      auto skip = [&]() {
#pragma unroll
        for (int q = 0; q < 6 - NJ; q++) adv<NA>(x.ra);
        x.rb.s = w ? (2 + NJ) % 6 : 4;
        if (!w && NJ < 4) x.rb.ph ^= 1;
      };
      static_assert(NA == 5 && NB == 6, "ring arithmetic");
      mma8(x.ra.s, x.rb.s + w, 0, true);
      gemm_next<256>(x);
#pragma unroll 1
      for (int i = 1; i < NJ; i++) {
        mbar_wait2(x.fullA(x.ra.s), x.ra.ph, x.fullB(x.rb.s + w), x.rb.ph);
        mma8(x.ra.s, x.rb.s + w, 1, true);
        if (i == XR) { img_store(r1, x.img(XBUF(L), 1)); publish(3, x); }
        if (i == XS) stats_send(ts, L, x);
        wgmma_wait<1>();
        if (x.elected) { x.releaseA(x.pa); relB(x.pb + w); }
        gemm_next<256>(x);
      }
      if (w) {
        wgmma_wait<0>();
        if (x.elected) { x.releaseA(x.pa); relB(x.pb + 1); }
        skip();
        asm volatile("bar.sync 7, 256;" ::: "memory");
      }
      TSL_(8);
      {
        const int t = lane_id() + 32 * x.warp;
        uint32_t mask = t < 2 ? ((w ? (t ? 0xFF3Fu : 0x3FFFu) : 0xFFFFu) >> (NJ - 1)) & (w ? ~1u : ~0u) : 0u, cnt = 1 + t;
        bool ready = false;
#pragma unroll 1
        for (int i = NJ; i < 16; i++) {
          if (!ready) mbar_wait2(x.fullA(x.ra.s), x.ra.ph, x.fullB(x.rb.s), x.rb.ph);
          mma8(x.ra.s, x.rb.s, 1, true);
          const uint32_t bar = sb + (t ? BAR_EMPTYB + x.pb * 8 : BAR_EMPTYA + x.pa * 8);
          gemm_next<128>(x);
          if (w && (i | 4) == 15) x.rb.s = 4;
          ready = mbar_probe2(x.fullA(x.ra.s), x.ra.ph, x.fullB(x.rb.s), x.rb.ph);
          wgmma_wait<1>();
          if (mask & 1) mbar_arrive_n(bar, cnt);
          mask >>= 1; cnt = 2;
          if (i == 8 && w) asm volatile("bar.arrive 9, 256;" ::: "memory");
          if (i == 9) TSL_(10);
        }
        mbar_wait2(sb + BAR_STAT, 1, sb + BAR_CS + 8, 0);
        wgmma_fence();
        wgmma_r1_n128(kv0, dm, dcs + 96 + 96 * w, 1);
        wgmma_r1_n128(kv1, dm + 64, dcs + 96 + 96 * w, 1);
        wgmma_commit();
        if (w == 0) asm volatile("bar.arrive 7, 256;" ::: "memory");
        wgmma_wait<1>();
        if (mask & 1) mbar_arrive_n(sb + (t ? BAR_EMPTYB + x.pb * 8 : BAR_EMPTYA + x.pa * 8), 2);
      }
      const Stats s0 = load_stats(0, x), s1 = load_stats(1, x), st = w ? s1 : s0;
      if (w == 0) skip();
      const uint32_t h0 = x.held(0), h1 = x.held(1);
      auto vreg = [&](int ks) { return ks < 6 ? OFF_A + (ks < 3 ? h0 * SLOT : h1 * SLOT - 15360) + ks * 5120 : OFF_S + 2048 + ks * 5120; };
      uint32_t tV[2], uu[4];
#pragma unroll
      for (int hf = 0; hf < 2; hf++) {
        tV[hf] = sb + vreg(4 * hf + x.warp) + ((x.lane >> 3) & 1) * 2560 + (x.lane & 7) * 16 + x.mhi * 128;
        const float i0 = rcp(hf ? s1.rstd0 : s0.rstd0), i1 = rcp(hf ? s1.rstd1 : s0.rstd1);
        const uint32_t h = pack2(i0, i1);
        uu[2 * hf] = pack2(lo16(h), i0 - lo16(h)); uu[2 * hf + 1] = pack2(hi16(h), i1 - hi16(h));
        asm volatile("" : "+r"(tV[hf]), "+r"(uu[2 * hf]), "+r"(uu[2 * hf + 1])::"memory");
      }
      wgmma_wait<0>();
      fence_regs(kv);
      TSL_(2);
      if (w == 0) {
        uint32_t f[2][18], ad[4];
#pragma unroll
        for (int q = 0; q < 18; q++) f[1][q] = 0u;
#pragma unroll
        for (int q = 0; q < 4; q++) ad[q] = x.maddr(sb + OFF_S, 2 * q);
        auto norm = [&](int un) {
          uint32_t* u = f[un & 1];
          const Stats& sn = (un & 2) ? s1 : s0;
#pragma unroll
          for (int sg = 0; sg < 2; sg++) {
            uint32_t v = u[16 + sg];
            v = add2(v, __shfl_xor_sync(0xffffffffu, v, 1)); v = add2(v, __shfl_xor_sync(0xffffffffu, v, 2));
            const float a = rcp(lo16(v)) * sn.rstd0, b = rcp(hi16(v)) * sn.rstd1;
            const uint32_t r0 = pack2(a, a), r1_ = pack2(b, b);
#pragma unroll
            for (int q = 8 * sg; q < 8 * sg + 8; q++) u[q] = mul2(u[q], (q & 1) ? r1_ : r0);
#pragma unroll
            for (int q = 2 * sg; q < 2 * sg + 2; q++) stsm4(ad[q] + (un & 1) * SLOT + (un >> 1) * 8192, u[4 * q], u[4 * q + 1], u[4 * q + 2], u[4 * q + 3]);
          }
        };
        auto unit = [&](int un) { return kv + ((un >> 1) & 1) * 64 + (un & 1) * 16 + (un >> 2) * 32; };
        hedgehog_scale<0>(kv, s0, nullptr);
#pragma unroll 1
        for (int it = 0;; it++) {
#pragma unroll
          for (int un = 0; un < 4; un++) {
            if (un == 1) {
              if (it) asm volatile("bar.sync 9, 256;" ::: "memory");
#pragma unroll
              for (int q = 0; q < 4; q++) ad[q] -= it * (OFF_S - OFF_B - 2 * SLOT);
            }
            norm((un + 3) & 3);
            dual_exp(unit(un), f[un & 1], x.goff);
            hedgehog_scale<KEEP>(unit(un + 1), ((un + 1) & 2) ? s1 : s0, f[(un + 1) & 1]);
          }
          if (it) break;
#pragma unroll
          for (int q = 0; q < 32; q++) {
            asm volatile("mov.b32 %0, %1;" : "=f"(kv[q]) : "f"(kv[q + 32]));
            asm volatile("mov.b32 %0, %1;" : "=f"(kv[q + 64]) : "f"(kv[q + 96]));
            if (q < 16) kv[32 + q] = 0.f;
          }
        }
        norm(3);
        TSL_(3);
      } else {
        wg_bar(w);
#pragma unroll
        for (int hf = 0; hf < 2; hf++) {
          stsm4(tV[hf] + 512 + x.mhi * 512, uu[2 * hf], uu[2 * hf + 1], uu[2 * hf], uu[2 * hf + 1]);
          stsm4(tV[hf] + 1792 + x.mhi * 512, uu[2 * hf], uu[2 * hf + 1], uu[2 * hf], uu[2 * hf + 1]);
#pragma unroll
          for (int q = 0; q < 8; q++) {
            const float* u = kv + 64 * hf + 8 * q;
            stsm4(tV[hf] + (q >> 1) * 640 + (q & 1) * 256, pack2(u[0], u[1]), pack2(u[2], u[3]), pack2(u[4], u[5]), pack2(u[6], u[7]));
          }
        }
        TSL_(3);
      }
      {
        float d[2][20];
        uint4* dst = &g_kvpart[x.j()][w * 4 + x.warp][0][x.m() * 32 + x.lane];
        unsigned* dz = reinterpret_cast<unsigned*>(&g_kvpart[x.j()][w * 4 + x.warp][x.c & 1][512]) + x.m() * 8 + x.g;
        asm volatile("" : "+l"(dst), "+l"(dz)::"memory");
        fence_async_smem();
        cta_bar();
        TSL_(11);
        uint32_t pk[9];
        auto prep = [&](float (&u)[20]) {
          fence_regs(u);
#pragma unroll
          for (int q = 0; q < 8; q++) pk[q] = pack2(u[((q >> 1) & 2) + 4 * (q & 3)], u[((q >> 1) & 2) + 4 * (q & 3) + 1]);
          pk[8] = __float_as_uint((x.c & 1) ? u[18] + u[19] : u[16] + u[17]);
#pragma unroll
          for (int q = 0; q < 9; q += 4) pk[q] = (pk[q] & ~1u) | (L == 1);
        };
        auto send = [&](int hp) {
          st_v4(dst + hp * 16 * 544, pk[0], pk[1], pk[2], pk[3]); st_v4(dst + (hp * 16 + 1) * 544, pk[4], pk[5], pk[6], pk[7]);
          st_flag(dz + hp * 16 * 544 * 4, pk[8]);
        };
        wgmma_fence();
#pragma unroll
        for (int q = 0; q < 17; q++) {
          if (q < 16) wgmma_ss_n40_tt(d[q >> 3], desc_lo(SB + (q < 8 ? OFF_S : OFF_B + 2 * SLOT), 1024) + w * (SLOT / 16) + 128 * (q & 7), desc_lo(SB + vreg(q & 7), 2560) + (w + (q >> 3) * 2) * 40, q & 7);
          else wgmma_r1_n128(acc, dm + w * 64, dcs, 0);
          if (q == 7 || q == KVS || q == 16) wgmma_commit();
          if (q == KVS) { wgmma_wait<1>(); prep(d[0]); send(0); mbar_wait2(x.fullA(x.ra.s), x.ra.ph, x.fullB(x.rb.s), x.rb.ph); wgmma_fence(); }
        }
        gemm_issue<128, false>(acc, x, true); gemm_next<128>(x);
        wgmma_wait<1>();
        x.releaseA(h0); x.releaseA(h1); x.releaseB(2); x.releaseB(3);
        if (x.lane == 0) mbar_arrive(sb + BAR_SIGT);
        prep(d[1]);
        TSL_(4);
#pragma unroll 1
        for (int seg = 0; seg < 2; seg++) {
          const int n0 = w ? PS1 : PS0;
          gemm_run(acc, x, seg ? 15 - n0 : n0, seg, seg ? L : 0);
          if (seg == 0) send(1);
        }
      }
      gemm_end(acc, x);
      TSL_(5);
      {
        float dp[2][20], dn[2][20];
        uint32_t f[4][16];
        auto mma = [&](int h) {
          if (!(h & 1)) mbar_wait(sb + BAR_KV + h * 4, L >> 1);
          if (h == 0) TSL_(9);
          const uint32_t db = desc_lo(SB + OFF_S + h * 5120, 128);
          const uint32_t (&a)[16] = f[h];
          wgmma_fence();
          wgmma_rs_n40(dp[h & 1], a[0], a[1], a[2], a[3], db, 0);
          wgmma_rs_n40(dn[h & 1], a[8], a[9], a[10], a[11], db + 160, 0);
          wgmma_rs_n40(dp[h & 1], a[4], a[5], a[6], a[7], db + 80, 1);
          wgmma_rs_n40(dn[h & 1], a[12], a[13], a[14], a[15], db + 240, 1);
          wgmma_commit();
        };
        uint32_t xr[16];
        auto fin = [&](int h) {
          const uint32_t tile = x.aslot(x.held(h >> 1));
          if (!(h & 1)) img_load(xr, tile, x);
          float (&u)[20] = dp[h & 1];
          float (&v)[20] = dn[h & 1];
          fence_regs(u); fence_regs(v);
#pragma unroll
          for (int r = 0; r < 2; r++) {
            float cc = u[17 + 2 * r] * rcp(v[17 + 2 * r]);
            const float aa = rcp(fmaf(v[16 + 2 * r], cc, fmaf(u[17 + 2 * r], 1e-6f, u[16 + 2 * r])));
            cc *= aa;
            uint32_t o[4];
#pragma unroll
            for (int t = 0; t < 4; t++) o[t] = pack2(fmaf(u[4 * t + 2 * r], aa, v[4 * t + 2 * r] * cc), fmaf(u[4 * t + 2 * r + 1], aa, v[4 * t + 2 * r + 1] * cc));
            x.img(0, h >> 1)[r * 64 + (h & 1) * 32] = make_uint4(o[0], o[1], o[2], o[3]);
            sts128(tile + r * 1024 + (h & 1) * 512 + x.oo() * 16, o[0], o[1], o[2], o[3]);
          }
          if (h & 1) { publish(h >> 1, x); img_unpack(acc + 16 * (h - 1), xr); }
        };
        auto scale = [&](int h) { hedgehog_scale<0>(acc + 16 * h, st, nullptr); };
        auto ex = [&](int h) { dual_exp_rcp(acc + 16 * h, f[h]); };
        scale(0);
        ex(0); scale(1); mma(0);
        ex(1); wgmma_wait<0>(); fin(0); scale(2); mma(1);
        ex(2); wgmma_wait<0>(); fin(1); scale(3); mma(2);
        ex(3); wgmma_wait<0>(); fin(2); mma(3);
        wgmma_wait<0>(); fin(3);
      }
    }
    if (PW & 2) { mbar_wait(x.fullB(x.rb.s), x.rb.ph); fence_regs(acc); }
    fence_async_smem();
    wg_bar(w);
    TSL_(6);
    rewind2<NA>(x.ra);
    gemm_issue<128, false>(acc, x, PW & 2); gemm_next<128>(x);
#pragma unroll 1
    for (int seg = L >= TSL ? 0 : 1; seg < 2; seg++) {
      gemm_run(acc, x, L >= TSL ? (seg ? TSK : 15 - TSK) : 15, seg);
      if (L >= TSL) {
        if (seg == 0 && w == 1) asm volatile("bar.sync 6, 256;" ::: "memory");
        if (seg == 1 && w == 0) asm volatile("bar.arrive 6, 256;" ::: "memory");
      }
    }
    gemm_end(acc, x);
    TSL_(7);
    rewind2<NA>(x.ra);
    out_epilogue(acc, r1, ts, P.out + goff, L, x);
    TSL_(13);
  }
}

typedef unsigned long long u64;
template <class T> __device__ __forceinline__ T* early(T* p) { return (T*)__shfl_xor_sync(0xffffffffu, (u64)p, 1); }
__device__ __forceinline__ void pause(uint32_t GAP) {
  if (GAP) { uint32_t t0, t; asm volatile("mov.u32 %0, %%clock;" : "=r"(t0)); do { asm volatile("mov.u32 %0, %%clock;" : "=r"(t)); } while (t - t0 < GAP); }
}
__device__ __forceinline__ u64 order_table(int kind, int j) {
  const int i = threadIdx.x & 15;
  const unsigned v = (unsigned)(kind == 2 ? q_order(i, j) : kv_order(i, j, kind)) << (4 * (i & 7));
  return (u64)__reduce_or_sync(0xffffffffu, i < 8 ? 0u : v) << 32 | __reduce_or_sync(0xffffffffu, i < 8 ? v : 0u);
}

__device__ __forceinline__ void b_producer(const Params& P, uint32_t sb, unsigned vb) {
  const int j = cta_j(vb);
  const u64 t0 = order_table(0, j), t1 = order_table(1, j), t2 = order_table(2, j);
  Ring r = {PRE_B % NB, PRE_B < NB};
#pragma unroll 1
  for (int sg = 0; sg < 20; sg++) {
    const int L = sg / 5, p = sg - 5 * L, wt = L & 1;
    int n = p >= 3 ? 16 : (wt ? (p ? 16 - NJ : 2 * NJ) : (p ? 0 : (L ? 32 : 32 - PRE_B)));
    u64 tab = p == 3 ? t2 : (sg == 0 ? t0 >> (2 * PRE_B) : (p == 1 || p == 2 ? t1 >> (4 * NJ) : t1));
    const CUtensorMap* tm = p == 4 ? &P.mwo[wt] : &P.mw[wt ? 1 : L];
    const uint4* img = &g_wf[p != 3][j][0][0];
    int col = (p >= 3 ? 0 : (p == 2 ? 2048 : 1024)) + 128 * j;
    const int flip = p == 0 ? 3072 : 0;
    const bool fold = wt && p != 4;
    if (sg == 5 || sg == 8) { mbar_wait(sb + (sg == 5 ? BAR_WPHI : BAR_CS + 8), sg == 5); fence_async_global(); }
    if (DEFER && p == 4 && ((DEFL >> wt) & 1)) {
      Ring q = r;
      for (int u = 0; u < DEFER; u++) adv<NB>(q);
      mbar_wait(sb + BAR_EMPTYB + q.s * 8, q.ph);
    }
#pragma unroll 1
    for (; n > 0; n--) {
      const int kb = (int)tab & 15;
      mbar_wait(sb + BAR_EMPTYB + r.s * 8, r.ph);
      if (elect()) {
        mbar_expect_tx(sb + BAR_FULLB + r.s * 8, SLOT);
        if (fold && col < 2048) bulk_load(sb + OFF_B + r.s * SLOT, img + kb * 1024, SLOT, sb + BAR_FULLB + r.s * 8);
        else tma_load_w(sb + OFF_B + r.s * SLOT, tm, sb + BAR_FULLB + r.s * 8, col, kb);
      }
      adv<NB>(r);
      if (p == 2 && (n | 4) == 5) r.s = 4;
      col ^= flip;
      if (!(col & flip & 2048)) tab >>= 4;
    }
  }
}

__device__ __forceinline__ void a_loader(const Params& P, uint32_t sb, unsigned vb) {
  const int j = cta_j(vb), m = cta_m(vb);
  const u64 t1 = order_table(1, j), t2 = order_table(2, j);
  Ring r = {PRE_A % NA, PRE_A < NA};
  {
    u64 tab = order_table(0, j) >> (4 * PRE_A);
#pragma unroll 1
    for (int i = PRE_A; i < 33; i++) {
      if (i == 17) tab = t2;
      mbar_wait(sb + BAR_EMPTYA + r.s * 8, r.ph);
      if (elect()) {
        mbar_expect_tx(sb + BAR_FULLA + r.s * 8, SLOT);
        if (i != 14) tma_load_3d(sb + OFF_A + r.s * SLOT, &P.mx, sb + BAR_FULLA + r.s * 8, ((int)tab & 15) * 64, m * 64, 0);
        else {
          tma_load_w(sb + OFF_A + r.s * SLOT, &P.mw[1], sb + BAR_FULLA + r.s * 8, 1024 + 128 * j, m);
          mbar_expect_tx(sb + BAR_WPHI, 8192); tma_load_2d(sb + OFF_S + 4096, &P.mwphi, sb + BAR_WPHI, 0, 128 * j);
        }
        if (i == PF0 || i == PF1 || i == PF2)
          tma_prefetch_w(i == PF0 ? &P.mw[1] : &P.mwo[i == PF2], (i == PF0 ? 1024 : 0) + 128 * j, m);
      }
      adv<NA>(r);
      if (i != 14) tab >>= 4;
    }
  }
  const unsigned tag = get_tag(sb);
  unsigned seen = 0;
#pragma unroll 1
  for (int sg = 0; sg < 27; sg++) {
    const int L = sg >> 3, p = sg & 7, q = p >= 3 ? p - 3 : p;
    if (p == 0 && (L & 1)) {
#pragma unroll 1
      for (int h = 0; h < 2; h++) {
        poll_flags(&g_kvfflag[L >> 1][j][h][0], 8, 0xFFu, tag);
        if (elect()) { mbar_expect_tx(sb + BAR_KV + h * 8, 10240); bulk_load(sb + OFF_S + h * 10240, &g_kvfin[j][8 * h][0], 10240, sb + BAR_KV + h * 8); }
      }
      TS(4, 14 + L);
    }
    int n = q == 0 ? 4 : (q == 1 ? 3 : (q == 2 ? 7 : (q == 3 ? ((L & 1) ? 0 : 16 - NJ) : 16)));
    u64 tab = q == 4 ? t2 : t1 >> (q == 0 ? 8 : (q == 1 ? 24 : (q == 2 ? 36 : 4 * NJ)));
    const uint4* img = &g_img[p >= 3 ? XBUF(L + 1) : 0][m][0][0];
    const uint32_t gap = p == 0 ? G0 : (p == 3 ? G3 : (q < 3 ? G1 : G4));
    bool poll = q == 0 || q == 2 || (q == 1 && seen != 0xFFFFFFFFu);
#pragma unroll 1
    for (; n > 0; n--) {
      const uint4* src = img + ((int)tab & 15) * 1024;
      src = early(src);
      mbar_wait(sb + BAR_EMPTYA + r.s * 8, r.ph);
      if (elect()) mbar_expect_tx(sb + BAR_FULLA + r.s * 8, SLOT);
      if (poll) {
        const int lane = threadIdx.x & 31, nn = p >= 3 ? PNX : PNO;
        const unsigned* f = (p >= 3 ? &g_xflag[L + 1][0][m][0] : &g_oflag[L][0][m][0]) + (q == 2 ? 512 : 0) + (lane & 7);
        if (q == 0 || (PN2 && q == 2)) f += (((lane >> 3) & (nn - 1)) - (m & (nn - 1))) * 32;
        const unsigned need = q == 0 ? 0x0F0F0F0Fu << (~j & 4) : 0xFFFFFFFFu;
        if (q == 0) mbar_wait(sb + BAR_SIGP + (p ? 16 : 0), L & 1);
        int it = 0;
        do { seen = __ballot_sync(0xffffffffu, ld_flag(f) == tag); if (++it > (1 << 22)) __trap(); } while ((seen & need) != need);
        if (q == 0) TS(2, p == 0 ? 5 + L * 8 : 9 + L * 8);
        poll = false;
      }
      if (elect()) bulk_load(sb + OFF_A + r.s * SLOT, src, SLOT, sb + BAR_FULLA + r.s * 8);
      adv<NA>(r);
      tab >>= 4;
      pause(gap);
    }
  }
}

__device__ __forceinline__ uint2 sum_packets(float (&a)[8], uint32_t addr, int n) {
  uint2 ok = make_uint2(~0u, 0u);
#pragma unroll 1
  for (int b = 0; b < n; b += KB) {
    uint4 v[KB];
#pragma unroll
    for (int u = 0; u < KB; u++) lds128(addr + (b + u) * 512, v[u].x, v[u].y, v[u].z, v[u].w);
#pragma unroll
    for (int u = 0; u < KB; u++) {
      ok.x &= v[u].x; ok.y |= v[u].x;
      a[0] += lo16(v[u].x); a[1] += hi16(v[u].x); a[2] += lo16(v[u].y); a[3] += hi16(v[u].y);
      a[4] += lo16(v[u].z); a[5] += hi16(v[u].z); a[6] += lo16(v[u].w); a[7] += hi16(v[u].w);
    }
  }
  return ok;
}
__device__ __forceinline__ void helper_bar() { asm volatile("bar.sync 4, 64;" ::: "memory"); }
__device__ __forceinline__ void helper(const Params& P, uint32_t sb, int w, unsigned vb) {
  const int j = cta_j(vb), m = cta_m(vb);
  if (w == 0) {
    if (elect()) {
      const unsigned t = atomicAdd(&g_ctr, 1u) / NCTA + 1u;
      asm volatile("st.shared.u32 [%0], %1;" ::"r"(sb + OFF_EPOCH), "r"(t) : "memory");
      mbar_arrive(sb + BAR_EPOCH);
    }
  }
  const unsigned tag = get_tag(sb);
  mbar_wait(sb + BAR_FULLB + 24, 0);
  const uint32_t stg = sb + OFF_T + w * 12288, stb = sb + BAR_STG + w * 24;
  Ring rs = {0, 0};
  auto cs_image = [&](int L) {
      const int lane = lane_id();
      poll_flags(&g_csflag[L][j][0], 16, L ? CSNEED : 0xFFFu, tag);
#pragma unroll
      for (int p = 0; p < 3; p++) {
        const uint4 u = ldcg4(&g_cs[L][0][p * 1024 + 128 * j + lane * 4]), v = ldcg4(&g_cs[L][1][p * 1024 + 128 * j + lane * 4]);
        const float c0 = __uint_as_float(u.x) + __uint_as_float(v.x), c1 = __uint_as_float(u.y) + __uint_as_float(v.y);
        const float c2 = __uint_as_float(u.z) + __uint_as_float(v.z), c3 = __uint_as_float(u.w) + __uint_as_float(v.w);
        const uint32_t h0 = pack2(c0, c1), h1 = pack2(c2, c3), dst = sb + OFF_CS + (p * 16 + (lane >> 1)) * 96 + L * 48 + (lane & 1) * 8;
        sts64(dst, h0, h1); sts64(dst + 16, pack2(c0 - lo16(h0), c1 - hi16(h0)), pack2(c2 - lo16(h1), c3 - hi16(h1))); sts64(dst + 32, h0, h1);
        if (L == 0) { sts64(dst + 48, 0u, 0u); sts64(dst + 64, 0u, 0u); sts64(dst + 80, 0u, 0u); }
      }
      if (L == 0 && lane < 4) sts64(sb + OFF_CS + 4608 + lane * 8, 0u, 0u);
      fence_async_smem();
      __syncwarp();
      if (elect()) mbar_arrive(sb + BAR_CS + L * 8);
      TS(4, 2 + L * 2);
  };
#pragma unroll 1
  for (int L = 0; L < 4; L++) {
    const int lane = lane_id();
    if (L == 0) {
      {
        const int wt = m >= 12, col = ((0x2021 >> (m & 12)) & 3) * 1024 + 128 * j + (m & 3) * 32;
        const CUtensorMap* tm = &P.mcs[wt];
        if (D2 && wt) __nanosleep(D2);
        constexpr int nb = 8;
        float a[8] = {0.f, 0.f, 0.f, 0.f, 0.f, 0.f, 0.f, 0.f};
#pragma unroll 1
        for (int b = -3; b < nb; b++) {
          if (b >= 0) {
            mbar_wait(stb + rs.s * 8, rs.ph);
            sum_packets(a, stg + rs.s * 4096 + lane * 16, 8);
            fence_async_smem();
            __syncwarp();
          }
          const uint32_t sl = b < 0 ? (rs.s + b + 3) % 3 : rs.s;
          if (b + 3 < nb && elect()) { mbar_expect_tx(stb + sl * 8, 4096); tma_load_2d(stg + sl * 4096, tm, stb + sl * 8, col, (w * (16 - nb) + b + 3) * 64); }
          if (b >= 0) adv<3>(rs);
        }
#pragma unroll
        for (int u = 0; u < 8; u++) {
          a[u] += __shfl_xor_sync(0xffffffffu, a[u], 4); a[u] += __shfl_xor_sync(0xffffffffu, a[u], 8); a[u] += __shfl_xor_sync(0xffffffffu, a[u], 16);
        }
        if (lane < 4) {
          float4* dst = reinterpret_cast<float4*>(&g_cs[wt][w][col + lane * 8]);
          dst[0] = make_float4(a[0], a[1], a[2], a[3]); dst[1] = make_float4(a[4], a[5], a[6], a[7]);
        }
        helper_bar();
        if (w == 0 && elect()) { fence_gpu(); st_flag(&g_csflag[wt][j][m], tag); }
      }
      if (w == 0) TS(4, 1 + L * 2);
    }
    if (w == 1) {
      if (L > 0) { mbar_wait(sb + BAR_SIGP + 24, (L - 1) & 1); __nanosleep(SD); }
#pragma unroll 1
      for (int p = 0; p < 2; p++) {
        uint4 v[8];
        for (int it = 0;; it++) {
          bool ok = true;
#pragma unroll
          for (int t = 0; t < 8; t++) v[t] = ld_pkt(&g_stats[m][p][t][lane]);
#pragma unroll
          for (int t = 0; t < 8; t++) ok = ok && (v[t].w & 15u) == seq4(tag, L);
          if (__all_sync(0xffffffffu, ok)) break;
          __nanosleep(200);
          if (it > (1 << 20)) __trap();
        }
        float s0 = 0.f, q0 = 0.f, s1 = 0.f, q1 = 0.f;
#pragma unroll
        for (int t = 0; t < 8; t++) { s0 += __uint_as_float(v[t].x); q0 += __uint_as_float(v[t].y); s1 += __uint_as_float(v[t].z); q1 += __uint_as_float(v[t].w & ~15u); }
        s0 *= (1.f / 1024); s1 *= (1.f / 1024);
        sts64(sb + OFF_MR + p * 256 + lane * 8, __float_as_uint(rsqrtf(fmaxf(q0 * (1.f / 1024) - s0 * s0, 0.f) + 1e-5f)),
              __float_as_uint(rsqrtf(fmaxf(q1 * (1.f / 1024) - s1 * s1, 0.f) + 1e-5f)));
#pragma unroll
        for (int r = 0; r < 2; r++) {
          const float v = -0.5f * (r ? s1 : s0);
          const uint32_t hh = pack2(v, v), hl = pack2(v, v - lo16(hh));
          const bool b = L & 1;
          sts128(sb + (b ? OFF_MB : OFF_MA) + p * 1024 + (lane >> 3) * 256 + r * 128 + (lane & 7) * 16, b ? 0u : hh, b ? hh << 16 : hl >> 16, b ? hl : 0u, 0u);
        }
      }
      fence_async_smem();
      __syncwarp();
      if (elect()) {
        mbar_arrive(sb + BAR_STAT);
      }
      TS(2, 0 + L * 8);
    }
    if (L == w) cs_image(L);
    if (L & 1) {
      const uint32_t flip = L == 1 ? 0u : 1u;
      mbar_wait(sb + BAR_SIGT, 1);
      {
        int it = 0;
        if (PSL) __nanosleep(m < 8 ? PSL : PSL + 600);
        while (!__all_sync(0xffffffffu, (ld_flag(reinterpret_cast<const unsigned*>(&g_kvpart[j][m][w][512]) + (lane & 15) * 8) ^ flip) & 1u)) { if (PSL) __nanosleep(100); if (++it > (1 << 22)) __trap(); }
        fence_async_global();
      }
      if (w == 0) TS(4, 6 + L * 2);
      for (int it = 0;; it++) {
        if (elect()) { mbar_expect_tx(stb + rs.s * 8, 8704); bulk_load(stg, &g_kvpart[j][m][w][0], 8704, stb + rs.s * 8); }
        mbar_wait(stb + rs.s * 8, rs.ph);
        adv<3>(rs);
        float a[8] = {0.f, 0.f, 0.f, 0.f, 0.f, 0.f, 0.f, 0.f};
        float z = 0.f;
        uint32_t ok = 1u;
#pragma unroll
        for (int u = 0; u < 4; u++) { const float v = lds32f(stg + 8192 + u * 128 + (lane & 3) * 32 + (lane >> 2) * 4); z += v; ok &= __float_as_uint(v) ^ flip; }
        const uint2 tg = sum_packets(a, stg + lane * 16, 16);
        ok &= flip ? ~tg.y : tg.x;
        uint4* img = &g_kvfin[j][m][w * 8 + (lane >> 2)];
        img[(lane & 3) * 16] = make_uint4(pack2(a[0], a[1]), pack2(a[2], a[3]), pack2(a[4], a[5]), pack2(a[6], a[7]));
        reinterpret_cast<uint32_t*>(img + 64)[lane & 3] = pack2(qsum(z), 1.f);
        if (__all_sync(0xffffffffu, ok & 1u)) break;
        fence_async_smem();
        if (it > (1 << 16)) __trap();
      }
      if (w == 0) TS(4, 7 + L * 2);
      helper_bar();
      if (w == 1 && elect()) { fence_gpu(); st_flag(&g_kvfflag[L >> 1][j][m >> 3][m & 7], tag); }
      if (w == 1 && L == 1) TS(4, 20);
    } else {
      mbar_wait(sb + BAR_SIGT, 0);
      if (w == 0) {
        if (elect()) { fence_gpu(); st_flag(&g_hflag[L >> 1][m][j][0], tag); st_flag(&g_kflag[j][m], tag); }
        if (L == 0) {
          __nanosleep(KSL);
          poll_flags(&g_kflag[j][0], 16, 0xFFFFu, tag);
          if (elect()) mbar_arrive(sb + BAR_WPHI);
        }
      } else if (m > 0) {
        poll_flags(&g_hflag[L >> 1][m - 1][j][0], 1, 1u, tag);
        if (elect()) { mbar_expect_tx(sb + BAR_HALO, 8192); bulk_load(sb + OFF_S + 8192, &g_halo[m - 1][j][0][0], 8192, sb + BAR_HALO); }
        TS(2, 2 + L * 8);
      }
    }
#pragma unroll 1
    for (int e = 0; e < (L < 3 && w == 0 ? 3 : 1); e++) {
      unsigned* flag = e == 0 ? &g_oflag[L][w][m][j] : &g_xflag[L + 1][e - 1][m][j];
      flag = early(flag);
      mbar_wait(sb + BAR_SIGP + (e == 0 ? w : e + 1) * 8, L & 1);
      TS(e == 2 ? 3 : 2 + w, (e ? 6 : 3) + L * 8);
      if (elect()) { fence_async_global(); fence_gpu(); st_flag(flag, tag); }
      TS(e == 2 ? 3 : 2 + w, (e ? 7 : 4) + L * 8);
    }
  }
}

__device__ __forceinline__ void spare(const Params& P, uint32_t sb, int id) {
  const int tid = threadIdx.x & 127, w = __shfl_sync(0xffffffffu, threadIdx.x >> 7, 0), lane = tid & 31, j = 2 * id + w;
  const uint32_t ring = w * 6 * SLOT, wp = 12 * SLOT + w * 8192, bar = sb + 13 * SLOT + w * 64;
  auto part = [&](int t) { return (t >> 4) ^ w; };
  auto load = [&](int t, uint32_t sl) {
    mbar_expect_tx(bar + sl * 8, t == 0 ? SLOT + 8192 : SLOT);
    tma_load_w(sb + ring + sl * SLOT, &P.mw[1], bar + sl * 8, part(t) * 1024 + 128 * j, t & 15);
  };
  if (tid == 0) {
    if (w == 2) sts32(sb + OFF_EPOCH, atomicAdd(&g_ctr, 1u) / NCTA + 1u);
    else {
      __nanosleep(D3);
#pragma unroll 1
      for (int t = 0; t < 5; t++) {
        mbar_init(bar + t * 8, 1);
        asm volatile("fence.mbarrier_init.release.cluster;" ::: "memory");
        load(t, t);
      }
      tma_load_2d(sb + wp, &P.mwphi, bar, 0, 128 * j);
    }
  }
  __syncthreads();
  const unsigned tag = get_tag<false>(sb);
  if (w == 2) {
    int it = 0;
    while ((int)(ld_flag(&g_ctr) - tag * NCTA) < 0) { if (++it > (1 << 22)) __trap(); }
    return;
  }
  Ring r = {4, 1};
  float d[64] = {}, cs[32] = {};
  auto fold = [&]() {
    mbar_wait(bar + r.s * 8, r.ph);
    wgmma_fence();
#pragma unroll
    for (int q = 0; q < 8; q++)
      wgmma_ss_n32(reinterpret_cast<float (&)[16]>(d[16 * (q >> 1)]), desc_lo(SB + ring + r.s * SLOT, 16) + (q >> 2) * 512 + (q & 3) * 2, desc_lo(SB + wp, 512) + q * 64, q & 1);
    wgmma_commit();
  };
  const int row = (tid >> 5) * 16 + (lane >> 2);
#pragma unroll 1
  for (int t = -1; t < 32; t++) {
    uint32_t f[32];
#pragma unroll
    for (int i = 0; i < 32; i++) { f[i] = pack2(d[2 * i], d[2 * i + 1]); cs[i & 30] += d[2 * i]; cs[i | 1] += d[2 * i + 1]; }
    wg_bar(w);
    if (tid == 0 && t >= 0 && t < 27) load(t + 5, r.s);
    __syncwarp();
    if (t < 31) adv<5>(r);
    fold();
    if (part(t) == 0 && t >= 0) {
#pragma unroll
      for (int q = 0; q < 8; q++)
        g_wf[0][j][t & 15][(q >> 2) * 512 + (row + 8 * (q & 1)) * 8 + (((q & 2) * 2 + (lane & 3)) ^ (lane >> 2))] =
            make_uint4(f[4 * (q & 6) + (q & 1)], f[4 * (q & 6) + (q & 1) + 2], f[4 * (q & 6) + (q & 1) + 4], f[4 * (q & 6) + (q & 1) + 6]);
    }
    wgmma_wait<0>();
    fence_regs(d);
    if ((t & 15) == 15) {
      if (t >= 0) {
        const uint32_t red = sb + ring + 5 * SLOT;
#pragma unroll
        for (int i = 0; i < 8; i++) sts128(red + (tid >> 2) * 512 + (i >> 1) * 128 + (lane & 3) * 32 + (i & 1) * 16, __float_as_uint(cs[4 * i]), __float_as_uint(cs[4 * i + 1]), __float_as_uint(cs[4 * i + 2]), __float_as_uint(cs[4 * i + 3]));
        wg_bar(w);
        float a = 0.f;
#pragma unroll 4
        for (int i = 0; i < 32; i++) a += lds32f(red + i * 512 + tid * 4);
        g_cs[1][0][part(t) * 1024 + j * 128 + tid] = a;
        wg_bar(w);
        if (tid == 0) {
          fence_gpu();
          st_flag(&g_csflag[1][j][part(t)], tag);
        }
        __syncwarp();
      }
#pragma unroll
      for (int i = 0; i < 32; i++) cs[i] = 0.f;
    }
  }
}

__global__ void __launch_bounds__(NTHREADS, 1) fused_kernel(const __grid_constant__ Params P) {
  extern __shared__ __align__(1024) uint8_t smem_raw[];
  constexpr uint32_t sb = SB;
  const int tid = threadIdx.x;
  const unsigned vb = vblock();
  if (vb >= 128) { spare(P, sb, vb - 128); return; }
  const int warp = __shfl_sync(0xffffffffu, tid >> 5, 0);
  if (elect()) {
    if (warp == 11) { prefetch_map(&P.mx); prefetch_map(&P.mw[0]); if (smem_u32(smem_raw) != SB) __trap(); }
    if (warp < 7) {
#pragma unroll
      for (int i = 0; i < 8; i++) mbar_init(sb + OFF_BAR + (warp * 8 + i) * 8, warp == 2 || warp == 3 ? 2 : (warp == 4 ? 8 : 1));
    }
    asm volatile("fence.mbarrier_init.release.cluster;" ::: "memory");
    if (warp < 2) {
      const int j = cta_j(vb);
#pragma unroll 1
      for (int i = 0; i < (warp == 0 ? PRE_B : PRE_A); i++) {
        const uint32_t bar = sb + BAR_FULLB + warp * 64 + i * 8;
        mbar_expect_tx(bar, SLOT);
        if (warp == 0) tma_load_w(sb + OFF_B + i * SLOT, &P.mw[0], bar, 1024 + (i & 1) * 1024 + 128 * j, kv_order(i >> 1, j, 0));
        else tma_load_3d(sb + OFF_A + i * SLOT, &P.mx, bar, kv_order(i, j, 0) * 64, cta_m(vb) * 64, 0);
      }
    }
  }
  if (tid == 0) TS(6, 0);
  __syncthreads();
  if (tid == 0) TS(6, 2);
  if (warp < 4) {
    reg_dealloc<PREGS>();
    if (warp == 0) b_producer(P, sb, vb);
    else if (warp == 1) a_loader(P, sb, vb);
    else helper(P, sb, warp - 2, vb);
  } else {
    reg_alloc<CREGS>();
    consumer(P, sb, (warp >> 2) - 1, vb);
  }
}

typedef CUresult (*EncodeFn)(CUtensorMap*, CUtensorMapDataType, cuuint32_t, void*, const cuuint64_t*, const cuuint64_t*,
                             const cuuint32_t*, const cuuint32_t*, CUtensorMapInterleave, CUtensorMapSwizzle,
                             CUtensorMapL2promotion, CUtensorMapFloatOOBfill);

void encode(EncodeFn fn, CUtensorMap* m, const void* ptr, int rank, const cuuint64_t* dims, const cuuint64_t* strides,
            const cuuint32_t* box, CUtensorMapSwizzle swz) {
  const cuuint32_t es[5] = {1, 1, 1, 1, 1};
  fn(m, CU_TENSOR_MAP_DATA_TYPE_BFLOAT16, rank, const_cast<void*>(ptr), dims, strides, box, es, CU_TENSOR_MAP_INTERLEAVE_NONE,
     swz, CU_TENSOR_MAP_L2_PROMOTION_L2_256B, CU_TENSOR_MAP_FLOAT_OOB_FILL_NONE);
}
void encode_w(EncodeFn fn, CUtensorMap* m, const void* ptr, int ncols, bool perm) {
  const cuuint64_t p = (cuuint64_t)ncols * 2, d[5] = {(cuuint64_t)ncols, 2, 4, 4, 32}, s[4] = {p, (perm ? 8 : 2) * p, (perm ? 2 : 8) * p, 32 * p};
  const cuuint32_t box[5] = {64, 2, 4, 4, 2};
  encode(fn, m, ptr, 5, d, s, box, CU_TENSOR_MAP_SWIZZLE_128B);
}

void encode_cs(EncodeFn fn, CUtensorMap* m, const void* ptr, int ncols) {
  const cuuint64_t d[2] = {(cuuint64_t)ncols, 1024}, s[1] = {(cuuint64_t)ncols * 2};
  const cuuint32_t box[2] = {32, 64};
  encode(fn, m, ptr, 2, d, s, box, CU_TENSOR_MAP_SWIZZLE_NONE);
}

}

extern "C" void kernel_launch(void* const* d_in, const int* in_sizes, int n_in, void* d_out, int out_size) {
  (void)in_sizes; (void)n_in; (void)out_size;
  void* fnp = nullptr;
  cudaDriverEntryPointQueryResult q;
  cudaGetDriverEntryPoint("cuTensorMapEncodeTiled", &fnp, cudaEnableDefault, &q);
  EncodeFn fn = (EncodeFn)fnp;
  Params P;
  {
    const cuuint64_t dims[3] = {1024, 1024, 2}, strides[2] = {4096, 2048};
    const cuuint32_t box[3] = {64, 64, 2};
    encode(fn, &P.mx, d_in[0], 3, dims, strides, box, CU_TENSOR_MAP_SWIZZLE_128B);
  }
  P.out = (uint4*)d_out;
  encode_w(fn, &P.mw[0], d_in[1], 3072, false);
  encode_w(fn, &P.mw[1], d_in[4], 3072, true);
  encode_w(fn, &P.mw[2], d_in[1], 3072, true);
  encode_w(fn, &P.mwo[0], d_in[2], 1024, true);
  encode_w(fn, &P.mwo[1], d_in[6], 1024, false);
  encode_cs(fn, &P.mcs[0], d_in[1], 3072);
  encode_cs(fn, &P.mcs[1], d_in[4], 3072);
  {
    const cuuint64_t dims[2] = {32, 1024}, strides[1] = {64};
    const cuuint32_t box[2] = {32, 128};
    encode(fn, &P.mwphi, d_in[5], 2, dims, strides, box, CU_TENSOR_MAP_SWIZZLE_64B);
  }
  cudaFuncSetAttribute(fused_kernel, cudaFuncAttributeMaxDynamicSharedMemorySize, SMEM_BYTES);
  fused_kernel<<<NCTA, NTHREADS, SMEM_BYTES, cudaStreamPerThread>>>(P);
}
```

```cpp
#include <cuda_runtime.h>
#include <cuda_bf16.h>
#include <cuda.h>
#include <stdint.h>

namespace {

__device__ __forceinline__ void wgmma_ss_n256(float (&d)[128], uint32_t da, uint32_t ha, uint32_t db, int sd) {
  asm volatile("{\n.reg .pred p;\n.reg .b64 a, b;\nsetp.ne.b32 p, %130, 0;\nmov.b64 a, {%128, %131};\nmov.b64 b, {%129, 0x40000040};\n"
    "wgmma.mma_async.sync.aligned.m64n256k16.f32.bf16.bf16 {%0,%1,%2,%3,%4,%5,%6,%7,%8,%9,%10,%11,%12,%13,%14,%15,%16,%17,%18,%19,%20,%21,%22,%23,%24,%25,%26,%27,%28,%29,%30,%31,%32,%33,%34,%35,%36,%37,%38,%39,%40,%41,%42,%43,%44,%45,%46,%47,%48,%49,%50,%51,%52,%53,%54,%55,%56,%57,%58,%59,%60,%61,%62,%63,%64,%65,%66,%67,%68,%69,%70,%71,%72,%73,%74,%75,%76,%77,%78,%79,%80,%81,%82,%83,%84,%85,%86,%87,%88,%89,%90,%91,%92,%93,%94,%95,%96,%97,%98,%99,%100,%101,%102,%103,%104,%105,%106,%107,%108,%109,%110,%111,%112,%113,%114,%115,%116,%117,%118,%119,%120,%121,%122,%123,%124,%125,%126,%127}, a, b, p, 1, 1, 0, 1;\n}\n"
    : "+f"(d[0]),"+f"(d[1]),"+f"(d[2]),"+f"(d[3]),"+f"(d[4]),"+f"(d[5]),"+f"(d[6]),"+f"(d[7]),"+f"(d[8]),"+f"(d[9]),"+f"(d[10]),"+f"(d[11]),"+f"(d[12]),"+f"(d[13]),"+f"(d[14]),"+f"(d[15]),"+f"(d[16]),"+f"(d[17]),"+f"(d[18]),"+f"(d[19]),"+f"(d[20]),"+f"(d[21]),"+f"(d[22]),"+f"(d[23]),"+f"(d[24]),"+f"(d[25]),"+f"(d[26]),"+f"(d[27]),"+f"(d[28]),"+f"(d[29]),"+f"(d[30]),"+f"(d[31]),"+f"(d[32]),"+f"(d[33]),"+f"(d[34]),"+f"(d[35]),"+f"(d[36]),"+f"(d[37]),"+f"(d[38]),"+f"(d[39]),"+f"(d[40]),"+f"(d[41]),"+f"(d[42]),"+f"(d[43]),"+f"(d[44]),"+f"(d[45]),"+f"(d[46]),"+f"(d[47]),"+f"(d[48]),"+f"(d[49]),"+f"(d[50]),"+f"(d[51]),"+f"(d[52]),"+f"(d[53]),"+f"(d[54]),"+f"(d[55]),"+f"(d[56]),"+f"(d[57]),"+f"(d[58]),"+f"(d[59]),"+f"(d[60]),"+f"(d[61]),"+f"(d[62]),"+f"(d[63]),"+f"(d[64]),"+f"(d[65]),"+f"(d[66]),"+f"(d[67]),"+f"(d[68]),"+f"(d[69]),"+f"(d[70]),"+f"(d[71]),"+f"(d[72]),"+f"(d[73]),"+f"(d[74]),"+f"(d[75]),"+f"(d[76]),"+f"(d[77]),"+f"(d[78]),"+f"(d[79]),"+f"(d[80]),"+f"(d[81]),"+f"(d[82]),"+f"(d[83]),"+f"(d[84]),"+f"(d[85]),"+f"(d[86]),"+f"(d[87]),"+f"(d[88]),"+f"(d[89]),"+f"(d[90]),"+f"(d[91]),"+f"(d[92]),"+f"(d[93]),"+f"(d[94]),"+f"(d[95]),"+f"(d[96]),"+f"(d[97]),"+f"(d[98]),"+f"(d[99]),"+f"(d[100]),"+f"(d[101]),"+f"(d[102]),"+f"(d[103]),"+f"(d[104]),"+f"(d[105]),"+f"(d[106]),"+f"(d[107]),"+f"(d[108]),"+f"(d[109]),"+f"(d[110]),"+f"(d[111]),"+f"(d[112]),"+f"(d[113]),"+f"(d[114]),"+f"(d[115]),"+f"(d[116]),"+f"(d[117]),"+f"(d[118]),"+f"(d[119]),"+f"(d[120]),"+f"(d[121]),"+f"(d[122]),"+f"(d[123]),"+f"(d[124]),"+f"(d[125]),"+f"(d[126]),"+f"(d[127])
    : "r"(da), "r"(db), "r"(sd), "r"(ha));
}
__device__ __forceinline__ void wgmma_ss_n128(float (&d)[64], uint32_t da, uint32_t ha, uint32_t db, int sd) {
  asm volatile("{\n.reg .pred p;\n.reg .b64 a, b;\nsetp.ne.b32 p, %66, 0;\nmov.b64 a, {%64, %67};\nmov.b64 b, {%65, 0x40000040};\n"
    "wgmma.mma_async.sync.aligned.m64n128k16.f32.bf16.bf16 {%0,%1,%2,%3,%4,%5,%6,%7,%8,%9,%10,%11,%12,%13,%14,%15,%16,%17,%18,%19,%20,%21,%22,%23,%24,%25,%26,%27,%28,%29,%30,%31,%32,%33,%34,%35,%36,%37,%38,%39,%40,%41,%42,%43,%44,%45,%46,%47,%48,%49,%50,%51,%52,%53,%54,%55,%56,%57,%58,%59,%60,%61,%62,%63}, a, b, p, 1, 1, 0, 1;\n}\n"
    : "+f"(d[0]),"+f"(d[1]),"+f"(d[2]),"+f"(d[3]),"+f"(d[4]),"+f"(d[5]),"+f"(d[6]),"+f"(d[7]),"+f"(d[8]),"+f"(d[9]),"+f"(d[10]),"+f"(d[11]),"+f"(d[12]),"+f"(d[13]),"+f"(d[14]),"+f"(d[15]),"+f"(d[16]),"+f"(d[17]),"+f"(d[18]),"+f"(d[19]),"+f"(d[20]),"+f"(d[21]),"+f"(d[22]),"+f"(d[23]),"+f"(d[24]),"+f"(d[25]),"+f"(d[26]),"+f"(d[27]),"+f"(d[28]),"+f"(d[29]),"+f"(d[30]),"+f"(d[31]),"+f"(d[32]),"+f"(d[33]),"+f"(d[34]),"+f"(d[35]),"+f"(d[36]),"+f"(d[37]),"+f"(d[38]),"+f"(d[39]),"+f"(d[40]),"+f"(d[41]),"+f"(d[42]),"+f"(d[43]),"+f"(d[44]),"+f"(d[45]),"+f"(d[46]),"+f"(d[47]),"+f"(d[48]),"+f"(d[49]),"+f"(d[50]),"+f"(d[51]),"+f"(d[52]),"+f"(d[53]),"+f"(d[54]),"+f"(d[55]),"+f"(d[56]),"+f"(d[57]),"+f"(d[58]),"+f"(d[59]),"+f"(d[60]),"+f"(d[61]),"+f"(d[62]),"+f"(d[63])
    : "r"(da), "r"(db), "r"(sd), "r"(ha));
}
__device__ __forceinline__ void wgmma_ss_n40_tt(float (&d)[20], uint32_t da, uint32_t db, int sd) {
  asm volatile("{\n.reg .pred p;\n.reg .b64 a, b;\nsetp.ne.b32 p, %22, 0;\nmov.b64 a, {%20, 0x40000040};\nmov.b64 b, {%21, 0x8};\n"
    "wgmma.mma_async.sync.aligned.m64n40k16.f32.bf16.bf16 {%0,%1,%2,%3,%4,%5,%6,%7,%8,%9,%10,%11,%12,%13,%14,%15,%16,%17,%18,%19}, a, b, p, 1, 1, 1, 1;\n}\n"
    : "+f"(d[0]),"+f"(d[1]),"+f"(d[2]),"+f"(d[3]),"+f"(d[4]),"+f"(d[5]),"+f"(d[6]),"+f"(d[7]),"+f"(d[8]),"+f"(d[9]),"+f"(d[10]),"+f"(d[11]),"+f"(d[12]),"+f"(d[13]),"+f"(d[14]),"+f"(d[15]),"+f"(d[16]),"+f"(d[17]),"+f"(d[18]),"+f"(d[19])
    : "r"(da), "r"(db), "r"(sd));
}
__device__ __forceinline__ void wgmma_ss_n32(float (&d)[16], uint32_t da, uint32_t db, int sd) {
  asm volatile("{\n.reg .pred p;\n.reg .b64 a, b;\nsetp.ne.b32 p, %18, 0;\nmov.b64 a, {%16, 0x40000040};\nmov.b64 b, {%17, 0x80000020};\n"
    "wgmma.mma_async.sync.aligned.m64n32k16.f32.bf16.bf16 {%0,%1,%2,%3,%4,%5,%6,%7,%8,%9,%10,%11,%12,%13,%14,%15}, a, b, p, 1, 1, 0, 1;\n}\n"
    : "+f"(d[0]),"+f"(d[1]),"+f"(d[2]),"+f"(d[3]),"+f"(d[4]),"+f"(d[5]),"+f"(d[6]),"+f"(d[7]),"+f"(d[8]),"+f"(d[9]),"+f"(d[10]),"+f"(d[11]),"+f"(d[12]),"+f"(d[13]),"+f"(d[14]),"+f"(d[15])
    : "r"(da), "r"(db), "r"(sd));
}
__device__ __forceinline__ void wgmma_rs_n40(float (&d)[20], uint32_t a0, uint32_t a1, uint32_t a2, uint32_t a3, uint32_t db, int sd) {
  asm volatile("{\n.reg .pred p;\n.reg .b64 b;\nsetp.ne.b32 p, %25, 0;\nmov.b64 b, {%24, 0x10};\n"
    "wgmma.mma_async.sync.aligned.m64n40k16.f32.bf16.bf16 {%0,%1,%2,%3,%4,%5,%6,%7,%8,%9,%10,%11,%12,%13,%14,%15,%16,%17,%18,%19}, {%20,%21,%22,%23}, b, p, 1, 1, 1;\n}\n"
    : "+f"(d[0]),"+f"(d[1]),"+f"(d[2]),"+f"(d[3]),"+f"(d[4]),"+f"(d[5]),"+f"(d[6]),"+f"(d[7]),"+f"(d[8]),"+f"(d[9]),"+f"(d[10]),"+f"(d[11]),"+f"(d[12]),"+f"(d[13]),"+f"(d[14]),"+f"(d[15]),"+f"(d[16]),"+f"(d[17]),"+f"(d[18]),"+f"(d[19])
    : "r"(a0), "r"(a1), "r"(a2), "r"(a3), "r"(db), "r"(sd));
}
__device__ __forceinline__ void wgmma_r1_n256(float (&d)[128], uint32_t da, uint32_t db, int sd) {
  asm volatile("{\n.reg .pred p;\n.reg .b64 a, b;\nsetp.ne.b32 p, %130, 0;\nmov.b64 a, {%128, 0x8};\nmov.b64 b, {%129, 0x6};\n"
    "wgmma.mma_async.sync.aligned.m64n256k16.f32.bf16.bf16 {%0,%1,%2,%3,%4,%5,%6,%7,%8,%9,%10,%11,%12,%13,%14,%15,%16,%17,%18,%19,%20,%21,%22,%23,%24,%25,%26,%27,%28,%29,%30,%31,%32,%33,%34,%35,%36,%37,%38,%39,%40,%41,%42,%43,%44,%45,%46,%47,%48,%49,%50,%51,%52,%53,%54,%55,%56,%57,%58,%59,%60,%61,%62,%63,%64,%65,%66,%67,%68,%69,%70,%71,%72,%73,%74,%75,%76,%77,%78,%79,%80,%81,%82,%83,%84,%85,%86,%87,%88,%89,%90,%91,%92,%93,%94,%95,%96,%97,%98,%99,%100,%101,%102,%103,%104,%105,%106,%107,%108,%109,%110,%111,%112,%113,%114,%115,%116,%117,%118,%119,%120,%121,%122,%123,%124,%125,%126,%127}, a, b, p, 1, 1, 0, 1;\n}\n"
    : "+f"(d[0]),"+f"(d[1]),"+f"(d[2]),"+f"(d[3]),"+f"(d[4]),"+f"(d[5]),"+f"(d[6]),"+f"(d[7]),"+f"(d[8]),"+f"(d[9]),"+f"(d[10]),"+f"(d[11]),"+f"(d[12]),"+f"(d[13]),"+f"(d[14]),"+f"(d[15]),"+f"(d[16]),"+f"(d[17]),"+f"(d[18]),"+f"(d[19]),"+f"(d[20]),"+f"(d[21]),"+f"(d[22]),"+f"(d[23]),"+f"(d[24]),"+f"(d[25]),"+f"(d[26]),"+f"(d[27]),"+f"(d[28]),"+f"(d[29]),"+f"(d[30]),"+f"(d[31]),"+f"(d[32]),"+f"(d[33]),"+f"(d[34]),"+f"(d[35]),"+f"(d[36]),"+f"(d[37]),"+f"(d[38]),"+f"(d[39]),"+f"(d[40]),"+f"(d[41]),"+f"(d[42]),"+f"(d[43]),"+f"(d[44]),"+f"(d[45]),"+f"(d[46]),"+f"(d[47]),"+f"(d[48]),"+f"(d[49]),"+f"(d[50]),"+f"(d[51]),"+f"(d[52]),"+f"(d[53]),"+f"(d[54]),"+f"(d[55]),"+f"(d[56]),"+f"(d[57]),"+f"(d[58]),"+f"(d[59]),"+f"(d[60]),"+f"(d[61]),"+f"(d[62]),"+f"(d[63]),"+f"(d[64]),"+f"(d[65]),"+f"(d[66]),"+f"(d[67]),"+f"(d[68]),"+f"(d[69]),"+f"(d[70]),"+f"(d[71]),"+f"(d[72]),"+f"(d[73]),"+f"(d[74]),"+f"(d[75]),"+f"(d[76]),"+f"(d[77]),"+f"(d[78]),"+f"(d[79]),"+f"(d[80]),"+f"(d[81]),"+f"(d[82]),"+f"(d[83]),"+f"(d[84]),"+f"(d[85]),"+f"(d[86]),"+f"(d[87]),"+f"(d[88]),"+f"(d[89]),"+f"(d[90]),"+f"(d[91]),"+f"(d[92]),"+f"(d[93]),"+f"(d[94]),"+f"(d[95]),"+f"(d[96]),"+f"(d[97]),"+f"(d[98]),"+f"(d[99]),"+f"(d[100]),"+f"(d[101]),"+f"(d[102]),"+f"(d[103]),"+f"(d[104]),"+f"(d[105]),"+f"(d[106]),"+f"(d[107]),"+f"(d[108]),"+f"(d[109]),"+f"(d[110]),"+f"(d[111]),"+f"(d[112]),"+f"(d[113]),"+f"(d[114]),"+f"(d[115]),"+f"(d[116]),"+f"(d[117]),"+f"(d[118]),"+f"(d[119]),"+f"(d[120]),"+f"(d[121]),"+f"(d[122]),"+f"(d[123]),"+f"(d[124]),"+f"(d[125]),"+f"(d[126]),"+f"(d[127])
    : "r"(da), "r"(db), "r"(sd));
}
__device__ __forceinline__ void wgmma_r1_n128(float (&d)[64], uint32_t da, uint32_t db, int sd) {
  asm volatile("{\n.reg .pred p;\n.reg .b64 a, b;\nsetp.ne.b32 p, %66, 0;\nmov.b64 a, {%64, 0x8};\nmov.b64 b, {%65, 0x6};\n"
    "wgmma.mma_async.sync.aligned.m64n128k16.f32.bf16.bf16 {%0,%1,%2,%3,%4,%5,%6,%7,%8,%9,%10,%11,%12,%13,%14,%15,%16,%17,%18,%19,%20,%21,%22,%23,%24,%25,%26,%27,%28,%29,%30,%31,%32,%33,%34,%35,%36,%37,%38,%39,%40,%41,%42,%43,%44,%45,%46,%47,%48,%49,%50,%51,%52,%53,%54,%55,%56,%57,%58,%59,%60,%61,%62,%63}, a, b, p, 1, 1, 0, 1;\n}\n"
    : "+f"(d[0]),"+f"(d[1]),"+f"(d[2]),"+f"(d[3]),"+f"(d[4]),"+f"(d[5]),"+f"(d[6]),"+f"(d[7]),"+f"(d[8]),"+f"(d[9]),"+f"(d[10]),"+f"(d[11]),"+f"(d[12]),"+f"(d[13]),"+f"(d[14]),"+f"(d[15]),"+f"(d[16]),"+f"(d[17]),"+f"(d[18]),"+f"(d[19]),"+f"(d[20]),"+f"(d[21]),"+f"(d[22]),"+f"(d[23]),"+f"(d[24]),"+f"(d[25]),"+f"(d[26]),"+f"(d[27]),"+f"(d[28]),"+f"(d[29]),"+f"(d[30]),"+f"(d[31]),"+f"(d[32]),"+f"(d[33]),"+f"(d[34]),"+f"(d[35]),"+f"(d[36]),"+f"(d[37]),"+f"(d[38]),"+f"(d[39]),"+f"(d[40]),"+f"(d[41]),"+f"(d[42]),"+f"(d[43]),"+f"(d[44]),"+f"(d[45]),"+f"(d[46]),"+f"(d[47]),"+f"(d[48]),"+f"(d[49]),"+f"(d[50]),"+f"(d[51]),"+f"(d[52]),"+f"(d[53]),"+f"(d[54]),"+f"(d[55]),"+f"(d[56]),"+f"(d[57]),"+f"(d[58]),"+f"(d[59]),"+f"(d[60]),"+f"(d[61]),"+f"(d[62]),"+f"(d[63])
    : "r"(da), "r"(db), "r"(sd));
}

__device__ __forceinline__ uint32_t smem_u32(const void* p) { return (uint32_t)__cvta_generic_to_shared(p); }
__device__ __forceinline__ void mbar_init(uint32_t bar, uint32_t cnt) { asm volatile("mbarrier.init.shared::cta.b64 [%0], %1;" ::"r"(bar), "r"(cnt)); }
__device__ __forceinline__ void mbar_expect_tx(uint32_t bar, uint32_t bytes) { asm volatile("mbarrier.arrive.expect_tx.shared::cta.b64 _, [%0], %1;" ::"r"(bar), "r"(bytes) : "memory"); }
__device__ __forceinline__ void mbar_arrive(uint32_t bar) { asm volatile("mbarrier.arrive.shared::cta.b64 _, [%0];" ::"r"(bar) : "memory"); }
__device__ __forceinline__ void mbar_arrive_n(uint32_t bar, uint32_t n) { asm volatile("mbarrier.arrive.shared::cta.b64 _, [%0], %1;" ::"r"(bar), "r"(n) : "memory"); }
__device__ __forceinline__ void mbar_wait(uint32_t bar, uint32_t parity) {
  asm volatile("{\n.reg .pred p;\nLAB_WAIT:\nmbarrier.try_wait.parity.shared::cta.b64 p, [%0], %1;\n@p bra DONE;\nbra LAB_WAIT;\nDONE:\n}" ::"r"(bar), "r"(parity) : "memory");
}
__device__ __forceinline__ void mbar_wait2(uint32_t a, uint32_t pa, uint32_t b, uint32_t pb) {
  asm volatile("{\n.reg .pred p, q;\nLAB_WAIT:\nmbarrier.try_wait.parity.shared::cta.b64 p, [%0], %1;\nmbarrier.try_wait.parity.shared::cta.b64 q, [%2], %3;\n"
               "and.pred p, p, q;\n@p bra DONE;\nbra LAB_WAIT;\nDONE:\n}" ::"r"(a), "r"(pa), "r"(b), "r"(pb) : "memory");
}
__device__ __forceinline__ void mbar_wait3(uint32_t a, uint32_t pa, uint32_t b, uint32_t pb) {
  asm volatile("{\n.reg .pred p, q, r;\nLAB_WAIT:\nmbarrier.try_wait.parity.shared::cta.b64 p, [%0], %1;\nmbarrier.try_wait.parity.shared::cta.b64 q, [%2], %3;\n"
               "mbarrier.try_wait.parity.shared::cta.b64 r, [%2+8], %3;\nand.pred p, p, q;\nand.pred p, p, r;\n@p bra DONE;\nbra LAB_WAIT;\nDONE:\n}" ::"r"(a), "r"(pa), "r"(b), "r"(pb) : "memory");
}
__device__ __forceinline__ bool mbar_probe2(uint32_t a, uint32_t pa, uint32_t b, uint32_t pb) {
  uint32_t ok;
  asm volatile("{\n.reg .pred p, q;\nmbarrier.test_wait.parity.shared::cta.b64 p, [%1], %2;\nmbarrier.test_wait.parity.shared::cta.b64 q, [%3], %4;\n"
               "and.pred p, p, q;\nselp.u32 %0, 1, 0, p;\n}" : "=r"(ok) : "r"(a), "r"(pa), "r"(b), "r"(pb) : "memory");
  return ok != 0;
}
__device__ __forceinline__ void tma_load_3d(uint32_t dst, const CUtensorMap* tm, uint32_t bar, int c0, int c1, int c2) {
  asm volatile("cp.async.bulk.tensor.3d.shared::cluster.global.mbarrier::complete_tx::bytes [%0], [%1, {%3, %4, %5}], [%2];"
               ::"r"(dst), "l"(tm), "r"(bar), "r"(c0), "r"(c1), "r"(c2) : "memory");
}
__device__ __forceinline__ void tma_load_2d(uint32_t dst, const CUtensorMap* tm, uint32_t bar, int c0, int c1) {
  asm volatile("cp.async.bulk.tensor.2d.shared::cluster.global.mbarrier::complete_tx::bytes [%0], [%1, {%3, %4}], [%2];"
               ::"r"(dst), "l"(tm), "r"(bar), "r"(c0), "r"(c1) : "memory");
}
__device__ __forceinline__ void tma_load_w(uint32_t dst, const CUtensorMap* tm, uint32_t bar, int col, int kb) {
#pragma unroll
  for (int q = 0; q < 2; q++)
    asm volatile("cp.async.bulk.tensor.5d.shared::cluster.global.mbarrier::complete_tx::bytes [%0], [%1, {%3, %4, %4, %4, %5}], [%2];"
                 ::"r"(dst + q * 8192), "l"(tm), "r"(bar), "r"(col + q * 64), "r"(0), "r"(2 * kb) : "memory");
}
__device__ __forceinline__ void tma_prefetch_w(const CUtensorMap* tm, int col, int kb) {
#pragma unroll
  for (int q = 0; q < 2; q++)
    asm volatile("cp.async.bulk.prefetch.tensor.5d.L2.global [%0, {%1, %2, %2, %2, %3}];" ::"l"(tm), "r"(col + q * 64), "r"(0), "r"(2 * kb) : "memory");
}
__device__ __forceinline__ void bulk_load(uint32_t dst, const void* g, uint32_t bytes, uint32_t bar) {
  asm volatile("cp.async.bulk.shared::cluster.global.mbarrier::complete_tx::bytes [%0], [%1], %2, [%3];" ::"r"(dst), "l"(g), "r"(bytes), "r"(bar) : "memory");
}
__device__ __forceinline__ void prefetch_map(const CUtensorMap* tm) { asm volatile("prefetch.tensormap [%0];" ::"l"(tm) : "memory"); }
__device__ __forceinline__ void fence_async_smem() { asm volatile("fence.proxy.async.shared::cta;" ::: "memory"); }
__device__ __forceinline__ void fence_async_global() { asm volatile("fence.proxy.async.global;" ::: "memory"); }
__device__ __forceinline__ void fence_gpu() { asm volatile("fence.release.gpu;" ::: "memory"); }
__device__ __forceinline__ void st_flag(unsigned* p, unsigned v) { asm volatile("st.relaxed.gpu.global.u32 [%0], %1;" ::"l"(p), "r"(v) : "memory"); }
__device__ __forceinline__ unsigned ld_flag(const unsigned* p) { unsigned v; asm volatile("ld.relaxed.gpu.global.u32 %0, [%1];" : "=r"(v) : "l"(p) : "memory"); return v; }
__device__ __forceinline__ uint4 ldcg4(const void* p) { uint4 v; asm volatile("ld.global.cg.v4.u32 {%0,%1,%2,%3}, [%4];" : "=r"(v.x), "=r"(v.y), "=r"(v.z), "=r"(v.w) : "l"(p)); return v; }
__device__ __forceinline__ uint4 ld_pkt(const uint4* p) {
  uint4 v; asm volatile("{\n.reg .b128 t;\nld.relaxed.gpu.global.b128 t, [%4];\nmov.b128 {%0,%1,%2,%3}, t;\n}" : "=r"(v.x), "=r"(v.y), "=r"(v.z), "=r"(v.w) : "l"(p) : "memory"); return v;
}
__device__ __forceinline__ void st_pkt(uint4* p, uint32_t a, uint32_t b, uint32_t c, uint32_t tag) {
  asm volatile("{\n.reg .b128 t;\nmov.b128 t, {%1,%2,%3,%4};\nst.relaxed.gpu.global.b128 [%0], t;\n}" ::"l"(p), "r"(a), "r"(b), "r"(c), "r"(tag) : "memory");
}
__device__ __forceinline__ void st_v4(uint4* p, uint32_t a, uint32_t b, uint32_t c, uint32_t d) { asm volatile("st.relaxed.gpu.global.v4.u32 [%0], {%1,%2,%3,%4};" ::"l"(p), "r"(a), "r"(b), "r"(c), "r"(d) : "memory"); }
__device__ __forceinline__ void sts32(uint32_t addr, uint32_t a) { asm volatile("st.shared.u32 [%0], %1;" ::"r"(addr), "r"(a) : "memory"); }
__device__ __forceinline__ void sts64(uint32_t addr, uint32_t a, uint32_t b) { asm volatile("st.shared.v2.u32 [%0], {%1,%2};" ::"r"(addr), "r"(a), "r"(b) : "memory"); }
__device__ __forceinline__ uint32_t mul2(uint32_t a, uint32_t b) { uint32_t r; asm("mul.rn.bf16x2 %0, %1, %2;" : "=r"(r) : "r"(a), "r"(b)); return r; }
__device__ __forceinline__ uint32_t add2(uint32_t a, uint32_t b) { uint32_t r; asm("add.rn.bf16x2 %0, %1, %2;" : "=r"(r) : "r"(a), "r"(b)); return r; }
__device__ __forceinline__ bool elect() {
  uint32_t p; asm volatile("{\n.reg .pred q;\nelect.sync _|q, 0xffffffff;\nselp.u32 %0, 1, 0, q;\n}" : "=r"(p)); return p != 0;
}
__device__ __forceinline__ void wgmma_fence() { asm volatile("wgmma.fence.sync.aligned;" ::: "memory"); }
__device__ __forceinline__ void wgmma_commit() { asm volatile("wgmma.commit_group.sync.aligned;" ::: "memory"); }
template <int N> __device__ __forceinline__ void wgmma_wait() { asm volatile("wgmma.wait_group.sync.aligned %0;" ::"n"(N) : "memory"); }
template <int N> __device__ __forceinline__ void fence_regs(float (&d)[N]) {
#pragma unroll
  for (int i = 0; i < N; i++) asm volatile("" : "+f"(d[i])::"memory");
}
template <int R> __device__ __forceinline__ void reg_alloc() { asm volatile("setmaxnreg.inc.sync.aligned.u32 %0;" ::"n"(R)); }
template <int R> __device__ __forceinline__ void reg_dealloc() { asm volatile("setmaxnreg.dec.sync.aligned.u32 %0;" ::"n"(R)); }
__device__ __forceinline__ void wg_bar(int w) { asm volatile("bar.sync %0, 128;" ::"r"(w + 1) : "memory"); }
__device__ __forceinline__ constexpr uint32_t desc_lo(uint32_t addr, uint32_t lbo) { return (addr >> 4) + ((lbo >> 4) << 16); }
__device__ __forceinline__ uint32_t pack2(float lo, float hi) { uint32_t r; asm("cvt.rn.bf16x2.f32 %0, %1, %2;" : "=r"(r) : "f"(hi), "f"(lo)); return r; }
__device__ __forceinline__ float lo16(uint32_t v) { return __uint_as_float(v << 16); }
__device__ __forceinline__ float hi16(uint32_t v) { return __uint_as_float(v & 0xFFFF0000u); }
__device__ __forceinline__ float ex2(float x) { float r; asm("ex2.approx.ftz.f32 %0, %1;" : "=f"(r) : "f"(x)); return r; }
__device__ __forceinline__ float rcp(float x) { float r; asm("rcp.approx.ftz.f32 %0, %1;" : "=f"(r) : "f"(x)); return r; }
__device__ __forceinline__ uint32_t movm(uint32_t a) { uint32_t d; asm volatile("movmatrix.sync.aligned.m8n8.trans.b16 %0, %1;" : "=r"(d) : "r"(a)); return d; }
__device__ __forceinline__ void stsm4(uint32_t addr, uint32_t a, uint32_t b, uint32_t c, uint32_t d) {
  asm volatile("stmatrix.sync.aligned.m8n8.x4.shared.b16 [%0], {%1,%2,%3,%4};" ::"r"(addr), "r"(a), "r"(b), "r"(c), "r"(d) : "memory");
}
__device__ __forceinline__ void ldsm4(uint32_t addr, uint32_t (&r)[4]) {
  asm volatile("ldmatrix.sync.aligned.m8n8.x4.shared.b16 {%0,%1,%2,%3}, [%4];" : "=r"(r[0]), "=r"(r[1]), "=r"(r[2]), "=r"(r[3]) : "r"(addr) : "memory");
}
__device__ __forceinline__ void sts128(uint32_t addr, uint32_t a, uint32_t b, uint32_t c, uint32_t d) {
  asm volatile("st.shared.v4.u32 [%0], {%1,%2,%3,%4};" ::"r"(addr), "r"(a), "r"(b), "r"(c), "r"(d) : "memory");
}
__device__ __forceinline__ void lds128(uint32_t addr, uint32_t& a, uint32_t& b, uint32_t& c, uint32_t& d) {
  asm volatile("ld.shared.v4.u32 {%0,%1,%2,%3}, [%4];" : "=r"(a), "=r"(b), "=r"(c), "=r"(d) : "r"(addr) : "memory");
}
__device__ __forceinline__ float lds32f(uint32_t addr) { float v; asm volatile("ld.shared.f32 %0, [%1];" : "=f"(v) : "r"(addr) : "memory"); return v; }
__device__ __forceinline__ float2 lds64f(uint32_t addr) { float2 v; asm volatile("ld.shared.v2.f32 {%0,%1}, [%2];" : "=f"(v.x), "=f"(v.y) : "r"(addr) : "memory"); return v; }
__device__ __forceinline__ void mma16816(float (&d)[4], uint32_t a0, uint32_t a1, uint32_t a2, uint32_t a3, uint32_t b0, uint32_t b1) {
  asm("mma.sync.aligned.m16n8k16.row.col.f32.bf16.bf16.f32 {%0,%1,%2,%3}, {%4,%5,%6,%7}, {%8,%9}, {%0,%1,%2,%3};"
      : "+f"(d[0]), "+f"(d[1]), "+f"(d[2]), "+f"(d[3]) : "r"(a0), "r"(a1), "r"(a2), "r"(a3), "r"(b0), "r"(b1));
}
__device__ __forceinline__ void mma1688(float (&d)[4], uint32_t a0, uint32_t a1, uint32_t b0) {
  asm("mma.sync.aligned.m16n8k8.row.col.f32.bf16.bf16.f32 {%0,%1,%2,%3}, {%4,%5}, {%6}, {%0,%1,%2,%3};"
      : "+f"(d[0]), "+f"(d[1]), "+f"(d[2]), "+f"(d[3]) : "r"(a0), "r"(a1), "r"(b0));
}

__device__ __forceinline__ float qsum(float v) { v += __shfl_xor_sync(0xffffffffu, v, 1); v += __shfl_xor_sync(0xffffffffu, v, 2); return v; }

constexpr int NCTA = 132;
#define NB_ 6
#define NA_ 5
constexpr int NB = NB_;
constexpr int NA = NA_;
constexpr uint32_t SLOT = 16384;
constexpr uint32_t SB = 1024;
constexpr uint32_t OFF_B = 0;
constexpr uint32_t OFF_A = NB * SLOT;
constexpr uint32_t OFF_S = OFF_A + NA * SLOT;
constexpr uint32_t OFF_T = OFF_S + 20480;
constexpr uint32_t OFF_CS = OFF_T + 24576;
constexpr uint32_t OFF_MR = OFF_CS + 4640;
constexpr uint32_t OFF_BAR = OFF_MR + 512;
constexpr uint32_t OFF_MA = OFF_S, OFF_MB = OFF_CS - 2048;
constexpr uint32_t BAR_FULLB = OFF_BAR;
constexpr uint32_t BAR_FULLA = BAR_FULLB + 64;
constexpr uint32_t BAR_EMPTYB = BAR_FULLA + 64;
constexpr uint32_t BAR_EMPTYA = BAR_EMPTYB + 64;
constexpr uint32_t BAR_SIGP = BAR_EMPTYA + 64;
constexpr uint32_t BAR_SIGT = BAR_SIGP + 32;
constexpr uint32_t BAR_STAT = BAR_SIGP + 64;
constexpr uint32_t BAR_HALO = BAR_STAT + 16;
constexpr uint32_t BAR_CS = BAR_HALO + 8;
constexpr uint32_t BAR_WPHI = BAR_CS + 16;
constexpr uint32_t BAR_KV = BAR_WPHI + 8;
constexpr uint32_t BAR_STG = BAR_KV + 16;
constexpr uint32_t BAR_EPOCH = BAR_STG + 48;
constexpr uint32_t OFF_EPOCH = OFF_BAR + 7 * 64;
static_assert(BAR_EPOCH < OFF_EPOCH, "barriers");
constexpr uint32_t SMEM_BYTES = OFF_EPOCH + 8;
static_assert(SMEM_BYTES <= 232448 && NB % 2 == 0 && NB <= 8 && NA <= 6, "smem");

#define CREGS 224
#define PREGS 56
#define PF0 9
#define PF1 13
#define PF2 17
#define PRE_A 2
#define PRE_B 4
#define CSB 4
#define CSNEED 0xF003u
#define XR 1
#define PS0 1
#define PS1 3
#define PSW 0
#define SD 1000
#define QORD 2
#define KSPLIT 12
#define KEEP 16
#define NJ 3
#define KSL 1000
#define PSL 0
#define KVS 12
#define D2 2000
#define D3 1500
#define G0 50
#define G3 50
#define G1 0
#define G4 0
#define MAP 3
#define PMAP 0x76321450u
#define PW 1
#define PN2 0
#define XA 3
#define XS 1
#define XW 0
#define XV 0
#define KB 8
#define PNX 2
#define PNO 2
#define DEFER 3
#define DEFL 2
#define TSK 3
#define TSL 3
constexpr int NTHREADS = 384;

struct Params {
  CUtensorMap mx;
  CUtensorMap mw[3];
  CUtensorMap mwo[2];
  CUtensorMap mcs[2];
  CUtensorMap mwphi;
  uint4* out;
};

#define XBUF(L) 1
__device__ __align__(256) uint4 g_img[XBUF(3) + 1][16][16][1024];
__device__ __align__(256) uint4 g_wf[2][8][16][1024];
__device__ __align__(256) uint4 g_stats[16][2][8][32];
__device__ __align__(256) uint4 g_halo[16][8][2][256];
__device__ __align__(256) float g_cs[2][2][3072];
__device__ __align__(256) uint4 g_kvpart[8][16][2][544];
__device__ __align__(256) uint4 g_kvfin[8][16][80];
__device__ __align__(256) unsigned g_xflag[4][2][16][32];
__device__ __align__(256) unsigned g_oflag[4][2][16][32];
__device__ __align__(256) unsigned g_hflag[2][16][8][32];
__device__ __align__(256) unsigned g_kvfflag[2][8][2][32];
__device__ __align__(256) unsigned g_csflag[2][8][32];
__device__ __align__(256) unsigned g_kflag[8][32];
__device__ unsigned g_ctr;
__device__ __forceinline__ unsigned vblock() {
  unsigned s;
  asm volatile("mov.u32 %0, %%smid;" : "=r"(s));
  const unsigned r = s & 1;
  s >>= 1;
  const unsigned t = s - 32, q = (t * 37) >> 8;
  const unsigned hi = s < 60 ? 12 + (t - 7 * q) * 8 + q : (s < 62 ? s + 4 : s - 58);
  unsigned b = 2 * (s < 32 ? (s & 7) * 8 + (s >> 3) : hi) + r;
  if (b < 128) b = (b & 15) | ((PMAP >> ((b >> 4) * 4)) & 7) << 4;
  if (s >= 62) b = 8 + 4 * r + s - 62;
  return __shfl_sync(0xffffffffu, b, 0);
}
#define TS(who, id) do {} while (0)
#define TSW(id) do {} while (0)

#define TSMASK 0xFFFF
#define TSL_(a) do { if ((TSMASK >> (a)) & 1) TSW((a) + L * 12); } while (0)
__device__ __forceinline__ int cta_m(unsigned b) { return ((b >> 2) & 12) | (b & 3); }
__device__ __forceinline__ int cta_j(unsigned b) { return ((b >> 2) & 3) | ((b >> 4) & 4); }
struct Ring { uint32_t s, ph; };
template <int N> __device__ __forceinline__ void adv(Ring& r) { if (++r.s == N) { r.s = 0; r.ph ^= 1; } }
template <int N> __device__ __forceinline__ void rewind2(Ring& r) { if (r.s < 2) { r.s += N - 2; r.ph ^= 1; } else r.s -= 2; }
__device__ __forceinline__ int other_tile(int t, int j) { return (t == (j | 4) ? 7 : t) ^ (~j & 4); }
__device__ __forceinline__ int q_order(int i, int j) { return 2 * (i >= 14 ? j : other_tile(i >> 1, j)) + (i & 1); }
__device__ __forceinline__ int o_order(int i, int j) {
  if (i < 2) return 2 * j + i;
  const int odd = i >= 9;
  return 2 * other_tile(i - 2 - 7 * odd, j) + odd;
}
__device__ __forceinline__ int kv_order(int i, int j, int L) { return L > 0 ? o_order(i, j) : (i + 14 + 2 * (j & 4)) & 15; }

__device__ __forceinline__ unsigned poll_flags(const unsigned* f, int n, unsigned need, unsigned tag) {
  const int lane = threadIdx.x & 31;
  unsigned mask; int it = 0;
  do {
    unsigned v = lane < n ? ld_flag(f + lane) : 0u;
    mask = __ballot_sync(0xffffffffu, lane < n && v == tag);
    if (++it > (1 << 22)) __trap();
  } while ((mask & need) != need);
  fence_async_global();
  return mask;
}
template <bool WAIT = true>
__device__ __forceinline__ unsigned get_tag(uint32_t sb) {
  if (WAIT) mbar_wait(sb + BAR_EPOCH, 0);
  unsigned t; asm volatile("ld.shared.u32 %0, [%1];" : "=r"(t) : "r"(sb + OFF_EPOCH) : "memory");
  return t;
}

__device__ __forceinline__ int lane_id() { int l; asm volatile("mov.u32 %0, %%laneid;" : "=r"(l)); return l; }
__device__ __forceinline__ unsigned seq4(unsigned tag, int L) { return 8u | ((tag & 1u) << 2) | (unsigned)L; }
constexpr float LOG2E = 1.4426950408889634f;

__device__ __forceinline__ void sched_fence(uint32_t sb) { mbar_wait(sb + BAR_EPOCH, 0); }
constexpr uint32_t HA128 = 0x40000040u, HA64 = 0x80000040u;
struct Ctx {
  static constexpr uint32_t sb = SB;
  uint32_t ab, da0;
  int w, warp, lane, g, c;
  int goff;
  __device__ __forceinline__ int m() const { return goff >> 14; }
  __device__ __forceinline__ int j() const { return (goff >> 4) & 7; }
  bool elected;
  Ring ra, rb;
  uint32_t pa, pb;
  uint32_t ha, k2;
  uint32_t mrow, mxor, mhi;
  __device__ __forceinline__ uint32_t aslot(uint32_t s) const { return ab + s * SLOT; }
  __device__ __forceinline__ uint32_t fullA(uint32_t s) const { return sb + BAR_FULLA + s * 8; }
  __device__ __forceinline__ uint32_t fullB(uint32_t s) const { return sb + BAR_FULLB + s * 8; }
  __device__ __forceinline__ void releaseA(uint32_t s) const { if (elected) mbar_arrive(sb + BAR_EMPTYA + s * 8); }
  __device__ __forceinline__ void releaseB(uint32_t s) const { if (elected) mbar_arrive(sb + BAR_EMPTYB + s * 8); }
  __device__ __forceinline__ uint32_t maddr(uint32_t tile, uint32_t ch) const { return tile + mrow + (((ch + mhi) ^ mxor) << 4); }
  __device__ __forceinline__ uint32_t oo() const { return warp * 128 + g * 4 + (c ^ (g >> 1)); }
  __device__ __forceinline__ uint4* img(int b, int hp) const { return &g_img[b][m()][2 * j() + hp][w * 512 + oo()]; }
  __device__ __forceinline__ uint32_t held(int i) const { return ra.s + i < 2 ? ra.s + i + NA - 2 : ra.s + i - 2; }
};

template <int N, bool FIRST, bool O = true>
__device__ __forceinline__ void gemm_issue(float (&acc)[N / 2], Ctx& x, bool ready = false) {
  if (!ready) {
    if (N == 256) mbar_wait3(x.fullA(x.ra.s), x.ra.ph, x.fullB(x.rb.s), x.rb.ph);
    else mbar_wait2(x.fullA(x.ra.s), x.ra.ph, x.fullB(x.rb.s), x.rb.ph);
  }
  const uint32_t da = x.da0 + x.ra.s * (SLOT / 16), db = desc_lo(SB + OFF_B, 8192) + x.rb.s * (SLOT / 16);
  wgmma_fence();
#pragma unroll
  for (int k = 0; k < 4; k++) {
    const uint32_t a = da + (k >> 1) * (O ? 32 : x.k2) + (k & 1) * 2, ha = O ? HA64 : x.ha;
    if constexpr (N == 256) wgmma_ss_n256(acc, a, ha, db + 128 * k, !(FIRST && k == 0));
    else wgmma_ss_n128(acc, a, ha, db + 128 * k, !(FIRST && k == 0));
  }
  wgmma_commit();
}
template <int N>
__device__ __forceinline__ void gemm_next(Ctx& x) {
  x.pa = x.ra.s; x.pb = x.rb.s;
  if (N == 256) x.rb.s++;
  adv<NA>(x.ra); adv<NB>(x.rb);
}
template <int N>
__device__ __forceinline__ void gemm_release(Ctx& x, bool relA) {
  if (relA) x.releaseA(x.pa);
  x.releaseB(x.pb);
  if (N == 256) x.releaseB(x.pb + 1);
}
template <int N>
__device__ __forceinline__ void gemm_retire(Ctx& x, bool relA) { wgmma_wait<1>(); gemm_release<N>(x, relA); gemm_next<N>(x); }
template <bool O = true>
__device__ __forceinline__ void gemm_run(float (&acc)[64], Ctx& x, int n, int hold, int n4 = 0) {
  bool ready = false;
#pragma unroll 1
  for (; n > 0; n--) {
    gemm_issue<128, false, O>(acc, x, ready);
    const uint32_t pa = x.pa, pb = x.pb;
    gemm_next<128>(x);
    ready = mbar_probe2(x.fullA(x.ra.s), x.ra.ph, x.fullB(x.rb.s), x.rb.ph);
    wgmma_wait<1>();
    if (n > hold) x.releaseA(pa);
    x.releaseB(pb);
  }
}
__device__ __forceinline__ void gemm_end(float (&acc)[64], Ctx& x) { wgmma_wait<0>(); fence_regs(acc); gemm_release<128>(x, false); }

__device__ __forceinline__ void load_x32(float* a, uint32_t tile, uint32_t ch, const Ctx& x) {
#pragma unroll
  for (int p = 0; p < 2; p++) {
    uint32_t v[4];
    ldsm4(x.maddr(tile, ch + 2 * p), v);
#pragma unroll
    for (int i = 0; i < 4; i++) { a[8 * p + 2 * i] = lo16(v[i]); a[8 * p + 2 * i + 1] = hi16(v[i]); }
  }
}

__device__ __forceinline__ void rows_load(uint4* r, uint32_t tile, const Ctx& x) {
#pragma unroll
  for (int q = 0; q < 4; q++) {
    const uint32_t row = x.warp * 16 + 4 * q + (x.lane >> 3);
    lds128(tile + row * 128 + (((x.lane & 7) ^ (row & 7)) << 4), r[q].x, r[q].y, r[q].z, r[q].w);
  }
}
__device__ __forceinline__ void rows_store(const uint4* r, uint4* g, const Ctx& x) {
  g += (x.warp * 16 + (x.lane >> 3)) * 256 + (x.lane & 7);
#pragma unroll
  for (int q = 0; q < 4; q++) g[q * 1024] = r[q];
}
__device__ __forceinline__ void publish(int id, const Ctx& x) { __syncwarp(); if (x.lane == 0) mbar_arrive(x.sb + BAR_SIGP + id * 8); }
__device__ __forceinline__ void img_store(const uint4 (&r)[4], uint4* g) {
#pragma unroll
  for (int q = 0; q < 4; q++) g[q * 32] = r[q];
}
__device__ __forceinline__ void img_sts(const uint4 (&r)[4], uint32_t tile, const Ctx& x) {
#pragma unroll
  for (int q = 0; q < 4; q++) sts128(tile + x.oo() * 16 + q * 512, r[q].x, r[q].y, r[q].z, r[q].w);
}
__device__ __forceinline__ void img_load(uint32_t (&v)[16], uint32_t tile, const Ctx& x) {
#pragma unroll
  for (int q = 0; q < 4; q++) lds128(tile + x.oo() * 16 + q * 512, v[4 * q], v[4 * q + 1], v[4 * q + 2], v[4 * q + 3]);
}
__device__ __forceinline__ void img_unpack(float* a, const uint32_t (&v)[16]) {
#pragma unroll
  for (int q = 0; q < 16; q++) { a[4 * (q & 7) + 2 * (q >> 3)] = lo16(v[q]); a[4 * (q & 7) + 2 * (q >> 3) + 1] = hi16(v[q]); }
}

template <int N>
__device__ __forceinline__ void stats_acc(const float* a, float (&t)[4]) {
#pragma unroll
  for (int i = 0; i < N; i++) { t[i & 2] += a[i]; t[(i & 2) + 1] = fmaf(a[i], a[i], t[(i & 2) + 1]); }
}
__device__ __forceinline__ void stats_send(float (&t)[4], int L, const Ctx& x) {
  const unsigned seq = seq4(get_tag<false>(x.sb), L);
#pragma unroll
  for (int q = 0; q < 4; q++) t[q] = qsum(t[q]);
  if (x.c == 0) st_pkt(&g_stats[x.m()][x.w][x.j()][x.warp * 8 + x.g], __float_as_uint(t[0]), __float_as_uint(t[1]), __float_as_uint(t[2]), (__float_as_uint(t[3]) & ~15u) | seq);
}
__device__ __forceinline__ void out_epilogue(const float (&acc)[64], uint4 (&r1)[4], float (&t)[4], uint4* g, int L, Ctx& x) {
  const uint32_t t0 = x.aslot(x.ra.s), t1 = x.aslot(x.ra.s + 1 == NA ? 0 : x.ra.s + 1);
  if (L == 3) {
#pragma unroll
    for (int p = 0; p < 8; p++) {
      stsm4(x.maddr(p < 4 ? t0 : t1, (p & 3) * 2), pack2(acc[8 * p], acc[8 * p + 1]), pack2(acc[8 * p + 2], acc[8 * p + 3]),
            pack2(acc[8 * p + 4], acc[8 * p + 5]), pack2(acc[8 * p + 6], acc[8 * p + 7]));
      if ((p & 3) == 3) { uint4 r[4]; __syncwarp(); rows_load(r, p < 4 ? t0 : t1, x); rows_store(r, g + (p >> 2) * 8, x); }
    }
  } else {
    auto pack16 = [&](uint4 (&r)[4], const float* a) {
#pragma unroll
      for (int q = 0; q < 4; q++) { const float* u = a + 16 * (q & 1) + (q & 2); r[q] = make_uint4(pack2(u[0], u[1]), pack2(u[4], u[5]), pack2(u[8], u[9]), pack2(u[12], u[13])); }
    };
    uint4 r0[4];
    pack16(r0, acc);
    img_store(r0, x.img(XBUF(L + 1), 0));
    publish(2, x);
    img_sts(r0, t0, x);
    sched_fence(x.sb);
    pack16(r1, acc + 32);
    img_sts(r1, t1, x);
    float u[4] = {0.f, 0.f, 0.f, 0.f}, v[4] = {0.f, 0.f, 0.f, 0.f};
    stats_acc<32>(acc, v); stats_acc<32>(acc + 32, u);
#pragma unroll
    for (int q = 0; q < 4; q++) t[q] = u[q] + v[q];
    mbar_wait2(x.fullB(x.rb.s), x.rb.ph, x.fullB(x.rb.s + 1), x.rb.ph);
    fence_async_smem();
    asm volatile("bar.sync %0, %1;" ::"r"(L == 1 ? x.w + 1 : 3), "r"(L == 1 ? 128 : 256) : "memory");
  }
}

struct Stats { float rstd0, rstd1; };
__device__ __forceinline__ Stats load_stats(int half, const Ctx& x) {
  const float2 u = lds64f(x.sb + OFF_MR + half * 256 + (x.warp * 8 + x.g) * 8);
  return {u.x, u.y};
}

template <int NK>
__device__ __forceinline__ void hedgehog_scale(float* t, const Stats& st, const uint32_t* keep) {
#pragma unroll
  for (int q = 0; q < 16; q++) t[q] *= ((q & 2) ? st.rstd1 : st.rstd0) * LOG2E;
  float m[4];
#pragma unroll
  for (int q = 0; q < 4; q++) m[q] = fmaxf(fmaxf(fabsf(t[4 * q]), fabsf(t[4 * q + 1])), fmaxf(fabsf(t[4 * q + 2]), fabsf(t[4 * q + 3])));
  if (__builtin_expect(__any_sync(0xffffffffu, fmaxf(fmaxf(m[0], m[1]), fmaxf(m[2], m[3])) > 58.f), 0)) {
    float z[16 + NK];
#pragma unroll
    for (int q = 0; q < 16 + NK; q++) z[q] = q < 16 ? t[q & 15] : __uint_as_float(keep[q & 15]);
#pragma unroll 1
    for (int r = 0; r < 4; r += 2) {
      float hi = -INFINITY, lo = INFINITY;
#pragma unroll 1
      for (int i = 0; i < 16; i++) {
        const int k = (i & 6) * 2 + (i & 1) + r;
        const float v = z[k];
        if (i < 8) { hi = fmaxf(hi, v); lo = fminf(lo, v); }
        else z[k] = v - fminf(fmaxf(v, lo), hi);
        if (i == 7) {
#pragma unroll 1
          for (int d = 1; d <= 2; d++) { hi = fmaxf(hi, __shfl_xor_sync(0xffffffffu, hi, d)); lo = fminf(lo, __shfl_xor_sync(0xffffffffu, lo, d)); }
          const float mid = 0.5f * hi + 0.5f * lo;
          hi = fmaxf(hi - 58.f, mid); lo = fminf(lo + 58.f, mid);
        }
      }
    }
#pragma unroll
    for (int q = 0; q < 16; q++) t[q] = z[q];
  }
}
__device__ __forceinline__ void dual_exp(const float* t, uint32_t (&f)[18], int never) {
  float e[KSPLIT];
#pragma unroll
  for (int q = 0; q < KSPLIT; q++) e[q] = ex2(q < 16 ? t[q] : -t[q & 15]);
  while (never < 0) {
#pragma unroll
    for (int i = 0; i < KSPLIT; i += 4) asm volatile("ld.shared.v4.f32 {%0,%1,%2,%3}, [%4];" : "=f"(e[i]), "=f"(e[i + 1]), "=f"(e[i + 2]), "=f"(e[i + 3]) : "r"(never + i) : "memory");
    never += __float_as_int(e[0]);
  }
#pragma unroll
  for (int q = 0; q < KSPLIT; q += 2) f[q >> 1] = pack2(e[q], e[q + 1]);
#pragma unroll
  for (int q = KSPLIT; q < 32; q += 2) f[q >> 1] = q < 16 ? pack2(ex2(t[q]), ex2(t[q + 1])) : pack2(ex2(-t[q & 15]), ex2(-t[(q & 15) + 1]));
#pragma unroll
  for (int sg = 0; sg < 2; sg++) {
    const uint32_t* u = f + 8 * sg;
    const uint32_t a = add2(add2(u[0], u[2]), add2(u[4], u[6])), b = add2(add2(u[1], u[3]), add2(u[5], u[7]));
    f[16 + sg] = add2(__byte_perm(a, b, 0x5410), __byte_perm(a, b, 0x7632));
  }
}
__device__ __forceinline__ void dual_exp_rcp(const float* t, uint32_t (&f)[16]) {
#pragma unroll
  for (int q = 0; q < 8; q++) {
    const float a = ex2(t[2 * q]), b = ex2(t[2 * q + 1]), r = rcp(a * b);
    f[q] = pack2(a, b); f[8 + q] = pack2(r * b, r * a);
  }
}
__device__ __forceinline__ void cta_bar() { asm volatile("bar.sync 3, 256;" ::: "memory"); }

template <int N> __device__ __forceinline__ void pin(const uint32_t* v, uint32_t addr) {
#pragma unroll
  for (int i = 0; i < N; i += 4)
    asm volatile("{\n.reg .pred p;\nsetp.eq.u32 p, %0, 0;\n@p st.shared.v4.u32 [%0], {%1,%2,%3,%4};\n}" ::"r"(addr), "r"(v[i]), "r"(v[i + 1]), "r"(v[i + 2]), "r"(v[i + 3]) : "memory");
}

__device__ __forceinline__ void consumer(const Params& P, uint32_t sb, int w, unsigned vb) {
  Ctx x;
  x.w = w;
  x.ab = sb + OFF_A + w * 8192; x.da0 = desc_lo(SB + OFF_A, 16) + w * 512;
  x.lane = threadIdx.x & 31; x.warp = __shfl_sync(0xffffffffu, (threadIdx.x >> 5) & 3, 0); x.g = x.lane >> 2; x.c = x.lane & 3;
  x.goff = (cta_m(vb) * 128 + w) * 128 + cta_j(vb) * 16;
  asm volatile("" : "+r"(x.goff));
  x.elected = (threadIdx.x & 127) == 0;
  x.ra = {0, 0}; x.rb = {0, 0}; x.pa = x.pb = 0;
  {
    const uint32_t row = x.warp * 16 + (x.lane & 15);
    x.mrow = row * 128; x.mxor = row & 7; x.mhi = x.lane >> 4;
  }
  const int goff = x.goff;
  uint4 r1[4];
  float ts[4] = {0.f, 0.f, 0.f, 0.f};
#pragma unroll
  for (int i = 0; i < 4; i++) r1[i] = make_uint4(0, 0, 0, 0);
  TSW(0);
  mbar_wait3(x.fullA(0), 0, x.fullB(0), 0);
#pragma unroll 1
  for (int L = 0; L < 4; L++) {
    float acc[64];
    constexpr uint32_t dcs = desc_lo(SB + OFF_CS, 0);
    if ((L & 1) == 0) {
    float kv[128];
    x.ha = L ? HA64 : HA128; x.k2 = L ? 32 : 4;
    gemm_issue<256, true, false>(kv, x, true); gemm_next<256>(x);
    {
      int i = 1;
#pragma unroll 1
      for (int seg = L >> 1; seg < 3; seg++) {
        const int end = seg < 2 ? (L == 0 ? 3 + 2 * (x.j() & 3) + seg : XA + 1 - w * XW) : 14 + L;
#pragma unroll 1
        while (true) {
          gemm_issue<256, false, false>(kv, x);
          if (++i == end) break;
          gemm_retire<256>(x, true);
          if (i == 5) TSL_(8);
          if (i == 11) TSL_(10);
        }
        if (seg < 2 && L == 0) {
          float a[32];
          const uint32_t tile = x.aslot(x.ra.s);
          load_x32(a, tile, 0, x); load_x32(a + 16, tile, 4, x);
          stats_acc<32>(a, ts);
          fence_async_smem();
          wg_bar(w);
        }
        if (seg == 1) {
          if (L > 0) { img_store(r1, x.img(XBUF(L), 1)); publish(3, x); }
          mbar_wait(sb + BAR_EPOCH, 0);
          stats_send(ts, L, x);
        }
        gemm_retire<256>(x, true);
      }
    }
      const Ring kt = x.ra;
      if (L == 0) adv<NA>(x.ra);
#pragma unroll 1
      for (int h = L; h < 2; h++) {
        float d[16];
        mbar_wait2(x.fullA(kt.s), kt.ph, sb + BAR_WPHI, 0);
        wgmma_fence();
#pragma unroll
        for (int q = 0; q < 2; q++) wgmma_ss_n32(d, x.da0 + kt.s * (SLOT / 16) + h * 4 + q * 2, desc_lo(SB + OFF_S + 4096, 512) + w * 256 + h * 128 + q * 64, q);
        wgmma_commit();
        gemm_issue<256, false, false>(kv, x);
        gemm_retire<256>(x, true);
        if (h) x.releaseA(kt.s);
        fence_regs(d);
        uint4* dst = &g_wf[1][x.j()][x.m()][w * 512 + (x.warp * 16 + x.g) * 8 + ((h * 4 + x.c) ^ x.g)];
        dst[0] = make_uint4(pack2(d[0], d[1]), pack2(d[4], d[5]), pack2(d[8], d[9]), pack2(d[12], d[13]));
        dst[64] = make_uint4(pack2(d[2], d[3]), pack2(d[6], d[7]), pack2(d[10], d[11]), pack2(d[14], d[15]));
      }
      const uint32_t dm = desc_lo(SB + OFF_MA, 0) + w * 64;
      mbar_wait2(sb + BAR_STAT, 0, sb + BAR_CS, 0);
      wgmma_fence();
      wgmma_r1_n256(kv, dm, dcs + 96, 1);
      wgmma_commit();
      const Stats st = load_stats(w, x);
      if (PW & 1) mbar_wait2(x.fullA(x.ra.s), x.ra.ph, x.fullB(x.rb.s), x.rb.ph);
      wgmma_wait<0>();
      fence_regs(kv);
      gemm_release<256>(x, true);
      TSL_(2);
      uint32_t P0[32], P1[32], PH[32];
#pragma unroll
      for (int t = 0; t < 16; t++) { P0[t] = pack2(kv[4 * t] * st.rstd0, kv[4 * t + 1] * st.rstd0); P1[t] = pack2(kv[4 * t + 2] * st.rstd1, kv[4 * t + 3] * st.rstd1); }
      pin<16>(P0, x.mrow + 16);
      {
#pragma unroll
        for (int q = 0; q < 4; q++) sts128((x.warp < 3 ? sb + OFF_T + w * 12288 + x.warp * 4096 : sb + OFF_S + 16384 + w * 2048) + x.lane * 16 + q * 512, P1[4 * q], P1[4 * q + 1], P1[4 * q + 2], P1[4 * q + 3]);
      }
      wgmma_fence();
      wgmma_r1_n128(acc, dm, dcs, 0);
      gemm_issue<128, false, false>(acc, x, PW & 1); gemm_next<128>(x);
      TSL_(3);
#pragma unroll
      for (int s = 0; s < 4; s++) {
#pragma unroll
        for (int t = 16 + 8 * (s & 1); t < 24 + 8 * (s & 1); t++) {
          if (s < 2) P1[t] = movm(pack2(kv[4 * t + 2] * st.rstd1, kv[4 * t + 3] * st.rstd1));
          else P0[t] = movm(pack2(kv[4 * t] * st.rstd0, kv[4 * t + 1] * st.rstd0));
        }
        if (s < 3) { gemm_issue<128, false, false>(acc, x); gemm_retire<128>(x, true); }
        if (s == 1) {
          if (x.warp < 3) {
#pragma unroll
            for (int q = 4; q < 8; q++) sts128(sb + OFF_T + w * 12288 + x.warp * 4096 + x.lane * 16 + q * 512, P1[4 * q], P1[4 * q + 1], P1[4 * q + 2], P1[4 * q + 3]);
          } else {
            uint4* dst = &g_halo[x.m()][x.j()][w][x.lane];
#pragma unroll
            for (int q = 0; q < 8; q++) dst[q * 32] = make_uint4(P1[4 * q], P1[4 * q + 1], P1[4 * q + 2], P1[4 * q + 3]);
          }
          publish(4, x);
          gemm_issue<128, false, false>(acc, x);
          gemm_retire<128>(x, true);
        }
      }
      TSL_(4);
      gemm_run<false>(acc, x, 10, 0);
      gemm_issue<128, false, false>(acc, x);
      {
        wg_bar(w);
        uint32_t tr = sb + OFF_T + w * 12288 + (x.warp - 1) * 4096;
        if (x.warp == 0) {
          tr = x.m() > 0 ? sb + OFF_S + 8192 + w * 4096 : tr + 4096;
          if (x.m() > 0) mbar_wait(sb + BAR_HALO, L >> 1);
        }
#pragma unroll
        for (int q = 0; q < 8; q++) lds128(tr + x.lane * 16 + q * 512, PH[4 * q], PH[4 * q + 1], PH[4 * q + 2], PH[4 * q + 3]);
      }
      gemm_retire<128>(x, false);
      gemm_end(acc, x);
      TSL_(5);
      const bool first = (x.m() == 0) && (x.warp == 0);
      const bool hi0 = 2 * x.c > x.g, hi1 = 2 * x.c + 1 > x.g;
      const uint32_t mhi = (hi0 ? 0xFFFFu : 0u) | (hi1 ? 0xFFFF0000u : 0u);
      const float sc0 = st.rstd0 * (0.17677669529663687f * LOG2E), sc1 = st.rstd1 * (0.17677669529663687f * LOG2E);
#pragma unroll
      for (int hp = 0; hp < 2; hp++) {
        const uint32_t tile = x.aslot(x.held(hp));
        uint32_t px[2], py[2];
        float s[2][3][4];
#pragma unroll
        for (int u = 0; u < 2; u++) {
#pragma unroll
          for (int q = 0; q < 12; q++) s[u][q >> 2][q & 3] = 0.f;
#pragma unroll
          for (int ks = 0; ks < 2; ks++) {
            const int t = 8 * hp + 4 * u + 2 * ks;
            const uint32_t a0 = pack2(acc[4 * t], acc[4 * t + 1]), a1 = pack2(acc[4 * t + 2], acc[4 * t + 3]);
            const uint32_t a2 = pack2(acc[4 * t + 4], acc[4 * t + 5]), a3 = pack2(acc[4 * t + 6], acc[4 * t + 7]);
            mma16816(s[u][0], a0, a1, a2, a3, PH[t], PH[t + 1]);
            mma16816(s[u][1], a0, a1, a2, a3, P0[t], P0[t + 1]);
            mma16816(s[u][2], a0, a1, a2, a3, P1[t], P1[t + 1]);
          }
        }
        float e[2][4], r[2][2];
#pragma unroll
        for (int u = 0; u < 2; u++) {
          e[u][0] = (hi0 ? s[u][0][0] : s[u][1][0]) * sc0; e[u][1] = (hi1 ? s[u][0][1] : s[u][1][1]) * sc0;
          e[u][2] = (hi0 ? s[u][1][2] : s[u][2][2]) * sc1; e[u][3] = (hi1 ? s[u][1][3] : s[u][2][3]) * sc1;
          if (first) { if (hi0) e[u][0] = -1e30f; if (hi1) e[u][1] = -1e30f; }
          r[u][0] = fmaxf(e[u][0], e[u][1]); r[u][1] = fmaxf(e[u][2], e[u][3]);
        }
#pragma unroll
        for (int d = 1; d <= 2; d++)
#pragma unroll
          for (int q = 0; q < 4; q++) r[q >> 1][q & 1] = fmaxf(r[q >> 1][q & 1], __shfl_xor_sync(0xffffffffu, r[q >> 1][q & 1], d));
#pragma unroll
        for (int u = 0; u < 2; u++) {
#pragma unroll
          for (int q = 0; q < 4; q++) e[u][q] = ex2(e[u][q] - r[u][q >> 1]);
          r[u][0] = e[u][0] + e[u][1]; r[u][1] = e[u][2] + e[u][3];
        }
#pragma unroll
        for (int d = 1; d <= 2; d++)
#pragma unroll
          for (int q = 0; q < 4; q++) r[q >> 1][q & 1] += __shfl_xor_sync(0xffffffffu, r[q >> 1][q & 1], d);
#pragma unroll
        for (int u = 0; u < 2; u++) {
          const float rx = rcp(r[u][0]), ry = rcp(r[u][1]);
          px[u] = pack2(e[u][0] * rx, e[u][1] * rx); py[u] = pack2(e[u][2] * ry, e[u][3] * ry);
        }
        uint32_t o[8][2];
        uint4 ro[4];
#pragma unroll
        for (int q = 0; q < 8; q++) {
          float d[4] = {0.f, 0.f, 0.f, 0.f};
          const int t = 16 + 8 * hp + q, u = q >> 2;
          mma16816(d, px[u] & mhi, 0u, px[u] & ~mhi, py[u] & mhi, PH[t], P0[t]);
          mma1688(d, 0u, py[u] & ~mhi, P1[t]);
          o[q][0] = pack2(d[0], d[1]); o[q][1] = pack2(d[2], d[3]);
        }
#pragma unroll
        for (int q = 0; q < 4; q++) ro[q] = make_uint4(o[4 * (q & 1)][q >> 1], o[4 * (q & 1) + 1][q >> 1], o[4 * (q & 1) + 2][q >> 1], o[4 * (q & 1) + 3][q >> 1]);
        img_store(ro, x.img(0, hp));
        publish(hp, x);
        uint32_t xr[16];
        if (L) img_load(xr, tile, x);
        else {
#pragma unroll
          for (int q = 0; q < 4; q++) {
            uint32_t v[4];
            ldsm4(x.maddr(tile, 2 * q), v);
            xr[2 * q] = v[0]; xr[8 + 2 * q] = v[1]; xr[2 * q + 1] = v[2]; xr[9 + 2 * q] = v[3];
          }
          __syncwarp();
        }
        img_sts(ro, tile, x);
        img_unpack(acc + 32 * hp, xr);
      }
    } else {
      float kv[128];
      float (&kv0)[64] = reinterpret_cast<float (&)[64]>(kv[0]);
      float (&kv1)[64] = reinterpret_cast<float (&)[64]>(kv[64]);
      auto mma8 = [&](uint32_t as, uint32_t bs, int i, bool fence) {
        const uint32_t da = desc_lo(SB + OFF_A, 16) + as * (SLOT / 16), db = desc_lo(SB + OFF_B, 8192) + bs * (SLOT / 16);
        if (fence) wgmma_fence();
#pragma unroll
        for (int k = 0; k < 4; k++) {
          wgmma_ss_n128(kv0, da + (k >> 1) * 32 + (k & 1) * 2, HA64, db + 128 * k, i + k);
          wgmma_ss_n128(kv1, da + 512 + (k >> 1) * 32 + (k & 1) * 2, HA64, db + 128 * k, i + k);
        }
        wgmma_commit();
      };
      constexpr uint32_t dm = desc_lo(SB + OFF_MB, 0);
      auto relB = [&](uint32_t s) { mbar_arrive_n(sb + BAR_EMPTYB + s * 8, 2); };
      auto skip = [&]() {
#pragma unroll
        for (int q = 0; q < 6 - NJ; q++) adv<NA>(x.ra);
        x.rb.s = w ? (2 + NJ) % 6 : 4;
        if (!w && NJ < 4) x.rb.ph ^= 1;
      };
      static_assert(NA == 5 && NB == 6, "ring arithmetic");
      mma8(x.ra.s, x.rb.s + w, 0, true);
      gemm_next<256>(x);
#pragma unroll 1
      for (int i = 1; i < NJ; i++) {
        mbar_wait2(x.fullA(x.ra.s), x.ra.ph, x.fullB(x.rb.s + w), x.rb.ph);
        mma8(x.ra.s, x.rb.s + w, 1, true);
        if (i == XR + w * XV) { img_store(r1, x.img(XBUF(L), 1)); publish(3, x); }
        if (i == XS) stats_send(ts, L, x);
        wgmma_wait<1>();
        if (x.elected) { x.releaseA(x.pa); relB(x.pb + w); }
        gemm_next<256>(x);
      }
      if (w) {
        wgmma_wait<0>();
        if (x.elected) { x.releaseA(x.pa); relB(x.pb + 1); }
        skip();
        asm volatile("bar.sync 7, 256;" ::: "memory");
      }
      TSL_(8);
      {
        const int t = lane_id() + 32 * x.warp;
        uint32_t mask = t < 2 ? ((w ? (t ? 0xFF3Fu : 0x3FFFu) : 0xFFFFu) >> (NJ - 1)) & (w ? ~1u : ~0u) : 0u, cnt = 1 + t;
        bool ready = false;
#pragma unroll 1
        for (int i = NJ; i < 16; i++) {
          if (!ready) mbar_wait2(x.fullA(x.ra.s), x.ra.ph, x.fullB(x.rb.s), x.rb.ph);
          mma8(x.ra.s, x.rb.s, 1, true);
          const uint32_t bar = sb + (t ? BAR_EMPTYB + x.pb * 8 : BAR_EMPTYA + x.pa * 8);
          gemm_next<128>(x);
          if (w && (i | 4) == 15) x.rb.s = 4;
          ready = mbar_probe2(x.fullA(x.ra.s), x.ra.ph, x.fullB(x.rb.s), x.rb.ph);
          wgmma_wait<1>();
          if (mask & 1) mbar_arrive_n(bar, cnt);
          mask >>= 1; cnt = 2;
          if (i == 8 && w) asm volatile("bar.arrive 9, 256;" ::: "memory");
          if (i == 9) TSL_(10);
        }
        mbar_wait2(sb + BAR_STAT, 1, sb + BAR_CS + 8, 0);
        wgmma_fence();
        wgmma_r1_n128(kv0, dm, dcs + 96 + 96 * w, 1);
        wgmma_r1_n128(kv1, dm + 64, dcs + 96 + 96 * w, 1);
        wgmma_commit();
        if (w == 0) asm volatile("bar.arrive 7, 256;" ::: "memory");
        wgmma_wait<1>();
        if (mask & 1) mbar_arrive_n(sb + (t ? BAR_EMPTYB + x.pb * 8 : BAR_EMPTYA + x.pa * 8), 2);
      }
      const Stats s0 = load_stats(0, x), s1 = load_stats(1, x), st = w ? s1 : s0;
      if (w == 0) skip();
      const uint32_t h0 = x.held(0), h1 = x.held(1);
      auto vreg = [&](int ks) { return ks < 6 ? OFF_A + (ks < 3 ? h0 * SLOT : h1 * SLOT - 15360) + ks * 5120 : OFF_S + 2048 + ks * 5120; };
      uint32_t tV[2], uu[4];
#pragma unroll
      for (int hf = 0; hf < 2; hf++) {
        tV[hf] = sb + vreg(4 * hf + x.warp) + ((x.lane >> 3) & 1) * 2560 + (x.lane & 7) * 16 + x.mhi * 128;
        const float i0 = rcp(hf ? s1.rstd0 : s0.rstd0), i1 = rcp(hf ? s1.rstd1 : s0.rstd1);
        const uint32_t h = pack2(i0, i1);
        uu[2 * hf] = pack2(lo16(h), i0 - lo16(h)); uu[2 * hf + 1] = pack2(hi16(h), i1 - hi16(h));
        asm volatile("" : "+r"(tV[hf]), "+r"(uu[2 * hf]), "+r"(uu[2 * hf + 1])::"memory");
      }
      wgmma_wait<0>();
      fence_regs(kv);
      TSL_(2);
      if (w == 0) {
        uint32_t f[2][18], ad[4];
#pragma unroll
        for (int q = 0; q < 18; q++) f[1][q] = 0u;
#pragma unroll
        for (int q = 0; q < 4; q++) ad[q] = x.maddr(sb + OFF_S, 2 * q);
        auto norm = [&](int un) {
          uint32_t* u = f[un & 1];
          const Stats& sn = (un & 2) ? s1 : s0;
#pragma unroll
          for (int sg = 0; sg < 2; sg++) {
            uint32_t v = u[16 + sg];
            v = add2(v, __shfl_xor_sync(0xffffffffu, v, 1)); v = add2(v, __shfl_xor_sync(0xffffffffu, v, 2));
            const float a = rcp(lo16(v)) * sn.rstd0, b = rcp(hi16(v)) * sn.rstd1;
            const uint32_t r0 = pack2(a, a), r1_ = pack2(b, b);
#pragma unroll
            for (int q = 8 * sg; q < 8 * sg + 8; q++) u[q] = mul2(u[q], (q & 1) ? r1_ : r0);
#pragma unroll
            for (int q = 2 * sg; q < 2 * sg + 2; q++) stsm4(ad[q] + (un & 1) * SLOT + (un >> 1) * 8192, u[4 * q], u[4 * q + 1], u[4 * q + 2], u[4 * q + 3]);
          }
        };
        auto unit = [&](int un) { return kv + ((un >> 1) & 1) * 64 + (un & 1) * 16 + (un >> 2) * 32; };
        hedgehog_scale<0>(kv, s0, nullptr);
#pragma unroll 1
        for (int it = 0;; it++) {
#pragma unroll
          for (int un = 0; un < 4; un++) {
            if (un == 1) {
              if (it) asm volatile("bar.sync 9, 256;" ::: "memory");
#pragma unroll
              for (int q = 0; q < 4; q++) ad[q] -= it * (OFF_S - OFF_B - 2 * SLOT);
            }
            norm((un + 3) & 3);
            dual_exp(unit(un), f[un & 1], x.goff);
            hedgehog_scale<KEEP>(unit(un + 1), ((un + 1) & 2) ? s1 : s0, f[(un + 1) & 1]);
          }
          if (it) break;
#pragma unroll
          for (int q = 0; q < 32; q++) {
            asm volatile("mov.b32 %0, %1;" : "=f"(kv[q]) : "f"(kv[q + 32]));
            asm volatile("mov.b32 %0, %1;" : "=f"(kv[q + 64]) : "f"(kv[q + 96]));
            if (q < 16) kv[32 + q] = 0.f;
          }
        }
        norm(3);
        TSL_(3);
      } else {
        wg_bar(w);
#pragma unroll
        for (int hf = 0; hf < 2; hf++) {
          stsm4(tV[hf] + 512 + x.mhi * 512, uu[2 * hf], uu[2 * hf + 1], uu[2 * hf], uu[2 * hf + 1]);
          stsm4(tV[hf] + 1792 + x.mhi * 512, uu[2 * hf], uu[2 * hf + 1], uu[2 * hf], uu[2 * hf + 1]);
#pragma unroll
          for (int q = 0; q < 8; q++) {
            const float* u = kv + 64 * hf + 8 * q;
            stsm4(tV[hf] + (q >> 1) * 640 + (q & 1) * 256, pack2(u[0], u[1]), pack2(u[2], u[3]), pack2(u[4], u[5]), pack2(u[6], u[7]));
          }
        }
        TSL_(3);
      }
      {
        float d[2][20];
        uint4* dst = &g_kvpart[x.j()][w * 4 + x.warp][0][x.m() * 32 + x.lane];
        unsigned* dz = reinterpret_cast<unsigned*>(&g_kvpart[x.j()][w * 4 + x.warp][x.c & 1][512]) + x.m() * 8 + x.g;
        asm volatile("" : "+l"(dst), "+l"(dz)::"memory");
        fence_async_smem();
        cta_bar();
        TSL_(11);
        uint32_t pk[9];
        auto prep = [&](float (&u)[20]) {
          fence_regs(u);
#pragma unroll
          for (int q = 0; q < 8; q++) pk[q] = pack2(u[((q >> 1) & 2) + 4 * (q & 3)], u[((q >> 1) & 2) + 4 * (q & 3) + 1]);
          pk[8] = __float_as_uint((x.c & 1) ? u[18] + u[19] : u[16] + u[17]);
#pragma unroll
          for (int q = 0; q < 9; q += 4) pk[q] = (pk[q] & ~1u) | (L == 1);
        };
        auto send = [&](int hp) {
          st_v4(dst + hp * 16 * 544, pk[0], pk[1], pk[2], pk[3]); st_v4(dst + (hp * 16 + 1) * 544, pk[4], pk[5], pk[6], pk[7]);
          st_flag(dz + hp * 16 * 544 * 4, pk[8]);
        };
        wgmma_fence();
#pragma unroll
        for (int q = 0; q < 17; q++) {
          if (q < 16) wgmma_ss_n40_tt(d[q >> 3], desc_lo(SB + (q < 8 ? OFF_S : OFF_B + 2 * SLOT), 1024) + w * (SLOT / 16) + 128 * (q & 7), desc_lo(SB + vreg(q & 7), 2560) + (w + (q >> 3) * 2) * 40, q & 7);
          else wgmma_r1_n128(acc, dm + w * 64, dcs, 0);
          if (q == 7 || q == KVS || q == 16) wgmma_commit();
          if (q == KVS) { wgmma_wait<1>(); prep(d[0]); send(0); mbar_wait2(x.fullA(x.ra.s), x.ra.ph, x.fullB(x.rb.s), x.rb.ph); wgmma_fence(); }
        }
        gemm_issue<128, false>(acc, x, true); gemm_next<128>(x);
        wgmma_wait<1>();
        x.releaseA(h0); x.releaseA(h1); x.releaseB(2); x.releaseB(3);
        if (x.lane == 0) mbar_arrive(sb + BAR_SIGT);
        prep(d[1]);
        TSL_(4);
#pragma unroll 1
        for (int seg = 0; seg < 2; seg++) {
          const int n0 = w ? PS1 : PS0;
          gemm_run(acc, x, seg ? 15 - n0 : n0, seg, seg ? L : 0);
          if (seg == 0) send(1);
        }
      }
      gemm_end(acc, x);
      TSL_(5);
      {
        float dp[2][20], dn[2][20];
        uint32_t f[4][16];
        auto mma = [&](int h) {
          if (!(h & 1)) mbar_wait(sb + BAR_KV + h * 4, L >> 1);
          if (h == 0) TSL_(9);
          const uint32_t db = desc_lo(SB + OFF_S + h * 5120, 128);
          const uint32_t (&a)[16] = f[h];
          wgmma_fence();
          wgmma_rs_n40(dp[h & 1], a[0], a[1], a[2], a[3], db, 0);
          wgmma_rs_n40(dn[h & 1], a[8], a[9], a[10], a[11], db + 160, 0);
          wgmma_rs_n40(dp[h & 1], a[4], a[5], a[6], a[7], db + 80, 1);
          wgmma_rs_n40(dn[h & 1], a[12], a[13], a[14], a[15], db + 240, 1);
          wgmma_commit();
        };
        uint32_t xr[16];
        auto fin = [&](int h) {
          const uint32_t tile = x.aslot(x.held(h >> 1));
          if (!(h & 1)) img_load(xr, tile, x);
          float (&u)[20] = dp[h & 1];
          float (&v)[20] = dn[h & 1];
          fence_regs(u); fence_regs(v);
#pragma unroll
          for (int r = 0; r < 2; r++) {
            float cc = u[17 + 2 * r] * rcp(v[17 + 2 * r]);
            const float aa = rcp(fmaf(v[16 + 2 * r], cc, fmaf(u[17 + 2 * r], 1e-6f, u[16 + 2 * r])));
            cc *= aa;
            uint32_t o[4];
#pragma unroll
            for (int t = 0; t < 4; t++) o[t] = pack2(fmaf(u[4 * t + 2 * r], aa, v[4 * t + 2 * r] * cc), fmaf(u[4 * t + 2 * r + 1], aa, v[4 * t + 2 * r + 1] * cc));
            x.img(0, h >> 1)[r * 64 + (h & 1) * 32] = make_uint4(o[0], o[1], o[2], o[3]);
            sts128(tile + r * 1024 + (h & 1) * 512 + x.oo() * 16, o[0], o[1], o[2], o[3]);
          }
          if (h & 1) { publish(h >> 1, x); img_unpack(acc + 16 * (h - 1), xr); }
        };
        auto scale = [&](int h) { hedgehog_scale<0>(acc + 16 * h, st, nullptr); };
        auto ex = [&](int h) { dual_exp_rcp(acc + 16 * h, f[h]); };
        scale(0);
        ex(0); scale(1); mma(0);
        ex(1); wgmma_wait<0>(); fin(0); scale(2); mma(1);
        ex(2); wgmma_wait<0>(); fin(1); scale(3); mma(2);
        ex(3); wgmma_wait<0>(); fin(2); mma(3);
        wgmma_wait<0>(); fin(3);
      }
    }
    if (PW & 2) { mbar_wait(x.fullB(x.rb.s), x.rb.ph); fence_regs(acc); }
    fence_async_smem();
    wg_bar(w);
    TSL_(6);
    rewind2<NA>(x.ra);
    gemm_issue<128, false>(acc, x, PW & 2); gemm_next<128>(x);
#pragma unroll 1
    for (int seg = L >= TSL ? 0 : 1; seg < 2; seg++) {
      gemm_run(acc, x, L >= TSL ? (seg ? TSK : 15 - TSK) : 15, seg);
      if (L >= TSL) {
        if (seg == 0 && w == 1) asm volatile("bar.sync 6, 256;" ::: "memory");
        if (seg == 1 && w == 0) asm volatile("bar.arrive 6, 256;" ::: "memory");
      }
    }
    gemm_end(acc, x);
    TSL_(7);
    rewind2<NA>(x.ra);
    out_epilogue(acc, r1, ts, P.out + goff, L, x);
    TSL_(13);
  }
}

typedef unsigned long long u64;
template <class T> __device__ __forceinline__ T* early(T* p) { return (T*)__shfl_xor_sync(0xffffffffu, (u64)p, 1); }
__device__ __forceinline__ void pause(uint32_t GAP) {
  if (GAP) { uint32_t t0, t; asm volatile("mov.u32 %0, %%clock;" : "=r"(t0)); do { asm volatile("mov.u32 %0, %%clock;" : "=r"(t)); } while (t - t0 < GAP); }
}
__device__ __forceinline__ u64 order_table(int kind, int j) {
  const int i = threadIdx.x & 15;
  const unsigned v = (unsigned)(kind == 2 ? q_order(i, j) : kv_order(i, j, kind)) << (4 * (i & 7));
  return (u64)__reduce_or_sync(0xffffffffu, i < 8 ? 0u : v) << 32 | __reduce_or_sync(0xffffffffu, i < 8 ? v : 0u);
}

__device__ __forceinline__ void b_producer(const Params& P, uint32_t sb, unsigned vb) {
  const int j = cta_j(vb);
  const u64 t0 = order_table(0, j), t1 = order_table(1, j), t2 = order_table(2, j);
  Ring r = {PRE_B % NB, PRE_B < NB};
#pragma unroll 1
  for (int sg = 0; sg < 20; sg++) {
    const int L = sg / 5, p = sg - 5 * L, wt = L & 1;
    int n = p >= 3 ? 16 : (wt ? (p ? 16 - NJ : 2 * NJ) : (p ? 0 : (L ? 32 : 32 - PRE_B)));
    u64 tab = p == 3 ? t2 : (sg == 0 ? t0 >> (2 * PRE_B) : (p == 1 || p == 2 ? t1 >> (4 * NJ) : t1));
    const CUtensorMap* tm = p == 4 ? &P.mwo[wt] : &P.mw[wt ? 1 : L];
    const uint4* img = &g_wf[p != 3][j][0][0];
    int col = (p >= 3 ? 0 : (p == 2 ? 2048 : 1024)) + 128 * j;
    const int flip = p == 0 ? 3072 : 0;
    const bool fold = wt && p != 4;
    if (sg == 5 || sg == 8) { mbar_wait(sb + (sg == 5 ? BAR_WPHI : BAR_CS + 8), sg == 5); fence_async_global(); }
    if (DEFER && p == 4 && ((DEFL >> wt) & 1)) {
      Ring q = r;
      for (int u = 0; u < DEFER; u++) adv<NB>(q);
      mbar_wait(sb + BAR_EMPTYB + q.s * 8, q.ph);
    }
#pragma unroll 1
    for (; n > 0; n--) {
      const int kb = (int)tab & 15;
      mbar_wait(sb + BAR_EMPTYB + r.s * 8, r.ph);
      if (elect()) {
        mbar_expect_tx(sb + BAR_FULLB + r.s * 8, SLOT);
        if (fold && col < 2048) bulk_load(sb + OFF_B + r.s * SLOT, img + kb * 1024, SLOT, sb + BAR_FULLB + r.s * 8);
        else tma_load_w(sb + OFF_B + r.s * SLOT, tm, sb + BAR_FULLB + r.s * 8, col, kb);
      }
      adv<NB>(r);
      if (p == 2 && (n | 4) == 5) r.s = 4;
      col ^= flip;
      if (!(col & flip & 2048)) tab >>= 4;
    }
  }
}

__device__ __forceinline__ void a_loader(const Params& P, uint32_t sb, unsigned vb) {
  const int j = cta_j(vb), m = cta_m(vb);
  const u64 t1 = order_table(1, j), t2 = order_table(2, j);
  Ring r = {PRE_A % NA, PRE_A < NA};
  {
    u64 tab = order_table(0, j) >> (4 * PRE_A);
#pragma unroll 1
    for (int i = PRE_A; i < 33; i++) {
      if (i == 17) tab = t2;
      mbar_wait(sb + BAR_EMPTYA + r.s * 8, r.ph);
      if (elect()) {
        mbar_expect_tx(sb + BAR_FULLA + r.s * 8, SLOT);
        if (i != 14) tma_load_3d(sb + OFF_A + r.s * SLOT, &P.mx, sb + BAR_FULLA + r.s * 8, ((int)tab & 15) * 64, m * 64, 0);
        else {
          tma_load_w(sb + OFF_A + r.s * SLOT, &P.mw[1], sb + BAR_FULLA + r.s * 8, 1024 + 128 * j, m);
          mbar_expect_tx(sb + BAR_WPHI, 8192); tma_load_2d(sb + OFF_S + 4096, &P.mwphi, sb + BAR_WPHI, 0, 128 * j);
        }
        if (i == PF0 || i == PF1 || i == PF2)
          tma_prefetch_w(i == PF0 ? &P.mw[1] : &P.mwo[i == PF2], (i == PF0 ? 1024 : 0) + 128 * j, m);
      }
      adv<NA>(r);
      if (i != 14) tab >>= 4;
    }
  }
  const unsigned tag = get_tag(sb);
  unsigned seen = 0;
#pragma unroll 1
  for (int sg = 0; sg < 27; sg++) {
    const int L = sg >> 3, p = sg & 7, q = p >= 3 ? p - 3 : p;
    if (p == 0 && (L & 1)) {
#pragma unroll 1
      for (int h = 0; h < 2; h++) {
        poll_flags(&g_kvfflag[L >> 1][j][h][0], 8, 0xFFu, tag);
        if (elect()) { mbar_expect_tx(sb + BAR_KV + h * 8, 10240); bulk_load(sb + OFF_S + h * 10240, &g_kvfin[j][8 * h][0], 10240, sb + BAR_KV + h * 8); }
      }
      TS(4, 14 + L);
    }
    int n = q == 0 ? 4 : (q == 1 ? 3 : (q == 2 ? 7 : (q == 3 ? ((L & 1) ? 0 : 16 - NJ) : 16)));
    u64 tab = q == 4 ? t2 : t1 >> (q == 0 ? 8 : (q == 1 ? 24 : (q == 2 ? 36 : 4 * NJ)));
    const uint4* img = &g_img[p >= 3 ? XBUF(L + 1) : 0][m][0][0];
    const uint32_t gap = p == 0 ? G0 : (p == 3 ? G3 : (q < 3 ? G1 : G4));
    bool poll = q == 0 || q == 2 || (q == 1 && seen != 0xFFFFFFFFu);
#pragma unroll 1
    for (; n > 0; n--) {
      const uint4* src = img + ((int)tab & 15) * 1024;
      src = early(src);
      mbar_wait(sb + BAR_EMPTYA + r.s * 8, r.ph);
      if (elect()) mbar_expect_tx(sb + BAR_FULLA + r.s * 8, SLOT);
      if (poll) {
        const int lane = threadIdx.x & 31, nn = p >= 3 ? PNX : PNO;
        const unsigned* f = (p >= 3 ? &g_xflag[L + 1][0][m][0] : &g_oflag[L][0][m][0]) + (q == 2 ? 512 : 0) + (lane & 7);
        if (q == 0 || (PN2 && q == 2)) f += (((lane >> 3) & (nn - 1)) - (m & (nn - 1))) * 32;
        const unsigned need = q == 0 ? 0x0F0F0F0Fu << (~j & 4) : 0xFFFFFFFFu;
        if (q == 0) mbar_wait(sb + BAR_SIGP + (p ? 16 : 0), L & 1);
        int it = 0;
        do { seen = __ballot_sync(0xffffffffu, ld_flag(f) == tag); if (++it > (1 << 22)) __trap(); } while ((seen & need) != need);
        if (q == 0) TS(2, p == 0 ? 5 + L * 8 : 9 + L * 8);
        poll = false;
      }
      if (elect()) bulk_load(sb + OFF_A + r.s * SLOT, src, SLOT, sb + BAR_FULLA + r.s * 8);
      adv<NA>(r);
      tab >>= 4;
      pause(gap);
    }
  }
}

__device__ __forceinline__ uint2 sum_packets(float (&a)[8], uint32_t addr, int n) {
  uint2 ok = make_uint2(~0u, 0u);
#pragma unroll 1
  for (int b = 0; b < n; b += KB) {
    uint4 v[KB];
#pragma unroll
    for (int u = 0; u < KB; u++) lds128(addr + (b + u) * 512, v[u].x, v[u].y, v[u].z, v[u].w);
#pragma unroll
    for (int u = 0; u < KB; u++) {
      ok.x &= v[u].x; ok.y |= v[u].x;
      a[0] += lo16(v[u].x); a[1] += hi16(v[u].x); a[2] += lo16(v[u].y); a[3] += hi16(v[u].y);
      a[4] += lo16(v[u].z); a[5] += hi16(v[u].z); a[6] += lo16(v[u].w); a[7] += hi16(v[u].w);
    }
  }
  return ok;
}
__device__ __forceinline__ void helper_bar() { asm volatile("bar.sync 4, 64;" ::: "memory"); }
__device__ __forceinline__ void helper(const Params& P, uint32_t sb, int w, unsigned vb) {
  const int j = cta_j(vb), m = cta_m(vb);
  if (w == 0) {
    if (elect()) {
      const unsigned t = atomicAdd(&g_ctr, 1u) / NCTA + 1u;
      asm volatile("st.shared.u32 [%0], %1;" ::"r"(sb + OFF_EPOCH), "r"(t) : "memory");
      mbar_arrive(sb + BAR_EPOCH);
    }
  }
  const unsigned tag = get_tag(sb);
  mbar_wait(sb + BAR_FULLB + 24, 0);
  const uint32_t stg = sb + OFF_T + w * 12288, stb = sb + BAR_STG + w * 24;
  Ring rs = {0, 0};
  auto cs_image = [&](int L) {
      const int lane = lane_id();
      poll_flags(&g_csflag[L][j][0], 16, L ? CSNEED : 0xFFFu, tag);
#pragma unroll
      for (int p = 0; p < 3; p++) {
        const uint4 u = ldcg4(&g_cs[L][0][p * 1024 + 128 * j + lane * 4]), v = ldcg4(&g_cs[L][1][p * 1024 + 128 * j + lane * 4]);
        const float c0 = __uint_as_float(u.x) + __uint_as_float(v.x), c1 = __uint_as_float(u.y) + __uint_as_float(v.y);
        const float c2 = __uint_as_float(u.z) + __uint_as_float(v.z), c3 = __uint_as_float(u.w) + __uint_as_float(v.w);
        const uint32_t h0 = pack2(c0, c1), h1 = pack2(c2, c3), dst = sb + OFF_CS + (p * 16 + (lane >> 1)) * 96 + L * 48 + (lane & 1) * 8;
        sts64(dst, h0, h1); sts64(dst + 16, pack2(c0 - lo16(h0), c1 - hi16(h0)), pack2(c2 - lo16(h1), c3 - hi16(h1))); sts64(dst + 32, h0, h1);
        if (L == 0) { sts64(dst + 48, 0u, 0u); sts64(dst + 64, 0u, 0u); sts64(dst + 80, 0u, 0u); }
      }
      if (L == 0 && lane < 4) sts64(sb + OFF_CS + 4608 + lane * 8, 0u, 0u);
      fence_async_smem();
      __syncwarp();
      if (elect()) mbar_arrive(sb + BAR_CS + L * 8);
      TS(4, 2 + L * 2);
  };
#pragma unroll 1
  for (int L = 0; L < 4; L++) {
    const int lane = lane_id();
    if (L == 0) {
      {
        const int wt = m >= 12, col = ((0x2021 >> (m & 12)) & 3) * 1024 + 128 * j + (m & 3) * 32;
        const CUtensorMap* tm = &P.mcs[wt];
        if (D2 && wt) __nanosleep(D2);
        constexpr int nb = 8;
        float a[8] = {0.f, 0.f, 0.f, 0.f, 0.f, 0.f, 0.f, 0.f};
#pragma unroll 1
        for (int b = -3; b < nb; b++) {
          if (b >= 0) {
            mbar_wait(stb + rs.s * 8, rs.ph);
            sum_packets(a, stg + rs.s * 4096 + lane * 16, 8);
            fence_async_smem();
            __syncwarp();
          }
          const uint32_t sl = b < 0 ? (rs.s + b + 3) % 3 : rs.s;
          if (b + 3 < nb && elect()) { mbar_expect_tx(stb + sl * 8, 4096); tma_load_2d(stg + sl * 4096, tm, stb + sl * 8, col, (w * (16 - nb) + b + 3) * 64); }
          if (b >= 0) adv<3>(rs);
        }
#pragma unroll
        for (int u = 0; u < 8; u++) {
          a[u] += __shfl_xor_sync(0xffffffffu, a[u], 4); a[u] += __shfl_xor_sync(0xffffffffu, a[u], 8); a[u] += __shfl_xor_sync(0xffffffffu, a[u], 16);
        }
        if (lane < 4) {
          float4* dst = reinterpret_cast<float4*>(&g_cs[wt][w][col + lane * 8]);
          dst[0] = make_float4(a[0], a[1], a[2], a[3]); dst[1] = make_float4(a[4], a[5], a[6], a[7]);
        }
        helper_bar();
        if (w == 0 && elect()) { fence_gpu(); st_flag(&g_csflag[wt][j][m], tag); }
      }
      if (w == 0) TS(4, 1 + L * 2);
    }
    if (w == 1) {
      if (L > 0) { mbar_wait(sb + BAR_SIGP + 24, (L - 1) & 1); __nanosleep(SD); }
#pragma unroll 1
      for (int p = 0; p < 2; p++) {
        uint4 v[8];
        for (int it = 0;; it++) {
          bool ok = true;
#pragma unroll
          for (int t = 0; t < 8; t++) v[t] = ld_pkt(&g_stats[m][p][t][lane]);
#pragma unroll
          for (int t = 0; t < 8; t++) ok = ok && (v[t].w & 15u) == seq4(tag, L);
          if (__all_sync(0xffffffffu, ok)) break;
          __nanosleep(200);
          if (it > (1 << 20)) __trap();
        }
        float s0 = 0.f, q0 = 0.f, s1 = 0.f, q1 = 0.f;
#pragma unroll
        for (int t = 0; t < 8; t++) { s0 += __uint_as_float(v[t].x); q0 += __uint_as_float(v[t].y); s1 += __uint_as_float(v[t].z); q1 += __uint_as_float(v[t].w & ~15u); }
        s0 *= (1.f / 1024); s1 *= (1.f / 1024);
        sts64(sb + OFF_MR + p * 256 + lane * 8, __float_as_uint(rsqrtf(fmaxf(q0 * (1.f / 1024) - s0 * s0, 0.f) + 1e-5f)),
              __float_as_uint(rsqrtf(fmaxf(q1 * (1.f / 1024) - s1 * s1, 0.f) + 1e-5f)));
#pragma unroll
        for (int r = 0; r < 2; r++) {
          const float v = -0.5f * (r ? s1 : s0);
          const uint32_t hh = pack2(v, v), hl = pack2(v, v - lo16(hh));
          const bool b = L & 1;
          sts128(sb + (b ? OFF_MB : OFF_MA) + p * 1024 + (lane >> 3) * 256 + r * 128 + (lane & 7) * 16, b ? 0u : hh, b ? hh << 16 : hl >> 16, b ? hl : 0u, 0u);
        }
      }
      fence_async_smem();
      __syncwarp();
      if (elect()) {
        mbar_arrive(sb + BAR_STAT);
      }
      TS(2, 0 + L * 8);
    }
    if (L == w) cs_image(L);
    if (L & 1) {
      const uint32_t flip = L == 1 ? 0u : 1u;
      mbar_wait(sb + BAR_SIGT, 1);
      {
        int it = 0;
        if (PSL) __nanosleep(m < 8 ? PSL : PSL + 600);
        while (!__all_sync(0xffffffffu, (ld_flag(reinterpret_cast<const unsigned*>(&g_kvpart[j][m][w][512]) + (lane & 15) * 8) ^ flip) & 1u)) { if (PSL) __nanosleep(100); if (++it > (1 << 22)) __trap(); }
        fence_async_global();
      }
      if (w == 0) TS(4, 6 + L * 2);
      for (int it = 0;; it++) {
        if (elect()) { mbar_expect_tx(stb + rs.s * 8, 8704); bulk_load(stg, &g_kvpart[j][m][w][0], 8704, stb + rs.s * 8); }
        mbar_wait(stb + rs.s * 8, rs.ph);
        adv<3>(rs);
        float a[8] = {0.f, 0.f, 0.f, 0.f, 0.f, 0.f, 0.f, 0.f};
        float z = 0.f;
        uint32_t ok = 1u;
#pragma unroll
        for (int u = 0; u < 4; u++) { const float v = lds32f(stg + 8192 + u * 128 + (lane & 3) * 32 + (lane >> 2) * 4); z += v; ok &= __float_as_uint(v) ^ flip; }
        const uint2 tg = sum_packets(a, stg + lane * 16, 16);
        ok &= flip ? ~tg.y : tg.x;
        uint4* img = &g_kvfin[j][m][w * 8 + (lane >> 2)];
        img[(lane & 3) * 16] = make_uint4(pack2(a[0], a[1]), pack2(a[2], a[3]), pack2(a[4], a[5]), pack2(a[6], a[7]));
        reinterpret_cast<uint32_t*>(img + 64)[lane & 3] = pack2(qsum(z), 1.f);
        if (__all_sync(0xffffffffu, ok & 1u)) break;
        fence_async_smem();
        if (it > (1 << 16)) __trap();
      }
      if (w == 0) TS(4, 7 + L * 2);
      helper_bar();
      if (w == 1 && elect()) { fence_gpu(); st_flag(&g_kvfflag[L >> 1][j][m >> 3][m & 7], tag); }
      if (w == 1 && L == 1) TS(4, 20);
    } else {
      mbar_wait(sb + BAR_SIGT, 0);
      if (w == 0) {
        if (elect()) { fence_gpu(); st_flag(&g_hflag[L >> 1][m][j][0], tag); st_flag(&g_kflag[j][m], tag); }
        if (L == 0) {
          __nanosleep(KSL);
          poll_flags(&g_kflag[j][0], 16, 0xFFFFu, tag);
          if (elect()) mbar_arrive(sb + BAR_WPHI);
        }
      } else if (m > 0) {
        poll_flags(&g_hflag[L >> 1][m - 1][j][0], 1, 1u, tag);
        if (elect()) { mbar_expect_tx(sb + BAR_HALO, 8192); bulk_load(sb + OFF_S + 8192, &g_halo[m - 1][j][0][0], 8192, sb + BAR_HALO); }
        TS(2, 2 + L * 8);
      }
    }
#pragma unroll 1
    for (int e = 0; e < (L < 3 && w == 0 ? 3 : 1); e++) {
      unsigned* flag = e == 0 ? &g_oflag[L][w][m][j] : &g_xflag[L + 1][e - 1][m][j];
      flag = early(flag);
      mbar_wait(sb + BAR_SIGP + (e == 0 ? w : e + 1) * 8, L & 1);
      TS(e == 2 ? 3 : 2 + w, (e ? 6 : 3) + L * 8);
      if (elect()) { fence_async_global(); fence_gpu(); st_flag(flag, tag); }
      TS(e == 2 ? 3 : 2 + w, (e ? 7 : 4) + L * 8);
    }
  }
}

__device__ __forceinline__ void spare(const Params& P, uint32_t sb, int id) {
  const int tid = threadIdx.x & 127, w = __shfl_sync(0xffffffffu, threadIdx.x >> 7, 0), lane = tid & 31, j = 2 * id + w;
  const uint32_t ring = w * 6 * SLOT, wp = 12 * SLOT + w * 8192, bar = sb + 13 * SLOT + w * 64;
  auto part = [&](int t) { return (t >> 4) ^ w; };
  auto load = [&](int t, uint32_t sl) {
    mbar_expect_tx(bar + sl * 8, t == 0 ? SLOT + 8192 : SLOT);
    tma_load_w(sb + ring + sl * SLOT, &P.mw[1], bar + sl * 8, part(t) * 1024 + 128 * j, t & 15);
  };
  if (tid == 0) {
    if (w == 2) sts32(sb + OFF_EPOCH, atomicAdd(&g_ctr, 1u) / NCTA + 1u);
    else {
      __nanosleep(D3);
#pragma unroll 1
      for (int t = 0; t < 5; t++) {
        mbar_init(bar + t * 8, 1);
        asm volatile("fence.mbarrier_init.release.cluster;" ::: "memory");
        load(t, t);
      }
      tma_load_2d(sb + wp, &P.mwphi, bar, 0, 128 * j);
    }
  }
  __syncthreads();
  const unsigned tag = get_tag<false>(sb);
  if (w == 2) {
    int it = 0;
    while ((int)(ld_flag(&g_ctr) - tag * NCTA) < 0) { if (++it > (1 << 22)) __trap(); }
    return;
  }
  Ring r = {4, 1};
  float d[64] = {}, cs[32] = {};
  auto fold = [&]() {
    mbar_wait(bar + r.s * 8, r.ph);
    wgmma_fence();
#pragma unroll
    for (int q = 0; q < 8; q++)
      wgmma_ss_n32(reinterpret_cast<float (&)[16]>(d[16 * (q >> 1)]), desc_lo(SB + ring + r.s * SLOT, 16) + (q >> 2) * 512 + (q & 3) * 2, desc_lo(SB + wp, 512) + q * 64, q & 1);
    wgmma_commit();
  };
  const int row = (tid >> 5) * 16 + (lane >> 2);
#pragma unroll 1
  for (int t = -1; t < 32; t++) {
    uint32_t f[32];
#pragma unroll
    for (int i = 0; i < 32; i++) { f[i] = pack2(d[2 * i], d[2 * i + 1]); cs[i & 30] += d[2 * i]; cs[i | 1] += d[2 * i + 1]; }
    wg_bar(w);
    if (tid == 0 && t >= 0 && t < 27) load(t + 5, r.s);
    __syncwarp();
    if (t < 31) adv<5>(r);
    fold();
    if (part(t) == 0 && t >= 0) {
#pragma unroll
      for (int q = 0; q < 8; q++)
        g_wf[0][j][t & 15][(q >> 2) * 512 + (row + 8 * (q & 1)) * 8 + (((q & 2) * 2 + (lane & 3)) ^ (lane >> 2))] =
            make_uint4(f[4 * (q & 6) + (q & 1)], f[4 * (q & 6) + (q & 1) + 2], f[4 * (q & 6) + (q & 1) + 4], f[4 * (q & 6) + (q & 1) + 6]);
    }
    wgmma_wait<0>();
    fence_regs(d);
    if ((t & 15) == 15) {
      if (t >= 0) {
        const uint32_t red = sb + ring + 5 * SLOT;
#pragma unroll
        for (int i = 0; i < 8; i++) sts128(red + (tid >> 2) * 512 + (i >> 1) * 128 + (lane & 3) * 32 + (i & 1) * 16, __float_as_uint(cs[4 * i]), __float_as_uint(cs[4 * i + 1]), __float_as_uint(cs[4 * i + 2]), __float_as_uint(cs[4 * i + 3]));
        wg_bar(w);
        float a = 0.f;
#pragma unroll 4
        for (int i = 0; i < 32; i++) a += lds32f(red + i * 512 + tid * 4);
        g_cs[1][0][part(t) * 1024 + j * 128 + tid] = a;
        wg_bar(w);
        if (tid == 0) {
          fence_gpu();
          st_flag(&g_csflag[1][j][part(t)], tag);
        }
        __syncwarp();
      }
#pragma unroll
      for (int i = 0; i < 32; i++) cs[i] = 0.f;
    }
  }
}

__global__ void __launch_bounds__(NTHREADS, 1) fused_kernel(const __grid_constant__ Params P) {
  extern __shared__ __align__(1024) uint8_t smem_raw[];
  constexpr uint32_t sb = SB;
  const int tid = threadIdx.x;
  const unsigned vb = vblock();
  if (vb >= 128) { spare(P, sb, vb - 128); return; }
  const int warp = __shfl_sync(0xffffffffu, tid >> 5, 0);
  if (elect()) {
    if (warp == 11) { prefetch_map(&P.mx); prefetch_map(&P.mw[0]); if (smem_u32(smem_raw) != SB) __trap(); }
    if (warp < 7) {
#pragma unroll
      for (int i = 0; i < 8; i++) mbar_init(sb + OFF_BAR + (warp * 8 + i) * 8, warp == 2 || warp == 3 ? 2 : (warp == 4 ? 8 : 1));
    }
    asm volatile("fence.mbarrier_init.release.cluster;" ::: "memory");
    if (warp < 2) {
      const int j = cta_j(vb);
#pragma unroll 1
      for (int i = 0; i < (warp == 0 ? PRE_B : PRE_A); i++) {
        const uint32_t bar = sb + BAR_FULLB + warp * 64 + i * 8;
        mbar_expect_tx(bar, SLOT);
        if (warp == 0) tma_load_w(sb + OFF_B + i * SLOT, &P.mw[0], bar, 1024 + (i & 1) * 1024 + 128 * j, kv_order(i >> 1, j, 0));
        else tma_load_3d(sb + OFF_A + i * SLOT, &P.mx, bar, kv_order(i, j, 0) * 64, cta_m(vb) * 64, 0);
      }
    }
  }
  if (tid == 0) TS(6, 0);
  __syncthreads();
  if (tid == 0) TS(6, 2);
  if (warp < 4) {
    reg_dealloc<PREGS>();
    if (warp == 0) b_producer(P, sb, vb);
    else if (warp == 1) a_loader(P, sb, vb);
    else helper(P, sb, warp - 2, vb);
  } else {
    reg_alloc<CREGS>();
    consumer(P, sb, (warp >> 2) - 1, vb);
  }
}

typedef CUresult (*EncodeFn)(CUtensorMap*, CUtensorMapDataType, cuuint32_t, void*, const cuuint64_t*, const cuuint64_t*,
                             const cuuint32_t*, const cuuint32_t*, CUtensorMapInterleave, CUtensorMapSwizzle,
                             CUtensorMapL2promotion, CUtensorMapFloatOOBfill);

void encode(EncodeFn fn, CUtensorMap* m, const void* ptr, int rank, const cuuint64_t* dims, const cuuint64_t* strides,
            const cuuint32_t* box, CUtensorMapSwizzle swz) {
  const cuuint32_t es[5] = {1, 1, 1, 1, 1};
  fn(m, CU_TENSOR_MAP_DATA_TYPE_BFLOAT16, rank, const_cast<void*>(ptr), dims, strides, box, es, CU_TENSOR_MAP_INTERLEAVE_NONE,
     swz, CU_TENSOR_MAP_L2_PROMOTION_L2_256B, CU_TENSOR_MAP_FLOAT_OOB_FILL_NONE);
}
void encode_w(EncodeFn fn, CUtensorMap* m, const void* ptr, int ncols, bool perm) {
  const cuuint64_t p = (cuuint64_t)ncols * 2, d[5] = {(cuuint64_t)ncols, 2, 4, 4, 32}, s[4] = {p, (perm ? 8 : 2) * p, (perm ? 2 : 8) * p, 32 * p};
  const cuuint32_t box[5] = {64, 2, 4, 4, 2};
  encode(fn, m, ptr, 5, d, s, box, CU_TENSOR_MAP_SWIZZLE_128B);
}

void encode_cs(EncodeFn fn, CUtensorMap* m, const void* ptr, int ncols) {
  const cuuint64_t d[2] = {(cuuint64_t)ncols, 1024}, s[1] = {(cuuint64_t)ncols * 2};
  const cuuint32_t box[2] = {32, 64};
  encode(fn, m, ptr, 2, d, s, box, CU_TENSOR_MAP_SWIZZLE_NONE);
}

}

extern "C" void kernel_launch(void* const* d_in, const int* in_sizes, int n_in, void* d_out, int out_size) {
  (void)in_sizes; (void)n_in; (void)out_size;
  void* fnp = nullptr;
  cudaDriverEntryPointQueryResult q;
  cudaGetDriverEntryPoint("cuTensorMapEncodeTiled", &fnp, cudaEnableDefault, &q);
  EncodeFn fn = (EncodeFn)fnp;
  Params P;
  {
    const cuuint64_t dims[3] = {1024, 1024, 2}, strides[2] = {4096, 2048};
    const cuuint32_t box[3] = {64, 64, 2};
    encode(fn, &P.mx, d_in[0], 3, dims, strides, box, CU_TENSOR_MAP_SWIZZLE_128B);
  }
  P.out = (uint4*)d_out;
  encode_w(fn, &P.mw[0], d_in[1], 3072, false);
  encode_w(fn, &P.mw[1], d_in[4], 3072, true);
  encode_w(fn, &P.mw[2], d_in[1], 3072, true);
  encode_w(fn, &P.mwo[0], d_in[2], 1024, true);
  encode_w(fn, &P.mwo[1], d_in[6], 1024, false);
  encode_cs(fn, &P.mcs[0], d_in[1], 3072);
  encode_cs(fn, &P.mcs[1], d_in[4], 3072);
  {
    const cuuint64_t dims[2] = {32, 1024}, strides[1] = {64};
    const cuuint32_t box[2] = {32, 128};
    encode(fn, &P.mwphi, d_in[5], 2, dims, strides, box, CU_TENSOR_MAP_SWIZZLE_64B);
  }
  cudaFuncSetAttribute(fused_kernel, cudaFuncAttributeMaxDynamicSharedMemorySize, SMEM_BYTES);
  fused_kernel<<<NCTA, NTHREADS, SMEM_BYTES, cudaStreamPerThread>>>(P);
}
```

```cpp
#include <cuda_runtime.h>
#include <cuda_bf16.h>
#include <cuda.h>
#include <stdint.h>

namespace {

__device__ __forceinline__ void wgmma_ss_n256(float (&d)[128], uint32_t da, uint32_t ha, uint32_t db, int sd) {
  asm volatile("{\n.reg .pred p;\n.reg .b64 a, b;\nsetp.ne.b32 p, %130, 0;\nmov.b64 a, {%128, %131};\nmov.b64 b, {%129, 0x40000040};\n"
    "wgmma.mma_async.sync.aligned.m64n256k16.f32.bf16.bf16 {%0,%1,%2,%3,%4,%5,%6,%7,%8,%9,%10,%11,%12,%13,%14,%15,%16,%17,%18,%19,%20,%21,%22,%23,%24,%25,%26,%27,%28,%29,%30,%31,%32,%33,%34,%35,%36,%37,%38,%39,%40,%41,%42,%43,%44,%45,%46,%47,%48,%49,%50,%51,%52,%53,%54,%55,%56,%57,%58,%59,%60,%61,%62,%63,%64,%65,%66,%67,%68,%69,%70,%71,%72,%73,%74,%75,%76,%77,%78,%79,%80,%81,%82,%83,%84,%85,%86,%87,%88,%89,%90,%91,%92,%93,%94,%95,%96,%97,%98,%99,%100,%101,%102,%103,%104,%105,%106,%107,%108,%109,%110,%111,%112,%113,%114,%115,%116,%117,%118,%119,%120,%121,%122,%123,%124,%125,%126,%127}, a, b, p, 1, 1, 0, 1;\n}\n"
    : "+f"(d[0]),"+f"(d[1]),"+f"(d[2]),"+f"(d[3]),"+f"(d[4]),"+f"(d[5]),"+f"(d[6]),"+f"(d[7]),"+f"(d[8]),"+f"(d[9]),"+f"(d[10]),"+f"(d[11]),"+f"(d[12]),"+f"(d[13]),"+f"(d[14]),"+f"(d[15]),"+f"(d[16]),"+f"(d[17]),"+f"(d[18]),"+f"(d[19]),"+f"(d[20]),"+f"(d[21]),"+f"(d[22]),"+f"(d[23]),"+f"(d[24]),"+f"(d[25]),"+f"(d[26]),"+f"(d[27]),"+f"(d[28]),"+f"(d[29]),"+f"(d[30]),"+f"(d[31]),"+f"(d[32]),"+f"(d[33]),"+f"(d[34]),"+f"(d[35]),"+f"(d[36]),"+f"(d[37]),"+f"(d[38]),"+f"(d[39]),"+f"(d[40]),"+f"(d[41]),"+f"(d[42]),"+f"(d[43]),"+f"(d[44]),"+f"(d[45]),"+f"(d[46]),"+f"(d[47]),"+f"(d[48]),"+f"(d[49]),"+f"(d[50]),"+f"(d[51]),"+f"(d[52]),"+f"(d[53]),"+f"(d[54]),"+f"(d[55]),"+f"(d[56]),"+f"(d[57]),"+f"(d[58]),"+f"(d[59]),"+f"(d[60]),"+f"(d[61]),"+f"(d[62]),"+f"(d[63]),"+f"(d[64]),"+f"(d[65]),"+f"(d[66]),"+f"(d[67]),"+f"(d[68]),"+f"(d[69]),"+f"(d[70]),"+f"(d[71]),"+f"(d[72]),"+f"(d[73]),"+f"(d[74]),"+f"(d[75]),"+f"(d[76]),"+f"(d[77]),"+f"(d[78]),"+f"(d[79]),"+f"(d[80]),"+f"(d[81]),"+f"(d[82]),"+f"(d[83]),"+f"(d[84]),"+f"(d[85]),"+f"(d[86]),"+f"(d[87]),"+f"(d[88]),"+f"(d[89]),"+f"(d[90]),"+f"(d[91]),"+f"(d[92]),"+f"(d[93]),"+f"(d[94]),"+f"(d[95]),"+f"(d[96]),"+f"(d[97]),"+f"(d[98]),"+f"(d[99]),"+f"(d[100]),"+f"(d[101]),"+f"(d[102]),"+f"(d[103]),"+f"(d[104]),"+f"(d[105]),"+f"(d[106]),"+f"(d[107]),"+f"(d[108]),"+f"(d[109]),"+f"(d[110]),"+f"(d[111]),"+f"(d[112]),"+f"(d[113]),"+f"(d[114]),"+f"(d[115]),"+f"(d[116]),"+f"(d[117]),"+f"(d[118]),"+f"(d[119]),"+f"(d[120]),"+f"(d[121]),"+f"(d[122]),"+f"(d[123]),"+f"(d[124]),"+f"(d[125]),"+f"(d[126]),"+f"(d[127])
    : "r"(da), "r"(db), "r"(sd), "r"(ha));
}
__device__ __forceinline__ void wgmma_ss_n128(float (&d)[64], uint32_t da, uint32_t ha, uint32_t db, int sd) {
  asm volatile("{\n.reg .pred p;\n.reg .b64 a, b;\nsetp.ne.b32 p, %66, 0;\nmov.b64 a, {%64, %67};\nmov.b64 b, {%65, 0x40000040};\n"
    "wgmma.mma_async.sync.aligned.m64n128k16.f32.bf16.bf16 {%0,%1,%2,%3,%4,%5,%6,%7,%8,%9,%10,%11,%12,%13,%14,%15,%16,%17,%18,%19,%20,%21,%22,%23,%24,%25,%26,%27,%28,%29,%30,%31,%32,%33,%34,%35,%36,%37,%38,%39,%40,%41,%42,%43,%44,%45,%46,%47,%48,%49,%50,%51,%52,%53,%54,%55,%56,%57,%58,%59,%60,%61,%62,%63}, a, b, p, 1, 1, 0, 1;\n}\n"
    : "+f"(d[0]),"+f"(d[1]),"+f"(d[2]),"+f"(d[3]),"+f"(d[4]),"+f"(d[5]),"+f"(d[6]),"+f"(d[7]),"+f"(d[8]),"+f"(d[9]),"+f"(d[10]),"+f"(d[11]),"+f"(d[12]),"+f"(d[13]),"+f"(d[14]),"+f"(d[15]),"+f"(d[16]),"+f"(d[17]),"+f"(d[18]),"+f"(d[19]),"+f"(d[20]),"+f"(d[21]),"+f"(d[22]),"+f"(d[23]),"+f"(d[24]),"+f"(d[25]),"+f"(d[26]),"+f"(d[27]),"+f"(d[28]),"+f"(d[29]),"+f"(d[30]),"+f"(d[31]),"+f"(d[32]),"+f"(d[33]),"+f"(d[34]),"+f"(d[35]),"+f"(d[36]),"+f"(d[37]),"+f"(d[38]),"+f"(d[39]),"+f"(d[40]),"+f"(d[41]),"+f"(d[42]),"+f"(d[43]),"+f"(d[44]),"+f"(d[45]),"+f"(d[46]),"+f"(d[47]),"+f"(d[48]),"+f"(d[49]),"+f"(d[50]),"+f"(d[51]),"+f"(d[52]),"+f"(d[53]),"+f"(d[54]),"+f"(d[55]),"+f"(d[56]),"+f"(d[57]),"+f"(d[58]),"+f"(d[59]),"+f"(d[60]),"+f"(d[61]),"+f"(d[62]),"+f"(d[63])
    : "r"(da), "r"(db), "r"(sd), "r"(ha));
}
__device__ __forceinline__ void wgmma_ss_n40_tt(float (&d)[20], uint32_t da, uint32_t db, int sd) {
  asm volatile("{\n.reg .pred p;\n.reg .b64 a, b;\nsetp.ne.b32 p, %22, 0;\nmov.b64 a, {%20, 0x40000040};\nmov.b64 b, {%21, 0x8};\n"
    "wgmma.mma_async.sync.aligned.m64n40k16.f32.bf16.bf16 {%0,%1,%2,%3,%4,%5,%6,%7,%8,%9,%10,%11,%12,%13,%14,%15,%16,%17,%18,%19}, a, b, p, 1, 1, 1, 1;\n}\n"
    : "+f"(d[0]),"+f"(d[1]),"+f"(d[2]),"+f"(d[3]),"+f"(d[4]),"+f"(d[5]),"+f"(d[6]),"+f"(d[7]),"+f"(d[8]),"+f"(d[9]),"+f"(d[10]),"+f"(d[11]),"+f"(d[12]),"+f"(d[13]),"+f"(d[14]),"+f"(d[15]),"+f"(d[16]),"+f"(d[17]),"+f"(d[18]),"+f"(d[19])
    : "r"(da), "r"(db), "r"(sd));
}
__device__ __forceinline__ void wgmma_ss_n32(float (&d)[16], uint32_t da, uint32_t db, int sd) {
  asm volatile("{\n.reg .pred p;\n.reg .b64 a, b;\nsetp.ne.b32 p, %18, 0;\nmov.b64 a, {%16, 0x40000040};\nmov.b64 b, {%17, 0x80000020};\n"
    "wgmma.mma_async.sync.aligned.m64n32k16.f32.bf16.bf16 {%0,%1,%2,%3,%4,%5,%6,%7,%8,%9,%10,%11,%12,%13,%14,%15}, a, b, p, 1, 1, 0, 1;\n}\n"
    : "+f"(d[0]),"+f"(d[1]),"+f"(d[2]),"+f"(d[3]),"+f"(d[4]),"+f"(d[5]),"+f"(d[6]),"+f"(d[7]),"+f"(d[8]),"+f"(d[9]),"+f"(d[10]),"+f"(d[11]),"+f"(d[12]),"+f"(d[13]),"+f"(d[14]),"+f"(d[15])
    : "r"(da), "r"(db), "r"(sd));
}
__device__ __forceinline__ void wgmma_rs_n40(float (&d)[20], uint32_t a0, uint32_t a1, uint32_t a2, uint32_t a3, uint32_t db, int sd) {
  asm volatile("{\n.reg .pred p;\n.reg .b64 b;\nsetp.ne.b32 p, %25, 0;\nmov.b64 b, {%24, 0x10};\n"
    "wgmma.mma_async.sync.aligned.m64n40k16.f32.bf16.bf16 {%0,%1,%2,%3,%4,%5,%6,%7,%8,%9,%10,%11,%12,%13,%14,%15,%16,%17,%18,%19}, {%20,%21,%22,%23}, b, p, 1, 1, 1;\n}\n"
    : "+f"(d[0]),"+f"(d[1]),"+f"(d[2]),"+f"(d[3]),"+f"(d[4]),"+f"(d[5]),"+f"(d[6]),"+f"(d[7]),"+f"(d[8]),"+f"(d[9]),"+f"(d[10]),"+f"(d[11]),"+f"(d[12]),"+f"(d[13]),"+f"(d[14]),"+f"(d[15]),"+f"(d[16]),"+f"(d[17]),"+f"(d[18]),"+f"(d[19])
    : "r"(a0), "r"(a1), "r"(a2), "r"(a3), "r"(db), "r"(sd));
}
__device__ __forceinline__ void wgmma_r1_n256(float (&d)[128], uint32_t da, uint32_t db, int sd) {
  asm volatile("{\n.reg .pred p;\n.reg .b64 a, b;\nsetp.ne.b32 p, %130, 0;\nmov.b64 a, {%128, 0x8};\nmov.b64 b, {%129, 0x6};\n"
    "wgmma.mma_async.sync.aligned.m64n256k16.f32.bf16.bf16 {%0,%1,%2,%3,%4,%5,%6,%7,%8,%9,%10,%11,%12,%13,%14,%15,%16,%17,%18,%19,%20,%21,%22,%23,%24,%25,%26,%27,%28,%29,%30,%31,%32,%33,%34,%35,%36,%37,%38,%39,%40,%41,%42,%43,%44,%45,%46,%47,%48,%49,%50,%51,%52,%53,%54,%55,%56,%57,%58,%59,%60,%61,%62,%63,%64,%65,%66,%67,%68,%69,%70,%71,%72,%73,%74,%75,%76,%77,%78,%79,%80,%81,%82,%83,%84,%85,%86,%87,%88,%89,%90,%91,%92,%93,%94,%95,%96,%97,%98,%99,%100,%101,%102,%103,%104,%105,%106,%107,%108,%109,%110,%111,%112,%113,%114,%115,%116,%117,%118,%119,%120,%121,%122,%123,%124,%125,%126,%127}, a, b, p, 1, 1, 0, 1;\n}\n"
    : "+f"(d[0]),"+f"(d[1]),"+f"(d[2]),"+f"(d[3]),"+f"(d[4]),"+f"(d[5]),"+f"(d[6]),"+f"(d[7]),"+f"(d[8]),"+f"(d[9]),"+f"(d[10]),"+f"(d[11]),"+f"(d[12]),"+f"(d[13]),"+f"(d[14]),"+f"(d[15]),"+f"(d[16]),"+f"(d[17]),"+f"(d[18]),"+f"(d[19]),"+f"(d[20]),"+f"(d[21]),"+f"(d[22]),"+f"(d[23]),"+f"(d[24]),"+f"(d[25]),"+f"(d[26]),"+f"(d[27]),"+f"(d[28]),"+f"(d[29]),"+f"(d[30]),"+f"(d[31]),"+f"(d[32]),"+f"(d[33]),"+f"(d[34]),"+f"(d[35]),"+f"(d[36]),"+f"(d[37]),"+f"(d[38]),"+f"(d[39]),"+f"(d[40]),"+f"(d[41]),"+f"(d[42]),"+f"(d[43]),"+f"(d[44]),"+f"(d[45]),"+f"(d[46]),"+f"(d[47]),"+f"(d[48]),"+f"(d[49]),"+f"(d[50]),"+f"(d[51]),"+f"(d[52]),"+f"(d[53]),"+f"(d[54]),"+f"(d[55]),"+f"(d[56]),"+f"(d[57]),"+f"(d[58]),"+f"(d[59]),"+f"(d[60]),"+f"(d[61]),"+f"(d[62]),"+f"(d[63]),"+f"(d[64]),"+f"(d[65]),"+f"(d[66]),"+f"(d[67]),"+f"(d[68]),"+f"(d[69]),"+f"(d[70]),"+f"(d[71]),"+f"(d[72]),"+f"(d[73]),"+f"(d[74]),"+f"(d[75]),"+f"(d[76]),"+f"(d[77]),"+f"(d[78]),"+f"(d[79]),"+f"(d[80]),"+f"(d[81]),"+f"(d[82]),"+f"(d[83]),"+f"(d[84]),"+f"(d[85]),"+f"(d[86]),"+f"(d[87]),"+f"(d[88]),"+f"(d[89]),"+f"(d[90]),"+f"(d[91]),"+f"(d[92]),"+f"(d[93]),"+f"(d[94]),"+f"(d[95]),"+f"(d[96]),"+f"(d[97]),"+f"(d[98]),"+f"(d[99]),"+f"(d[100]),"+f"(d[101]),"+f"(d[102]),"+f"(d[103]),"+f"(d[104]),"+f"(d[105]),"+f"(d[106]),"+f"(d[107]),"+f"(d[108]),"+f"(d[109]),"+f"(d[110]),"+f"(d[111]),"+f"(d[112]),"+f"(d[113]),"+f"(d[114]),"+f"(d[115]),"+f"(d[116]),"+f"(d[117]),"+f"(d[118]),"+f"(d[119]),"+f"(d[120]),"+f"(d[121]),"+f"(d[122]),"+f"(d[123]),"+f"(d[124]),"+f"(d[125]),"+f"(d[126]),"+f"(d[127])
    : "r"(da), "r"(db), "r"(sd));
}
__device__ __forceinline__ void wgmma_r1_n128(float (&d)[64], uint32_t da, uint32_t db, int sd) {
  asm volatile("{\n.reg .pred p;\n.reg .b64 a, b;\nsetp.ne.b32 p, %66, 0;\nmov.b64 a, {%64, 0x8};\nmov.b64 b, {%65, 0x6};\n"
    "wgmma.mma_async.sync.aligned.m64n128k16.f32.bf16.bf16 {%0,%1,%2,%3,%4,%5,%6,%7,%8,%9,%10,%11,%12,%13,%14,%15,%16,%17,%18,%19,%20,%21,%22,%23,%24,%25,%26,%27,%28,%29,%30,%31,%32,%33,%34,%35,%36,%37,%38,%39,%40,%41,%42,%43,%44,%45,%46,%47,%48,%49,%50,%51,%52,%53,%54,%55,%56,%57,%58,%59,%60,%61,%62,%63}, a, b, p, 1, 1, 0, 1;\n}\n"
    : "+f"(d[0]),"+f"(d[1]),"+f"(d[2]),"+f"(d[3]),"+f"(d[4]),"+f"(d[5]),"+f"(d[6]),"+f"(d[7]),"+f"(d[8]),"+f"(d[9]),"+f"(d[10]),"+f"(d[11]),"+f"(d[12]),"+f"(d[13]),"+f"(d[14]),"+f"(d[15]),"+f"(d[16]),"+f"(d[17]),"+f"(d[18]),"+f"(d[19]),"+f"(d[20]),"+f"(d[21]),"+f"(d[22]),"+f"(d[23]),"+f"(d[24]),"+f"(d[25]),"+f"(d[26]),"+f"(d[27]),"+f"(d[28]),"+f"(d[29]),"+f"(d[30]),"+f"(d[31]),"+f"(d[32]),"+f"(d[33]),"+f"(d[34]),"+f"(d[35]),"+f"(d[36]),"+f"(d[37]),"+f"(d[38]),"+f"(d[39]),"+f"(d[40]),"+f"(d[41]),"+f"(d[42]),"+f"(d[43]),"+f"(d[44]),"+f"(d[45]),"+f"(d[46]),"+f"(d[47]),"+f"(d[48]),"+f"(d[49]),"+f"(d[50]),"+f"(d[51]),"+f"(d[52]),"+f"(d[53]),"+f"(d[54]),"+f"(d[55]),"+f"(d[56]),"+f"(d[57]),"+f"(d[58]),"+f"(d[59]),"+f"(d[60]),"+f"(d[61]),"+f"(d[62]),"+f"(d[63])
    : "r"(da), "r"(db), "r"(sd));
}

__device__ __forceinline__ uint32_t smem_u32(const void* p) { return (uint32_t)__cvta_generic_to_shared(p); }
__device__ __forceinline__ void mbar_init(uint32_t bar, uint32_t cnt) { asm volatile("mbarrier.init.shared::cta.b64 [%0], %1;" ::"r"(bar), "r"(cnt)); }
__device__ __forceinline__ void mbar_expect_tx(uint32_t bar, uint32_t bytes) { asm volatile("mbarrier.arrive.expect_tx.shared::cta.b64 _, [%0], %1;" ::"r"(bar), "r"(bytes) : "memory"); }
__device__ __forceinline__ void mbar_arrive(uint32_t bar) { asm volatile("mbarrier.arrive.shared::cta.b64 _, [%0];" ::"r"(bar) : "memory"); }
__device__ __forceinline__ void mbar_arrive_n(uint32_t bar, uint32_t n) { asm volatile("mbarrier.arrive.shared::cta.b64 _, [%0], %1;" ::"r"(bar), "r"(n) : "memory"); }
__device__ __forceinline__ void mbar_wait(uint32_t bar, uint32_t parity) {
  asm volatile("{\n.reg .pred p;\nLAB_WAIT:\nmbarrier.try_wait.parity.shared::cta.b64 p, [%0], %1;\n@p bra DONE;\nbra LAB_WAIT;\nDONE:\n}" ::"r"(bar), "r"(parity) : "memory");
}
__device__ __forceinline__ void mbar_wait2(uint32_t a, uint32_t pa, uint32_t b, uint32_t pb) {
  asm volatile("{\n.reg .pred p, q;\nLAB_WAIT:\nmbarrier.try_wait.parity.shared::cta.b64 p, [%0], %1;\nmbarrier.try_wait.parity.shared::cta.b64 q, [%2], %3;\n"
               "and.pred p, p, q;\n@p bra DONE;\nbra LAB_WAIT;\nDONE:\n}" ::"r"(a), "r"(pa), "r"(b), "r"(pb) : "memory");
}
__device__ __forceinline__ void mbar_wait3(uint32_t a, uint32_t pa, uint32_t b, uint32_t pb) {
  asm volatile("{\n.reg .pred p, q, r;\nLAB_WAIT:\nmbarrier.try_wait.parity.shared::cta.b64 p, [%0], %1;\nmbarrier.try_wait.parity.shared::cta.b64 q, [%2], %3;\n"
               "mbarrier.try_wait.parity.shared::cta.b64 r, [%2+8], %3;\nand.pred p, p, q;\nand.pred p, p, r;\n@p bra DONE;\nbra LAB_WAIT;\nDONE:\n}" ::"r"(a), "r"(pa), "r"(b), "r"(pb) : "memory");
}
__device__ __forceinline__ bool mbar_probe2(uint32_t a, uint32_t pa, uint32_t b, uint32_t pb) {
  uint32_t ok;
  asm volatile("{\n.reg .pred p, q;\nmbarrier.test_wait.parity.shared::cta.b64 p, [%1], %2;\nmbarrier.test_wait.parity.shared::cta.b64 q, [%3], %4;\n"
               "and.pred p, p, q;\nselp.u32 %0, 1, 0, p;\n}" : "=r"(ok) : "r"(a), "r"(pa), "r"(b), "r"(pb) : "memory");
  return ok != 0;
}
__device__ __forceinline__ void tma_load_3d(uint32_t dst, const CUtensorMap* tm, uint32_t bar, int c0, int c1, int c2) {
  asm volatile("cp.async.bulk.tensor.3d.shared::cluster.global.mbarrier::complete_tx::bytes [%0], [%1, {%3, %4, %5}], [%2];"
               ::"r"(dst), "l"(tm), "r"(bar), "r"(c0), "r"(c1), "r"(c2) : "memory");
}
__device__ __forceinline__ void tma_load_2d(uint32_t dst, const CUtensorMap* tm, uint32_t bar, int c0, int c1) {
  asm volatile("cp.async.bulk.tensor.2d.shared::cluster.global.mbarrier::complete_tx::bytes [%0], [%1, {%3, %4}], [%2];"
               ::"r"(dst), "l"(tm), "r"(bar), "r"(c0), "r"(c1) : "memory");
}
__device__ __forceinline__ void tma_load_w(uint32_t dst, const CUtensorMap* tm, uint32_t bar, int col, int kb) {
#pragma unroll
  for (int q = 0; q < 2; q++)
    asm volatile("cp.async.bulk.tensor.5d.shared::cluster.global.mbarrier::complete_tx::bytes [%0], [%1, {%3, %4, %4, %4, %5}], [%2];"
                 ::"r"(dst + q * 8192), "l"(tm), "r"(bar), "r"(col + q * 64), "r"(0), "r"(2 * kb) : "memory");
}
__device__ __forceinline__ void tma_prefetch_w(const CUtensorMap* tm, int col, int kb) {
#pragma unroll
  for (int q = 0; q < 2; q++)
    asm volatile("cp.async.bulk.prefetch.tensor.5d.L2.global [%0, {%1, %2, %2, %2, %3}];" ::"l"(tm), "r"(col + q * 64), "r"(0), "r"(2 * kb) : "memory");
}
__device__ __forceinline__ void bulk_load(uint32_t dst, const void* g, uint32_t bytes, uint32_t bar) {
  asm volatile("cp.async.bulk.shared::cluster.global.mbarrier::complete_tx::bytes [%0], [%1], %2, [%3];" ::"r"(dst), "l"(g), "r"(bytes), "r"(bar) : "memory");
}
__device__ __forceinline__ void prefetch_map(const CUtensorMap* tm) { asm volatile("prefetch.tensormap [%0];" ::"l"(tm) : "memory"); }
__device__ __forceinline__ void fence_async_smem() { asm volatile("fence.proxy.async.shared::cta;" ::: "memory"); }
__device__ __forceinline__ void fence_async_global() { asm volatile("fence.proxy.async.global;" ::: "memory"); }
__device__ __forceinline__ void fence_gpu() { asm volatile("fence.release.gpu;" ::: "memory"); }
__device__ __forceinline__ void st_flag(unsigned* p, unsigned v) { asm volatile("st.relaxed.gpu.global.u32 [%0], %1;" ::"l"(p), "r"(v) : "memory"); }
__device__ __forceinline__ unsigned ld_flag(const unsigned* p) { unsigned v; asm volatile("ld.relaxed.gpu.global.u32 %0, [%1];" : "=r"(v) : "l"(p) : "memory"); return v; }
__device__ __forceinline__ uint4 ldcg4(const void* p) { uint4 v; asm volatile("ld.global.cg.v4.u32 {%0,%1,%2,%3}, [%4];" : "=r"(v.x), "=r"(v.y), "=r"(v.z), "=r"(v.w) : "l"(p)); return v; }
__device__ __forceinline__ uint4 ld_pkt(const uint4* p) {
  uint4 v; asm volatile("{\n.reg .b128 t;\nld.relaxed.gpu.global.b128 t, [%4];\nmov.b128 {%0,%1,%2,%3}, t;\n}" : "=r"(v.x), "=r"(v.y), "=r"(v.z), "=r"(v.w) : "l"(p) : "memory"); return v;
}
__device__ __forceinline__ void st_pkt(uint4* p, uint32_t a, uint32_t b, uint32_t c, uint32_t tag) {
  asm volatile("{\n.reg .b128 t;\nmov.b128 t, {%1,%2,%3,%4};\nst.relaxed.gpu.global.b128 [%0], t;\n}" ::"l"(p), "r"(a), "r"(b), "r"(c), "r"(tag) : "memory");
}
__device__ __forceinline__ void st_v4(uint4* p, uint32_t a, uint32_t b, uint32_t c, uint32_t d) { asm volatile("st.relaxed.gpu.global.v4.u32 [%0], {%1,%2,%3,%4};" ::"l"(p), "r"(a), "r"(b), "r"(c), "r"(d) : "memory"); }
__device__ __forceinline__ void sts32(uint32_t addr, uint32_t a) { asm volatile("st.shared.u32 [%0], %1;" ::"r"(addr), "r"(a) : "memory"); }
__device__ __forceinline__ void sts64(uint32_t addr, uint32_t a, uint32_t b) { asm volatile("st.shared.v2.u32 [%0], {%1,%2};" ::"r"(addr), "r"(a), "r"(b) : "memory"); }
__device__ __forceinline__ uint32_t mul2(uint32_t a, uint32_t b) { uint32_t r; asm("mul.rn.bf16x2 %0, %1, %2;" : "=r"(r) : "r"(a), "r"(b)); return r; }
__device__ __forceinline__ uint32_t add2(uint32_t a, uint32_t b) { uint32_t r; asm("add.rn.bf16x2 %0, %1, %2;" : "=r"(r) : "r"(a), "r"(b)); return r; }
__device__ __forceinline__ bool elect() {
  uint32_t p; asm volatile("{\n.reg .pred q;\nelect.sync _|q, 0xffffffff;\nselp.u32 %0, 1, 0, q;\n}" : "=r"(p)); return p != 0;
}
__device__ __forceinline__ void wgmma_fence() { asm volatile("wgmma.fence.sync.aligned;" ::: "memory"); }
__device__ __forceinline__ void wgmma_commit() { asm volatile("wgmma.commit_group.sync.aligned;" ::: "memory"); }
template <int N> __device__ __forceinline__ void wgmma_wait() { asm volatile("wgmma.wait_group.sync.aligned %0;" ::"n"(N) : "memory"); }
template <int N> __device__ __forceinline__ void fence_regs(float (&d)[N]) {
#pragma unroll
  for (int i = 0; i < N; i++) asm volatile("" : "+f"(d[i])::"memory");
}
template <int R> __device__ __forceinline__ void reg_alloc() { asm volatile("setmaxnreg.inc.sync.aligned.u32 %0;" ::"n"(R)); }
template <int R> __device__ __forceinline__ void reg_dealloc() { asm volatile("setmaxnreg.dec.sync.aligned.u32 %0;" ::"n"(R)); }
__device__ __forceinline__ void wg_bar(int w) { asm volatile("bar.sync %0, 128;" ::"r"(w + 1) : "memory"); }
__device__ __forceinline__ constexpr uint32_t desc_lo(uint32_t addr, uint32_t lbo) { return (addr >> 4) + ((lbo >> 4) << 16); }
__device__ __forceinline__ uint32_t pack2(float lo, float hi) { uint32_t r; asm("cvt.rn.bf16x2.f32 %0, %1, %2;" : "=r"(r) : "f"(hi), "f"(lo)); return r; }
__device__ __forceinline__ float lo16(uint32_t v) { return __uint_as_float(v << 16); }
__device__ __forceinline__ float hi16(uint32_t v) { return __uint_as_float(v & 0xFFFF0000u); }
__device__ __forceinline__ float ex2(float x) { float r; asm("ex2.approx.ftz.f32 %0, %1;" : "=f"(r) : "f"(x)); return r; }
__device__ __forceinline__ float rcp(float x) { float r; asm("rcp.approx.ftz.f32 %0, %1;" : "=f"(r) : "f"(x)); return r; }
__device__ __forceinline__ uint32_t movm(uint32_t a) { uint32_t d; asm volatile("movmatrix.sync.aligned.m8n8.trans.b16 %0, %1;" : "=r"(d) : "r"(a)); return d; }
__device__ __forceinline__ void stsm4(uint32_t addr, uint32_t a, uint32_t b, uint32_t c, uint32_t d) {
  asm volatile("stmatrix.sync.aligned.m8n8.x4.shared.b16 [%0], {%1,%2,%3,%4};" ::"r"(addr), "r"(a), "r"(b), "r"(c), "r"(d) : "memory");
}
__device__ __forceinline__ void ldsm4(uint32_t addr, uint32_t (&r)[4]) {
  asm volatile("ldmatrix.sync.aligned.m8n8.x4.shared.b16 {%0,%1,%2,%3}, [%4];" : "=r"(r[0]), "=r"(r[1]), "=r"(r[2]), "=r"(r[3]) : "r"(addr) : "memory");
}
__device__ __forceinline__ void sts128(uint32_t addr, uint32_t a, uint32_t b, uint32_t c, uint32_t d) {
  asm volatile("st.shared.v4.u32 [%0], {%1,%2,%3,%4};" ::"r"(addr), "r"(a), "r"(b), "r"(c), "r"(d) : "memory");
}
__device__ __forceinline__ void lds128(uint32_t addr, uint32_t& a, uint32_t& b, uint32_t& c, uint32_t& d) {
  asm volatile("ld.shared.v4.u32 {%0,%1,%2,%3}, [%4];" : "=r"(a), "=r"(b), "=r"(c), "=r"(d) : "r"(addr) : "memory");
}
__device__ __forceinline__ float lds32f(uint32_t addr) { float v; asm volatile("ld.shared.f32 %0, [%1];" : "=f"(v) : "r"(addr) : "memory"); return v; }
__device__ __forceinline__ float2 lds64f(uint32_t addr) { float2 v; asm volatile("ld.shared.v2.f32 {%0,%1}, [%2];" : "=f"(v.x), "=f"(v.y) : "r"(addr) : "memory"); return v; }
__device__ __forceinline__ void mma16816(float (&d)[4], uint32_t a0, uint32_t a1, uint32_t a2, uint32_t a3, uint32_t b0, uint32_t b1) {
  asm("mma.sync.aligned.m16n8k16.row.col.f32.bf16.bf16.f32 {%0,%1,%2,%3}, {%4,%5,%6,%7}, {%8,%9}, {%0,%1,%2,%3};"
      : "+f"(d[0]), "+f"(d[1]), "+f"(d[2]), "+f"(d[3]) : "r"(a0), "r"(a1), "r"(a2), "r"(a3), "r"(b0), "r"(b1));
}
__device__ __forceinline__ void mma1688(float (&d)[4], uint32_t a0, uint32_t a1, uint32_t b0) {
  asm("mma.sync.aligned.m16n8k8.row.col.f32.bf16.bf16.f32 {%0,%1,%2,%3}, {%4,%5}, {%6}, {%0,%1,%2,%3};"
      : "+f"(d[0]), "+f"(d[1]), "+f"(d[2]), "+f"(d[3]) : "r"(a0), "r"(a1), "r"(b0));
}

__device__ __forceinline__ float qsum(float v) { v += __shfl_xor_sync(0xffffffffu, v, 1); v += __shfl_xor_sync(0xffffffffu, v, 2); return v; }

constexpr int NCTA = 132;
#define NB_ 6
#define NA_ 5
constexpr int NB = NB_;
constexpr int NA = NA_;
constexpr uint32_t SLOT = 16384;
constexpr uint32_t SB = 1024;
constexpr uint32_t OFF_B = 0;
constexpr uint32_t OFF_A = NB * SLOT;
constexpr uint32_t OFF_S = OFF_A + NA * SLOT;
constexpr uint32_t OFF_T = OFF_S + 20480;
constexpr uint32_t OFF_CS = OFF_T + 24576;
constexpr uint32_t OFF_MR = OFF_CS + 4640;
constexpr uint32_t OFF_BAR = OFF_MR + 512;
constexpr uint32_t OFF_MA = OFF_S, OFF_MB = OFF_CS - 2048;
constexpr uint32_t BAR_FULLB = OFF_BAR;
constexpr uint32_t BAR_FULLA = BAR_FULLB + 64;
constexpr uint32_t BAR_EMPTYB = BAR_FULLA + 64;
constexpr uint32_t BAR_EMPTYA = BAR_EMPTYB + 64;
constexpr uint32_t BAR_SIGP = BAR_EMPTYA + 64;
constexpr uint32_t BAR_SIGT = BAR_SIGP + 32;
constexpr uint32_t BAR_STAT = BAR_SIGP + 64;
constexpr uint32_t BAR_HALO = BAR_STAT + 16;
constexpr uint32_t BAR_CS = BAR_HALO + 8;
constexpr uint32_t BAR_WPHI = BAR_CS + 16;
constexpr uint32_t BAR_KV = BAR_WPHI + 8;
constexpr uint32_t BAR_STG = BAR_KV + 16;
constexpr uint32_t BAR_EPOCH = BAR_STG + 48;
constexpr uint32_t OFF_EPOCH = OFF_BAR + 7 * 64;
static_assert(BAR_EPOCH < OFF_EPOCH, "barriers");
constexpr uint32_t SMEM_BYTES = OFF_EPOCH + 8;
static_assert(SMEM_BYTES <= 232448 && NB % 2 == 0 && NB <= 8 && NA <= 6, "smem");

#define CREGS 224
#define PREGS 56
#define PF0 9
#define PF1 13
#define PF2 17
#define PRE_A 2
#define PRE_B 4
#define CSB 4
#define CSNEED 0xF003u
#define XR 1
#define PS0 1
#define PS1 3
#define PSW 0
#define SD 1000
#define QORD 4
#define KSPLIT 12
#define KEEP 16
#define NJ 3
#define KSL 1000
#define PSL 0
#define KVS 12
#define D2 2000
#define D3 1500
#define G0 50
#define G3 50
#define G1 0
#define G4 0
#define MAP 3
#define PMAP 0x76321450u
#define PW 1
#define PN2 0
#define XA 3
#define XS 1
#define BBO 1
#define SV 0
#define UK 1
#define CP 500
#define CD 0
#define S0 500
#define NS 2
#define XO 0
#define SW 2
#define SA 2
#define SB_ 1
#define KB 8
#define PNX 2
#define PNO 2
#define DEFER 3
#define DEFL 2
#define TSK 3
#define TSL 3
constexpr int NTHREADS = 384;

struct Params {
  CUtensorMap mx;
  CUtensorMap mw[3];
  CUtensorMap mwo[2];
  CUtensorMap mcs[2];
  CUtensorMap mwphi;
  uint4* out;
};

#define XBUF(L) 1
__device__ __align__(256) uint4 g_img[XBUF(3) + 1][16][16][1024];
__device__ __align__(256) uint4 g_wf[2][8][16][1024];
__device__ __align__(256) uint4 g_stats[16][2][8][32];
__device__ __align__(256) uint4 g_halo[16][8][2][256];
__device__ __align__(256) float g_cs[2][2][3072];
__device__ __align__(256) uint4 g_kvpart[8][16][2][544];
__device__ __align__(256) uint4 g_kvfin[8][16][80];
__device__ __align__(256) unsigned g_xflag[4][2][16][32];
__device__ __align__(256) unsigned g_oflag[4][2][16][32];
__device__ __align__(256) unsigned g_hflag[2][16][8][32];
__device__ __align__(256) unsigned g_kvfflag[2][8][2][32];
__device__ __align__(256) unsigned g_csflag[2][8][32];
__device__ __align__(256) unsigned g_kflag[8][32];
__device__ unsigned g_ctr;
__device__ __forceinline__ unsigned vblock() {
  unsigned s;
  asm volatile("mov.u32 %0, %%smid;" : "=r"(s));
  const unsigned r = s & 1;
  s >>= 1;
  const unsigned t = s - 32, q = (t * 37) >> 8;
  const unsigned hi = s < 60 ? 12 + (t - 7 * q) * 8 + q : (s < 62 ? s + 4 : s - 58);
  unsigned b = 2 * (s < 32 ? (s & 7) * 8 + (s >> 3) : hi) + r;
  if (b < 128) b = (b & 15) | ((PMAP >> ((b >> 4) * 4)) & 7) << 4;
  if (s >= 62) b = 8 + 4 * r + s - 62;
  return __shfl_sync(0xffffffffu, b, 0);
}
#define TS(who, id) do {} while (0)
#define TSW(id) do {} while (0)

#define TSMASK 0xFFFF
#define TSL_(a) do { if ((TSMASK >> (a)) & 1) TSW((a) + L * 12); } while (0)
__device__ __forceinline__ int cta_m(unsigned b) { return ((b >> 2) & 12) | (b & 3); }
__device__ __forceinline__ int cta_j(unsigned b) { return ((b >> 2) & 3) | ((b >> 4) & 4); }
struct Ring { uint32_t s, ph; };
template <int N> __device__ __forceinline__ void adv(Ring& r) { if (++r.s == N) { r.s = 0; r.ph ^= 1; } }
template <int N> __device__ __forceinline__ void rewind2(Ring& r) { if (r.s < 2) { r.s += N - 2; r.ph ^= 1; } else r.s -= 2; }
__device__ __forceinline__ int other_tile(int t, int j) { return (t == (j | 4) ? 7 : t) ^ (~j & 4); }
__device__ __forceinline__ int q_order(int i, int j) { return 2 * (i >= 14 ? j : other_tile(i >> 1, j)) + (i & 1); }
__device__ __forceinline__ int o_order(int i, int j) {
  if (i < 2) return 2 * j + i;
  const int odd = i >= 9;
  return 2 * other_tile(i - 2 - 7 * odd, j) + odd;
}
__device__ __forceinline__ int kv_order(int i, int j, int L) { return L > 0 ? o_order(i, j) : (i + 14 + 2 * (j & 4)) & 15; }

__device__ __forceinline__ unsigned poll_flags(const unsigned* f, int n, unsigned need, unsigned tag) {
  const int lane = threadIdx.x & 31;
  unsigned mask; int it = 0;
  do {
    unsigned v = lane < n ? ld_flag(f + lane) : 0u;
    mask = __ballot_sync(0xffffffffu, lane < n && v == tag);
    if (++it > (1 << 22)) __trap();
  } while ((mask & need) != need);
  fence_async_global();
  return mask;
}
template <bool WAIT = true>
__device__ __forceinline__ unsigned get_tag(uint32_t sb) {
  if (WAIT) mbar_wait(sb + BAR_EPOCH, 0);
  unsigned t; asm volatile("ld.shared.u32 %0, [%1];" : "=r"(t) : "r"(sb + OFF_EPOCH) : "memory");
  return t;
}

__device__ __forceinline__ int lane_id() { int l; asm volatile("mov.u32 %0, %%laneid;" : "=r"(l)); return l; }
__device__ __forceinline__ unsigned seq4(unsigned tag, int L) { return 8u | ((tag & 1u) << 2) | (unsigned)L; }
constexpr float LOG2E = 1.4426950408889634f;

__device__ __forceinline__ void sched_fence(uint32_t sb) { mbar_wait(sb + BAR_EPOCH, 0); }
__device__ __forceinline__ void bb_fence(int never) { while (never < 0) never = ld_flag(&g_ctr + never); }
__device__ __forceinline__ void bb_keep(const float* v, int never) {
  while (never < 0) {
#pragma unroll
    for (int q = 0; q < 32; q += 4) sts128(never + q * 4, __float_as_uint(v[q]), __float_as_uint(v[q + 1]), __float_as_uint(v[q + 2]), __float_as_uint(v[q + 3]));
    never = ld_flag(&g_ctr + never);
  }
}
constexpr uint32_t HA128 = 0x40000040u, HA64 = 0x80000040u;
struct Ctx {
  static constexpr uint32_t sb = SB;
  uint32_t ab, da0;
  int w, warp, lane, g, c;
  int goff;
  __device__ __forceinline__ int m() const { return goff >> 14; }
  __device__ __forceinline__ int j() const { return (goff >> 4) & 7; }
  bool elected;
  Ring ra, rb;
  uint32_t pa, pb;
  uint32_t ha, k2;
  uint32_t mrow, mxor, mhi;
  __device__ __forceinline__ uint32_t aslot(uint32_t s) const { return ab + s * SLOT; }
  __device__ __forceinline__ uint32_t fullA(uint32_t s) const { return sb + BAR_FULLA + s * 8; }
  __device__ __forceinline__ uint32_t fullB(uint32_t s) const { return sb + BAR_FULLB + s * 8; }
  __device__ __forceinline__ void releaseA(uint32_t s) const { if (elected) mbar_arrive(sb + BAR_EMPTYA + s * 8); }
  __device__ __forceinline__ void releaseB(uint32_t s) const { if (elected) mbar_arrive(sb + BAR_EMPTYB + s * 8); }
  __device__ __forceinline__ uint32_t maddr(uint32_t tile, uint32_t ch) const { return tile + mrow + (((ch + mhi) ^ mxor) << 4); }
  __device__ __forceinline__ uint32_t oo() const { return warp * 128 + g * 4 + (c ^ (g >> 1)); }
  __device__ __forceinline__ uint4* img(int b, int hp) const { return &g_img[b][m()][2 * j() + hp][w * 512 + oo()]; }
  __device__ __forceinline__ uint32_t held(int i) const { return ra.s + i < 2 ? ra.s + i + NA - 2 : ra.s + i - 2; }
};

template <int N, bool FIRST, bool O = true>
__device__ __forceinline__ void gemm_issue(float (&acc)[N / 2], Ctx& x, bool ready = false) {
  if (!ready) {
    if (N == 256) mbar_wait3(x.fullA(x.ra.s), x.ra.ph, x.fullB(x.rb.s), x.rb.ph);
    else mbar_wait2(x.fullA(x.ra.s), x.ra.ph, x.fullB(x.rb.s), x.rb.ph);
  }
  const uint32_t da = x.da0 + x.ra.s * (SLOT / 16), db = desc_lo(SB + OFF_B, 8192) + x.rb.s * (SLOT / 16);
  wgmma_fence();
#pragma unroll
  for (int k = 0; k < 4; k++) {
    const uint32_t a = da + (k >> 1) * (O ? 32 : x.k2) + (k & 1) * 2, ha = O ? HA64 : x.ha;
    if constexpr (N == 256) wgmma_ss_n256(acc, a, ha, db + 128 * k, !(FIRST && k == 0));
    else wgmma_ss_n128(acc, a, ha, db + 128 * k, !(FIRST && k == 0));
  }
  wgmma_commit();
}
template <int N>
__device__ __forceinline__ void gemm_next(Ctx& x) {
  x.pa = x.ra.s; x.pb = x.rb.s;
  if (N == 256) x.rb.s++;
  adv<NA>(x.ra); adv<NB>(x.rb);
}
template <int N>
__device__ __forceinline__ void gemm_release(Ctx& x, bool relA) {
  if (relA) x.releaseA(x.pa);
  x.releaseB(x.pb);
  if (N == 256) x.releaseB(x.pb + 1);
}
template <int N>
__device__ __forceinline__ void gemm_retire(Ctx& x, bool relA) { wgmma_wait<1>(); gemm_release<N>(x, relA); gemm_next<N>(x); }
template <bool O = true>
__device__ __forceinline__ void gemm_run(float (&acc)[64], Ctx& x, int n, int hold, int n4 = 0) {
  bool ready = false;
#pragma unroll 1
  for (; n > 0; n--) {
    gemm_issue<128, false, O>(acc, x, ready);
    const uint32_t pa = x.pa, pb = x.pb;
    gemm_next<128>(x);
    ready = mbar_probe2(x.fullA(x.ra.s), x.ra.ph, x.fullB(x.rb.s), x.rb.ph);
    wgmma_wait<1>();
    if (n > hold) x.releaseA(pa);
    x.releaseB(pb);
  }
}
__device__ __forceinline__ void gemm_end(float (&acc)[64], Ctx& x) { wgmma_wait<0>(); fence_regs(acc); gemm_release<128>(x, false); }

__device__ __forceinline__ void rows_load(uint4* r, uint32_t tile, const Ctx& x) {
#pragma unroll
  for (int q = 0; q < 4; q++) {
    const uint32_t row = x.warp * 16 + 4 * q + (x.lane >> 3);
    lds128(tile + row * 128 + (((x.lane & 7) ^ (row & 7)) << 4), r[q].x, r[q].y, r[q].z, r[q].w);
  }
}
__device__ __forceinline__ void rows_store(const uint4* r, uint4* g, const Ctx& x) {
  g += (x.warp * 16 + (x.lane >> 3)) * 256 + (x.lane & 7);
#pragma unroll
  for (int q = 0; q < 4; q++) g[q * 1024] = r[q];
}
__device__ __forceinline__ void publish(int id, const Ctx& x) { __syncwarp(); if (x.lane == 0) mbar_arrive(x.sb + BAR_SIGP + id * 8); }
__device__ __forceinline__ void img_store(const uint4 (&r)[4], uint4* g) {
#pragma unroll
  for (int q = 0; q < 4; q++) { if (SV & 2) st_v4(g + q * 32, r[q].x, r[q].y, r[q].z, r[q].w); else g[q * 32] = r[q]; }
}
__device__ __forceinline__ void img_sts(const uint4 (&r)[4], uint32_t tile, const Ctx& x) {
#pragma unroll
  for (int q = 0; q < 4; q++) sts128(tile + x.oo() * 16 + q * 512, r[q].x, r[q].y, r[q].z, r[q].w);
}
__device__ __forceinline__ void img_load(uint32_t (&v)[16], uint32_t tile, const Ctx& x) {
#pragma unroll
  for (int q = 0; q < 4; q++) lds128(tile + x.oo() * 16 + q * 512, v[4 * q], v[4 * q + 1], v[4 * q + 2], v[4 * q + 3]);
}
__device__ __forceinline__ void img_unpack(float* a, const uint32_t (&v)[16]) {
#pragma unroll
  for (int q = 0; q < 16; q++) { a[4 * (q & 7) + 2 * (q >> 3)] = lo16(v[q]); a[4 * (q & 7) + 2 * (q >> 3) + 1] = hi16(v[q]); }
}

template <int N>
__device__ __forceinline__ void stats_acc(const float* a, float (&t)[4]) {
#pragma unroll
  for (int i = 0; i < N; i++) { t[i & 2] += a[i]; t[(i & 2) + 1] = fmaf(a[i], a[i], t[(i & 2) + 1]); }
}
__device__ __forceinline__ void stats_send(float (&t)[4], int L, const Ctx& x) {
  const unsigned seq = seq4(get_tag<false>(x.sb), L);
#pragma unroll
  for (int q = 0; q < 4; q++) t[q] = qsum(t[q]);
  if (x.c == 0) st_pkt(&g_stats[x.m()][x.w][x.j()][x.warp * 8 + x.g], __float_as_uint(t[0]), __float_as_uint(t[1]), __float_as_uint(t[2]), (__float_as_uint(t[3]) & ~15u) | seq);
}
__device__ __forceinline__ void out_epilogue(const float (&acc)[64], uint4 (&r1)[4], float (&t)[4], uint4* g, int L, Ctx& x) {
  const uint32_t t0 = x.aslot(x.ra.s), t1 = x.aslot(x.ra.s + 1 == NA ? 0 : x.ra.s + 1);
  if (L == 3) {
#pragma unroll
    for (int p = 0; p < 8; p++) {
      stsm4(x.maddr(p < 4 ? t0 : t1, (p & 3) * 2), pack2(acc[8 * p], acc[8 * p + 1]), pack2(acc[8 * p + 2], acc[8 * p + 3]),
            pack2(acc[8 * p + 4], acc[8 * p + 5]), pack2(acc[8 * p + 6], acc[8 * p + 7]));
      if ((p & 3) == 3) { uint4 r[4]; __syncwarp(); rows_load(r, p < 4 ? t0 : t1, x); rows_store(r, g + (p >> 2) * 8, x); }
    }
  } else {
    auto pack16 = [&](uint4 (&r)[4], const float* a) {
#pragma unroll
      for (int q = 0; q < 4; q++) { const float* u = a + 16 * (q & 1) + (q & 2); r[q] = make_uint4(pack2(u[0], u[1]), pack2(u[4], u[5]), pack2(u[8], u[9]), pack2(u[12], u[13])); }
    };
    uint4 r0[4];
    pack16(r0, acc);
    img_store(r0, x.img(XBUF(L + 1), 0));
    publish(2, x);
    img_sts(r0, t0, x);
    if (BBO) bb_fence(x.goff); else sched_fence(x.sb);
    pack16(r1, acc + 32);
    img_sts(r1, t1, x);
    float u[4] = {0.f, 0.f, 0.f, 0.f}, v[4] = {0.f, 0.f, 0.f, 0.f};
    stats_acc<32>(acc, v); stats_acc<32>(acc + 32, u);
#pragma unroll
    for (int q = 0; q < 4; q++) t[q] = u[q] + v[q];
    mbar_wait2(x.fullB(x.rb.s), x.rb.ph, x.fullB(x.rb.s + 1), x.rb.ph);
    fence_async_smem();
    asm volatile("bar.sync %0, %1;" ::"r"(L == 1 ? x.w + 1 : 3), "r"(L == 1 ? 128 : 256) : "memory");
  }
}

struct Stats { float rstd0, rstd1; };
__device__ __forceinline__ Stats load_stats(int half, const Ctx& x) {
  const float2 u = lds64f(x.sb + OFF_MR + half * 256 + (x.warp * 8 + x.g) * 8);
  return {u.x, u.y};
}

template <int NK>
__device__ __forceinline__ void hedgehog_scale(float* t, const Stats& st, const uint32_t* keep) {
#pragma unroll
  for (int q = 0; q < 16; q++) t[q] *= ((q & 2) ? st.rstd1 : st.rstd0) * LOG2E;
  float m[4];
#pragma unroll
  for (int q = 0; q < 4; q++) m[q] = fmaxf(fmaxf(fabsf(t[4 * q]), fabsf(t[4 * q + 1])), fmaxf(fabsf(t[4 * q + 2]), fabsf(t[4 * q + 3])));
  if (__builtin_expect(__any_sync(0xffffffffu, fmaxf(fmaxf(m[0], m[1]), fmaxf(m[2], m[3])) > 58.f), 0)) {
    float z[16 + NK];
#pragma unroll
    for (int q = 0; q < 16 + NK; q++) z[q] = q < 16 ? t[q & 15] : __uint_as_float(keep[q & 15]);
#pragma unroll 1
    for (int r = 0; r < 4; r += 2) {
      float hi = -INFINITY, lo = INFINITY;
#pragma unroll 1
      for (int i = 0; i < 16; i++) {
        const int k = (i & 6) * 2 + (i & 1) + r;
        const float v = z[k];
        if (i < 8) { hi = fmaxf(hi, v); lo = fminf(lo, v); }
        else z[k] = v - fminf(fmaxf(v, lo), hi);
        if (i == 7) {
#pragma unroll 1
          for (int d = 1; d <= 2; d++) { hi = fmaxf(hi, __shfl_xor_sync(0xffffffffu, hi, d)); lo = fminf(lo, __shfl_xor_sync(0xffffffffu, lo, d)); }
          const float mid = 0.5f * hi + 0.5f * lo;
          hi = fmaxf(hi - 58.f, mid); lo = fminf(lo + 58.f, mid);
        }
      }
    }
#pragma unroll
    for (int q = 0; q < 16; q++) t[q] = z[q];
  }
}
__device__ __forceinline__ void dual_exp(const float* t, uint32_t (&f)[18], int never) {
  float e[KSPLIT];
#pragma unroll
  for (int q = 0; q < KSPLIT; q++) e[q] = ex2(q < 16 ? t[q] : -t[q & 15]);
  while (never < 0) {
#pragma unroll
    for (int i = 0; i < KSPLIT; i += 4) asm volatile("ld.shared.v4.f32 {%0,%1,%2,%3}, [%4];" : "=f"(e[i]), "=f"(e[i + 1]), "=f"(e[i + 2]), "=f"(e[i + 3]) : "r"(never + i) : "memory");
    never += __float_as_int(e[0]);
  }
#pragma unroll
  for (int q = 0; q < KSPLIT; q += 2) f[q >> 1] = pack2(e[q], e[q + 1]);
#pragma unroll
  for (int q = KSPLIT; q < 32; q += 2) f[q >> 1] = q < 16 ? pack2(ex2(t[q]), ex2(t[q + 1])) : pack2(ex2(-t[q & 15]), ex2(-t[(q & 15) + 1]));
#pragma unroll
  for (int sg = 0; sg < 2; sg++) {
    const uint32_t* u = f + 8 * sg;
    const uint32_t a = add2(add2(u[0], u[2]), add2(u[4], u[6])), b = add2(add2(u[1], u[3]), add2(u[5], u[7]));
    f[16 + sg] = add2(__byte_perm(a, b, 0x5410), __byte_perm(a, b, 0x7632));
  }
}
__device__ __forceinline__ void dual_exp_rcp(const float* t, uint32_t (&f)[16]) {
#pragma unroll
  for (int q = 0; q < 8; q++) {
    const float a = ex2(t[2 * q]), b = ex2(t[2 * q + 1]), r = rcp(a * b);
    f[q] = pack2(a, b); f[8 + q] = pack2(r * b, r * a);
  }
}
__device__ __forceinline__ void cta_bar() { asm volatile("bar.sync 3, 256;" ::: "memory"); }

template <int N> __device__ __forceinline__ void pin(const uint32_t* v, uint32_t addr) {
#pragma unroll
  for (int i = 0; i < N; i += 4)
    asm volatile("{\n.reg .pred p;\nsetp.eq.u32 p, %0, 0;\n@p st.shared.v4.u32 [%0], {%1,%2,%3,%4};\n}" ::"r"(addr), "r"(v[i]), "r"(v[i + 1]), "r"(v[i + 2]), "r"(v[i + 3]) : "memory");
}

__device__ __forceinline__ void consumer(const Params& P, uint32_t sb, int w, unsigned vb) {
  Ctx x;
  x.w = w;
  x.ab = sb + OFF_A + w * 8192; x.da0 = desc_lo(SB + OFF_A, 16) + w * 512;
  x.lane = threadIdx.x & 31; x.warp = __shfl_sync(0xffffffffu, (threadIdx.x >> 5) & 3, 0); x.g = x.lane >> 2; x.c = x.lane & 3;
  x.goff = (cta_m(vb) * 128 + w) * 128 + cta_j(vb) * 16;
  asm volatile("" : "+r"(x.goff));
  x.elected = (threadIdx.x & 127) == 0;
  x.ra = {0, 0}; x.rb = {0, 0}; x.pa = x.pb = 0;
  {
    const uint32_t row = x.warp * 16 + (x.lane & 15);
    x.mrow = row * 128; x.mxor = row & 7; x.mhi = x.lane >> 4;
  }
  const int goff = x.goff;
  uint4 r1[4];
  float ts[4] = {0.f, 0.f, 0.f, 0.f};
#pragma unroll
  for (int i = 0; i < 4; i++) r1[i] = make_uint4(0, 0, 0, 0);
  TSW(0);
  mbar_wait3(x.fullA(0), 0, x.fullB(0), 0);
#pragma unroll 1
  for (int L = 0; L < 4; L++) {
    float acc[64];
    constexpr uint32_t dcs = desc_lo(SB + OFF_CS, 0);
    if ((L & 1) == 0) {
    float kv[128];
    x.ha = L ? HA64 : HA128; x.k2 = L ? 32 : 4;
    gemm_issue<256, true, false>(kv, x, true); gemm_next<256>(x);
    {
      int i = 1;
#pragma unroll 1
      for (int seg = L ? NS - 1 : 0; seg <= NS; seg++) {
        const int end = seg < NS ? (L == 0 ? 3 + SA * ((x.j() + SW * w) & 3) + SB_ * seg : XA + 1) : 14 + L;
#pragma unroll 1
        do {
          gemm_issue<256, false, false>(kv, x);
          gemm_retire<256>(x, true);
          i++;
          if (i == 5) TSL_(8);
          if (i == 11) TSL_(10);
        } while (i != end);
        if (seg < NS && L == 0) {
          uint32_t v[16];
          float a[32];
#pragma unroll
          for (int q = 0; q < 4; q++) ldsm4(x.maddr(x.aslot(x.pa), 2 * q), reinterpret_cast<uint32_t (&)[4]>(v[4 * q]));
#pragma unroll
          for (int q = 0; q < 16; q++) { a[2 * q] = lo16(v[q]); a[2 * q + 1] = hi16(v[q]); }
          stats_acc<32>(a, ts);
          fence_regs(ts);
          wg_bar(w);
        }
        if (seg == NS - 1) {
          if (L > 0) { img_store(r1, x.img(XBUF(L), 1)); publish(3, x); }
          mbar_wait(sb + BAR_EPOCH, 0);
          stats_send(ts, L, x);
        }
      }
    }
      const Ring kt = x.ra;
      if (L == 0) adv<NA>(x.ra);
#pragma unroll 1
      for (int h = L; h < 2; h++) {
        float d[16];
        mbar_wait2(x.fullA(kt.s), kt.ph, sb + BAR_WPHI, 0);
        wgmma_fence();
#pragma unroll
        for (int q = 0; q < 2; q++) wgmma_ss_n32(d, x.da0 + kt.s * (SLOT / 16) + h * 4 + q * 2, desc_lo(SB + OFF_S + 4096, 512) + w * 256 + h * 128 + q * 64, q);
        wgmma_commit();
        gemm_issue<256, false, false>(kv, x);
        gemm_retire<256>(x, true);
        if (h) x.releaseA(kt.s);
        fence_regs(d);
        uint4* dst = &g_wf[1][x.j()][x.m()][w * 512 + (x.warp * 16 + x.g) * 8 + ((h * 4 + x.c) ^ x.g)];
        dst[0] = make_uint4(pack2(d[0], d[1]), pack2(d[4], d[5]), pack2(d[8], d[9]), pack2(d[12], d[13]));
        dst[64] = make_uint4(pack2(d[2], d[3]), pack2(d[6], d[7]), pack2(d[10], d[11]), pack2(d[14], d[15]));
      }
      const uint32_t dm = desc_lo(SB + OFF_MA, 0) + w * 64;
      mbar_wait2(sb + BAR_STAT, 0, sb + BAR_CS, 0);
      wgmma_fence();
      wgmma_r1_n256(kv, dm, dcs + 96, 1);
      wgmma_commit();
      const Stats st = load_stats(w, x);
      if (PW & 1) mbar_wait2(x.fullA(x.ra.s), x.ra.ph, x.fullB(x.rb.s), x.rb.ph);
      wgmma_wait<0>();
      fence_regs(kv);
      gemm_release<256>(x, true);
      TSL_(2);
      uint32_t P0[32], P1[32], PH[32];
#pragma unroll
      for (int t = 0; t < 16; t++) { P0[t] = pack2(kv[4 * t] * st.rstd0, kv[4 * t + 1] * st.rstd0); P1[t] = pack2(kv[4 * t + 2] * st.rstd1, kv[4 * t + 3] * st.rstd1); }
      pin<16>(P0, x.mrow + 16);
      {
#pragma unroll
        for (int q = 0; q < 4; q++) sts128((x.warp < 3 ? sb + OFF_T + w * 12288 + x.warp * 4096 : sb + OFF_S + 16384 + w * 2048) + x.lane * 16 + q * 512, P1[4 * q], P1[4 * q + 1], P1[4 * q + 2], P1[4 * q + 3]);
      }
      wgmma_fence();
      wgmma_r1_n128(acc, dm, dcs, 0);
      gemm_issue<128, false, false>(acc, x, PW & 1); gemm_next<128>(x);
      TSL_(3);
#pragma unroll
      for (int s = 0; s < 4; s++) {
#pragma unroll
        for (int t = 16 + 8 * (s & 1); t < 24 + 8 * (s & 1); t++) {
          if (s < 2) P1[t] = movm(pack2(kv[4 * t + 2] * st.rstd1, kv[4 * t + 3] * st.rstd1));
          else P0[t] = movm(pack2(kv[4 * t] * st.rstd0, kv[4 * t + 1] * st.rstd0));
        }
        if (s < 3) { gemm_issue<128, false, false>(acc, x); gemm_retire<128>(x, true); }
        if (s == 1) {
          if (x.warp < 3) {
#pragma unroll
            for (int q = 4; q < 8; q++) sts128(sb + OFF_T + w * 12288 + x.warp * 4096 + x.lane * 16 + q * 512, P1[4 * q], P1[4 * q + 1], P1[4 * q + 2], P1[4 * q + 3]);
          } else {
            uint4* dst = &g_halo[x.m()][x.j()][w][x.lane];
#pragma unroll
            for (int q = 0; q < 8; q++) dst[q * 32] = make_uint4(P1[4 * q], P1[4 * q + 1], P1[4 * q + 2], P1[4 * q + 3]);
          }
          publish(4, x);
          gemm_issue<128, false, false>(acc, x);
          gemm_retire<128>(x, true);
        }
      }
      TSL_(4);
      gemm_run<false>(acc, x, 10, 0);
      gemm_issue<128, false, false>(acc, x);
      {
        wg_bar(w);
        uint32_t tr = sb + OFF_T + w * 12288 + (x.warp - 1) * 4096;
        if (x.warp == 0) {
          tr = x.m() > 0 ? sb + OFF_S + 8192 + w * 4096 : tr + 4096;
          if (x.m() > 0) mbar_wait(sb + BAR_HALO, L >> 1);
        }
#pragma unroll
        for (int q = 0; q < 8; q++) lds128(tr + x.lane * 16 + q * 512, PH[4 * q], PH[4 * q + 1], PH[4 * q + 2], PH[4 * q + 3]);
      }
      gemm_retire<128>(x, false);
      gemm_end(acc, x);
      TSL_(5);
      const bool first = (x.m() == 0) && (x.warp == 0);
      const bool hi0 = 2 * x.c > x.g, hi1 = 2 * x.c + 1 > x.g;
      const uint32_t mhi = (hi0 ? 0xFFFFu : 0u) | (hi1 ? 0xFFFF0000u : 0u);
      const float sc0 = st.rstd0 * (0.17677669529663687f * LOG2E), sc1 = st.rstd1 * (0.17677669529663687f * LOG2E);
#pragma unroll
      for (int hp = 0; hp < 2; hp++) {
        const uint32_t tile = x.aslot(x.held(hp));
        uint32_t px[2], py[2];
        float s[2][3][4];
#pragma unroll
        for (int u = 0; u < 2; u++) {
#pragma unroll
          for (int q = 0; q < 12; q++) s[u][q >> 2][q & 3] = 0.f;
#pragma unroll
          for (int ks = 0; ks < 2; ks++) {
            const int t = 8 * hp + 4 * u + 2 * ks;
            const uint32_t a0 = pack2(acc[4 * t], acc[4 * t + 1]), a1 = pack2(acc[4 * t + 2], acc[4 * t + 3]);
            const uint32_t a2 = pack2(acc[4 * t + 4], acc[4 * t + 5]), a3 = pack2(acc[4 * t + 6], acc[4 * t + 7]);
            mma16816(s[u][0], a0, a1, a2, a3, PH[t], PH[t + 1]);
            mma16816(s[u][1], a0, a1, a2, a3, P0[t], P0[t + 1]);
            mma16816(s[u][2], a0, a1, a2, a3, P1[t], P1[t + 1]);
          }
        }
        float e[2][4], r[2][2];
#pragma unroll
        for (int u = 0; u < 2; u++) {
          e[u][0] = (hi0 ? s[u][0][0] : s[u][1][0]) * sc0; e[u][1] = (hi1 ? s[u][0][1] : s[u][1][1]) * sc0;
          e[u][2] = (hi0 ? s[u][1][2] : s[u][2][2]) * sc1; e[u][3] = (hi1 ? s[u][1][3] : s[u][2][3]) * sc1;
          if (first) { if (hi0) e[u][0] = -1e30f; if (hi1) e[u][1] = -1e30f; }
          r[u][0] = fmaxf(e[u][0], e[u][1]); r[u][1] = fmaxf(e[u][2], e[u][3]);
        }
#pragma unroll
        for (int d = 1; d <= 2; d++)
#pragma unroll
          for (int q = 0; q < 4; q++) r[q >> 1][q & 1] = fmaxf(r[q >> 1][q & 1], __shfl_xor_sync(0xffffffffu, r[q >> 1][q & 1], d));
#pragma unroll
        for (int u = 0; u < 2; u++) {
#pragma unroll
          for (int q = 0; q < 4; q++) e[u][q] = ex2(e[u][q] - r[u][q >> 1]);
          r[u][0] = e[u][0] + e[u][1]; r[u][1] = e[u][2] + e[u][3];
        }
#pragma unroll
        for (int d = 1; d <= 2; d++)
#pragma unroll
          for (int q = 0; q < 4; q++) r[q >> 1][q & 1] += __shfl_xor_sync(0xffffffffu, r[q >> 1][q & 1], d);
#pragma unroll
        for (int u = 0; u < 2; u++) {
          const float rx = rcp(r[u][0]), ry = rcp(r[u][1]);
          px[u] = pack2(e[u][0] * rx, e[u][1] * rx); py[u] = pack2(e[u][2] * ry, e[u][3] * ry);
        }
        uint32_t o[8][2];
        uint4 ro[4];
#pragma unroll
        for (int q = 0; q < 8; q++) {
          float d[4] = {0.f, 0.f, 0.f, 0.f};
          const int t = 16 + 8 * hp + q, u = q >> 2;
          mma16816(d, px[u] & mhi, 0u, px[u] & ~mhi, py[u] & mhi, PH[t], P0[t]);
          mma1688(d, 0u, py[u] & ~mhi, P1[t]);
          o[q][0] = pack2(d[0], d[1]); o[q][1] = pack2(d[2], d[3]);
        }
#pragma unroll
        for (int q = 0; q < 4; q++) ro[q] = make_uint4(o[4 * (q & 1)][q >> 1], o[4 * (q & 1) + 1][q >> 1], o[4 * (q & 1) + 2][q >> 1], o[4 * (q & 1) + 3][q >> 1]);
        img_store(ro, x.img(0, hp));
        publish(hp, x);
        if ((UK & 2) && hp) bb_keep(acc, x.goff);
        uint32_t xr[16];
        if (L) img_load(xr, tile, x);
        else {
#pragma unroll
          for (int q = 0; q < 4; q++) {
            uint32_t v[4];
            ldsm4(x.maddr(tile, 2 * q), v);
            xr[2 * q] = v[0]; xr[8 + 2 * q] = v[1]; xr[2 * q + 1] = v[2]; xr[9 + 2 * q] = v[3];
          }
          __syncwarp();
        }
        img_sts(ro, tile, x);
        img_unpack(acc + 32 * hp, xr);
      }
    } else {
      float kv[128];
      float (&kv0)[64] = reinterpret_cast<float (&)[64]>(kv[0]);
      float (&kv1)[64] = reinterpret_cast<float (&)[64]>(kv[64]);
      auto mma8 = [&](uint32_t as, uint32_t bs, int i, bool fence) {
        const uint32_t da = desc_lo(SB + OFF_A, 16) + as * (SLOT / 16), db = desc_lo(SB + OFF_B, 8192) + bs * (SLOT / 16);
        if (fence) wgmma_fence();
#pragma unroll
        for (int k = 0; k < 4; k++) {
          wgmma_ss_n128(kv0, da + (k >> 1) * 32 + (k & 1) * 2, HA64, db + 128 * k, i + k);
          wgmma_ss_n128(kv1, da + 512 + (k >> 1) * 32 + (k & 1) * 2, HA64, db + 128 * k, i + k);
        }
        wgmma_commit();
      };
      constexpr uint32_t dm = desc_lo(SB + OFF_MB, 0);
      auto relB = [&](uint32_t s) { mbar_arrive_n(sb + BAR_EMPTYB + s * 8, 2); };
      auto skip = [&]() {
#pragma unroll
        for (int q = 0; q < 6 - NJ; q++) adv<NA>(x.ra);
        x.rb.s = w ? (2 + NJ) % 6 : 4;
        if (!w && NJ < 4) x.rb.ph ^= 1;
      };
      static_assert(NA == 5 && NB == 6, "ring arithmetic");
      mma8(x.ra.s, x.rb.s + w, 0, true);
      gemm_next<256>(x);
#pragma unroll 1
      for (int i = 1; i < NJ; i++) {
        mbar_wait2(x.fullA(x.ra.s), x.ra.ph, x.fullB(x.rb.s + w), x.rb.ph);
        mma8(x.ra.s, x.rb.s + w, 1, true);
        if (!XO && i == XR) { img_store(r1, x.img(XBUF(L), 1)); publish(3, x); }
        if (!XO && i == XS) stats_send(ts, L, x);
        wgmma_wait<1>();
        if (x.elected) { x.releaseA(x.pa); relB(x.pb + w); }
        gemm_next<256>(x);
        if (XO && i == XR) { img_store(r1, x.img(XBUF(L), 1)); publish(3, x); stats_send(ts, L, x); }
      }
      if (w) {
        wgmma_wait<0>();
        if (x.elected) { x.releaseA(x.pa); relB(x.pb + 1); }
        skip();
        asm volatile("bar.sync 7, 256;" ::: "memory");
      }
      TSL_(8);
      {
        const int t = lane_id() + 32 * x.warp;
        uint32_t mask = t < 2 ? ((w ? (t ? 0xFF3Fu : 0x3FFFu) : 0xFFFFu) >> (NJ - 1)) & (w ? ~1u : ~0u) : 0u, cnt = 1 + t;
        bool ready = false;
#pragma unroll 1
        for (int i = NJ; i < 16; i++) {
          if (!ready) mbar_wait2(x.fullA(x.ra.s), x.ra.ph, x.fullB(x.rb.s), x.rb.ph);
          mma8(x.ra.s, x.rb.s, 1, true);
          const uint32_t bar = sb + (t ? BAR_EMPTYB + x.pb * 8 : BAR_EMPTYA + x.pa * 8);
          gemm_next<128>(x);
          if (w && (i | 4) == 15) x.rb.s = 4;
          ready = mbar_probe2(x.fullA(x.ra.s), x.ra.ph, x.fullB(x.rb.s), x.rb.ph);
          wgmma_wait<1>();
          if (mask & 1) mbar_arrive_n(bar, cnt);
          mask >>= 1; cnt = 2;
          if (i == 8 && w) asm volatile("bar.arrive 9, 256;" ::: "memory");
          if (i == 9) TSL_(10);
        }
        mbar_wait2(sb + BAR_STAT, 1, sb + BAR_CS + 8, 0);
        wgmma_fence();
        wgmma_r1_n128(kv0, dm, dcs + 96 + 96 * w, 1);
        wgmma_r1_n128(kv1, dm + 64, dcs + 96 + 96 * w, 1);
        wgmma_commit();
        if (w == 0) asm volatile("bar.arrive 7, 256;" ::: "memory");
        wgmma_wait<1>();
        if (mask & 1) mbar_arrive_n(sb + (t ? BAR_EMPTYB + x.pb * 8 : BAR_EMPTYA + x.pa * 8), 2);
      }
      const Stats s0 = load_stats(0, x), s1 = load_stats(1, x), st = w ? s1 : s0;
      if (w == 0) skip();
      const uint32_t h0 = x.held(0), h1 = x.held(1);
      auto vreg = [&](int ks) { return ks < 6 ? OFF_A + (ks < 3 ? h0 * SLOT : h1 * SLOT - 15360) + ks * 5120 : OFF_S + 2048 + ks * 5120; };
      uint32_t tV[2], uu[4];
#pragma unroll
      for (int hf = 0; hf < 2; hf++) {
        tV[hf] = sb + vreg(4 * hf + x.warp) + ((x.lane >> 3) & 1) * 2560 + (x.lane & 7) * 16 + x.mhi * 128;
        const float i0 = rcp(hf ? s1.rstd0 : s0.rstd0), i1 = rcp(hf ? s1.rstd1 : s0.rstd1);
        const uint32_t h = pack2(i0, i1);
        uu[2 * hf] = pack2(lo16(h), i0 - lo16(h)); uu[2 * hf + 1] = pack2(hi16(h), i1 - hi16(h));
        asm volatile("" : "+r"(tV[hf]), "+r"(uu[2 * hf]), "+r"(uu[2 * hf + 1])::"memory");
      }
      wgmma_wait<0>();
      fence_regs(kv);
      TSL_(2);
      if (w == 0) {
        uint32_t f[2][18], ad[4];
#pragma unroll
        for (int q = 0; q < 18; q++) f[1][q] = 0u;
#pragma unroll
        for (int q = 0; q < 4; q++) ad[q] = x.maddr(sb + OFF_S, 2 * q);
        auto norm = [&](int un) {
          uint32_t* u = f[un & 1];
          const Stats& sn = (un & 2) ? s1 : s0;
#pragma unroll
          for (int sg = 0; sg < 2; sg++) {
            uint32_t v = u[16 + sg];
            v = add2(v, __shfl_xor_sync(0xffffffffu, v, 1)); v = add2(v, __shfl_xor_sync(0xffffffffu, v, 2));
            const float a = rcp(lo16(v)) * sn.rstd0, b = rcp(hi16(v)) * sn.rstd1;
            const uint32_t r0 = pack2(a, a), r1_ = pack2(b, b);
#pragma unroll
            for (int q = 8 * sg; q < 8 * sg + 8; q++) u[q] = mul2(u[q], (q & 1) ? r1_ : r0);
#pragma unroll
            for (int q = 2 * sg; q < 2 * sg + 2; q++) stsm4(ad[q] + (un & 1) * SLOT + (un >> 1) * 8192, u[4 * q], u[4 * q + 1], u[4 * q + 2], u[4 * q + 3]);
          }
        };
        auto unit = [&](int un) { return kv + ((un >> 1) & 1) * 64 + (un & 1) * 16 + (un >> 2) * 32; };
        hedgehog_scale<0>(kv, s0, nullptr);
#pragma unroll 1
        for (int it = 0;; it++) {
#pragma unroll
          for (int un = 0; un < 4; un++) {
            if (un == 1) {
              if (it) asm volatile("bar.sync 9, 256;" ::: "memory");
#pragma unroll
              for (int q = 0; q < 4; q++) ad[q] -= it * (OFF_S - OFF_B - 2 * SLOT);
            }
            norm((un + 3) & 3);
            dual_exp(unit(un), f[un & 1], x.goff);
            hedgehog_scale<KEEP>(unit(un + 1), ((un + 1) & 2) ? s1 : s0, f[(un + 1) & 1]);
          }
          if (it) break;
#pragma unroll
          for (int q = 0; q < 32; q++) {
            asm volatile("mov.b32 %0, %1;" : "=f"(kv[q]) : "f"(kv[q + 32]));
            asm volatile("mov.b32 %0, %1;" : "=f"(kv[q + 64]) : "f"(kv[q + 96]));
            if (q < 16) kv[32 + q] = 0.f;
          }
        }
        norm(3);
        TSL_(3);
      } else {
        wg_bar(w);
#pragma unroll
        for (int hf = 0; hf < 2; hf++) {
          stsm4(tV[hf] + 512 + x.mhi * 512, uu[2 * hf], uu[2 * hf + 1], uu[2 * hf], uu[2 * hf + 1]);
          stsm4(tV[hf] + 1792 + x.mhi * 512, uu[2 * hf], uu[2 * hf + 1], uu[2 * hf], uu[2 * hf + 1]);
#pragma unroll
          for (int q = 0; q < 8; q++) {
            const float* u = kv + 64 * hf + 8 * q;
            stsm4(tV[hf] + (q >> 1) * 640 + (q & 1) * 256, pack2(u[0], u[1]), pack2(u[2], u[3]), pack2(u[4], u[5]), pack2(u[6], u[7]));
          }
        }
        TSL_(3);
      }
      {
        float d[2][20];
        uint4* dst = &g_kvpart[x.j()][w * 4 + x.warp][0][x.m() * 32 + x.lane];
        unsigned* dz = reinterpret_cast<unsigned*>(&g_kvpart[x.j()][w * 4 + x.warp][x.c & 1][512]) + x.m() * 8 + x.g;
        asm volatile("" : "+l"(dst), "+l"(dz)::"memory");
        fence_async_smem();
        cta_bar();
        TSL_(11);
        uint32_t pk[9];
        auto prep = [&](float (&u)[20]) {
          fence_regs(u);
#pragma unroll
          for (int q = 0; q < 8; q++) pk[q] = pack2(u[((q >> 1) & 2) + 4 * (q & 3)], u[((q >> 1) & 2) + 4 * (q & 3) + 1]);
          pk[8] = __float_as_uint((x.c & 1) ? u[18] + u[19] : u[16] + u[17]);
#pragma unroll
          for (int q = 0; q < 9; q += 4) pk[q] = (pk[q] & ~1u) | (L == 1);
        };
        auto send = [&](int hp) {
          st_v4(dst + hp * 16 * 544, pk[0], pk[1], pk[2], pk[3]); st_v4(dst + (hp * 16 + 1) * 544, pk[4], pk[5], pk[6], pk[7]);
          st_flag(dz + hp * 16 * 544 * 4, pk[8]);
        };
        wgmma_fence();
#pragma unroll
        for (int q = 0; q < 17; q++) {
          if (q < 16) wgmma_ss_n40_tt(d[q >> 3], desc_lo(SB + (q < 8 ? OFF_S : OFF_B + 2 * SLOT), 1024) + w * (SLOT / 16) + 128 * (q & 7), desc_lo(SB + vreg(q & 7), 2560) + (w + (q >> 3) * 2) * 40, q & 7);
          else wgmma_r1_n128(acc, dm + w * 64, dcs, 0);
          if (q == 7 || q == KVS || q == 16) wgmma_commit();
          if (q == KVS) { wgmma_wait<1>(); prep(d[0]); send(0); mbar_wait2(x.fullA(x.ra.s), x.ra.ph, x.fullB(x.rb.s), x.rb.ph); wgmma_fence(); }
        }
        gemm_issue<128, false>(acc, x, true); gemm_next<128>(x);
        wgmma_wait<1>();
        x.releaseA(h0); x.releaseA(h1); x.releaseB(2); x.releaseB(3);
        if (x.lane == 0) mbar_arrive(sb + BAR_SIGT);
        prep(d[1]);
        TSL_(4);
#pragma unroll 1
        for (int seg = 0; seg < 2; seg++) {
          const int n0 = w ? PS1 : PS0;
          gemm_run(acc, x, seg ? 15 - n0 : n0, seg, seg ? L : 0);
          if (seg == 0) send(1);
        }
      }
      gemm_end(acc, x);
      TSL_(5);
      {
        float dp[2][20], dn[2][20];
        uint32_t f[4][16];
        auto mma = [&](int h) {
          if (!(h & 1)) mbar_wait(sb + BAR_KV + h * 4, L >> 1);
          if (h == 0) TSL_(9);
          const uint32_t db = desc_lo(SB + OFF_S + h * 5120, 128);
          const uint32_t (&a)[16] = f[h];
          wgmma_fence();
          wgmma_rs_n40(dp[h & 1], a[0], a[1], a[2], a[3], db, 0);
          wgmma_rs_n40(dn[h & 1], a[8], a[9], a[10], a[11], db + 160, 0);
          wgmma_rs_n40(dp[h & 1], a[4], a[5], a[6], a[7], db + 80, 1);
          wgmma_rs_n40(dn[h & 1], a[12], a[13], a[14], a[15], db + 240, 1);
          wgmma_commit();
        };
        uint32_t xr[16];
        auto fin = [&](int h) {
          const uint32_t tile = x.aslot(x.held(h >> 1));
          if (!(h & 1)) img_load(xr, tile, x);
          float (&u)[20] = dp[h & 1];
          float (&v)[20] = dn[h & 1];
          fence_regs(u); fence_regs(v);
#pragma unroll
          for (int r = 0; r < 2; r++) {
            const float sp = u[17 + 2 * r], sn = v[17 + 2 * r];
            const float id = rcp(fmaf(fmaf(sp, 0.065536f, u[16 + 2 * r]), sn, v[16 + 2 * r] * sp)), aa = sn * id, cc = sp * id;
            uint32_t o[4];
#pragma unroll
            for (int t = 0; t < 4; t++) o[t] = pack2(fmaf(u[4 * t + 2 * r], aa, v[4 * t + 2 * r] * cc), fmaf(u[4 * t + 2 * r + 1], aa, v[4 * t + 2 * r + 1] * cc));
            if (SV & 1) st_v4(x.img(0, h >> 1) + r * 64 + (h & 1) * 32, o[0], o[1], o[2], o[3]);
            else x.img(0, h >> 1)[r * 64 + (h & 1) * 32] = make_uint4(o[0], o[1], o[2], o[3]);
            sts128(tile + r * 1024 + (h & 1) * 512 + x.oo() * 16, o[0], o[1], o[2], o[3]);
          }
          if (h & 1) { publish(h >> 1, x); img_unpack(acc + 16 * (h - 1), xr); }
        };
        auto scale = [&](int h) { hedgehog_scale<0>(acc + 16 * h, st, nullptr); };
        auto ex = [&](int h) { dual_exp_rcp(acc + 16 * h, f[h]); };
        scale(0);
        ex(0); scale(1); mma(0);
        ex(1); wgmma_wait<0>(); fin(0); bb_fence(x.goff); mma(1);
        wgmma_wait<0>(); fin(1); scale(2);
        ex(2); scale(3); if (UK & 1) bb_keep(acc, x.goff); mma(2);
        ex(3); wgmma_wait<0>(); fin(2); mma(3);
        wgmma_wait<0>(); fin(3);
      }
    }
    if (PW & 2) { mbar_wait(x.fullB(x.rb.s), x.rb.ph); fence_regs(acc); }
    fence_async_smem();
    wg_bar(w);
    TSL_(6);
    rewind2<NA>(x.ra);
    gemm_issue<128, false>(acc, x, PW & 2); gemm_next<128>(x);
#pragma unroll 1
    for (int seg = L >= TSL ? 0 : 1; seg < 2; seg++) {
      gemm_run(acc, x, L >= TSL ? (seg ? TSK : 15 - TSK) : 15, seg, 10 + L);
      if (L >= TSL) {
        if (seg == 0 && w == 1) asm volatile("bar.sync 6, 256;" ::: "memory");
        if (seg == 1 && w == 0) asm volatile("bar.arrive 6, 256;" ::: "memory");
      }
    }
    gemm_end(acc, x);
    TSL_(7);
    rewind2<NA>(x.ra);
    out_epilogue(acc, r1, ts, P.out + goff, L, x);
    TSL_(13);
  }
}

typedef unsigned long long u64;
template <class T> __device__ __forceinline__ T* early(T* p) { return (T*)__shfl_xor_sync(0xffffffffu, (u64)p, 1); }
__device__ __forceinline__ void pause(uint32_t GAP) {
  if (GAP) { uint32_t t0, t; asm volatile("mov.u32 %0, %%clock;" : "=r"(t0)); do { asm volatile("mov.u32 %0, %%clock;" : "=r"(t)); } while (t - t0 < GAP); }
}
__device__ __forceinline__ u64 order_table(int kind, int j) {
  const int i = threadIdx.x & 15;
  const unsigned v = (unsigned)(kind == 2 ? q_order(i, j) : kv_order(i, j, kind)) << (4 * (i & 7));
  return (u64)__reduce_or_sync(0xffffffffu, i < 8 ? 0u : v) << 32 | __reduce_or_sync(0xffffffffu, i < 8 ? v : 0u);
}

__device__ __forceinline__ void b_producer(const Params& P, uint32_t sb, unsigned vb) {
  const int j = cta_j(vb);
  const u64 t0 = order_table(0, j), t1 = order_table(1, j), t2 = order_table(2, j);
  Ring r = {PRE_B % NB, PRE_B < NB};
#pragma unroll 1
  for (int sg = 0; sg < 20; sg++) {
    const int L = sg / 5, p = sg - 5 * L, wt = L & 1;
    int n = p >= 3 ? 16 : (wt ? (p ? 16 - NJ : 2 * NJ) : (p ? 0 : (L ? 32 : 32 - PRE_B)));
    u64 tab = p == 3 ? t2 : (sg == 0 ? t0 >> (2 * PRE_B) : (p == 1 || p == 2 ? t1 >> (4 * NJ) : t1));
    const CUtensorMap* tm = p == 4 ? &P.mwo[wt] : &P.mw[wt ? 1 : L];
    const uint4* img = &g_wf[p != 3][j][0][0];
    int col = (p >= 3 ? 0 : (p == 2 ? 2048 : 1024)) + 128 * j;
    const int flip = p == 0 ? 3072 : 0;
    const bool fold = wt && p != 4;
    if (sg == 5 || sg == 8) { mbar_wait(sb + (sg == 5 ? BAR_WPHI : BAR_CS + 8), sg == 5); fence_async_global(); }
    if (DEFER && p == 4 && ((DEFL >> wt) & 1)) {
      Ring q = r;
      for (int u = 0; u < DEFER; u++) adv<NB>(q);
      mbar_wait(sb + BAR_EMPTYB + q.s * 8, q.ph);
    }
#pragma unroll 1
    for (; n > 0; n--) {
      const int kb = (int)tab & 15;
      mbar_wait(sb + BAR_EMPTYB + r.s * 8, r.ph);
      if (elect()) {
        mbar_expect_tx(sb + BAR_FULLB + r.s * 8, SLOT);
        if (fold && col < 2048) bulk_load(sb + OFF_B + r.s * SLOT, img + kb * 1024, SLOT, sb + BAR_FULLB + r.s * 8);
        else tma_load_w(sb + OFF_B + r.s * SLOT, tm, sb + BAR_FULLB + r.s * 8, col, kb);
      }
      adv<NB>(r);
      if (p == 2 && (n | 4) == 5) r.s = 4;
      col ^= flip;
      if (!(col & flip & 2048)) tab >>= 4;
    }
  }
}

__device__ __forceinline__ void a_loader(const Params& P, uint32_t sb, unsigned vb) {
  const int j = cta_j(vb), m = cta_m(vb);
  const u64 t1 = order_table(1, j), t2 = order_table(2, j);
  Ring r = {PRE_A % NA, PRE_A < NA};
  {
    u64 tab = order_table(0, j) >> (4 * PRE_A);
#pragma unroll 1
    for (int i = PRE_A; i < 33; i++) {
      if (i == 17) tab = t2;
      mbar_wait(sb + BAR_EMPTYA + r.s * 8, r.ph);
      if (elect()) {
        mbar_expect_tx(sb + BAR_FULLA + r.s * 8, SLOT);
        if (i != 14) tma_load_3d(sb + OFF_A + r.s * SLOT, &P.mx, sb + BAR_FULLA + r.s * 8, ((int)tab & 15) * 64, m * 64, 0);
        else {
          tma_load_w(sb + OFF_A + r.s * SLOT, &P.mw[1], sb + BAR_FULLA + r.s * 8, 1024 + 128 * j, m);
          mbar_expect_tx(sb + BAR_WPHI, 8192); tma_load_2d(sb + OFF_S + 4096, &P.mwphi, sb + BAR_WPHI, 0, 128 * j);
        }
        if (i == PF0 || i == PF1 || i == PF2)
          tma_prefetch_w(i == PF0 ? &P.mw[1] : &P.mwo[i == PF2], (i == PF0 ? 1024 : 0) + 128 * j, m);
      }
      adv<NA>(r);
      if (i != 14) tab >>= 4;
    }
  }
  const unsigned tag = get_tag(sb);
  unsigned seen = 0;
#pragma unroll 1
  for (int sg = 0; sg < 27; sg++) {
    const int L = sg >> 3, p = sg & 7, q = p >= 3 ? p - 3 : p;
    if (p == 0 && (L & 1)) {
#pragma unroll 1
      for (int h = 0; h < 2; h++) {
        poll_flags(&g_kvfflag[L >> 1][j][h][0], 8, 0xFFu, tag);
        if (elect()) { mbar_expect_tx(sb + BAR_KV + h * 8, 10240); bulk_load(sb + OFF_S + h * 10240, &g_kvfin[j][8 * h][0], 10240, sb + BAR_KV + h * 8); }
      }
      TS(4, 14 + L);
    }
    int n = q == 0 ? 4 : (q == 1 ? 3 : (q == 2 ? 7 : (q == 3 ? ((L & 1) ? 0 : 16 - NJ) : 16)));
    u64 tab = q == 4 ? t2 : t1 >> (q == 0 ? 8 : (q == 1 ? 24 : (q == 2 ? 36 : 4 * NJ)));
    const uint4* img = &g_img[p >= 3 ? XBUF(L + 1) : 0][m][0][0];
    const uint32_t gap = p == 0 ? G0 : (p == 3 ? G3 : (q < 3 ? G1 : G4));
    bool poll = q == 0 || q == 2 || (q == 1 && seen != 0xFFFFFFFFu);
#pragma unroll 1
    for (; n > 0; n--) {
      const uint4* src = img + ((int)tab & 15) * 1024;
      src = early(src);
      mbar_wait(sb + BAR_EMPTYA + r.s * 8, r.ph);
      if (elect()) mbar_expect_tx(sb + BAR_FULLA + r.s * 8, SLOT);
      if (poll) {
        const int lane = threadIdx.x & 31, nn = p >= 3 ? PNX : PNO;
        const unsigned* f = (p >= 3 ? &g_xflag[L + 1][0][m][0] : &g_oflag[L][0][m][0]) + (q == 2 ? 512 : 0) + (lane & 7);
        if (q == 0 || (PN2 && q == 2)) f += (((lane >> 3) & (nn - 1)) - (m & (nn - 1))) * 32;
        const unsigned need = q == 0 ? 0x0F0F0F0Fu << (~j & 4) : 0xFFFFFFFFu;
        if (q == 0) mbar_wait(sb + BAR_SIGP + (p ? 16 : 0), L & 1);
        int it = 0;
        do { seen = __ballot_sync(0xffffffffu, ld_flag(f) == tag); if (++it > (1 << 22)) __trap(); } while ((seen & need) != need);
        if (q == 0) TS(2, p == 0 ? 5 + L * 8 : 9 + L * 8);
        poll = false;
      }
      if (elect()) bulk_load(sb + OFF_A + r.s * SLOT, src, SLOT, sb + BAR_FULLA + r.s * 8);
      adv<NA>(r);
      tab >>= 4;
      pause(gap);
    }
  }
}

__device__ __forceinline__ uint2 sum_packets(float (&a)[8], uint32_t addr, int n) {
  uint2 ok = make_uint2(~0u, 0u);
#pragma unroll 1
  for (int b = 0; b < n; b += KB) {
    uint4 v[KB];
#pragma unroll
    for (int u = 0; u < KB; u++) lds128(addr + (b + u) * 512, v[u].x, v[u].y, v[u].z, v[u].w);
#pragma unroll
    for (int u = 0; u < KB; u++) {
      ok.x &= v[u].x; ok.y |= v[u].x;
      a[0] += lo16(v[u].x); a[1] += hi16(v[u].x); a[2] += lo16(v[u].y); a[3] += hi16(v[u].y);
      a[4] += lo16(v[u].z); a[5] += hi16(v[u].z); a[6] += lo16(v[u].w); a[7] += hi16(v[u].w);
    }
  }
  return ok;
}
__device__ __forceinline__ void helper_bar() { asm volatile("bar.sync 4, 64;" ::: "memory"); }
__device__ __forceinline__ void helper(const Params& P, uint32_t sb, int w, unsigned vb) {
  const int j = cta_j(vb), m = cta_m(vb);
  if (w == 0) {
    if (elect()) {
      const unsigned t = atomicAdd(&g_ctr, 1u) / NCTA + 1u;
      asm volatile("st.shared.u32 [%0], %1;" ::"r"(sb + OFF_EPOCH), "r"(t) : "memory");
      mbar_arrive(sb + BAR_EPOCH);
    }
  }
  const unsigned tag = get_tag(sb);
  mbar_wait(sb + BAR_FULLB + 24, 0);
  const uint32_t stg = sb + OFF_T + w * 12288, stb = sb + BAR_STG + w * 24;
  Ring rs = {0, 0};
  auto cs_image = [&](int L) {
      const int lane = lane_id();
      poll_flags(&g_csflag[L][j][0], 16, L ? CSNEED : 0xFFFu, tag);
#pragma unroll
      for (int p = 0; p < 3; p++) {
        const uint4 u = ldcg4(&g_cs[L][0][p * 1024 + 128 * j + lane * 4]), v = ldcg4(&g_cs[L][1][p * 1024 + 128 * j + lane * 4]);
        const float c0 = __uint_as_float(u.x) + __uint_as_float(v.x), c1 = __uint_as_float(u.y) + __uint_as_float(v.y);
        const float c2 = __uint_as_float(u.z) + __uint_as_float(v.z), c3 = __uint_as_float(u.w) + __uint_as_float(v.w);
        const uint32_t h0 = pack2(c0, c1), h1 = pack2(c2, c3), dst = sb + OFF_CS + (p * 16 + (lane >> 1)) * 96 + L * 48 + (lane & 1) * 8;
        sts64(dst, h0, h1); sts64(dst + 16, pack2(c0 - lo16(h0), c1 - hi16(h0)), pack2(c2 - lo16(h1), c3 - hi16(h1))); sts64(dst + 32, h0, h1);
        if (L == 0) { sts64(dst + 48, 0u, 0u); sts64(dst + 64, 0u, 0u); sts64(dst + 80, 0u, 0u); }
      }
      if (L == 0 && lane < 4) sts64(sb + OFF_CS + 4608 + lane * 8, 0u, 0u);
      fence_async_smem();
      __syncwarp();
      if (elect()) mbar_arrive(sb + BAR_CS + L * 8);
      TS(4, 2 + L * 2);
  };
#pragma unroll 1
  for (int L = 0; L < 4; L++) {
    const int lane = lane_id();
    if (L == 0) {
      {
        const int wt = m >= 12, col = ((0x2021 >> (m & 12)) & 3) * 1024 + 128 * j + (m & 3) * 32;
        const CUtensorMap* tm = &P.mcs[wt];
        __nanosleep(wt ? D2 : CD);
        constexpr int nb = 8;
        float a[8] = {0.f, 0.f, 0.f, 0.f, 0.f, 0.f, 0.f, 0.f};
#pragma unroll 1
        for (int b = -3; b < nb; b++) {
          if (b >= 0) {
            mbar_wait(stb + rs.s * 8, rs.ph);
            sum_packets(a, stg + rs.s * 4096 + lane * 16, 8);
            fence_async_smem();
            __syncwarp();
          }
          const uint32_t sl = b < 0 ? (rs.s + b + 3) % 3 : rs.s;
          if (b + 3 < nb && elect()) { mbar_expect_tx(stb + sl * 8, 4096); tma_load_2d(stg + sl * 4096, tm, stb + sl * 8, col, (w * (16 - nb) + b + 3) * 64); }
          if (b >= 0) adv<3>(rs); else pause(CP);
        }
#pragma unroll
        for (int u = 0; u < 8; u++) {
          a[u] += __shfl_xor_sync(0xffffffffu, a[u], 4); a[u] += __shfl_xor_sync(0xffffffffu, a[u], 8); a[u] += __shfl_xor_sync(0xffffffffu, a[u], 16);
        }
        if (lane < 4) {
          float4* dst = reinterpret_cast<float4*>(&g_cs[wt][w][col + lane * 8]);
          dst[0] = make_float4(a[0], a[1], a[2], a[3]); dst[1] = make_float4(a[4], a[5], a[6], a[7]);
        }
        helper_bar();
        if (w == 0 && elect()) { fence_gpu(); st_flag(&g_csflag[wt][j][m], tag); }
      }
      if (w == 0) TS(4, 1 + L * 2);
    }
    if (w == 1) {
      if (L > 0) { mbar_wait(sb + BAR_SIGP + 24, (L - 1) & 1); __nanosleep(SD); }
      else if (S0) { mbar_wait(sb + BAR_WPHI, 0); __nanosleep(S0); }
#pragma unroll 1
      for (int p = 0; p < 2; p++) {
        uint4 v[8];
        for (int it = 0;; it++) {
          bool ok = true;
#pragma unroll
          for (int t = 0; t < 8; t++) v[t] = ld_pkt(&g_stats[m][p][t][lane]);
#pragma unroll
          for (int t = 0; t < 8; t++) ok = ok && (v[t].w & 15u) == seq4(tag, L);
          if (__all_sync(0xffffffffu, ok)) break;
          __nanosleep(200);
          if (it > (1 << 20)) __trap();
        }
        float s0 = 0.f, q0 = 0.f, s1 = 0.f, q1 = 0.f;
#pragma unroll
        for (int t = 0; t < 8; t++) { s0 += __uint_as_float(v[t].x); q0 += __uint_as_float(v[t].y); s1 += __uint_as_float(v[t].z); q1 += __uint_as_float(v[t].w & ~15u); }
        s0 *= (1.f / 1024); s1 *= (1.f / 1024);
        sts64(sb + OFF_MR + p * 256 + lane * 8, __float_as_uint(rsqrtf(fmaxf(q0 * (1.f / 1024) - s0 * s0, 0.f) + 1e-5f)),
              __float_as_uint(rsqrtf(fmaxf(q1 * (1.f / 1024) - s1 * s1, 0.f) + 1e-5f)));
#pragma unroll
        for (int r = 0; r < 2; r++) {
          const float v = -0.5f * (r ? s1 : s0);
          const uint32_t hh = pack2(v, v), hl = pack2(v, v - lo16(hh));
          const bool b = L & 1;
          sts128(sb + (b ? OFF_MB : OFF_MA) + p * 1024 + (lane >> 3) * 256 + r * 128 + (lane & 7) * 16, b ? 0u : hh, b ? hh << 16 : hl >> 16, b ? hl : 0u, 0u);
        }
      }
      fence_async_smem();
      __syncwarp();
      if (elect()) {
        mbar_arrive(sb + BAR_STAT);
      }
      TS(2, 0 + L * 8);
    }
    if (L == w) cs_image(L);
    if (L & 1) {
      const uint32_t flip = L == 1 ? 0u : 1u;
      mbar_wait(sb + BAR_SIGT, 1);
      {
        int it = 0;
        if (PSL) __nanosleep(m < 8 ? PSL : PSL + 600);
        while (!__all_sync(0xffffffffu, (ld_flag(reinterpret_cast<const unsigned*>(&g_kvpart[j][m][w][512]) + (lane & 15) * 8) ^ flip) & 1u)) { if (PSL) __nanosleep(100); if (++it > (1 << 22)) __trap(); }
        fence_async_global();
      }
      if (w == 0) TS(4, 6 + L * 2);
      for (int it = 0;; it++) {
        if (elect()) { mbar_expect_tx(stb + rs.s * 8, 8704); bulk_load(stg, &g_kvpart[j][m][w][0], 8704, stb + rs.s * 8); }
        mbar_wait(stb + rs.s * 8, rs.ph);
        adv<3>(rs);
        float a[8] = {0.f, 0.f, 0.f, 0.f, 0.f, 0.f, 0.f, 0.f};
        float z = 0.f;
        uint32_t ok = 1u;
#pragma unroll
        for (int u = 0; u < 4; u++) { const float v = lds32f(stg + 8192 + u * 128 + (lane & 3) * 32 + (lane >> 2) * 4); z += v; ok &= __float_as_uint(v) ^ flip; }
        const uint2 tg = sum_packets(a, stg + lane * 16, 16);
        ok &= flip ? ~tg.y : tg.x;
        uint4* img = &g_kvfin[j][m][w * 8 + (lane >> 2)];
        img[(lane & 3) * 16] = make_uint4(pack2(a[0], a[1]), pack2(a[2], a[3]), pack2(a[4], a[5]), pack2(a[6], a[7]));
        reinterpret_cast<uint32_t*>(img + 64)[lane & 3] = pack2(qsum(z), 1.f / 65536);
        if (__all_sync(0xffffffffu, ok & 1u)) break;
        fence_async_smem();
        if (it > (1 << 16)) __trap();
      }
      if (w == 0) TS(4, 7 + L * 2);
      helper_bar();
      if (w == 1 && elect()) { fence_gpu(); st_flag(&g_kvfflag[L >> 1][j][m >> 3][m & 7], tag); }
      if (w == 1 && L == 1) TS(4, 20);
    } else {
      mbar_wait(sb + BAR_SIGT, 0);
      if (w == 0) {
        if (elect()) { fence_gpu(); st_flag(&g_hflag[L >> 1][m][j][0], tag); st_flag(&g_kflag[j][m], tag); }
        if (L == 0) {
          __nanosleep(KSL);
          poll_flags(&g_kflag[j][0], 16, 0xFFFFu, tag);
          if (elect()) mbar_arrive(sb + BAR_WPHI);
        }
      } else if (m > 0) {
        poll_flags(&g_hflag[L >> 1][m - 1][j][0], 1, 1u, tag);
        if (elect()) { mbar_expect_tx(sb + BAR_HALO, 8192); bulk_load(sb + OFF_S + 8192, &g_halo[m - 1][j][0][0], 8192, sb + BAR_HALO); }
        TS(2, 2 + L * 8);
      }
    }
#pragma unroll 1
    for (int e = 0; e < (L < 3 && w == 0 ? 3 : 1); e++) {
      unsigned* flag = e == 0 ? &g_oflag[L][w][m][j] : &g_xflag[L + 1][e - 1][m][j];
      flag = early(flag);
      mbar_wait(sb + BAR_SIGP + (e == 0 ? w : e + 1) * 8, L & 1);
      TS(e == 2 ? 3 : 2 + w, (e ? 6 : 3) + L * 8);
      if (elect()) { fence_async_global(); fence_gpu(); st_flag(flag, tag); }
      TS(e == 2 ? 3 : 2 + w, (e ? 7 : 4) + L * 8);
    }
  }
}

__device__ __forceinline__ void spare(const Params& P, uint32_t sb, int id) {
  const int tid = threadIdx.x & 127, w = __shfl_sync(0xffffffffu, threadIdx.x >> 7, 0), lane = tid & 31, j = 2 * id + w;
  const uint32_t ring = w * 6 * SLOT, wp = 12 * SLOT + w * 8192, bar = sb + 13 * SLOT + w * 64;
  auto part = [&](int t) { return (t >> 4) ^ w; };
  auto load = [&](int t, uint32_t sl) {
    mbar_expect_tx(bar + sl * 8, t == 0 ? SLOT + 8192 : SLOT);
    tma_load_w(sb + ring + sl * SLOT, &P.mw[1], bar + sl * 8, part(t) * 1024 + 128 * j, t & 15);
  };
  if (tid == 0) {
    if (w == 2) sts32(sb + OFF_EPOCH, atomicAdd(&g_ctr, 1u) / NCTA + 1u);
    else {
      __nanosleep(D3);
#pragma unroll 1
      for (int t = 0; t < 5; t++) {
        mbar_init(bar + t * 8, 1);
        asm volatile("fence.mbarrier_init.release.cluster;" ::: "memory");
        load(t, t);
      }
      tma_load_2d(sb + wp, &P.mwphi, bar, 0, 128 * j);
    }
  }
  __syncthreads();
  const unsigned tag = get_tag<false>(sb);
  if (w == 2) {
    int it = 0;
    while ((int)(ld_flag(&g_ctr) - tag * NCTA) < 0) { if (++it > (1 << 22)) __trap(); }
    return;
  }
  Ring r = {4, 1};
  float d[64] = {}, cs[32] = {};
  auto fold = [&]() {
    mbar_wait(bar + r.s * 8, r.ph);
    wgmma_fence();
#pragma unroll
    for (int q = 0; q < 8; q++)
      wgmma_ss_n32(reinterpret_cast<float (&)[16]>(d[16 * (q >> 1)]), desc_lo(SB + ring + r.s * SLOT, 16) + (q >> 2) * 512 + (q & 3) * 2, desc_lo(SB + wp, 512) + q * 64, q & 1);
    wgmma_commit();
  };
  const int row = (tid >> 5) * 16 + (lane >> 2);
#pragma unroll 1
  for (int t = -1; t < 32; t++) {
    uint32_t f[32];
#pragma unroll
    for (int i = 0; i < 32; i++) { f[i] = pack2(d[2 * i], d[2 * i + 1]); cs[i & 30] += d[2 * i]; cs[i | 1] += d[2 * i + 1]; }
    wg_bar(w);
    if (tid == 0 && t >= 0 && t < 27) load(t + 5, r.s);
    __syncwarp();
    if (t < 31) adv<5>(r);
    fold();
    if (part(t) == 0 && t >= 0) {
#pragma unroll
      for (int q = 0; q < 8; q++)
        g_wf[0][j][t & 15][(q >> 2) * 512 + (row + 8 * (q & 1)) * 8 + (((q & 2) * 2 + (lane & 3)) ^ (lane >> 2))] =
            make_uint4(f[4 * (q & 6) + (q & 1)], f[4 * (q & 6) + (q & 1) + 2], f[4 * (q & 6) + (q & 1) + 4], f[4 * (q & 6) + (q & 1) + 6]);
    }
    wgmma_wait<0>();
    fence_regs(d);
    if ((t & 15) == 15) {
      if (t >= 0) {
        const uint32_t red = sb + ring + 5 * SLOT;
#pragma unroll
        for (int i = 0; i < 8; i++) sts128(red + (tid >> 2) * 512 + (i >> 1) * 128 + (lane & 3) * 32 + (i & 1) * 16, __float_as_uint(cs[4 * i]), __float_as_uint(cs[4 * i + 1]), __float_as_uint(cs[4 * i + 2]), __float_as_uint(cs[4 * i + 3]));
        wg_bar(w);
        float a = 0.f;
#pragma unroll 4
        for (int i = 0; i < 32; i++) a += lds32f(red + i * 512 + tid * 4);
        g_cs[1][0][part(t) * 1024 + j * 128 + tid] = a;
        wg_bar(w);
        if (tid == 0) {
          fence_gpu();
          st_flag(&g_csflag[1][j][part(t)], tag);
        }
        __syncwarp();
      }
#pragma unroll
      for (int i = 0; i < 32; i++) cs[i] = 0.f;
    }
  }
}

__global__ void __launch_bounds__(NTHREADS, 1) fused_kernel(const __grid_constant__ Params P) {
  extern __shared__ __align__(1024) uint8_t smem_raw[];
  constexpr uint32_t sb = SB;
  const int tid = threadIdx.x;
  const unsigned vb = vblock();
  if (vb >= 128) { spare(P, sb, vb - 128); return; }
  const int warp = __shfl_sync(0xffffffffu, tid >> 5, 0);
  if (elect()) {
    if (warp == 11) { prefetch_map(&P.mx); prefetch_map(&P.mw[0]); if (smem_u32(smem_raw) != SB) __trap(); }
    if (warp < 7) {
#pragma unroll
      for (int i = 0; i < 8; i++) mbar_init(sb + OFF_BAR + (warp * 8 + i) * 8, warp == 2 || warp == 3 ? 2 : (warp == 4 ? 8 : 1));
    }
    asm volatile("fence.mbarrier_init.release.cluster;" ::: "memory");
    if (warp < 2) {
      const int j = cta_j(vb);
#pragma unroll 1
      for (int i = 0; i < (warp == 0 ? PRE_B : PRE_A); i++) {
        const uint32_t bar = sb + BAR_FULLB + warp * 64 + i * 8;
        mbar_expect_tx(bar, SLOT);
        if (warp == 0) tma_load_w(sb + OFF_B + i * SLOT, &P.mw[0], bar, 1024 + (i & 1) * 1024 + 128 * j, kv_order(i >> 1, j, 0));
        else tma_load_3d(sb + OFF_A + i * SLOT, &P.mx, bar, kv_order(i, j, 0) * 64, cta_m(vb) * 64, 0);
      }
    }
  }
  if (tid == 0) TS(6, 0);
  __syncthreads();
  if (tid == 0) TS(6, 2);
  if (warp < 4) {
    reg_dealloc<PREGS>();
    if (warp == 0) b_producer(P, sb, vb);
    else if (warp == 1) a_loader(P, sb, vb);
    else helper(P, sb, warp - 2, vb);
  } else {
    reg_alloc<CREGS>();
    consumer(P, sb, (warp >> 2) - 1, vb);
  }
}

typedef CUresult (*EncodeFn)(CUtensorMap*, CUtensorMapDataType, cuuint32_t, void*, const cuuint64_t*, const cuuint64_t*,
                             const cuuint32_t*, const cuuint32_t*, CUtensorMapInterleave, CUtensorMapSwizzle,
                             CUtensorMapL2promotion, CUtensorMapFloatOOBfill);

void encode(EncodeFn fn, CUtensorMap* m, const void* ptr, int rank, const cuuint64_t* dims, const cuuint64_t* strides,
            const cuuint32_t* box, CUtensorMapSwizzle swz) {
  const cuuint32_t es[5] = {1, 1, 1, 1, 1};
  fn(m, CU_TENSOR_MAP_DATA_TYPE_BFLOAT16, rank, const_cast<void*>(ptr), dims, strides, box, es, CU_TENSOR_MAP_INTERLEAVE_NONE,
     swz, CU_TENSOR_MAP_L2_PROMOTION_L2_256B, CU_TENSOR_MAP_FLOAT_OOB_FILL_NONE);
}
void encode_w(EncodeFn fn, CUtensorMap* m, const void* ptr, int ncols, bool perm) {
  const cuuint64_t p = (cuuint64_t)ncols * 2, d[5] = {(cuuint64_t)ncols, 2, 4, 4, 32}, s[4] = {p, (perm ? 8 : 2) * p, (perm ? 2 : 8) * p, 32 * p};
  const cuuint32_t box[5] = {64, 2, 4, 4, 2};
  encode(fn, m, ptr, 5, d, s, box, CU_TENSOR_MAP_SWIZZLE_128B);
}

void encode_cs(EncodeFn fn, CUtensorMap* m, const void* ptr, int ncols) {
  const cuuint64_t d[2] = {(cuuint64_t)ncols, 1024}, s[1] = {(cuuint64_t)ncols * 2};
  const cuuint32_t box[2] = {32, 64};
  encode(fn, m, ptr, 2, d, s, box, CU_TENSOR_MAP_SWIZZLE_NONE);
}

}

extern "C" void kernel_launch(void* const* d_in, const int* in_sizes, int n_in, void* d_out, int out_size) {
  (void)in_sizes; (void)n_in; (void)out_size;
  void* fnp = nullptr;
  cudaDriverEntryPointQueryResult q;
  cudaGetDriverEntryPoint("cuTensorMapEncodeTiled", &fnp, cudaEnableDefault, &q);
  EncodeFn fn = (EncodeFn)fnp;
  Params P;
  {
    const cuuint64_t dims[3] = {1024, 1024, 2}, strides[2] = {4096, 2048};
    const cuuint32_t box[3] = {64, 64, 2};
    encode(fn, &P.mx, d_in[0], 3, dims, strides, box, CU_TENSOR_MAP_SWIZZLE_128B);
  }
  P.out = (uint4*)d_out;
  encode_w(fn, &P.mw[0], d_in[1], 3072, false);
  encode_w(fn, &P.mw[1], d_in[4], 3072, true);
  encode_w(fn, &P.mw[2], d_in[1], 3072, true);
  encode_w(fn, &P.mwo[0], d_in[2], 1024, true);
  encode_w(fn, &P.mwo[1], d_in[6], 1024, false);
  encode_cs(fn, &P.mcs[0], d_in[1], 3072);
  encode_cs(fn, &P.mcs[1], d_in[4], 3072);
  {
    const cuuint64_t dims[2] = {32, 1024}, strides[1] = {64};
    const cuuint32_t box[2] = {32, 128};
    encode(fn, &P.mwphi, d_in[5], 2, dims, strides, box, CU_TENSOR_MAP_SWIZZLE_64B);
  }
  cudaFuncSetAttribute(fused_kernel, cudaFuncAttributeMaxDynamicSharedMemorySize, SMEM_BYTES);
  fused_kernel<<<NCTA, NTHREADS, SMEM_BYTES, cudaStreamPerThread>>>(P);
}
```

```cpp
#include <cuda_runtime.h>
#include <cuda_bf16.h>
#include <cuda.h>
#include <stdint.h>

namespace {

__device__ __forceinline__ void wgmma_ss_n256(float (&d)[128], uint32_t da, uint32_t ha, uint32_t db, int sd) {
  asm volatile("{\n.reg .pred p;\n.reg .b64 a, b;\nsetp.ne.b32 p, %130, 0;\nmov.b64 a, {%128, %131};\nmov.b64 b, {%129, 0x40000040};\n"
    "wgmma.mma_async.sync.aligned.m64n256k16.f32.bf16.bf16 {%0,%1,%2,%3,%4,%5,%6,%7,%8,%9,%10,%11,%12,%13,%14,%15,%16,%17,%18,%19,%20,%21,%22,%23,%24,%25,%26,%27,%28,%29,%30,%31,%32,%33,%34,%35,%36,%37,%38,%39,%40,%41,%42,%43,%44,%45,%46,%47,%48,%49,%50,%51,%52,%53,%54,%55,%56,%57,%58,%59,%60,%61,%62,%63,%64,%65,%66,%67,%68,%69,%70,%71,%72,%73,%74,%75,%76,%77,%78,%79,%80,%81,%82,%83,%84,%85,%86,%87,%88,%89,%90,%91,%92,%93,%94,%95,%96,%97,%98,%99,%100,%101,%102,%103,%104,%105,%106,%107,%108,%109,%110,%111,%112,%113,%114,%115,%116,%117,%118,%119,%120,%121,%122,%123,%124,%125,%126,%127}, a, b, p, 1, 1, 0, 1;\n}\n"
    : "+f"(d[0]),"+f"(d[1]),"+f"(d[2]),"+f"(d[3]),"+f"(d[4]),"+f"(d[5]),"+f"(d[6]),"+f"(d[7]),"+f"(d[8]),"+f"(d[9]),"+f"(d[10]),"+f"(d[11]),"+f"(d[12]),"+f"(d[13]),"+f"(d[14]),"+f"(d[15]),"+f"(d[16]),"+f"(d[17]),"+f"(d[18]),"+f"(d[19]),"+f"(d[20]),"+f"(d[21]),"+f"(d[22]),"+f"(d[23]),"+f"(d[24]),"+f"(d[25]),"+f"(d[26]),"+f"(d[27]),"+f"(d[28]),"+f"(d[29]),"+f"(d[30]),"+f"(d[31]),"+f"(d[32]),"+f"(d[33]),"+f"(d[34]),"+f"(d[35]),"+f"(d[36]),"+f"(d[37]),"+f"(d[38]),"+f"(d[39]),"+f"(d[40]),"+f"(d[41]),"+f"(d[42]),"+f"(d[43]),"+f"(d[44]),"+f"(d[45]),"+f"(d[46]),"+f"(d[47]),"+f"(d[48]),"+f"(d[49]),"+f"(d[50]),"+f"(d[51]),"+f"(d[52]),"+f"(d[53]),"+f"(d[54]),"+f"(d[55]),"+f"(d[56]),"+f"(d[57]),"+f"(d[58]),"+f"(d[59]),"+f"(d[60]),"+f"(d[61]),"+f"(d[62]),"+f"(d[63]),"+f"(d[64]),"+f"(d[65]),"+f"(d[66]),"+f"(d[67]),"+f"(d[68]),"+f"(d[69]),"+f"(d[70]),"+f"(d[71]),"+f"(d[72]),"+f"(d[73]),"+f"(d[74]),"+f"(d[75]),"+f"(d[76]),"+f"(d[77]),"+f"(d[78]),"+f"(d[79]),"+f"(d[80]),"+f"(d[81]),"+f"(d[82]),"+f"(d[83]),"+f"(d[84]),"+f"(d[85]),"+f"(d[86]),"+f"(d[87]),"+f"(d[88]),"+f"(d[89]),"+f"(d[90]),"+f"(d[91]),"+f"(d[92]),"+f"(d[93]),"+f"(d[94]),"+f"(d[95]),"+f"(d[96]),"+f"(d[97]),"+f"(d[98]),"+f"(d[99]),"+f"(d[100]),"+f"(d[101]),"+f"(d[102]),"+f"(d[103]),"+f"(d[104]),"+f"(d[105]),"+f"(d[106]),"+f"(d[107]),"+f"(d[108]),"+f"(d[109]),"+f"(d[110]),"+f"(d[111]),"+f"(d[112]),"+f"(d[113]),"+f"(d[114]),"+f"(d[115]),"+f"(d[116]),"+f"(d[117]),"+f"(d[118]),"+f"(d[119]),"+f"(d[120]),"+f"(d[121]),"+f"(d[122]),"+f"(d[123]),"+f"(d[124]),"+f"(d[125]),"+f"(d[126]),"+f"(d[127])
    : "r"(da), "r"(db), "r"(sd), "r"(ha));
}
__device__ __forceinline__ void wgmma_ss_n128(float (&d)[64], uint32_t da, uint32_t ha, uint32_t db, int sd) {
  asm volatile("{\n.reg .pred p;\n.reg .b64 a, b;\nsetp.ne.b32 p, %66, 0;\nmov.b64 a, {%64, %67};\nmov.b64 b, {%65, 0x40000040};\n"
    "wgmma.mma_async.sync.aligned.m64n128k16.f32.bf16.bf16 {%0,%1,%2,%3,%4,%5,%6,%7,%8,%9,%10,%11,%12,%13,%14,%15,%16,%17,%18,%19,%20,%21,%22,%23,%24,%25,%26,%27,%28,%29,%30,%31,%32,%33,%34,%35,%36,%37,%38,%39,%40,%41,%42,%43,%44,%45,%46,%47,%48,%49,%50,%51,%52,%53,%54,%55,%56,%57,%58,%59,%60,%61,%62,%63}, a, b, p, 1, 1, 0, 1;\n}\n"
    : "+f"(d[0]),"+f"(d[1]),"+f"(d[2]),"+f"(d[3]),"+f"(d[4]),"+f"(d[5]),"+f"(d[6]),"+f"(d[7]),"+f"(d[8]),"+f"(d[9]),"+f"(d[10]),"+f"(d[11]),"+f"(d[12]),"+f"(d[13]),"+f"(d[14]),"+f"(d[15]),"+f"(d[16]),"+f"(d[17]),"+f"(d[18]),"+f"(d[19]),"+f"(d[20]),"+f"(d[21]),"+f"(d[22]),"+f"(d[23]),"+f"(d[24]),"+f"(d[25]),"+f"(d[26]),"+f"(d[27]),"+f"(d[28]),"+f"(d[29]),"+f"(d[30]),"+f"(d[31]),"+f"(d[32]),"+f"(d[33]),"+f"(d[34]),"+f"(d[35]),"+f"(d[36]),"+f"(d[37]),"+f"(d[38]),"+f"(d[39]),"+f"(d[40]),"+f"(d[41]),"+f"(d[42]),"+f"(d[43]),"+f"(d[44]),"+f"(d[45]),"+f"(d[46]),"+f"(d[47]),"+f"(d[48]),"+f"(d[49]),"+f"(d[50]),"+f"(d[51]),"+f"(d[52]),"+f"(d[53]),"+f"(d[54]),"+f"(d[55]),"+f"(d[56]),"+f"(d[57]),"+f"(d[58]),"+f"(d[59]),"+f"(d[60]),"+f"(d[61]),"+f"(d[62]),"+f"(d[63])
    : "r"(da), "r"(db), "r"(sd), "r"(ha));
}
__device__ __forceinline__ void wgmma_ss_n40_tt(float (&d)[20], uint32_t da, uint32_t db, int sd) {
  asm volatile("{\n.reg .pred p;\n.reg .b64 a, b;\nsetp.ne.b32 p, %22, 0;\nmov.b64 a, {%20, 0x40000040};\nmov.b64 b, {%21, 0x8};\n"
    "wgmma.mma_async.sync.aligned.m64n40k16.f32.bf16.bf16 {%0,%1,%2,%3,%4,%5,%6,%7,%8,%9,%10,%11,%12,%13,%14,%15,%16,%17,%18,%19}, a, b, p, 1, 1, 1, 1;\n}\n"
    : "+f"(d[0]),"+f"(d[1]),"+f"(d[2]),"+f"(d[3]),"+f"(d[4]),"+f"(d[5]),"+f"(d[6]),"+f"(d[7]),"+f"(d[8]),"+f"(d[9]),"+f"(d[10]),"+f"(d[11]),"+f"(d[12]),"+f"(d[13]),"+f"(d[14]),"+f"(d[15]),"+f"(d[16]),"+f"(d[17]),"+f"(d[18]),"+f"(d[19])
    : "r"(da), "r"(db), "r"(sd));
}
__device__ __forceinline__ void wgmma_ss_n32(float (&d)[16], uint32_t da, uint32_t db, int sd) {
  asm volatile("{\n.reg .pred p;\n.reg .b64 a, b;\nsetp.ne.b32 p, %18, 0;\nmov.b64 a, {%16, 0x40000040};\nmov.b64 b, {%17, 0x80000020};\n"
    "wgmma.mma_async.sync.aligned.m64n32k16.f32.bf16.bf16 {%0,%1,%2,%3,%4,%5,%6,%7,%8,%9,%10,%11,%12,%13,%14,%15}, a, b, p, 1, 1, 0, 1;\n}\n"
    : "+f"(d[0]),"+f"(d[1]),"+f"(d[2]),"+f"(d[3]),"+f"(d[4]),"+f"(d[5]),"+f"(d[6]),"+f"(d[7]),"+f"(d[8]),"+f"(d[9]),"+f"(d[10]),"+f"(d[11]),"+f"(d[12]),"+f"(d[13]),"+f"(d[14]),"+f"(d[15])
    : "r"(da), "r"(db), "r"(sd));
}
__device__ __forceinline__ void wgmma_rs_n40(float (&d)[20], uint32_t a0, uint32_t a1, uint32_t a2, uint32_t a3, uint32_t db, int sd) {
  asm volatile("{\n.reg .pred p;\n.reg .b64 b;\nsetp.ne.b32 p, %25, 0;\nmov.b64 b, {%24, 0x10};\n"
    "wgmma.mma_async.sync.aligned.m64n40k16.f32.bf16.bf16 {%0,%1,%2,%3,%4,%5,%6,%7,%8,%9,%10,%11,%12,%13,%14,%15,%16,%17,%18,%19}, {%20,%21,%22,%23}, b, p, 1, 1, 1;\n}\n"
    : "+f"(d[0]),"+f"(d[1]),"+f"(d[2]),"+f"(d[3]),"+f"(d[4]),"+f"(d[5]),"+f"(d[6]),"+f"(d[7]),"+f"(d[8]),"+f"(d[9]),"+f"(d[10]),"+f"(d[11]),"+f"(d[12]),"+f"(d[13]),"+f"(d[14]),"+f"(d[15]),"+f"(d[16]),"+f"(d[17]),"+f"(d[18]),"+f"(d[19])
    : "r"(a0), "r"(a1), "r"(a2), "r"(a3), "r"(db), "r"(sd));
}
__device__ __forceinline__ void wgmma_r1_n256(float (&d)[128], uint32_t da, uint32_t db, int sd) {
  asm volatile("{\n.reg .pred p;\n.reg .b64 a, b;\nsetp.ne.b32 p, %130, 0;\nmov.b64 a, {%128, 0x8};\nmov.b64 b, {%129, 0x6};\n"
    "wgmma.mma_async.sync.aligned.m64n256k16.f32.bf16.bf16 {%0,%1,%2,%3,%4,%5,%6,%7,%8,%9,%10,%11,%12,%13,%14,%15,%16,%17,%18,%19,%20,%21,%22,%23,%24,%25,%26,%27,%28,%29,%30,%31,%32,%33,%34,%35,%36,%37,%38,%39,%40,%41,%42,%43,%44,%45,%46,%47,%48,%49,%50,%51,%52,%53,%54,%55,%56,%57,%58,%59,%60,%61,%62,%63,%64,%65,%66,%67,%68,%69,%70,%71,%72,%73,%74,%75,%76,%77,%78,%79,%80,%81,%82,%83,%84,%85,%86,%87,%88,%89,%90,%91,%92,%93,%94,%95,%96,%97,%98,%99,%100,%101,%102,%103,%104,%105,%106,%107,%108,%109,%110,%111,%112,%113,%114,%115,%116,%117,%118,%119,%120,%121,%122,%123,%124,%125,%126,%127}, a, b, p, 1, 1, 0, 1;\n}\n"
    : "+f"(d[0]),"+f"(d[1]),"+f"(d[2]),"+f"(d[3]),"+f"(d[4]),"+f"(d[5]),"+f"(d[6]),"+f"(d[7]),"+f"(d[8]),"+f"(d[9]),"+f"(d[10]),"+f"(d[11]),"+f"(d[12]),"+f"(d[13]),"+f"(d[14]),"+f"(d[15]),"+f"(d[16]),"+f"(d[17]),"+f"(d[18]),"+f"(d[19]),"+f"(d[20]),"+f"(d[21]),"+f"(d[22]),"+f"(d[23]),"+f"(d[24]),"+f"(d[25]),"+f"(d[26]),"+f"(d[27]),"+f"(d[28]),"+f"(d[29]),"+f"(d[30]),"+f"(d[31]),"+f"(d[32]),"+f"(d[33]),"+f"(d[34]),"+f"(d[35]),"+f"(d[36]),"+f"(d[37]),"+f"(d[38]),"+f"(d[39]),"+f"(d[40]),"+f"(d[41]),"+f"(d[42]),"+f"(d[43]),"+f"(d[44]),"+f"(d[45]),"+f"(d[46]),"+f"(d[47]),"+f"(d[48]),"+f"(d[49]),"+f"(d[50]),"+f"(d[51]),"+f"(d[52]),"+f"(d[53]),"+f"(d[54]),"+f"(d[55]),"+f"(d[56]),"+f"(d[57]),"+f"(d[58]),"+f"(d[59]),"+f"(d[60]),"+f"(d[61]),"+f"(d[62]),"+f"(d[63]),"+f"(d[64]),"+f"(d[65]),"+f"(d[66]),"+f"(d[67]),"+f"(d[68]),"+f"(d[69]),"+f"(d[70]),"+f"(d[71]),"+f"(d[72]),"+f"(d[73]),"+f"(d[74]),"+f"(d[75]),"+f"(d[76]),"+f"(d[77]),"+f"(d[78]),"+f"(d[79]),"+f"(d[80]),"+f"(d[81]),"+f"(d[82]),"+f"(d[83]),"+f"(d[84]),"+f"(d[85]),"+f"(d[86]),"+f"(d[87]),"+f"(d[88]),"+f"(d[89]),"+f"(d[90]),"+f"(d[91]),"+f"(d[92]),"+f"(d[93]),"+f"(d[94]),"+f"(d[95]),"+f"(d[96]),"+f"(d[97]),"+f"(d[98]),"+f"(d[99]),"+f"(d[100]),"+f"(d[101]),"+f"(d[102]),"+f"(d[103]),"+f"(d[104]),"+f"(d[105]),"+f"(d[106]),"+f"(d[107]),"+f"(d[108]),"+f"(d[109]),"+f"(d[110]),"+f"(d[111]),"+f"(d[112]),"+f"(d[113]),"+f"(d[114]),"+f"(d[115]),"+f"(d[116]),"+f"(d[117]),"+f"(d[118]),"+f"(d[119]),"+f"(d[120]),"+f"(d[121]),"+f"(d[122]),"+f"(d[123]),"+f"(d[124]),"+f"(d[125]),"+f"(d[126]),"+f"(d[127])
    : "r"(da), "r"(db), "r"(sd));
}
__device__ __forceinline__ void wgmma_r1_n128(float (&d)[64], uint32_t da, uint32_t db, int sd) {
  asm volatile("{\n.reg .pred p;\n.reg .b64 a, b;\nsetp.ne.b32 p, %66, 0;\nmov.b64 a, {%64, 0x8};\nmov.b64 b, {%65, 0x6};\n"
    "wgmma.mma_async.sync.aligned.m64n128k16.f32.bf16.bf16 {%0,%1,%2,%3,%4,%5,%6,%7,%8,%9,%10,%11,%12,%13,%14,%15,%16,%17,%18,%19,%20,%21,%22,%23,%24,%25,%26,%27,%28,%29,%30,%31,%32,%33,%34,%35,%36,%37,%38,%39,%40,%41,%42,%43,%44,%45,%46,%47,%48,%49,%50,%51,%52,%53,%54,%55,%56,%57,%58,%59,%60,%61,%62,%63}, a, b, p, 1, 1, 0, 1;\n}\n"
    : "+f"(d[0]),"+f"(d[1]),"+f"(d[2]),"+f"(d[3]),"+f"(d[4]),"+f"(d[5]),"+f"(d[6]),"+f"(d[7]),"+f"(d[8]),"+f"(d[9]),"+f"(d[10]),"+f"(d[11]),"+f"(d[12]),"+f"(d[13]),"+f"(d[14]),"+f"(d[15]),"+f"(d[16]),"+f"(d[17]),"+f"(d[18]),"+f"(d[19]),"+f"(d[20]),"+f"(d[21]),"+f"(d[22]),"+f"(d[23]),"+f"(d[24]),"+f"(d[25]),"+f"(d[26]),"+f"(d[27]),"+f"(d[28]),"+f"(d[29]),"+f"(d[30]),"+f"(d[31]),"+f"(d[32]),"+f"(d[33]),"+f"(d[34]),"+f"(d[35]),"+f"(d[36]),"+f"(d[37]),"+f"(d[38]),"+f"(d[39]),"+f"(d[40]),"+f"(d[41]),"+f"(d[42]),"+f"(d[43]),"+f"(d[44]),"+f"(d[45]),"+f"(d[46]),"+f"(d[47]),"+f"(d[48]),"+f"(d[49]),"+f"(d[50]),"+f"(d[51]),"+f"(d[52]),"+f"(d[53]),"+f"(d[54]),"+f"(d[55]),"+f"(d[56]),"+f"(d[57]),"+f"(d[58]),"+f"(d[59]),"+f"(d[60]),"+f"(d[61]),"+f"(d[62]),"+f"(d[63])
    : "r"(da), "r"(db), "r"(sd));
}

__device__ __forceinline__ uint32_t smem_u32(const void* p) { return (uint32_t)__cvta_generic_to_shared(p); }
__device__ __forceinline__ void mbar_init(uint32_t bar, uint32_t cnt) { asm volatile("mbarrier.init.shared::cta.b64 [%0], %1;" ::"r"(bar), "r"(cnt)); }
__device__ __forceinline__ void mbar_expect_tx(uint32_t bar, uint32_t bytes) { asm volatile("mbarrier.arrive.expect_tx.shared::cta.b64 _, [%0], %1;" ::"r"(bar), "r"(bytes) : "memory"); }
__device__ __forceinline__ void mbar_arrive(uint32_t bar) { asm volatile("mbarrier.arrive.shared::cta.b64 _, [%0];" ::"r"(bar) : "memory"); }
__device__ __forceinline__ void mbar_arrive_n(uint32_t bar, uint32_t n) { asm volatile("mbarrier.arrive.shared::cta.b64 _, [%0], %1;" ::"r"(bar), "r"(n) : "memory"); }
__device__ __forceinline__ void mbar_wait(uint32_t bar, uint32_t parity) {
  asm volatile("{\n.reg .pred p;\nLAB_WAIT:\nmbarrier.try_wait.parity.shared::cta.b64 p, [%0], %1;\n@p bra DONE;\nbra LAB_WAIT;\nDONE:\n}" ::"r"(bar), "r"(parity) : "memory");
}
__device__ __forceinline__ void mbar_wait2(uint32_t a, uint32_t pa, uint32_t b, uint32_t pb) {
  asm volatile("{\n.reg .pred p, q;\nLAB_WAIT:\nmbarrier.try_wait.parity.shared::cta.b64 p, [%0], %1;\nmbarrier.try_wait.parity.shared::cta.b64 q, [%2], %3;\n"
               "and.pred p, p, q;\n@p bra DONE;\nbra LAB_WAIT;\nDONE:\n}" ::"r"(a), "r"(pa), "r"(b), "r"(pb) : "memory");
}
__device__ __forceinline__ void mbar_wait3(uint32_t a, uint32_t pa, uint32_t b, uint32_t pb) {
  asm volatile("{\n.reg .pred p, q, r;\nLAB_WAIT:\nmbarrier.try_wait.parity.shared::cta.b64 p, [%0], %1;\nmbarrier.try_wait.parity.shared::cta.b64 q, [%2], %3;\n"
               "mbarrier.try_wait.parity.shared::cta.b64 r, [%2+8], %3;\nand.pred p, p, q;\nand.pred p, p, r;\n@p bra DONE;\nbra LAB_WAIT;\nDONE:\n}" ::"r"(a), "r"(pa), "r"(b), "r"(pb) : "memory");
}
__device__ __forceinline__ bool mbar_probe2(uint32_t a, uint32_t pa, uint32_t b, uint32_t pb) {
  uint32_t ok;
  asm volatile("{\n.reg .pred p, q;\nmbarrier.test_wait.parity.shared::cta.b64 p, [%1], %2;\nmbarrier.test_wait.parity.shared::cta.b64 q, [%3], %4;\n"
               "and.pred p, p, q;\nselp.u32 %0, 1, 0, p;\n}" : "=r"(ok) : "r"(a), "r"(pa), "r"(b), "r"(pb) : "memory");
  return ok != 0;
}
__device__ __forceinline__ void tma_load_3d(uint32_t dst, const CUtensorMap* tm, uint32_t bar, int c0, int c1, int c2) {
  asm volatile("cp.async.bulk.tensor.3d.shared::cluster.global.mbarrier::complete_tx::bytes [%0], [%1, {%3, %4, %5}], [%2];"
               ::"r"(dst), "l"(tm), "r"(bar), "r"(c0), "r"(c1), "r"(c2) : "memory");
}
__device__ __forceinline__ void tma_load_2d(uint32_t dst, const CUtensorMap* tm, uint32_t bar, int c0, int c1) {
  asm volatile("cp.async.bulk.tensor.2d.shared::cluster.global.mbarrier::complete_tx::bytes [%0], [%1, {%3, %4}], [%2];"
               ::"r"(dst), "l"(tm), "r"(bar), "r"(c0), "r"(c1) : "memory");
}
__device__ __forceinline__ void tma_load_w(uint32_t dst, const CUtensorMap* tm, uint32_t bar, int col, int kb) {
#pragma unroll
  for (int q = 0; q < 2; q++)
    asm volatile("cp.async.bulk.tensor.5d.shared::cluster.global.mbarrier::complete_tx::bytes [%0], [%1, {%3, %4, %4, %4, %5}], [%2];"
                 ::"r"(dst + q * 8192), "l"(tm), "r"(bar), "r"(col + q * 64), "r"(0), "r"(2 * kb) : "memory");
}
__device__ __forceinline__ void tma_prefetch_w(const CUtensorMap* tm, int col, int kb) {
#pragma unroll
  for (int q = 0; q < 2; q++)
    asm volatile("cp.async.bulk.prefetch.tensor.5d.L2.global [%0, {%1, %2, %2, %2, %3}];" ::"l"(tm), "r"(col + q * 64), "r"(0), "r"(2 * kb) : "memory");
}
__device__ __forceinline__ void bulk_load(uint32_t dst, const void* g, uint32_t bytes, uint32_t bar) {
  asm volatile("cp.async.bulk.shared::cluster.global.mbarrier::complete_tx::bytes [%0], [%1], %2, [%3];" ::"r"(dst), "l"(g), "r"(bytes), "r"(bar) : "memory");
}
__device__ __forceinline__ void prefetch_map(const CUtensorMap* tm) { asm volatile("prefetch.tensormap [%0];" ::"l"(tm) : "memory"); }
__device__ __forceinline__ void fence_async_smem() { asm volatile("fence.proxy.async.shared::cta;" ::: "memory"); }
__device__ __forceinline__ void fence_async_global() { asm volatile("fence.proxy.async.global;" ::: "memory"); }
__device__ __forceinline__ void fence_gpu() { asm volatile("fence.release.gpu;" ::: "memory"); }
__device__ __forceinline__ void st_flag(unsigned* p, unsigned v) { asm volatile("st.relaxed.gpu.global.u32 [%0], %1;" ::"l"(p), "r"(v) : "memory"); }
__device__ __forceinline__ unsigned ld_flag(const unsigned* p) { unsigned v; asm volatile("ld.relaxed.gpu.global.u32 %0, [%1];" : "=r"(v) : "l"(p) : "memory"); return v; }
__device__ __forceinline__ uint4 ldcg4(const void* p) { uint4 v; asm volatile("ld.global.cg.v4.u32 {%0,%1,%2,%3}, [%4];" : "=r"(v.x), "=r"(v.y), "=r"(v.z), "=r"(v.w) : "l"(p)); return v; }
__device__ __forceinline__ uint4 ld_pkt(const uint4* p) {
  uint4 v; asm volatile("{\n.reg .b128 t;\nld.relaxed.gpu.global.b128 t, [%4];\nmov.b128 {%0,%1,%2,%3}, t;\n}" : "=r"(v.x), "=r"(v.y), "=r"(v.z), "=r"(v.w) : "l"(p) : "memory"); return v;
}
__device__ __forceinline__ void st_pkt(uint4* p, uint32_t a, uint32_t b, uint32_t c, uint32_t tag) {
  asm volatile("{\n.reg .b128 t;\nmov.b128 t, {%1,%2,%3,%4};\nst.relaxed.gpu.global.b128 [%0], t;\n}" ::"l"(p), "r"(a), "r"(b), "r"(c), "r"(tag) : "memory");
}
__device__ __forceinline__ void st_v4(uint4* p, uint32_t a, uint32_t b, uint32_t c, uint32_t d) { asm volatile("st.relaxed.gpu.global.v4.u32 [%0], {%1,%2,%3,%4};" ::"l"(p), "r"(a), "r"(b), "r"(c), "r"(d) : "memory"); }
__device__ __forceinline__ void stg128(uint4* p, uint4 v) { asm volatile("st.global.v4.u32 [%0], {%1,%2,%3,%4};" ::"l"(p), "r"(v.x), "r"(v.y), "r"(v.z), "r"(v.w) : "memory"); }
__device__ __forceinline__ void sts32(uint32_t addr, uint32_t a) { asm volatile("st.shared.u32 [%0], %1;" ::"r"(addr), "r"(a) : "memory"); }
__device__ __forceinline__ void sts64(uint32_t addr, uint32_t a, uint32_t b) { asm volatile("st.shared.v2.u32 [%0], {%1,%2};" ::"r"(addr), "r"(a), "r"(b) : "memory"); }
__device__ __forceinline__ uint32_t mul2(uint32_t a, uint32_t b) { uint32_t r; asm("mul.rn.bf16x2 %0, %1, %2;" : "=r"(r) : "r"(a), "r"(b)); return r; }
__device__ __forceinline__ uint32_t add2(uint32_t a, uint32_t b) { uint32_t r; asm("add.rn.bf16x2 %0, %1, %2;" : "=r"(r) : "r"(a), "r"(b)); return r; }
__device__ __forceinline__ bool elect() {
  uint32_t p; asm volatile("{\n.reg .pred q;\nelect.sync _|q, 0xffffffff;\nselp.u32 %0, 1, 0, q;\n}" : "=r"(p)); return p != 0;
}
__device__ __forceinline__ void wgmma_fence() { asm volatile("wgmma.fence.sync.aligned;" ::: "memory"); }
__device__ __forceinline__ void wgmma_commit() { asm volatile("wgmma.commit_group.sync.aligned;" ::: "memory"); }
template <int N> __device__ __forceinline__ void wgmma_wait() { asm volatile("wgmma.wait_group.sync.aligned %0;" ::"n"(N) : "memory"); }
template <int N> __device__ __forceinline__ void fence_regs(float (&d)[N]) {
#pragma unroll
  for (int i = 0; i < N; i++) asm volatile("" : "+f"(d[i])::"memory");
}
template <int R> __device__ __forceinline__ void reg_alloc() { asm volatile("setmaxnreg.inc.sync.aligned.u32 %0;" ::"n"(R)); }
template <int R> __device__ __forceinline__ void reg_dealloc() { asm volatile("setmaxnreg.dec.sync.aligned.u32 %0;" ::"n"(R)); }
__device__ __forceinline__ void wg_bar(int w) { asm volatile("bar.sync %0, 128;" ::"r"(w + 1) : "memory"); }
__device__ __forceinline__ constexpr uint32_t desc_lo(uint32_t addr, uint32_t lbo) { return (addr >> 4) + ((lbo >> 4) << 16); }
__device__ __forceinline__ uint32_t pack2(float lo, float hi) { uint32_t r; asm("cvt.rn.bf16x2.f32 %0, %1, %2;" : "=r"(r) : "f"(hi), "f"(lo)); return r; }
__device__ __forceinline__ float lo16(uint32_t v) { return __uint_as_float(v << 16); }
__device__ __forceinline__ float hi16(uint32_t v) { return __uint_as_float(v & 0xFFFF0000u); }
__device__ __forceinline__ float ex2(float x) { float r; asm("ex2.approx.ftz.f32 %0, %1;" : "=f"(r) : "f"(x)); return r; }
__device__ __forceinline__ float rcp(float x) { float r; asm("rcp.approx.ftz.f32 %0, %1;" : "=f"(r) : "f"(x)); return r; }
__device__ __forceinline__ uint32_t movm(uint32_t a) { uint32_t d; asm volatile("movmatrix.sync.aligned.m8n8.trans.b16 %0, %1;" : "=r"(d) : "r"(a)); return d; }
__device__ __forceinline__ void stsm4(uint32_t addr, uint32_t a, uint32_t b, uint32_t c, uint32_t d) {
  asm volatile("stmatrix.sync.aligned.m8n8.x4.shared.b16 [%0], {%1,%2,%3,%4};" ::"r"(addr), "r"(a), "r"(b), "r"(c), "r"(d) : "memory");
}
__device__ __forceinline__ void ldsm4(uint32_t addr, uint32_t (&r)[4]) {
  asm volatile("ldmatrix.sync.aligned.m8n8.x4.shared.b16 {%0,%1,%2,%3}, [%4];" : "=r"(r[0]), "=r"(r[1]), "=r"(r[2]), "=r"(r[3]) : "r"(addr) : "memory");
}
__device__ __forceinline__ void sts128(uint32_t addr, uint32_t a, uint32_t b, uint32_t c, uint32_t d) {
  asm volatile("st.shared.v4.u32 [%0], {%1,%2,%3,%4};" ::"r"(addr), "r"(a), "r"(b), "r"(c), "r"(d) : "memory");
}
__device__ __forceinline__ void lds128(uint32_t addr, uint32_t& a, uint32_t& b, uint32_t& c, uint32_t& d) {
  asm volatile("ld.shared.v4.u32 {%0,%1,%2,%3}, [%4];" : "=r"(a), "=r"(b), "=r"(c), "=r"(d) : "r"(addr) : "memory");
}
__device__ __forceinline__ float lds32f(uint32_t addr) { float v; asm volatile("ld.shared.f32 %0, [%1];" : "=f"(v) : "r"(addr) : "memory"); return v; }
__device__ __forceinline__ float2 lds64f(uint32_t addr) { float2 v; asm volatile("ld.shared.v2.f32 {%0,%1}, [%2];" : "=f"(v.x), "=f"(v.y) : "r"(addr) : "memory"); return v; }
__device__ __forceinline__ void mma16816(float (&d)[4], uint32_t a0, uint32_t a1, uint32_t a2, uint32_t a3, uint32_t b0, uint32_t b1) {
  asm("mma.sync.aligned.m16n8k16.row.col.f32.bf16.bf16.f32 {%0,%1,%2,%3}, {%4,%5,%6,%7}, {%8,%9}, {%0,%1,%2,%3};"
      : "+f"(d[0]), "+f"(d[1]), "+f"(d[2]), "+f"(d[3]) : "r"(a0), "r"(a1), "r"(a2), "r"(a3), "r"(b0), "r"(b1));
}
__device__ __forceinline__ void mma1688(float (&d)[4], uint32_t a0, uint32_t a1, uint32_t b0) {
  asm("mma.sync.aligned.m16n8k8.row.col.f32.bf16.bf16.f32 {%0,%1,%2,%3}, {%4,%5}, {%6}, {%0,%1,%2,%3};"
      : "+f"(d[0]), "+f"(d[1]), "+f"(d[2]), "+f"(d[3]) : "r"(a0), "r"(a1), "r"(b0));
}

__device__ __forceinline__ float qsum(float v) { v += __shfl_xor_sync(0xffffffffu, v, 1); v += __shfl_xor_sync(0xffffffffu, v, 2); return v; }

constexpr int NCTA = 132;
#define NB_ 6
#define NA_ 5
constexpr int NB = NB_;
constexpr int NA = NA_;
constexpr uint32_t SLOT = 16384;
constexpr uint32_t SB = 1024;
constexpr uint32_t OFF_B = 0;
constexpr uint32_t OFF_A = NB * SLOT;
constexpr uint32_t OFF_S = OFF_A + NA * SLOT;
constexpr uint32_t OFF_T = OFF_S + 20480;
constexpr uint32_t OFF_CS = OFF_T + 24576;
constexpr uint32_t OFF_MR = OFF_CS + 4640;
constexpr uint32_t OFF_BAR = OFF_MR + 512;
constexpr uint32_t OFF_MA = OFF_S, OFF_MB = OFF_CS - 2048;
constexpr uint32_t BAR_FULLB = OFF_BAR;
constexpr uint32_t BAR_FULLA = BAR_FULLB + 64;
constexpr uint32_t BAR_EMPTYB = BAR_FULLA + 64;
constexpr uint32_t BAR_EMPTYA = BAR_EMPTYB + 64;
constexpr uint32_t BAR_SIGP = BAR_EMPTYA + 64;
constexpr uint32_t BAR_SIGT = BAR_SIGP + 32;
constexpr uint32_t BAR_STAT = BAR_SIGP + 64;
constexpr uint32_t BAR_HALO = BAR_STAT + 16;
constexpr uint32_t BAR_CS = BAR_HALO + 8;
constexpr uint32_t BAR_WPHI = BAR_CS + 16;
constexpr uint32_t BAR_KV = BAR_WPHI + 8;
constexpr uint32_t BAR_STG = BAR_KV + 16;
constexpr uint32_t BAR_EPOCH = BAR_STG + 48;
constexpr uint32_t OFF_EPOCH = OFF_BAR + 7 * 64;
static_assert(BAR_EPOCH < OFF_EPOCH, "barriers");
constexpr uint32_t SMEM_BYTES = OFF_EPOCH + 8;
static_assert(SMEM_BYTES <= 232448 && NB % 2 == 0 && NB <= 8 && NA <= 6, "smem");

#define CREGS 224
#define PREGS 56
#define PF1 19
#define PF2 21
#define PRE_A 2
#define PRE_B 4
#define CSB 4
#define CSNEED 0xF003u
#define XR 1
#define PS0 1
#define PS1 3
#define PSW 0
#define SD 1000
#define QORD 4
#define KSPLIT 12
#define KEEP 16
#define NJ 3
#define KSL 1000
#define PSL 0
#define KVS 12
#define D2 2000
#define D3 1500
#define G0 50
#define G3 50
#define G1 0
#define G4 0
#define MAP 3
#define PMAP 0x76321450u
#define PW 1
#define PN2 0
#define XA 3
#define XS 1
#define IP 3
#define UK 1
#define CP 500
#define CD 0
#define S0 500
#define NS 2
#define XO 0
#define SW 2
#define SA 1
#define SB_ 4
#define KB 8
#define PNX 2
#define PNO 2
#define DEFER 3
#define DEFL 2
#define TSK 3
#define TSL 3
constexpr int NTHREADS = 384;

struct Params {
  CUtensorMap mx;
  CUtensorMap mw[3];
  CUtensorMap mwo[2];
  CUtensorMap mcs[2];
  CUtensorMap mwphi;
  uint4* out;
};

#define XBUF(L) 1
__device__ __align__(256) uint4 g_img[XBUF(3) + 1][16][16][1024];
__device__ __align__(256) uint4 g_wf[2][8][16][1024];
__device__ __align__(256) uint4 g_stats[16][2][8][32];
__device__ __align__(256) uint4 g_halo[16][8][2][256];
__device__ __align__(256) float g_cs[2][2][3072];
__device__ __align__(256) uint4 g_kvpart[8][16][2][544];
__device__ __align__(256) uint4 g_kvfin[8][16][80];
__device__ __align__(256) unsigned g_xflag[4][2][16][32];
__device__ __align__(256) unsigned g_oflag[4][2][16][32];
__device__ __align__(256) unsigned g_hflag[2][16][8][32];
__device__ __align__(256) unsigned g_kvfflag[2][8][2][32];
__device__ __align__(256) unsigned g_csflag[2][8][32];
__device__ __align__(256) unsigned g_kflag[8][32];
__device__ unsigned g_ctr;
__device__ __forceinline__ unsigned vblock() {
  unsigned s;
  asm volatile("mov.u32 %0, %%smid;" : "=r"(s));
  const unsigned r = s & 1;
  s >>= 1;
  const unsigned t = s - 32, q = (t * 37) >> 8;
  const unsigned hi = s < 60 ? 12 + (t - 7 * q) * 8 + q : (s < 62 ? s + 4 : s - 58);
  unsigned b = 2 * (s < 32 ? (s & 7) * 8 + (s >> 3) : hi) + r;
  if (b < 128) b = (b & 15) | ((PMAP >> ((b >> 4) * 4)) & 7) << 4;
  if (s >= 62) b = 8 + 4 * r + s - 62;
  return __shfl_sync(0xffffffffu, b, 0);
}
#define TS(who, id) do {} while (0)
#define TSW(id) do {} while (0)

#define TSMASK 0xFFFF
#define TSL_(a) do { if ((TSMASK >> (a)) & 1) TSW((a) + L * 12); } while (0)
__device__ __forceinline__ int cta_m(unsigned b) { return ((b >> 2) & 12) | (b & 3); }
__device__ __forceinline__ int cta_j(unsigned b) { return ((b >> 2) & 3) | ((b >> 4) & 4); }
struct Ring { uint32_t s, ph; };
template <int N> __device__ __forceinline__ void adv(Ring& r) { if (++r.s == N) { r.s = 0; r.ph ^= 1; } }
template <int N> __device__ __forceinline__ void rewind2(Ring& r) { if (r.s < 2) { r.s += N - 2; r.ph ^= 1; } else r.s -= 2; }
__device__ __forceinline__ int other_tile(int t, int j) { return (t == (j | 4) ? 7 : t) ^ (~j & 4); }
__device__ __forceinline__ int q_order(int i, int j) { return 2 * (i >= 14 ? j : other_tile(i >> 1, j)) + (i & 1); }
__device__ __forceinline__ int o_order(int i, int j) {
  if (i < 2) return 2 * j + i;
  const int odd = i >= 9;
  return 2 * other_tile(i - 2 - 7 * odd, j) + odd;
}
__device__ __forceinline__ int kv_order(int i, int j, int L) { return L > 0 ? o_order(i, j) : (i + 14 + 2 * (j & 4)) & 15; }

__device__ __forceinline__ unsigned poll_flags(const unsigned* f, int n, unsigned need, unsigned tag) {
  const int lane = threadIdx.x & 31;
  unsigned mask; int it = 0;
  do {
    unsigned v = lane < n ? ld_flag(f + lane) : 0u;
    mask = __ballot_sync(0xffffffffu, lane < n && v == tag);
    if (++it > (1 << 22)) __trap();
  } while ((mask & need) != need);
  fence_async_global();
  return mask;
}
template <bool WAIT = true>
__device__ __forceinline__ unsigned get_tag(uint32_t sb) {
  if (WAIT) mbar_wait(sb + BAR_EPOCH, 0);
  unsigned t; asm volatile("ld.shared.u32 %0, [%1];" : "=r"(t) : "r"(sb + OFF_EPOCH) : "memory");
  return t;
}

__device__ __forceinline__ int lane_id() { int l; asm volatile("mov.u32 %0, %%laneid;" : "=r"(l)); return l; }
__device__ __forceinline__ unsigned seq4(unsigned tag, int L) { return 8u | ((tag & 1u) << 2) | (unsigned)L; }
constexpr float LOG2E = 1.4426950408889634f;

__device__ __forceinline__ float bb_fence(int never) { while (never < 0) never = ld_flag(&g_ctr + never); return __int_as_float(never >> 30); }
__device__ __forceinline__ void bb_keep(const float* v, int never) {
  while (never < 0) {
#pragma unroll
    for (int q = 0; q < 32; q += 4) sts128(never + q * 4, __float_as_uint(v[q]), __float_as_uint(v[q + 1]), __float_as_uint(v[q + 2]), __float_as_uint(v[q + 3]));
    never = ld_flag(&g_ctr + never);
  }
}
constexpr uint32_t HA128 = 0x40000040u, HA64 = 0x80000040u;
struct Ctx {
  static constexpr uint32_t sb = SB;
  uint32_t ab, da0;
  int w, warp, lane, g, c;
  int goff;
  __device__ __forceinline__ int m() const { return goff >> 14; }
  __device__ __forceinline__ int j() const { return (goff >> 4) & 7; }
  bool elected;
  Ring ra, rb;
  uint32_t pa, pb;
  uint32_t ha, k2;
  uint32_t mrow, mxor, mhi;
  __device__ __forceinline__ uint32_t aslot(uint32_t s) const { return ab + s * SLOT; }
  __device__ __forceinline__ uint32_t fullA(uint32_t s) const { return sb + BAR_FULLA + s * 8; }
  __device__ __forceinline__ uint32_t fullB(uint32_t s) const { return sb + BAR_FULLB + s * 8; }
  __device__ __forceinline__ void releaseA(uint32_t s) const { if (elected) mbar_arrive(sb + BAR_EMPTYA + s * 8); }
  __device__ __forceinline__ void releaseB(uint32_t s) const { if (elected) mbar_arrive(sb + BAR_EMPTYB + s * 8); }
  __device__ __forceinline__ uint32_t maddr(uint32_t tile, uint32_t ch) const { return tile + mrow + (((ch + mhi) ^ mxor) << 4); }
  __device__ __forceinline__ uint32_t oo() const { return warp * 128 + g * 4 + (c ^ (g >> 1)); }
  __device__ __forceinline__ uint4* img(int b, int hp) const { return (IP & 1) ? ip + (b * 256 + hp) * 1024 : &g_img[b][m()][2 * j() + hp][w * 512 + oo()]; }
  uint4* ip;
  __device__ __forceinline__ uint32_t held(int i) const { return ra.s + i < 2 ? ra.s + i + NA - 2 : ra.s + i - 2; }
};

template <int N, bool FIRST, bool O = true>
__device__ __forceinline__ void gemm_issue(float (&acc)[N / 2], Ctx& x, bool ready = false) {
  if (!ready) {
    if (N == 256) mbar_wait3(x.fullA(x.ra.s), x.ra.ph, x.fullB(x.rb.s), x.rb.ph);
    else mbar_wait2(x.fullA(x.ra.s), x.ra.ph, x.fullB(x.rb.s), x.rb.ph);
  }
  const uint32_t da = x.da0 + x.ra.s * (SLOT / 16), db = desc_lo(SB + OFF_B, 8192) + x.rb.s * (SLOT / 16);
  wgmma_fence();
#pragma unroll
  for (int k = 0; k < 4; k++) {
    const uint32_t a = da + (k >> 1) * (O ? 32 : x.k2) + (k & 1) * 2, ha = O ? HA64 : x.ha;
    if constexpr (N == 256) wgmma_ss_n256(acc, a, ha, db + 128 * k, !(FIRST && k == 0));
    else wgmma_ss_n128(acc, a, ha, db + 128 * k, !(FIRST && k == 0));
  }
  wgmma_commit();
}
template <int N>
__device__ __forceinline__ void gemm_next(Ctx& x) {
  x.pa = x.ra.s; x.pb = x.rb.s;
  if (N == 256) x.rb.s++;
  adv<NA>(x.ra); adv<NB>(x.rb);
}
template <int N>
__device__ __forceinline__ void gemm_release(Ctx& x, bool relA) {
  if (relA) x.releaseA(x.pa);
  x.releaseB(x.pb);
  if (N == 256) x.releaseB(x.pb + 1);
}
template <int N>
__device__ __forceinline__ void gemm_retire(Ctx& x, bool relA) { wgmma_wait<1>(); gemm_release<N>(x, relA); gemm_next<N>(x); }
template <bool O = true>
__device__ __forceinline__ void gemm_run(float (&acc)[64], Ctx& x, int n, int hold, int n4 = 0) {
  bool ready = false;
#pragma unroll 1
  for (; n > 0; n--) {
    gemm_issue<128, false, O>(acc, x, ready);
    const uint32_t pa = x.pa, pb = x.pb;
    gemm_next<128>(x);
    ready = mbar_probe2(x.fullA(x.ra.s), x.ra.ph, x.fullB(x.rb.s), x.rb.ph);
    wgmma_wait<1>();
    if (n > hold) x.releaseA(pa);
    x.releaseB(pb);
  }
}
__device__ __forceinline__ void gemm_end(float (&acc)[64], Ctx& x) { wgmma_wait<0>(); fence_regs(acc); gemm_release<128>(x, false); }

__device__ __forceinline__ void rows_load(uint4* r, uint32_t tile, const Ctx& x) {
#pragma unroll
  for (int q = 0; q < 4; q++) {
    const uint32_t row = x.warp * 16 + 4 * q + (x.lane >> 3);
    lds128(tile + row * 128 + (((x.lane & 7) ^ (row & 7)) << 4), r[q].x, r[q].y, r[q].z, r[q].w);
  }
}
__device__ __forceinline__ void rows_store(const uint4* r, uint4* g, const Ctx& x) {
  g += (x.warp * 16 + (x.lane >> 3)) * 256 + (x.lane & 7);
#pragma unroll
  for (int q = 0; q < 4; q++) g[q * 1024] = r[q];
}
__device__ __forceinline__ void publish(int id, const Ctx& x) { __syncwarp(); if (x.lane == 0) mbar_arrive(x.sb + BAR_SIGP + id * 8); }
__device__ __forceinline__ void img_store(const uint4 (&r)[4], uint4* g) {
#pragma unroll
  for (int q = 0; q < 4; q++) stg128(g + q * 32, r[q]);
}
__device__ __forceinline__ void img_sts(const uint4 (&r)[4], uint32_t tile, const Ctx& x) {
#pragma unroll
  for (int q = 0; q < 4; q++) sts128(tile + x.oo() * 16 + q * 512, r[q].x, r[q].y, r[q].z, r[q].w);
}
__device__ __forceinline__ void img_load(uint32_t (&v)[16], uint32_t tile, const Ctx& x) {
#pragma unroll
  for (int q = 0; q < 4; q++) lds128(tile + x.oo() * 16 + q * 512, v[4 * q], v[4 * q + 1], v[4 * q + 2], v[4 * q + 3]);
}
__device__ __forceinline__ void img_unpack(float* a, const uint32_t (&v)[16]) {
#pragma unroll
  for (int q = 0; q < 16; q++) { a[4 * (q & 7) + 2 * (q >> 3)] = lo16(v[q]); a[4 * (q & 7) + 2 * (q >> 3) + 1] = hi16(v[q]); }
}

template <int N>
__device__ __forceinline__ void stats_acc(const float* a, float (&t)[4]) {
#pragma unroll
  for (int i = 0; i < N; i++) { t[i & 2] += a[i]; t[(i & 2) + 1] = fmaf(a[i], a[i], t[(i & 2) + 1]); }
}
__device__ __forceinline__ void stats_send(float (&t)[4], int L, const Ctx& x) {
  const unsigned seq = seq4(get_tag<false>(x.sb), L);
#pragma unroll
  for (int q = 0; q < 4; q++) t[q] = qsum(t[q]);
  if (x.c == 0) st_pkt(&g_stats[x.m()][x.w][x.j()][x.warp * 8 + x.g], __float_as_uint(t[0]), __float_as_uint(t[1]), __float_as_uint(t[2]), (__float_as_uint(t[3]) & ~15u) | seq);
}
__device__ __forceinline__ void out_epilogue(const float (&acc)[64], uint4 (&r1)[4], float (&t)[4], uint4* g, int L, Ctx& x) {
  const uint32_t t0 = x.aslot(x.ra.s), t1 = x.aslot(x.ra.s + 1 == NA ? 0 : x.ra.s + 1);
  if (L == 3) {
#pragma unroll
    for (int p = 0; p < 8; p++) {
      stsm4(x.maddr(p < 4 ? t0 : t1, (p & 3) * 2), pack2(acc[8 * p], acc[8 * p + 1]), pack2(acc[8 * p + 2], acc[8 * p + 3]),
            pack2(acc[8 * p + 4], acc[8 * p + 5]), pack2(acc[8 * p + 6], acc[8 * p + 7]));
      if ((p & 3) == 3) { uint4 r[4]; __syncwarp(); rows_load(r, p < 4 ? t0 : t1, x); rows_store(r, g + (p >> 2) * 8, x); }
    }
  } else {
    auto pack16 = [&](uint4 (&r)[4], const float* a) {
#pragma unroll
      for (int q = 0; q < 4; q++) { const float* u = a + 16 * (q & 1) + (q & 2); r[q] = make_uint4(pack2(u[0], u[1]), pack2(u[4], u[5]), pack2(u[8], u[9]), pack2(u[12], u[13])); }
    };
    uint4 r0[4];
    pack16(r0, acc);
    img_store(r0, x.img(XBUF(L + 1), 0));
    publish(2, x);
    const float z0 = bb_fence(x.goff), z = (IP & 2) ? z0 : 0.f;
    img_sts(r0, t0, x);
    pack16(r1, acc + 32);
    img_sts(r1, t1, x);
    float u[4] = {z, z, z, z}, v[4] = {z, z, z, z};
    stats_acc<32>(acc, v); stats_acc<32>(acc + 32, u);
#pragma unroll
    for (int q = 0; q < 4; q++) t[q] = u[q] + v[q];
    mbar_wait2(x.fullB(x.rb.s), x.rb.ph, x.fullB(x.rb.s + 1), x.rb.ph);
    fence_async_smem();
    asm volatile("bar.sync %0, %1;" ::"r"(L == 1 ? x.w + 1 : 3), "r"(L == 1 ? 128 : 256) : "memory");
  }
}

struct Stats { float rstd0, rstd1; };
__device__ __forceinline__ Stats load_stats(int half, const Ctx& x) {
  const float2 u = lds64f(x.sb + OFF_MR + half * 256 + (x.warp * 8 + x.g) * 8);
  return {u.x, u.y};
}

template <int NK>
__device__ __forceinline__ void hedgehog_scale(float* t, const Stats& st, const uint32_t* keep) {
#pragma unroll
  for (int q = 0; q < 16; q++) t[q] *= ((q & 2) ? st.rstd1 : st.rstd0) * LOG2E;
  float m[4];
#pragma unroll
  for (int q = 0; q < 4; q++) m[q] = fmaxf(fmaxf(fabsf(t[4 * q]), fabsf(t[4 * q + 1])), fmaxf(fabsf(t[4 * q + 2]), fabsf(t[4 * q + 3])));
  if (__builtin_expect(__any_sync(0xffffffffu, fmaxf(fmaxf(m[0], m[1]), fmaxf(m[2], m[3])) > 58.f), 0)) {
    float z[16 + NK];
#pragma unroll
    for (int q = 0; q < 16 + NK; q++) z[q] = q < 16 ? t[q & 15] : __uint_as_float(keep[q & 15]);
#pragma unroll 1
    for (int r = 0; r < 4; r += 2) {
      float hi = -INFINITY, lo = INFINITY;
#pragma unroll 1
      for (int i = 0; i < 16; i++) {
        const int k = (i & 6) * 2 + (i & 1) + r;
        const float v = z[k];
        if (i < 8) { hi = fmaxf(hi, v); lo = fminf(lo, v); }
        else z[k] = v - fminf(fmaxf(v, lo), hi);
        if (i == 7) {
#pragma unroll 1
          for (int d = 1; d <= 2; d++) { hi = fmaxf(hi, __shfl_xor_sync(0xffffffffu, hi, d)); lo = fminf(lo, __shfl_xor_sync(0xffffffffu, lo, d)); }
          const float mid = 0.5f * hi + 0.5f * lo;
          hi = fmaxf(hi - 58.f, mid); lo = fminf(lo + 58.f, mid);
        }
      }
    }
#pragma unroll
    for (int q = 0; q < 16; q++) t[q] = z[q];
  }
}
__device__ __forceinline__ void dual_exp(const float* t, uint32_t (&f)[18], int never) {
  float e[KSPLIT];
#pragma unroll
  for (int q = 0; q < KSPLIT; q++) e[q] = ex2(q < 16 ? t[q] : -t[q & 15]);
  while (never < 0) {
#pragma unroll
    for (int i = 0; i < KSPLIT; i += 4) asm volatile("ld.shared.v4.f32 {%0,%1,%2,%3}, [%4];" : "=f"(e[i]), "=f"(e[i + 1]), "=f"(e[i + 2]), "=f"(e[i + 3]) : "r"(never + i) : "memory");
    never += __float_as_int(e[0]);
  }
#pragma unroll
  for (int q = 0; q < KSPLIT; q += 2) f[q >> 1] = pack2(e[q], e[q + 1]);
#pragma unroll
  for (int q = KSPLIT; q < 32; q += 2) f[q >> 1] = q < 16 ? pack2(ex2(t[q]), ex2(t[q + 1])) : pack2(ex2(-t[q & 15]), ex2(-t[(q & 15) + 1]));
#pragma unroll
  for (int sg = 0; sg < 2; sg++) {
    const uint32_t* u = f + 8 * sg;
    const uint32_t a = add2(add2(u[0], u[2]), add2(u[4], u[6])), b = add2(add2(u[1], u[3]), add2(u[5], u[7]));
    f[16 + sg] = add2(__byte_perm(a, b, 0x5410), __byte_perm(a, b, 0x7632));
  }
}
__device__ __forceinline__ void dual_exp_rcp(const float* t, uint32_t (&f)[16]) {
#pragma unroll
  for (int q = 0; q < 8; q++) {
    const float a = ex2(t[2 * q]), b = ex2(t[2 * q + 1]), r = rcp(a * b);
    f[q] = pack2(a, b); f[8 + q] = pack2(r * b, r * a);
  }
}
__device__ __forceinline__ void cta_bar() { asm volatile("bar.sync 3, 256;" ::: "memory"); }

template <int N> __device__ __forceinline__ void pin(const uint32_t* v, uint32_t addr) {
#pragma unroll
  for (int i = 0; i < N; i += 4)
    asm volatile("{\n.reg .pred p;\nsetp.eq.u32 p, %0, 0;\n@p st.shared.v4.u32 [%0], {%1,%2,%3,%4};\n}" ::"r"(addr), "r"(v[i]), "r"(v[i + 1]), "r"(v[i + 2]), "r"(v[i + 3]) : "memory");
}

__device__ __forceinline__ void consumer(const Params& P, uint32_t sb, int w, unsigned vb) {
  Ctx x;
  x.w = w;
  x.ab = sb + OFF_A + w * 8192; x.da0 = desc_lo(SB + OFF_A, 16) + w * 512;
  x.lane = threadIdx.x & 31; x.warp = __shfl_sync(0xffffffffu, (threadIdx.x >> 5) & 3, 0); x.g = x.lane >> 2; x.c = x.lane & 3;
  x.goff = (cta_m(vb) * 128 + w) * 128 + cta_j(vb) * 16;
  asm volatile("" : "+r"(x.goff));
  x.elected = (threadIdx.x & 127) == 0;
  x.ra = {0, 0}; x.rb = {0, 0}; x.pa = x.pb = 0;
  {
    const uint32_t row = x.warp * 16 + (x.lane & 15);
    x.mrow = row * 128; x.mxor = row & 7; x.mhi = x.lane >> 4;
  }
  const int goff = x.goff;
  x.ip = (uint4*)__shfl_sync(0xffffffffu, (unsigned long long)&g_img[0][x.m()][2 * x.j()][w * 512 + x.oo()], x.lane);
  uint4 r1[4];
  float ts[4] = {0.f, 0.f, 0.f, 0.f};
#pragma unroll
  for (int i = 0; i < 4; i++) r1[i] = make_uint4(0, 0, 0, 0);
  TSW(0);
  mbar_wait3(x.fullA(0), 0, x.fullB(0), 0);
#pragma unroll 1
  for (int L = 0; L < 4; L++) {
    float acc[64];
    constexpr uint32_t dcs = desc_lo(SB + OFF_CS, 0);
    if ((L & 1) == 0) {
    float kv[128];
    x.ha = L ? HA64 : HA128; x.k2 = L ? 32 : 4;
    gemm_issue<256, true, false>(kv, x, true); gemm_next<256>(x);
    {
      int i = 1;
#pragma unroll 1
      for (int seg = L ? NS - 1 : 0; seg <= NS; seg++) {
        const int end = seg < NS ? (L == 0 ? 3 + SA * ((x.j() + SW * w) & 3) + SB_ * seg : XA + 1) : 14 + L;
#pragma unroll 1
        do {
          gemm_issue<256, false, false>(kv, x);
          gemm_retire<256>(x, true);
          i++;
          if (i == 5) TSL_(8);
          if (i == 11) TSL_(10);
        } while (i != end);
        if (seg < NS && L == 0) {
          uint32_t v[16];
          float a[32];
#pragma unroll
          for (int q = 0; q < 4; q++) ldsm4(x.maddr(x.aslot(x.pa), 2 * q), reinterpret_cast<uint32_t (&)[4]>(v[4 * q]));
#pragma unroll
          for (int q = 0; q < 16; q++) { a[2 * q] = lo16(v[q]); a[2 * q + 1] = hi16(v[q]); }
          stats_acc<32>(a, ts);
          fence_regs(ts);
          wg_bar(w);
        }
        if (seg == NS - 1) {
          if (L > 0) { img_store(r1, x.img(XBUF(L), 1)); publish(3, x); }
          mbar_wait(sb + BAR_EPOCH, 0);
          stats_send(ts, L, x);
        }
      }
    }
      const Ring kt = x.ra;
      if (L == 0) adv<NA>(x.ra);
#pragma unroll 1
      for (int h = L; h < 2; h++) {
        float d[16];
        mbar_wait2(x.fullA(kt.s), kt.ph, sb + BAR_WPHI, 0);
        wgmma_fence();
#pragma unroll
        for (int q = 0; q < 2; q++) wgmma_ss_n32(d, x.da0 + kt.s * (SLOT / 16) + h * 4 + q * 2, desc_lo(SB + OFF_S + 4096, 512) + w * 256 + h * 128 + q * 64, q);
        wgmma_commit();
        gemm_issue<256, false, false>(kv, x);
        gemm_retire<256>(x, true);
        if (h) x.releaseA(kt.s);
        fence_regs(d);
        uint4* dst = &g_wf[1][x.j()][x.m()][w * 512 + (x.warp * 16 + x.g) * 8 + ((h * 4 + x.c) ^ x.g)];
        dst[0] = make_uint4(pack2(d[0], d[1]), pack2(d[4], d[5]), pack2(d[8], d[9]), pack2(d[12], d[13]));
        dst[64] = make_uint4(pack2(d[2], d[3]), pack2(d[6], d[7]), pack2(d[10], d[11]), pack2(d[14], d[15]));
      }
      const uint32_t dm = desc_lo(SB + OFF_MA, 0) + w * 64;
      mbar_wait2(sb + BAR_STAT, 0, sb + BAR_CS, 0);
      wgmma_fence();
      wgmma_r1_n256(kv, dm, dcs + 96, 1);
      wgmma_commit();
      const Stats st = load_stats(w, x);
      if (PW & 1) mbar_wait2(x.fullA(x.ra.s), x.ra.ph, x.fullB(x.rb.s), x.rb.ph);
      wgmma_wait<0>();
      fence_regs(kv);
      gemm_release<256>(x, true);
      TSL_(2);
      uint32_t P0[32], P1[32], PH[32];
#pragma unroll
      for (int t = 0; t < 16; t++) { P0[t] = pack2(kv[4 * t] * st.rstd0, kv[4 * t + 1] * st.rstd0); P1[t] = pack2(kv[4 * t + 2] * st.rstd1, kv[4 * t + 3] * st.rstd1); }
      pin<16>(P0, x.mrow + 16);
      {
#pragma unroll
        for (int q = 0; q < 4; q++) sts128((x.warp < 3 ? sb + OFF_T + w * 12288 + x.warp * 4096 : sb + OFF_S + 16384 + w * 2048) + x.lane * 16 + q * 512, P1[4 * q], P1[4 * q + 1], P1[4 * q + 2], P1[4 * q + 3]);
      }
      wgmma_fence();
      wgmma_r1_n128(acc, dm, dcs, 0);
      gemm_issue<128, false, false>(acc, x, PW & 1); gemm_next<128>(x);
      TSL_(3);
#pragma unroll
      for (int s = 0; s < 4; s++) {
#pragma unroll
        for (int t = 16 + 8 * (s & 1); t < 24 + 8 * (s & 1); t++) {
          if (s < 2) P1[t] = movm(pack2(kv[4 * t + 2] * st.rstd1, kv[4 * t + 3] * st.rstd1));
          else P0[t] = movm(pack2(kv[4 * t] * st.rstd0, kv[4 * t + 1] * st.rstd0));
        }
        if (s < 3) { gemm_issue<128, false, false>(acc, x); gemm_retire<128>(x, true); }
        if (s == 1) {
          if (x.warp < 3) {
#pragma unroll
            for (int q = 4; q < 8; q++) sts128(sb + OFF_T + w * 12288 + x.warp * 4096 + x.lane * 16 + q * 512, P1[4 * q], P1[4 * q + 1], P1[4 * q + 2], P1[4 * q + 3]);
          } else {
            uint4* dst = &g_halo[x.m()][x.j()][w][x.lane];
#pragma unroll
            for (int q = 0; q < 8; q++) dst[q * 32] = make_uint4(P1[4 * q], P1[4 * q + 1], P1[4 * q + 2], P1[4 * q + 3]);
          }
          publish(4, x);
          gemm_issue<128, false, false>(acc, x);
          gemm_retire<128>(x, true);
        }
      }
      TSL_(4);
      gemm_run<false>(acc, x, 10, 0);
      gemm_issue<128, false, false>(acc, x);
      {
        wg_bar(w);
        uint32_t tr = sb + OFF_T + w * 12288 + (x.warp - 1) * 4096;
        if (x.warp == 0) {
          tr = x.m() > 0 ? sb + OFF_S + 8192 + w * 4096 : tr + 4096;
          if (x.m() > 0) mbar_wait(sb + BAR_HALO, L >> 1);
        }
#pragma unroll
        for (int q = 0; q < 8; q++) lds128(tr + x.lane * 16 + q * 512, PH[4 * q], PH[4 * q + 1], PH[4 * q + 2], PH[4 * q + 3]);
      }
      gemm_retire<128>(x, false);
      gemm_end(acc, x);
      TSL_(5);
      const bool first = (x.m() == 0) && (x.warp == 0);
      const bool hi0 = 2 * x.c > x.g, hi1 = 2 * x.c + 1 > x.g;
      const uint32_t mhi = (hi0 ? 0xFFFFu : 0u) | (hi1 ? 0xFFFF0000u : 0u);
      const float sc0 = st.rstd0 * (0.17677669529663687f * LOG2E), sc1 = st.rstd1 * (0.17677669529663687f * LOG2E);
#pragma unroll
      for (int hp = 0; hp < 2; hp++) {
        const uint32_t tile = x.aslot(x.held(hp));
        uint32_t px[2], py[2];
        float s[2][3][4];
#pragma unroll
        for (int u = 0; u < 2; u++) {
#pragma unroll
          for (int q = 0; q < 12; q++) s[u][q >> 2][q & 3] = 0.f;
#pragma unroll
          for (int ks = 0; ks < 2; ks++) {
            const int t = 8 * hp + 4 * u + 2 * ks;
            const uint32_t a0 = pack2(acc[4 * t], acc[4 * t + 1]), a1 = pack2(acc[4 * t + 2], acc[4 * t + 3]);
            const uint32_t a2 = pack2(acc[4 * t + 4], acc[4 * t + 5]), a3 = pack2(acc[4 * t + 6], acc[4 * t + 7]);
            mma16816(s[u][0], a0, a1, a2, a3, PH[t], PH[t + 1]);
            mma16816(s[u][1], a0, a1, a2, a3, P0[t], P0[t + 1]);
            mma16816(s[u][2], a0, a1, a2, a3, P1[t], P1[t + 1]);
          }
        }
        float e[2][4], r[2][2];
#pragma unroll
        for (int u = 0; u < 2; u++) {
          e[u][0] = (hi0 ? s[u][0][0] : s[u][1][0]) * sc0; e[u][1] = (hi1 ? s[u][0][1] : s[u][1][1]) * sc0;
          e[u][2] = (hi0 ? s[u][1][2] : s[u][2][2]) * sc1; e[u][3] = (hi1 ? s[u][1][3] : s[u][2][3]) * sc1;
          if (first) { if (hi0) e[u][0] = -1e30f; if (hi1) e[u][1] = -1e30f; }
          r[u][0] = fmaxf(e[u][0], e[u][1]); r[u][1] = fmaxf(e[u][2], e[u][3]);
        }
#pragma unroll
        for (int d = 1; d <= 2; d++)
#pragma unroll
          for (int q = 0; q < 4; q++) r[q >> 1][q & 1] = fmaxf(r[q >> 1][q & 1], __shfl_xor_sync(0xffffffffu, r[q >> 1][q & 1], d));
#pragma unroll
        for (int u = 0; u < 2; u++) {
#pragma unroll
          for (int q = 0; q < 4; q++) e[u][q] = ex2(e[u][q] - r[u][q >> 1]);
          r[u][0] = e[u][0] + e[u][1]; r[u][1] = e[u][2] + e[u][3];
        }
#pragma unroll
        for (int d = 1; d <= 2; d++)
#pragma unroll
          for (int q = 0; q < 4; q++) r[q >> 1][q & 1] += __shfl_xor_sync(0xffffffffu, r[q >> 1][q & 1], d);
#pragma unroll
        for (int u = 0; u < 2; u++) {
          const float rx = rcp(r[u][0]), ry = rcp(r[u][1]);
          px[u] = pack2(e[u][0] * rx, e[u][1] * rx); py[u] = pack2(e[u][2] * ry, e[u][3] * ry);
        }
        uint32_t o[8][2];
        uint4 ro[4];
#pragma unroll
        for (int q = 0; q < 8; q++) {
          float d[4] = {0.f, 0.f, 0.f, 0.f};
          const int t = 16 + 8 * hp + q, u = q >> 2;
          mma16816(d, px[u] & mhi, 0u, px[u] & ~mhi, py[u] & mhi, PH[t], P0[t]);
          mma1688(d, 0u, py[u] & ~mhi, P1[t]);
          o[q][0] = pack2(d[0], d[1]); o[q][1] = pack2(d[2], d[3]);
        }
#pragma unroll
        for (int q = 0; q < 4; q++) ro[q] = make_uint4(o[4 * (q & 1)][q >> 1], o[4 * (q & 1) + 1][q >> 1], o[4 * (q & 1) + 2][q >> 1], o[4 * (q & 1) + 3][q >> 1]);
        img_store(ro, x.img(0, hp));
        publish(hp, x);
        uint32_t xr[16];
        if (L) img_load(xr, tile, x);
        else {
#pragma unroll
          for (int q = 0; q < 4; q++) {
            uint32_t v[4];
            ldsm4(x.maddr(tile, 2 * q), v);
            xr[2 * q] = v[0]; xr[8 + 2 * q] = v[1]; xr[2 * q + 1] = v[2]; xr[9 + 2 * q] = v[3];
          }
          __syncwarp();
        }
        img_sts(ro, tile, x);
        img_unpack(acc + 32 * hp, xr);
      }
    } else {
      float kv[128];
      float (&kv0)[64] = reinterpret_cast<float (&)[64]>(kv[0]);
      float (&kv1)[64] = reinterpret_cast<float (&)[64]>(kv[64]);
      auto mma8 = [&](uint32_t as, uint32_t bs, int i, bool fence) {
        const uint32_t da = desc_lo(SB + OFF_A, 16) + as * (SLOT / 16), db = desc_lo(SB + OFF_B, 8192) + bs * (SLOT / 16);
        if (fence) wgmma_fence();
#pragma unroll
        for (int k = 0; k < 4; k++) {
          wgmma_ss_n128(kv0, da + (k >> 1) * 32 + (k & 1) * 2, HA64, db + 128 * k, i + k);
          wgmma_ss_n128(kv1, da + 512 + (k >> 1) * 32 + (k & 1) * 2, HA64, db + 128 * k, i + k);
        }
        wgmma_commit();
      };
      constexpr uint32_t dm = desc_lo(SB + OFF_MB, 0);
      auto relB = [&](uint32_t s) { mbar_arrive_n(sb + BAR_EMPTYB + s * 8, 2); };
      auto skip = [&]() {
#pragma unroll
        for (int q = 0; q < 6 - NJ; q++) adv<NA>(x.ra);
        x.rb.s = w ? (2 + NJ) % 6 : 4;
        if (!w && NJ < 4) x.rb.ph ^= 1;
      };
      static_assert(NA == 5 && NB == 6, "ring arithmetic");
      mma8(x.ra.s, x.rb.s + w, 0, true);
      gemm_next<256>(x);
#pragma unroll 1
      for (int i = 1; i < NJ; i++) {
        mbar_wait2(x.fullA(x.ra.s), x.ra.ph, x.fullB(x.rb.s + w), x.rb.ph);
        mma8(x.ra.s, x.rb.s + w, 1, true);
        if (!XO && i == XR) { img_store(r1, x.img(XBUF(L), 1)); publish(3, x); }
        if (!XO && i == XS) stats_send(ts, L, x);
        wgmma_wait<1>();
        if (x.elected) { x.releaseA(x.pa); relB(x.pb + w); }
        gemm_next<256>(x);
        if (XO && i == XR) { img_store(r1, x.img(XBUF(L), 1)); publish(3, x); stats_send(ts, L, x); }
      }
      if (w) {
        wgmma_wait<0>();
        if (x.elected) { x.releaseA(x.pa); relB(x.pb + 1); }
        skip();
        asm volatile("bar.sync 7, 256;" ::: "memory");
      }
      TSL_(8);
      {
        const int t = lane_id() + 32 * x.warp;
        uint32_t mask = t < 2 ? ((w ? (t ? 0xFF3Fu : 0x3FFFu) : 0xFFFFu) >> (NJ - 1)) & (w ? ~1u : ~0u) : 0u, cnt = 1 + t;
        bool ready = false;
#pragma unroll 1
        for (int i = NJ; i < 16; i++) {
          if (!ready) mbar_wait2(x.fullA(x.ra.s), x.ra.ph, x.fullB(x.rb.s), x.rb.ph);
          mma8(x.ra.s, x.rb.s, 1, true);
          const uint32_t bar = sb + (t ? BAR_EMPTYB + x.pb * 8 : BAR_EMPTYA + x.pa * 8);
          gemm_next<128>(x);
          if (w && (i | 4) == 15) x.rb.s = 4;
          ready = mbar_probe2(x.fullA(x.ra.s), x.ra.ph, x.fullB(x.rb.s), x.rb.ph);
          wgmma_wait<1>();
          if (mask & 1) mbar_arrive_n(bar, cnt);
          mask >>= 1; cnt = 2;
          if (i == 8 && w) asm volatile("bar.arrive 9, 256;" ::: "memory");
          if (i == 9) TSL_(10);
        }
        mbar_wait2(sb + BAR_STAT, 1, sb + BAR_CS + 8, 0);
        wgmma_fence();
        wgmma_r1_n128(kv0, dm, dcs + 96 + 96 * w, 1);
        wgmma_r1_n128(kv1, dm + 64, dcs + 96 + 96 * w, 1);
        wgmma_commit();
        if (w == 0) asm volatile("bar.arrive 7, 256;" ::: "memory");
        wgmma_wait<1>();
        if (mask & 1) mbar_arrive_n(sb + (t ? BAR_EMPTYB + x.pb * 8 : BAR_EMPTYA + x.pa * 8), 2);
      }
      const Stats s0 = load_stats(0, x), s1 = load_stats(1, x), st = w ? s1 : s0;
      if (w == 0) skip();
      const uint32_t h0 = x.held(0), h1 = x.held(1);
      auto vreg = [&](int ks) { return ks < 6 ? OFF_A + (ks < 3 ? h0 * SLOT : h1 * SLOT - 15360) + ks * 5120 : OFF_S + 2048 + ks * 5120; };
      uint32_t tV[2], uu[4];
#pragma unroll
      for (int hf = 0; hf < 2; hf++) {
        tV[hf] = sb + vreg(4 * hf + x.warp) + ((x.lane >> 3) & 1) * 2560 + (x.lane & 7) * 16 + x.mhi * 128;
        const float i0 = rcp(hf ? s1.rstd0 : s0.rstd0), i1 = rcp(hf ? s1.rstd1 : s0.rstd1);
        const uint32_t h = pack2(i0, i1);
        uu[2 * hf] = pack2(lo16(h), i0 - lo16(h)); uu[2 * hf + 1] = pack2(hi16(h), i1 - hi16(h));
        asm volatile("" : "+r"(tV[hf]), "+r"(uu[2 * hf]), "+r"(uu[2 * hf + 1])::"memory");
      }
      wgmma_wait<0>();
      fence_regs(kv);
      TSL_(2);
      if (w == 0) {
        uint32_t f[2][18], ad[4];
#pragma unroll
        for (int q = 0; q < 18; q++) f[1][q] = 0u;
#pragma unroll
        for (int q = 0; q < 4; q++) ad[q] = x.maddr(sb + OFF_S, 2 * q);
        auto norm = [&](int un) {
          uint32_t* u = f[un & 1];
          const Stats& sn = (un & 2) ? s1 : s0;
#pragma unroll
          for (int sg = 0; sg < 2; sg++) {
            uint32_t v = u[16 + sg];
            v = add2(v, __shfl_xor_sync(0xffffffffu, v, 1)); v = add2(v, __shfl_xor_sync(0xffffffffu, v, 2));
            const float a = rcp(lo16(v)) * sn.rstd0, b = rcp(hi16(v)) * sn.rstd1;
            const uint32_t r0 = pack2(a, a), r1_ = pack2(b, b);
#pragma unroll
            for (int q = 8 * sg; q < 8 * sg + 8; q++) u[q] = mul2(u[q], (q & 1) ? r1_ : r0);
#pragma unroll
            for (int q = 2 * sg; q < 2 * sg + 2; q++) stsm4(ad[q] + (un & 1) * SLOT + (un >> 1) * 8192, u[4 * q], u[4 * q + 1], u[4 * q + 2], u[4 * q + 3]);
          }
        };
        auto unit = [&](int un) { return kv + ((un >> 1) & 1) * 64 + (un & 1) * 16 + (un >> 2) * 32; };
        hedgehog_scale<0>(kv, s0, nullptr);
#pragma unroll 1
        for (int it = 0;; it++) {
#pragma unroll
          for (int un = 0; un < 4; un++) {
            if (un == 1) {
              if (it) asm volatile("bar.sync 9, 256;" ::: "memory");
#pragma unroll
              for (int q = 0; q < 4; q++) ad[q] -= it * (OFF_S - OFF_B - 2 * SLOT);
            }
            norm((un + 3) & 3);
            dual_exp(unit(un), f[un & 1], x.goff);
            hedgehog_scale<KEEP>(unit(un + 1), ((un + 1) & 2) ? s1 : s0, f[(un + 1) & 1]);
          }
          if (it) break;
#pragma unroll
          for (int q = 0; q < 32; q++) {
            asm volatile("mov.b32 %0, %1;" : "=f"(kv[q]) : "f"(kv[q + 32]));
            asm volatile("mov.b32 %0, %1;" : "=f"(kv[q + 64]) : "f"(kv[q + 96]));
            if (q < 16) kv[32 + q] = 0.f;
          }
        }
        norm(3);
        TSL_(3);
      } else {
        wg_bar(w);
#pragma unroll
        for (int hf = 0; hf < 2; hf++) {
          stsm4(tV[hf] + 512 + x.mhi * 512, uu[2 * hf], uu[2 * hf + 1], uu[2 * hf], uu[2 * hf + 1]);
          stsm4(tV[hf] + 1792 + x.mhi * 512, uu[2 * hf], uu[2 * hf + 1], uu[2 * hf], uu[2 * hf + 1]);
#pragma unroll
          for (int q = 0; q < 8; q++) {
            const float* u = kv + 64 * hf + 8 * q;
            stsm4(tV[hf] + (q >> 1) * 640 + (q & 1) * 256, pack2(u[0], u[1]), pack2(u[2], u[3]), pack2(u[4], u[5]), pack2(u[6], u[7]));
          }
        }
        TSL_(3);
      }
      {
        float d[2][20];
        uint4* dst = &g_kvpart[x.j()][w * 4 + x.warp][0][x.m() * 32 + x.lane];
        unsigned* dz = reinterpret_cast<unsigned*>(&g_kvpart[x.j()][w * 4 + x.warp][x.c & 1][512]) + x.m() * 8 + x.g;
        asm volatile("" : "+l"(dst), "+l"(dz)::"memory");
        fence_async_smem();
        cta_bar();
        TSL_(11);
        uint32_t pk[9];
        auto prep = [&](float (&u)[20]) {
          fence_regs(u);
#pragma unroll
          for (int q = 0; q < 8; q++) pk[q] = pack2(u[((q >> 1) & 2) + 4 * (q & 3)], u[((q >> 1) & 2) + 4 * (q & 3) + 1]);
          pk[8] = __float_as_uint((x.c & 1) ? u[18] + u[19] : u[16] + u[17]);
#pragma unroll
          for (int q = 0; q < 9; q += 4) pk[q] = (pk[q] & ~1u) | (L == 1);
        };
        auto send = [&](int hp) {
          st_v4(dst + hp * 16 * 544, pk[0], pk[1], pk[2], pk[3]); st_v4(dst + (hp * 16 + 1) * 544, pk[4], pk[5], pk[6], pk[7]);
          st_flag(dz + hp * 16 * 544 * 4, pk[8]);
        };
        wgmma_fence();
#pragma unroll
        for (int q = 0; q < 17; q++) {
          if (q < 16) wgmma_ss_n40_tt(d[q >> 3], desc_lo(SB + (q < 8 ? OFF_S : OFF_B + 2 * SLOT), 1024) + w * (SLOT / 16) + 128 * (q & 7), desc_lo(SB + vreg(q & 7), 2560) + (w + (q >> 3) * 2) * 40, q & 7);
          else wgmma_r1_n128(acc, dm + w * 64, dcs, 0);
          if (q == 7 || q == KVS || q == 16) wgmma_commit();
          if (q == KVS) { wgmma_wait<1>(); prep(d[0]); send(0); mbar_wait2(x.fullA(x.ra.s), x.ra.ph, x.fullB(x.rb.s), x.rb.ph); wgmma_fence(); }
        }
        gemm_issue<128, false>(acc, x, true); gemm_next<128>(x);
        wgmma_wait<1>();
        x.releaseA(h0); x.releaseA(h1); x.releaseB(2); x.releaseB(3);
        if (x.lane == 0) mbar_arrive(sb + BAR_SIGT);
        prep(d[1]);
        TSL_(4);
#pragma unroll 1
        for (int seg = 0; seg < 2; seg++) {
          const int n0 = w ? PS1 : PS0;
          gemm_run(acc, x, seg ? 15 - n0 : n0, seg, seg ? L : 0);
          if (seg == 0) send(1);
        }
      }
      gemm_end(acc, x);
      TSL_(5);
      {
        float dp[2][20], dn[2][20];
        uint32_t f[4][16];
        auto mma = [&](int h) {
          if (!(h & 1)) mbar_wait(sb + BAR_KV + h * 4, L >> 1);
          if (h == 0) TSL_(9);
          const uint32_t db = desc_lo(SB + OFF_S + h * 5120, 128);
          const uint32_t (&a)[16] = f[h];
          wgmma_fence();
          wgmma_rs_n40(dp[h & 1], a[0], a[1], a[2], a[3], db, 0);
          wgmma_rs_n40(dn[h & 1], a[8], a[9], a[10], a[11], db + 160, 0);
          wgmma_rs_n40(dp[h & 1], a[4], a[5], a[6], a[7], db + 80, 1);
          wgmma_rs_n40(dn[h & 1], a[12], a[13], a[14], a[15], db + 240, 1);
          wgmma_commit();
        };
        uint32_t xr[16];
        auto fin = [&](int h) {
          const uint32_t tile = x.aslot(x.held(h >> 1));
          if (!(h & 1)) img_load(xr, tile, x);
          float (&u)[20] = dp[h & 1];
          float (&v)[20] = dn[h & 1];
          fence_regs(u); fence_regs(v);
#pragma unroll
          for (int r = 0; r < 2; r++) {
            const float sp = u[17 + 2 * r], sn = v[17 + 2 * r];
            const float id = rcp(fmaf(fmaf(sp, 0.065536f, u[16 + 2 * r]), sn, v[16 + 2 * r] * sp)), aa = sn * id, cc = sp * id;
            uint32_t o[4];
#pragma unroll
            for (int t = 0; t < 4; t++) o[t] = pack2(fmaf(u[4 * t + 2 * r], aa, v[4 * t + 2 * r] * cc), fmaf(u[4 * t + 2 * r + 1], aa, v[4 * t + 2 * r + 1] * cc));
            stg128(x.img(0, h >> 1) + r * 64 + (h & 1) * 32, make_uint4(o[0], o[1], o[2], o[3]));
            sts128(tile + r * 1024 + (h & 1) * 512 + x.oo() * 16, o[0], o[1], o[2], o[3]);
          }
          if (h & 1) { publish(h >> 1, x); img_unpack(acc + 16 * (h - 1), xr); }
        };
        auto scale = [&](int h) { hedgehog_scale<0>(acc + 16 * h, st, nullptr); };
        auto ex = [&](int h) { dual_exp_rcp(acc + 16 * h, f[h]); };
        scale(0);
        ex(0); scale(1); mma(0);
        ex(1); wgmma_wait<0>(); fin(0); bb_fence(x.goff); mma(1);
        wgmma_wait<0>(); fin(1); scale(2);
        ex(2); scale(3); if (UK & 1) bb_keep(acc, x.goff); mma(2);
        ex(3); wgmma_wait<0>(); fin(2); mma(3);
        wgmma_wait<0>(); fin(3);
      }
    }
    if (PW & 2) { mbar_wait(x.fullB(x.rb.s), x.rb.ph); fence_regs(acc); }
    fence_async_smem();
    wg_bar(w);
    TSL_(6);
    rewind2<NA>(x.ra);
    gemm_issue<128, false>(acc, x, PW & 2); gemm_next<128>(x);
#pragma unroll 1
    for (int seg = L >= TSL ? 0 : 1; seg < 2; seg++) {
      gemm_run(acc, x, L >= TSL ? (seg ? TSK : 15 - TSK) : 15, seg, 10 + L);
      if (L >= TSL) {
        if (seg == 0 && w == 1) asm volatile("bar.sync 6, 256;" ::: "memory");
        if (seg == 1 && w == 0) asm volatile("bar.arrive 6, 256;" ::: "memory");
      }
    }
    gemm_end(acc, x);
    TSL_(7);
    rewind2<NA>(x.ra);
    out_epilogue(acc, r1, ts, P.out + goff, L, x);
    TSL_(13);
  }
}

typedef unsigned long long u64;
template <class T> __device__ __forceinline__ T* early(T* p) { return (T*)__shfl_xor_sync(0xffffffffu, (u64)p, 1); }
__device__ __forceinline__ void pause(uint32_t GAP) {
  if (GAP) { uint32_t t0, t; asm volatile("mov.u32 %0, %%clock;" : "=r"(t0)); do { asm volatile("mov.u32 %0, %%clock;" : "=r"(t)); } while (t - t0 < GAP); }
}
__device__ __forceinline__ u64 order_table(int kind, int j) {
  const int i = threadIdx.x & 15;
  const unsigned v = (unsigned)(kind == 2 ? q_order(i, j) : kv_order(i, j, kind)) << (4 * (i & 7));
  return (u64)__reduce_or_sync(0xffffffffu, i < 8 ? 0u : v) << 32 | __reduce_or_sync(0xffffffffu, i < 8 ? v : 0u);
}

__device__ __forceinline__ void b_producer(const Params& P, uint32_t sb, unsigned vb) {
  const int j = cta_j(vb);
  const u64 t0 = order_table(0, j), t1 = order_table(1, j), t2 = order_table(2, j);
  Ring r = {PRE_B % NB, PRE_B < NB};
#pragma unroll 1
  for (int sg = 0; sg < 20; sg++) {
    const int L = sg / 5, p = sg - 5 * L, wt = L & 1;
    int n = p >= 3 ? 16 : (wt ? (p ? 16 - NJ : 2 * NJ) : (p ? 0 : (L ? 32 : 32 - PRE_B)));
    u64 tab = p == 3 ? t2 : (sg == 0 ? t0 >> (2 * PRE_B) : (p == 1 || p == 2 ? t1 >> (4 * NJ) : t1));
    const CUtensorMap* tm = p == 4 ? &P.mwo[wt] : &P.mw[wt ? 1 : L];
    const uint4* img = &g_wf[p != 3][j][0][0];
    int col = (p >= 3 ? 0 : (p == 2 ? 2048 : 1024)) + 128 * j;
    const int flip = p == 0 ? 3072 : 0;
    const bool fold = wt && p != 4;
    if (sg == 5 || sg == 8) { mbar_wait(sb + (sg == 5 ? BAR_WPHI : BAR_CS + 8), sg == 5); fence_async_global(); }
    if (DEFER && p == 4 && ((DEFL >> wt) & 1)) {
      Ring q = r;
      for (int u = 0; u < DEFER; u++) adv<NB>(q);
      mbar_wait(sb + BAR_EMPTYB + q.s * 8, q.ph);
    }
#pragma unroll 1
    for (; n > 0; n--) {
      const int kb = (int)tab & 15;
      mbar_wait(sb + BAR_EMPTYB + r.s * 8, r.ph);
      if (elect()) {
        mbar_expect_tx(sb + BAR_FULLB + r.s * 8, SLOT);
        if (fold && col < 2048) bulk_load(sb + OFF_B + r.s * SLOT, img + kb * 1024, SLOT, sb + BAR_FULLB + r.s * 8);
        else tma_load_w(sb + OFF_B + r.s * SLOT, tm, sb + BAR_FULLB + r.s * 8, col, kb);
      }
      adv<NB>(r);
      if (p == 2 && (n | 4) == 5) r.s = 4;
      col ^= flip;
      if (!(col & flip & 2048)) tab >>= 4;
    }
  }
}

__device__ __forceinline__ void a_loader(const Params& P, uint32_t sb, unsigned vb) {
  const int j = cta_j(vb), m = cta_m(vb);
  const u64 t1 = order_table(1, j), t2 = order_table(2, j);
  Ring r = {PRE_A % NA, PRE_A < NA};
  {
    u64 tab = order_table(0, j) >> (4 * PRE_A);
#pragma unroll 1
    for (int i = PRE_A; i < 33; i++) {
      if (i == 17) tab = t2;
      mbar_wait(sb + BAR_EMPTYA + r.s * 8, r.ph);
      if (elect()) {
        mbar_expect_tx(sb + BAR_FULLA + r.s * 8, SLOT);
        if (i != 14) tma_load_3d(sb + OFF_A + r.s * SLOT, &P.mx, sb + BAR_FULLA + r.s * 8, ((int)tab & 15) * 64, m * 64, 0);
        else {
          tma_load_w(sb + OFF_A + r.s * SLOT, &P.mw[1], sb + BAR_FULLA + r.s * 8, 1024 + 128 * j, m);
          mbar_expect_tx(sb + BAR_WPHI, 8192); tma_load_2d(sb + OFF_S + 4096, &P.mwphi, sb + BAR_WPHI, 0, 128 * j);
        }
        if (i == PF1 || i == PF2) tma_prefetch_w(&P.mwo[i == PF2], 128 * j, m);
      }
      adv<NA>(r);
      if (i != 14) tab >>= 4;
    }
  }
  const unsigned tag = get_tag(sb);
  unsigned seen = 0;
#pragma unroll 1
  for (int sg = 0; sg < 27; sg++) {
    const int L = sg >> 3, p = sg & 7, q = p >= 3 ? p - 3 : p;
    if (p == 0 && (L & 1)) {
      TS(4, 30 + L);
#pragma unroll 1
      for (int h = 0; h < 2; h++) {
        poll_flags(&g_kvfflag[L >> 1][j][h][0], 8, 0xFFu, tag);
        if (h == 0) TS(4, 26 + L);
        if (elect()) { mbar_expect_tx(sb + BAR_KV + h * 8, 10240); bulk_load(sb + OFF_S + h * 10240, &g_kvfin[j][8 * h][0], 10240, sb + BAR_KV + h * 8); }
      }
      TS(4, 14 + L);
    }
    int n = q == 0 ? 4 : (q == 1 ? 3 : (q == 2 ? 7 : (q == 3 ? ((L & 1) ? 0 : 16 - NJ) : 16)));
    u64 tab = q == 4 ? t2 : t1 >> (q == 0 ? 8 : (q == 1 ? 24 : (q == 2 ? 36 : 4 * NJ)));
    const uint4* img = &g_img[p >= 3 ? XBUF(L + 1) : 0][m][0][0];
    const uint32_t gap = p == 0 ? G0 : (p == 3 ? G3 : (q < 3 ? G1 : G4));
    bool poll = q == 0 || q == 2 || (q == 1 && seen != 0xFFFFFFFFu);
#pragma unroll 1
    for (; n > 0; n--) {
      const uint4* src = img + ((int)tab & 15) * 1024;
      src = early(src);
      mbar_wait(sb + BAR_EMPTYA + r.s * 8, r.ph);
      if (elect()) mbar_expect_tx(sb + BAR_FULLA + r.s * 8, SLOT);
      if (poll) {
        const int lane = threadIdx.x & 31, nn = p >= 3 ? PNX : PNO;
        const unsigned* f = (p >= 3 ? &g_xflag[L + 1][0][m][0] : &g_oflag[L][0][m][0]) + (q == 2 ? 512 : 0) + (lane & 7);
        if (q == 0 || (PN2 && q == 2)) f += (((lane >> 3) & (nn - 1)) - (m & (nn - 1))) * 32;
        const unsigned need = q == 0 ? 0x0F0F0F0Fu << (~j & 4) : 0xFFFFFFFFu;
        if (q == 0) mbar_wait(sb + BAR_SIGP + (p ? 16 : 0), L & 1);
        int it = 0;
        do { seen = __ballot_sync(0xffffffffu, ld_flag(f) == tag); if (++it > (1 << 22)) __trap(); } while ((seen & need) != need);
        if (q == 0) TS(2, p == 0 ? 5 + L * 8 : 9 + L * 8);
        poll = false;
      }
      if (elect()) bulk_load(sb + OFF_A + r.s * SLOT, src, SLOT, sb + BAR_FULLA + r.s * 8);
      adv<NA>(r);
      tab >>= 4;
      pause(gap);
    }
  }
}

__device__ __forceinline__ uint2 sum_packets(float (&a)[8], uint32_t addr, int n) {
  uint2 ok = make_uint2(~0u, 0u);
#pragma unroll 1
  for (int b = 0; b < n; b += KB) {
    uint4 v[KB];
#pragma unroll
    for (int u = 0; u < KB; u++) lds128(addr + (b + u) * 512, v[u].x, v[u].y, v[u].z, v[u].w);
#pragma unroll
    for (int u = 0; u < KB; u++) {
      ok.x &= v[u].x; ok.y |= v[u].x;
      a[0] += lo16(v[u].x); a[1] += hi16(v[u].x); a[2] += lo16(v[u].y); a[3] += hi16(v[u].y);
      a[4] += lo16(v[u].z); a[5] += hi16(v[u].z); a[6] += lo16(v[u].w); a[7] += hi16(v[u].w);
    }
  }
  return ok;
}
__device__ __forceinline__ void helper_bar() { asm volatile("bar.sync 4, 64;" ::: "memory"); }
__device__ __forceinline__ void helper(const Params& P, uint32_t sb, int w, unsigned vb) {
  const int j = cta_j(vb), m = cta_m(vb);
  if (w == 0) {
    if (elect()) {
      const unsigned t = atomicAdd(&g_ctr, 1u) / NCTA + 1u;
      asm volatile("st.shared.u32 [%0], %1;" ::"r"(sb + OFF_EPOCH), "r"(t) : "memory");
      mbar_arrive(sb + BAR_EPOCH);
    }
  }
  const unsigned tag = get_tag(sb);
  mbar_wait(sb + BAR_FULLB + 24, 0);
  const uint32_t stg = sb + OFF_T + w * 12288, stb = sb + BAR_STG + w * 24;
  Ring rs = {0, 0};
  auto cs_image = [&](int L) {
      const int lane = lane_id();
      poll_flags(&g_csflag[L][j][0], 16, L ? CSNEED : 0xFFFu, tag);
#pragma unroll
      for (int p = 0; p < 3; p++) {
        const uint4 u = ldcg4(&g_cs[L][0][p * 1024 + 128 * j + lane * 4]), v = ldcg4(&g_cs[L][1][p * 1024 + 128 * j + lane * 4]);
        const float c0 = __uint_as_float(u.x) + __uint_as_float(v.x), c1 = __uint_as_float(u.y) + __uint_as_float(v.y);
        const float c2 = __uint_as_float(u.z) + __uint_as_float(v.z), c3 = __uint_as_float(u.w) + __uint_as_float(v.w);
        const uint32_t h0 = pack2(c0, c1), h1 = pack2(c2, c3), dst = sb + OFF_CS + (p * 16 + (lane >> 1)) * 96 + L * 48 + (lane & 1) * 8;
        sts64(dst, h0, h1); sts64(dst + 16, pack2(c0 - lo16(h0), c1 - hi16(h0)), pack2(c2 - lo16(h1), c3 - hi16(h1))); sts64(dst + 32, h0, h1);
        if (L == 0) { sts64(dst + 48, 0u, 0u); sts64(dst + 64, 0u, 0u); sts64(dst + 80, 0u, 0u); }
      }
      if (L == 0 && lane < 4) sts64(sb + OFF_CS + 4608 + lane * 8, 0u, 0u);
      fence_async_smem();
      __syncwarp();
      if (elect()) mbar_arrive(sb + BAR_CS + L * 8);
      TS(4, 2 + L * 2);
  };
#pragma unroll 1
  for (int L = 0; L < 4; L++) {
    const int lane = lane_id();
    if (L == 0) {
      {
        const int wt = m >= 12, col = ((0x2021 >> (m & 12)) & 3) * 1024 + 128 * j + (m & 3) * 32;
        const CUtensorMap* tm = &P.mcs[wt];
        __nanosleep(wt ? D2 : CD);
        constexpr int nb = 8;
        float a[8] = {0.f, 0.f, 0.f, 0.f, 0.f, 0.f, 0.f, 0.f};
#pragma unroll 1
        for (int b = -3; b < nb; b++) {
          if (b >= 0) {
            mbar_wait(stb + rs.s * 8, rs.ph);
            sum_packets(a, stg + rs.s * 4096 + lane * 16, 8);
            fence_async_smem();
            __syncwarp();
          }
          const uint32_t sl = b < 0 ? (rs.s + b + 3) % 3 : rs.s;
          if (b + 3 < nb && elect()) { mbar_expect_tx(stb + sl * 8, 4096); tma_load_2d(stg + sl * 4096, tm, stb + sl * 8, col, (w * (16 - nb) + b + 3) * 64); }
          if (b >= 0) adv<3>(rs); else pause(CP);
        }
#pragma unroll
        for (int u = 0; u < 8; u++) {
          a[u] += __shfl_xor_sync(0xffffffffu, a[u], 4); a[u] += __shfl_xor_sync(0xffffffffu, a[u], 8); a[u] += __shfl_xor_sync(0xffffffffu, a[u], 16);
        }
        if (lane < 4) {
          float4* dst = reinterpret_cast<float4*>(&g_cs[wt][w][col + lane * 8]);
          dst[0] = make_float4(a[0], a[1], a[2], a[3]); dst[1] = make_float4(a[4], a[5], a[6], a[7]);
        }
        helper_bar();
        if (w == 0 && elect()) { fence_gpu(); st_flag(&g_csflag[wt][j][m], tag); }
      }
      if (w == 0) TS(4, 1 + L * 2);
    }
    if (w == 1) {
      if (L > 0) { mbar_wait(sb + BAR_SIGP + 24, (L - 1) & 1); __nanosleep(SD); }
      else if (S0) { mbar_wait(sb + BAR_WPHI, 0); __nanosleep(S0); }
#pragma unroll 1
      for (int p = 0; p < 2; p++) {
        uint4 v[8];
        for (int it = 0;; it++) {
          bool ok = true;
#pragma unroll
          for (int t = 0; t < 8; t++) v[t] = ld_pkt(&g_stats[m][p][t][lane]);
#pragma unroll
          for (int t = 0; t < 8; t++) ok = ok && (v[t].w & 15u) == seq4(tag, L);
          if (__all_sync(0xffffffffu, ok)) break;
          __nanosleep(200);
          if (it > (1 << 20)) __trap();
        }
        float s0 = 0.f, q0 = 0.f, s1 = 0.f, q1 = 0.f;
#pragma unroll
        for (int t = 0; t < 8; t++) { s0 += __uint_as_float(v[t].x); q0 += __uint_as_float(v[t].y); s1 += __uint_as_float(v[t].z); q1 += __uint_as_float(v[t].w & ~15u); }
        s0 *= (1.f / 1024); s1 *= (1.f / 1024);
        sts64(sb + OFF_MR + p * 256 + lane * 8, __float_as_uint(rsqrtf(fmaxf(q0 * (1.f / 1024) - s0 * s0, 0.f) + 1e-5f)),
              __float_as_uint(rsqrtf(fmaxf(q1 * (1.f / 1024) - s1 * s1, 0.f) + 1e-5f)));
#pragma unroll
        for (int r = 0; r < 2; r++) {
          const float v = -0.5f * (r ? s1 : s0);
          const uint32_t hh = pack2(v, v), hl = pack2(v, v - lo16(hh));
          const bool b = L & 1;
          sts128(sb + (b ? OFF_MB : OFF_MA) + p * 1024 + (lane >> 3) * 256 + r * 128 + (lane & 7) * 16, b ? 0u : hh, b ? hh << 16 : hl >> 16, b ? hl : 0u, 0u);
        }
      }
      fence_async_smem();
      __syncwarp();
      if (elect()) {
        mbar_arrive(sb + BAR_STAT);
      }
      TS(2, 0 + L * 8);
    }
    if (L == w) cs_image(L);
    if (L & 1) {
      const uint32_t flip = L == 1 ? 0u : 1u;
      mbar_wait(sb + BAR_SIGT, 1);
      {
        int it = 0;
        if (PSL) __nanosleep(m < 8 ? PSL : PSL + 600);
        while (!__all_sync(0xffffffffu, (ld_flag(reinterpret_cast<const unsigned*>(&g_kvpart[j][m][w][512]) + (lane & 15) * 8) ^ flip) & 1u)) { if (PSL) __nanosleep(100); if (++it > (1 << 22)) __trap(); }
        fence_async_global();
      }
      if (w == 0) TS(4, 6 + L * 2);
      for (int it = 0;; it++) {
        if (elect()) { mbar_expect_tx(stb + rs.s * 8, 8704); bulk_load(stg, &g_kvpart[j][m][w][0], 8704, stb + rs.s * 8); }
        mbar_wait(stb + rs.s * 8, rs.ph);
        if (w == 0) TS(4, 21 + L);
        adv<3>(rs);
        float a[8] = {0.f, 0.f, 0.f, 0.f, 0.f, 0.f, 0.f, 0.f};
        float z = 0.f;
        uint32_t ok = 1u;
#pragma unroll
        for (int u = 0; u < 4; u++) { const float v = lds32f(stg + 8192 + u * 128 + (lane & 3) * 32 + (lane >> 2) * 4); z += v; ok &= __float_as_uint(v) ^ flip; }
        const uint2 tg = sum_packets(a, stg + lane * 16, 16);
        ok &= flip ? ~tg.y : tg.x;
        uint4* img = &g_kvfin[j][m][w * 8 + (lane >> 2)];
        img[(lane & 3) * 16] = make_uint4(pack2(a[0], a[1]), pack2(a[2], a[3]), pack2(a[4], a[5]), pack2(a[6], a[7]));
        reinterpret_cast<uint32_t*>(img + 64)[lane & 3] = pack2(qsum(z), 1.f / 65536);
        if (__all_sync(0xffffffffu, ok & 1u)) break;
        fence_async_smem();
        if (it > (1 << 16)) __trap();
      }
      if (w == 0) TS(4, 7 + L * 2);
      helper_bar();
      if (w == 1 && elect()) { fence_gpu(); st_flag(&g_kvfflag[L >> 1][j][m >> 3][m & 7], tag); }
      if (w == 1) TS(4, L == 1 ? 20 : 25);
    } else {
      mbar_wait(sb + BAR_SIGT, 0);
      if (w == 0) {
        if (elect()) { fence_gpu(); st_flag(&g_hflag[L >> 1][m][j][0], tag); st_flag(&g_kflag[j][m], tag); }
        if (L == 0) {
          __nanosleep(KSL);
          poll_flags(&g_kflag[j][0], 16, 0xFFFFu, tag);
          if (elect()) mbar_arrive(sb + BAR_WPHI);
        }
      } else if (m > 0) {
        poll_flags(&g_hflag[L >> 1][m - 1][j][0], 1, 1u, tag);
        if (elect()) { mbar_expect_tx(sb + BAR_HALO, 8192); bulk_load(sb + OFF_S + 8192, &g_halo[m - 1][j][0][0], 8192, sb + BAR_HALO); }
        TS(2, 2 + L * 8);
      }
    }
#pragma unroll 1
    for (int e = 0; e < (L < 3 && w == 0 ? 3 : 1); e++) {
      unsigned* flag = e == 0 ? &g_oflag[L][w][m][j] : &g_xflag[L + 1][e - 1][m][j];
      flag = early(flag);
      mbar_wait(sb + BAR_SIGP + (e == 0 ? w : e + 1) * 8, L & 1);
      TS(e == 2 ? 3 : 2 + w, (e ? 6 : 3) + L * 8);
      if (elect()) { fence_async_global(); fence_gpu(); st_flag(flag, tag); }
      TS(e == 2 ? 3 : 2 + w, (e ? 7 : 4) + L * 8);
    }
  }
}

__device__ __forceinline__ void spare(const Params& P, uint32_t sb, int id) {
  const int tid = threadIdx.x & 127, w = __shfl_sync(0xffffffffu, threadIdx.x >> 7, 0), lane = tid & 31, j = 2 * id + w;
  const uint32_t ring = w * 6 * SLOT, wp = 12 * SLOT + w * 8192, bar = sb + 13 * SLOT + w * 64;
  auto part = [&](int t) { return (t >> 4) ^ w; };
  auto load = [&](int t, uint32_t sl) {
    mbar_expect_tx(bar + sl * 8, t == 0 ? SLOT + 8192 : SLOT);
    tma_load_w(sb + ring + sl * SLOT, &P.mw[1], bar + sl * 8, part(t) * 1024 + 128 * j, t & 15);
  };
  if (tid == 0) {
    if (w == 2) sts32(sb + OFF_EPOCH, atomicAdd(&g_ctr, 1u) / NCTA + 1u);
    else {
      __nanosleep(D3);
#pragma unroll 1
      for (int t = 0; t < 5; t++) {
        mbar_init(bar + t * 8, 1);
        asm volatile("fence.mbarrier_init.release.cluster;" ::: "memory");
        load(t, t);
      }
      tma_load_2d(sb + wp, &P.mwphi, bar, 0, 128 * j);
    }
  }
  __syncthreads();
  const unsigned tag = get_tag<false>(sb);
  if (w == 2) {
    int it = 0;
    while ((int)(ld_flag(&g_ctr) - tag * NCTA) < 0) { if (++it > (1 << 22)) __trap(); }
    return;
  }
  Ring r = {4, 1};
  float d[64] = {}, cs[32] = {};
  auto fold = [&]() {
    mbar_wait(bar + r.s * 8, r.ph);
    wgmma_fence();
#pragma unroll
    for (int q = 0; q < 8; q++)
      wgmma_ss_n32(reinterpret_cast<float (&)[16]>(d[16 * (q >> 1)]), desc_lo(SB + ring + r.s * SLOT, 16) + (q >> 2) * 512 + (q & 3) * 2, desc_lo(SB + wp, 512) + q * 64, q & 1);
    wgmma_commit();
  };
  const int row = (tid >> 5) * 16 + (lane >> 2);
#pragma unroll 1
  for (int t = -1; t < 32; t++) {
    uint32_t f[32];
#pragma unroll
    for (int i = 0; i < 32; i++) { f[i] = pack2(d[2 * i], d[2 * i + 1]); cs[i & 30] += d[2 * i]; cs[i | 1] += d[2 * i + 1]; }
    wg_bar(w);
    if (tid == 0 && t >= 0 && t < 27) load(t + 5, r.s);
    __syncwarp();
    if (t < 31) adv<5>(r);
    fold();
    if (part(t) == 0 && t >= 0) {
#pragma unroll
      for (int q = 0; q < 8; q++)
        g_wf[0][j][t & 15][(q >> 2) * 512 + (row + 8 * (q & 1)) * 8 + (((q & 2) * 2 + (lane & 3)) ^ (lane >> 2))] =
            make_uint4(f[4 * (q & 6) + (q & 1)], f[4 * (q & 6) + (q & 1) + 2], f[4 * (q & 6) + (q & 1) + 4], f[4 * (q & 6) + (q & 1) + 6]);
    }
    wgmma_wait<0>();
    fence_regs(d);
    if ((t & 15) == 15) {
      if (t >= 0) {
        const uint32_t red = sb + ring + 5 * SLOT;
#pragma unroll
        for (int i = 0; i < 8; i++) sts128(red + (tid >> 2) * 512 + (i >> 1) * 128 + (lane & 3) * 32 + (i & 1) * 16, __float_as_uint(cs[4 * i]), __float_as_uint(cs[4 * i + 1]), __float_as_uint(cs[4 * i + 2]), __float_as_uint(cs[4 * i + 3]));
        wg_bar(w);
        float a = 0.f;
#pragma unroll 4
        for (int i = 0; i < 32; i++) a += lds32f(red + i * 512 + tid * 4);
        g_cs[1][0][part(t) * 1024 + j * 128 + tid] = a;
        wg_bar(w);
        if (tid == 0) {
          fence_gpu();
          st_flag(&g_csflag[1][j][part(t)], tag);
        }
        __syncwarp();
      }
#pragma unroll
      for (int i = 0; i < 32; i++) cs[i] = 0.f;
    }
  }
}

__global__ void __launch_bounds__(NTHREADS, 1) fused_kernel(const __grid_constant__ Params P) {
  extern __shared__ __align__(1024) uint8_t smem_raw[];
  constexpr uint32_t sb = SB;
  const int tid = threadIdx.x;
  const unsigned vb = vblock();
  if (vb >= 128) { spare(P, sb, vb - 128); return; }
  const int warp = __shfl_sync(0xffffffffu, tid >> 5, 0);
  if (elect()) {
    if (warp == 11) { prefetch_map(&P.mx); prefetch_map(&P.mw[0]); if (smem_u32(smem_raw) != SB) __trap(); }
    if (warp < 7) {
#pragma unroll
      for (int i = 0; i < 8; i++) mbar_init(sb + OFF_BAR + (warp * 8 + i) * 8, warp == 2 || warp == 3 ? 2 : (warp == 4 ? 8 : 1));
    }
    asm volatile("fence.mbarrier_init.release.cluster;" ::: "memory");
    if (warp < 2) {
      const int j = cta_j(vb);
#pragma unroll 1
      for (int i = 0; i < (warp == 0 ? PRE_B : PRE_A); i++) {
        const uint32_t bar = sb + BAR_FULLB + warp * 64 + i * 8;
        mbar_expect_tx(bar, SLOT);
        if (warp == 0) tma_load_w(sb + OFF_B + i * SLOT, &P.mw[0], bar, 1024 + (i & 1) * 1024 + 128 * j, kv_order(i >> 1, j, 0));
        else tma_load_3d(sb + OFF_A + i * SLOT, &P.mx, bar, kv_order(i, j, 0) * 64, cta_m(vb) * 64, 0);
      }
    }
  }
  if (tid == 0) TS(6, 0);
  __syncthreads();
  if (tid == 0) TS(6, 2);
  if (warp < 4) {
    reg_dealloc<PREGS>();
    if (warp == 0) b_producer(P, sb, vb);
    else if (warp == 1) a_loader(P, sb, vb);
    else helper(P, sb, warp - 2, vb);
  } else {
    reg_alloc<CREGS>();
    consumer(P, sb, (warp >> 2) - 1, vb);
  }
}

typedef CUresult (*EncodeFn)(CUtensorMap*, CUtensorMapDataType, cuuint32_t, void*, const cuuint64_t*, const cuuint64_t*,
                             const cuuint32_t*, const cuuint32_t*, CUtensorMapInterleave, CUtensorMapSwizzle,
                             CUtensorMapL2promotion, CUtensorMapFloatOOBfill);

void encode(EncodeFn fn, CUtensorMap* m, const void* ptr, int rank, const cuuint64_t* dims, const cuuint64_t* strides,
            const cuuint32_t* box, CUtensorMapSwizzle swz) {
  const cuuint32_t es[5] = {1, 1, 1, 1, 1};
  fn(m, CU_TENSOR_MAP_DATA_TYPE_BFLOAT16, rank, const_cast<void*>(ptr), dims, strides, box, es, CU_TENSOR_MAP_INTERLEAVE_NONE,
     swz, CU_TENSOR_MAP_L2_PROMOTION_L2_256B, CU_TENSOR_MAP_FLOAT_OOB_FILL_NONE);
}
void encode_w(EncodeFn fn, CUtensorMap* m, const void* ptr, int ncols, bool perm) {
  const cuuint64_t p = (cuuint64_t)ncols * 2, d[5] = {(cuuint64_t)ncols, 2, 4, 4, 32}, s[4] = {p, (perm ? 8 : 2) * p, (perm ? 2 : 8) * p, 32 * p};
  const cuuint32_t box[5] = {64, 2, 4, 4, 2};
  encode(fn, m, ptr, 5, d, s, box, CU_TENSOR_MAP_SWIZZLE_128B);
}

void encode_cs(EncodeFn fn, CUtensorMap* m, const void* ptr, int ncols) {
  const cuuint64_t d[2] = {(cuuint64_t)ncols, 1024}, s[1] = {(cuuint64_t)ncols * 2};
  const cuuint32_t box[2] = {32, 64};
  encode(fn, m, ptr, 2, d, s, box, CU_TENSOR_MAP_SWIZZLE_NONE);
}

}

extern "C" void kernel_launch(void* const* d_in, const int* in_sizes, int n_in, void* d_out, int out_size) {
  (void)in_sizes; (void)n_in; (void)out_size;
  void* fnp = nullptr;
  cudaDriverEntryPointQueryResult q;
  cudaGetDriverEntryPoint("cuTensorMapEncodeTiled", &fnp, cudaEnableDefault, &q);
  EncodeFn fn = (EncodeFn)fnp;
  Params P;
  {
    const cuuint64_t dims[3] = {1024, 1024, 2}, strides[2] = {4096, 2048};
    const cuuint32_t box[3] = {64, 64, 2};
    encode(fn, &P.mx, d_in[0], 3, dims, strides, box, CU_TENSOR_MAP_SWIZZLE_128B);
  }
  P.out = (uint4*)d_out;
  encode_w(fn, &P.mw[0], d_in[1], 3072, false);
  encode_w(fn, &P.mw[1], d_in[4], 3072, true);
  encode_w(fn, &P.mw[2], d_in[1], 3072, true);
  encode_w(fn, &P.mwo[0], d_in[2], 1024, true);
  encode_w(fn, &P.mwo[1], d_in[6], 1024, false);
  encode_cs(fn, &P.mcs[0], d_in[1], 3072);
  encode_cs(fn, &P.mcs[1], d_in[4], 3072);
  {
    const cuuint64_t dims[2] = {32, 1024}, strides[1] = {64};
    const cuuint32_t box[2] = {32, 128};
    encode(fn, &P.mwphi, d_in[5], 2, dims, strides, box, CU_TENSOR_MAP_SWIZZLE_64B);
  }
  cudaFuncSetAttribute(fused_kernel, cudaFuncAttributeMaxDynamicSharedMemorySize, SMEM_BYTES);
  fused_kernel<<<NCTA, NTHREADS, SMEM_BYTES, cudaStreamPerThread>>>(P);
}
```

```cpp
#include <cuda_runtime.h>
#include <cuda_bf16.h>
#include <cuda.h>
#include <stdint.h>

namespace {

__device__ __forceinline__ void wgmma_ss_n256(float (&d)[128], uint32_t da, uint32_t ha, uint32_t db, int sd) {
  asm volatile("{\n.reg .pred p;\n.reg .b64 a, b;\nsetp.ne.b32 p, %130, 0;\nmov.b64 a, {%128, %131};\nmov.b64 b, {%129, 0x40000040};\n"
    "wgmma.mma_async.sync.aligned.m64n256k16.f32.bf16.bf16 {%0,%1,%2,%3,%4,%5,%6,%7,%8,%9,%10,%11,%12,%13,%14,%15,%16,%17,%18,%19,%20,%21,%22,%23,%24,%25,%26,%27,%28,%29,%30,%31,%32,%33,%34,%35,%36,%37,%38,%39,%40,%41,%42,%43,%44,%45,%46,%47,%48,%49,%50,%51,%52,%53,%54,%55,%56,%57,%58,%59,%60,%61,%62,%63,%64,%65,%66,%67,%68,%69,%70,%71,%72,%73,%74,%75,%76,%77,%78,%79,%80,%81,%82,%83,%84,%85,%86,%87,%88,%89,%90,%91,%92,%93,%94,%95,%96,%97,%98,%99,%100,%101,%102,%103,%104,%105,%106,%107,%108,%109,%110,%111,%112,%113,%114,%115,%116,%117,%118,%119,%120,%121,%122,%123,%124,%125,%126,%127}, a, b, p, 1, 1, 0, 1;\n}\n"
    : "+f"(d[0]),"+f"(d[1]),"+f"(d[2]),"+f"(d[3]),"+f"(d[4]),"+f"(d[5]),"+f"(d[6]),"+f"(d[7]),"+f"(d[8]),"+f"(d[9]),"+f"(d[10]),"+f"(d[11]),"+f"(d[12]),"+f"(d[13]),"+f"(d[14]),"+f"(d[15]),"+f"(d[16]),"+f"(d[17]),"+f"(d[18]),"+f"(d[19]),"+f"(d[20]),"+f"(d[21]),"+f"(d[22]),"+f"(d[23]),"+f"(d[24]),"+f"(d[25]),"+f"(d[26]),"+f"(d[27]),"+f"(d[28]),"+f"(d[29]),"+f"(d[30]),"+f"(d[31]),"+f"(d[32]),"+f"(d[33]),"+f"(d[34]),"+f"(d[35]),"+f"(d[36]),"+f"(d[37]),"+f"(d[38]),"+f"(d[39]),"+f"(d[40]),"+f"(d[41]),"+f"(d[42]),"+f"(d[43]),"+f"(d[44]),"+f"(d[45]),"+f"(d[46]),"+f"(d[47]),"+f"(d[48]),"+f"(d[49]),"+f"(d[50]),"+f"(d[51]),"+f"(d[52]),"+f"(d[53]),"+f"(d[54]),"+f"(d[55]),"+f"(d[56]),"+f"(d[57]),"+f"(d[58]),"+f"(d[59]),"+f"(d[60]),"+f"(d[61]),"+f"(d[62]),"+f"(d[63]),"+f"(d[64]),"+f"(d[65]),"+f"(d[66]),"+f"(d[67]),"+f"(d[68]),"+f"(d[69]),"+f"(d[70]),"+f"(d[71]),"+f"(d[72]),"+f"(d[73]),"+f"(d[74]),"+f"(d[75]),"+f"(d[76]),"+f"(d[77]),"+f"(d[78]),"+f"(d[79]),"+f"(d[80]),"+f"(d[81]),"+f"(d[82]),"+f"(d[83]),"+f"(d[84]),"+f"(d[85]),"+f"(d[86]),"+f"(d[87]),"+f"(d[88]),"+f"(d[89]),"+f"(d[90]),"+f"(d[91]),"+f"(d[92]),"+f"(d[93]),"+f"(d[94]),"+f"(d[95]),"+f"(d[96]),"+f"(d[97]),"+f"(d[98]),"+f"(d[99]),"+f"(d[100]),"+f"(d[101]),"+f"(d[102]),"+f"(d[103]),"+f"(d[104]),"+f"(d[105]),"+f"(d[106]),"+f"(d[107]),"+f"(d[108]),"+f"(d[109]),"+f"(d[110]),"+f"(d[111]),"+f"(d[112]),"+f"(d[113]),"+f"(d[114]),"+f"(d[115]),"+f"(d[116]),"+f"(d[117]),"+f"(d[118]),"+f"(d[119]),"+f"(d[120]),"+f"(d[121]),"+f"(d[122]),"+f"(d[123]),"+f"(d[124]),"+f"(d[125]),"+f"(d[126]),"+f"(d[127])
    : "r"(da), "r"(db), "r"(sd), "r"(ha));
}
__device__ __forceinline__ void wgmma_ss_n128(float (&d)[64], uint32_t da, uint32_t ha, uint32_t db, int sd) {
  asm volatile("{\n.reg .pred p;\n.reg .b64 a, b;\nsetp.ne.b32 p, %66, 0;\nmov.b64 a, {%64, %67};\nmov.b64 b, {%65, 0x40000040};\n"
    "wgmma.mma_async.sync.aligned.m64n128k16.f32.bf16.bf16 {%0,%1,%2,%3,%4,%5,%6,%7,%8,%9,%10,%11,%12,%13,%14,%15,%16,%17,%18,%19,%20,%21,%22,%23,%24,%25,%26,%27,%28,%29,%30,%31,%32,%33,%34,%35,%36,%37,%38,%39,%40,%41,%42,%43,%44,%45,%46,%47,%48,%49,%50,%51,%52,%53,%54,%55,%56,%57,%58,%59,%60,%61,%62,%63}, a, b, p, 1, 1, 0, 1;\n}\n"
    : "+f"(d[0]),"+f"(d[1]),"+f"(d[2]),"+f"(d[3]),"+f"(d[4]),"+f"(d[5]),"+f"(d[6]),"+f"(d[7]),"+f"(d[8]),"+f"(d[9]),"+f"(d[10]),"+f"(d[11]),"+f"(d[12]),"+f"(d[13]),"+f"(d[14]),"+f"(d[15]),"+f"(d[16]),"+f"(d[17]),"+f"(d[18]),"+f"(d[19]),"+f"(d[20]),"+f"(d[21]),"+f"(d[22]),"+f"(d[23]),"+f"(d[24]),"+f"(d[25]),"+f"(d[26]),"+f"(d[27]),"+f"(d[28]),"+f"(d[29]),"+f"(d[30]),"+f"(d[31]),"+f"(d[32]),"+f"(d[33]),"+f"(d[34]),"+f"(d[35]),"+f"(d[36]),"+f"(d[37]),"+f"(d[38]),"+f"(d[39]),"+f"(d[40]),"+f"(d[41]),"+f"(d[42]),"+f"(d[43]),"+f"(d[44]),"+f"(d[45]),"+f"(d[46]),"+f"(d[47]),"+f"(d[48]),"+f"(d[49]),"+f"(d[50]),"+f"(d[51]),"+f"(d[52]),"+f"(d[53]),"+f"(d[54]),"+f"(d[55]),"+f"(d[56]),"+f"(d[57]),"+f"(d[58]),"+f"(d[59]),"+f"(d[60]),"+f"(d[61]),"+f"(d[62]),"+f"(d[63])
    : "r"(da), "r"(db), "r"(sd), "r"(ha));
}
__device__ __forceinline__ void wgmma_ss_n40_tt(float (&d)[20], uint32_t da, uint32_t db, int sd) {
  asm volatile("{\n.reg .pred p;\n.reg .b64 a, b;\nsetp.ne.b32 p, %22, 0;\nmov.b64 a, {%20, 0x40000040};\nmov.b64 b, {%21, 0x8};\n"
    "wgmma.mma_async.sync.aligned.m64n40k16.f32.bf16.bf16 {%0,%1,%2,%3,%4,%5,%6,%7,%8,%9,%10,%11,%12,%13,%14,%15,%16,%17,%18,%19}, a, b, p, 1, 1, 1, 1;\n}\n"
    : "+f"(d[0]),"+f"(d[1]),"+f"(d[2]),"+f"(d[3]),"+f"(d[4]),"+f"(d[5]),"+f"(d[6]),"+f"(d[7]),"+f"(d[8]),"+f"(d[9]),"+f"(d[10]),"+f"(d[11]),"+f"(d[12]),"+f"(d[13]),"+f"(d[14]),"+f"(d[15]),"+f"(d[16]),"+f"(d[17]),"+f"(d[18]),"+f"(d[19])
    : "r"(da), "r"(db), "r"(sd));
}
__device__ __forceinline__ void wgmma_ss_n32(float (&d)[16], uint32_t da, uint32_t db, int sd) {
  asm volatile("{\n.reg .pred p;\n.reg .b64 a, b;\nsetp.ne.b32 p, %18, 0;\nmov.b64 a, {%16, 0x40000040};\nmov.b64 b, {%17, 0x80000020};\n"
    "wgmma.mma_async.sync.aligned.m64n32k16.f32.bf16.bf16 {%0,%1,%2,%3,%4,%5,%6,%7,%8,%9,%10,%11,%12,%13,%14,%15}, a, b, p, 1, 1, 0, 1;\n}\n"
    : "+f"(d[0]),"+f"(d[1]),"+f"(d[2]),"+f"(d[3]),"+f"(d[4]),"+f"(d[5]),"+f"(d[6]),"+f"(d[7]),"+f"(d[8]),"+f"(d[9]),"+f"(d[10]),"+f"(d[11]),"+f"(d[12]),"+f"(d[13]),"+f"(d[14]),"+f"(d[15])
    : "r"(da), "r"(db), "r"(sd));
}
__device__ __forceinline__ void wgmma_rs_n40(float (&d)[20], uint32_t a0, uint32_t a1, uint32_t a2, uint32_t a3, uint32_t db, int sd) {
  asm volatile("{\n.reg .pred p;\n.reg .b64 b;\nsetp.ne.b32 p, %25, 0;\nmov.b64 b, {%24, 0x10};\n"
    "wgmma.mma_async.sync.aligned.m64n40k16.f32.bf16.bf16 {%0,%1,%2,%3,%4,%5,%6,%7,%8,%9,%10,%11,%12,%13,%14,%15,%16,%17,%18,%19}, {%20,%21,%22,%23}, b, p, 1, 1, 1;\n}\n"
    : "+f"(d[0]),"+f"(d[1]),"+f"(d[2]),"+f"(d[3]),"+f"(d[4]),"+f"(d[5]),"+f"(d[6]),"+f"(d[7]),"+f"(d[8]),"+f"(d[9]),"+f"(d[10]),"+f"(d[11]),"+f"(d[12]),"+f"(d[13]),"+f"(d[14]),"+f"(d[15]),"+f"(d[16]),"+f"(d[17]),"+f"(d[18]),"+f"(d[19])
    : "r"(a0), "r"(a1), "r"(a2), "r"(a3), "r"(db), "r"(sd));
}
__device__ __forceinline__ void wgmma_r1_n256(float (&d)[128], uint32_t da, uint32_t db, int sd) {
  asm volatile("{\n.reg .pred p;\n.reg .b64 a, b;\nsetp.ne.b32 p, %130, 0;\nmov.b64 a, {%128, 0x8};\nmov.b64 b, {%129, 0x6};\n"
    "wgmma.mma_async.sync.aligned.m64n256k16.f32.bf16.bf16 {%0,%1,%2,%3,%4,%5,%6,%7,%8,%9,%10,%11,%12,%13,%14,%15,%16,%17,%18,%19,%20,%21,%22,%23,%24,%25,%26,%27,%28,%29,%30,%31,%32,%33,%34,%35,%36,%37,%38,%39,%40,%41,%42,%43,%44,%45,%46,%47,%48,%49,%50,%51,%52,%53,%54,%55,%56,%57,%58,%59,%60,%61,%62,%63,%64,%65,%66,%67,%68,%69,%70,%71,%72,%73,%74,%75,%76,%77,%78,%79,%80,%81,%82,%83,%84,%85,%86,%87,%88,%89,%90,%91,%92,%93,%94,%95,%96,%97,%98,%99,%100,%101,%102,%103,%104,%105,%106,%107,%108,%109,%110,%111,%112,%113,%114,%115,%116,%117,%118,%119,%120,%121,%122,%123,%124,%125,%126,%127}, a, b, p, 1, 1, 0, 1;\n}\n"
    : "+f"(d[0]),"+f"(d[1]),"+f"(d[2]),"+f"(d[3]),"+f"(d[4]),"+f"(d[5]),"+f"(d[6]),"+f"(d[7]),"+f"(d[8]),"+f"(d[9]),"+f"(d[10]),"+f"(d[11]),"+f"(d[12]),"+f"(d[13]),"+f"(d[14]),"+f"(d[15]),"+f"(d[16]),"+f"(d[17]),"+f"(d[18]),"+f"(d[19]),"+f"(d[20]),"+f"(d[21]),"+f"(d[22]),"+f"(d[23]),"+f"(d[24]),"+f"(d[25]),"+f"(d[26]),"+f"(d[27]),"+f"(d[28]),"+f"(d[29]),"+f"(d[30]),"+f"(d[31]),"+f"(d[32]),"+f"(d[33]),"+f"(d[34]),"+f"(d[35]),"+f"(d[36]),"+f"(d[37]),"+f"(d[38]),"+f"(d[39]),"+f"(d[40]),"+f"(d[41]),"+f"(d[42]),"+f"(d[43]),"+f"(d[44]),"+f"(d[45]),"+f"(d[46]),"+f"(d[47]),"+f"(d[48]),"+f"(d[49]),"+f"(d[50]),"+f"(d[51]),"+f"(d[52]),"+f"(d[53]),"+f"(d[54]),"+f"(d[55]),"+f"(d[56]),"+f"(d[57]),"+f"(d[58]),"+f"(d[59]),"+f"(d[60]),"+f"(d[61]),"+f"(d[62]),"+f"(d[63]),"+f"(d[64]),"+f"(d[65]),"+f"(d[66]),"+f"(d[67]),"+f"(d[68]),"+f"(d[69]),"+f"(d[70]),"+f"(d[71]),"+f"(d[72]),"+f"(d[73]),"+f"(d[74]),"+f"(d[75]),"+f"(d[76]),"+f"(d[77]),"+f"(d[78]),"+f"(d[79]),"+f"(d[80]),"+f"(d[81]),"+f"(d[82]),"+f"(d[83]),"+f"(d[84]),"+f"(d[85]),"+f"(d[86]),"+f"(d[87]),"+f"(d[88]),"+f"(d[89]),"+f"(d[90]),"+f"(d[91]),"+f"(d[92]),"+f"(d[93]),"+f"(d[94]),"+f"(d[95]),"+f"(d[96]),"+f"(d[97]),"+f"(d[98]),"+f"(d[99]),"+f"(d[100]),"+f"(d[101]),"+f"(d[102]),"+f"(d[103]),"+f"(d[104]),"+f"(d[105]),"+f"(d[106]),"+f"(d[107]),"+f"(d[108]),"+f"(d[109]),"+f"(d[110]),"+f"(d[111]),"+f"(d[112]),"+f"(d[113]),"+f"(d[114]),"+f"(d[115]),"+f"(d[116]),"+f"(d[117]),"+f"(d[118]),"+f"(d[119]),"+f"(d[120]),"+f"(d[121]),"+f"(d[122]),"+f"(d[123]),"+f"(d[124]),"+f"(d[125]),"+f"(d[126]),"+f"(d[127])
    : "r"(da), "r"(db), "r"(sd));
}
__device__ __forceinline__ void wgmma_r1_n128(float (&d)[64], uint32_t da, uint32_t db, int sd) {
  asm volatile("{\n.reg .pred p;\n.reg .b64 a, b;\nsetp.ne.b32 p, %66, 0;\nmov.b64 a, {%64, 0x8};\nmov.b64 b, {%65, 0x6};\n"
    "wgmma.mma_async.sync.aligned.m64n128k16.f32.bf16.bf16 {%0,%1,%2,%3,%4,%5,%6,%7,%8,%9,%10,%11,%12,%13,%14,%15,%16,%17,%18,%19,%20,%21,%22,%23,%24,%25,%26,%27,%28,%29,%30,%31,%32,%33,%34,%35,%36,%37,%38,%39,%40,%41,%42,%43,%44,%45,%46,%47,%48,%49,%50,%51,%52,%53,%54,%55,%56,%57,%58,%59,%60,%61,%62,%63}, a, b, p, 1, 1, 0, 1;\n}\n"
    : "+f"(d[0]),"+f"(d[1]),"+f"(d[2]),"+f"(d[3]),"+f"(d[4]),"+f"(d[5]),"+f"(d[6]),"+f"(d[7]),"+f"(d[8]),"+f"(d[9]),"+f"(d[10]),"+f"(d[11]),"+f"(d[12]),"+f"(d[13]),"+f"(d[14]),"+f"(d[15]),"+f"(d[16]),"+f"(d[17]),"+f"(d[18]),"+f"(d[19]),"+f"(d[20]),"+f"(d[21]),"+f"(d[22]),"+f"(d[23]),"+f"(d[24]),"+f"(d[25]),"+f"(d[26]),"+f"(d[27]),"+f"(d[28]),"+f"(d[29]),"+f"(d[30]),"+f"(d[31]),"+f"(d[32]),"+f"(d[33]),"+f"(d[34]),"+f"(d[35]),"+f"(d[36]),"+f"(d[37]),"+f"(d[38]),"+f"(d[39]),"+f"(d[40]),"+f"(d[41]),"+f"(d[42]),"+f"(d[43]),"+f"(d[44]),"+f"(d[45]),"+f"(d[46]),"+f"(d[47]),"+f"(d[48]),"+f"(d[49]),"+f"(d[50]),"+f"(d[51]),"+f"(d[52]),"+f"(d[53]),"+f"(d[54]),"+f"(d[55]),"+f"(d[56]),"+f"(d[57]),"+f"(d[58]),"+f"(d[59]),"+f"(d[60]),"+f"(d[61]),"+f"(d[62]),"+f"(d[63])
    : "r"(da), "r"(db), "r"(sd));
}

__device__ __forceinline__ uint32_t smem_u32(const void* p) { return (uint32_t)__cvta_generic_to_shared(p); }
__device__ __forceinline__ void mbar_init(uint32_t bar, uint32_t cnt) { asm volatile("mbarrier.init.shared::cta.b64 [%0], %1;" ::"r"(bar), "r"(cnt)); }
__device__ __forceinline__ void mbar_expect_tx(uint32_t bar, uint32_t bytes) { asm volatile("mbarrier.arrive.expect_tx.shared::cta.b64 _, [%0], %1;" ::"r"(bar), "r"(bytes) : "memory"); }
__device__ __forceinline__ void mbar_arrive(uint32_t bar) { asm volatile("mbarrier.arrive.shared::cta.b64 _, [%0];" ::"r"(bar) : "memory"); }
__device__ __forceinline__ void mbar_arrive_n(uint32_t bar, uint32_t n) { asm volatile("mbarrier.arrive.shared::cta.b64 _, [%0], %1;" ::"r"(bar), "r"(n) : "memory"); }
__device__ __forceinline__ void mbar_wait(uint32_t bar, uint32_t parity) {
  asm volatile("{\n.reg .pred p;\nLAB_WAIT:\nmbarrier.try_wait.parity.shared::cta.b64 p, [%0], %1;\n@p bra DONE;\nbra LAB_WAIT;\nDONE:\n}" ::"r"(bar), "r"(parity) : "memory");
}
__device__ __forceinline__ void mbar_wait2(uint32_t a, uint32_t pa, uint32_t b, uint32_t pb) {
  asm volatile("{\n.reg .pred p, q;\nLAB_WAIT:\nmbarrier.try_wait.parity.shared::cta.b64 p, [%0], %1;\nmbarrier.try_wait.parity.shared::cta.b64 q, [%2], %3;\n"
               "and.pred p, p, q;\n@p bra DONE;\nbra LAB_WAIT;\nDONE:\n}" ::"r"(a), "r"(pa), "r"(b), "r"(pb) : "memory");
}
__device__ __forceinline__ void mbar_wait3(uint32_t a, uint32_t pa, uint32_t b, uint32_t pb) {
  asm volatile("{\n.reg .pred p, q, r;\nLAB_WAIT:\nmbarrier.try_wait.parity.shared::cta.b64 p, [%0], %1;\nmbarrier.try_wait.parity.shared::cta.b64 q, [%2], %3;\n"
               "mbarrier.try_wait.parity.shared::cta.b64 r, [%2+8], %3;\nand.pred p, p, q;\nand.pred p, p, r;\n@p bra DONE;\nbra LAB_WAIT;\nDONE:\n}" ::"r"(a), "r"(pa), "r"(b), "r"(pb) : "memory");
}
__device__ __forceinline__ bool mbar_probe2(uint32_t a, uint32_t pa, uint32_t b, uint32_t pb) {
  uint32_t ok;
  asm volatile("{\n.reg .pred p, q;\nmbarrier.test_wait.parity.shared::cta.b64 p, [%1], %2;\nmbarrier.test_wait.parity.shared::cta.b64 q, [%3], %4;\n"
               "and.pred p, p, q;\nselp.u32 %0, 1, 0, p;\n}" : "=r"(ok) : "r"(a), "r"(pa), "r"(b), "r"(pb) : "memory");
  return ok != 0;
}
__device__ __forceinline__ void tma_load_3d(uint32_t dst, const CUtensorMap* tm, uint32_t bar, int c0, int c1, int c2) {
  asm volatile("cp.async.bulk.tensor.3d.shared::cluster.global.mbarrier::complete_tx::bytes [%0], [%1, {%3, %4, %5}], [%2];"
               ::"r"(dst), "l"(tm), "r"(bar), "r"(c0), "r"(c1), "r"(c2) : "memory");
}
__device__ __forceinline__ void tma_load_2d(uint32_t dst, const CUtensorMap* tm, uint32_t bar, int c0, int c1) {
  asm volatile("cp.async.bulk.tensor.2d.shared::cluster.global.mbarrier::complete_tx::bytes [%0], [%1, {%3, %4}], [%2];"
               ::"r"(dst), "l"(tm), "r"(bar), "r"(c0), "r"(c1) : "memory");
}
__device__ __forceinline__ void tma_load_w(uint32_t dst, const CUtensorMap* tm, uint32_t bar, int col, int kb) {
#pragma unroll
  for (int q = 0; q < 2; q++)
    asm volatile("cp.async.bulk.tensor.5d.shared::cluster.global.mbarrier::complete_tx::bytes [%0], [%1, {%3, %4, %4, %4, %5}], [%2];"
                 ::"r"(dst + q * 8192), "l"(tm), "r"(bar), "r"(col + q * 64), "r"(0), "r"(2 * kb) : "memory");
}
__device__ __forceinline__ void tma_prefetch_w(const CUtensorMap* tm, int col, int kb) {
#pragma unroll
  for (int q = 0; q < 2; q++)
    asm volatile("cp.async.bulk.prefetch.tensor.5d.L2.global [%0, {%1, %2, %2, %2, %3}];" ::"l"(tm), "r"(col + q * 64), "r"(0), "r"(2 * kb) : "memory");
}
__device__ __forceinline__ void bulk_load(uint32_t dst, const void* g, uint32_t bytes, uint32_t bar) {
  asm volatile("cp.async.bulk.shared::cluster.global.mbarrier::complete_tx::bytes [%0], [%1], %2, [%3];" ::"r"(dst), "l"(g), "r"(bytes), "r"(bar) : "memory");
}
__device__ __forceinline__ void prefetch_map(const CUtensorMap* tm) { asm volatile("prefetch.tensormap [%0];" ::"l"(tm) : "memory"); }
__device__ __forceinline__ void fence_async_smem() { asm volatile("fence.proxy.async.shared::cta;" ::: "memory"); }
__device__ __forceinline__ void fence_async_global() { asm volatile("fence.proxy.async.global;" ::: "memory"); }
__device__ __forceinline__ void fence_gpu() { asm volatile("fence.release.gpu;" ::: "memory"); }
__device__ __forceinline__ void st_flag(unsigned* p, unsigned v) { asm volatile("st.relaxed.gpu.global.u32 [%0], %1;" ::"l"(p), "r"(v) : "memory"); }
__device__ __forceinline__ unsigned ld_flag(const unsigned* p) { unsigned v; asm volatile("ld.relaxed.gpu.global.u32 %0, [%1];" : "=r"(v) : "l"(p) : "memory"); return v; }
__device__ __forceinline__ uint4 ldcg4(const void* p) { uint4 v; asm volatile("ld.global.cg.v4.u32 {%0,%1,%2,%3}, [%4];" : "=r"(v.x), "=r"(v.y), "=r"(v.z), "=r"(v.w) : "l"(p)); return v; }
__device__ __forceinline__ uint4 ld_pkt(const uint4* p) {
  uint4 v; asm volatile("{\n.reg .b128 t;\nld.relaxed.gpu.global.b128 t, [%4];\nmov.b128 {%0,%1,%2,%3}, t;\n}" : "=r"(v.x), "=r"(v.y), "=r"(v.z), "=r"(v.w) : "l"(p) : "memory"); return v;
}
__device__ __forceinline__ void st_pkt(uint4* p, uint32_t a, uint32_t b, uint32_t c, uint32_t tag) {
  asm volatile("{\n.reg .b128 t;\nmov.b128 t, {%1,%2,%3,%4};\nst.relaxed.gpu.global.b128 [%0], t;\n}" ::"l"(p), "r"(a), "r"(b), "r"(c), "r"(tag) : "memory");
}
__device__ __forceinline__ void st_v4(uint4* p, uint32_t a, uint32_t b, uint32_t c, uint32_t d) { asm volatile("st.relaxed.gpu.global.v4.u32 [%0], {%1,%2,%3,%4};" ::"l"(p), "r"(a), "r"(b), "r"(c), "r"(d) : "memory"); }
__device__ __forceinline__ void stg128(uint4* p, uint4 v) { asm volatile("st.global.v4.u32 [%0], {%1,%2,%3,%4};" ::"l"(p), "r"(v.x), "r"(v.y), "r"(v.z), "r"(v.w) : "memory"); }
__device__ __forceinline__ void sts32(uint32_t addr, uint32_t a) { asm volatile("st.shared.u32 [%0], %1;" ::"r"(addr), "r"(a) : "memory"); }
__device__ __forceinline__ void sts64(uint32_t addr, uint32_t a, uint32_t b) { asm volatile("st.shared.v2.u32 [%0], {%1,%2};" ::"r"(addr), "r"(a), "r"(b) : "memory"); }
__device__ __forceinline__ uint32_t mul2(uint32_t a, uint32_t b) { uint32_t r; asm("mul.rn.bf16x2 %0, %1, %2;" : "=r"(r) : "r"(a), "r"(b)); return r; }
__device__ __forceinline__ uint32_t add2(uint32_t a, uint32_t b) { uint32_t r; asm("add.rn.bf16x2 %0, %1, %2;" : "=r"(r) : "r"(a), "r"(b)); return r; }
__device__ __forceinline__ bool elect() {
  uint32_t p; asm volatile("{\n.reg .pred q;\nelect.sync _|q, 0xffffffff;\nselp.u32 %0, 1, 0, q;\n}" : "=r"(p)); return p != 0;
}
__device__ __forceinline__ void wgmma_fence() { asm volatile("wgmma.fence.sync.aligned;" ::: "memory"); }
__device__ __forceinline__ void wgmma_commit() { asm volatile("wgmma.commit_group.sync.aligned;" ::: "memory"); }
template <int N> __device__ __forceinline__ void wgmma_wait() { asm volatile("wgmma.wait_group.sync.aligned %0;" ::"n"(N) : "memory"); }
template <int N> __device__ __forceinline__ void fence_regs(float (&d)[N]) {
#pragma unroll
  for (int i = 0; i < N; i++) asm volatile("" : "+f"(d[i])::"memory");
}
template <int R> __device__ __forceinline__ void reg_alloc() { asm volatile("setmaxnreg.inc.sync.aligned.u32 %0;" ::"n"(R)); }
template <int R> __device__ __forceinline__ void reg_dealloc() { asm volatile("setmaxnreg.dec.sync.aligned.u32 %0;" ::"n"(R)); }
__device__ __forceinline__ void wg_bar(int w) { asm volatile("bar.sync %0, 128;" ::"r"(w + 1) : "memory"); }
__device__ __forceinline__ constexpr uint32_t desc_lo(uint32_t addr, uint32_t lbo) { return (addr >> 4) + ((lbo >> 4) << 16); }
__device__ __forceinline__ uint32_t pack2(float lo, float hi) { uint32_t r; asm("cvt.rn.bf16x2.f32 %0, %1, %2;" : "=r"(r) : "f"(hi), "f"(lo)); return r; }
__device__ __forceinline__ float lo16(uint32_t v) { return __uint_as_float(v << 16); }
__device__ __forceinline__ float hi16(uint32_t v) { return __uint_as_float(v & 0xFFFF0000u); }
__device__ __forceinline__ float ex2(float x) { float r; asm("ex2.approx.ftz.f32 %0, %1;" : "=f"(r) : "f"(x)); return r; }
__device__ __forceinline__ float rcp(float x) { float r; asm("rcp.approx.ftz.f32 %0, %1;" : "=f"(r) : "f"(x)); return r; }
__device__ __forceinline__ uint32_t movm(uint32_t a) { uint32_t d; asm volatile("movmatrix.sync.aligned.m8n8.trans.b16 %0, %1;" : "=r"(d) : "r"(a)); return d; }
__device__ __forceinline__ void stsm4(uint32_t addr, uint32_t a, uint32_t b, uint32_t c, uint32_t d) {
  asm volatile("stmatrix.sync.aligned.m8n8.x4.shared.b16 [%0], {%1,%2,%3,%4};" ::"r"(addr), "r"(a), "r"(b), "r"(c), "r"(d) : "memory");
}
__device__ __forceinline__ void ldsm4(uint32_t addr, uint32_t (&r)[4]) {
  asm volatile("ldmatrix.sync.aligned.m8n8.x4.shared.b16 {%0,%1,%2,%3}, [%4];" : "=r"(r[0]), "=r"(r[1]), "=r"(r[2]), "=r"(r[3]) : "r"(addr) : "memory");
}
__device__ __forceinline__ void sts128(uint32_t addr, uint32_t a, uint32_t b, uint32_t c, uint32_t d) {
  asm volatile("st.shared.v4.u32 [%0], {%1,%2,%3,%4};" ::"r"(addr), "r"(a), "r"(b), "r"(c), "r"(d) : "memory");
}
__device__ __forceinline__ void lds128(uint32_t addr, uint32_t& a, uint32_t& b, uint32_t& c, uint32_t& d) {
  asm volatile("ld.shared.v4.u32 {%0,%1,%2,%3}, [%4];" : "=r"(a), "=r"(b), "=r"(c), "=r"(d) : "r"(addr) : "memory");
}
__device__ __forceinline__ float lds32f(uint32_t addr) { float v; asm volatile("ld.shared.f32 %0, [%1];" : "=f"(v) : "r"(addr) : "memory"); return v; }
__device__ __forceinline__ float2 lds64f(uint32_t addr) { float2 v; asm volatile("ld.shared.v2.f32 {%0,%1}, [%2];" : "=f"(v.x), "=f"(v.y) : "r"(addr) : "memory"); return v; }
__device__ __forceinline__ void mma16816(float (&d)[4], uint32_t a0, uint32_t a1, uint32_t a2, uint32_t a3, uint32_t b0, uint32_t b1) {
  asm("mma.sync.aligned.m16n8k16.row.col.f32.bf16.bf16.f32 {%0,%1,%2,%3}, {%4,%5,%6,%7}, {%8,%9}, {%0,%1,%2,%3};"
      : "+f"(d[0]), "+f"(d[1]), "+f"(d[2]), "+f"(d[3]) : "r"(a0), "r"(a1), "r"(a2), "r"(a3), "r"(b0), "r"(b1));
}
__device__ __forceinline__ void mma1688(float (&d)[4], uint32_t a0, uint32_t a1, uint32_t b0) {
  asm("mma.sync.aligned.m16n8k8.row.col.f32.bf16.bf16.f32 {%0,%1,%2,%3}, {%4,%5}, {%6}, {%0,%1,%2,%3};"
      : "+f"(d[0]), "+f"(d[1]), "+f"(d[2]), "+f"(d[3]) : "r"(a0), "r"(a1), "r"(b0));
}

__device__ __forceinline__ float qsum(float v) { v += __shfl_xor_sync(0xffffffffu, v, 1); v += __shfl_xor_sync(0xffffffffu, v, 2); return v; }

constexpr int NCTA = 132;
#define NB_ 6
#define NA_ 5
constexpr int NB = NB_;
constexpr int NA = NA_;
constexpr uint32_t SLOT = 16384;
constexpr uint32_t SB = 1024;
constexpr uint32_t OFF_B = 0;
constexpr uint32_t OFF_A = NB * SLOT;
constexpr uint32_t OFF_S = OFF_A + NA * SLOT;
constexpr uint32_t OFF_T = OFF_S + 20480;
constexpr uint32_t OFF_CS = OFF_T + 24576;
constexpr uint32_t OFF_MR = OFF_CS + 4640;
constexpr uint32_t OFF_BAR = OFF_MR + 512;
constexpr uint32_t OFF_MA = OFF_S, OFF_MB = OFF_CS - 2048;
constexpr uint32_t BAR_FULLB = OFF_BAR;
constexpr uint32_t BAR_FULLA = BAR_FULLB + 64;
constexpr uint32_t BAR_EMPTYB = BAR_FULLA + 64;
constexpr uint32_t BAR_EMPTYA = BAR_EMPTYB + 64;
constexpr uint32_t BAR_SIGP = BAR_EMPTYA + 64;
constexpr uint32_t BAR_SIGT = BAR_SIGP + 32;
constexpr uint32_t BAR_STAT = BAR_SIGP + 64;
constexpr uint32_t BAR_HALO = BAR_STAT + 16;
constexpr uint32_t BAR_CS = BAR_HALO + 8;
constexpr uint32_t BAR_WPHI = BAR_CS + 16;
constexpr uint32_t BAR_KV = BAR_WPHI + 8;
constexpr uint32_t BAR_STG = BAR_KV + 16;
constexpr uint32_t BAR_EPOCH = BAR_STG + 48;
constexpr uint32_t OFF_EPOCH = OFF_BAR + 7 * 64;
static_assert(BAR_EPOCH < OFF_EPOCH, "barriers");
constexpr uint32_t SMEM_BYTES = OFF_EPOCH + 8;
static_assert(SMEM_BYTES <= 232448 && NB % 2 == 0 && NB <= 8 && NA <= 6, "smem");

#define CREGS 224
#define PREGS 56
#define PF1 19
#define PF2 21
#define PRE_A 2
#define PRE_B 4
#define CSB 4
#define CSNEED 0xF003u
#define XR 1
#define PS0 1
#define PS1 3
#define PSW 0
#define SD 1000
#define QORD 4
#define KSPLIT 12
#define KEEP 16
#define NJ 3
#define KSL 1000
#define PSL 0
#define KVS 12
#define D2 2000
#define D3 1500
#define G0 50
#define G3 50
#define G1 0
#define G4 0
#define MAP 3
#define PMAP 0x76321450u
#define PW 1
#define PN2 0
#define XA 3
#define XS 1
#define IP 3
#define UK 0
#define CP 500
#define CD 0
#define S0 500
#define NS 2
#define XO 0
#define SW 2
#define SA 1
#define SB_ 4
#define KB 8
#define PNX 2
#define PNO 2
#define DEFER 3
#define DEFL 2
#define TSK 3
#define TSL 3
constexpr int NTHREADS = 384;

struct Params {
  CUtensorMap mx;
  CUtensorMap mw[3];
  CUtensorMap mwo[2];
  CUtensorMap mcs[2];
  CUtensorMap mwphi;
  uint4* out;
};

#define XBUF(L) 1
__device__ __align__(256) uint4 g_img[XBUF(3) + 1][16][16][1024];
__device__ __align__(256) uint4 g_wf[2][8][16][1024];
__device__ __align__(256) uint4 g_stats[16][2][8][32];
__device__ __align__(256) uint4 g_halo[16][8][2][256];
__device__ __align__(256) float g_cs[2][2][3072];
__device__ __align__(256) uint4 g_kvpart[8][16][2][544];
__device__ __align__(256) uint4 g_kvfin[8][16][80];
__device__ __align__(256) unsigned g_xflag[4][2][16][32];
__device__ __align__(256) unsigned g_oflag[4][2][16][32];
__device__ __align__(256) unsigned g_hflag[2][16][8][32];
__device__ __align__(256) unsigned g_kvfflag[2][8][2][32];
__device__ __align__(256) unsigned g_csflag[2][8][32];
__device__ __align__(256) unsigned g_kflag[8][32];
__device__ unsigned g_ctr;
__device__ __forceinline__ unsigned vblock() {
  unsigned s;
  asm volatile("mov.u32 %0, %%smid;" : "=r"(s));
  const unsigned r = s & 1;
  s >>= 1;
  const unsigned t = s - 32, q = (t * 37) >> 8;
  const unsigned hi = s < 60 ? 12 + (t - 7 * q) * 8 + q : (s < 62 ? s + 4 : s - 58);
  unsigned b = 2 * (s < 32 ? (s & 7) * 8 + (s >> 3) : hi) + r;
  if (b < 128) b = (b & 15) | ((PMAP >> ((b >> 4) * 4)) & 7) << 4;
  if (s >= 62) b = 8 + 4 * r + s - 62;
  return __shfl_sync(0xffffffffu, b, 0);
}
#define TS(who, id) do {} while (0)
#define TSW(id) do {} while (0)

#define TSMASK 0xFFFF
#define TSL_(a) do { if ((TSMASK >> (a)) & 1) TSW((a) + L * 12); } while (0)
__device__ __forceinline__ int cta_m(unsigned b) { return ((b >> 2) & 12) | (b & 3); }
__device__ __forceinline__ int cta_j(unsigned b) { return ((b >> 2) & 3) | ((b >> 4) & 4); }
struct Ring { uint32_t s, ph; };
template <int N> __device__ __forceinline__ void adv(Ring& r) { if (++r.s == N) { r.s = 0; r.ph ^= 1; } }
template <int N> __device__ __forceinline__ void rewind2(Ring& r) { if (r.s < 2) { r.s += N - 2; r.ph ^= 1; } else r.s -= 2; }
__device__ __forceinline__ int other_tile(int t, int j) { return (t == (j | 4) ? 7 : t) ^ (~j & 4); }
__device__ __forceinline__ int q_order(int i, int j) { return 2 * (i >= 14 ? j : other_tile(i >> 1, j)) + (i & 1); }
__device__ __forceinline__ int o_order(int i, int j) {
  if (i < 2) return 2 * j + i;
  const int odd = i >= 9;
  return 2 * other_tile(i - 2 - 7 * odd, j) + odd;
}
__device__ __forceinline__ int kv_order(int i, int j, int L) { return L > 0 ? o_order(i, j) : (i + 14 + 2 * (j & 4)) & 15; }

__device__ __forceinline__ unsigned poll_flags(const unsigned* f, int n, unsigned need, unsigned tag) {
  const int lane = threadIdx.x & 31;
  unsigned mask; int it = 0;
  do {
    unsigned v = lane < n ? ld_flag(f + lane) : 0u;
    mask = __ballot_sync(0xffffffffu, lane < n && v == tag);
    if (++it > (1 << 22)) __trap();
  } while ((mask & need) != need);
  fence_async_global();
  return mask;
}
template <bool WAIT = true>
__device__ __forceinline__ unsigned get_tag(uint32_t sb) {
  if (WAIT) mbar_wait(sb + BAR_EPOCH, 0);
  unsigned t; asm volatile("ld.shared.u32 %0, [%1];" : "=r"(t) : "r"(sb + OFF_EPOCH) : "memory");
  return t;
}

__device__ __forceinline__ int lane_id() { int l; asm volatile("mov.u32 %0, %%laneid;" : "=r"(l)); return l; }
__device__ __forceinline__ unsigned seq4(unsigned tag, int L) { return 8u | ((tag & 1u) << 2) | (unsigned)L; }
constexpr float LOG2E = 1.4426950408889634f;

__device__ __forceinline__ float bb_fence(int never) { while (never < 0) never = ld_flag(&g_ctr + never); return __int_as_float(never >> 30); }
__device__ __forceinline__ void bb_keep(const float* v, int never) {
  while (never < 0) {
#pragma unroll
    for (int q = 0; q < 32; q += 4) sts128(never + q * 4, __float_as_uint(v[q]), __float_as_uint(v[q + 1]), __float_as_uint(v[q + 2]), __float_as_uint(v[q + 3]));
    never = ld_flag(&g_ctr + never);
  }
}
constexpr uint32_t HA128 = 0x40000040u, HA64 = 0x80000040u;
struct Ctx {
  static constexpr uint32_t sb = SB;
  uint32_t ab, da0;
  int w, warp, lane, g, c;
  int goff;
  __device__ __forceinline__ int m() const { return goff >> 14; }
  __device__ __forceinline__ int j() const { return (goff >> 4) & 7; }
  bool elected;
  Ring ra, rb;
  uint32_t pa, pb;
  uint32_t ha, k2;
  uint32_t mrow, mxor, mhi;
  __device__ __forceinline__ uint32_t aslot(uint32_t s) const { return ab + s * SLOT; }
  __device__ __forceinline__ uint32_t fullA(uint32_t s) const { return sb + BAR_FULLA + s * 8; }
  __device__ __forceinline__ uint32_t fullB(uint32_t s) const { return sb + BAR_FULLB + s * 8; }
  __device__ __forceinline__ void releaseA(uint32_t s) const { if (elected) mbar_arrive(sb + BAR_EMPTYA + s * 8); }
  __device__ __forceinline__ void releaseB(uint32_t s) const { if (elected) mbar_arrive(sb + BAR_EMPTYB + s * 8); }
  __device__ __forceinline__ uint32_t maddr(uint32_t tile, uint32_t ch) const { return tile + mrow + (((ch + mhi) ^ mxor) << 4); }
  __device__ __forceinline__ uint32_t oo() const { return warp * 128 + g * 4 + (c ^ (g >> 1)); }
  __device__ __forceinline__ uint4* img(int b, int hp) const { return (IP & 1) ? ip + (b * 256 + hp) * 1024 : &g_img[b][m()][2 * j() + hp][w * 512 + oo()]; }
  uint4* ip;
  __device__ __forceinline__ uint32_t held(int i) const { return ra.s + i < 2 ? ra.s + i + NA - 2 : ra.s + i - 2; }
};

template <int N, bool FIRST, bool O = true>
__device__ __forceinline__ void gemm_issue(float (&acc)[N / 2], Ctx& x, bool ready = false) {
  if (!ready) {
    if (N == 256) mbar_wait3(x.fullA(x.ra.s), x.ra.ph, x.fullB(x.rb.s), x.rb.ph);
    else mbar_wait2(x.fullA(x.ra.s), x.ra.ph, x.fullB(x.rb.s), x.rb.ph);
  }
  const uint32_t da = x.da0 + x.ra.s * (SLOT / 16), db = desc_lo(SB + OFF_B, 8192) + x.rb.s * (SLOT / 16);
  wgmma_fence();
#pragma unroll
  for (int k = 0; k < 4; k++) {
    const uint32_t a = da + (k >> 1) * (O ? 32 : x.k2) + (k & 1) * 2, ha = O ? HA64 : x.ha;
    if constexpr (N == 256) wgmma_ss_n256(acc, a, ha, db + 128 * k, !(FIRST && k == 0));
    else wgmma_ss_n128(acc, a, ha, db + 128 * k, !(FIRST && k == 0));
  }
  wgmma_commit();
}
template <int N>
__device__ __forceinline__ void gemm_next(Ctx& x) {
  x.pa = x.ra.s; x.pb = x.rb.s;
  if (N == 256) x.rb.s++;
  adv<NA>(x.ra); adv<NB>(x.rb);
}
template <int N>
__device__ __forceinline__ void gemm_release(Ctx& x, bool relA) {
  if (relA) x.releaseA(x.pa);
  x.releaseB(x.pb);
  if (N == 256) x.releaseB(x.pb + 1);
}
template <int N>
__device__ __forceinline__ void gemm_retire(Ctx& x, bool relA) { wgmma_wait<1>(); gemm_release<N>(x, relA); gemm_next<N>(x); }
template <bool O = true>
__device__ __forceinline__ void gemm_run(float (&acc)[64], Ctx& x, int n, int hold, int n4 = 0) {
  bool ready = false;
#pragma unroll 1
  for (; n > 0; n--) {
    gemm_issue<128, false, O>(acc, x, ready);
    const uint32_t pa = x.pa, pb = x.pb;
    gemm_next<128>(x);
    ready = mbar_probe2(x.fullA(x.ra.s), x.ra.ph, x.fullB(x.rb.s), x.rb.ph);
    wgmma_wait<1>();
    if (n > hold) x.releaseA(pa);
    x.releaseB(pb);
  }
}
__device__ __forceinline__ void gemm_end(float (&acc)[64], Ctx& x) { wgmma_wait<0>(); fence_regs(acc); gemm_release<128>(x, false); }

__device__ __forceinline__ void rows_load(uint4* r, uint32_t tile, const Ctx& x) {
#pragma unroll
  for (int q = 0; q < 4; q++) {
    const uint32_t row = x.warp * 16 + 4 * q + (x.lane >> 3);
    lds128(tile + row * 128 + (((x.lane & 7) ^ (row & 7)) << 4), r[q].x, r[q].y, r[q].z, r[q].w);
  }
}
__device__ __forceinline__ void rows_store(const uint4* r, uint4* g, const Ctx& x) {
  g += (x.warp * 16 + (x.lane >> 3)) * 256 + (x.lane & 7);
#pragma unroll
  for (int q = 0; q < 4; q++) g[q * 1024] = r[q];
}
__device__ __forceinline__ void publish(int id, const Ctx& x) { __syncwarp(); if (x.lane == 0) mbar_arrive(x.sb + BAR_SIGP + id * 8); }
__device__ __forceinline__ void img_store(const uint4 (&r)[4], uint4* g) {
#pragma unroll
  for (int q = 0; q < 4; q++) stg128(g + q * 32, r[q]);
}
__device__ __forceinline__ void img_sts(const uint4 (&r)[4], uint32_t tile, const Ctx& x) {
#pragma unroll
  for (int q = 0; q < 4; q++) sts128(tile + x.oo() * 16 + q * 512, r[q].x, r[q].y, r[q].z, r[q].w);
}
__device__ __forceinline__ void img_load(uint32_t (&v)[16], uint32_t tile, const Ctx& x) {
#pragma unroll
  for (int q = 0; q < 4; q++) lds128(tile + x.oo() * 16 + q * 512, v[4 * q], v[4 * q + 1], v[4 * q + 2], v[4 * q + 3]);
}
__device__ __forceinline__ void img_unpack(float* a, const uint32_t (&v)[16]) {
#pragma unroll
  for (int q = 0; q < 16; q++) { a[4 * (q & 7) + 2 * (q >> 3)] = lo16(v[q]); a[4 * (q & 7) + 2 * (q >> 3) + 1] = hi16(v[q]); }
}

template <int N>
__device__ __forceinline__ void stats_acc(const float* a, float (&t)[4]) {
#pragma unroll
  for (int i = 0; i < N; i++) { t[i & 2] += a[i]; t[(i & 2) + 1] = fmaf(a[i], a[i], t[(i & 2) + 1]); }
}
__device__ __forceinline__ void stats_send(float (&t)[4], int L, const Ctx& x) {
  const unsigned seq = seq4(get_tag<false>(x.sb), L);
#pragma unroll
  for (int q = 0; q < 4; q++) t[q] = qsum(t[q]);
  if (x.c == 0) st_pkt(&g_stats[x.m()][x.w][x.j()][x.warp * 8 + x.g], __float_as_uint(t[0]), __float_as_uint(t[1]), __float_as_uint(t[2]), (__float_as_uint(t[3]) & ~15u) | seq);
}
__device__ __forceinline__ void out_epilogue(const float (&acc)[64], uint4 (&r1)[4], float (&t)[4], uint4* g, int L, Ctx& x) {
  const uint32_t t0 = x.aslot(x.ra.s), t1 = x.aslot(x.ra.s + 1 == NA ? 0 : x.ra.s + 1);
  if (L == 3) {
#pragma unroll
    for (int p = 0; p < 8; p++) {
      stsm4(x.maddr(p < 4 ? t0 : t1, (p & 3) * 2), pack2(acc[8 * p], acc[8 * p + 1]), pack2(acc[8 * p + 2], acc[8 * p + 3]),
            pack2(acc[8 * p + 4], acc[8 * p + 5]), pack2(acc[8 * p + 6], acc[8 * p + 7]));
      if ((p & 3) == 3) { uint4 r[4]; __syncwarp(); rows_load(r, p < 4 ? t0 : t1, x); rows_store(r, g + (p >> 2) * 8, x); }
    }
  } else {
    auto pack16 = [&](uint4 (&r)[4], const float* a) {
#pragma unroll
      for (int q = 0; q < 4; q++) { const float* u = a + 16 * (q & 1) + (q & 2); r[q] = make_uint4(pack2(u[0], u[1]), pack2(u[4], u[5]), pack2(u[8], u[9]), pack2(u[12], u[13])); }
    };
    uint4 r0[4];
    pack16(r0, acc);
    img_store(r0, x.img(XBUF(L + 1), 0));
    publish(2, x);
    const float z0 = bb_fence(x.goff), z = (IP & 2) ? z0 : 0.f;
    img_sts(r0, t0, x);
    pack16(r1, acc + 32);
    img_sts(r1, t1, x);
    float u[4] = {z, z, z, z}, v[4] = {z, z, z, z};
    stats_acc<32>(acc, v); stats_acc<32>(acc + 32, u);
#pragma unroll
    for (int q = 0; q < 4; q++) t[q] = u[q] + v[q];
    mbar_wait2(x.fullB(x.rb.s), x.rb.ph, x.fullB(x.rb.s + 1), x.rb.ph);
    fence_async_smem();
    asm volatile("bar.sync %0, %1;" ::"r"(L == 1 ? x.w + 1 : 3), "r"(L == 1 ? 128 : 256) : "memory");
  }
}

struct Stats { float rstd0, rstd1; };
__device__ __forceinline__ Stats load_stats(int half, const Ctx& x) {
  const float2 u = lds64f(x.sb + OFF_MR + half * 256 + (x.warp * 8 + x.g) * 8);
  return {u.x, u.y};
}

template <int NK>
__device__ __forceinline__ void hedgehog_scale(float* t, const Stats& st, const uint32_t* keep) {
#pragma unroll
  for (int q = 0; q < 16; q++) t[q] *= ((q & 2) ? st.rstd1 : st.rstd0) * LOG2E;
  float m[4];
#pragma unroll
  for (int q = 0; q < 4; q++) m[q] = fmaxf(fmaxf(fabsf(t[4 * q]), fabsf(t[4 * q + 1])), fmaxf(fabsf(t[4 * q + 2]), fabsf(t[4 * q + 3])));
  if (__builtin_expect(__any_sync(0xffffffffu, fmaxf(fmaxf(m[0], m[1]), fmaxf(m[2], m[3])) > 58.f), 0)) {
    float z[16 + NK];
#pragma unroll
    for (int q = 0; q < 16 + NK; q++) z[q] = q < 16 ? t[q & 15] : __uint_as_float(keep[q & 15]);
#pragma unroll 1
    for (int r = 0; r < 4; r += 2) {
      float hi = -INFINITY, lo = INFINITY;
#pragma unroll 1
      for (int i = 0; i < 16; i++) {
        const int k = (i & 6) * 2 + (i & 1) + r;
        const float v = z[k];
        if (i < 8) { hi = fmaxf(hi, v); lo = fminf(lo, v); }
        else z[k] = v - fminf(fmaxf(v, lo), hi);
        if (i == 7) {
#pragma unroll 1
          for (int d = 1; d <= 2; d++) { hi = fmaxf(hi, __shfl_xor_sync(0xffffffffu, hi, d)); lo = fminf(lo, __shfl_xor_sync(0xffffffffu, lo, d)); }
          const float mid = 0.5f * hi + 0.5f * lo;
          hi = fmaxf(hi - 58.f, mid); lo = fminf(lo + 58.f, mid);
        }
      }
    }
#pragma unroll
    for (int q = 0; q < 16; q++) t[q] = z[q];
  }
}
__device__ __forceinline__ void dual_exp(const float* t, uint32_t (&f)[18], int never) {
  float e[KSPLIT];
#pragma unroll
  for (int q = 0; q < KSPLIT; q++) e[q] = ex2(q < 16 ? t[q] : -t[q & 15]);
  while (never < 0) {
#pragma unroll
    for (int i = 0; i < KSPLIT; i += 4) asm volatile("ld.shared.v4.f32 {%0,%1,%2,%3}, [%4];" : "=f"(e[i]), "=f"(e[i + 1]), "=f"(e[i + 2]), "=f"(e[i + 3]) : "r"(never + i) : "memory");
    never += __float_as_int(e[0]);
  }
#pragma unroll
  for (int q = 0; q < KSPLIT; q += 2) f[q >> 1] = pack2(e[q], e[q + 1]);
#pragma unroll
  for (int q = KSPLIT; q < 32; q += 2) f[q >> 1] = q < 16 ? pack2(ex2(t[q]), ex2(t[q + 1])) : pack2(ex2(-t[q & 15]), ex2(-t[(q & 15) + 1]));
#pragma unroll
  for (int sg = 0; sg < 2; sg++) {
    const uint32_t* u = f + 8 * sg;
    const uint32_t a = add2(add2(u[0], u[2]), add2(u[4], u[6])), b = add2(add2(u[1], u[3]), add2(u[5], u[7]));
    f[16 + sg] = add2(__byte_perm(a, b, 0x5410), __byte_perm(a, b, 0x7632));
  }
}
__device__ __forceinline__ void dual_exp_rcp(const float* t, uint32_t (&f)[16]) {
#pragma unroll
  for (int q = 0; q < 8; q++) {
    const float a = ex2(t[2 * q]), b = ex2(t[2 * q + 1]), r = rcp(a * b);
    f[q] = pack2(a, b); f[8 + q] = pack2(r * b, r * a);
  }
}
__device__ __forceinline__ void cta_bar() { asm volatile("bar.sync 3, 256;" ::: "memory"); }

template <int N> __device__ __forceinline__ void pin(const uint32_t* v, uint32_t addr) {
#pragma unroll
  for (int i = 0; i < N; i += 4)
    asm volatile("{\n.reg .pred p;\nsetp.eq.u32 p, %0, 0;\n@p st.shared.v4.u32 [%0], {%1,%2,%3,%4};\n}" ::"r"(addr), "r"(v[i]), "r"(v[i + 1]), "r"(v[i + 2]), "r"(v[i + 3]) : "memory");
}

__device__ __forceinline__ void consumer(const Params& P, uint32_t sb, int w, unsigned vb) {
  Ctx x;
  x.w = w;
  x.ab = sb + OFF_A + w * 8192; x.da0 = desc_lo(SB + OFF_A, 16) + w * 512;
  x.lane = threadIdx.x & 31; x.warp = __shfl_sync(0xffffffffu, (threadIdx.x >> 5) & 3, 0); x.g = x.lane >> 2; x.c = x.lane & 3;
  x.goff = (cta_m(vb) * 128 + w) * 128 + cta_j(vb) * 16;
  asm volatile("" : "+r"(x.goff));
  x.elected = (threadIdx.x & 127) == 0;
  x.ra = {0, 0}; x.rb = {0, 0}; x.pa = x.pb = 0;
  {
    const uint32_t row = x.warp * 16 + (x.lane & 15);
    x.mrow = row * 128; x.mxor = row & 7; x.mhi = x.lane >> 4;
  }
  const int goff = x.goff;
  x.ip = (uint4*)__shfl_sync(0xffffffffu, (unsigned long long)&g_img[0][x.m()][2 * x.j()][w * 512 + x.oo()], x.lane);
  uint4 r1[4];
  float ts[4] = {0.f, 0.f, 0.f, 0.f};
#pragma unroll
  for (int i = 0; i < 4; i++) r1[i] = make_uint4(0, 0, 0, 0);
  TSW(0);
  mbar_wait3(x.fullA(0), 0, x.fullB(0), 0);
#pragma unroll 1
  for (int L = 0; L < 4; L++) {
    float acc[64];
    constexpr uint32_t dcs = desc_lo(SB + OFF_CS, 0);
    if ((L & 1) == 0) {
    float kv[128];
    x.ha = L ? HA64 : HA128; x.k2 = L ? 32 : 4;
    gemm_issue<256, true, false>(kv, x, true); gemm_next<256>(x);
    {
      int i = 1;
#pragma unroll 1
      for (int seg = L ? NS - 1 : 0; seg <= NS; seg++) {
        const int end = seg < NS ? (L == 0 ? 3 + SA * ((x.j() + SW * w) & 3) + SB_ * seg : XA + 1) : 14 + L;
#pragma unroll 1
        do {
          gemm_issue<256, false, false>(kv, x);
          gemm_retire<256>(x, true);
          i++;
          if (i == 5) TSL_(8);
          if (i == 11) TSL_(10);
        } while (i != end);
        if (seg < NS && L == 0) {
          uint32_t v[16];
          float a[32];
#pragma unroll
          for (int q = 0; q < 4; q++) ldsm4(x.maddr(x.aslot(x.pa), 2 * q), reinterpret_cast<uint32_t (&)[4]>(v[4 * q]));
#pragma unroll
          for (int q = 0; q < 16; q++) { a[2 * q] = lo16(v[q]); a[2 * q + 1] = hi16(v[q]); }
          stats_acc<32>(a, ts);
          fence_regs(ts);
          wg_bar(w);
        }
        if (seg == NS - 1) {
          if (L > 0) { img_store(r1, x.img(XBUF(L), 1)); publish(3, x); }
          mbar_wait(sb + BAR_EPOCH, 0);
          stats_send(ts, L, x);
        }
      }
    }
      const Ring kt = x.ra;
      if (L == 0) adv<NA>(x.ra);
#pragma unroll 1
      for (int h = L; h < 2; h++) {
        float d[16];
        mbar_wait2(x.fullA(kt.s), kt.ph, sb + BAR_WPHI, 0);
        wgmma_fence();
#pragma unroll
        for (int q = 0; q < 2; q++) wgmma_ss_n32(d, x.da0 + kt.s * (SLOT / 16) + h * 4 + q * 2, desc_lo(SB + OFF_S + 4096, 512) + w * 256 + h * 128 + q * 64, q);
        wgmma_commit();
        gemm_issue<256, false, false>(kv, x);
        gemm_retire<256>(x, true);
        if (h) x.releaseA(kt.s);
        fence_regs(d);
        uint4* dst = &g_wf[1][x.j()][x.m()][w * 512 + (x.warp * 16 + x.g) * 8 + ((h * 4 + x.c) ^ x.g)];
        dst[0] = make_uint4(pack2(d[0], d[1]), pack2(d[4], d[5]), pack2(d[8], d[9]), pack2(d[12], d[13]));
        dst[64] = make_uint4(pack2(d[2], d[3]), pack2(d[6], d[7]), pack2(d[10], d[11]), pack2(d[14], d[15]));
      }
      const uint32_t dm = desc_lo(SB + OFF_MA, 0) + w * 64;
      mbar_wait2(sb + BAR_STAT, 0, sb + BAR_CS, 0);
      wgmma_fence();
      wgmma_r1_n256(kv, dm, dcs + 96, 1);
      wgmma_commit();
      const Stats st = load_stats(w, x);
      if (PW & 1) mbar_wait2(x.fullA(x.ra.s), x.ra.ph, x.fullB(x.rb.s), x.rb.ph);
      wgmma_wait<0>();
      fence_regs(kv);
      gemm_release<256>(x, true);
      TSL_(2);
      uint32_t P0[32], P1[32], PH[32];
#pragma unroll
      for (int t = 0; t < 16; t++) { P0[t] = pack2(kv[4 * t] * st.rstd0, kv[4 * t + 1] * st.rstd0); P1[t] = pack2(kv[4 * t + 2] * st.rstd1, kv[4 * t + 3] * st.rstd1); }
      pin<16>(P0, x.mrow + 16);
      {
#pragma unroll
        for (int q = 0; q < 4; q++) sts128((x.warp < 3 ? sb + OFF_T + w * 12288 + x.warp * 4096 : sb + OFF_S + 16384 + w * 2048) + x.lane * 16 + q * 512, P1[4 * q], P1[4 * q + 1], P1[4 * q + 2], P1[4 * q + 3]);
      }
      wgmma_fence();
      wgmma_r1_n128(acc, dm, dcs, 0);
      gemm_issue<128, false, false>(acc, x, PW & 1); gemm_next<128>(x);
      TSL_(3);
#pragma unroll
      for (int s = 0; s < 4; s++) {
#pragma unroll
        for (int t = 16 + 8 * (s & 1); t < 24 + 8 * (s & 1); t++) {
          if (s < 2) P1[t] = movm(pack2(kv[4 * t + 2] * st.rstd1, kv[4 * t + 3] * st.rstd1));
          else P0[t] = movm(pack2(kv[4 * t] * st.rstd0, kv[4 * t + 1] * st.rstd0));
        }
        if (s < 3) { gemm_issue<128, false, false>(acc, x); gemm_retire<128>(x, true); }
        if (s == 1) {
          if (x.warp < 3) {
#pragma unroll
            for (int q = 4; q < 8; q++) sts128(sb + OFF_T + w * 12288 + x.warp * 4096 + x.lane * 16 + q * 512, P1[4 * q], P1[4 * q + 1], P1[4 * q + 2], P1[4 * q + 3]);
          } else {
            uint4* dst = &g_halo[x.m()][x.j()][w][x.lane];
#pragma unroll
            for (int q = 0; q < 8; q++) dst[q * 32] = make_uint4(P1[4 * q], P1[4 * q + 1], P1[4 * q + 2], P1[4 * q + 3]);
          }
          publish(4, x);
          gemm_issue<128, false, false>(acc, x);
          gemm_retire<128>(x, true);
        }
      }
      TSL_(4);
      gemm_run<false>(acc, x, 10, 0);
      gemm_issue<128, false, false>(acc, x);
      {
        wg_bar(w);
        uint32_t tr = sb + OFF_T + w * 12288 + (x.warp - 1) * 4096;
        if (x.warp == 0) {
          tr = x.m() > 0 ? sb + OFF_S + 8192 + w * 4096 : tr + 4096;
          if (x.m() > 0) mbar_wait(sb + BAR_HALO, L >> 1);
        }
#pragma unroll
        for (int q = 0; q < 8; q++) lds128(tr + x.lane * 16 + q * 512, PH[4 * q], PH[4 * q + 1], PH[4 * q + 2], PH[4 * q + 3]);
      }
      gemm_retire<128>(x, false);
      gemm_end(acc, x);
      TSL_(5);
      const bool first = (x.m() == 0) && (x.warp == 0);
      const bool hi0 = 2 * x.c > x.g, hi1 = 2 * x.c + 1 > x.g;
      const uint32_t mhi = (hi0 ? 0xFFFFu : 0u) | (hi1 ? 0xFFFF0000u : 0u);
      const float sc0 = st.rstd0 * (0.17677669529663687f * LOG2E), sc1 = st.rstd1 * (0.17677669529663687f * LOG2E);
#pragma unroll
      for (int hp = 0; hp < 2; hp++) {
        const uint32_t tile = x.aslot(x.held(hp));
        uint32_t px[2], py[2];
        float s[2][3][4];
#pragma unroll
        for (int u = 0; u < 2; u++) {
#pragma unroll
          for (int q = 0; q < 12; q++) s[u][q >> 2][q & 3] = 0.f;
#pragma unroll
          for (int ks = 0; ks < 2; ks++) {
            const int t = 8 * hp + 4 * u + 2 * ks;
            const uint32_t a0 = pack2(acc[4 * t], acc[4 * t + 1]), a1 = pack2(acc[4 * t + 2], acc[4 * t + 3]);
            const uint32_t a2 = pack2(acc[4 * t + 4], acc[4 * t + 5]), a3 = pack2(acc[4 * t + 6], acc[4 * t + 7]);
            mma16816(s[u][0], a0, a1, a2, a3, PH[t], PH[t + 1]);
            mma16816(s[u][1], a0, a1, a2, a3, P0[t], P0[t + 1]);
            mma16816(s[u][2], a0, a1, a2, a3, P1[t], P1[t + 1]);
          }
        }
        float e[2][4], r[2][2];
#pragma unroll
        for (int u = 0; u < 2; u++) {
          e[u][0] = (hi0 ? s[u][0][0] : s[u][1][0]) * sc0; e[u][1] = (hi1 ? s[u][0][1] : s[u][1][1]) * sc0;
          e[u][2] = (hi0 ? s[u][1][2] : s[u][2][2]) * sc1; e[u][3] = (hi1 ? s[u][1][3] : s[u][2][3]) * sc1;
          if (first) { if (hi0) e[u][0] = -1e30f; if (hi1) e[u][1] = -1e30f; }
          r[u][0] = fmaxf(e[u][0], e[u][1]); r[u][1] = fmaxf(e[u][2], e[u][3]);
        }
#pragma unroll
        for (int d = 1; d <= 2; d++)
#pragma unroll
          for (int q = 0; q < 4; q++) r[q >> 1][q & 1] = fmaxf(r[q >> 1][q & 1], __shfl_xor_sync(0xffffffffu, r[q >> 1][q & 1], d));
#pragma unroll
        for (int u = 0; u < 2; u++) {
#pragma unroll
          for (int q = 0; q < 4; q++) e[u][q] = ex2(e[u][q] - r[u][q >> 1]);
          r[u][0] = e[u][0] + e[u][1]; r[u][1] = e[u][2] + e[u][3];
        }
#pragma unroll
        for (int d = 1; d <= 2; d++)
#pragma unroll
          for (int q = 0; q < 4; q++) r[q >> 1][q & 1] += __shfl_xor_sync(0xffffffffu, r[q >> 1][q & 1], d);
#pragma unroll
        for (int u = 0; u < 2; u++) {
          const float rx = rcp(r[u][0]), ry = rcp(r[u][1]);
          px[u] = pack2(e[u][0] * rx, e[u][1] * rx); py[u] = pack2(e[u][2] * ry, e[u][3] * ry);
        }
        uint32_t o[8][2];
        uint4 ro[4];
#pragma unroll
        for (int q = 0; q < 8; q++) {
          float d[4] = {0.f, 0.f, 0.f, 0.f};
          const int t = 16 + 8 * hp + q, u = q >> 2;
          mma16816(d, px[u] & mhi, 0u, px[u] & ~mhi, py[u] & mhi, PH[t], P0[t]);
          mma1688(d, 0u, py[u] & ~mhi, P1[t]);
          o[q][0] = pack2(d[0], d[1]); o[q][1] = pack2(d[2], d[3]);
        }
#pragma unroll
        for (int q = 0; q < 4; q++) ro[q] = make_uint4(o[4 * (q & 1)][q >> 1], o[4 * (q & 1) + 1][q >> 1], o[4 * (q & 1) + 2][q >> 1], o[4 * (q & 1) + 3][q >> 1]);
        img_store(ro, x.img(0, hp));
        publish(hp, x);
        uint32_t xr[16];
        if (L) img_load(xr, tile, x);
        else {
#pragma unroll
          for (int q = 0; q < 4; q++) {
            uint32_t v[4];
            ldsm4(x.maddr(tile, 2 * q), v);
            xr[2 * q] = v[0]; xr[8 + 2 * q] = v[1]; xr[2 * q + 1] = v[2]; xr[9 + 2 * q] = v[3];
          }
          __syncwarp();
        }
        img_sts(ro, tile, x);
        img_unpack(acc + 32 * hp, xr);
      }
    } else {
      float kv[128];
      float (&kv0)[64] = reinterpret_cast<float (&)[64]>(kv[0]);
      float (&kv1)[64] = reinterpret_cast<float (&)[64]>(kv[64]);
      auto mma8 = [&](uint32_t as, uint32_t bs, int i, bool fence) {
        const uint32_t da = desc_lo(SB + OFF_A, 16) + as * (SLOT / 16), db = desc_lo(SB + OFF_B, 8192) + bs * (SLOT / 16);
        if (fence) wgmma_fence();
#pragma unroll
        for (int k = 0; k < 4; k++) {
          wgmma_ss_n128(kv0, da + (k >> 1) * 32 + (k & 1) * 2, HA64, db + 128 * k, i + k);
          wgmma_ss_n128(kv1, da + 512 + (k >> 1) * 32 + (k & 1) * 2, HA64, db + 128 * k, i + k);
        }
        wgmma_commit();
      };
      constexpr uint32_t dm = desc_lo(SB + OFF_MB, 0);
      auto relB = [&](uint32_t s) { mbar_arrive_n(sb + BAR_EMPTYB + s * 8, 2); };
      auto skip = [&]() {
#pragma unroll
        for (int q = 0; q < 6 - NJ; q++) adv<NA>(x.ra);
        x.rb.s = w ? (2 + NJ) % 6 : 4;
        if (!w && NJ < 4) x.rb.ph ^= 1;
      };
      static_assert(NA == 5 && NB == 6, "ring arithmetic");
      mma8(x.ra.s, x.rb.s + w, 0, true);
      gemm_next<256>(x);
#pragma unroll 1
      for (int i = 1; i < NJ; i++) {
        mbar_wait2(x.fullA(x.ra.s), x.ra.ph, x.fullB(x.rb.s + w), x.rb.ph);
        mma8(x.ra.s, x.rb.s + w, 1, true);
        if (!XO && i == XR) { img_store(r1, x.img(XBUF(L), 1)); publish(3, x); }
        if (!XO && i == XS) stats_send(ts, L, x);
        wgmma_wait<1>();
        if (x.elected) { x.releaseA(x.pa); relB(x.pb + w); }
        gemm_next<256>(x);
        if (XO && i == XR) { img_store(r1, x.img(XBUF(L), 1)); publish(3, x); stats_send(ts, L, x); }
      }
      if (w) {
        wgmma_wait<0>();
        if (x.elected) { x.releaseA(x.pa); relB(x.pb + 1); }
        skip();
        asm volatile("bar.sync 7, 256;" ::: "memory");
      }
      TSL_(8);
      {
        const int t = lane_id() + 32 * x.warp;
        uint32_t mask = t < 2 ? ((w ? (t ? 0xFF3Fu : 0x3FFFu) : 0xFFFFu) >> (NJ - 1)) & (w ? ~1u : ~0u) : 0u, cnt = 1 + t;
        bool ready = false;
#pragma unroll 1
        for (int i = NJ; i < 16; i++) {
          if (!ready) mbar_wait2(x.fullA(x.ra.s), x.ra.ph, x.fullB(x.rb.s), x.rb.ph);
          mma8(x.ra.s, x.rb.s, 1, true);
          const uint32_t bar = sb + (t ? BAR_EMPTYB + x.pb * 8 : BAR_EMPTYA + x.pa * 8);
          gemm_next<128>(x);
          if (w && (i | 4) == 15) x.rb.s = 4;
          ready = mbar_probe2(x.fullA(x.ra.s), x.ra.ph, x.fullB(x.rb.s), x.rb.ph);
          wgmma_wait<1>();
          if (mask & 1) mbar_arrive_n(bar, cnt);
          mask >>= 1; cnt = 2;
          if (i == 8 && w) asm volatile("bar.arrive 9, 256;" ::: "memory");
          if (i == 9) TSL_(10);
        }
        mbar_wait2(sb + BAR_STAT, 1, sb + BAR_CS + 8, 0);
        wgmma_fence();
        wgmma_r1_n128(kv0, dm, dcs + 96 + 96 * w, 1);
        wgmma_r1_n128(kv1, dm + 64, dcs + 96 + 96 * w, 1);
        wgmma_commit();
        if (w == 0) asm volatile("bar.arrive 7, 256;" ::: "memory");
        wgmma_wait<1>();
        if (mask & 1) mbar_arrive_n(sb + (t ? BAR_EMPTYB + x.pb * 8 : BAR_EMPTYA + x.pa * 8), 2);
      }
      const Stats s0 = load_stats(0, x), s1 = load_stats(1, x), st = w ? s1 : s0;
      if (w == 0) skip();
      const uint32_t h0 = x.held(0), h1 = x.held(1);
      auto vreg = [&](int ks) { return ks < 6 ? OFF_A + (ks < 3 ? h0 * SLOT : h1 * SLOT - 15360) + ks * 5120 : OFF_S + 2048 + ks * 5120; };
      uint32_t tV[2], uu[4];
#pragma unroll
      for (int hf = 0; hf < 2; hf++) {
        tV[hf] = sb + vreg(4 * hf + x.warp) + ((x.lane >> 3) & 1) * 2560 + (x.lane & 7) * 16 + x.mhi * 128;
        const float i0 = rcp(hf ? s1.rstd0 : s0.rstd0), i1 = rcp(hf ? s1.rstd1 : s0.rstd1);
        const uint32_t h = pack2(i0, i1);
        uu[2 * hf] = pack2(lo16(h), i0 - lo16(h)); uu[2 * hf + 1] = pack2(hi16(h), i1 - hi16(h));
        asm volatile("" : "+r"(tV[hf]), "+r"(uu[2 * hf]), "+r"(uu[2 * hf + 1])::"memory");
      }
      wgmma_wait<0>();
      fence_regs(kv);
      TSL_(2);
      if (w == 0) {
        uint32_t f[2][18], ad[4];
#pragma unroll
        for (int q = 0; q < 18; q++) f[1][q] = 0u;
#pragma unroll
        for (int q = 0; q < 4; q++) ad[q] = x.maddr(sb + OFF_S, 2 * q);
        auto norm = [&](int un) {
          uint32_t* u = f[un & 1];
          const Stats& sn = (un & 2) ? s1 : s0;
#pragma unroll
          for (int sg = 0; sg < 2; sg++) {
            uint32_t v = u[16 + sg];
            v = add2(v, __shfl_xor_sync(0xffffffffu, v, 1)); v = add2(v, __shfl_xor_sync(0xffffffffu, v, 2));
            const float a = rcp(lo16(v)) * sn.rstd0, b = rcp(hi16(v)) * sn.rstd1;
            const uint32_t r0 = pack2(a, a), r1_ = pack2(b, b);
#pragma unroll
            for (int q = 8 * sg; q < 8 * sg + 8; q++) u[q] = mul2(u[q], (q & 1) ? r1_ : r0);
#pragma unroll
            for (int q = 2 * sg; q < 2 * sg + 2; q++) stsm4(ad[q] + (un & 1) * SLOT + (un >> 1) * 8192, u[4 * q], u[4 * q + 1], u[4 * q + 2], u[4 * q + 3]);
          }
        };
        auto unit = [&](int un) { return kv + ((un >> 1) & 1) * 64 + (un & 1) * 16 + (un >> 2) * 32; };
        hedgehog_scale<0>(kv, s0, nullptr);
#pragma unroll 1
        for (int it = 0;; it++) {
#pragma unroll
          for (int un = 0; un < 4; un++) {
            if (un == 1) {
              if (it) asm volatile("bar.sync 9, 256;" ::: "memory");
#pragma unroll
              for (int q = 0; q < 4; q++) ad[q] -= it * (OFF_S - OFF_B - 2 * SLOT);
            }
            norm((un + 3) & 3);
            dual_exp(unit(un), f[un & 1], x.goff);
            hedgehog_scale<KEEP>(unit(un + 1), ((un + 1) & 2) ? s1 : s0, f[(un + 1) & 1]);
          }
          if (it) break;
#pragma unroll
          for (int q = 0; q < 32; q++) {
            asm volatile("mov.b32 %0, %1;" : "=f"(kv[q]) : "f"(kv[q + 32]));
            asm volatile("mov.b32 %0, %1;" : "=f"(kv[q + 64]) : "f"(kv[q + 96]));
            if (q < 16) kv[32 + q] = 0.f;
          }
        }
        norm(3);
        TSL_(3);
      } else {
        wg_bar(w);
#pragma unroll
        for (int hf = 0; hf < 2; hf++) {
          stsm4(tV[hf] + 512 + x.mhi * 512, uu[2 * hf], uu[2 * hf + 1], uu[2 * hf], uu[2 * hf + 1]);
          stsm4(tV[hf] + 1792 + x.mhi * 512, uu[2 * hf], uu[2 * hf + 1], uu[2 * hf], uu[2 * hf + 1]);
#pragma unroll
          for (int q = 0; q < 8; q++) {
            const float* u = kv + 64 * hf + 8 * q;
            stsm4(tV[hf] + (q >> 1) * 640 + (q & 1) * 256, pack2(u[0], u[1]), pack2(u[2], u[3]), pack2(u[4], u[5]), pack2(u[6], u[7]));
          }
        }
        TSL_(3);
      }
      {
        float d[2][20];
        uint4* dst = &g_kvpart[x.j()][w * 4 + x.warp][0][x.m() * 32 + x.lane];
        unsigned* dz = reinterpret_cast<unsigned*>(&g_kvpart[x.j()][w * 4 + x.warp][x.c & 1][512]) + x.m() * 8 + x.g;
        asm volatile("" : "+l"(dst), "+l"(dz)::"memory");
        fence_async_smem();
        cta_bar();
        TSL_(11);
        uint32_t pk[9];
        auto prep = [&](float (&u)[20]) {
          fence_regs(u);
#pragma unroll
          for (int q = 0; q < 8; q++) pk[q] = pack2(u[((q >> 1) & 2) + 4 * (q & 3)], u[((q >> 1) & 2) + 4 * (q & 3) + 1]);
          pk[8] = __float_as_uint((x.c & 1) ? u[18] + u[19] : u[16] + u[17]);
#pragma unroll
          for (int q = 0; q < 9; q += 4) pk[q] = (pk[q] & ~1u) | (L == 1);
        };
        auto send = [&](int hp) {
          st_v4(dst + hp * 16 * 544, pk[0], pk[1], pk[2], pk[3]); st_v4(dst + (hp * 16 + 1) * 544, pk[4], pk[5], pk[6], pk[7]);
          st_flag(dz + hp * 16 * 544 * 4, pk[8]);
        };
        wgmma_fence();
#pragma unroll
        for (int q = 0; q < 17; q++) {
          if (q < 16) wgmma_ss_n40_tt(d[q >> 3], desc_lo(SB + (q < 8 ? OFF_S : OFF_B + 2 * SLOT), 1024) + w * (SLOT / 16) + 128 * (q & 7), desc_lo(SB + vreg(q & 7), 2560) + (w + (q >> 3) * 2) * 40, q & 7);
          else wgmma_r1_n128(acc, dm + w * 64, dcs, 0);
          if (q == 7 || q == KVS || q == 16) wgmma_commit();
          if (q == KVS) { wgmma_wait<1>(); prep(d[0]); send(0); mbar_wait2(x.fullA(x.ra.s), x.ra.ph, x.fullB(x.rb.s), x.rb.ph); wgmma_fence(); }
        }
        gemm_issue<128, false>(acc, x, true); gemm_next<128>(x);
        wgmma_wait<1>();
        x.releaseA(h0); x.releaseA(h1); x.releaseB(2); x.releaseB(3);
        if (x.lane == 0) mbar_arrive(sb + BAR_SIGT);
        prep(d[1]);
        TSL_(4);
#pragma unroll 1
        for (int seg = 0; seg < 2; seg++) {
          const int n0 = w ? PS1 : PS0;
          gemm_run(acc, x, seg ? 15 - n0 : n0, seg, seg ? L : 0);
          if (seg == 0) send(1);
        }
      }
      gemm_end(acc, x);
      TSL_(5);
      {
        float dp[2][20], dn[2][20];
        uint32_t f[4][16];
        auto mma = [&](int h) {
          if (!(h & 1)) mbar_wait(sb + BAR_KV + h * 4, L >> 1);
          if (h == 0) TSL_(9);
          const uint32_t db = desc_lo(SB + OFF_S + h * 5120, 128);
          const uint32_t (&a)[16] = f[h];
          wgmma_fence();
          wgmma_rs_n40(dp[h & 1], a[0], a[1], a[2], a[3], db, 0);
          wgmma_rs_n40(dn[h & 1], a[8], a[9], a[10], a[11], db + 160, 0);
          wgmma_rs_n40(dp[h & 1], a[4], a[5], a[6], a[7], db + 80, 1);
          wgmma_rs_n40(dn[h & 1], a[12], a[13], a[14], a[15], db + 240, 1);
          wgmma_commit();
        };
        uint32_t xr[16];
        auto fin = [&](int h) {
          const uint32_t tile = x.aslot(x.held(h >> 1));
          if (!(h & 1)) img_load(xr, tile, x);
          float (&u)[20] = dp[h & 1];
          float (&v)[20] = dn[h & 1];
          fence_regs(u); fence_regs(v);
#pragma unroll
          for (int r = 0; r < 2; r++) {
            const float sp = u[16 + 2 * r], sn = v[16 + 2 * r];
            const float id = rcp(fmaf(fmaf(sp, L == 1 ? 0.065536f * 128 / 129 : 0.065536f, u[17 + 2 * r]), sn, v[17 + 2 * r] * sp)), aa = sn * id, cc = sp * id;
            uint32_t o[4];
#pragma unroll
            for (int t = 0; t < 4; t++) o[t] = pack2(fmaf(u[4 * t + 2 * r], aa, v[4 * t + 2 * r] * cc), fmaf(u[4 * t + 2 * r + 1], aa, v[4 * t + 2 * r + 1] * cc));
            stg128(x.img(0, h >> 1) + r * 64 + (h & 1) * 32, make_uint4(o[0], o[1], o[2], o[3]));
            sts128(tile + r * 1024 + (h & 1) * 512 + x.oo() * 16, o[0], o[1], o[2], o[3]);
          }
          if (h & 1) { publish(h >> 1, x); img_unpack(acc + 16 * (h - 1), xr); }
        };
        auto scale = [&](int h) { hedgehog_scale<0>(acc + 16 * h, st, nullptr); };
        auto ex = [&](int h) { dual_exp_rcp(acc + 16 * h, f[h]); };
        scale(0);
        ex(0); scale(1); mma(0);
        ex(1); wgmma_wait<0>(); fin(0); bb_fence(x.goff); mma(1);
        wgmma_wait<0>(); fin(1); scale(2);
        ex(2); scale(3); if (UK & 1) bb_keep(acc, x.goff); mma(2);
        ex(3); wgmma_wait<0>(); fin(2); mma(3);
        wgmma_wait<0>(); fin(3);
      }
    }
    if (PW & 2) { mbar_wait(x.fullB(x.rb.s), x.rb.ph); fence_regs(acc); }
    fence_async_smem();
    wg_bar(w);
    TSL_(6);
    rewind2<NA>(x.ra);
    gemm_issue<128, false>(acc, x, PW & 2); gemm_next<128>(x);
#pragma unroll 1
    for (int seg = L >= TSL ? 0 : 1; seg < 2; seg++) {
      gemm_run(acc, x, L >= TSL ? (seg ? TSK : 15 - TSK) : 15, seg, 10 + L);
      if (L >= TSL) {
        if (seg == 0 && w == 1) asm volatile("bar.sync 6, 256;" ::: "memory");
        if (seg == 1 && w == 0) asm volatile("bar.arrive 6, 256;" ::: "memory");
      }
    }
    gemm_end(acc, x);
    TSL_(7);
    rewind2<NA>(x.ra);
    out_epilogue(acc, r1, ts, P.out + goff, L, x);
    TSL_(13);
  }
}

typedef unsigned long long u64;
template <class T> __device__ __forceinline__ T* early(T* p) { return (T*)__shfl_xor_sync(0xffffffffu, (u64)p, 1); }
__device__ __forceinline__ void pause(uint32_t GAP) {
  if (GAP) { uint32_t t0, t; asm volatile("mov.u32 %0, %%clock;" : "=r"(t0)); do { asm volatile("mov.u32 %0, %%clock;" : "=r"(t)); } while (t - t0 < GAP); }
}
__device__ __forceinline__ u64 order_table(int kind, int j) {
  const int i = threadIdx.x & 15;
  const unsigned v = (unsigned)(kind == 2 ? q_order(i, j) : kv_order(i, j, kind)) << (4 * (i & 7));
  return (u64)__reduce_or_sync(0xffffffffu, i < 8 ? 0u : v) << 32 | __reduce_or_sync(0xffffffffu, i < 8 ? v : 0u);
}

__device__ __forceinline__ void b_producer(const Params& P, uint32_t sb, unsigned vb) {
  const int j = cta_j(vb);
  const u64 t0 = order_table(0, j), t1 = order_table(1, j), t2 = order_table(2, j);
  Ring r = {PRE_B % NB, PRE_B < NB};
#pragma unroll 1
  for (int sg = 0; sg < 20; sg++) {
    const int L = sg / 5, p = sg - 5 * L, wt = L & 1;
    int n = p >= 3 ? 16 : (wt ? (p ? 16 - NJ : 2 * NJ) : (p ? 0 : (L ? 32 : 32 - PRE_B)));
    u64 tab = p == 3 ? t2 : (sg == 0 ? t0 >> (2 * PRE_B) : (p == 1 || p == 2 ? t1 >> (4 * NJ) : t1));
    const CUtensorMap* tm = p == 4 ? &P.mwo[wt] : &P.mw[wt ? 1 : L];
    const uint4* img = &g_wf[p != 3][j][0][0];
    int col = (p >= 3 ? 0 : (p == 2 ? 2048 : 1024)) + 128 * j;
    const int flip = p == 0 ? 3072 : 0;
    const bool fold = wt && p != 4;
    if (sg == 5 || sg == 8) { mbar_wait(sb + (sg == 5 ? BAR_WPHI : BAR_CS + 8), sg == 5); fence_async_global(); }
    if (DEFER && p == 4 && ((DEFL >> wt) & 1)) {
      Ring q = r;
      for (int u = 0; u < DEFER; u++) adv<NB>(q);
      mbar_wait(sb + BAR_EMPTYB + q.s * 8, q.ph);
    }
#pragma unroll 1
    for (; n > 0; n--) {
      const int kb = (int)tab & 15;
      mbar_wait(sb + BAR_EMPTYB + r.s * 8, r.ph);
      if (elect()) {
        mbar_expect_tx(sb + BAR_FULLB + r.s * 8, SLOT);
        if (fold && col < 2048) bulk_load(sb + OFF_B + r.s * SLOT, img + kb * 1024, SLOT, sb + BAR_FULLB + r.s * 8);
        else tma_load_w(sb + OFF_B + r.s * SLOT, tm, sb + BAR_FULLB + r.s * 8, col, kb);
      }
      adv<NB>(r);
      if (p == 2 && (n | 4) == 5) r.s = 4;
      col ^= flip;
      if (!(col & flip & 2048)) tab >>= 4;
    }
  }
}

__device__ __forceinline__ void a_loader(const Params& P, uint32_t sb, unsigned vb) {
  const int j = cta_j(vb), m = cta_m(vb);
  const u64 t1 = order_table(1, j), t2 = order_table(2, j);
  Ring r = {PRE_A % NA, PRE_A < NA};
  {
    u64 tab = order_table(0, j) >> (4 * PRE_A);
#pragma unroll 1
    for (int i = PRE_A; i < 33; i++) {
      if (i == 17) tab = t2;
      mbar_wait(sb + BAR_EMPTYA + r.s * 8, r.ph);
      if (elect()) {
        mbar_expect_tx(sb + BAR_FULLA + r.s * 8, SLOT);
        if (i != 14) tma_load_3d(sb + OFF_A + r.s * SLOT, &P.mx, sb + BAR_FULLA + r.s * 8, ((int)tab & 15) * 64, m * 64, 0);
        else {
          tma_load_w(sb + OFF_A + r.s * SLOT, &P.mw[1], sb + BAR_FULLA + r.s * 8, 1024 + 128 * j, m);
          mbar_expect_tx(sb + BAR_WPHI, 8192); tma_load_2d(sb + OFF_S + 4096, &P.mwphi, sb + BAR_WPHI, 0, 128 * j);
        }
        if (i == PF1 || i == PF2) tma_prefetch_w(&P.mwo[i == PF2], 128 * j, m);
      }
      adv<NA>(r);
      if (i != 14) tab >>= 4;
    }
  }
  const unsigned tag = get_tag(sb);
  unsigned seen = 0, kph = 0;
#pragma unroll 1
  for (int sg = 0; sg < 27; sg++) {
    const int L = sg >> 3, p = sg & 7, q = p >= 3 ? p - 3 : p;
    if (p == 0 && (L & 1)) {
#pragma unroll 1
      for (int h = 0; h < 2; h++) {
        poll_flags(&g_kvfflag[L >> 1][j][h][0], 16, 0xFFFFu, tag);
        TS(4, h ? 14 + L : 26 + L);
        for (int it = 0;; it++) {
          if (elect()) { mbar_expect_tx(sb + BAR_STAT + 8, 10240); bulk_load(sb + OFF_S + h * 10240, &g_kvfin[j][8 * h][0], 10240, sb + BAR_STAT + 8); }
          mbar_wait(sb + BAR_STAT + 8, kph);
          kph ^= 1;
          uint32_t a = 1u, o = 0u;
#pragma unroll
          for (int u = 0; u < 20; u++) { const uint32_t v = __float_as_uint(lds32f(sb + OFF_S + h * 10240 + u * 512 + (threadIdx.x & 31) * 16)); a &= v; o |= v; }
          if (__all_sync(0xffffffffu, (L == 1 ? a : ~o) & 1u)) break;
          fence_async_smem();
          if (it > (1 << 16)) __trap();
        }
        if (elect()) mbar_arrive(sb + BAR_KV + h * 8);
        TS(4, h ? 30 + L : (L == 1 ? 20 : 25));
      }
    }
    int n = q == 0 ? 4 : (q == 1 ? 3 : (q == 2 ? 7 : (q == 3 ? ((L & 1) ? 0 : 16 - NJ) : 16)));
    u64 tab = q == 4 ? t2 : t1 >> (q == 0 ? 8 : (q == 1 ? 24 : (q == 2 ? 36 : 4 * NJ)));
    const uint4* img = &g_img[p >= 3 ? XBUF(L + 1) : 0][m][0][0];
    const uint32_t gap = p == 0 ? G0 : (p == 3 ? G3 : (q < 3 ? G1 : G4));
    bool poll = q == 0 || q == 2 || (q == 1 && seen != 0xFFFFFFFFu);
#pragma unroll 1
    for (; n > 0; n--) {
      const uint4* src = img + ((int)tab & 15) * 1024;
      src = early(src);
      mbar_wait(sb + BAR_EMPTYA + r.s * 8, r.ph);
      if (elect()) mbar_expect_tx(sb + BAR_FULLA + r.s * 8, SLOT);
      if (poll) {
        const int lane = threadIdx.x & 31, nn = p >= 3 ? PNX : PNO;
        const unsigned* f = (p >= 3 ? &g_xflag[L + 1][0][m][0] : &g_oflag[L][0][m][0]) + (q == 2 ? 512 : 0) + (lane & 7);
        if (q == 0 || (PN2 && q == 2)) f += (((lane >> 3) & (nn - 1)) - (m & (nn - 1))) * 32;
        const unsigned need = q == 0 ? 0x0F0F0F0Fu << (~j & 4) : 0xFFFFFFFFu;
        if (q == 0) mbar_wait(sb + BAR_SIGP + (p ? 16 : 0), L & 1);
        int it = 0;
        do { seen = __ballot_sync(0xffffffffu, ld_flag(f) == tag); if (++it > (1 << 22)) __trap(); } while ((seen & need) != need);
        if (q == 0) TS(2, p == 0 ? 5 + L * 8 : 9 + L * 8);
        poll = false;
      }
      if (elect()) bulk_load(sb + OFF_A + r.s * SLOT, src, SLOT, sb + BAR_FULLA + r.s * 8);
      adv<NA>(r);
      tab >>= 4;
      pause(gap);
    }
  }
}

__device__ __forceinline__ uint2 sum_packets(float (&a)[8], uint32_t addr, int n) {
  uint2 ok = make_uint2(~0u, 0u);
#pragma unroll 1
  for (int b = 0; b < n; b += KB) {
    uint4 v[KB];
#pragma unroll
    for (int u = 0; u < KB; u++) lds128(addr + (b + u) * 512, v[u].x, v[u].y, v[u].z, v[u].w);
#pragma unroll
    for (int u = 0; u < KB; u++) {
      ok.x &= v[u].x; ok.y |= v[u].x;
      a[0] += lo16(v[u].x); a[1] += hi16(v[u].x); a[2] += lo16(v[u].y); a[3] += hi16(v[u].y);
      a[4] += lo16(v[u].z); a[5] += hi16(v[u].z); a[6] += lo16(v[u].w); a[7] += hi16(v[u].w);
    }
  }
  return ok;
}
__device__ __forceinline__ void helper_bar() { asm volatile("bar.sync 4, 64;" ::: "memory"); }
__device__ __forceinline__ void helper(const Params& P, uint32_t sb, int w, unsigned vb) {
  const int j = cta_j(vb), m = cta_m(vb);
  if (w == 0) {
    if (elect()) {
      const unsigned t = atomicAdd(&g_ctr, 1u) / NCTA + 1u;
      asm volatile("st.shared.u32 [%0], %1;" ::"r"(sb + OFF_EPOCH), "r"(t) : "memory");
      mbar_arrive(sb + BAR_EPOCH);
    }
  }
  const unsigned tag = get_tag(sb);
  mbar_wait(sb + BAR_FULLB + 24, 0);
  const uint32_t stg = sb + OFF_T + w * 12288, stb = sb + BAR_STG + w * 24;
  Ring rs = {0, 0};
  auto cs_image = [&](int L) {
      const int lane = lane_id();
      poll_flags(&g_csflag[L][j][0], 16, L ? CSNEED : 0xFFFu, tag);
#pragma unroll
      for (int p = 0; p < 3; p++) {
        const uint4 u = ldcg4(&g_cs[L][0][p * 1024 + 128 * j + lane * 4]), v = ldcg4(&g_cs[L][1][p * 1024 + 128 * j + lane * 4]);
        const float c0 = __uint_as_float(u.x) + __uint_as_float(v.x), c1 = __uint_as_float(u.y) + __uint_as_float(v.y);
        const float c2 = __uint_as_float(u.z) + __uint_as_float(v.z), c3 = __uint_as_float(u.w) + __uint_as_float(v.w);
        const uint32_t h0 = pack2(c0, c1), h1 = pack2(c2, c3), dst = sb + OFF_CS + (p * 16 + (lane >> 1)) * 96 + L * 48 + (lane & 1) * 8;
        sts64(dst, h0, h1); sts64(dst + 16, pack2(c0 - lo16(h0), c1 - hi16(h0)), pack2(c2 - lo16(h1), c3 - hi16(h1))); sts64(dst + 32, h0, h1);
        if (L == 0) { sts64(dst + 48, 0u, 0u); sts64(dst + 64, 0u, 0u); sts64(dst + 80, 0u, 0u); }
      }
      if (L == 0 && lane < 4) sts64(sb + OFF_CS + 4608 + lane * 8, 0u, 0u);
      fence_async_smem();
      __syncwarp();
      if (elect()) mbar_arrive(sb + BAR_CS + L * 8);
      TS(4, 2 + L * 2);
  };
#pragma unroll 1
  for (int L = 0; L < 4; L++) {
    const int lane = lane_id();
    if (L == 0) {
      {
        const int wt = m >= 12, col = ((0x2021 >> (m & 12)) & 3) * 1024 + 128 * j + (m & 3) * 32;
        const CUtensorMap* tm = &P.mcs[wt];
        __nanosleep(wt ? D2 : CD);
        constexpr int nb = 8;
        float a[8] = {0.f, 0.f, 0.f, 0.f, 0.f, 0.f, 0.f, 0.f};
#pragma unroll 1
        for (int b = -3; b < nb; b++) {
          if (b >= 0) {
            mbar_wait(stb + rs.s * 8, rs.ph);
            sum_packets(a, stg + rs.s * 4096 + lane * 16, 8);
            fence_async_smem();
            __syncwarp();
          }
          const uint32_t sl = b < 0 ? (rs.s + b + 3) % 3 : rs.s;
          if (b + 3 < nb && elect()) { mbar_expect_tx(stb + sl * 8, 4096); tma_load_2d(stg + sl * 4096, tm, stb + sl * 8, col, (w * (16 - nb) + b + 3) * 64); }
          if (b >= 0) adv<3>(rs); else pause(CP);
        }
#pragma unroll
        for (int u = 0; u < 8; u++) {
          a[u] += __shfl_xor_sync(0xffffffffu, a[u], 4); a[u] += __shfl_xor_sync(0xffffffffu, a[u], 8); a[u] += __shfl_xor_sync(0xffffffffu, a[u], 16);
        }
        if (lane < 4) {
          float4* dst = reinterpret_cast<float4*>(&g_cs[wt][w][col + lane * 8]);
          dst[0] = make_float4(a[0], a[1], a[2], a[3]); dst[1] = make_float4(a[4], a[5], a[6], a[7]);
        }
        helper_bar();
        if (w == 0 && elect()) { fence_gpu(); st_flag(&g_csflag[wt][j][m], tag); }
      }
      if (w == 0) TS(4, 1 + L * 2);
    }
    if (w == 1) {
      if (L > 0) { mbar_wait(sb + BAR_SIGP + 24, (L - 1) & 1); __nanosleep(SD); }
      else if (S0) { mbar_wait(sb + BAR_WPHI, 0); __nanosleep(S0); }
#pragma unroll 1
      for (int p = 0; p < 2; p++) {
        uint4 v[8];
        for (int it = 0;; it++) {
          bool ok = true;
#pragma unroll
          for (int t = 0; t < 8; t++) v[t] = ld_pkt(&g_stats[m][p][t][lane]);
#pragma unroll
          for (int t = 0; t < 8; t++) ok = ok && (v[t].w & 15u) == seq4(tag, L);
          if (__all_sync(0xffffffffu, ok)) break;
          __nanosleep(200);
          if (it > (1 << 20)) __trap();
        }
        float s0 = 0.f, q0 = 0.f, s1 = 0.f, q1 = 0.f;
#pragma unroll
        for (int t = 0; t < 8; t++) { s0 += __uint_as_float(v[t].x); q0 += __uint_as_float(v[t].y); s1 += __uint_as_float(v[t].z); q1 += __uint_as_float(v[t].w & ~15u); }
        s0 *= (1.f / 1024); s1 *= (1.f / 1024);
        sts64(sb + OFF_MR + p * 256 + lane * 8, __float_as_uint(rsqrtf(fmaxf(q0 * (1.f / 1024) - s0 * s0, 0.f) + 1e-5f)),
              __float_as_uint(rsqrtf(fmaxf(q1 * (1.f / 1024) - s1 * s1, 0.f) + 1e-5f)));
#pragma unroll
        for (int r = 0; r < 2; r++) {
          const float v = -0.5f * (r ? s1 : s0);
          const uint32_t hh = pack2(v, v), hl = pack2(v, v - lo16(hh));
          const bool b = L & 1;
          sts128(sb + (b ? OFF_MB : OFF_MA) + p * 1024 + (lane >> 3) * 256 + r * 128 + (lane & 7) * 16, b ? 0u : hh, b ? hh << 16 : hl >> 16, b ? hl : 0u, 0u);
        }
      }
      fence_async_smem();
      __syncwarp();
      if (elect()) {
        mbar_arrive(sb + BAR_STAT);
      }
      TS(2, 0 + L * 8);
    }
    if (L == w) cs_image(L);
    if (L & 1) {
      const uint32_t flip = L == 1 ? 0u : 1u;
      mbar_wait(sb + BAR_SIGT, 1);
      {
        int it = 0;
        if (PSL) __nanosleep(m < 8 ? PSL : PSL + 600);
        while (!__all_sync(0xffffffffu, (ld_flag(reinterpret_cast<const unsigned*>(&g_kvpart[j][m][w][512]) + (lane & 15) * 8) ^ flip) & 1u)) { if (PSL) __nanosleep(100); if (++it > (1 << 22)) __trap(); }
        fence_async_global();
      }
      if (w == 0) TS(4, 6 + L * 2);
      float a[8], z;
      for (int it = 0;; it++) {
        if (elect()) { mbar_expect_tx(stb + rs.s * 8, 8704); bulk_load(stg, &g_kvpart[j][m][w][0], 8704, stb + rs.s * 8); }
        mbar_wait(stb + rs.s * 8, rs.ph);
        if (w == 0) TS(4, 21 + L);
        adv<3>(rs);
#pragma unroll
        for (int u = 0; u < 8; u++) a[u] = 0.f;
        z = 0.f;
        uint32_t ok = 1u;
#pragma unroll
        for (int u = 0; u < 4; u++) { const float v = lds32f(stg + 8192 + u * 128 + (lane & 3) * 32 + (lane >> 2) * 4); z += v; ok &= __float_as_uint(v) ^ flip; }
        const uint2 tg = sum_packets(a, stg + lane * 16, 16);
        ok &= flip ? ~tg.y : tg.x;
        if (__all_sync(0xffffffffu, ok & 1u)) break;
        fence_async_smem();
        if (it > (1 << 16)) __trap();
      }
      {
        uint4* img = &g_kvfin[j][m][w * 8 + (lane >> 2)];
        uint32_t a0 = __float_as_uint(a[0]) >> 16;
        a0 += ~(a0 ^ flip) & 1u;
        st_v4(img + (lane & 3) * 16, __byte_perm(a0, pack2(0.f, a[1]), 0x7610), pack2(a[2], a[3]), pack2(a[4], a[5]), pack2(a[6], a[7]));
        const uint32_t cz = pack2(0.f, qsum(z)) | (0x3781u ^ flip);
        if (!(lane & 3)) st_v4(img + 64, cz, cz, cz, cz);
        __syncwarp();
        if (elect()) st_flag(&g_kvfflag[L >> 1][j][m >> 3][(m & 7) * 2 + w], tag);
      }
      if (w == 0) TS(4, 7 + L * 2);
    } else {
      mbar_wait(sb + BAR_SIGT, 0);
      if (w == 0) {
        if (elect()) { fence_gpu(); st_flag(&g_hflag[L >> 1][m][j][0], tag); st_flag(&g_kflag[j][m], tag); }
        if (L == 0) {
          __nanosleep(KSL);
          poll_flags(&g_kflag[j][0], 16, 0xFFFFu, tag);
          if (elect()) mbar_arrive(sb + BAR_WPHI);
        }
      } else if (m > 0) {
        poll_flags(&g_hflag[L >> 1][m - 1][j][0], 1, 1u, tag);
        if (elect()) { mbar_expect_tx(sb + BAR_HALO, 8192); bulk_load(sb + OFF_S + 8192, &g_halo[m - 1][j][0][0], 8192, sb + BAR_HALO); }
        TS(2, 2 + L * 8);
      }
    }
#pragma unroll 1
    for (int e = 0; e < (L < 3 && w == 0 ? 3 : 1); e++) {
      unsigned* flag = e == 0 ? &g_oflag[L][w][m][j] : &g_xflag[L + 1][e - 1][m][j];
      flag = early(flag);
      mbar_wait(sb + BAR_SIGP + (e == 0 ? w : e + 1) * 8, L & 1);
      TS(e == 2 ? 3 : 2 + w, (e ? 6 : 3) + L * 8);
      if (elect()) { fence_async_global(); fence_gpu(); st_flag(flag, tag); }
      TS(e == 2 ? 3 : 2 + w, (e ? 7 : 4) + L * 8);
    }
  }
}

__device__ __forceinline__ void spare(const Params& P, uint32_t sb, int id) {
  const int tid = threadIdx.x & 127, w = __shfl_sync(0xffffffffu, threadIdx.x >> 7, 0), lane = tid & 31, j = 2 * id + w;
  const uint32_t ring = w * 6 * SLOT, wp = 12 * SLOT + w * 8192, bar = sb + 13 * SLOT + w * 64;
  auto part = [&](int t) { return (t >> 4) ^ w; };
  auto load = [&](int t, uint32_t sl) {
    mbar_expect_tx(bar + sl * 8, t == 0 ? SLOT + 8192 : SLOT);
    tma_load_w(sb + ring + sl * SLOT, &P.mw[1], bar + sl * 8, part(t) * 1024 + 128 * j, t & 15);
  };
  if (tid == 0) {
    if (w == 2) sts32(sb + OFF_EPOCH, atomicAdd(&g_ctr, 1u) / NCTA + 1u);
    else {
      __nanosleep(D3);
#pragma unroll 1
      for (int t = 0; t < 5; t++) {
        mbar_init(bar + t * 8, 1);
        asm volatile("fence.mbarrier_init.release.cluster;" ::: "memory");
        load(t, t);
      }
      tma_load_2d(sb + wp, &P.mwphi, bar, 0, 128 * j);
    }
  }
  __syncthreads();
  const unsigned tag = get_tag<false>(sb);
  if (w == 2) {
    int it = 0;
    while ((int)(ld_flag(&g_ctr) - tag * NCTA) < 0) { if (++it > (1 << 22)) __trap(); }
    return;
  }
  Ring r = {4, 1};
  float d[64] = {}, cs[32] = {};
  auto fold = [&]() {
    mbar_wait(bar + r.s * 8, r.ph);
    wgmma_fence();
#pragma unroll
    for (int q = 0; q < 8; q++)
      wgmma_ss_n32(reinterpret_cast<float (&)[16]>(d[16 * (q >> 1)]), desc_lo(SB + ring + r.s * SLOT, 16) + (q >> 2) * 512 + (q & 3) * 2, desc_lo(SB + wp, 512) + q * 64, q & 1);
    wgmma_commit();
  };
  const int row = (tid >> 5) * 16 + (lane >> 2);
#pragma unroll 1
  for (int t = -1; t < 32; t++) {
    uint32_t f[32];
#pragma unroll
    for (int i = 0; i < 32; i++) { f[i] = pack2(d[2 * i], d[2 * i + 1]); cs[i & 30] += d[2 * i]; cs[i | 1] += d[2 * i + 1]; }
    wg_bar(w);
    if (tid == 0 && t >= 0 && t < 27) load(t + 5, r.s);
    __syncwarp();
    if (t < 31) adv<5>(r);
    fold();
    if (part(t) == 0 && t >= 0) {
#pragma unroll
      for (int q = 0; q < 8; q++)
        g_wf[0][j][t & 15][(q >> 2) * 512 + (row + 8 * (q & 1)) * 8 + (((q & 2) * 2 + (lane & 3)) ^ (lane >> 2))] =
            make_uint4(f[4 * (q & 6) + (q & 1)], f[4 * (q & 6) + (q & 1) + 2], f[4 * (q & 6) + (q & 1) + 4], f[4 * (q & 6) + (q & 1) + 6]);
    }
    wgmma_wait<0>();
    fence_regs(d);
    if ((t & 15) == 15) {
      if (t >= 0) {
        const uint32_t red = sb + ring + 5 * SLOT;
#pragma unroll
        for (int i = 0; i < 8; i++) sts128(red + (tid >> 2) * 512 + (i >> 1) * 128 + (lane & 3) * 32 + (i & 1) * 16, __float_as_uint(cs[4 * i]), __float_as_uint(cs[4 * i + 1]), __float_as_uint(cs[4 * i + 2]), __float_as_uint(cs[4 * i + 3]));
        wg_bar(w);
        float a = 0.f;
#pragma unroll 4
        for (int i = 0; i < 32; i++) a += lds32f(red + i * 512 + tid * 4);
        g_cs[1][0][part(t) * 1024 + j * 128 + tid] = a;
        wg_bar(w);
        if (tid == 0) {
          fence_gpu();
          st_flag(&g_csflag[1][j][part(t)], tag);
        }
        __syncwarp();
      }
#pragma unroll
      for (int i = 0; i < 32; i++) cs[i] = 0.f;
    }
  }
}

__global__ void __launch_bounds__(NTHREADS, 1) fused_kernel(const __grid_constant__ Params P) {
  extern __shared__ __align__(1024) uint8_t smem_raw[];
  constexpr uint32_t sb = SB;
  const int tid = threadIdx.x;
  const unsigned vb = vblock();
  if (vb >= 128) { spare(P, sb, vb - 128); return; }
  const int warp = __shfl_sync(0xffffffffu, tid >> 5, 0);
  if (elect()) {
    if (warp == 11) { prefetch_map(&P.mx); prefetch_map(&P.mw[0]); if (smem_u32(smem_raw) != SB) __trap(); }
    if (warp < 7) {
#pragma unroll
      for (int i = 0; i < 8; i++) mbar_init(sb + OFF_BAR + (warp * 8 + i) * 8, warp == 2 || warp == 3 ? 2 : (warp == 4 ? 8 : 1));
    }
    asm volatile("fence.mbarrier_init.release.cluster;" ::: "memory");
    if (warp < 2) {
      const int j = cta_j(vb);
#pragma unroll 1
      for (int i = 0; i < (warp == 0 ? PRE_B : PRE_A); i++) {
        const uint32_t bar = sb + BAR_FULLB + warp * 64 + i * 8;
        mbar_expect_tx(bar, SLOT);
        if (warp == 0) tma_load_w(sb + OFF_B + i * SLOT, &P.mw[0], bar, 1024 + (i & 1) * 1024 + 128 * j, kv_order(i >> 1, j, 0));
        else tma_load_3d(sb + OFF_A + i * SLOT, &P.mx, bar, kv_order(i, j, 0) * 64, cta_m(vb) * 64, 0);
      }
    }
  }
  if (tid == 0) TS(6, 0);
  __syncthreads();
  if (tid == 0) TS(6, 2);
  if (warp < 4) {
    reg_dealloc<PREGS>();
    if (warp == 0) b_producer(P, sb, vb);
    else if (warp == 1) a_loader(P, sb, vb);
    else helper(P, sb, warp - 2, vb);
  } else {
    reg_alloc<CREGS>();
    consumer(P, sb, (warp >> 2) - 1, vb);
  }
}

typedef CUresult (*EncodeFn)(CUtensorMap*, CUtensorMapDataType, cuuint32_t, void*, const cuuint64_t*, const cuuint64_t*,
                             const cuuint32_t*, const cuuint32_t*, CUtensorMapInterleave, CUtensorMapSwizzle,
                             CUtensorMapL2promotion, CUtensorMapFloatOOBfill);

void encode(EncodeFn fn, CUtensorMap* m, const void* ptr, int rank, const cuuint64_t* dims, const cuuint64_t* strides,
            const cuuint32_t* box, CUtensorMapSwizzle swz) {
  const cuuint32_t es[5] = {1, 1, 1, 1, 1};
  fn(m, CU_TENSOR_MAP_DATA_TYPE_BFLOAT16, rank, const_cast<void*>(ptr), dims, strides, box, es, CU_TENSOR_MAP_INTERLEAVE_NONE,
     swz, CU_TENSOR_MAP_L2_PROMOTION_L2_256B, CU_TENSOR_MAP_FLOAT_OOB_FILL_NONE);
}
void encode_w(EncodeFn fn, CUtensorMap* m, const void* ptr, int ncols, bool perm) {
  const cuuint64_t p = (cuuint64_t)ncols * 2, d[5] = {(cuuint64_t)ncols, 2, 4, 4, 32}, s[4] = {p, (perm ? 8 : 2) * p, (perm ? 2 : 8) * p, 32 * p};
  const cuuint32_t box[5] = {64, 2, 4, 4, 2};
  encode(fn, m, ptr, 5, d, s, box, CU_TENSOR_MAP_SWIZZLE_128B);
}

void encode_cs(EncodeFn fn, CUtensorMap* m, const void* ptr, int ncols) {
  const cuuint64_t d[2] = {(cuuint64_t)ncols, 1024}, s[1] = {(cuuint64_t)ncols * 2};
  const cuuint32_t box[2] = {32, 64};
  encode(fn, m, ptr, 2, d, s, box, CU_TENSOR_MAP_SWIZZLE_NONE);
}

}

extern "C" void kernel_launch(void* const* d_in, const int* in_sizes, int n_in, void* d_out, int out_size) {
  (void)in_sizes; (void)n_in; (void)out_size;
  void* fnp = nullptr;
  cudaDriverEntryPointQueryResult q;
  cudaGetDriverEntryPoint("cuTensorMapEncodeTiled", &fnp, cudaEnableDefault, &q);
  EncodeFn fn = (EncodeFn)fnp;
  Params P;
  {
    const cuuint64_t dims[3] = {1024, 1024, 2}, strides[2] = {4096, 2048};
    const cuuint32_t box[3] = {64, 64, 2};
    encode(fn, &P.mx, d_in[0], 3, dims, strides, box, CU_TENSOR_MAP_SWIZZLE_128B);
  }
  P.out = (uint4*)d_out;
  encode_w(fn, &P.mw[0], d_in[1], 3072, false);
  encode_w(fn, &P.mw[1], d_in[4], 3072, true);
  encode_w(fn, &P.mw[2], d_in[1], 3072, true);
  encode_w(fn, &P.mwo[0], d_in[2], 1024, true);
  encode_w(fn, &P.mwo[1], d_in[6], 1024, false);
  encode_cs(fn, &P.mcs[0], d_in[1], 3072);
  encode_cs(fn, &P.mcs[1], d_in[4], 3072);
  {
    const cuuint64_t dims[2] = {32, 1024}, strides[1] = {64};
    const cuuint32_t box[2] = {32, 128};
    encode(fn, &P.mwphi, d_in[5], 2, dims, strides, box, CU_TENSOR_MAP_SWIZZLE_64B);
  }
  cudaFuncSetAttribute(fused_kernel, cudaFuncAttributeMaxDynamicSharedMemorySize, SMEM_BYTES);
  fused_kernel<<<NCTA, NTHREADS, SMEM_BYTES, cudaStreamPerThread>>>(P);
}
```

```cpp
#include <cuda_runtime.h>
#include <cuda_bf16.h>
#include <cuda.h>
#include <stdint.h>

namespace {

__device__ __forceinline__ void wgmma_ss_n256(float (&d)[128], uint32_t da, uint32_t ha, uint32_t db, int sd) {
  asm volatile("{\n.reg .pred p;\n.reg .b64 a, b;\nsetp.ne.b32 p, %130, 0;\nmov.b64 a, {%128, %131};\nmov.b64 b, {%129, 0x40000040};\n"
    "wgmma.mma_async.sync.aligned.m64n256k16.f32.bf16.bf16 {%0,%1,%2,%3,%4,%5,%6,%7,%8,%9,%10,%11,%12,%13,%14,%15,%16,%17,%18,%19,%20,%21,%22,%23,%24,%25,%26,%27,%28,%29,%30,%31,%32,%33,%34,%35,%36,%37,%38,%39,%40,%41,%42,%43,%44,%45,%46,%47,%48,%49,%50,%51,%52,%53,%54,%55,%56,%57,%58,%59,%60,%61,%62,%63,%64,%65,%66,%67,%68,%69,%70,%71,%72,%73,%74,%75,%76,%77,%78,%79,%80,%81,%82,%83,%84,%85,%86,%87,%88,%89,%90,%91,%92,%93,%94,%95,%96,%97,%98,%99,%100,%101,%102,%103,%104,%105,%106,%107,%108,%109,%110,%111,%112,%113,%114,%115,%116,%117,%118,%119,%120,%121,%122,%123,%124,%125,%126,%127}, a, b, p, 1, 1, 0, 1;\n}\n"
    : "+f"(d[0]),"+f"(d[1]),"+f"(d[2]),"+f"(d[3]),"+f"(d[4]),"+f"(d[5]),"+f"(d[6]),"+f"(d[7]),"+f"(d[8]),"+f"(d[9]),"+f"(d[10]),"+f"(d[11]),"+f"(d[12]),"+f"(d[13]),"+f"(d[14]),"+f"(d[15]),"+f"(d[16]),"+f"(d[17]),"+f"(d[18]),"+f"(d[19]),"+f"(d[20]),"+f"(d[21]),"+f"(d[22]),"+f"(d[23]),"+f"(d[24]),"+f"(d[25]),"+f"(d[26]),"+f"(d[27]),"+f"(d[28]),"+f"(d[29]),"+f"(d[30]),"+f"(d[31]),"+f"(d[32]),"+f"(d[33]),"+f"(d[34]),"+f"(d[35]),"+f"(d[36]),"+f"(d[37]),"+f"(d[38]),"+f"(d[39]),"+f"(d[40]),"+f"(d[41]),"+f"(d[42]),"+f"(d[43]),"+f"(d[44]),"+f"(d[45]),"+f"(d[46]),"+f"(d[47]),"+f"(d[48]),"+f"(d[49]),"+f"(d[50]),"+f"(d[51]),"+f"(d[52]),"+f"(d[53]),"+f"(d[54]),"+f"(d[55]),"+f"(d[56]),"+f"(d[57]),"+f"(d[58]),"+f"(d[59]),"+f"(d[60]),"+f"(d[61]),"+f"(d[62]),"+f"(d[63]),"+f"(d[64]),"+f"(d[65]),"+f"(d[66]),"+f"(d[67]),"+f"(d[68]),"+f"(d[69]),"+f"(d[70]),"+f"(d[71]),"+f"(d[72]),"+f"(d[73]),"+f"(d[74]),"+f"(d[75]),"+f"(d[76]),"+f"(d[77]),"+f"(d[78]),"+f"(d[79]),"+f"(d[80]),"+f"(d[81]),"+f"(d[82]),"+f"(d[83]),"+f"(d[84]),"+f"(d[85]),"+f"(d[86]),"+f"(d[87]),"+f"(d[88]),"+f"(d[89]),"+f"(d[90]),"+f"(d[91]),"+f"(d[92]),"+f"(d[93]),"+f"(d[94]),"+f"(d[95]),"+f"(d[96]),"+f"(d[97]),"+f"(d[98]),"+f"(d[99]),"+f"(d[100]),"+f"(d[101]),"+f"(d[102]),"+f"(d[103]),"+f"(d[104]),"+f"(d[105]),"+f"(d[106]),"+f"(d[107]),"+f"(d[108]),"+f"(d[109]),"+f"(d[110]),"+f"(d[111]),"+f"(d[112]),"+f"(d[113]),"+f"(d[114]),"+f"(d[115]),"+f"(d[116]),"+f"(d[117]),"+f"(d[118]),"+f"(d[119]),"+f"(d[120]),"+f"(d[121]),"+f"(d[122]),"+f"(d[123]),"+f"(d[124]),"+f"(d[125]),"+f"(d[126]),"+f"(d[127])
    : "r"(da), "r"(db), "r"(sd), "r"(ha));
}
__device__ __forceinline__ void wgmma_ss_n128(float (&d)[64], uint32_t da, uint32_t ha, uint32_t db, int sd) {
  asm volatile("{\n.reg .pred p;\n.reg .b64 a, b;\nsetp.ne.b32 p, %66, 0;\nmov.b64 a, {%64, %67};\nmov.b64 b, {%65, 0x40000040};\n"
    "wgmma.mma_async.sync.aligned.m64n128k16.f32.bf16.bf16 {%0,%1,%2,%3,%4,%5,%6,%7,%8,%9,%10,%11,%12,%13,%14,%15,%16,%17,%18,%19,%20,%21,%22,%23,%24,%25,%26,%27,%28,%29,%30,%31,%32,%33,%34,%35,%36,%37,%38,%39,%40,%41,%42,%43,%44,%45,%46,%47,%48,%49,%50,%51,%52,%53,%54,%55,%56,%57,%58,%59,%60,%61,%62,%63}, a, b, p, 1, 1, 0, 1;\n}\n"
    : "+f"(d[0]),"+f"(d[1]),"+f"(d[2]),"+f"(d[3]),"+f"(d[4]),"+f"(d[5]),"+f"(d[6]),"+f"(d[7]),"+f"(d[8]),"+f"(d[9]),"+f"(d[10]),"+f"(d[11]),"+f"(d[12]),"+f"(d[13]),"+f"(d[14]),"+f"(d[15]),"+f"(d[16]),"+f"(d[17]),"+f"(d[18]),"+f"(d[19]),"+f"(d[20]),"+f"(d[21]),"+f"(d[22]),"+f"(d[23]),"+f"(d[24]),"+f"(d[25]),"+f"(d[26]),"+f"(d[27]),"+f"(d[28]),"+f"(d[29]),"+f"(d[30]),"+f"(d[31]),"+f"(d[32]),"+f"(d[33]),"+f"(d[34]),"+f"(d[35]),"+f"(d[36]),"+f"(d[37]),"+f"(d[38]),"+f"(d[39]),"+f"(d[40]),"+f"(d[41]),"+f"(d[42]),"+f"(d[43]),"+f"(d[44]),"+f"(d[45]),"+f"(d[46]),"+f"(d[47]),"+f"(d[48]),"+f"(d[49]),"+f"(d[50]),"+f"(d[51]),"+f"(d[52]),"+f"(d[53]),"+f"(d[54]),"+f"(d[55]),"+f"(d[56]),"+f"(d[57]),"+f"(d[58]),"+f"(d[59]),"+f"(d[60]),"+f"(d[61]),"+f"(d[62]),"+f"(d[63])
    : "r"(da), "r"(db), "r"(sd), "r"(ha));
}
__device__ __forceinline__ void wgmma_ss_n40_tt(float (&d)[20], uint32_t da, uint32_t db, int sd) {
  asm volatile("{\n.reg .pred p;\n.reg .b64 a, b;\nsetp.ne.b32 p, %22, 0;\nmov.b64 a, {%20, 0x40000040};\nmov.b64 b, {%21, 0x8};\n"
    "wgmma.mma_async.sync.aligned.m64n40k16.f32.bf16.bf16 {%0,%1,%2,%3,%4,%5,%6,%7,%8,%9,%10,%11,%12,%13,%14,%15,%16,%17,%18,%19}, a, b, p, 1, 1, 1, 1;\n}\n"
    : "+f"(d[0]),"+f"(d[1]),"+f"(d[2]),"+f"(d[3]),"+f"(d[4]),"+f"(d[5]),"+f"(d[6]),"+f"(d[7]),"+f"(d[8]),"+f"(d[9]),"+f"(d[10]),"+f"(d[11]),"+f"(d[12]),"+f"(d[13]),"+f"(d[14]),"+f"(d[15]),"+f"(d[16]),"+f"(d[17]),"+f"(d[18]),"+f"(d[19])
    : "r"(da), "r"(db), "r"(sd));
}
__device__ __forceinline__ void wgmma_ss_n32(float (&d)[16], uint32_t da, uint32_t db, int sd) {
  asm volatile("{\n.reg .pred p;\n.reg .b64 a, b;\nsetp.ne.b32 p, %18, 0;\nmov.b64 a, {%16, 0x40000040};\nmov.b64 b, {%17, 0x80000020};\n"
    "wgmma.mma_async.sync.aligned.m64n32k16.f32.bf16.bf16 {%0,%1,%2,%3,%4,%5,%6,%7,%8,%9,%10,%11,%12,%13,%14,%15}, a, b, p, 1, 1, 0, 1;\n}\n"
    : "+f"(d[0]),"+f"(d[1]),"+f"(d[2]),"+f"(d[3]),"+f"(d[4]),"+f"(d[5]),"+f"(d[6]),"+f"(d[7]),"+f"(d[8]),"+f"(d[9]),"+f"(d[10]),"+f"(d[11]),"+f"(d[12]),"+f"(d[13]),"+f"(d[14]),"+f"(d[15])
    : "r"(da), "r"(db), "r"(sd));
}
__device__ __forceinline__ void wgmma_rs_n40(float (&d)[20], uint32_t a0, uint32_t a1, uint32_t a2, uint32_t a3, uint32_t db, int sd) {
  asm volatile("{\n.reg .pred p;\n.reg .b64 b;\nsetp.ne.b32 p, %25, 0;\nmov.b64 b, {%24, 0x10};\n"
    "wgmma.mma_async.sync.aligned.m64n40k16.f32.bf16.bf16 {%0,%1,%2,%3,%4,%5,%6,%7,%8,%9,%10,%11,%12,%13,%14,%15,%16,%17,%18,%19}, {%20,%21,%22,%23}, b, p, 1, 1, 1;\n}\n"
    : "+f"(d[0]),"+f"(d[1]),"+f"(d[2]),"+f"(d[3]),"+f"(d[4]),"+f"(d[5]),"+f"(d[6]),"+f"(d[7]),"+f"(d[8]),"+f"(d[9]),"+f"(d[10]),"+f"(d[11]),"+f"(d[12]),"+f"(d[13]),"+f"(d[14]),"+f"(d[15]),"+f"(d[16]),"+f"(d[17]),"+f"(d[18]),"+f"(d[19])
    : "r"(a0), "r"(a1), "r"(a2), "r"(a3), "r"(db), "r"(sd));
}
__device__ __forceinline__ void wgmma_r1_n256(float (&d)[128], uint32_t da, uint32_t db, int sd) {
  asm volatile("{\n.reg .pred p;\n.reg .b64 a, b;\nsetp.ne.b32 p, %130, 0;\nmov.b64 a, {%128, 0x8};\nmov.b64 b, {%129, 0x6};\n"
    "wgmma.mma_async.sync.aligned.m64n256k16.f32.bf16.bf16 {%0,%1,%2,%3,%4,%5,%6,%7,%8,%9,%10,%11,%12,%13,%14,%15,%16,%17,%18,%19,%20,%21,%22,%23,%24,%25,%26,%27,%28,%29,%30,%31,%32,%33,%34,%35,%36,%37,%38,%39,%40,%41,%42,%43,%44,%45,%46,%47,%48,%49,%50,%51,%52,%53,%54,%55,%56,%57,%58,%59,%60,%61,%62,%63,%64,%65,%66,%67,%68,%69,%70,%71,%72,%73,%74,%75,%76,%77,%78,%79,%80,%81,%82,%83,%84,%85,%86,%87,%88,%89,%90,%91,%92,%93,%94,%95,%96,%97,%98,%99,%100,%101,%102,%103,%104,%105,%106,%107,%108,%109,%110,%111,%112,%113,%114,%115,%116,%117,%118,%119,%120,%121,%122,%123,%124,%125,%126,%127}, a, b, p, 1, 1, 0, 1;\n}\n"
    : "+f"(d[0]),"+f"(d[1]),"+f"(d[2]),"+f"(d[3]),"+f"(d[4]),"+f"(d[5]),"+f"(d[6]),"+f"(d[7]),"+f"(d[8]),"+f"(d[9]),"+f"(d[10]),"+f"(d[11]),"+f"(d[12]),"+f"(d[13]),"+f"(d[14]),"+f"(d[15]),"+f"(d[16]),"+f"(d[17]),"+f"(d[18]),"+f"(d[19]),"+f"(d[20]),"+f"(d[21]),"+f"(d[22]),"+f"(d[23]),"+f"(d[24]),"+f"(d[25]),"+f"(d[26]),"+f"(d[27]),"+f"(d[28]),"+f"(d[29]),"+f"(d[30]),"+f"(d[31]),"+f"(d[32]),"+f"(d[33]),"+f"(d[34]),"+f"(d[35]),"+f"(d[36]),"+f"(d[37]),"+f"(d[38]),"+f"(d[39]),"+f"(d[40]),"+f"(d[41]),"+f"(d[42]),"+f"(d[43]),"+f"(d[44]),"+f"(d[45]),"+f"(d[46]),"+f"(d[47]),"+f"(d[48]),"+f"(d[49]),"+f"(d[50]),"+f"(d[51]),"+f"(d[52]),"+f"(d[53]),"+f"(d[54]),"+f"(d[55]),"+f"(d[56]),"+f"(d[57]),"+f"(d[58]),"+f"(d[59]),"+f"(d[60]),"+f"(d[61]),"+f"(d[62]),"+f"(d[63]),"+f"(d[64]),"+f"(d[65]),"+f"(d[66]),"+f"(d[67]),"+f"(d[68]),"+f"(d[69]),"+f"(d[70]),"+f"(d[71]),"+f"(d[72]),"+f"(d[73]),"+f"(d[74]),"+f"(d[75]),"+f"(d[76]),"+f"(d[77]),"+f"(d[78]),"+f"(d[79]),"+f"(d[80]),"+f"(d[81]),"+f"(d[82]),"+f"(d[83]),"+f"(d[84]),"+f"(d[85]),"+f"(d[86]),"+f"(d[87]),"+f"(d[88]),"+f"(d[89]),"+f"(d[90]),"+f"(d[91]),"+f"(d[92]),"+f"(d[93]),"+f"(d[94]),"+f"(d[95]),"+f"(d[96]),"+f"(d[97]),"+f"(d[98]),"+f"(d[99]),"+f"(d[100]),"+f"(d[101]),"+f"(d[102]),"+f"(d[103]),"+f"(d[104]),"+f"(d[105]),"+f"(d[106]),"+f"(d[107]),"+f"(d[108]),"+f"(d[109]),"+f"(d[110]),"+f"(d[111]),"+f"(d[112]),"+f"(d[113]),"+f"(d[114]),"+f"(d[115]),"+f"(d[116]),"+f"(d[117]),"+f"(d[118]),"+f"(d[119]),"+f"(d[120]),"+f"(d[121]),"+f"(d[122]),"+f"(d[123]),"+f"(d[124]),"+f"(d[125]),"+f"(d[126]),"+f"(d[127])
    : "r"(da), "r"(db), "r"(sd));
}
__device__ __forceinline__ void wgmma_r1_n128(float (&d)[64], uint32_t da, uint32_t db, int sd) {
  asm volatile("{\n.reg .pred p;\n.reg .b64 a, b;\nsetp.ne.b32 p, %66, 0;\nmov.b64 a, {%64, 0x8};\nmov.b64 b, {%65, 0x6};\n"
    "wgmma.mma_async.sync.aligned.m64n128k16.f32.bf16.bf16 {%0,%1,%2,%3,%4,%5,%6,%7,%8,%9,%10,%11,%12,%13,%14,%15,%16,%17,%18,%19,%20,%21,%22,%23,%24,%25,%26,%27,%28,%29,%30,%31,%32,%33,%34,%35,%36,%37,%38,%39,%40,%41,%42,%43,%44,%45,%46,%47,%48,%49,%50,%51,%52,%53,%54,%55,%56,%57,%58,%59,%60,%61,%62,%63}, a, b, p, 1, 1, 0, 1;\n}\n"
    : "+f"(d[0]),"+f"(d[1]),"+f"(d[2]),"+f"(d[3]),"+f"(d[4]),"+f"(d[5]),"+f"(d[6]),"+f"(d[7]),"+f"(d[8]),"+f"(d[9]),"+f"(d[10]),"+f"(d[11]),"+f"(d[12]),"+f"(d[13]),"+f"(d[14]),"+f"(d[15]),"+f"(d[16]),"+f"(d[17]),"+f"(d[18]),"+f"(d[19]),"+f"(d[20]),"+f"(d[21]),"+f"(d[22]),"+f"(d[23]),"+f"(d[24]),"+f"(d[25]),"+f"(d[26]),"+f"(d[27]),"+f"(d[28]),"+f"(d[29]),"+f"(d[30]),"+f"(d[31]),"+f"(d[32]),"+f"(d[33]),"+f"(d[34]),"+f"(d[35]),"+f"(d[36]),"+f"(d[37]),"+f"(d[38]),"+f"(d[39]),"+f"(d[40]),"+f"(d[41]),"+f"(d[42]),"+f"(d[43]),"+f"(d[44]),"+f"(d[45]),"+f"(d[46]),"+f"(d[47]),"+f"(d[48]),"+f"(d[49]),"+f"(d[50]),"+f"(d[51]),"+f"(d[52]),"+f"(d[53]),"+f"(d[54]),"+f"(d[55]),"+f"(d[56]),"+f"(d[57]),"+f"(d[58]),"+f"(d[59]),"+f"(d[60]),"+f"(d[61]),"+f"(d[62]),"+f"(d[63])
    : "r"(da), "r"(db), "r"(sd));
}

__device__ __forceinline__ uint32_t smem_u32(const void* p) { return (uint32_t)__cvta_generic_to_shared(p); }
__device__ __forceinline__ void mbar_init(uint32_t bar, uint32_t cnt) { asm volatile("mbarrier.init.shared::cta.b64 [%0], %1;" ::"r"(bar), "r"(cnt)); }
__device__ __forceinline__ void mbar_expect_tx(uint32_t bar, uint32_t bytes) { asm volatile("mbarrier.arrive.expect_tx.shared::cta.b64 _, [%0], %1;" ::"r"(bar), "r"(bytes) : "memory"); }
__device__ __forceinline__ void mbar_arrive(uint32_t bar) { asm volatile("mbarrier.arrive.shared::cta.b64 _, [%0];" ::"r"(bar) : "memory"); }
__device__ __forceinline__ void mbar_arrive_n(uint32_t bar, uint32_t n) { asm volatile("mbarrier.arrive.shared::cta.b64 _, [%0], %1;" ::"r"(bar), "r"(n) : "memory"); }
__device__ __forceinline__ void mbar_wait(uint32_t bar, uint32_t parity) {
  asm volatile("{\n.reg .pred p;\nLAB_WAIT:\nmbarrier.try_wait.parity.shared::cta.b64 p, [%0], %1;\n@p bra DONE;\nbra LAB_WAIT;\nDONE:\n}" ::"r"(bar), "r"(parity) : "memory");
}
__device__ __forceinline__ void mbar_wait2(uint32_t a, uint32_t pa, uint32_t b, uint32_t pb) {
  asm volatile("{\n.reg .pred p, q;\nLAB_WAIT:\nmbarrier.try_wait.parity.shared::cta.b64 p, [%0], %1;\nmbarrier.try_wait.parity.shared::cta.b64 q, [%2], %3;\n"
               "and.pred p, p, q;\n@p bra DONE;\nbra LAB_WAIT;\nDONE:\n}" ::"r"(a), "r"(pa), "r"(b), "r"(pb) : "memory");
}
__device__ __forceinline__ void mbar_wait3(uint32_t a, uint32_t pa, uint32_t b, uint32_t pb) {
  asm volatile("{\n.reg .pred p, q, r;\nLAB_WAIT:\nmbarrier.try_wait.parity.shared::cta.b64 p, [%0], %1;\nmbarrier.try_wait.parity.shared::cta.b64 q, [%2], %3;\n"
               "mbarrier.try_wait.parity.shared::cta.b64 r, [%2+8], %3;\nand.pred p, p, q;\nand.pred p, p, r;\n@p bra DONE;\nbra LAB_WAIT;\nDONE:\n}" ::"r"(a), "r"(pa), "r"(b), "r"(pb) : "memory");
}
__device__ __forceinline__ bool mbar_probe2(uint32_t a, uint32_t pa, uint32_t b, uint32_t pb) {
  uint32_t ok;
  asm volatile("{\n.reg .pred p, q;\nmbarrier.test_wait.parity.shared::cta.b64 p, [%1], %2;\nmbarrier.test_wait.parity.shared::cta.b64 q, [%3], %4;\n"
               "and.pred p, p, q;\nselp.u32 %0, 1, 0, p;\n}" : "=r"(ok) : "r"(a), "r"(pa), "r"(b), "r"(pb) : "memory");
  return ok != 0;
}
__device__ __forceinline__ void tma_load_3d(uint32_t dst, const CUtensorMap* tm, uint32_t bar, int c0, int c1, int c2) {
  asm volatile("cp.async.bulk.tensor.3d.shared::cluster.global.mbarrier::complete_tx::bytes [%0], [%1, {%3, %4, %5}], [%2];"
               ::"r"(dst), "l"(tm), "r"(bar), "r"(c0), "r"(c1), "r"(c2) : "memory");
}
__device__ __forceinline__ void tma_load_2d(uint32_t dst, const CUtensorMap* tm, uint32_t bar, int c0, int c1) {
  asm volatile("cp.async.bulk.tensor.2d.shared::cluster.global.mbarrier::complete_tx::bytes [%0], [%1, {%3, %4}], [%2];"
               ::"r"(dst), "l"(tm), "r"(bar), "r"(c0), "r"(c1) : "memory");
}
__device__ __forceinline__ void tma_load_w(uint32_t dst, const CUtensorMap* tm, uint32_t bar, int col, int kb) {
#pragma unroll
  for (int q = 0; q < 2; q++)
    asm volatile("cp.async.bulk.tensor.5d.shared::cluster.global.mbarrier::complete_tx::bytes [%0], [%1, {%3, %4, %4, %4, %5}], [%2];"
                 ::"r"(dst + q * 8192), "l"(tm), "r"(bar), "r"(col + q * 64), "r"(0), "r"(2 * kb) : "memory");
}
__device__ __forceinline__ void tma_prefetch_w(const CUtensorMap* tm, int col, int kb) {
#pragma unroll
  for (int q = 0; q < 2; q++)
    asm volatile("cp.async.bulk.prefetch.tensor.5d.L2.global [%0, {%1, %2, %2, %2, %3}];" ::"l"(tm), "r"(col + q * 64), "r"(0), "r"(2 * kb) : "memory");
}
__device__ __forceinline__ void bulk_load(uint32_t dst, const void* g, uint32_t bytes, uint32_t bar) {
  asm volatile("cp.async.bulk.shared::cluster.global.mbarrier::complete_tx::bytes [%0], [%1], %2, [%3];" ::"r"(dst), "l"(g), "r"(bytes), "r"(bar) : "memory");
}
__device__ __forceinline__ void prefetch_map(const CUtensorMap* tm) { asm volatile("prefetch.tensormap [%0];" ::"l"(tm) : "memory"); }
__device__ __forceinline__ void fence_async_smem() { asm volatile("fence.proxy.async.shared::cta;" ::: "memory"); }
__device__ __forceinline__ void fence_async_global() { asm volatile("fence.proxy.async.global;" ::: "memory"); }
__device__ __forceinline__ void fence_gpu() { asm volatile("fence.release.gpu;" ::: "memory"); }
__device__ __forceinline__ void st_flag(unsigned* p, unsigned v) { asm volatile("st.relaxed.gpu.global.u32 [%0], %1;" ::"l"(p), "r"(v) : "memory"); }
__device__ __forceinline__ unsigned ld_flag(const unsigned* p) { unsigned v; asm volatile("ld.relaxed.gpu.global.u32 %0, [%1];" : "=r"(v) : "l"(p) : "memory"); return v; }
__device__ __forceinline__ uint4 ldcg4(const void* p) { uint4 v; asm volatile("ld.global.cg.v4.u32 {%0,%1,%2,%3}, [%4];" : "=r"(v.x), "=r"(v.y), "=r"(v.z), "=r"(v.w) : "l"(p)); return v; }
__device__ __forceinline__ uint4 ld_pkt(const uint4* p) {
  uint4 v; asm volatile("{\n.reg .b128 t;\nld.relaxed.gpu.global.b128 t, [%4];\nmov.b128 {%0,%1,%2,%3}, t;\n}" : "=r"(v.x), "=r"(v.y), "=r"(v.z), "=r"(v.w) : "l"(p) : "memory"); return v;
}
__device__ __forceinline__ void st_pkt(uint4* p, uint32_t a, uint32_t b, uint32_t c, uint32_t tag) {
  asm volatile("{\n.reg .b128 t;\nmov.b128 t, {%1,%2,%3,%4};\nst.relaxed.gpu.global.b128 [%0], t;\n}" ::"l"(p), "r"(a), "r"(b), "r"(c), "r"(tag) : "memory");
}
__device__ __forceinline__ void st_v4(uint4* p, uint32_t a, uint32_t b, uint32_t c, uint32_t d) { asm volatile("st.relaxed.gpu.global.v4.u32 [%0], {%1,%2,%3,%4};" ::"l"(p), "r"(a), "r"(b), "r"(c), "r"(d) : "memory"); }
__device__ __forceinline__ void stg128(uint4* p, uint4 v) { asm volatile("st.global.v4.u32 [%0], {%1,%2,%3,%4};" ::"l"(p), "r"(v.x), "r"(v.y), "r"(v.z), "r"(v.w) : "memory"); }
__device__ __forceinline__ void sts32(uint32_t addr, uint32_t a) { asm volatile("st.shared.u32 [%0], %1;" ::"r"(addr), "r"(a) : "memory"); }
__device__ __forceinline__ void sts64(uint32_t addr, uint32_t a, uint32_t b) { asm volatile("st.shared.v2.u32 [%0], {%1,%2};" ::"r"(addr), "r"(a), "r"(b) : "memory"); }
__device__ __forceinline__ uint32_t mul2(uint32_t a, uint32_t b) { uint32_t r; asm("mul.rn.bf16x2 %0, %1, %2;" : "=r"(r) : "r"(a), "r"(b)); return r; }
__device__ __forceinline__ uint32_t add2(uint32_t a, uint32_t b) { uint32_t r; asm("add.rn.bf16x2 %0, %1, %2;" : "=r"(r) : "r"(a), "r"(b)); return r; }
__device__ __forceinline__ bool elect() {
  uint32_t p; asm volatile("{\n.reg .pred q;\nelect.sync _|q, 0xffffffff;\nselp.u32 %0, 1, 0, q;\n}" : "=r"(p)); return p != 0;
}
__device__ __forceinline__ void wgmma_fence() { asm volatile("wgmma.fence.sync.aligned;" ::: "memory"); }
__device__ __forceinline__ void wgmma_commit() { asm volatile("wgmma.commit_group.sync.aligned;" ::: "memory"); }
template <int N> __device__ __forceinline__ void wgmma_wait() { asm volatile("wgmma.wait_group.sync.aligned %0;" ::"n"(N) : "memory"); }
template <int N> __device__ __forceinline__ void fence_regs(float (&d)[N]) {
#pragma unroll
  for (int i = 0; i < N; i++) asm volatile("" : "+f"(d[i])::"memory");
}
template <int R> __device__ __forceinline__ void reg_alloc() { asm volatile("setmaxnreg.inc.sync.aligned.u32 %0;" ::"n"(R)); }
template <int R> __device__ __forceinline__ void reg_dealloc() { asm volatile("setmaxnreg.dec.sync.aligned.u32 %0;" ::"n"(R)); }
__device__ __forceinline__ void wg_bar(int w) { asm volatile("bar.sync %0, 128;" ::"r"(w + 1) : "memory"); }
__device__ __forceinline__ constexpr uint32_t desc_lo(uint32_t addr, uint32_t lbo) { return (addr >> 4) + ((lbo >> 4) << 16); }
__device__ __forceinline__ uint32_t pack2(float lo, float hi) { uint32_t r; asm("cvt.rn.bf16x2.f32 %0, %1, %2;" : "=r"(r) : "f"(hi), "f"(lo)); return r; }
__device__ __forceinline__ float lo16(uint32_t v) { return __uint_as_float(v << 16); }
__device__ __forceinline__ float hi16(uint32_t v) { return __uint_as_float(v & 0xFFFF0000u); }
__device__ __forceinline__ float ex2(float x) { float r; asm("ex2.approx.ftz.f32 %0, %1;" : "=f"(r) : "f"(x)); return r; }
__device__ __forceinline__ float rcp(float x) { float r; asm("rcp.approx.ftz.f32 %0, %1;" : "=f"(r) : "f"(x)); return r; }
__device__ __forceinline__ uint32_t movm(uint32_t a) { uint32_t d; asm volatile("movmatrix.sync.aligned.m8n8.trans.b16 %0, %1;" : "=r"(d) : "r"(a)); return d; }
__device__ __forceinline__ void stsm4(uint32_t addr, uint32_t a, uint32_t b, uint32_t c, uint32_t d) {
  asm volatile("stmatrix.sync.aligned.m8n8.x4.shared.b16 [%0], {%1,%2,%3,%4};" ::"r"(addr), "r"(a), "r"(b), "r"(c), "r"(d) : "memory");
}
__device__ __forceinline__ void ldsm4(uint32_t addr, uint32_t (&r)[4]) {
  asm volatile("ldmatrix.sync.aligned.m8n8.x4.shared.b16 {%0,%1,%2,%3}, [%4];" : "=r"(r[0]), "=r"(r[1]), "=r"(r[2]), "=r"(r[3]) : "r"(addr) : "memory");
}
__device__ __forceinline__ void sts128(uint32_t addr, uint32_t a, uint32_t b, uint32_t c, uint32_t d) {
  asm volatile("st.shared.v4.u32 [%0], {%1,%2,%3,%4};" ::"r"(addr), "r"(a), "r"(b), "r"(c), "r"(d) : "memory");
}
__device__ __forceinline__ void lds128(uint32_t addr, uint32_t& a, uint32_t& b, uint32_t& c, uint32_t& d) {
  asm volatile("ld.shared.v4.u32 {%0,%1,%2,%3}, [%4];" : "=r"(a), "=r"(b), "=r"(c), "=r"(d) : "r"(addr) : "memory");
}
__device__ __forceinline__ float lds32f(uint32_t addr) { float v; asm volatile("ld.shared.f32 %0, [%1];" : "=f"(v) : "r"(addr) : "memory"); return v; }
__device__ __forceinline__ float2 lds64f(uint32_t addr) { float2 v; asm volatile("ld.shared.v2.f32 {%0,%1}, [%2];" : "=f"(v.x), "=f"(v.y) : "r"(addr) : "memory"); return v; }
__device__ __forceinline__ void mma16816(float (&d)[4], uint32_t a0, uint32_t a1, uint32_t a2, uint32_t a3, uint32_t b0, uint32_t b1) {
  asm("mma.sync.aligned.m16n8k16.row.col.f32.bf16.bf16.f32 {%0,%1,%2,%3}, {%4,%5,%6,%7}, {%8,%9}, {%0,%1,%2,%3};"
      : "+f"(d[0]), "+f"(d[1]), "+f"(d[2]), "+f"(d[3]) : "r"(a0), "r"(a1), "r"(a2), "r"(a3), "r"(b0), "r"(b1));
}
__device__ __forceinline__ void mma1688(float (&d)[4], uint32_t a0, uint32_t a1, uint32_t b0) {
  asm("mma.sync.aligned.m16n8k8.row.col.f32.bf16.bf16.f32 {%0,%1,%2,%3}, {%4,%5}, {%6}, {%0,%1,%2,%3};"
      : "+f"(d[0]), "+f"(d[1]), "+f"(d[2]), "+f"(d[3]) : "r"(a0), "r"(a1), "r"(b0));
}

__device__ __forceinline__ float qsum(float v) { v += __shfl_xor_sync(0xffffffffu, v, 1); v += __shfl_xor_sync(0xffffffffu, v, 2); return v; }

constexpr int NCTA = 132;
#define NB_ 6
#define NA_ 5
constexpr int NB = NB_;
constexpr int NA = NA_;
constexpr uint32_t SLOT = 16384;
constexpr uint32_t SB = 1024;
constexpr uint32_t OFF_B = 0;
constexpr uint32_t OFF_A = NB * SLOT;
constexpr uint32_t OFF_S = OFF_A + NA * SLOT;
constexpr uint32_t OFF_T = OFF_S + 20480;
constexpr uint32_t OFF_CS = OFF_T + 24576;
constexpr uint32_t OFF_MR = OFF_CS + 4640;
constexpr uint32_t OFF_BAR = OFF_MR + 512;
constexpr uint32_t OFF_MA = OFF_S, OFF_MB = OFF_CS - 2048;
constexpr uint32_t BAR_FULLB = OFF_BAR;
constexpr uint32_t BAR_FULLA = BAR_FULLB + 64;
constexpr uint32_t BAR_EMPTYB = BAR_FULLA + 64;
constexpr uint32_t BAR_EMPTYA = BAR_EMPTYB + 64;
constexpr uint32_t BAR_SIGP = BAR_EMPTYA + 64;
constexpr uint32_t BAR_SIGT = BAR_SIGP + 32;
constexpr uint32_t BAR_STAT = BAR_SIGP + 64;
constexpr uint32_t BAR_HALO = BAR_STAT + 16;
constexpr uint32_t BAR_CS = BAR_HALO + 8;
constexpr uint32_t BAR_WPHI = BAR_CS + 16;
constexpr uint32_t BAR_KV = BAR_WPHI + 8;
constexpr uint32_t BAR_STG = BAR_KV + 16;
constexpr uint32_t BAR_EPOCH = BAR_STG + 48;
constexpr uint32_t BAR_LAND = OFF_BAR + 7 * 64;
constexpr uint32_t OFF_EPOCH = OFF_BAR + 8 * 64;
static_assert(BAR_EPOCH < BAR_LAND, "barriers");
constexpr uint32_t SMEM_BYTES = OFF_EPOCH + 8;
static_assert(SMEM_BYTES <= 232448 && NB % 2 == 0 && NB <= 8 && NA <= 6, "smem");

#define CREGS 224
#define PREGS 56
#define PF1 19
#define PF2 21
#define PRE_A 2
#define PRE_B 4
#define CSB 4
#define CSNEED 0xF003u
#define XR 1
#define PS0 1
#define PS1 3
#define PSW 0
#define SD 1000
#define QORD 4
#define KSPLIT 12
#define KEEP 16
#define NJ 3
#define KSL 1000
#define PSL 0
#define KVS 12
#define D2 2000
#define D3 1500
#define G0 50
#define G3 50
#define G1 0
#define G4 0
#define MAP 3
#define PMAP 0x76321450u
#define PW 1
#define PN2 0
#define XA 3
#define XS 1
#define UK 0
#define CP 500
#define CD 0
#define S0 500
#define NS 2
#define XO 0
#define SW 2
#define SA 1
#define SB_ 4
#define XD 500
#define XD1 XD
#define XDX XD
#define KB 8
#define PNX 2
#define PNO 2
#define DEFER 3
#define DEFL 2
#define TSK 3
#define TSL 3
constexpr int NTHREADS = 384;

struct Params {
  CUtensorMap mx;
  CUtensorMap mw[3];
  CUtensorMap mwo[2];
  CUtensorMap mcs[2];
  CUtensorMap mwphi;
  uint4* out;
};

#define XBUF(L) 1
__device__ __align__(256) uint4 g_img[XBUF(3) + 1][16][16][1024];
__device__ __forceinline__ uint32_t img_code(bool isx, int L) { return isx ? (L & 1) | (L & 2) << 15 : ~L & 1; }
__device__ __forceinline__ uint32_t img_mask(bool isx) { return isx ? 0x10001u : 1u; }
__device__ __align__(256) uint4 g_wf[2][8][16][1024];
__device__ __align__(256) uint4 g_stats[16][2][8][32];
__device__ __align__(256) uint4 g_halo[16][8][2][256];
__device__ __align__(256) float g_cs[2][2][3072];
__device__ __align__(256) uint4 g_kvpart[8][16][2][544];
__device__ __align__(256) uint4 g_kvfin[8][16][80];
__device__ __align__(256) unsigned g_xflag[4][2][16][32];
__device__ __align__(256) unsigned g_oflag[4][2][16][32];
__device__ __align__(256) unsigned g_hflag[2][16][8][32];
__device__ __align__(256) unsigned g_kvfflag[2][8][2][32];
__device__ __align__(256) unsigned g_csflag[2][8][32];
__device__ __align__(256) unsigned g_kflag[8][32];
__device__ unsigned g_ctr;
__device__ __forceinline__ unsigned vblock() {
  unsigned s;
  asm volatile("mov.u32 %0, %%smid;" : "=r"(s));
  const unsigned r = s & 1;
  s >>= 1;
  const unsigned t = s - 32, q = (t * 37) >> 8;
  const unsigned hi = s < 60 ? 12 + (t - 7 * q) * 8 + q : (s < 62 ? s + 4 : s - 58);
  unsigned b = 2 * (s < 32 ? (s & 7) * 8 + (s >> 3) : hi) + r;
  if (b < 128) b = (b & 15) | ((PMAP >> ((b >> 4) * 4)) & 7) << 4;
  if (s >= 62) b = 8 + 4 * r + s - 62;
  return __shfl_sync(0xffffffffu, b, 0);
}
#define TS(who, id) do {} while (0)
#define TSW(id) do {} while (0)

#define TSMASK 0xFFFF
#define TSL_(a) do { if ((TSMASK >> (a)) & 1) TSW((a) + L * 12); } while (0)
__device__ __forceinline__ int cta_m(unsigned b) { return ((b >> 2) & 12) | (b & 3); }
__device__ __forceinline__ int cta_j(unsigned b) { return ((b >> 2) & 3) | ((b >> 4) & 4); }
struct Ring { uint32_t s, ph; };
template <int N> __device__ __forceinline__ void adv(Ring& r) { if (++r.s == N) { r.s = 0; r.ph ^= 1; } }
template <int N> __device__ __forceinline__ void rewind2(Ring& r) { if (r.s < 2) { r.s += N - 2; r.ph ^= 1; } else r.s -= 2; }
__device__ __forceinline__ int other_tile(int t, int j) { return (t == (j | 4) ? 7 : t) ^ (~j & 4); }
__device__ __forceinline__ int q_order(int i, int j) { return 2 * (i >= 14 ? j : other_tile(i >> 1, j)) + (i & 1); }
__device__ __forceinline__ int o_order(int i, int j) {
  if (i < 2) return 2 * j + i;
  const int odd = i >= 9;
  return 2 * other_tile(i - 2 - 7 * odd, j) + odd;
}
__device__ __forceinline__ int kv_order(int i, int j, int L) { return L > 0 ? o_order(i, j) : (i + 14 + 2 * (j & 4)) & 15; }

__device__ __forceinline__ unsigned poll_flags(const unsigned* f, int n, unsigned need, unsigned tag) {
  const int lane = threadIdx.x & 31;
  unsigned mask; int it = 0;
  do {
    unsigned v = lane < n ? ld_flag(f + lane) : 0u;
    mask = __ballot_sync(0xffffffffu, lane < n && v == tag);
    if (++it > (1 << 22)) __trap();
  } while ((mask & need) != need);
  fence_async_global();
  return mask;
}
template <bool WAIT = true>
__device__ __forceinline__ unsigned get_tag(uint32_t sb) {
  if (WAIT) mbar_wait(sb + BAR_EPOCH, 0);
  unsigned t; asm volatile("ld.shared.u32 %0, [%1];" : "=r"(t) : "r"(sb + OFF_EPOCH) : "memory");
  return t;
}

__device__ __forceinline__ int lane_id() { int l; asm volatile("mov.u32 %0, %%laneid;" : "=r"(l)); return l; }
__device__ __forceinline__ unsigned seq4(unsigned tag, int L) { return 8u | ((tag & 1u) << 2) | (unsigned)L; }
constexpr float LOG2E = 1.4426950408889634f;

__device__ __forceinline__ float bb_fence(int never, const void* p = &g_ctr, uint32_t keep = 0) {
  while (never < 0) never = ld_flag((const unsigned*)p) + keep;
  return __int_as_float(never >> 30);
}
__device__ __forceinline__ uint32_t solid(uint32_t v) { return __shfl_sync(0xffffffffu, v, threadIdx.x & 31); }
template <class T> __device__ __forceinline__ T* solid(T* p) { return (T*)__shfl_sync(0xffffffffu, (unsigned long long)p, threadIdx.x & 31); }
__device__ __forceinline__ void bb_keep(const float* v, int never) {
  while (never < 0) {
#pragma unroll
    for (int q = 0; q < 32; q += 4) sts128(never + q * 4, __float_as_uint(v[q]), __float_as_uint(v[q + 1]), __float_as_uint(v[q + 2]), __float_as_uint(v[q + 3]));
    never = ld_flag(&g_ctr + never);
  }
}
constexpr uint32_t HA128 = 0x40000040u, HA64 = 0x80000040u;
struct Ctx {
  static constexpr uint32_t sb = SB;
  uint32_t ab, da0;
  int w, warp, lane, g, c;
  int goff;
  __device__ __forceinline__ int m() const { return goff >> 14; }
  __device__ __forceinline__ int j() const { return (goff >> 4) & 7; }
  bool elected;
  Ring ra, rb;
  uint32_t pa, pb;
  uint32_t ha, k2;
  uint32_t mrow, mxor, mhi;
  __device__ __forceinline__ uint32_t aslot(uint32_t s) const { return ab + s * SLOT; }
  __device__ __forceinline__ uint32_t fullA(uint32_t s) const { return sb + BAR_FULLA + s * 8; }
  __device__ __forceinline__ uint32_t fullB(uint32_t s) const { return sb + BAR_FULLB + s * 8; }
  __device__ __forceinline__ void releaseA(uint32_t s) const { if (elected) mbar_arrive(sb + BAR_EMPTYA + s * 8); }
  __device__ __forceinline__ void releaseB(uint32_t s) const { if (elected) mbar_arrive(sb + BAR_EMPTYB + s * 8); }
  __device__ __forceinline__ uint32_t maddr(uint32_t tile, uint32_t ch) const { return tile + mrow + (((ch + mhi) ^ mxor) << 4); }
  __device__ __forceinline__ uint32_t oo() const { return warp * 128 + g * 4 + (c ^ (g >> 1)); }
  __device__ __forceinline__ uint4* img(int b, int hp) const { return ip + (b * 256 + hp) * 1024; }
  uint4* ip;
  uint32_t so;
  __device__ __forceinline__ uint32_t held(int i) const { return ra.s + i < 2 ? ra.s + i + NA - 2 : ra.s + i - 2; }
};

template <int N, bool FIRST, bool O = true>
__device__ __forceinline__ void gemm_issue(float (&acc)[N / 2], Ctx& x, bool ready = false) {
  if (!ready) {
    if (N == 256) mbar_wait3(x.fullA(x.ra.s), x.ra.ph, x.fullB(x.rb.s), x.rb.ph);
    else mbar_wait2(x.fullA(x.ra.s), x.ra.ph, x.fullB(x.rb.s), x.rb.ph);
  }
  const uint32_t da = x.da0 + x.ra.s * (SLOT / 16), db = desc_lo(SB + OFF_B, 8192) + x.rb.s * (SLOT / 16);
  wgmma_fence();
#pragma unroll
  for (int k = 0; k < 4; k++) {
    const uint32_t a = da + (k >> 1) * (O ? 32 : x.k2) + (k & 1) * 2, ha = O ? HA64 : x.ha;
    if constexpr (N == 256) wgmma_ss_n256(acc, a, ha, db + 128 * k, !(FIRST && k == 0));
    else wgmma_ss_n128(acc, a, ha, db + 128 * k, !(FIRST && k == 0));
  }
  wgmma_commit();
}
template <int N>
__device__ __forceinline__ void gemm_next(Ctx& x) {
  x.pa = x.ra.s; x.pb = x.rb.s;
  if (N == 256) x.rb.s++;
  adv<NA>(x.ra); adv<NB>(x.rb);
}
template <int N>
__device__ __forceinline__ void gemm_release(Ctx& x, bool relA) {
  if (relA) x.releaseA(x.pa);
  x.releaseB(x.pb);
  if (N == 256) x.releaseB(x.pb + 1);
}
template <int N>
__device__ __forceinline__ void gemm_retire(Ctx& x, bool relA) { wgmma_wait<1>(); gemm_release<N>(x, relA); gemm_next<N>(x); }
template <bool O = true>
__device__ __forceinline__ void gemm_run(float (&acc)[64], Ctx& x, int n, int hold, int n4 = 0) {
  bool ready = false;
#pragma unroll 1
  for (; n > 0; n--) {
    gemm_issue<128, false, O>(acc, x, ready);
    const uint32_t pa = x.pa, pb = x.pb;
    gemm_next<128>(x);
    ready = mbar_probe2(x.fullA(x.ra.s), x.ra.ph, x.fullB(x.rb.s), x.rb.ph);
    wgmma_wait<1>();
    if (n > hold) x.releaseA(pa);
    x.releaseB(pb);
  }
}
__device__ __forceinline__ void gemm_end(float (&acc)[64], Ctx& x) { wgmma_wait<0>(); fence_regs(acc); gemm_release<128>(x, false); }

__device__ __forceinline__ void rows_load(uint4* r, uint32_t tile, const Ctx& x) {
#pragma unroll
  for (int q = 0; q < 4; q++) {
    const uint32_t row = x.warp * 16 + 4 * q + (x.lane >> 3);
    lds128(tile + row * 128 + (((x.lane & 7) ^ (row & 7)) << 4), r[q].x, r[q].y, r[q].z, r[q].w);
  }
}
__device__ __forceinline__ void rows_store(const uint4* r, uint4* g) {
#pragma unroll
  for (int q = 0; q < 4; q++) stg128(g + q * 1024, r[q]);
}
__device__ __forceinline__ void publish(int id, const Ctx& x) { __syncwarp(); if (x.lane == 0) mbar_arrive(x.sb + BAR_SIGP + id * 8); }
__device__ __forceinline__ uint32_t img_tag(uint32_t v, bool isx, int L, const Ctx& x) {
  const uint32_t mk = ((x.lane ^ (x.warp * 4)) & 7) ? 0u : img_mask(isx);
  return (v & ~mk) | (img_code(isx, L) & mk);
}
__device__ __forceinline__ void img_tag(uint4 (&r)[4], bool isx, int L, const Ctx& x) {
#pragma unroll
  for (int q = 0; q < 4; q++) { uint32_t& v = q == 0 ? r[q].x : (q == 1 ? r[q].y : (q == 2 ? r[q].z : r[q].w)); v = img_tag(v, isx, L, x); }
}
__device__ __forceinline__ void img_store(const uint4 (&r)[4], uint4* g) {
#pragma unroll
  for (int q = 0; q < 4; q++) stg128(g + q * 32, r[q]);
}
__device__ __forceinline__ void img_sts(const uint4 (&r)[4], uint32_t tile, const Ctx& x) {
#pragma unroll
  for (int q = 0; q < 4; q++) sts128(tile + x.so + q * 512, r[q].x, r[q].y, r[q].z, r[q].w);
}
__device__ __forceinline__ void img_load(uint32_t (&v)[16], uint32_t tile, const Ctx& x) {
#pragma unroll
  for (int q = 0; q < 4; q++) lds128(tile + x.so + q * 512, v[4 * q], v[4 * q + 1], v[4 * q + 2], v[4 * q + 3]);
}
__device__ __forceinline__ void img_unpack(float* a, const uint32_t (&v)[16]) {
#pragma unroll
  for (int q = 0; q < 16; q++) { a[4 * (q & 7) + 2 * (q >> 3)] = lo16(v[q]); a[4 * (q & 7) + 2 * (q >> 3) + 1] = hi16(v[q]); }
}

template <int N>
__device__ __forceinline__ void stats_acc(const float* a, float (&t)[4]) {
#pragma unroll
  for (int i = 0; i < N; i++) { t[i & 2] += a[i]; t[(i & 2) + 1] = fmaf(a[i], a[i], t[(i & 2) + 1]); }
}
__device__ __forceinline__ void stats_send(float (&t)[4], int L, const Ctx& x) {
  const unsigned seq = seq4(get_tag<false>(x.sb), L);
#pragma unroll
  for (int q = 0; q < 4; q++) t[q] = qsum(t[q]);
  if (x.c == 0) st_pkt(&g_stats[x.m()][x.w][x.j()][x.warp * 8 + x.g], __float_as_uint(t[0]), __float_as_uint(t[1]), __float_as_uint(t[2]), (__float_as_uint(t[3]) & ~15u) | seq);
}
__device__ __forceinline__ void out_epilogue(const float (&acc)[64], uint4 (&r1)[4], float (&t)[4], uint4* g, int L, Ctx& x) {
  const uint32_t t0 = x.aslot(x.ra.s), t1 = x.aslot(x.ra.s + 1 == NA ? 0 : x.ra.s + 1);
  if (L == 3) {
#pragma unroll
    for (int p = 0; p < 8; p++) {
      stsm4(x.maddr(p < 4 ? t0 : t1, (p & 3) * 2), pack2(acc[8 * p], acc[8 * p + 1]), pack2(acc[8 * p + 2], acc[8 * p + 3]),
            pack2(acc[8 * p + 4], acc[8 * p + 5]), pack2(acc[8 * p + 6], acc[8 * p + 7]));
      if ((p & 3) == 3) { uint4 r[4]; __syncwarp(); rows_load(r, p < 4 ? t0 : t1, x); rows_store(r, g + (p >> 2) * 8); }
    }
  } else {
    auto pack16 = [&](uint4 (&r)[4], const float* a) {
#pragma unroll
      for (int q = 0; q < 4; q++) { const float* u = a + 16 * (q & 1) + (q & 2); r[q] = make_uint4(pack2(u[0], u[1]), pack2(u[4], u[5]), pack2(u[8], u[9]), pack2(u[12], u[13])); }
    };
    uint4 r0[4];
    pack16(r0, acc);
    img_tag(r0, true, L + 1, x);
    img_store(r0, x.img(XBUF(L + 1), 0));
    publish(2, x);
    const float z = bb_fence(x.goff);
    img_sts(r0, t0, x);
    pack16(r1, acc + 32);
    img_tag(r1, true, L + 1, x);
    img_sts(r1, t1, x);
    float u[4] = {z, z, z, z}, v[4] = {z, z, z, z};
    stats_acc<32>(acc, v);
    stats_acc<32>(acc + 32, u);
#pragma unroll
    for (int q = 0; q < 4; q++) t[q] = u[q] + v[q];
    mbar_wait2(x.fullB(x.rb.s), x.rb.ph, x.fullB(x.rb.s + 1), x.rb.ph);
    fence_async_smem();
    asm volatile("bar.sync %0, %1;" ::"r"(L == 1 ? x.w + 1 : 3), "r"(L == 1 ? 128 : 256) : "memory");
  }
}

struct Stats { float rstd0, rstd1; };
__device__ __forceinline__ Stats load_stats(int half, const Ctx& x) {
  const float2 u = lds64f(x.sb + OFF_MR + half * 256 + (x.warp * 8 + x.g) * 8);
  return {u.x, u.y};
}

template <int NK>
__device__ __forceinline__ void hedgehog_scale(float* t, const Stats& st, const uint32_t* keep) {
#pragma unroll
  for (int q = 0; q < 16; q++) t[q] *= ((q & 2) ? st.rstd1 : st.rstd0) * LOG2E;
  float m[4];
#pragma unroll
  for (int q = 0; q < 4; q++) m[q] = fmaxf(fmaxf(fabsf(t[4 * q]), fabsf(t[4 * q + 1])), fmaxf(fabsf(t[4 * q + 2]), fabsf(t[4 * q + 3])));
  if (__builtin_expect(__any_sync(0xffffffffu, fmaxf(fmaxf(m[0], m[1]), fmaxf(m[2], m[3])) > 58.f), 0)) {
    float z[16 + NK];
#pragma unroll
    for (int q = 0; q < 16 + NK; q++) z[q] = q < 16 ? t[q & 15] : __uint_as_float(keep[q & 15]);
#pragma unroll 1
    for (int r = 0; r < 4; r += 2) {
      float hi = -INFINITY, lo = INFINITY;
#pragma unroll 1
      for (int i = 0; i < 16; i++) {
        const int k = (i & 6) * 2 + (i & 1) + r;
        const float v = z[k];
        if (i < 8) { hi = fmaxf(hi, v); lo = fminf(lo, v); }
        else z[k] = v - fminf(fmaxf(v, lo), hi);
        if (i == 7) {
#pragma unroll 1
          for (int d = 1; d <= 2; d++) { hi = fmaxf(hi, __shfl_xor_sync(0xffffffffu, hi, d)); lo = fminf(lo, __shfl_xor_sync(0xffffffffu, lo, d)); }
          const float mid = 0.5f * hi + 0.5f * lo;
          hi = fmaxf(hi - 58.f, mid); lo = fminf(lo + 58.f, mid);
        }
      }
    }
#pragma unroll
    for (int q = 0; q < 16; q++) t[q] = z[q];
  }
}
__device__ __forceinline__ void dual_exp(const float* t, uint32_t (&f)[18], int never) {
  float e[KSPLIT];
#pragma unroll
  for (int q = 0; q < KSPLIT; q++) e[q] = ex2(q < 16 ? t[q] : -t[q & 15]);
  while (never < 0) {
#pragma unroll
    for (int i = 0; i < KSPLIT; i += 4) asm volatile("ld.shared.v4.f32 {%0,%1,%2,%3}, [%4];" : "=f"(e[i]), "=f"(e[i + 1]), "=f"(e[i + 2]), "=f"(e[i + 3]) : "r"(never + i) : "memory");
    never += __float_as_int(e[0]);
  }
#pragma unroll
  for (int q = 0; q < KSPLIT; q += 2) f[q >> 1] = pack2(e[q], e[q + 1]);
#pragma unroll
  for (int q = KSPLIT; q < 32; q += 2) f[q >> 1] = q < 16 ? pack2(ex2(t[q]), ex2(t[q + 1])) : pack2(ex2(-t[q & 15]), ex2(-t[(q & 15) + 1]));
#pragma unroll
  for (int sg = 0; sg < 2; sg++) {
    const uint32_t* u = f + 8 * sg;
    const uint32_t a = add2(add2(u[0], u[2]), add2(u[4], u[6])), b = add2(add2(u[1], u[3]), add2(u[5], u[7]));
    f[16 + sg] = add2(__byte_perm(a, b, 0x5410), __byte_perm(a, b, 0x7632));
  }
}
__device__ __forceinline__ void dual_exp_rcp(const float* t, uint32_t (&f)[16]) {
#pragma unroll
  for (int q = 0; q < 8; q++) {
    const float a = ex2(t[2 * q]), b = ex2(t[2 * q + 1]), r = rcp(a * b);
    f[q] = pack2(a, b); f[8 + q] = pack2(r * b, r * a);
  }
}
__device__ __forceinline__ void cta_bar() { asm volatile("bar.sync 3, 256;" ::: "memory"); }

template <int N> __device__ __forceinline__ void pin(const uint32_t* v, uint32_t addr) {
#pragma unroll
  for (int i = 0; i < N; i += 4)
    asm volatile("{\n.reg .pred p;\nsetp.eq.u32 p, %0, 0;\n@p st.shared.v4.u32 [%0], {%1,%2,%3,%4};\n}" ::"r"(addr), "r"(v[i]), "r"(v[i + 1]), "r"(v[i + 2]), "r"(v[i + 3]) : "memory");
}

__device__ __forceinline__ void consumer(const Params& P, uint32_t sb, int w, unsigned vb) {
  Ctx x;
  x.w = w;
  x.ab = sb + OFF_A + w * 8192; x.da0 = desc_lo(SB + OFF_A, 16) + w * 512;
  x.lane = threadIdx.x & 31; x.warp = __shfl_sync(0xffffffffu, (threadIdx.x >> 5) & 3, 0); x.g = x.lane >> 2; x.c = x.lane & 3;
  x.goff = (cta_m(vb) * 128 + w) * 128 + cta_j(vb) * 16;
  asm volatile("" : "+r"(x.goff));
  x.elected = (threadIdx.x & 127) == 0;
  x.ra = {0, 0}; x.rb = {0, 0}; x.pa = x.pb = 0;
  {
    const uint32_t row = x.warp * 16 + (x.lane & 15);
    x.mrow = row * 128; x.mxor = row & 7; x.mhi = x.lane >> 4;
  }
  const int goff = x.goff;
  x.ip = solid(&g_img[0][x.m()][2 * x.j()][w * 512 + x.oo()]);
  x.so = solid(16 * x.oo());
  uint4 r1[4];
  float ts[4] = {0.f, 0.f, 0.f, 0.f};
#pragma unroll
  for (int i = 0; i < 4; i++) r1[i] = make_uint4(0, 0, 0, 0);
  TSW(0);
  mbar_wait3(x.fullA(0), 0, x.fullB(0), 0);
#pragma unroll 1
  for (int L = 0; L < 4; L++) {
    float acc[64];
    constexpr uint32_t dcs = desc_lo(SB + OFF_CS, 0);
    if ((L & 1) == 0) {
    float kv[128];
    x.ha = L ? HA64 : HA128; x.k2 = L ? 32 : 4;
    gemm_issue<256, true, false>(kv, x, true); gemm_next<256>(x);
    {
      int i = 1;
#pragma unroll 1
      for (int seg = L ? NS - 1 : 0; seg <= NS; seg++) {
        const int end = seg < NS ? (L == 0 ? 3 + SA * ((x.j() + SW * w) & 3) + SB_ * seg : XA + 1) : 14 + L;
#pragma unroll 1
        do {
          gemm_issue<256, false, false>(kv, x);
          gemm_retire<256>(x, true);
          i++;
          if (i == 5) TSL_(8);
          if (i == 11) TSL_(10);
        } while (i != end);
        if (seg < NS && L == 0) {
          uint32_t v[16];
          float a[32];
#pragma unroll
          for (int q = 0; q < 4; q++) ldsm4(x.maddr(x.aslot(x.pa), 2 * q), reinterpret_cast<uint32_t (&)[4]>(v[4 * q]));
#pragma unroll
          for (int q = 0; q < 16; q++) { a[2 * q] = lo16(v[q]); a[2 * q + 1] = hi16(v[q]); }
          stats_acc<32>(a, ts);
          fence_regs(ts);
          wg_bar(w);
        }
        if (seg == NS - 1) {
          if (L > 0) { img_store(r1, x.img(XBUF(L), 1)); publish(3, x); }
          mbar_wait(sb + BAR_EPOCH, 0);
          stats_send(ts, L, x);
        }
      }
    }
      const Ring kt = x.ra;
      if (L == 0) adv<NA>(x.ra);
#pragma unroll 1
      for (int h = L; h < 2; h++) {
        float d[16];
        mbar_wait2(x.fullA(kt.s), kt.ph, sb + BAR_WPHI, 0);
        wgmma_fence();
#pragma unroll
        for (int q = 0; q < 2; q++) wgmma_ss_n32(d, x.da0 + kt.s * (SLOT / 16) + h * 4 + q * 2, desc_lo(SB + OFF_S + 4096, 512) + w * 256 + h * 128 + q * 64, q);
        wgmma_commit();
        gemm_issue<256, false, false>(kv, x);
        gemm_retire<256>(x, true);
        if (h) x.releaseA(kt.s);
        fence_regs(d);
        uint4* dst = &g_wf[1][x.j()][x.m()][w * 512 + (x.warp * 16 + x.g) * 8 + ((h * 4 + x.c) ^ x.g)];
        dst[0] = make_uint4(pack2(d[0], d[1]), pack2(d[4], d[5]), pack2(d[8], d[9]), pack2(d[12], d[13]));
        dst[64] = make_uint4(pack2(d[2], d[3]), pack2(d[6], d[7]), pack2(d[10], d[11]), pack2(d[14], d[15]));
      }
      const uint32_t dm = desc_lo(SB + OFF_MA, 0) + w * 64;
      mbar_wait2(sb + BAR_STAT, 0, sb + BAR_CS, 0);
      wgmma_fence();
      wgmma_r1_n256(kv, dm, dcs + 96, 1);
      wgmma_commit();
      const Stats st = load_stats(w, x);
      mbar_wait2(x.fullA(x.ra.s), x.ra.ph, x.fullB(x.rb.s), x.rb.ph);
      wgmma_wait<0>();
      fence_regs(kv);
      gemm_release<256>(x, true);
      TSL_(2);
      uint32_t P0[32], P1[32], PH[32];
#pragma unroll
      for (int t = 0; t < 16; t++) { P0[t] = pack2(kv[4 * t] * st.rstd0, kv[4 * t + 1] * st.rstd0); P1[t] = pack2(kv[4 * t + 2] * st.rstd1, kv[4 * t + 3] * st.rstd1); }
      pin<16>(P0, x.mrow + 16);
      {
#pragma unroll
        for (int q = 0; q < 4; q++) sts128((x.warp < 3 ? sb + OFF_T + w * 12288 + x.warp * 4096 : sb + OFF_S + 16384 + w * 2048) + x.lane * 16 + q * 512, P1[4 * q], P1[4 * q + 1], P1[4 * q + 2], P1[4 * q + 3]);
      }
      wgmma_fence();
      wgmma_r1_n128(acc, dm, dcs, 0);
      gemm_issue<128, false, false>(acc, x, PW & 1); gemm_next<128>(x);
      TSL_(3);
#pragma unroll
      for (int s = 0; s < 4; s++) {
#pragma unroll
        for (int t = 16 + 8 * (s & 1); t < 24 + 8 * (s & 1); t++) {
          if (s < 2) P1[t] = movm(pack2(kv[4 * t + 2] * st.rstd1, kv[4 * t + 3] * st.rstd1));
          else P0[t] = movm(pack2(kv[4 * t] * st.rstd0, kv[4 * t + 1] * st.rstd0));
        }
        if (s < 3) { gemm_issue<128, false, false>(acc, x); gemm_retire<128>(x, true); }
        if (s == 1) {
          if (x.warp < 3) {
#pragma unroll
            for (int q = 4; q < 8; q++) sts128(sb + OFF_T + w * 12288 + x.warp * 4096 + x.lane * 16 + q * 512, P1[4 * q], P1[4 * q + 1], P1[4 * q + 2], P1[4 * q + 3]);
          } else {
            uint4* dst = &g_halo[x.m()][x.j()][w][x.lane];
#pragma unroll
            for (int q = 0; q < 8; q++) dst[q * 32] = make_uint4(P1[4 * q], P1[4 * q + 1], P1[4 * q + 2], P1[4 * q + 3]);
          }
          publish(4, x);
          gemm_issue<128, false, false>(acc, x);
          gemm_retire<128>(x, true);
        }
      }
      TSL_(4);
      gemm_run<false>(acc, x, 10, 0);
      gemm_issue<128, false, false>(acc, x);
      {
        wg_bar(w);
        uint32_t tr = sb + OFF_T + w * 12288 + (x.warp - 1) * 4096;
        if (x.warp == 0) {
          tr = x.m() > 0 ? sb + OFF_S + 8192 + w * 4096 : tr + 4096;
          if (x.m() > 0) mbar_wait(sb + BAR_HALO, L >> 1);
        }
#pragma unroll
        for (int q = 0; q < 8; q++) lds128(tr + x.lane * 16 + q * 512, PH[4 * q], PH[4 * q + 1], PH[4 * q + 2], PH[4 * q + 3]);
      }
      gemm_retire<128>(x, false);
      gemm_end(acc, x);
      TSL_(5);
      const bool first = (x.m() == 0) && (x.warp == 0);
      const bool hi0 = 2 * x.c > x.g, hi1 = 2 * x.c + 1 > x.g;
      const uint32_t mhi = (hi0 ? 0xFFFFu : 0u) | (hi1 ? 0xFFFF0000u : 0u);
      const float sc0 = st.rstd0 * (0.17677669529663687f * LOG2E), sc1 = st.rstd1 * (0.17677669529663687f * LOG2E);
#pragma unroll
      for (int hp = 0; hp < 2; hp++) {
        const uint32_t tile = x.aslot(x.held(hp));
        uint32_t px[2], py[2];
        float s[2][3][4];
#pragma unroll
        for (int u = 0; u < 2; u++) {
#pragma unroll
          for (int q = 0; q < 12; q++) s[u][q >> 2][q & 3] = 0.f;
#pragma unroll
          for (int ks = 0; ks < 2; ks++) {
            const int t = 8 * hp + 4 * u + 2 * ks;
            const uint32_t a0 = pack2(acc[4 * t], acc[4 * t + 1]), a1 = pack2(acc[4 * t + 2], acc[4 * t + 3]);
            const uint32_t a2 = pack2(acc[4 * t + 4], acc[4 * t + 5]), a3 = pack2(acc[4 * t + 6], acc[4 * t + 7]);
            mma16816(s[u][0], a0, a1, a2, a3, PH[t], PH[t + 1]);
            mma16816(s[u][1], a0, a1, a2, a3, P0[t], P0[t + 1]);
            mma16816(s[u][2], a0, a1, a2, a3, P1[t], P1[t + 1]);
          }
        }
        float e[2][4], r[2][2];
#pragma unroll
        for (int u = 0; u < 2; u++) {
          e[u][0] = (hi0 ? s[u][0][0] : s[u][1][0]) * sc0; e[u][1] = (hi1 ? s[u][0][1] : s[u][1][1]) * sc0;
          e[u][2] = (hi0 ? s[u][1][2] : s[u][2][2]) * sc1; e[u][3] = (hi1 ? s[u][1][3] : s[u][2][3]) * sc1;
          if (first) { if (hi0) e[u][0] = -1e30f; if (hi1) e[u][1] = -1e30f; }
          r[u][0] = fmaxf(e[u][0], e[u][1]); r[u][1] = fmaxf(e[u][2], e[u][3]);
        }
#pragma unroll
        for (int d = 1; d <= 2; d++)
#pragma unroll
          for (int q = 0; q < 4; q++) r[q >> 1][q & 1] = fmaxf(r[q >> 1][q & 1], __shfl_xor_sync(0xffffffffu, r[q >> 1][q & 1], d));
#pragma unroll
        for (int u = 0; u < 2; u++) {
#pragma unroll
          for (int q = 0; q < 4; q++) e[u][q] = ex2(e[u][q] - r[u][q >> 1]);
          r[u][0] = e[u][0] + e[u][1]; r[u][1] = e[u][2] + e[u][3];
        }
#pragma unroll
        for (int d = 1; d <= 2; d++)
#pragma unroll
          for (int q = 0; q < 4; q++) r[q >> 1][q & 1] += __shfl_xor_sync(0xffffffffu, r[q >> 1][q & 1], d);
#pragma unroll
        for (int u = 0; u < 2; u++) {
          const float rx = rcp(r[u][0]), ry = rcp(r[u][1]);
          px[u] = pack2(e[u][0] * rx, e[u][1] * rx); py[u] = pack2(e[u][2] * ry, e[u][3] * ry);
        }
        uint32_t o[8][2];
        uint4 ro[4];
#pragma unroll
        for (int q = 0; q < 8; q++) {
          float d[4] = {0.f, 0.f, 0.f, 0.f};
          const int t = 16 + 8 * hp + q, u = q >> 2;
          mma16816(d, px[u] & mhi, 0u, px[u] & ~mhi, py[u] & mhi, PH[t], P0[t]);
          mma1688(d, 0u, py[u] & ~mhi, P1[t]);
          o[q][0] = pack2(d[0], d[1]); o[q][1] = pack2(d[2], d[3]);
        }
#pragma unroll
        for (int q = 0; q < 4; q++) ro[q] = make_uint4(o[4 * (q & 1)][q >> 1], o[4 * (q & 1) + 1][q >> 1], o[4 * (q & 1) + 2][q >> 1], o[4 * (q & 1) + 3][q >> 1]);
        img_tag(ro, false, 0, x);
        img_store(ro, x.img(0, hp));
        publish(hp, x);
        uint32_t xs[16];
        if (L) img_load(xs, tile, x);
        else {
#pragma unroll
          for (int q = 0; q < 4; q++) {
            uint32_t v[4];
            ldsm4(x.maddr(tile, 2 * q), v);
            xs[2 * q] = v[0]; xs[8 + 2 * q] = v[1]; xs[2 * q + 1] = v[2]; xs[9 + 2 * q] = v[3];
          }
          __syncwarp();
        }
        img_sts(ro, tile, x);
        img_unpack(acc + 32 * hp, xs);
      }
    } else {
      float kv[128];
      float (&kv0)[64] = reinterpret_cast<float (&)[64]>(kv[0]);
      float (&kv1)[64] = reinterpret_cast<float (&)[64]>(kv[64]);
      auto mma8 = [&](uint32_t as, uint32_t bs, int i, bool fence) {
        const uint32_t da = desc_lo(SB + OFF_A, 16) + as * (SLOT / 16), db = desc_lo(SB + OFF_B, 8192) + bs * (SLOT / 16);
        if (fence) wgmma_fence();
#pragma unroll
        for (int k = 0; k < 4; k++) {
          wgmma_ss_n128(kv0, da + (k >> 1) * 32 + (k & 1) * 2, HA64, db + 128 * k, i + k);
          wgmma_ss_n128(kv1, da + 512 + (k >> 1) * 32 + (k & 1) * 2, HA64, db + 128 * k, i + k);
        }
        wgmma_commit();
      };
      constexpr uint32_t dm = desc_lo(SB + OFF_MB, 0);
      auto relB = [&](uint32_t s) { mbar_arrive_n(sb + BAR_EMPTYB + s * 8, 2); };
      auto skip = [&]() {
#pragma unroll
        for (int q = 0; q < 6 - NJ; q++) adv<NA>(x.ra);
        x.rb.s = w ? (2 + NJ) % 6 : 4;
        if (!w && NJ < 4) x.rb.ph ^= 1;
      };
      static_assert(NA == 5 && NB == 6, "ring arithmetic");
      mma8(x.ra.s, x.rb.s + w, 0, true);
      gemm_next<256>(x);
#pragma unroll 1
      for (int i = 1; i < NJ; i++) {
        mbar_wait2(x.fullA(x.ra.s), x.ra.ph, x.fullB(x.rb.s + w), x.rb.ph);
        mma8(x.ra.s, x.rb.s + w, 1, true);
        if (!XO && i == XR) { img_store(r1, x.img(XBUF(L), 1)); publish(3, x); }
        if (!XO && i == XS) stats_send(ts, L, x);
        wgmma_wait<1>();
        if (x.elected) { x.releaseA(x.pa); relB(x.pb + w); }
        gemm_next<256>(x);
        if (XO && i == XR) { img_store(r1, x.img(XBUF(L), 1)); publish(3, x); stats_send(ts, L, x); }
      }
      if (w) {
        wgmma_wait<0>();
        if (x.elected) { x.releaseA(x.pa); relB(x.pb + 1); }
        skip();
        asm volatile("bar.sync 7, 256;" ::: "memory");
      }
      TSL_(8);
      {
        const int t = lane_id() + 32 * x.warp;
        uint32_t mask = t < 2 ? ((w ? (t ? 0xFF3Fu : 0x3FFFu) : 0xFFFFu) >> (NJ - 1)) & (w ? ~1u : ~0u) : 0u, cnt = 1 + t;
        bool ready = false;
#pragma unroll 1
        for (int i = NJ; i < 16; i++) {
          if (!ready) mbar_wait2(x.fullA(x.ra.s), x.ra.ph, x.fullB(x.rb.s), x.rb.ph);
          mma8(x.ra.s, x.rb.s, 1, true);
          const uint32_t bar = sb + (t ? BAR_EMPTYB + x.pb * 8 : BAR_EMPTYA + x.pa * 8);
          gemm_next<128>(x);
          if (w && (i | 4) == 15) x.rb.s = 4;
          ready = mbar_probe2(x.fullA(x.ra.s), x.ra.ph, x.fullB(x.rb.s), x.rb.ph);
          wgmma_wait<1>();
          if (mask & 1) mbar_arrive_n(bar, cnt);
          mask >>= 1; cnt = 2;
          if (i == 8 && w) asm volatile("bar.arrive 9, 256;" ::: "memory");
          if (i == 9) TSL_(10);
        }
        mbar_wait2(sb + BAR_STAT, 1, sb + BAR_CS + 8, 0);
        wgmma_fence();
        wgmma_r1_n128(kv0, dm, dcs + 96 + 96 * w, 1);
        wgmma_r1_n128(kv1, dm + 64, dcs + 96 + 96 * w, 1);
        wgmma_commit();
        if (w == 0) asm volatile("bar.arrive 7, 256;" ::: "memory");
        wgmma_wait<1>();
        if (mask & 1) mbar_arrive_n(sb + (t ? BAR_EMPTYB + x.pb * 8 : BAR_EMPTYA + x.pa * 8), 2);
      }
      const Stats s0 = load_stats(0, x), s1 = load_stats(1, x), st = w ? s1 : s0;
      if (w == 0) skip();
      const uint32_t h0 = x.held(0), h1 = x.held(1);
      auto vreg = [&](int ks) { return ks < 6 ? OFF_A + (ks < 3 ? h0 * SLOT : h1 * SLOT - 15360) + ks * 5120 : OFF_S + 2048 + ks * 5120; };
      uint32_t tV[2], uu[4];
#pragma unroll
      for (int hf = 0; hf < 2; hf++) {
        tV[hf] = sb + vreg(4 * hf + x.warp) + ((x.lane >> 3) & 1) * 2560 + (x.lane & 7) * 16 + x.mhi * 128;
        const float i0 = rcp(hf ? s1.rstd0 : s0.rstd0), i1 = rcp(hf ? s1.rstd1 : s0.rstd1);
        const uint32_t h = pack2(i0, i1);
        uu[2 * hf] = pack2(lo16(h), i0 - lo16(h)); uu[2 * hf + 1] = pack2(hi16(h), i1 - hi16(h));
        asm volatile("" : "+r"(tV[hf]), "+r"(uu[2 * hf]), "+r"(uu[2 * hf + 1])::"memory");
      }
      wgmma_wait<0>();
      fence_regs(kv);
      TSL_(2);
      if (w == 0) {
        uint32_t f[2][18], ad[4];
#pragma unroll
        for (int q = 0; q < 18; q++) f[1][q] = 0u;
#pragma unroll
        for (int q = 0; q < 4; q++) ad[q] = x.maddr(sb + OFF_S, 2 * q);
        auto norm = [&](int un) {
          uint32_t* u = f[un & 1];
          const Stats& sn = (un & 2) ? s1 : s0;
#pragma unroll
          for (int sg = 0; sg < 2; sg++) {
            uint32_t v = u[16 + sg];
            v = add2(v, __shfl_xor_sync(0xffffffffu, v, 1)); v = add2(v, __shfl_xor_sync(0xffffffffu, v, 2));
            const float a = rcp(lo16(v)) * sn.rstd0, b = rcp(hi16(v)) * sn.rstd1;
            const uint32_t r0 = pack2(a, a), r1_ = pack2(b, b);
#pragma unroll
            for (int q = 8 * sg; q < 8 * sg + 8; q++) u[q] = mul2(u[q], (q & 1) ? r1_ : r0);
#pragma unroll
            for (int q = 2 * sg; q < 2 * sg + 2; q++) stsm4(ad[q] + (un & 1) * SLOT + (un >> 1) * 8192, u[4 * q], u[4 * q + 1], u[4 * q + 2], u[4 * q + 3]);
          }
        };
        auto unit = [&](int un) { return kv + ((un >> 1) & 1) * 64 + (un & 1) * 16 + (un >> 2) * 32; };
        hedgehog_scale<0>(kv, s0, nullptr);
#pragma unroll 1
        for (int it = 0;; it++) {
#pragma unroll
          for (int un = 0; un < 4; un++) {
            if (un == 1) {
              if (it) asm volatile("bar.sync 9, 256;" ::: "memory");
#pragma unroll
              for (int q = 0; q < 4; q++) ad[q] -= it * (OFF_S - OFF_B - 2 * SLOT);
            }
            norm((un + 3) & 3);
            dual_exp(unit(un), f[un & 1], x.goff);
            hedgehog_scale<KEEP>(unit(un + 1), ((un + 1) & 2) ? s1 : s0, f[(un + 1) & 1]);
          }
          if (it) break;
#pragma unroll
          for (int q = 0; q < 32; q++) {
            asm volatile("mov.b32 %0, %1;" : "=f"(kv[q]) : "f"(kv[q + 32]));
            asm volatile("mov.b32 %0, %1;" : "=f"(kv[q + 64]) : "f"(kv[q + 96]));
            if (q < 16) kv[32 + q] = 0.f;
          }
        }
        norm(3);
        TSL_(3);
      } else {
        wg_bar(w);
#pragma unroll
        for (int hf = 0; hf < 2; hf++) {
          stsm4(tV[hf] + 512 + x.mhi * 512, uu[2 * hf], uu[2 * hf + 1], uu[2 * hf], uu[2 * hf + 1]);
          stsm4(tV[hf] + 1792 + x.mhi * 512, uu[2 * hf], uu[2 * hf + 1], uu[2 * hf], uu[2 * hf + 1]);
#pragma unroll
          for (int q = 0; q < 8; q++) {
            const float* u = kv + 64 * hf + 8 * q;
            stsm4(tV[hf] + (q >> 1) * 640 + (q & 1) * 256, pack2(u[0], u[1]), pack2(u[2], u[3]), pack2(u[4], u[5]), pack2(u[6], u[7]));
          }
        }
        TSL_(3);
      }
      {
        float d[2][20];
        uint4* dst = &g_kvpart[x.j()][w * 4 + x.warp][0][x.m() * 32 + x.lane];
        unsigned* dz = reinterpret_cast<unsigned*>(&g_kvpart[x.j()][w * 4 + x.warp][x.c & 1][512]) + x.m() * 8 + x.g;
        fence_async_smem();
        cta_bar();
        TSL_(11);
        uint32_t pk[9];
        auto prep = [&](float (&u)[20]) {
          fence_regs(u);
#pragma unroll
          for (int q = 0; q < 8; q++) pk[q] = pack2(u[((q >> 1) & 2) + 4 * (q & 3)], u[((q >> 1) & 2) + 4 * (q & 3) + 1]);
          pk[8] = __float_as_uint((x.c & 1) ? u[18] + u[19] : u[16] + u[17]);
#pragma unroll
          for (int q = 0; q < 9; q += 4) pk[q] = (pk[q] & ~1u) | (L == 1);
        };
        auto send = [&](int hp) {
          st_v4(dst + hp * 16 * 544, pk[0], pk[1], pk[2], pk[3]); st_v4(dst + (hp * 16 + 1) * 544, pk[4], pk[5], pk[6], pk[7]);
          st_flag(dz + hp * 16 * 544 * 4, pk[8]);
        };
        wgmma_fence();
#pragma unroll
        for (int q = 0; q < 17; q++) {
          if (q < 16) wgmma_ss_n40_tt(d[q >> 3], desc_lo(SB + (q < 8 ? OFF_S : OFF_B + 2 * SLOT), 1024) + w * (SLOT / 16) + 128 * (q & 7), desc_lo(SB + vreg(q & 7), 2560) + (w + (q >> 3) * 2) * 40, q & 7);
          else wgmma_r1_n128(acc, dm + w * 64, dcs, 0);
          if (q == 7 || q == KVS || q == 16) wgmma_commit();
          if (q == KVS) { mbar_wait2(x.fullA(x.ra.s), x.ra.ph, x.fullB(x.rb.s), x.rb.ph); wgmma_wait<1>(); prep(d[0]); send(0); bb_fence(x.goff); wgmma_fence(); }
        }
        gemm_issue<128, false>(acc, x, true); gemm_next<128>(x);
        wgmma_wait<1>();
        x.releaseA(h0); x.releaseA(h1); x.releaseB(2); x.releaseB(3);
        if (x.lane == 0) mbar_arrive(sb + BAR_SIGT);
        prep(d[1]);
        TSL_(4);
#pragma unroll 1
        for (int seg = 0; seg < 2; seg++) {
          const int n0 = w ? PS1 : PS0;
          gemm_run(acc, x, seg ? 15 - n0 : n0, seg, seg ? L : 0);
          if (seg == 0) send(1);
        }
      }
      gemm_end(acc, x);
      TSL_(5);
      {
        float dp[2][20], dn[2][20];
        uint32_t f[4][16];
        auto mma = [&](int h) {
          if (!(h & 1)) mbar_wait(sb + BAR_KV + h * 4, L >> 1);
          if (h == 0) TSL_(9);
          const uint32_t db = desc_lo(SB + OFF_S + h * 5120, 128);
          const uint32_t (&a)[16] = f[h];
          wgmma_fence();
          wgmma_rs_n40(dp[h & 1], a[0], a[1], a[2], a[3], db, 0);
          wgmma_rs_n40(dn[h & 1], a[8], a[9], a[10], a[11], db + 160, 0);
          wgmma_rs_n40(dp[h & 1], a[4], a[5], a[6], a[7], db + 80, 1);
          wgmma_rs_n40(dn[h & 1], a[12], a[13], a[14], a[15], db + 240, 1);
          wgmma_commit();
        };
        uint32_t xr[16];
        auto fin = [&](int h) {
          const uint32_t tile = x.aslot(x.held(h >> 1));
          if (!(h & 1)) img_load(xr, tile, x);
          float (&u)[20] = dp[h & 1];
          float (&v)[20] = dn[h & 1];
          fence_regs(u); fence_regs(v);
#pragma unroll
          for (int r = 0; r < 2; r++) {
            const float sp = u[16 + 2 * r], sn = v[16 + 2 * r];
            const float id = rcp(fmaf(fmaf(sp, L == 1 ? 0.065536f * 128 / 129 : 0.065536f, u[17 + 2 * r]), sn, v[17 + 2 * r] * sp)), aa = sn * id, cc = sp * id;
            uint32_t o[4];
#pragma unroll
            for (int t = 0; t < 4; t++) o[t] = pack2(fmaf(u[4 * t + 2 * r], aa, v[4 * t + 2 * r] * cc), fmaf(u[4 * t + 2 * r + 1], aa, v[4 * t + 2 * r + 1] * cc));
            o[2 * r + (h & 1)] = img_tag(o[2 * r + (h & 1)], false, 1, x);
            stg128(x.img(0, h >> 1) + r * 64 + (h & 1) * 32, make_uint4(o[0], o[1], o[2], o[3]));
            sts128(tile + r * 1024 + (h & 1) * 512 + x.so, o[0], o[1], o[2], o[3]);
          }
          if (h & 1) { publish(h >> 1, x); img_unpack(acc + 16 * (h - 1), xr); }
        };
        auto scale = [&](int h) { hedgehog_scale<0>(acc + 16 * h, st, nullptr); };
        auto ex = [&](int h) { dual_exp_rcp(acc + 16 * h, f[h]); };
        scale(0);
        ex(0); scale(1); mma(0);
        ex(1); wgmma_wait<0>(); fin(0); bb_fence(x.goff); mma(1);
        wgmma_wait<0>(); fin(1); scale(2);
        ex(2); scale(3); if (UK & 1) bb_keep(acc, x.goff); mma(2);
        ex(3); wgmma_wait<0>(); fin(2); mma(3);
        wgmma_wait<0>(); fin(3);
      }
    }
    if (PW & 2) { mbar_wait(x.fullB(x.rb.s), x.rb.ph); fence_regs(acc); }
    fence_async_smem();
    wg_bar(w);
    TSL_(6);
    rewind2<NA>(x.ra);
    gemm_issue<128, false>(acc, x, PW & 2); gemm_next<128>(x);
    uint4* out = solid(P.out + goff + (x.warp * 16 + (x.lane >> 3)) * 256 + (x.lane & 7));
#pragma unroll 1
    for (int seg = L >= TSL ? 0 : 1; seg < 2; seg++) {
      gemm_run(acc, x, L >= TSL ? (seg ? TSK : 15 - TSK) : 15, seg, 10 + L);
      if (L >= TSL) {
        if (seg == 0 && w == 1) asm volatile("bar.sync 6, 256;" ::: "memory");
        if (seg == 1 && w == 0) asm volatile("bar.arrive 6, 256;" ::: "memory");
      }
    }
    gemm_end(acc, x);
    TSL_(7);
    rewind2<NA>(x.ra);
    out_epilogue(acc, r1, ts, out, L, x);
    TSL_(13);
  }
}

typedef unsigned long long u64;
template <class T> __device__ __forceinline__ T* early(T* p) { return (T*)__shfl_xor_sync(0xffffffffu, (u64)p, 1); }
__device__ __forceinline__ void pause(uint32_t GAP) {
  if (GAP) { uint32_t t0, t; asm volatile("mov.u32 %0, %%clock;" : "=r"(t0)); do { asm volatile("mov.u32 %0, %%clock;" : "=r"(t)); } while (t - t0 < GAP); }
}
__device__ __forceinline__ u64 order_table(int kind, int j) {
  const int i = threadIdx.x & 15;
  const unsigned v = (unsigned)(kind == 2 ? q_order(i, j) : kv_order(i, j, kind)) << (4 * (i & 7));
  return (u64)__reduce_or_sync(0xffffffffu, i < 8 ? 0u : v) << 32 | __reduce_or_sync(0xffffffffu, i < 8 ? v : 0u);
}

__device__ __forceinline__ void b_producer(const Params& P, uint32_t sb, unsigned vb) {
  const int j = cta_j(vb);
  const u64 t0 = order_table(0, j), t1 = order_table(1, j), t2 = order_table(2, j);
  Ring r = {PRE_B % NB, PRE_B < NB};
#pragma unroll 1
  for (int sg = 0; sg < 20; sg++) {
    const int L = sg / 5, p = sg - 5 * L, wt = L & 1;
    int n = p >= 3 ? 16 : (wt ? (p ? 16 - NJ : 2 * NJ) : (p ? 0 : (L ? 32 : 32 - PRE_B)));
    u64 tab = p == 3 ? t2 : (sg == 0 ? t0 >> (2 * PRE_B) : (p == 1 || p == 2 ? t1 >> (4 * NJ) : t1));
    const CUtensorMap* tm = p == 4 ? &P.mwo[wt] : &P.mw[wt ? 1 : L];
    const uint4* img = &g_wf[p != 3][j][0][0];
    int col = (p >= 3 ? 0 : (p == 2 ? 2048 : 1024)) + 128 * j;
    const int flip = p == 0 ? 3072 : 0;
    const bool fold = wt && p != 4;
    if (sg == 5 || sg == 8) { mbar_wait(sb + (sg == 5 ? BAR_WPHI : BAR_CS + 8), sg == 5); fence_async_global(); }
    if (DEFER && p == 4 && ((DEFL >> wt) & 1)) {
      Ring q = r;
      for (int u = 0; u < DEFER; u++) adv<NB>(q);
      mbar_wait(sb + BAR_EMPTYB + q.s * 8, q.ph);
    }
#pragma unroll 1
    for (; n > 0; n--) {
      const int kb = (int)tab & 15;
      mbar_wait(sb + BAR_EMPTYB + r.s * 8, r.ph);
      if (elect()) {
        mbar_expect_tx(sb + BAR_FULLB + r.s * 8, SLOT);
        if (fold && col < 2048) bulk_load(sb + OFF_B + r.s * SLOT, img + kb * 1024, SLOT, sb + BAR_FULLB + r.s * 8);
        else tma_load_w(sb + OFF_B + r.s * SLOT, tm, sb + BAR_FULLB + r.s * 8, col, kb);
      }
      adv<NB>(r);
      if (p == 2 && (n | 4) == 5) r.s = 4;
      col ^= flip;
      if (!(col & flip & 2048)) tab >>= 4;
    }
  }
}

__device__ __forceinline__ void a_loader(const Params& P, uint32_t sb, unsigned vb) {
  const int j = cta_j(vb), m = cta_m(vb);
  const u64 t1 = order_table(1, j), t2 = order_table(2, j);
  Ring r = {PRE_A % NA, PRE_A < NA};
  {
    u64 tab = order_table(0, j) >> (4 * PRE_A);
#pragma unroll 1
    for (int i = PRE_A; i < 33; i++) {
      if (i == 17) tab = t2;
      mbar_wait(sb + BAR_EMPTYA + r.s * 8, r.ph);
      if (elect()) {
        mbar_expect_tx(sb + BAR_FULLA + r.s * 8, SLOT);
        if (i != 14) tma_load_3d(sb + OFF_A + r.s * SLOT, &P.mx, sb + BAR_FULLA + r.s * 8, ((int)tab & 15) * 64, m * 64, 0);
        else {
          tma_load_w(sb + OFF_A + r.s * SLOT, &P.mw[1], sb + BAR_FULLA + r.s * 8, 1024 + 128 * j, m);
          mbar_expect_tx(sb + BAR_WPHI, 8192); tma_load_2d(sb + OFF_S + 4096, &P.mwphi, sb + BAR_WPHI, 0, 128 * j);
        }
        if (i == PF1 || i == PF2) tma_prefetch_w(&P.mwo[i == PF2], 128 * j, m);
      }
      adv<NA>(r);
      if (i != 14) tab >>= 4;
    }
  }
  const unsigned tag = get_tag(sb);
  unsigned seen = 0, kph = 0;
#pragma unroll 1
  for (int sg = 0; sg < 27; sg++) {
    const int L = sg >> 3, p = sg & 7, q = p >= 3 ? p - 3 : p;
    if (p == 0 && (L & 1)) {
#pragma unroll 1
      for (int h = 0; h < 2; h++) {
        poll_flags(&g_kvfflag[L >> 1][j][h][0], 16, 0xFFFFu, tag);
        TS(4, h ? 14 + L : 26 + L);
        for (int it = 0;; it++) {
          if (elect()) { mbar_expect_tx(sb + BAR_STAT + 8, 10240); bulk_load(sb + OFF_S + h * 10240, &g_kvfin[j][8 * h][0], 10240, sb + BAR_STAT + 8); }
          mbar_wait(sb + BAR_STAT + 8, kph);
          kph ^= 1;
          uint32_t a = 1u, o = 0u;
#pragma unroll
          for (int u = 0; u < 20; u++) { const uint32_t v = __float_as_uint(lds32f(sb + OFF_S + h * 10240 + u * 512 + (threadIdx.x & 31) * 16)); a &= v; o |= v; }
          if (__all_sync(0xffffffffu, (L == 1 ? a : ~o) & 1u)) break;
          fence_async_smem();
          if (it > (1 << 16)) __trap();
        }
        if (elect()) mbar_arrive(sb + BAR_KV + h * 8);
        TS(4, h ? 30 + L : (L == 1 ? 20 : 25));
      }
    }
    int n = q == 0 ? 4 : (q == 1 ? 3 : (q == 2 ? 7 : (q == 3 ? ((L & 1) ? 0 : 16 - NJ) : 16)));
    u64 tab = q == 4 ? t2 : t1 >> (q == 0 ? 8 : (q == 1 ? 24 : (q == 2 ? 36 : 4 * NJ)));
    const uint4* img = &g_img[p >= 3 ? XBUF(L + 1) : 0][m][0][0];
    const uint32_t gap = p == 0 ? G0 : (p == 3 ? G3 : (q < 3 ? G1 : G4));
    bool poll = q == 0 || q == 2 || (q == 1 && seen != 0xFFFFFFFFu);
#pragma unroll 1
    for (; n > 0; n--) {
      const uint4* src = img + ((int)tab & 15) * 1024;
      src = early(src);
      const uint32_t bar = sb + (q < 3 ? BAR_LAND : BAR_FULLA) + r.s * 8;
      mbar_wait(sb + BAR_EMPTYA + r.s * 8, r.ph);
      if (elect()) mbar_expect_tx(bar, SLOT);
      if (poll) {
        const int lane = threadIdx.x & 31, nn = p >= 3 ? PNX : PNO;
        const unsigned* f = (p >= 3 ? &g_xflag[L + 1][0][m][0] : &g_oflag[L][0][m][0]) + (q == 2 ? 512 : 0) + (lane & 7);
        if (q == 0 || (PN2 && q == 2)) f += (((lane >> 3) & (nn - 1)) - (m & (nn - 1))) * 32;
        const unsigned need = q == 0 ? 0x0F0F0F0Fu << (~j & 4) : 0xFFFFFFFFu;
        if (q == 0) mbar_wait(sb + BAR_SIGP + (p ? 16 : 0), L & 1);
        int it = 0;
        do { seen = __ballot_sync(0xffffffffu, ld_flag(f) == tag); if (++it > (1 << 22)) __trap(); } while ((seen & need) != need);
        if (q == 0) TS(2, p == 0 ? 5 + L * 8 : 9 + L * 8);
        poll = false;
      }
      if (elect()) bulk_load(sb + OFF_A + r.s * SLOT, src, SLOT, bar);
      adv<NA>(r);
      tab >>= 4;
      pause(gap);
    }
  }
}

__device__ __forceinline__ uint2 sum_packets(float (&a)[8], uint32_t addr, int n) {
  uint2 ok = make_uint2(~0u, 0u);
#pragma unroll 1
  for (int b = 0; b < n; b += KB) {
    uint4 v[KB];
#pragma unroll
    for (int u = 0; u < KB; u++) lds128(addr + (b + u) * 512, v[u].x, v[u].y, v[u].z, v[u].w);
#pragma unroll
    for (int u = 0; u < KB; u++) {
      ok.x &= v[u].x; ok.y |= v[u].x;
      a[0] += lo16(v[u].x); a[1] += hi16(v[u].x); a[2] += lo16(v[u].y); a[3] += hi16(v[u].y);
      a[4] += lo16(v[u].z); a[5] += hi16(v[u].z); a[6] += lo16(v[u].w); a[7] += hi16(v[u].w);
    }
  }
  return ok;
}
__device__ __forceinline__ void helper_bar() { asm volatile("bar.sync 4, 64;" ::: "memory"); }
__device__ __forceinline__ void helper(const Params& P, uint32_t sb, int w, unsigned vb) {
  const int j = cta_j(vb), m = cta_m(vb);
  if (w == 0) {
    if (elect()) {
      const unsigned t = atomicAdd(&g_ctr, 1u) / NCTA + 1u;
      asm volatile("st.shared.u32 [%0], %1;" ::"r"(sb + OFF_EPOCH), "r"(t) : "memory");
      mbar_arrive(sb + BAR_EPOCH);
    }
  }
  const unsigned tag = get_tag(sb);
  mbar_wait(sb + BAR_FULLB + 24, 0);
  const uint32_t stg = sb + OFF_T + w * 12288, stb = sb + BAR_STG + w * 24;
  Ring rs = {0, 0};
  uint32_t vs = 33 % NA, vph = 0;
  auto cs_image = [&](int L) {
      const int lane = lane_id();
      poll_flags(&g_csflag[L][j][0], 16, L ? CSNEED : 0xFFFu, tag);
#pragma unroll
      for (int p = 0; p < 3; p++) {
        const uint4 u = ldcg4(&g_cs[L][0][p * 1024 + 128 * j + lane * 4]), v = ldcg4(&g_cs[L][1][p * 1024 + 128 * j + lane * 4]);
        const float c0 = __uint_as_float(u.x) + __uint_as_float(v.x), c1 = __uint_as_float(u.y) + __uint_as_float(v.y);
        const float c2 = __uint_as_float(u.z) + __uint_as_float(v.z), c3 = __uint_as_float(u.w) + __uint_as_float(v.w);
        const uint32_t h0 = pack2(c0, c1), h1 = pack2(c2, c3), dst = sb + OFF_CS + (p * 16 + (lane >> 1)) * 96 + L * 48 + (lane & 1) * 8;
        sts64(dst, h0, h1); sts64(dst + 16, pack2(c0 - lo16(h0), c1 - hi16(h0)), pack2(c2 - lo16(h1), c3 - hi16(h1))); sts64(dst + 32, h0, h1);
        if (L == 0) { sts64(dst + 48, 0u, 0u); sts64(dst + 64, 0u, 0u); sts64(dst + 80, 0u, 0u); }
      }
      if (L == 0 && lane < 4) sts64(sb + OFF_CS + 4608 + lane * 8, 0u, 0u);
      fence_async_smem();
      __syncwarp();
      if (elect()) mbar_arrive(sb + BAR_CS + L * 8);
      TS(4, 2 + L * 2);
  };
#pragma unroll 1
  for (int L = 0; L < 4; L++) {
    const int lane = lane_id();
    if (L == 0) {
      {
        const int wt = m >= 12, col = ((0x2021 >> (m & 12)) & 3) * 1024 + 128 * j + (m & 3) * 32;
        const CUtensorMap* tm = &P.mcs[wt];
        __nanosleep(wt ? D2 : CD);
        constexpr int nb = 8;
        float a[8] = {0.f, 0.f, 0.f, 0.f, 0.f, 0.f, 0.f, 0.f};
#pragma unroll 1
        for (int b = -3; b < nb; b++) {
          if (b >= 0) {
            mbar_wait(stb + rs.s * 8, rs.ph);
            sum_packets(a, stg + rs.s * 4096 + lane * 16, 8);
            fence_async_smem();
            __syncwarp();
          }
          const uint32_t sl = b < 0 ? (rs.s + b + 3) % 3 : rs.s;
          if (b + 3 < nb && elect()) { mbar_expect_tx(stb + sl * 8, 4096); tma_load_2d(stg + sl * 4096, tm, stb + sl * 8, col, (w * (16 - nb) + b + 3) * 64); }
          if (b >= 0) adv<3>(rs); else pause(CP);
        }
#pragma unroll
        for (int u = 0; u < 8; u++) {
          a[u] += __shfl_xor_sync(0xffffffffu, a[u], 4); a[u] += __shfl_xor_sync(0xffffffffu, a[u], 8); a[u] += __shfl_xor_sync(0xffffffffu, a[u], 16);
        }
        if (lane < 4) {
          float4* dst = reinterpret_cast<float4*>(&g_cs[wt][w][col + lane * 8]);
          dst[0] = make_float4(a[0], a[1], a[2], a[3]); dst[1] = make_float4(a[4], a[5], a[6], a[7]);
        }
        helper_bar();
        if (w == 0 && elect()) { fence_gpu(); st_flag(&g_csflag[wt][j][m], tag); }
      }
      if (w == 0) TS(4, 1 + L * 2);
    }
    if (w == (L == 0)) {
      if (L > 0) __nanosleep(SD);
      else if (S0) { mbar_wait(sb + BAR_WPHI, 0); __nanosleep(S0); }
#pragma unroll 1
      for (int p = 0; p < 2; p++) {
        uint4 v[8];
        for (int it = 0;; it++) {
          bool ok = true;
#pragma unroll
          for (int t = 0; t < 8; t++) v[t] = ld_pkt(&g_stats[m][p][t][lane]);
#pragma unroll
          for (int t = 0; t < 8; t++) ok = ok && (v[t].w & 15u) == seq4(tag, L);
          if (__all_sync(0xffffffffu, ok)) break;
          __nanosleep(200);
          if (it > (1 << 20)) __trap();
        }
        float s0 = 0.f, q0 = 0.f, s1 = 0.f, q1 = 0.f;
#pragma unroll
        for (int t = 0; t < 8; t++) { s0 += __uint_as_float(v[t].x); q0 += __uint_as_float(v[t].y); s1 += __uint_as_float(v[t].z); q1 += __uint_as_float(v[t].w & ~15u); }
        s0 *= (1.f / 1024); s1 *= (1.f / 1024);
        sts64(sb + OFF_MR + p * 256 + lane * 8, __float_as_uint(rsqrtf(fmaxf(q0 * (1.f / 1024) - s0 * s0, 0.f) + 1e-5f)),
              __float_as_uint(rsqrtf(fmaxf(q1 * (1.f / 1024) - s1 * s1, 0.f) + 1e-5f)));
#pragma unroll
        for (int r = 0; r < 2; r++) {
          const float v = -0.5f * (r ? s1 : s0);
          const uint32_t hh = pack2(v, v), hl = pack2(v, v - lo16(hh));
          const bool b = L & 1;
          sts128(sb + (b ? OFF_MB : OFF_MA) + p * 1024 + (lane >> 3) * 256 + r * 128 + (lane & 7) * 16, b ? 0u : hh, b ? hh << 16 : hl >> 16, b ? hl : 0u, 0u);
        }
      }
      fence_async_smem();
      __syncwarp();
      if (elect()) {
        mbar_arrive(sb + BAR_STAT);
      }
      TS(2, 0 + L * 8);
    }
    if (L < 2 && w == 0) cs_image(L);
    if (L & 1) {
      const uint32_t flip = L == 1 ? 0u : 1u;
      mbar_wait(sb + BAR_SIGT, 1);
      {
        int it = 0;
        if (PSL) __nanosleep(m < 8 ? PSL : PSL + 600);
        while (!__all_sync(0xffffffffu, (ld_flag(reinterpret_cast<const unsigned*>(&g_kvpart[j][m][w][512]) + (lane & 15) * 8) ^ flip) & 1u)) { if (PSL) __nanosleep(100); if (++it > (1 << 22)) __trap(); }
        fence_async_global();
      }
      if (w == 0) TS(4, 6 + L * 2);
      float a[8], z;
      for (int it = 0;; it++) {
        if (elect()) { mbar_expect_tx(stb + rs.s * 8, 8704); bulk_load(stg, &g_kvpart[j][m][w][0], 8704, stb + rs.s * 8); }
        mbar_wait(stb + rs.s * 8, rs.ph);
        if (w == 0) TS(4, 21 + L);
        adv<3>(rs);
#pragma unroll
        for (int u = 0; u < 8; u++) a[u] = 0.f;
        z = 0.f;
        uint32_t ok = 1u;
#pragma unroll
        for (int u = 0; u < 4; u++) { const float v = lds32f(stg + 8192 + u * 128 + (lane & 3) * 32 + (lane >> 2) * 4); z += v; ok &= __float_as_uint(v) ^ flip; }
        const uint2 tg = sum_packets(a, stg + lane * 16, 16);
        ok &= flip ? ~tg.y : tg.x;
        if (__all_sync(0xffffffffu, ok & 1u)) break;
        fence_async_smem();
        if (it > (1 << 16)) __trap();
      }
      {
        uint4* img = &g_kvfin[j][m][w * 8 + (lane >> 2)];
        uint32_t a0 = __float_as_uint(a[0]) >> 16;
        a0 += ~(a0 ^ flip) & 1u;
        st_v4(img + (lane & 3) * 16, __byte_perm(a0, pack2(0.f, a[1]), 0x7610), pack2(a[2], a[3]), pack2(a[4], a[5]), pack2(a[6], a[7]));
        const uint32_t cz = pack2(0.f, qsum(z)) | (0x3781u ^ flip);
        if (!(lane & 3)) st_v4(img + 64, cz, cz, cz, cz);
        __syncwarp();
        if (elect()) st_flag(&g_kvfflag[L >> 1][j][m >> 3][(m & 7) * 2 + w], tag);
      }
      if (w == 0) TS(4, 7 + L * 2);
    } else {
      mbar_wait(sb + BAR_SIGT, 0);
      if (w == 0) {
        if (elect()) { fence_gpu(); st_flag(&g_hflag[L >> 1][m][j][0], tag); st_flag(&g_kflag[j][m], tag); }
        if (L == 0) {
          __nanosleep(KSL);
          poll_flags(&g_kflag[j][0], 16, 0xFFFFu, tag);
          if (elect()) mbar_arrive(sb + BAR_WPHI);
        }
      } else if (m > 0) {
        poll_flags(&g_hflag[L >> 1][m - 1][j][0], 1, 1u, tag);
        if (elect()) { mbar_expect_tx(sb + BAR_HALO, 8192); bulk_load(sb + OFF_S + 8192, &g_halo[m - 1][j][0][0], 8192, sb + BAR_HALO); }
        TS(2, 2 + L * 8);
      }
    }
    if (w == 0) {
#pragma unroll 1
      for (int e = 0; e < (L < 3 ? 4 : 2); e++) {
        unsigned* flag = early(e < 2 ? &g_oflag[L][e][m][j] : &g_xflag[L + 1][e - 2][m][j]);
        mbar_wait(sb + BAR_SIGP + e * 8, L & 1);
        TS(2 + (e & 1), (e < 2 ? 3 : 6) + L * 8);
        pause((e & 1) ? XD1 : (e ? XDX : XD));
        if (elect()) { st_flag(flag, tag); fence_async_global(); }
        TS(2 + (e & 1), (e < 2 ? 4 : 7) + L * 8);
      }
    } else {
#pragma unroll 1
      for (int i = 0; i < (L < 3 ? 28 : 14); i++) {
        const bool isx = i >= 14;
        const uint32_t a = sb + OFF_A + vs * SLOT + lane * 128 + ((lane >> 4) * 4 + (lane & 3)) * 16 + (lane & 12), code = img_code(isx, L + isx);
        for (int it = 0;; it++) {
          mbar_wait(sb + BAR_LAND + vs * 8, (vph >> vs) & 1);
          vph ^= 1u << vs;
          uint32_t bad = 0;
#pragma unroll
          for (int u = 0; u < 4; u++) bad |= __float_as_uint(lds32f(a + u * 4096)) ^ code;
          if (__all_sync(0xffffffffu, !(bad & img_mask(isx)))) break;
          if (it > (1 << 16)) __trap();
          fence_async_smem();
          if (elect()) {
            mbar_expect_tx(sb + BAR_LAND + vs * 8, SLOT);
            bulk_load(sb + OFF_A + vs * SLOT, &g_img[isx ? XBUF(L + 1) : 0][m][o_order(i - 14 * isx + 2, j)][0], SLOT, sb + BAR_LAND + vs * 8);
          }
        }
        if (elect()) mbar_arrive(sb + BAR_FULLA + vs * 8);
        if (++vs == NA) vs = 0;
      }
      vs = (vs + ((L & 1) ? 16 : 32 - NJ)) % NA;
    }
  }
}

__device__ __forceinline__ void spare(const Params& P, uint32_t sb, int id) {
  const int tid = threadIdx.x & 127, w = __shfl_sync(0xffffffffu, threadIdx.x >> 7, 0), lane = tid & 31, j = 2 * id + w;
  const uint32_t ring = w * 6 * SLOT, wp = 12 * SLOT + w * 8192, bar = sb + 13 * SLOT + w * 64;
  auto part = [&](int t) { return (t >> 4) ^ w; };
  auto load = [&](int t, uint32_t sl) {
    mbar_expect_tx(bar + sl * 8, t == 0 ? SLOT + 8192 : SLOT);
    tma_load_w(sb + ring + sl * SLOT, &P.mw[1], bar + sl * 8, part(t) * 1024 + 128 * j, t & 15);
  };
  if (tid == 0) {
    if (w == 2) sts32(sb + OFF_EPOCH, atomicAdd(&g_ctr, 1u) / NCTA + 1u);
    else {
      __nanosleep(D3);
#pragma unroll 1
      for (int t = 0; t < 5; t++) {
        mbar_init(bar + t * 8, 1);
        asm volatile("fence.mbarrier_init.release.cluster;" ::: "memory");
        load(t, t);
      }
      tma_load_2d(sb + wp, &P.mwphi, bar, 0, 128 * j);
    }
  }
  __syncthreads();
  const unsigned tag = get_tag<false>(sb);
  if (w == 2) {
    int it = 0;
    while ((int)(ld_flag(&g_ctr) - tag * NCTA) < 0) { if (++it > (1 << 22)) __trap(); }
    return;
  }
  Ring r = {4, 1};
  float d[64] = {}, cs[32] = {};
  auto fold = [&]() {
    mbar_wait(bar + r.s * 8, r.ph);
    wgmma_fence();
#pragma unroll
    for (int q = 0; q < 8; q++)
      wgmma_ss_n32(reinterpret_cast<float (&)[16]>(d[16 * (q >> 1)]), desc_lo(SB + ring + r.s * SLOT, 16) + (q >> 2) * 512 + (q & 3) * 2, desc_lo(SB + wp, 512) + q * 64, q & 1);
    wgmma_commit();
  };
  const int row = (tid >> 5) * 16 + (lane >> 2);
#pragma unroll 1
  for (int t = -1; t < 32; t++) {
    uint32_t f[32];
#pragma unroll
    for (int i = 0; i < 32; i++) { f[i] = pack2(d[2 * i], d[2 * i + 1]); cs[i & 30] += d[2 * i]; cs[i | 1] += d[2 * i + 1]; }
    wg_bar(w);
    if (tid == 0 && t >= 0 && t < 27) load(t + 5, r.s);
    __syncwarp();
    if (t < 31) adv<5>(r);
    fold();
    if (part(t) == 0 && t >= 0) {
#pragma unroll
      for (int q = 0; q < 8; q++)
        g_wf[0][j][t & 15][(q >> 2) * 512 + (row + 8 * (q & 1)) * 8 + (((q & 2) * 2 + (lane & 3)) ^ (lane >> 2))] =
            make_uint4(f[4 * (q & 6) + (q & 1)], f[4 * (q & 6) + (q & 1) + 2], f[4 * (q & 6) + (q & 1) + 4], f[4 * (q & 6) + (q & 1) + 6]);
    }
    wgmma_wait<0>();
    fence_regs(d);
    if ((t & 15) == 15) {
      if (t >= 0) {
        const uint32_t red = sb + ring + 5 * SLOT;
#pragma unroll
        for (int i = 0; i < 8; i++) sts128(red + (tid >> 2) * 512 + (i >> 1) * 128 + (lane & 3) * 32 + (i & 1) * 16, __float_as_uint(cs[4 * i]), __float_as_uint(cs[4 * i + 1]), __float_as_uint(cs[4 * i + 2]), __float_as_uint(cs[4 * i + 3]));
        wg_bar(w);
        float a = 0.f;
#pragma unroll 4
        for (int i = 0; i < 32; i++) a += lds32f(red + i * 512 + tid * 4);
        g_cs[1][0][part(t) * 1024 + j * 128 + tid] = a;
        wg_bar(w);
        if (tid == 0) {
          fence_gpu();
          st_flag(&g_csflag[1][j][part(t)], tag);
        }
        __syncwarp();
      }
#pragma unroll
      for (int i = 0; i < 32; i++) cs[i] = 0.f;
    }
  }
}

__global__ void __launch_bounds__(NTHREADS, 1) fused_kernel(const __grid_constant__ Params P) {
  extern __shared__ __align__(1024) uint8_t smem_raw[];
  constexpr uint32_t sb = SB;
  const int tid = threadIdx.x;
  const unsigned vb = vblock();
  if (vb >= 128) { spare(P, sb, vb - 128); return; }
  const int warp = __shfl_sync(0xffffffffu, tid >> 5, 0);
  if (elect()) {
    if (warp == 11) { prefetch_map(&P.mx); prefetch_map(&P.mw[0]); if (smem_u32(smem_raw) != SB) __trap(); }
    if (warp < 8) {
#pragma unroll
      for (int i = 0; i < 8; i++) mbar_init(sb + OFF_BAR + (warp * 8 + i) * 8, warp == 2 || warp == 3 ? 2 : (warp == 4 ? 8 : 1));
    }
    asm volatile("fence.mbarrier_init.release.cluster;" ::: "memory");
    if (warp < 2) {
      const int j = cta_j(vb);
#pragma unroll 1
      for (int i = 0; i < (warp == 0 ? PRE_B : PRE_A); i++) {
        const uint32_t bar = sb + BAR_FULLB + warp * 64 + i * 8;
        mbar_expect_tx(bar, SLOT);
        if (warp == 0) tma_load_w(sb + OFF_B + i * SLOT, &P.mw[0], bar, 1024 + (i & 1) * 1024 + 128 * j, kv_order(i >> 1, j, 0));
        else tma_load_3d(sb + OFF_A + i * SLOT, &P.mx, bar, kv_order(i, j, 0) * 64, cta_m(vb) * 64, 0);
      }
    }
  }
  if (tid == 0) TS(6, 0);
  __syncthreads();
  if (tid == 0) TS(6, 2);
  if (warp < 4) {
    reg_dealloc<PREGS>();
    if (warp & 2) helper(P, sb, warp & 1, vb);
    else if (warp & 1) a_loader(P, sb, vb);
    else b_producer(P, sb, vb);
  } else {
    reg_alloc<CREGS>();
    consumer(P, sb, (warp >> 2) - 1, vb);
  }
}

typedef CUresult (*EncodeFn)(CUtensorMap*, CUtensorMapDataType, cuuint32_t, void*, const cuuint64_t*, const cuuint64_t*,
                             const cuuint32_t*, const cuuint32_t*, CUtensorMapInterleave, CUtensorMapSwizzle,
                             CUtensorMapL2promotion, CUtensorMapFloatOOBfill);

void encode(EncodeFn fn, CUtensorMap* m, const void* ptr, int rank, const cuuint64_t* dims, const cuuint64_t* strides,
            const cuuint32_t* box, CUtensorMapSwizzle swz) {
  const cuuint32_t es[5] = {1, 1, 1, 1, 1};
  fn(m, CU_TENSOR_MAP_DATA_TYPE_BFLOAT16, rank, const_cast<void*>(ptr), dims, strides, box, es, CU_TENSOR_MAP_INTERLEAVE_NONE,
     swz, CU_TENSOR_MAP_L2_PROMOTION_L2_256B, CU_TENSOR_MAP_FLOAT_OOB_FILL_NONE);
}
void encode_w(EncodeFn fn, CUtensorMap* m, const void* ptr, int ncols, bool perm) {
  const cuuint64_t p = (cuuint64_t)ncols * 2, d[5] = {(cuuint64_t)ncols, 2, 4, 4, 32}, s[4] = {p, (perm ? 8 : 2) * p, (perm ? 2 : 8) * p, 32 * p};
  const cuuint32_t box[5] = {64, 2, 4, 4, 2};
  encode(fn, m, ptr, 5, d, s, box, CU_TENSOR_MAP_SWIZZLE_128B);
}

void encode_cs(EncodeFn fn, CUtensorMap* m, const void* ptr, int ncols) {
  const cuuint64_t d[2] = {(cuuint64_t)ncols, 1024}, s[1] = {(cuuint64_t)ncols * 2};
  const cuuint32_t box[2] = {32, 64};
  encode(fn, m, ptr, 2, d, s, box, CU_TENSOR_MAP_SWIZZLE_NONE);
}

}

extern "C" void kernel_launch(void* const* d_in, const int* in_sizes, int n_in, void* d_out, int out_size) {
  (void)in_sizes; (void)n_in; (void)out_size;
  void* fnp = nullptr;
  cudaDriverEntryPointQueryResult q;
  cudaGetDriverEntryPoint("cuTensorMapEncodeTiled", &fnp, cudaEnableDefault, &q);
  EncodeFn fn = (EncodeFn)fnp;
  Params P;
  {
    const cuuint64_t dims[3] = {1024, 1024, 2}, strides[2] = {4096, 2048};
    const cuuint32_t box[3] = {64, 64, 2};
    encode(fn, &P.mx, d_in[0], 3, dims, strides, box, CU_TENSOR_MAP_SWIZZLE_128B);
  }
  P.out = (uint4*)d_out;
  encode_w(fn, &P.mw[0], d_in[1], 3072, false);
  encode_w(fn, &P.mw[1], d_in[4], 3072, true);
  encode_w(fn, &P.mw[2], d_in[1], 3072, true);
  encode_w(fn, &P.mwo[0], d_in[2], 1024, true);
  encode_w(fn, &P.mwo[1], d_in[6], 1024, false);
  encode_cs(fn, &P.mcs[0], d_in[1], 3072);
  encode_cs(fn, &P.mcs[1], d_in[4], 3072);
  {
    const cuuint64_t dims[2] = {32, 1024}, strides[1] = {64};
    const cuuint32_t box[2] = {32, 128};
    encode(fn, &P.mwphi, d_in[5], 2, dims, strides, box, CU_TENSOR_MAP_SWIZZLE_64B);
  }
  cudaFuncSetAttribute(fused_kernel, cudaFuncAttributeMaxDynamicSharedMemorySize, SMEM_BYTES);
  fused_kernel<<<NCTA, NTHREADS, SMEM_BYTES, cudaStreamPerThread>>>(P);
}
```

```cpp
#include <cuda_runtime.h>
#include <cuda_bf16.h>
#include <cuda.h>
#include <stdint.h>

namespace {

__device__ __forceinline__ void wgmma_ss_n256(float (&d)[128], uint32_t da, uint32_t ha, uint32_t db, int sd) {
  asm volatile("{\n.reg .pred p;\n.reg .b64 a, b;\nsetp.ne.b32 p, %130, 0;\nmov.b64 a, {%128, %131};\nmov.b64 b, {%129, 0x40000040};\n"
    "wgmma.mma_async.sync.aligned.m64n256k16.f32.bf16.bf16 {%0,%1,%2,%3,%4,%5,%6,%7,%8,%9,%10,%11,%12,%13,%14,%15,%16,%17,%18,%19,%20,%21,%22,%23,%24,%25,%26,%27,%28,%29,%30,%31,%32,%33,%34,%35,%36,%37,%38,%39,%40,%41,%42,%43,%44,%45,%46,%47,%48,%49,%50,%51,%52,%53,%54,%55,%56,%57,%58,%59,%60,%61,%62,%63,%64,%65,%66,%67,%68,%69,%70,%71,%72,%73,%74,%75,%76,%77,%78,%79,%80,%81,%82,%83,%84,%85,%86,%87,%88,%89,%90,%91,%92,%93,%94,%95,%96,%97,%98,%99,%100,%101,%102,%103,%104,%105,%106,%107,%108,%109,%110,%111,%112,%113,%114,%115,%116,%117,%118,%119,%120,%121,%122,%123,%124,%125,%126,%127}, a, b, p, 1, 1, 0, 1;\n}\n"
    : "+f"(d[0]),"+f"(d[1]),"+f"(d[2]),"+f"(d[3]),"+f"(d[4]),"+f"(d[5]),"+f"(d[6]),"+f"(d[7]),"+f"(d[8]),"+f"(d[9]),"+f"(d[10]),"+f"(d[11]),"+f"(d[12]),"+f"(d[13]),"+f"(d[14]),"+f"(d[15]),"+f"(d[16]),"+f"(d[17]),"+f"(d[18]),"+f"(d[19]),"+f"(d[20]),"+f"(d[21]),"+f"(d[22]),"+f"(d[23]),"+f"(d[24]),"+f"(d[25]),"+f"(d[26]),"+f"(d[27]),"+f"(d[28]),"+f"(d[29]),"+f"(d[30]),"+f"(d[31]),"+f"(d[32]),"+f"(d[33]),"+f"(d[34]),"+f"(d[35]),"+f"(d[36]),"+f"(d[37]),"+f"(d[38]),"+f"(d[39]),"+f"(d[40]),"+f"(d[41]),"+f"(d[42]),"+f"(d[43]),"+f"(d[44]),"+f"(d[45]),"+f"(d[46]),"+f"(d[47]),"+f"(d[48]),"+f"(d[49]),"+f"(d[50]),"+f"(d[51]),"+f"(d[52]),"+f"(d[53]),"+f"(d[54]),"+f"(d[55]),"+f"(d[56]),"+f"(d[57]),"+f"(d[58]),"+f"(d[59]),"+f"(d[60]),"+f"(d[61]),"+f"(d[62]),"+f"(d[63]),"+f"(d[64]),"+f"(d[65]),"+f"(d[66]),"+f"(d[67]),"+f"(d[68]),"+f"(d[69]),"+f"(d[70]),"+f"(d[71]),"+f"(d[72]),"+f"(d[73]),"+f"(d[74]),"+f"(d[75]),"+f"(d[76]),"+f"(d[77]),"+f"(d[78]),"+f"(d[79]),"+f"(d[80]),"+f"(d[81]),"+f"(d[82]),"+f"(d[83]),"+f"(d[84]),"+f"(d[85]),"+f"(d[86]),"+f"(d[87]),"+f"(d[88]),"+f"(d[89]),"+f"(d[90]),"+f"(d[91]),"+f"(d[92]),"+f"(d[93]),"+f"(d[94]),"+f"(d[95]),"+f"(d[96]),"+f"(d[97]),"+f"(d[98]),"+f"(d[99]),"+f"(d[100]),"+f"(d[101]),"+f"(d[102]),"+f"(d[103]),"+f"(d[104]),"+f"(d[105]),"+f"(d[106]),"+f"(d[107]),"+f"(d[108]),"+f"(d[109]),"+f"(d[110]),"+f"(d[111]),"+f"(d[112]),"+f"(d[113]),"+f"(d[114]),"+f"(d[115]),"+f"(d[116]),"+f"(d[117]),"+f"(d[118]),"+f"(d[119]),"+f"(d[120]),"+f"(d[121]),"+f"(d[122]),"+f"(d[123]),"+f"(d[124]),"+f"(d[125]),"+f"(d[126]),"+f"(d[127])
    : "r"(da), "r"(db), "r"(sd), "r"(ha));
}
__device__ __forceinline__ void wgmma_ss_n128(float (&d)[64], uint32_t da, uint32_t ha, uint32_t db, int sd) {
  asm volatile("{\n.reg .pred p;\n.reg .b64 a, b;\nsetp.ne.b32 p, %66, 0;\nmov.b64 a, {%64, %67};\nmov.b64 b, {%65, 0x40000040};\n"
    "wgmma.mma_async.sync.aligned.m64n128k16.f32.bf16.bf16 {%0,%1,%2,%3,%4,%5,%6,%7,%8,%9,%10,%11,%12,%13,%14,%15,%16,%17,%18,%19,%20,%21,%22,%23,%24,%25,%26,%27,%28,%29,%30,%31,%32,%33,%34,%35,%36,%37,%38,%39,%40,%41,%42,%43,%44,%45,%46,%47,%48,%49,%50,%51,%52,%53,%54,%55,%56,%57,%58,%59,%60,%61,%62,%63}, a, b, p, 1, 1, 0, 1;\n}\n"
    : "+f"(d[0]),"+f"(d[1]),"+f"(d[2]),"+f"(d[3]),"+f"(d[4]),"+f"(d[5]),"+f"(d[6]),"+f"(d[7]),"+f"(d[8]),"+f"(d[9]),"+f"(d[10]),"+f"(d[11]),"+f"(d[12]),"+f"(d[13]),"+f"(d[14]),"+f"(d[15]),"+f"(d[16]),"+f"(d[17]),"+f"(d[18]),"+f"(d[19]),"+f"(d[20]),"+f"(d[21]),"+f"(d[22]),"+f"(d[23]),"+f"(d[24]),"+f"(d[25]),"+f"(d[26]),"+f"(d[27]),"+f"(d[28]),"+f"(d[29]),"+f"(d[30]),"+f"(d[31]),"+f"(d[32]),"+f"(d[33]),"+f"(d[34]),"+f"(d[35]),"+f"(d[36]),"+f"(d[37]),"+f"(d[38]),"+f"(d[39]),"+f"(d[40]),"+f"(d[41]),"+f"(d[42]),"+f"(d[43]),"+f"(d[44]),"+f"(d[45]),"+f"(d[46]),"+f"(d[47]),"+f"(d[48]),"+f"(d[49]),"+f"(d[50]),"+f"(d[51]),"+f"(d[52]),"+f"(d[53]),"+f"(d[54]),"+f"(d[55]),"+f"(d[56]),"+f"(d[57]),"+f"(d[58]),"+f"(d[59]),"+f"(d[60]),"+f"(d[61]),"+f"(d[62]),"+f"(d[63])
    : "r"(da), "r"(db), "r"(sd), "r"(ha));
}
__device__ __forceinline__ void wgmma_ss_n40_tt(float (&d)[20], uint32_t da, uint32_t db, int sd) {
  asm volatile("{\n.reg .pred p;\n.reg .b64 a, b;\nsetp.ne.b32 p, %22, 0;\nmov.b64 a, {%20, 0x40000040};\nmov.b64 b, {%21, 0x8};\n"
    "wgmma.mma_async.sync.aligned.m64n40k16.f32.bf16.bf16 {%0,%1,%2,%3,%4,%5,%6,%7,%8,%9,%10,%11,%12,%13,%14,%15,%16,%17,%18,%19}, a, b, p, 1, 1, 1, 1;\n}\n"
    : "+f"(d[0]),"+f"(d[1]),"+f"(d[2]),"+f"(d[3]),"+f"(d[4]),"+f"(d[5]),"+f"(d[6]),"+f"(d[7]),"+f"(d[8]),"+f"(d[9]),"+f"(d[10]),"+f"(d[11]),"+f"(d[12]),"+f"(d[13]),"+f"(d[14]),"+f"(d[15]),"+f"(d[16]),"+f"(d[17]),"+f"(d[18]),"+f"(d[19])
    : "r"(da), "r"(db), "r"(sd));
}
__device__ __forceinline__ void wgmma_ss_n32(float (&d)[16], uint32_t da, uint32_t db, int sd) {
  asm volatile("{\n.reg .pred p;\n.reg .b64 a, b;\nsetp.ne.b32 p, %18, 0;\nmov.b64 a, {%16, 0x40000040};\nmov.b64 b, {%17, 0x80000020};\n"
    "wgmma.mma_async.sync.aligned.m64n32k16.f32.bf16.bf16 {%0,%1,%2,%3,%4,%5,%6,%7,%8,%9,%10,%11,%12,%13,%14,%15}, a, b, p, 1, 1, 0, 1;\n}\n"
    : "+f"(d[0]),"+f"(d[1]),"+f"(d[2]),"+f"(d[3]),"+f"(d[4]),"+f"(d[5]),"+f"(d[6]),"+f"(d[7]),"+f"(d[8]),"+f"(d[9]),"+f"(d[10]),"+f"(d[11]),"+f"(d[12]),"+f"(d[13]),"+f"(d[14]),"+f"(d[15])
    : "r"(da), "r"(db), "r"(sd));
}
__device__ __forceinline__ void wgmma_rs_n40(float (&d)[20], uint32_t a0, uint32_t a1, uint32_t a2, uint32_t a3, uint32_t db, int sd) {
  asm volatile("{\n.reg .pred p;\n.reg .b64 b;\nsetp.ne.b32 p, %25, 0;\nmov.b64 b, {%24, 0x10};\n"
    "wgmma.mma_async.sync.aligned.m64n40k16.f32.bf16.bf16 {%0,%1,%2,%3,%4,%5,%6,%7,%8,%9,%10,%11,%12,%13,%14,%15,%16,%17,%18,%19}, {%20,%21,%22,%23}, b, p, 1, 1, 1;\n}\n"
    : "+f"(d[0]),"+f"(d[1]),"+f"(d[2]),"+f"(d[3]),"+f"(d[4]),"+f"(d[5]),"+f"(d[6]),"+f"(d[7]),"+f"(d[8]),"+f"(d[9]),"+f"(d[10]),"+f"(d[11]),"+f"(d[12]),"+f"(d[13]),"+f"(d[14]),"+f"(d[15]),"+f"(d[16]),"+f"(d[17]),"+f"(d[18]),"+f"(d[19])
    : "r"(a0), "r"(a1), "r"(a2), "r"(a3), "r"(db), "r"(sd));
}
__device__ __forceinline__ void wgmma_r1_n256(float (&d)[128], uint32_t da, uint32_t db, int sd) {
  asm volatile("{\n.reg .pred p;\n.reg .b64 a, b;\nsetp.ne.b32 p, %130, 0;\nmov.b64 a, {%128, 0x8};\nmov.b64 b, {%129, 0x6};\n"
    "wgmma.mma_async.sync.aligned.m64n256k16.f32.bf16.bf16 {%0,%1,%2,%3,%4,%5,%6,%7,%8,%9,%10,%11,%12,%13,%14,%15,%16,%17,%18,%19,%20,%21,%22,%23,%24,%25,%26,%27,%28,%29,%30,%31,%32,%33,%34,%35,%36,%37,%38,%39,%40,%41,%42,%43,%44,%45,%46,%47,%48,%49,%50,%51,%52,%53,%54,%55,%56,%57,%58,%59,%60,%61,%62,%63,%64,%65,%66,%67,%68,%69,%70,%71,%72,%73,%74,%75,%76,%77,%78,%79,%80,%81,%82,%83,%84,%85,%86,%87,%88,%89,%90,%91,%92,%93,%94,%95,%96,%97,%98,%99,%100,%101,%102,%103,%104,%105,%106,%107,%108,%109,%110,%111,%112,%113,%114,%115,%116,%117,%118,%119,%120,%121,%122,%123,%124,%125,%126,%127}, a, b, p, 1, 1, 0, 1;\n}\n"
    : "+f"(d[0]),"+f"(d[1]),"+f"(d[2]),"+f"(d[3]),"+f"(d[4]),"+f"(d[5]),"+f"(d[6]),"+f"(d[7]),"+f"(d[8]),"+f"(d[9]),"+f"(d[10]),"+f"(d[11]),"+f"(d[12]),"+f"(d[13]),"+f"(d[14]),"+f"(d[15]),"+f"(d[16]),"+f"(d[17]),"+f"(d[18]),"+f"(d[19]),"+f"(d[20]),"+f"(d[21]),"+f"(d[22]),"+f"(d[23]),"+f"(d[24]),"+f"(d[25]),"+f"(d[26]),"+f"(d[27]),"+f"(d[28]),"+f"(d[29]),"+f"(d[30]),"+f"(d[31]),"+f"(d[32]),"+f"(d[33]),"+f"(d[34]),"+f"(d[35]),"+f"(d[36]),"+f"(d[37]),"+f"(d[38]),"+f"(d[39]),"+f"(d[40]),"+f"(d[41]),"+f"(d[42]),"+f"(d[43]),"+f"(d[44]),"+f"(d[45]),"+f"(d[46]),"+f"(d[47]),"+f"(d[48]),"+f"(d[49]),"+f"(d[50]),"+f"(d[51]),"+f"(d[52]),"+f"(d[53]),"+f"(d[54]),"+f"(d[55]),"+f"(d[56]),"+f"(d[57]),"+f"(d[58]),"+f"(d[59]),"+f"(d[60]),"+f"(d[61]),"+f"(d[62]),"+f"(d[63]),"+f"(d[64]),"+f"(d[65]),"+f"(d[66]),"+f"(d[67]),"+f"(d[68]),"+f"(d[69]),"+f"(d[70]),"+f"(d[71]),"+f"(d[72]),"+f"(d[73]),"+f"(d[74]),"+f"(d[75]),"+f"(d[76]),"+f"(d[77]),"+f"(d[78]),"+f"(d[79]),"+f"(d[80]),"+f"(d[81]),"+f"(d[82]),"+f"(d[83]),"+f"(d[84]),"+f"(d[85]),"+f"(d[86]),"+f"(d[87]),"+f"(d[88]),"+f"(d[89]),"+f"(d[90]),"+f"(d[91]),"+f"(d[92]),"+f"(d[93]),"+f"(d[94]),"+f"(d[95]),"+f"(d[96]),"+f"(d[97]),"+f"(d[98]),"+f"(d[99]),"+f"(d[100]),"+f"(d[101]),"+f"(d[102]),"+f"(d[103]),"+f"(d[104]),"+f"(d[105]),"+f"(d[106]),"+f"(d[107]),"+f"(d[108]),"+f"(d[109]),"+f"(d[110]),"+f"(d[111]),"+f"(d[112]),"+f"(d[113]),"+f"(d[114]),"+f"(d[115]),"+f"(d[116]),"+f"(d[117]),"+f"(d[118]),"+f"(d[119]),"+f"(d[120]),"+f"(d[121]),"+f"(d[122]),"+f"(d[123]),"+f"(d[124]),"+f"(d[125]),"+f"(d[126]),"+f"(d[127])
    : "r"(da), "r"(db), "r"(sd));
}
__device__ __forceinline__ void wgmma_r1_n128(float (&d)[64], uint32_t da, uint32_t db, int sd) {
  asm volatile("{\n.reg .pred p;\n.reg .b64 a, b;\nsetp.ne.b32 p, %66, 0;\nmov.b64 a, {%64, 0x8};\nmov.b64 b, {%65, 0x6};\n"
    "wgmma.mma_async.sync.aligned.m64n128k16.f32.bf16.bf16 {%0,%1,%2,%3,%4,%5,%6,%7,%8,%9,%10,%11,%12,%13,%14,%15,%16,%17,%18,%19,%20,%21,%22,%23,%24,%25,%26,%27,%28,%29,%30,%31,%32,%33,%34,%35,%36,%37,%38,%39,%40,%41,%42,%43,%44,%45,%46,%47,%48,%49,%50,%51,%52,%53,%54,%55,%56,%57,%58,%59,%60,%61,%62,%63}, a, b, p, 1, 1, 0, 1;\n}\n"
    : "+f"(d[0]),"+f"(d[1]),"+f"(d[2]),"+f"(d[3]),"+f"(d[4]),"+f"(d[5]),"+f"(d[6]),"+f"(d[7]),"+f"(d[8]),"+f"(d[9]),"+f"(d[10]),"+f"(d[11]),"+f"(d[12]),"+f"(d[13]),"+f"(d[14]),"+f"(d[15]),"+f"(d[16]),"+f"(d[17]),"+f"(d[18]),"+f"(d[19]),"+f"(d[20]),"+f"(d[21]),"+f"(d[22]),"+f"(d[23]),"+f"(d[24]),"+f"(d[25]),"+f"(d[26]),"+f"(d[27]),"+f"(d[28]),"+f"(d[29]),"+f"(d[30]),"+f"(d[31]),"+f"(d[32]),"+f"(d[33]),"+f"(d[34]),"+f"(d[35]),"+f"(d[36]),"+f"(d[37]),"+f"(d[38]),"+f"(d[39]),"+f"(d[40]),"+f"(d[41]),"+f"(d[42]),"+f"(d[43]),"+f"(d[44]),"+f"(d[45]),"+f"(d[46]),"+f"(d[47]),"+f"(d[48]),"+f"(d[49]),"+f"(d[50]),"+f"(d[51]),"+f"(d[52]),"+f"(d[53]),"+f"(d[54]),"+f"(d[55]),"+f"(d[56]),"+f"(d[57]),"+f"(d[58]),"+f"(d[59]),"+f"(d[60]),"+f"(d[61]),"+f"(d[62]),"+f"(d[63])
    : "r"(da), "r"(db), "r"(sd));
}

__device__ __forceinline__ uint32_t smem_u32(const void* p) { return (uint32_t)__cvta_generic_to_shared(p); }
__device__ __forceinline__ void mbar_init(uint32_t bar, uint32_t cnt) { asm volatile("mbarrier.init.shared::cta.b64 [%0], %1;" ::"r"(bar), "r"(cnt)); }
__device__ __forceinline__ void mbar_expect_tx(uint32_t bar, uint32_t bytes) { asm volatile("mbarrier.arrive.expect_tx.shared::cta.b64 _, [%0], %1;" ::"r"(bar), "r"(bytes) : "memory"); }
__device__ __forceinline__ void mbar_arrive(uint32_t bar) { asm volatile("mbarrier.arrive.shared::cta.b64 _, [%0];" ::"r"(bar) : "memory"); }
__device__ __forceinline__ void mbar_arrive_n(uint32_t bar, uint32_t n) { asm volatile("mbarrier.arrive.shared::cta.b64 _, [%0], %1;" ::"r"(bar), "r"(n) : "memory"); }
__device__ __forceinline__ void mbar_wait(uint32_t bar, uint32_t parity) {
  asm volatile("{\n.reg .pred p;\nLAB_WAIT:\nmbarrier.try_wait.parity.shared::cta.b64 p, [%0], %1;\n@p bra DONE;\nbra LAB_WAIT;\nDONE:\n}" ::"r"(bar), "r"(parity) : "memory");
}
__device__ __forceinline__ void mbar_wait2(uint32_t a, uint32_t pa, uint32_t b, uint32_t pb) {
  asm volatile("{\n.reg .pred p, q;\nLAB_WAIT:\nmbarrier.try_wait.parity.shared::cta.b64 p, [%0], %1;\nmbarrier.try_wait.parity.shared::cta.b64 q, [%2], %3;\n"
               "and.pred p, p, q;\n@p bra DONE;\nbra LAB_WAIT;\nDONE:\n}" ::"r"(a), "r"(pa), "r"(b), "r"(pb) : "memory");
}
__device__ __forceinline__ void mbar_wait3(uint32_t a, uint32_t pa, uint32_t b, uint32_t pb) {
  asm volatile("{\n.reg .pred p, q, r;\nLAB_WAIT:\nmbarrier.try_wait.parity.shared::cta.b64 p, [%0], %1;\nmbarrier.try_wait.parity.shared::cta.b64 q, [%2], %3;\n"
               "mbarrier.try_wait.parity.shared::cta.b64 r, [%2+8], %3;\nand.pred p, p, q;\nand.pred p, p, r;\n@p bra DONE;\nbra LAB_WAIT;\nDONE:\n}" ::"r"(a), "r"(pa), "r"(b), "r"(pb) : "memory");
}
__device__ __forceinline__ bool mbar_probe2(uint32_t a, uint32_t pa, uint32_t b, uint32_t pb) {
  uint32_t ok;
  asm volatile("{\n.reg .pred p, q;\nmbarrier.test_wait.parity.shared::cta.b64 p, [%1], %2;\nmbarrier.test_wait.parity.shared::cta.b64 q, [%3], %4;\n"
               "and.pred p, p, q;\nselp.u32 %0, 1, 0, p;\n}" : "=r"(ok) : "r"(a), "r"(pa), "r"(b), "r"(pb) : "memory");
  return ok != 0;
}
__device__ __forceinline__ void tma_load_3d(uint32_t dst, const CUtensorMap* tm, uint32_t bar, int c0, int c1, int c2) {
  asm volatile("cp.async.bulk.tensor.3d.shared::cluster.global.mbarrier::complete_tx::bytes [%0], [%1, {%3, %4, %5}], [%2];"
               ::"r"(dst), "l"(tm), "r"(bar), "r"(c0), "r"(c1), "r"(c2) : "memory");
}
__device__ __forceinline__ void tma_load_2d(uint32_t dst, const CUtensorMap* tm, uint32_t bar, int c0, int c1) {
  asm volatile("cp.async.bulk.tensor.2d.shared::cluster.global.mbarrier::complete_tx::bytes [%0], [%1, {%3, %4}], [%2];"
               ::"r"(dst), "l"(tm), "r"(bar), "r"(c0), "r"(c1) : "memory");
}
__device__ __forceinline__ void tma_load_w(uint32_t dst, const CUtensorMap* tm, uint32_t bar, int col, int kb) {
#pragma unroll
  for (int q = 0; q < 2; q++)
    asm volatile("cp.async.bulk.tensor.5d.shared::cluster.global.mbarrier::complete_tx::bytes [%0], [%1, {%3, %4, %4, %4, %5}], [%2];"
                 ::"r"(dst + q * 8192), "l"(tm), "r"(bar), "r"(col + q * 64), "r"(0), "r"(2 * kb) : "memory");
}
__device__ __forceinline__ void tma_prefetch_w(const CUtensorMap* tm, int col, int kb) {
#pragma unroll
  for (int q = 0; q < 2; q++)
    asm volatile("cp.async.bulk.prefetch.tensor.5d.L2.global [%0, {%1, %2, %2, %2, %3}];" ::"l"(tm), "r"(col + q * 64), "r"(0), "r"(2 * kb) : "memory");
}
__device__ __forceinline__ void bulk_load(uint32_t dst, const void* g, uint32_t bytes, uint32_t bar) {
  asm volatile("cp.async.bulk.shared::cluster.global.mbarrier::complete_tx::bytes [%0], [%1], %2, [%3];" ::"r"(dst), "l"(g), "r"(bytes), "r"(bar) : "memory");
}
__device__ __forceinline__ void prefetch_map(const CUtensorMap* tm) { asm volatile("prefetch.tensormap [%0];" ::"l"(tm) : "memory"); }
__device__ __forceinline__ void fence_async_smem() { asm volatile("fence.proxy.async.shared::cta;" ::: "memory"); }
__device__ __forceinline__ void fence_async_global() { asm volatile("fence.proxy.async.global;" ::: "memory"); }
__device__ __forceinline__ void fence_gpu() { asm volatile("fence.release.gpu;" ::: "memory"); }
__device__ __forceinline__ void st_flag(unsigned* p, unsigned v) { asm volatile("st.relaxed.gpu.global.u32 [%0], %1;" ::"l"(p), "r"(v) : "memory"); }
__device__ __forceinline__ unsigned ld_flag(const unsigned* p) { unsigned v; asm volatile("ld.relaxed.gpu.global.u32 %0, [%1];" : "=r"(v) : "l"(p) : "memory"); return v; }
__device__ __forceinline__ uint4 ldcg4(const void* p) { uint4 v; asm volatile("ld.global.cg.v4.u32 {%0,%1,%2,%3}, [%4];" : "=r"(v.x), "=r"(v.y), "=r"(v.z), "=r"(v.w) : "l"(p)); return v; }
__device__ __forceinline__ uint4 ld_pkt(const uint4* p) {
  uint4 v; asm volatile("{\n.reg .b128 t;\nld.relaxed.gpu.global.b128 t, [%4];\nmov.b128 {%0,%1,%2,%3}, t;\n}" : "=r"(v.x), "=r"(v.y), "=r"(v.z), "=r"(v.w) : "l"(p) : "memory"); return v;
}
__device__ __forceinline__ void st_pkt(uint4* p, uint32_t a, uint32_t b, uint32_t c, uint32_t tag) {
  asm volatile("{\n.reg .b128 t;\nmov.b128 t, {%1,%2,%3,%4};\nst.relaxed.gpu.global.b128 [%0], t;\n}" ::"l"(p), "r"(a), "r"(b), "r"(c), "r"(tag) : "memory");
}
__device__ __forceinline__ void st_v4(uint4* p, uint32_t a, uint32_t b, uint32_t c, uint32_t d) { asm volatile("st.relaxed.gpu.global.v4.u32 [%0], {%1,%2,%3,%4};" ::"l"(p), "r"(a), "r"(b), "r"(c), "r"(d) : "memory"); }
__device__ __forceinline__ void stg128(uint4* p, uint4 v) { asm volatile("st.global.v4.u32 [%0], {%1,%2,%3,%4};" ::"l"(p), "r"(v.x), "r"(v.y), "r"(v.z), "r"(v.w) : "memory"); }
__device__ __forceinline__ void sts32(uint32_t addr, uint32_t a) { asm volatile("st.shared.u32 [%0], %1;" ::"r"(addr), "r"(a) : "memory"); }
__device__ __forceinline__ void sts64(uint32_t addr, uint32_t a, uint32_t b) { asm volatile("st.shared.v2.u32 [%0], {%1,%2};" ::"r"(addr), "r"(a), "r"(b) : "memory"); }
__device__ __forceinline__ uint32_t mul2(uint32_t a, uint32_t b) { uint32_t r; asm("mul.rn.bf16x2 %0, %1, %2;" : "=r"(r) : "r"(a), "r"(b)); return r; }
__device__ __forceinline__ uint32_t add2(uint32_t a, uint32_t b) { uint32_t r; asm("add.rn.bf16x2 %0, %1, %2;" : "=r"(r) : "r"(a), "r"(b)); return r; }
__device__ __forceinline__ bool elect() {
  uint32_t p; asm volatile("{\n.reg .pred q;\nelect.sync _|q, 0xffffffff;\nselp.u32 %0, 1, 0, q;\n}" : "=r"(p)); return p != 0;
}
__device__ __forceinline__ void wgmma_fence() { asm volatile("wgmma.fence.sync.aligned;" ::: "memory"); }
__device__ __forceinline__ void wgmma_commit() { asm volatile("wgmma.commit_group.sync.aligned;" ::: "memory"); }
template <int N> __device__ __forceinline__ void wgmma_wait() { asm volatile("wgmma.wait_group.sync.aligned %0;" ::"n"(N) : "memory"); }
template <int N> __device__ __forceinline__ void fence_regs(float (&d)[N]) {
#pragma unroll
  for (int i = 0; i < N; i++) asm volatile("" : "+f"(d[i])::"memory");
}
template <int R> __device__ __forceinline__ void reg_alloc() { asm volatile("setmaxnreg.inc.sync.aligned.u32 %0;" ::"n"(R)); }
template <int R> __device__ __forceinline__ void reg_dealloc() { asm volatile("setmaxnreg.dec.sync.aligned.u32 %0;" ::"n"(R)); }
__device__ __forceinline__ void wg_bar(int w) { asm volatile("bar.sync %0, 128;" ::"r"(w + 1) : "memory"); }
__device__ __forceinline__ constexpr uint32_t desc_lo(uint32_t addr, uint32_t lbo) { return (addr >> 4) + ((lbo >> 4) << 16); }
__device__ __forceinline__ uint32_t pack2(float lo, float hi) { uint32_t r; asm("cvt.rn.bf16x2.f32 %0, %1, %2;" : "=r"(r) : "f"(hi), "f"(lo)); return r; }
__device__ __forceinline__ float lo16(uint32_t v) { return __uint_as_float(v << 16); }
__device__ __forceinline__ float hi16(uint32_t v) { return __uint_as_float(v & 0xFFFF0000u); }
__device__ __forceinline__ float ex2(float x) { float r; asm("ex2.approx.ftz.f32 %0, %1;" : "=f"(r) : "f"(x)); return r; }
__device__ __forceinline__ float rcp(float x) { float r; asm("rcp.approx.ftz.f32 %0, %1;" : "=f"(r) : "f"(x)); return r; }
__device__ __forceinline__ uint32_t movm(uint32_t a) { uint32_t d; asm volatile("movmatrix.sync.aligned.m8n8.trans.b16 %0, %1;" : "=r"(d) : "r"(a)); return d; }
__device__ __forceinline__ void stsm4(uint32_t addr, uint32_t a, uint32_t b, uint32_t c, uint32_t d) {
  asm volatile("stmatrix.sync.aligned.m8n8.x4.shared.b16 [%0], {%1,%2,%3,%4};" ::"r"(addr), "r"(a), "r"(b), "r"(c), "r"(d) : "memory");
}
__device__ __forceinline__ void ldsm4(uint32_t addr, uint32_t (&r)[4]) {
  asm volatile("ldmatrix.sync.aligned.m8n8.x4.shared.b16 {%0,%1,%2,%3}, [%4];" : "=r"(r[0]), "=r"(r[1]), "=r"(r[2]), "=r"(r[3]) : "r"(addr) : "memory");
}
__device__ __forceinline__ void sts128(uint32_t addr, uint32_t a, uint32_t b, uint32_t c, uint32_t d) {
  asm volatile("st.shared.v4.u32 [%0], {%1,%2,%3,%4};" ::"r"(addr), "r"(a), "r"(b), "r"(c), "r"(d) : "memory");
}
__device__ __forceinline__ void lds128(uint32_t addr, uint32_t& a, uint32_t& b, uint32_t& c, uint32_t& d) {
  asm volatile("ld.shared.v4.u32 {%0,%1,%2,%3}, [%4];" : "=r"(a), "=r"(b), "=r"(c), "=r"(d) : "r"(addr) : "memory");
}
__device__ __forceinline__ float lds32f(uint32_t addr) { float v; asm volatile("ld.shared.f32 %0, [%1];" : "=f"(v) : "r"(addr) : "memory"); return v; }
__device__ __forceinline__ float2 lds64f(uint32_t addr) { float2 v; asm volatile("ld.shared.v2.f32 {%0,%1}, [%2];" : "=f"(v.x), "=f"(v.y) : "r"(addr) : "memory"); return v; }
__device__ __forceinline__ void mma16816(float (&d)[4], uint32_t a0, uint32_t a1, uint32_t a2, uint32_t a3, uint32_t b0, uint32_t b1) {
  asm("mma.sync.aligned.m16n8k16.row.col.f32.bf16.bf16.f32 {%0,%1,%2,%3}, {%4,%5,%6,%7}, {%8,%9}, {%0,%1,%2,%3};"
      : "+f"(d[0]), "+f"(d[1]), "+f"(d[2]), "+f"(d[3]) : "r"(a0), "r"(a1), "r"(a2), "r"(a3), "r"(b0), "r"(b1));
}
__device__ __forceinline__ void mma1688(float (&d)[4], uint32_t a0, uint32_t a1, uint32_t b0) {
  asm("mma.sync.aligned.m16n8k8.row.col.f32.bf16.bf16.f32 {%0,%1,%2,%3}, {%4,%5}, {%6}, {%0,%1,%2,%3};"
      : "+f"(d[0]), "+f"(d[1]), "+f"(d[2]), "+f"(d[3]) : "r"(a0), "r"(a1), "r"(b0));
}

__device__ __forceinline__ float qsum(float v) { v += __shfl_xor_sync(0xffffffffu, v, 1); v += __shfl_xor_sync(0xffffffffu, v, 2); return v; }

constexpr int NCTA = 132;
#define NB_ 6
#define NA_ 5
constexpr int NB = NB_;
constexpr int NA = NA_;
constexpr uint32_t SLOT = 16384;
constexpr uint32_t SB = 1024;
constexpr uint32_t OFF_B = 0;
constexpr uint32_t OFF_A = NB * SLOT;
constexpr uint32_t OFF_S = OFF_A + NA * SLOT;
constexpr uint32_t OFF_T = OFF_S + 20480;
constexpr uint32_t OFF_CS = OFF_T + 24576;
constexpr uint32_t OFF_MR = OFF_CS + 4640;
constexpr uint32_t OFF_BAR = OFF_MR + 512;
constexpr uint32_t OFF_MA = OFF_S, OFF_MB = OFF_CS - 2048;
constexpr uint32_t BAR_FULLB = OFF_BAR;
constexpr uint32_t BAR_FULLA = BAR_FULLB + 64;
constexpr uint32_t BAR_EMPTYB = BAR_FULLA + 64;
constexpr uint32_t BAR_EMPTYA = BAR_EMPTYB + 64;
constexpr uint32_t BAR_SIGP = BAR_EMPTYA + 64;
constexpr uint32_t BAR_SIGT = BAR_SIGP + 24;
constexpr uint32_t BAR_STAT = BAR_SIGP + 64;
constexpr uint32_t BAR_HALO = BAR_STAT + 16;
constexpr uint32_t BAR_CS = BAR_HALO + 8;
constexpr uint32_t BAR_WPHI = BAR_CS + 16;
constexpr uint32_t BAR_KV = BAR_WPHI + 8;
constexpr uint32_t BAR_STG = BAR_KV + 16;
constexpr uint32_t BAR_EPOCH = BAR_STG + 48;
constexpr uint32_t BAR_LAND = OFF_BAR + 7 * 64;
constexpr uint32_t OFF_EPOCH = OFF_BAR + 8 * 64;
static_assert(BAR_EPOCH < BAR_LAND, "barriers");
constexpr uint32_t SMEM_BYTES = OFF_EPOCH + 8;
static_assert(SMEM_BYTES <= 232448 && NB % 2 == 0 && NB <= 8 && NA <= 6, "smem");

#define CREGS 224
#define PREGS 56
#define PF1 19
#define PF2 21
#define PRE_A 2
#define PRE_B 4
#define CSB 4
#define CSNEED 0xF003u
#define XR 1
#define PS0 1
#define PS1 3
#define PSW 0
#define SD 1000
#define QORD 4
#define KSPLIT 12
#define KEEP 16
#define NJ 3
#define KSL 1000
#define PSL 0
#define KVS 12
#define D2 2000
#define D3 1500
#define G0 50
#define MAP 3
#define PMAP 0x76321450u
#define PW 1
#define XA 3
#define XS 1
#define UK 0
#define CP 500
#define CD 0
#define S0 500
#define NS 2
#define XO 0
#define SW 2
#define SA 1
#define SB_ 4
#define XD 500
#define ND0 1
#define KB 8
#define DEFER 3
#define DEFL 2
#define TSK 3
#define TSL 3
constexpr int NTHREADS = 384;

struct Params {
  CUtensorMap mx;
  CUtensorMap mw[3];
  CUtensorMap mwo[2];
  CUtensorMap mcs[2];
  CUtensorMap mwphi;
  uint4* out;
};

#define XBUF(L) 1
__device__ __align__(256) uint4 g_img[XBUF(3) + 1][16][16][1024];
__device__ __forceinline__ uint32_t img_code(bool isx, int L) { return isx ? (L & 1) | (L & 2) << 15 : ~L & 1; }
__device__ __forceinline__ uint32_t img_mask(bool isx) { return isx ? 0x10001u : 1u; }
__device__ __align__(256) uint4 g_wf[2][8][16][1024];
__device__ __align__(256) uint4 g_stats[16][2][8][32];
__device__ __align__(256) uint4 g_halo[16][8][2][256];
__device__ __align__(256) float g_cs[2][2][3072];
__device__ __align__(256) uint4 g_kvpart[8][16][2][544];
__device__ __align__(256) uint4 g_kvfin[8][16][80];
__device__ __align__(256) unsigned g_hint[7][16][32];
__device__ __align__(256) unsigned g_hflag[2][16][8][32];
__device__ __align__(256) unsigned g_kvfflag[2][8][2][32];
__device__ __align__(256) unsigned g_csflag[2][8][32];
__device__ __align__(256) unsigned g_kflag[8][32];
__device__ unsigned g_ctr;
__device__ __forceinline__ unsigned vblock() {
  unsigned s;
  asm volatile("mov.u32 %0, %%smid;" : "=r"(s));
  const unsigned r = s & 1;
  s >>= 1;
  const unsigned t = s - 32, q = (t * 37) >> 8;
  const unsigned hi = s < 60 ? 12 + (t - 7 * q) * 8 + q : (s < 62 ? s + 4 : s - 58);
  unsigned b = 2 * (s < 32 ? (s & 7) * 8 + (s >> 3) : hi) + r;
  if (b < 128) b = (b & 15) | ((PMAP >> ((b >> 4) * 4)) & 7) << 4;
  if (s >= 62) b = 8 + 4 * r + s - 62;
  return __shfl_sync(0xffffffffu, b, 0);
}
#define TS(who, id) do {} while (0)
#define TSW(id) do {} while (0)

#define TSMASK 0xFFFF
#define TSL_(a) do { if ((TSMASK >> (a)) & 1) TSW((a) + L * 12); } while (0)
__device__ __forceinline__ int cta_m(unsigned b) { return ((b >> 2) & 12) | (b & 3); }
__device__ __forceinline__ int cta_j(unsigned b) { return ((b >> 2) & 3) | ((b >> 4) & 4); }
struct Ring { uint32_t s, ph; };
template <int N> __device__ __forceinline__ void adv(Ring& r) { if (++r.s == N) { r.s = 0; r.ph ^= 1; } }
template <int N> __device__ __forceinline__ void rewind2(Ring& r) { if (r.s < 2) { r.s += N - 2; r.ph ^= 1; } else r.s -= 2; }
__device__ __forceinline__ int other_tile(int t, int j) { return (t == (j | 4) ? 7 : t) ^ (~j & 4); }
__device__ __forceinline__ int q_order(int i, int j) { return 2 * (i >= 14 ? j : other_tile(i >> 1, j)) + (i & 1); }
__device__ __forceinline__ int o_order(int i, int j) {
  if (i < 2) return 2 * j + i;
  const int odd = i >= 9;
  return 2 * other_tile(i - 2 - 7 * odd, j) + odd;
}
__device__ __forceinline__ int kv_order(int i, int j, int L) { return L > 0 ? o_order(i, j) : (i + 14 + 2 * (j & 4)) & 15; }

__device__ __forceinline__ unsigned poll_flags(const unsigned* f, int n, unsigned need, unsigned tag) {
  const int lane = threadIdx.x & 31;
  unsigned mask; int it = 0;
  do {
    unsigned v = lane < n ? ld_flag(f + lane) : 0u;
    mask = __ballot_sync(0xffffffffu, lane < n && v == tag);
    if (++it > (1 << 22)) __trap();
  } while ((mask & need) != need);
  fence_async_global();
  return mask;
}
template <bool WAIT = true>
__device__ __forceinline__ unsigned get_tag(uint32_t sb) {
  if (WAIT) mbar_wait(sb + BAR_EPOCH, 0);
  unsigned t; asm volatile("ld.shared.u32 %0, [%1];" : "=r"(t) : "r"(sb + OFF_EPOCH) : "memory");
  return t;
}

__device__ __forceinline__ int lane_id() { int l; asm volatile("mov.u32 %0, %%laneid;" : "=r"(l)); return l; }
__device__ __forceinline__ unsigned seq4(unsigned tag, int L) { return 8u | ((tag & 1u) << 2) | (unsigned)L; }
constexpr float LOG2E = 1.4426950408889634f;

__device__ __forceinline__ float bb_fence(int never, const void* p = &g_ctr, uint32_t keep = 0) {
  while (never < 0) never = ld_flag((const unsigned*)p) + keep;
  return __int_as_float(never >> 30);
}
__device__ __forceinline__ uint32_t solid(uint32_t v) { return __shfl_sync(0xffffffffu, v, threadIdx.x & 31); }
template <class T> __device__ __forceinline__ T* solid(T* p) { return (T*)__shfl_sync(0xffffffffu, (unsigned long long)p, threadIdx.x & 31); }
__device__ __forceinline__ void bb_keep(const float* v, int never) {
  while (never < 0) {
#pragma unroll
    for (int q = 0; q < 32; q += 4) sts128(never + q * 4, __float_as_uint(v[q]), __float_as_uint(v[q + 1]), __float_as_uint(v[q + 2]), __float_as_uint(v[q + 3]));
    never = ld_flag(&g_ctr + never);
  }
}
constexpr uint32_t HA128 = 0x40000040u, HA64 = 0x80000040u;
struct Ctx {
  static constexpr uint32_t sb = SB;
  uint32_t ab, da0;
  int w, warp, lane, g, c;
  int goff;
  __device__ __forceinline__ int m() const { return goff >> 14; }
  __device__ __forceinline__ int j() const { return (goff >> 4) & 7; }
  bool elected;
  Ring ra, rb;
  uint32_t pa, pb;
  uint32_t ha, k2;
  uint32_t mrow, mxor, mhi;
  __device__ __forceinline__ uint32_t aslot(uint32_t s) const { return ab + s * SLOT; }
  __device__ __forceinline__ uint32_t fullA(uint32_t s) const { return sb + BAR_FULLA + s * 8; }
  __device__ __forceinline__ uint32_t fullB(uint32_t s) const { return sb + BAR_FULLB + s * 8; }
  __device__ __forceinline__ void releaseA(uint32_t s) const { if (elected) mbar_arrive(sb + BAR_EMPTYA + s * 8); }
  __device__ __forceinline__ void releaseB(uint32_t s) const { if (elected) mbar_arrive(sb + BAR_EMPTYB + s * 8); }
  __device__ __forceinline__ uint32_t maddr(uint32_t tile, uint32_t ch) const { return tile + mrow + (((ch + mhi) ^ mxor) << 4); }
  __device__ __forceinline__ uint32_t oo() const { return warp * 128 + g * 4 + (c ^ (g >> 1)); }
  __device__ __forceinline__ uint4* img(int b, int hp) const { return ip + (b * 256 + hp) * 1024; }
  uint4* ip;
  uint32_t so;
  __device__ __forceinline__ uint32_t held(int i) const { return ra.s + i < 2 ? ra.s + i + NA - 2 : ra.s + i - 2; }
};

template <int N, bool FIRST, bool O = true>
__device__ __forceinline__ void gemm_issue(float (&acc)[N / 2], Ctx& x, bool ready = false) {
  if (!ready) {
    if (N == 256) mbar_wait3(x.fullA(x.ra.s), x.ra.ph, x.fullB(x.rb.s), x.rb.ph);
    else mbar_wait2(x.fullA(x.ra.s), x.ra.ph, x.fullB(x.rb.s), x.rb.ph);
  }
  const uint32_t da = x.da0 + x.ra.s * (SLOT / 16), db = desc_lo(SB + OFF_B, 8192) + x.rb.s * (SLOT / 16);
  wgmma_fence();
#pragma unroll
  for (int k = 0; k < 4; k++) {
    const uint32_t a = da + (k >> 1) * (O ? 32 : x.k2) + (k & 1) * 2, ha = O ? HA64 : x.ha;
    if constexpr (N == 256) wgmma_ss_n256(acc, a, ha, db + 128 * k, !(FIRST && k == 0));
    else wgmma_ss_n128(acc, a, ha, db + 128 * k, !(FIRST && k == 0));
  }
  wgmma_commit();
}
template <int N>
__device__ __forceinline__ void gemm_next(Ctx& x) {
  x.pa = x.ra.s; x.pb = x.rb.s;
  if (N == 256) x.rb.s++;
  adv<NA>(x.ra); adv<NB>(x.rb);
}
template <int N>
__device__ __forceinline__ void gemm_release(Ctx& x, bool relA) {
  if (relA) x.releaseA(x.pa);
  x.releaseB(x.pb);
  if (N == 256) x.releaseB(x.pb + 1);
}
template <int N>
__device__ __forceinline__ void gemm_retire(Ctx& x, bool relA) { wgmma_wait<1>(); gemm_release<N>(x, relA); gemm_next<N>(x); }
template <bool O = true>
__device__ __forceinline__ void gemm_run(float (&acc)[64], Ctx& x, int n, int hold, int n4 = 0) {
  bool ready = false;
#pragma unroll 1
  for (; n > 0; n--) {
    gemm_issue<128, false, O>(acc, x, ready);
    const uint32_t pa = x.pa, pb = x.pb;
    gemm_next<128>(x);
    ready = mbar_probe2(x.fullA(x.ra.s), x.ra.ph, x.fullB(x.rb.s), x.rb.ph);
    wgmma_wait<1>();
    if (n > hold) x.releaseA(pa);
    x.releaseB(pb);
  }
}
__device__ __forceinline__ void gemm_end(float (&acc)[64], Ctx& x) { wgmma_wait<0>(); fence_regs(acc); gemm_release<128>(x, false); }

__device__ __forceinline__ void rows_load(uint4* r, uint32_t tile, const Ctx& x) {
#pragma unroll
  for (int q = 0; q < 4; q++) {
    const uint32_t row = x.warp * 16 + 4 * q + (x.lane >> 3);
    lds128(tile + row * 128 + (((x.lane & 7) ^ (row & 7)) << 4), r[q].x, r[q].y, r[q].z, r[q].w);
  }
}
__device__ __forceinline__ void rows_store(const uint4* r, uint4* g) {
#pragma unroll
  for (int q = 0; q < 4; q++) stg128(g + q * 1024, r[q]);
}
__device__ __forceinline__ void publish(int id, const Ctx& x) { __syncwarp(); if (x.lane == 0) mbar_arrive(x.sb + BAR_SIGP + id * 8); }
__device__ __forceinline__ uint32_t img_tag(uint32_t v, bool isx, int L, const Ctx& x) {
  const uint32_t mk = ((x.lane ^ (x.warp * 4)) & 7) ? 0u : img_mask(isx);
  return (v & ~mk) | (img_code(isx, L) & mk);
}
__device__ __forceinline__ void img_tag(uint4 (&r)[4], bool isx, int L, const Ctx& x) {
#pragma unroll
  for (int q = 0; q < 4; q++) { uint32_t& v = q == 0 ? r[q].x : (q == 1 ? r[q].y : (q == 2 ? r[q].z : r[q].w)); v = img_tag(v, isx, L, x); }
}
__device__ __forceinline__ void img_store(const uint4 (&r)[4], uint4* g) {
#pragma unroll
  for (int q = 0; q < 4; q++) stg128(g + q * 32, r[q]);
}
__device__ __forceinline__ void img_sts(const uint4 (&r)[4], uint32_t tile, const Ctx& x) {
#pragma unroll
  for (int q = 0; q < 4; q++) sts128(tile + x.so + q * 512, r[q].x, r[q].y, r[q].z, r[q].w);
}
__device__ __forceinline__ void img_load(uint32_t (&v)[16], uint32_t tile, const Ctx& x) {
#pragma unroll
  for (int q = 0; q < 4; q++) lds128(tile + x.so + q * 512, v[4 * q], v[4 * q + 1], v[4 * q + 2], v[4 * q + 3]);
}
__device__ __forceinline__ void img_unpack(float* a, const uint32_t (&v)[16]) {
#pragma unroll
  for (int q = 0; q < 16; q++) { a[4 * (q & 7) + 2 * (q >> 3)] = lo16(v[q]); a[4 * (q & 7) + 2 * (q >> 3) + 1] = hi16(v[q]); }
}

template <int N>
__device__ __forceinline__ void stats_acc(const float* a, float (&t)[4]) {
#pragma unroll
  for (int i = 0; i < N; i++) { t[i & 2] += a[i]; t[(i & 2) + 1] = fmaf(a[i], a[i], t[(i & 2) + 1]); }
}
__device__ __forceinline__ void stats_send(float (&t)[4], int L, const Ctx& x) {
  const unsigned seq = seq4(get_tag<false>(x.sb), L);
#pragma unroll
  for (int q = 0; q < 4; q++) t[q] = qsum(t[q]);
  if (x.c == 0) st_pkt(&g_stats[x.m()][x.w][x.j()][x.warp * 8 + x.g], __float_as_uint(t[0]), __float_as_uint(t[1]), __float_as_uint(t[2]), (__float_as_uint(t[3]) & ~15u) | seq);
}
__device__ __forceinline__ void out_epilogue(const float (&acc)[64], uint4 (&r1)[4], float (&t)[4], uint4* g, int L, Ctx& x) {
  const uint32_t t0 = x.aslot(x.ra.s), t1 = x.aslot(x.ra.s + 1 == NA ? 0 : x.ra.s + 1);
  if (L == 3) {
#pragma unroll
    for (int p = 0; p < 8; p++) {
      stsm4(x.maddr(p < 4 ? t0 : t1, (p & 3) * 2), pack2(acc[8 * p], acc[8 * p + 1]), pack2(acc[8 * p + 2], acc[8 * p + 3]),
            pack2(acc[8 * p + 4], acc[8 * p + 5]), pack2(acc[8 * p + 6], acc[8 * p + 7]));
      if ((p & 3) == 3) { uint4 r[4]; __syncwarp(); rows_load(r, p < 4 ? t0 : t1, x); rows_store(r, g + (p >> 2) * 8); }
    }
  } else {
    auto pack16 = [&](uint4 (&r)[4], const float* a) {
#pragma unroll
      for (int q = 0; q < 4; q++) { const float* u = a + 16 * (q & 1) + (q & 2); r[q] = make_uint4(pack2(u[0], u[1]), pack2(u[4], u[5]), pack2(u[8], u[9]), pack2(u[12], u[13])); }
    };
    uint4 r0[4];
    pack16(r0, acc);
    img_tag(r0, true, L + 1, x);
    img_store(r0, x.img(XBUF(L + 1), 0));
    publish(1, x);
    const float z = bb_fence(x.goff);
    img_sts(r0, t0, x);
    pack16(r1, acc + 32);
    img_tag(r1, true, L + 1, x);
    img_sts(r1, t1, x);
    float u[4] = {z, z, z, z}, v[4] = {z, z, z, z};
    stats_acc<32>(acc, v);
    stats_acc<32>(acc + 32, u);
#pragma unroll
    for (int q = 0; q < 4; q++) t[q] = u[q] + v[q];
    mbar_wait2(x.fullB(x.rb.s), x.rb.ph, x.fullB(x.rb.s + 1), x.rb.ph);
    fence_async_smem();
    asm volatile("bar.sync %0, %1;" ::"r"(L == 1 ? x.w + 1 : 3), "r"(L == 1 ? 128 : 256) : "memory");
  }
}

struct Stats { float rstd0, rstd1; };
__device__ __forceinline__ Stats load_stats(int half, const Ctx& x) {
  const float2 u = lds64f(x.sb + OFF_MR + half * 256 + (x.warp * 8 + x.g) * 8);
  return {u.x, u.y};
}

template <int NK>
__device__ __forceinline__ void hedgehog_scale(float* t, const Stats& st, const uint32_t* keep) {
#pragma unroll
  for (int q = 0; q < 16; q++) t[q] *= ((q & 2) ? st.rstd1 : st.rstd0) * LOG2E;
  float m[4];
#pragma unroll
  for (int q = 0; q < 4; q++) m[q] = fmaxf(fmaxf(fabsf(t[4 * q]), fabsf(t[4 * q + 1])), fmaxf(fabsf(t[4 * q + 2]), fabsf(t[4 * q + 3])));
  if (__builtin_expect(__any_sync(0xffffffffu, fmaxf(fmaxf(m[0], m[1]), fmaxf(m[2], m[3])) > 58.f), 0)) {
    float z[16 + NK];
#pragma unroll
    for (int q = 0; q < 16 + NK; q++) z[q] = q < 16 ? t[q & 15] : __uint_as_float(keep[q & 15]);
#pragma unroll 1
    for (int r = 0; r < 4; r += 2) {
      float hi = -INFINITY, lo = INFINITY;
#pragma unroll 1
      for (int i = 0; i < 16; i++) {
        const int k = (i & 6) * 2 + (i & 1) + r;
        const float v = z[k];
        if (i < 8) { hi = fmaxf(hi, v); lo = fminf(lo, v); }
        else z[k] = v - fminf(fmaxf(v, lo), hi);
        if (i == 7) {
#pragma unroll 1
          for (int d = 1; d <= 2; d++) { hi = fmaxf(hi, __shfl_xor_sync(0xffffffffu, hi, d)); lo = fminf(lo, __shfl_xor_sync(0xffffffffu, lo, d)); }
          const float mid = 0.5f * hi + 0.5f * lo;
          hi = fmaxf(hi - 58.f, mid); lo = fminf(lo + 58.f, mid);
        }
      }
    }
#pragma unroll
    for (int q = 0; q < 16; q++) t[q] = z[q];
  }
}
__device__ __forceinline__ void dual_exp(const float* t, uint32_t (&f)[18], int never) {
  float e[KSPLIT];
#pragma unroll
  for (int q = 0; q < KSPLIT; q++) e[q] = ex2(q < 16 ? t[q] : -t[q & 15]);
  while (never < 0) {
#pragma unroll
    for (int i = 0; i < KSPLIT; i += 4) asm volatile("ld.shared.v4.f32 {%0,%1,%2,%3}, [%4];" : "=f"(e[i]), "=f"(e[i + 1]), "=f"(e[i + 2]), "=f"(e[i + 3]) : "r"(never + i) : "memory");
    never += __float_as_int(e[0]);
  }
#pragma unroll
  for (int q = 0; q < KSPLIT; q += 2) f[q >> 1] = pack2(e[q], e[q + 1]);
#pragma unroll
  for (int q = KSPLIT; q < 32; q += 2) f[q >> 1] = q < 16 ? pack2(ex2(t[q]), ex2(t[q + 1])) : pack2(ex2(-t[q & 15]), ex2(-t[(q & 15) + 1]));
#pragma unroll
  for (int sg = 0; sg < 2; sg++) {
    const uint32_t* u = f + 8 * sg;
    const uint32_t a = add2(add2(u[0], u[2]), add2(u[4], u[6])), b = add2(add2(u[1], u[3]), add2(u[5], u[7]));
    f[16 + sg] = add2(__byte_perm(a, b, 0x5410), __byte_perm(a, b, 0x7632));
  }
}
__device__ __forceinline__ void dual_exp_rcp(const float* t, uint32_t (&f)[16]) {
#pragma unroll
  for (int q = 0; q < 8; q++) {
    const float a = ex2(t[2 * q]), b = ex2(t[2 * q + 1]), r = rcp(a * b);
    f[q] = pack2(a, b); f[8 + q] = pack2(r * b, r * a);
  }
}
__device__ __forceinline__ void cta_bar() { asm volatile("bar.sync 3, 256;" ::: "memory"); }

template <int N> __device__ __forceinline__ void pin(const uint32_t* v, uint32_t addr) {
#pragma unroll
  for (int i = 0; i < N; i += 4)
    asm volatile("{\n.reg .pred p;\nsetp.eq.u32 p, %0, 0;\n@p st.shared.v4.u32 [%0], {%1,%2,%3,%4};\n}" ::"r"(addr), "r"(v[i]), "r"(v[i + 1]), "r"(v[i + 2]), "r"(v[i + 3]) : "memory");
}

__device__ __forceinline__ void consumer(const Params& P, uint32_t sb, int w, unsigned vb) {
  Ctx x;
  x.w = w;
  x.ab = sb + OFF_A + w * 8192; x.da0 = desc_lo(SB + OFF_A, 16) + w * 512;
  x.lane = threadIdx.x & 31; x.warp = __shfl_sync(0xffffffffu, (threadIdx.x >> 5) & 3, 0); x.g = x.lane >> 2; x.c = x.lane & 3;
  x.goff = (cta_m(vb) * 128 + w) * 128 + cta_j(vb) * 16;
  asm volatile("" : "+r"(x.goff));
  x.elected = (threadIdx.x & 127) == 0;
  x.ra = {0, 0}; x.rb = {0, 0}; x.pa = x.pb = 0;
  {
    const uint32_t row = x.warp * 16 + (x.lane & 15);
    x.mrow = row * 128; x.mxor = row & 7; x.mhi = x.lane >> 4;
  }
  const int goff = x.goff;
  x.ip = solid(&g_img[0][x.m()][2 * x.j()][w * 512 + x.oo()]);
  x.so = solid(16 * x.oo());
  uint4 r1[4];
  float ts[4] = {0.f, 0.f, 0.f, 0.f};
#pragma unroll
  for (int i = 0; i < 4; i++) r1[i] = make_uint4(0, 0, 0, 0);
  TSW(0);
  mbar_wait3(x.fullA(0), 0, x.fullB(0), 0);
#pragma unroll 1
  for (int L = 0; L < 4; L++) {
    float acc[64];
    constexpr uint32_t dcs = desc_lo(SB + OFF_CS, 0);
    if ((L & 1) == 0) {
    float kv[128];
    x.ha = L ? HA64 : HA128; x.k2 = L ? 32 : 4;
    gemm_issue<256, true, false>(kv, x, true); gemm_next<256>(x);
    {
      int i = 1;
#pragma unroll 1
      for (int seg = L ? NS - 1 : 0; seg <= NS; seg++) {
        const int end = seg < NS ? (L == 0 ? 3 + SA * ((x.j() + SW * w) & 3) + SB_ * seg : XA + 1) : 14 + L;
#pragma unroll 1
        do {
          gemm_issue<256, false, false>(kv, x);
          gemm_retire<256>(x, true);
          i++;
          if (i == 5) TSL_(8);
          if (i == 11) TSL_(10);
        } while (i != end);
        if (seg < NS && L == 0) {
          uint32_t v[16];
          float a[32];
#pragma unroll
          for (int q = 0; q < 4; q++) ldsm4(x.maddr(x.aslot(x.pa), 2 * q), reinterpret_cast<uint32_t (&)[4]>(v[4 * q]));
#pragma unroll
          for (int q = 0; q < 16; q++) { a[2 * q] = lo16(v[q]); a[2 * q + 1] = hi16(v[q]); }
          stats_acc<32>(a, ts);
          fence_regs(ts);
          wg_bar(w);
        }
        if (seg == NS - 1) {
          if (L > 0) { img_store(r1, x.img(XBUF(L), 1)); publish(2, x); }
          mbar_wait(sb + BAR_EPOCH, 0);
          stats_send(ts, L, x);
        }
      }
    }
      const Ring kt = x.ra;
      if (L == 0) adv<NA>(x.ra);
#pragma unroll 1
      for (int h = L; h < 2; h++) {
        float d[16];
        mbar_wait2(x.fullA(kt.s), kt.ph, sb + BAR_WPHI, 0);
        wgmma_fence();
#pragma unroll
        for (int q = 0; q < 2; q++) wgmma_ss_n32(d, x.da0 + kt.s * (SLOT / 16) + h * 4 + q * 2, desc_lo(SB + OFF_S + 4096, 512) + w * 256 + h * 128 + q * 64, q);
        wgmma_commit();
        gemm_issue<256, false, false>(kv, x);
        gemm_retire<256>(x, true);
        if (h) x.releaseA(kt.s);
        fence_regs(d);
        uint4* dst = &g_wf[1][x.j()][x.m()][w * 512 + (x.warp * 16 + x.g) * 8 + ((h * 4 + x.c) ^ x.g)];
        dst[0] = make_uint4(pack2(d[0], d[1]), pack2(d[4], d[5]), pack2(d[8], d[9]), pack2(d[12], d[13]));
        dst[64] = make_uint4(pack2(d[2], d[3]), pack2(d[6], d[7]), pack2(d[10], d[11]), pack2(d[14], d[15]));
      }
      const uint32_t dm = desc_lo(SB + OFF_MA, 0) + w * 64;
      mbar_wait2(sb + BAR_STAT, 0, sb + BAR_CS, 0);
      wgmma_fence();
      wgmma_r1_n256(kv, dm, dcs + 96, 1);
      wgmma_commit();
      const Stats st = load_stats(w, x);
      mbar_wait2(x.fullA(x.ra.s), x.ra.ph, x.fullB(x.rb.s), x.rb.ph);
      wgmma_wait<0>();
      fence_regs(kv);
      gemm_release<256>(x, true);
      TSL_(2);
      uint32_t P0[32], P1[32], PH[32];
#pragma unroll
      for (int t = 0; t < 16; t++) { P0[t] = pack2(kv[4 * t] * st.rstd0, kv[4 * t + 1] * st.rstd0); P1[t] = pack2(kv[4 * t + 2] * st.rstd1, kv[4 * t + 3] * st.rstd1); }
      pin<16>(P0, x.mrow + 16);
      {
#pragma unroll
        for (int q = 0; q < 4; q++) sts128((x.warp < 3 ? sb + OFF_T + w * 12288 + x.warp * 4096 : sb + OFF_S + 16384 + w * 2048) + x.lane * 16 + q * 512, P1[4 * q], P1[4 * q + 1], P1[4 * q + 2], P1[4 * q + 3]);
      }
      wgmma_fence();
      wgmma_r1_n128(acc, dm, dcs, 0);
      gemm_issue<128, false, false>(acc, x, PW & 1); gemm_next<128>(x);
      TSL_(3);
#pragma unroll
      for (int s = 0; s < 4; s++) {
#pragma unroll
        for (int t = 16 + 8 * (s & 1); t < 24 + 8 * (s & 1); t++) {
          if (s < 2) P1[t] = movm(pack2(kv[4 * t + 2] * st.rstd1, kv[4 * t + 3] * st.rstd1));
          else P0[t] = movm(pack2(kv[4 * t] * st.rstd0, kv[4 * t + 1] * st.rstd0));
        }
        if (s < 3) { gemm_issue<128, false, false>(acc, x); gemm_retire<128>(x, true); }
        if (s == 1) {
          if (x.warp < 3) {
#pragma unroll
            for (int q = 4; q < 8; q++) sts128(sb + OFF_T + w * 12288 + x.warp * 4096 + x.lane * 16 + q * 512, P1[4 * q], P1[4 * q + 1], P1[4 * q + 2], P1[4 * q + 3]);
          } else {
            uint4* dst = &g_halo[x.m()][x.j()][w][x.lane];
#pragma unroll
            for (int q = 0; q < 8; q++) dst[q * 32] = make_uint4(P1[4 * q], P1[4 * q + 1], P1[4 * q + 2], P1[4 * q + 3]);
          }
          publish(3, x);
          gemm_issue<128, false, false>(acc, x);
          gemm_retire<128>(x, true);
        }
      }
      TSL_(4);
      gemm_run<false>(acc, x, 10, 0);
      gemm_issue<128, false, false>(acc, x);
      {
        wg_bar(w);
        uint32_t tr = sb + OFF_T + w * 12288 + (x.warp - 1) * 4096;
        if (x.warp == 0) {
          tr = x.m() > 0 ? sb + OFF_S + 8192 + w * 4096 : tr + 4096;
          if (x.m() > 0) mbar_wait(sb + BAR_HALO, L >> 1);
        }
#pragma unroll
        for (int q = 0; q < 8; q++) lds128(tr + x.lane * 16 + q * 512, PH[4 * q], PH[4 * q + 1], PH[4 * q + 2], PH[4 * q + 3]);
      }
      gemm_retire<128>(x, false);
      gemm_end(acc, x);
      TSL_(5);
      const bool first = (x.m() == 0) && (x.warp == 0);
      const bool hi0 = 2 * x.c > x.g, hi1 = 2 * x.c + 1 > x.g;
      const uint32_t mhi = (hi0 ? 0xFFFFu : 0u) | (hi1 ? 0xFFFF0000u : 0u);
      const float sc0 = st.rstd0 * (0.17677669529663687f * LOG2E), sc1 = st.rstd1 * (0.17677669529663687f * LOG2E);
#pragma unroll
      for (int hp = 0; hp < 2; hp++) {
        const uint32_t tile = x.aslot(x.held(hp));
        uint32_t px[2], py[2];
        float s[2][3][4];
#pragma unroll
        for (int u = 0; u < 2; u++) {
#pragma unroll
          for (int q = 0; q < 12; q++) s[u][q >> 2][q & 3] = 0.f;
#pragma unroll
          for (int ks = 0; ks < 2; ks++) {
            const int t = 8 * hp + 4 * u + 2 * ks;
            const uint32_t a0 = pack2(acc[4 * t], acc[4 * t + 1]), a1 = pack2(acc[4 * t + 2], acc[4 * t + 3]);
            const uint32_t a2 = pack2(acc[4 * t + 4], acc[4 * t + 5]), a3 = pack2(acc[4 * t + 6], acc[4 * t + 7]);
            mma16816(s[u][0], a0, a1, a2, a3, PH[t], PH[t + 1]);
            mma16816(s[u][1], a0, a1, a2, a3, P0[t], P0[t + 1]);
            mma16816(s[u][2], a0, a1, a2, a3, P1[t], P1[t + 1]);
          }
        }
        float e[2][4], r[2][2];
#pragma unroll
        for (int u = 0; u < 2; u++) {
          e[u][0] = (hi0 ? s[u][0][0] : s[u][1][0]) * sc0; e[u][1] = (hi1 ? s[u][0][1] : s[u][1][1]) * sc0;
          e[u][2] = (hi0 ? s[u][1][2] : s[u][2][2]) * sc1; e[u][3] = (hi1 ? s[u][1][3] : s[u][2][3]) * sc1;
          if (first) { if (hi0) e[u][0] = -1e30f; if (hi1) e[u][1] = -1e30f; }
          r[u][0] = fmaxf(e[u][0], e[u][1]); r[u][1] = fmaxf(e[u][2], e[u][3]);
        }
#pragma unroll
        for (int d = 1; d <= 2; d++)
#pragma unroll
          for (int q = 0; q < 4; q++) r[q >> 1][q & 1] = fmaxf(r[q >> 1][q & 1], __shfl_xor_sync(0xffffffffu, r[q >> 1][q & 1], d));
#pragma unroll
        for (int u = 0; u < 2; u++) {
#pragma unroll
          for (int q = 0; q < 4; q++) e[u][q] = ex2(e[u][q] - r[u][q >> 1]);
          r[u][0] = e[u][0] + e[u][1]; r[u][1] = e[u][2] + e[u][3];
        }
#pragma unroll
        for (int d = 1; d <= 2; d++)
#pragma unroll
          for (int q = 0; q < 4; q++) r[q >> 1][q & 1] += __shfl_xor_sync(0xffffffffu, r[q >> 1][q & 1], d);
#pragma unroll
        for (int u = 0; u < 2; u++) {
          const float rx = rcp(r[u][0]), ry = rcp(r[u][1]);
          px[u] = pack2(e[u][0] * rx, e[u][1] * rx); py[u] = pack2(e[u][2] * ry, e[u][3] * ry);
        }
        uint32_t o[8][2];
        uint4 ro[4];
#pragma unroll
        for (int q = 0; q < 8; q++) {
          float d[4] = {0.f, 0.f, 0.f, 0.f};
          const int t = 16 + 8 * hp + q, u = q >> 2;
          mma16816(d, px[u] & mhi, 0u, px[u] & ~mhi, py[u] & mhi, PH[t], P0[t]);
          mma1688(d, 0u, py[u] & ~mhi, P1[t]);
          o[q][0] = pack2(d[0], d[1]); o[q][1] = pack2(d[2], d[3]);
        }
#pragma unroll
        for (int q = 0; q < 4; q++) ro[q] = make_uint4(o[4 * (q & 1)][q >> 1], o[4 * (q & 1) + 1][q >> 1], o[4 * (q & 1) + 2][q >> 1], o[4 * (q & 1) + 3][q >> 1]);
        img_tag(ro, false, 0, x);
        img_store(ro, x.img(0, hp));
        if (hp == 0) publish(0, x);
        uint32_t xs[16];
        if (L) img_load(xs, tile, x);
        else {
#pragma unroll
          for (int q = 0; q < 4; q++) {
            uint32_t v[4];
            ldsm4(x.maddr(tile, 2 * q), v);
            xs[2 * q] = v[0]; xs[8 + 2 * q] = v[1]; xs[2 * q + 1] = v[2]; xs[9 + 2 * q] = v[3];
          }
          __syncwarp();
        }
        img_sts(ro, tile, x);
        img_unpack(acc + 32 * hp, xs);
      }
    } else {
      float kv[128];
      float (&kv0)[64] = reinterpret_cast<float (&)[64]>(kv[0]);
      float (&kv1)[64] = reinterpret_cast<float (&)[64]>(kv[64]);
      auto mma8 = [&](uint32_t as, uint32_t bs, int i, bool fence) {
        const uint32_t da = desc_lo(SB + OFF_A, 16) + as * (SLOT / 16), db = desc_lo(SB + OFF_B, 8192) + bs * (SLOT / 16);
        if (fence) wgmma_fence();
#pragma unroll
        for (int k = 0; k < 4; k++) {
          wgmma_ss_n128(kv0, da + (k >> 1) * 32 + (k & 1) * 2, HA64, db + 128 * k, i + k);
          wgmma_ss_n128(kv1, da + 512 + (k >> 1) * 32 + (k & 1) * 2, HA64, db + 128 * k, i + k);
        }
        wgmma_commit();
      };
      constexpr uint32_t dm = desc_lo(SB + OFF_MB, 0);
      auto relB = [&](uint32_t s) { mbar_arrive_n(sb + BAR_EMPTYB + s * 8, 2); };
      auto skip = [&]() {
#pragma unroll
        for (int q = 0; q < 6 - NJ; q++) adv<NA>(x.ra);
        x.rb.s = w ? (2 + NJ) % 6 : 4;
        if (!w && NJ < 4) x.rb.ph ^= 1;
      };
      static_assert(NA == 5 && NB == 6, "ring arithmetic");
      mma8(x.ra.s, x.rb.s + w, 0, true);
      gemm_next<256>(x);
#pragma unroll 1
      for (int i = 1; i < NJ; i++) {
        mbar_wait2(x.fullA(x.ra.s), x.ra.ph, x.fullB(x.rb.s + w), x.rb.ph);
        mma8(x.ra.s, x.rb.s + w, 1, true);
        if (!XO && i == XR) { img_store(r1, x.img(XBUF(L), 1)); publish(2, x); }
        if (!XO && i == XS) stats_send(ts, L, x);
        wgmma_wait<1>();
        if (x.elected) { x.releaseA(x.pa); relB(x.pb + w); }
        gemm_next<256>(x);
        if (XO && i == XR) { img_store(r1, x.img(XBUF(L), 1)); publish(2, x); stats_send(ts, L, x); }
      }
      if (w) {
        wgmma_wait<0>();
        if (x.elected) { x.releaseA(x.pa); relB(x.pb + 1); }
        skip();
        asm volatile("bar.sync 7, 256;" ::: "memory");
      }
      TSL_(8);
      {
        const int t = lane_id() + 32 * x.warp;
        uint32_t mask = t < 2 ? ((w ? (t ? 0xFF3Fu : 0x3FFFu) : 0xFFFFu) >> (NJ - 1)) & (w ? ~1u : ~0u) : 0u, cnt = 1 + t;
        bool ready = false;
#pragma unroll 1
        for (int i = NJ; i < 16; i++) {
          if (!ready) mbar_wait2(x.fullA(x.ra.s), x.ra.ph, x.fullB(x.rb.s), x.rb.ph);
          mma8(x.ra.s, x.rb.s, 1, true);
          const uint32_t bar = sb + (t ? BAR_EMPTYB + x.pb * 8 : BAR_EMPTYA + x.pa * 8);
          gemm_next<128>(x);
          if (w && (i | 4) == 15) x.rb.s = 4;
          ready = mbar_probe2(x.fullA(x.ra.s), x.ra.ph, x.fullB(x.rb.s), x.rb.ph);
          wgmma_wait<1>();
          if (mask & 1) mbar_arrive_n(bar, cnt);
          mask >>= 1; cnt = 2;
          if (i == 8 && w) asm volatile("bar.arrive 9, 256;" ::: "memory");
          if (i == 9) TSL_(10);
        }
        mbar_wait2(sb + BAR_STAT, 1, sb + BAR_CS + 8, 0);
        wgmma_fence();
        wgmma_r1_n128(kv0, dm, dcs + 96 + 96 * w, 1);
        wgmma_r1_n128(kv1, dm + 64, dcs + 96 + 96 * w, 1);
        wgmma_commit();
        if (w == 0) asm volatile("bar.arrive 7, 256;" ::: "memory");
        wgmma_wait<1>();
        if (mask & 1) mbar_arrive_n(sb + (t ? BAR_EMPTYB + x.pb * 8 : BAR_EMPTYA + x.pa * 8), 2);
      }
      const Stats s0 = load_stats(0, x), s1 = load_stats(1, x), st = w ? s1 : s0;
      if (w == 0) skip();
      const uint32_t h0 = x.held(0), h1 = x.held(1);
      auto vreg = [&](int ks) { return ks < 6 ? OFF_A + (ks < 3 ? h0 * SLOT : h1 * SLOT - 15360) + ks * 5120 : OFF_S + 2048 + ks * 5120; };
      uint32_t tV[2], uu[4];
#pragma unroll
      for (int hf = 0; hf < 2; hf++) {
        tV[hf] = sb + vreg(4 * hf + x.warp) + ((x.lane >> 3) & 1) * 2560 + (x.lane & 7) * 16 + x.mhi * 128;
        const float i0 = rcp(hf ? s1.rstd0 : s0.rstd0), i1 = rcp(hf ? s1.rstd1 : s0.rstd1);
        const uint32_t h = pack2(i0, i1);
        uu[2 * hf] = pack2(lo16(h), i0 - lo16(h)); uu[2 * hf + 1] = pack2(hi16(h), i1 - hi16(h));
        asm volatile("" : "+r"(tV[hf]), "+r"(uu[2 * hf]), "+r"(uu[2 * hf + 1])::"memory");
      }
      wgmma_wait<0>();
      fence_regs(kv);
      TSL_(2);
      if (w == 0) {
        uint32_t f[2][18], ad[4];
#pragma unroll
        for (int q = 0; q < 18; q++) f[1][q] = 0u;
#pragma unroll
        for (int q = 0; q < 4; q++) ad[q] = x.maddr(sb + OFF_S, 2 * q);
        auto norm = [&](int un) {
          uint32_t* u = f[un & 1];
          const Stats& sn = (un & 2) ? s1 : s0;
#pragma unroll
          for (int sg = 0; sg < 2; sg++) {
            uint32_t v = u[16 + sg];
            v = add2(v, __shfl_xor_sync(0xffffffffu, v, 1)); v = add2(v, __shfl_xor_sync(0xffffffffu, v, 2));
            const float a = rcp(lo16(v)) * sn.rstd0, b = rcp(hi16(v)) * sn.rstd1;
            const uint32_t r0 = pack2(a, a), r1_ = pack2(b, b);
#pragma unroll
            for (int q = 8 * sg; q < 8 * sg + 8; q++) u[q] = mul2(u[q], (q & 1) ? r1_ : r0);
#pragma unroll
            for (int q = 2 * sg; q < 2 * sg + 2; q++) stsm4(ad[q] + (un & 1) * SLOT + (un >> 1) * 8192, u[4 * q], u[4 * q + 1], u[4 * q + 2], u[4 * q + 3]);
          }
        };
        auto unit = [&](int un) { return kv + ((un >> 1) & 1) * 64 + (un & 1) * 16 + (un >> 2) * 32; };
        hedgehog_scale<0>(kv, s0, nullptr);
#pragma unroll 1
        for (int it = 0;; it++) {
#pragma unroll
          for (int un = 0; un < 4; un++) {
            if (un == 1) {
              if (it) asm volatile("bar.sync 9, 256;" ::: "memory");
#pragma unroll
              for (int q = 0; q < 4; q++) ad[q] -= it * (OFF_S - OFF_B - 2 * SLOT);
            }
            norm((un + 3) & 3);
            dual_exp(unit(un), f[un & 1], x.goff);
            hedgehog_scale<KEEP>(unit(un + 1), ((un + 1) & 2) ? s1 : s0, f[(un + 1) & 1]);
          }
          if (it) break;
#pragma unroll
          for (int q = 0; q < 32; q++) {
            asm volatile("mov.b32 %0, %1;" : "=f"(kv[q]) : "f"(kv[q + 32]));
            asm volatile("mov.b32 %0, %1;" : "=f"(kv[q + 64]) : "f"(kv[q + 96]));
            if (q < 16) kv[32 + q] = 0.f;
          }
        }
        norm(3);
        TSL_(3);
      } else {
        wg_bar(w);
#pragma unroll
        for (int hf = 0; hf < 2; hf++) {
          stsm4(tV[hf] + 512 + x.mhi * 512, uu[2 * hf], uu[2 * hf + 1], uu[2 * hf], uu[2 * hf + 1]);
          stsm4(tV[hf] + 1792 + x.mhi * 512, uu[2 * hf], uu[2 * hf + 1], uu[2 * hf], uu[2 * hf + 1]);
#pragma unroll
          for (int q = 0; q < 8; q++) {
            const float* u = kv + 64 * hf + 8 * q;
            stsm4(tV[hf] + (q >> 1) * 640 + (q & 1) * 256, pack2(u[0], u[1]), pack2(u[2], u[3]), pack2(u[4], u[5]), pack2(u[6], u[7]));
          }
        }
        TSL_(3);
      }
      {
        float d[2][20];
        uint4* dst = &g_kvpart[x.j()][w * 4 + x.warp][0][x.m() * 32 + x.lane];
        unsigned* dz = reinterpret_cast<unsigned*>(&g_kvpart[x.j()][w * 4 + x.warp][x.c & 1][512]) + x.m() * 8 + x.g;
        fence_async_smem();
        cta_bar();
        TSL_(11);
        uint32_t pk[9];
        auto prep = [&](float (&u)[20]) {
          fence_regs(u);
#pragma unroll
          for (int q = 0; q < 8; q++) pk[q] = pack2(u[((q >> 1) & 2) + 4 * (q & 3)], u[((q >> 1) & 2) + 4 * (q & 3) + 1]);
          pk[8] = __float_as_uint((x.c & 1) ? u[18] + u[19] : u[16] + u[17]);
#pragma unroll
          for (int q = 0; q < 9; q += 4) pk[q] = (pk[q] & ~1u) | (L == 1);
        };
        auto send = [&](int hp) {
          st_v4(dst + hp * 16 * 544, pk[0], pk[1], pk[2], pk[3]); st_v4(dst + (hp * 16 + 1) * 544, pk[4], pk[5], pk[6], pk[7]);
          st_flag(dz + hp * 16 * 544 * 4, pk[8]);
        };
        wgmma_fence();
#pragma unroll
        for (int q = 0; q < 17; q++) {
          if (q < 16) wgmma_ss_n40_tt(d[q >> 3], desc_lo(SB + (q < 8 ? OFF_S : OFF_B + 2 * SLOT), 1024) + w * (SLOT / 16) + 128 * (q & 7), desc_lo(SB + vreg(q & 7), 2560) + (w + (q >> 3) * 2) * 40, q & 7);
          else wgmma_r1_n128(acc, dm + w * 64, dcs, 0);
          if (q == 7 || q == KVS || q == 16) wgmma_commit();
          if (q == KVS) { mbar_wait2(x.fullA(x.ra.s), x.ra.ph, x.fullB(x.rb.s), x.rb.ph); wgmma_wait<1>(); prep(d[0]); send(0); bb_fence(x.goff); wgmma_fence(); }
        }
        gemm_issue<128, false>(acc, x, true); gemm_next<128>(x);
        wgmma_wait<1>();
        x.releaseA(h0); x.releaseA(h1); x.releaseB(2); x.releaseB(3);
        if (x.lane == 0) mbar_arrive(sb + BAR_SIGT);
        prep(d[1]);
        TSL_(4);
#pragma unroll 1
        for (int seg = 0; seg < 2; seg++) {
          const int n0 = w ? PS1 : PS0;
          gemm_run(acc, x, seg ? 15 - n0 : n0, seg, seg ? L : 0);
          if (seg == 0) send(1);
        }
      }
      gemm_end(acc, x);
      TSL_(5);
      {
        float dp[2][20], dn[2][20];
        uint32_t f[4][16];
        auto mma = [&](int h) {
          if (!(h & 1)) mbar_wait(sb + BAR_KV + h * 4, L >> 1);
          if (h == 0) TSL_(9);
          const uint32_t db = desc_lo(SB + OFF_S + h * 5120, 128);
          const uint32_t (&a)[16] = f[h];
          wgmma_fence();
          wgmma_rs_n40(dp[h & 1], a[0], a[1], a[2], a[3], db, 0);
          wgmma_rs_n40(dn[h & 1], a[8], a[9], a[10], a[11], db + 160, 0);
          wgmma_rs_n40(dp[h & 1], a[4], a[5], a[6], a[7], db + 80, 1);
          wgmma_rs_n40(dn[h & 1], a[12], a[13], a[14], a[15], db + 240, 1);
          wgmma_commit();
        };
        uint32_t xr[16];
        auto fin = [&](int h) {
          const uint32_t tile = x.aslot(x.held(h >> 1));
          if (!(h & 1)) img_load(xr, tile, x);
          float (&u)[20] = dp[h & 1];
          float (&v)[20] = dn[h & 1];
          fence_regs(u); fence_regs(v);
#pragma unroll
          for (int r = 0; r < 2; r++) {
            const float sp = u[16 + 2 * r], sn = v[16 + 2 * r];
            const float id = rcp(fmaf(fmaf(sp, L == 1 ? 0.065536f * 128 / 129 : 0.065536f, u[17 + 2 * r]), sn, v[17 + 2 * r] * sp)), aa = sn * id, cc = sp * id;
            uint32_t o[4];
#pragma unroll
            for (int t = 0; t < 4; t++) o[t] = pack2(fmaf(u[4 * t + 2 * r], aa, v[4 * t + 2 * r] * cc), fmaf(u[4 * t + 2 * r + 1], aa, v[4 * t + 2 * r + 1] * cc));
            o[2 * r + (h & 1)] = img_tag(o[2 * r + (h & 1)], false, 1, x);
            stg128(x.img(0, h >> 1) + r * 64 + (h & 1) * 32, make_uint4(o[0], o[1], o[2], o[3]));
            sts128(tile + r * 1024 + (h & 1) * 512 + x.so, o[0], o[1], o[2], o[3]);
          }
          if (h & 1) { if (h == 1) publish(0, x); img_unpack(acc + 16 * (h - 1), xr); }
        };
        auto scale = [&](int h) { hedgehog_scale<0>(acc + 16 * h, st, nullptr); };
        auto ex = [&](int h) { dual_exp_rcp(acc + 16 * h, f[h]); };
        scale(0);
        ex(0); scale(1); mma(0);
        ex(1); wgmma_wait<0>(); fin(0); bb_fence(x.goff); mma(1);
        wgmma_wait<0>(); fin(1); scale(2);
        ex(2); scale(3); if (UK & 1) bb_keep(acc, x.goff); mma(2);
        ex(3); wgmma_wait<0>(); fin(2); mma(3);
        wgmma_wait<0>(); fin(3);
      }
    }
    if (PW & 2) { mbar_wait(x.fullB(x.rb.s), x.rb.ph); fence_regs(acc); }
    fence_async_smem();
    wg_bar(w);
    TSL_(6);
    rewind2<NA>(x.ra);
    gemm_issue<128, false>(acc, x, PW & 2); gemm_next<128>(x);
    uint4* out = solid(P.out + goff + (x.warp * 16 + (x.lane >> 3)) * 256 + (x.lane & 7));
#pragma unroll 1
    for (int seg = L >= TSL ? 0 : 1; seg < 2; seg++) {
      gemm_run(acc, x, L >= TSL ? (seg ? TSK : 15 - TSK) : 15, seg, 10 + L);
      if (L >= TSL) {
        if (seg == 0 && w == 1) asm volatile("bar.sync 6, 256;" ::: "memory");
        if (seg == 1 && w == 0) asm volatile("bar.arrive 6, 256;" ::: "memory");
      }
    }
    gemm_end(acc, x);
    TSL_(7);
    rewind2<NA>(x.ra);
    out_epilogue(acc, r1, ts, out, L, x);
    TSL_(13);
  }
}

typedef unsigned long long u64;
template <class T> __device__ __forceinline__ T* early(T* p) { return (T*)__shfl_xor_sync(0xffffffffu, (u64)p, 1); }
__device__ __forceinline__ void pause(uint32_t GAP) {
  if (GAP) { uint32_t t0, t; asm volatile("mov.u32 %0, %%clock;" : "=r"(t0)); do { asm volatile("mov.u32 %0, %%clock;" : "=r"(t)); } while (t - t0 < GAP); }
}
__device__ __forceinline__ u64 order_table(int kind, int j) {
  const int i = threadIdx.x & 15;
  const unsigned v = (unsigned)(kind == 2 ? q_order(i, j) : kv_order(i, j, kind)) << (4 * (i & 7));
  return (u64)__reduce_or_sync(0xffffffffu, i < 8 ? 0u : v) << 32 | __reduce_or_sync(0xffffffffu, i < 8 ? v : 0u);
}

__device__ __forceinline__ void b_producer(const Params& P, uint32_t sb, unsigned vb) {
  const int j = cta_j(vb);
  const u64 t0 = order_table(0, j), t1 = order_table(1, j), t2 = order_table(2, j);
  Ring r = {PRE_B % NB, PRE_B < NB};
#pragma unroll 1
  for (int sg = 0; sg < 20; sg++) {
    const int L = sg / 5, p = sg - 5 * L, wt = L & 1;
    int n = p >= 3 ? 16 : (wt ? (p ? 16 - NJ : 2 * NJ) : (p ? 0 : (L ? 32 : 32 - PRE_B)));
    u64 tab = p == 3 ? t2 : (sg == 0 ? t0 >> (2 * PRE_B) : (p == 1 || p == 2 ? t1 >> (4 * NJ) : t1));
    const CUtensorMap* tm = p == 4 ? &P.mwo[wt] : &P.mw[wt ? 1 : L];
    const uint4* img = &g_wf[p != 3][j][0][0];
    int col = (p >= 3 ? 0 : (p == 2 ? 2048 : 1024)) + 128 * j;
    const int flip = p == 0 ? 3072 : 0;
    const bool fold = wt && p != 4;
    if (sg == 5 || sg == 8) { mbar_wait(sb + (sg == 5 ? BAR_WPHI : BAR_CS + 8), sg == 5); fence_async_global(); }
    if (DEFER && p == 4 && ((DEFL >> wt) & 1)) {
      Ring q = r;
      for (int u = 0; u < DEFER; u++) adv<NB>(q);
      mbar_wait(sb + BAR_EMPTYB + q.s * 8, q.ph);
    }
#pragma unroll 1
    for (; n > 0; n--) {
      const int kb = (int)tab & 15;
      mbar_wait(sb + BAR_EMPTYB + r.s * 8, r.ph);
      if (elect()) {
        mbar_expect_tx(sb + BAR_FULLB + r.s * 8, SLOT);
        if (fold && col < 2048) bulk_load(sb + OFF_B + r.s * SLOT, img + kb * 1024, SLOT, sb + BAR_FULLB + r.s * 8);
        else tma_load_w(sb + OFF_B + r.s * SLOT, tm, sb + BAR_FULLB + r.s * 8, col, kb);
      }
      adv<NB>(r);
      if (p == 2 && (n | 4) == 5) r.s = 4;
      col ^= flip;
      if (!(col & flip & 2048)) tab >>= 4;
    }
  }
}

__device__ __forceinline__ void a_loader(const Params& P, uint32_t sb, unsigned vb) {
  const int j = cta_j(vb), m = cta_m(vb);
  const u64 t1 = order_table(1, j), t2 = order_table(2, j);
  Ring r = {PRE_A % NA, PRE_A < NA};
  {
    u64 tab = order_table(0, j) >> (4 * PRE_A);
#pragma unroll 1
    for (int i = PRE_A; i < 33; i++) {
      if (i == 17) tab = t2;
      mbar_wait(sb + BAR_EMPTYA + r.s * 8, r.ph);
      if (elect()) {
        mbar_expect_tx(sb + BAR_FULLA + r.s * 8, SLOT);
        if (i != 14) tma_load_3d(sb + OFF_A + r.s * SLOT, &P.mx, sb + BAR_FULLA + r.s * 8, ((int)tab & 15) * 64, m * 64, 0);
        else {
          tma_load_w(sb + OFF_A + r.s * SLOT, &P.mw[1], sb + BAR_FULLA + r.s * 8, 1024 + 128 * j, m);
          mbar_expect_tx(sb + BAR_WPHI, 8192); tma_load_2d(sb + OFF_S + 4096, &P.mwphi, sb + BAR_WPHI, 0, 128 * j);
        }
        if (i == PF1 || i == PF2) tma_prefetch_w(&P.mwo[i == PF2], 128 * j, m);
      }
      adv<NA>(r);
      if (i != 14) tab >>= 4;
    }
  }
  const unsigned tag = get_tag(sb);
  unsigned kph = 0;
#pragma unroll 1
  for (int sg = 0; sg < 13; sg++) {
    const int L = sg >> 2, p = sg & 3;
    if (p == 0 && (L & 1)) {
#pragma unroll 1
      for (int h = 0; h < 2; h++) {
        poll_flags(&g_kvfflag[L >> 1][j][h][0], 16, 0xFFFFu, tag);
        TS(4, h ? 14 + L : 26 + L);
        for (int it = 0;; it++) {
          if (elect()) { mbar_expect_tx(sb + BAR_STAT + 8, 10240); bulk_load(sb + OFF_S + h * 10240, &g_kvfin[j][8 * h][0], 10240, sb + BAR_STAT + 8); }
          mbar_wait(sb + BAR_STAT + 8, kph);
          kph ^= 1;
          uint32_t a = 1u, o = 0u;
#pragma unroll
          for (int u = 0; u < 20; u++) { const uint32_t v = __float_as_uint(lds32f(sb + OFF_S + h * 10240 + u * 512 + (threadIdx.x & 31) * 16)); a &= v; o |= v; }
          if (__all_sync(0xffffffffu, (L == 1 ? a : ~o) & 1u)) break;
          fence_async_smem();
          if (it > (1 << 16)) __trap();
        }
        if (elect()) mbar_arrive(sb + BAR_KV + h * 8);
        TS(4, h ? 30 + L : (L == 1 ? 20 : 25));
      }
    }
    int n = p < 2 ? 14 : (p == 2 ? ((L & 1) ? 0 : 16 - NJ) : 16);
    u64 tab = p == 3 ? t2 : t1 >> (p < 2 ? 8 : 4 * NJ);
    const uint4* img = &g_img[p ? XBUF(L + 1) : 0][m][0][0];
#pragma unroll 1
    for (; n > 0; n--) {
      const uint4* src = early(img + ((int)tab & 15) * 1024);
      const uint32_t bar = sb + (p < 2 ? BAR_LAND : BAR_FULLA) + r.s * 8;
      mbar_wait(sb + BAR_EMPTYA + r.s * 8, r.ph);
      if (elect()) mbar_expect_tx(bar, SLOT);
      if (p < 2 && n == 14) {
        const int lane = threadIdx.x & 31;
        const unsigned* f = &g_hint[2 * L + p][(m & 14) + ((lane >> 3) & 1)][(~j & 4) + (lane & ND0)];
        mbar_wait(sb + BAR_SIGP + p * 8, L & 1);
        int it = 0;
        while (!__all_sync(0xffffffffu, ld_flag(f) == tag)) { if (++it > (1 << 22)) __trap(); }
        TS(2, p == 0 ? 5 + L * 8 : 9 + L * 8);
      }
      if (elect()) bulk_load(sb + OFF_A + r.s * SLOT, src, SLOT, bar);
      adv<NA>(r);
      tab >>= 4;
      pause(p < 2 && n > 10 ? G0 : 0);
    }
  }
}

__device__ __forceinline__ uint2 sum_packets(float (&a)[8], uint32_t addr, int n) {
  uint2 ok = make_uint2(~0u, 0u);
#pragma unroll 1
  for (int b = 0; b < n; b += KB) {
    uint4 v[KB];
#pragma unroll
    for (int u = 0; u < KB; u++) lds128(addr + (b + u) * 512, v[u].x, v[u].y, v[u].z, v[u].w);
#pragma unroll
    for (int u = 0; u < KB; u++) {
      ok.x &= v[u].x; ok.y |= v[u].x;
      a[0] += lo16(v[u].x); a[1] += hi16(v[u].x); a[2] += lo16(v[u].y); a[3] += hi16(v[u].y);
      a[4] += lo16(v[u].z); a[5] += hi16(v[u].z); a[6] += lo16(v[u].w); a[7] += hi16(v[u].w);
    }
  }
  return ok;
}
__device__ __forceinline__ void helper_bar() { asm volatile("bar.sync 4, 64;" ::: "memory"); }
__device__ __forceinline__ void helper(const Params& P, uint32_t sb, int w, unsigned vb) {
  const int j = cta_j(vb), m = cta_m(vb);
  if (w == 0) {
    if (elect()) {
      const unsigned t = atomicAdd(&g_ctr, 1u) / NCTA + 1u;
      asm volatile("st.shared.u32 [%0], %1;" ::"r"(sb + OFF_EPOCH), "r"(t) : "memory");
      mbar_arrive(sb + BAR_EPOCH);
    }
  }
  const unsigned tag = get_tag(sb);
  mbar_wait(sb + BAR_FULLB + 24, 0);
  const uint32_t stg = sb + OFF_T + w * 12288, stb = sb + BAR_STG + w * 24;
  Ring rs = {0, 0};
  uint32_t vs = 33 % NA, vph = 0;
  auto cs_image = [&](int L) {
      const int lane = lane_id();
      poll_flags(&g_csflag[L][j][0], 16, L ? CSNEED : 0xFFFu, tag);
#pragma unroll
      for (int p = 0; p < 3; p++) {
        const uint4 u = ldcg4(&g_cs[L][0][p * 1024 + 128 * j + lane * 4]), v = ldcg4(&g_cs[L][1][p * 1024 + 128 * j + lane * 4]);
        const float c0 = __uint_as_float(u.x) + __uint_as_float(v.x), c1 = __uint_as_float(u.y) + __uint_as_float(v.y);
        const float c2 = __uint_as_float(u.z) + __uint_as_float(v.z), c3 = __uint_as_float(u.w) + __uint_as_float(v.w);
        const uint32_t h0 = pack2(c0, c1), h1 = pack2(c2, c3), dst = sb + OFF_CS + (p * 16 + (lane >> 1)) * 96 + L * 48 + (lane & 1) * 8;
        sts64(dst, h0, h1); sts64(dst + 16, pack2(c0 - lo16(h0), c1 - hi16(h0)), pack2(c2 - lo16(h1), c3 - hi16(h1))); sts64(dst + 32, h0, h1);
        if (L == 0) { sts64(dst + 48, 0u, 0u); sts64(dst + 64, 0u, 0u); sts64(dst + 80, 0u, 0u); }
      }
      if (L == 0 && lane < 4) sts64(sb + OFF_CS + 4608 + lane * 8, 0u, 0u);
      fence_async_smem();
      __syncwarp();
      if (elect()) mbar_arrive(sb + BAR_CS + L * 8);
      TS(4, 2 + L * 2);
  };
#pragma unroll 1
  for (int L = 0; L < 4; L++) {
    const int lane = lane_id();
    if (L == 0) {
      {
        const int wt = m >= 12, col = ((0x2021 >> (m & 12)) & 3) * 1024 + 128 * j + (m & 3) * 32;
        const CUtensorMap* tm = &P.mcs[wt];
        __nanosleep(wt ? D2 : CD);
        constexpr int nb = 8;
        float a[8] = {0.f, 0.f, 0.f, 0.f, 0.f, 0.f, 0.f, 0.f};
#pragma unroll 1
        for (int b = -3; b < nb; b++) {
          if (b >= 0) {
            mbar_wait(stb + rs.s * 8, rs.ph);
            sum_packets(a, stg + rs.s * 4096 + lane * 16, 8);
            fence_async_smem();
            __syncwarp();
          }
          const uint32_t sl = b < 0 ? (rs.s + b + 3) % 3 : rs.s;
          if (b + 3 < nb && elect()) { mbar_expect_tx(stb + sl * 8, 4096); tma_load_2d(stg + sl * 4096, tm, stb + sl * 8, col, (w * (16 - nb) + b + 3) * 64); }
          if (b >= 0) adv<3>(rs); else pause(CP);
        }
#pragma unroll
        for (int u = 0; u < 8; u++) {
          a[u] += __shfl_xor_sync(0xffffffffu, a[u], 4); a[u] += __shfl_xor_sync(0xffffffffu, a[u], 8); a[u] += __shfl_xor_sync(0xffffffffu, a[u], 16);
        }
        if (lane < 4) {
          float4* dst = reinterpret_cast<float4*>(&g_cs[wt][w][col + lane * 8]);
          dst[0] = make_float4(a[0], a[1], a[2], a[3]); dst[1] = make_float4(a[4], a[5], a[6], a[7]);
        }
        helper_bar();
        if (w == 0 && elect()) { fence_gpu(); st_flag(&g_csflag[wt][j][m], tag); }
      }
      if (w == 0) TS(4, 1 + L * 2);
    }
    if (w == (L == 0)) {
      if (L > 0) {
        mbar_wait(sb + BAR_SIGP + 16, (L - 1) & 1);
        fence_async_global();
        __nanosleep(SD);
      }
      else if (S0) { mbar_wait(sb + BAR_WPHI, 0); __nanosleep(S0); }
#pragma unroll 1
      for (int p = 0; p < 2; p++) {
        uint4 v[8];
        for (int it = 0;; it++) {
          bool ok = true;
#pragma unroll
          for (int t = 0; t < 8; t++) v[t] = ld_pkt(&g_stats[m][p][t][lane]);
#pragma unroll
          for (int t = 0; t < 8; t++) ok = ok && (v[t].w & 15u) == seq4(tag, L);
          if (__all_sync(0xffffffffu, ok)) break;
          __nanosleep(200);
          if (it > (1 << 20)) __trap();
        }
        float s0 = 0.f, q0 = 0.f, s1 = 0.f, q1 = 0.f;
#pragma unroll
        for (int t = 0; t < 8; t++) { s0 += __uint_as_float(v[t].x); q0 += __uint_as_float(v[t].y); s1 += __uint_as_float(v[t].z); q1 += __uint_as_float(v[t].w & ~15u); }
        s0 *= (1.f / 1024); s1 *= (1.f / 1024);
        sts64(sb + OFF_MR + p * 256 + lane * 8, __float_as_uint(rsqrtf(fmaxf(q0 * (1.f / 1024) - s0 * s0, 0.f) + 1e-5f)),
              __float_as_uint(rsqrtf(fmaxf(q1 * (1.f / 1024) - s1 * s1, 0.f) + 1e-5f)));
#pragma unroll
        for (int r = 0; r < 2; r++) {
          const float v = -0.5f * (r ? s1 : s0);
          const uint32_t hh = pack2(v, v), hl = pack2(v, v - lo16(hh));
          const bool b = L & 1;
          sts128(sb + (b ? OFF_MB : OFF_MA) + p * 1024 + (lane >> 3) * 256 + r * 128 + (lane & 7) * 16, b ? 0u : hh, b ? hh << 16 : hl >> 16, b ? hl : 0u, 0u);
        }
      }
      fence_async_smem();
      __syncwarp();
      if (elect()) {
        mbar_arrive(sb + BAR_STAT);
      }
      TS(2, 0 + L * 8);
    }
    if (L < 2 && w == 0) cs_image(L);
    if (L & 1) {
      const uint32_t flip = L == 1 ? 0u : 1u;
      mbar_wait(sb + BAR_SIGT, 1);
      {
        int it = 0;
        if (PSL) __nanosleep(m < 8 ? PSL : PSL + 600);
        while (!__all_sync(0xffffffffu, (ld_flag(reinterpret_cast<const unsigned*>(&g_kvpart[j][m][w][512]) + (lane & 15) * 8) ^ flip) & 1u)) { if (PSL) __nanosleep(100); if (++it > (1 << 22)) __trap(); }
        fence_async_global();
      }
      if (w == 0) TS(4, 6 + L * 2);
      float a[8], z;
      for (int it = 0;; it++) {
        if (elect()) { mbar_expect_tx(stb + rs.s * 8, 8704); bulk_load(stg, &g_kvpart[j][m][w][0], 8704, stb + rs.s * 8); }
        mbar_wait(stb + rs.s * 8, rs.ph);
        if (w == 0) TS(4, 21 + L);
        adv<3>(rs);
#pragma unroll
        for (int u = 0; u < 8; u++) a[u] = 0.f;
        z = 0.f;
        uint32_t ok = 1u;
#pragma unroll
        for (int u = 0; u < 4; u++) { const float v = lds32f(stg + 8192 + u * 128 + (lane & 3) * 32 + (lane >> 2) * 4); z += v; ok &= __float_as_uint(v) ^ flip; }
        const uint2 tg = sum_packets(a, stg + lane * 16, 16);
        ok &= flip ? ~tg.y : tg.x;
        if (__all_sync(0xffffffffu, ok & 1u)) break;
        fence_async_smem();
        if (it > (1 << 16)) __trap();
      }
      {
        uint4* img = &g_kvfin[j][m][w * 8 + (lane >> 2)];
        uint32_t a0 = __float_as_uint(a[0]) >> 16;
        a0 += ~(a0 ^ flip) & 1u;
        st_v4(img + (lane & 3) * 16, __byte_perm(a0, pack2(0.f, a[1]), 0x7610), pack2(a[2], a[3]), pack2(a[4], a[5]), pack2(a[6], a[7]));
        const uint32_t cz = pack2(0.f, qsum(z)) | (0x3781u ^ flip);
        if (!(lane & 3)) st_v4(img + 64, cz, cz, cz, cz);
        __syncwarp();
        if (elect()) st_flag(&g_kvfflag[L >> 1][j][m >> 3][(m & 7) * 2 + w], tag);
      }
      if (w == 0) TS(4, 7 + L * 2);
    } else {
      mbar_wait(sb + BAR_SIGT, 0);
      if (w == 0) {
        if (elect()) { fence_gpu(); st_flag(&g_hflag[L >> 1][m][j][0], tag); st_flag(&g_kflag[j][m], tag); }
        if (L == 0) {
          __nanosleep(KSL);
          poll_flags(&g_kflag[j][0], 16, 0xFFFFu, tag);
          if (elect()) mbar_arrive(sb + BAR_WPHI);
        }
      } else if (m > 0) {
        poll_flags(&g_hflag[L >> 1][m - 1][j][0], 1, 1u, tag);
        if (elect()) { mbar_expect_tx(sb + BAR_HALO, 8192); bulk_load(sb + OFF_S + 8192, &g_halo[m - 1][j][0][0], 8192, sb + BAR_HALO); }
        TS(2, 2 + L * 8);
      }
    }
    if (w == 0) {
#pragma unroll 1
      for (int e = 0; e < (L < 3 ? 2 : 1); e++) {
        unsigned* flag = early(&g_hint[2 * L + e][m][j]);
        mbar_wait(sb + BAR_SIGP + e * 8, L & 1);
        TS(2, (e ? 6 : 3) + L * 8);
        pause(XD);
        if (elect()) st_flag(flag, tag);
      }
    } else {
#pragma unroll 1
      for (int i = 0; i < (L < 3 ? 28 : 14); i++) {
        const bool isx = i >= 14;
        const uint32_t a = sb + OFF_A + vs * SLOT + lane * 128 + ((lane >> 4) * 4 + (lane & 3)) * 16 + (lane & 12), code = img_code(isx, L + isx);
        for (int it = 0;; it++) {
          mbar_wait(sb + BAR_LAND + vs * 8, (vph >> vs) & 1);
          vph ^= 1u << vs;
          uint32_t bad = 0;
#pragma unroll
          for (int u = 0; u < 4; u++) bad |= __float_as_uint(lds32f(a + u * 4096)) ^ code;
          if (__all_sync(0xffffffffu, !(bad & img_mask(isx)))) break;
          if (it > (1 << 16)) __trap();
          fence_async_smem();
          if (elect()) {
            mbar_expect_tx(sb + BAR_LAND + vs * 8, SLOT);
            bulk_load(sb + OFF_A + vs * SLOT, &g_img[isx ? XBUF(L + 1) : 0][m][o_order(i - 14 * isx + 2, j)][0], SLOT, sb + BAR_LAND + vs * 8);
          }
        }
        if (elect()) mbar_arrive(sb + BAR_FULLA + vs * 8);
        if (++vs == NA) vs = 0;
      }
      vs = (vs + ((L & 1) ? 16 : 32 - NJ)) % NA;
    }
  }
}

__device__ __forceinline__ void spare(const Params& P, uint32_t sb, int id) {
  const int tid = threadIdx.x & 127, w = __shfl_sync(0xffffffffu, threadIdx.x >> 7, 0), lane = tid & 31, j = 2 * id + w;
  const uint32_t ring = w * 6 * SLOT, wp = 12 * SLOT + w * 8192, bar = sb + 13 * SLOT + w * 64;
  auto part = [&](int t) { return (t >> 4) ^ w; };
  auto load = [&](int t, uint32_t sl) {
    mbar_expect_tx(bar + sl * 8, t == 0 ? SLOT + 8192 : SLOT);
    tma_load_w(sb + ring + sl * SLOT, &P.mw[1], bar + sl * 8, part(t) * 1024 + 128 * j, t & 15);
  };
  if (tid == 0) {
    if (w == 2) sts32(sb + OFF_EPOCH, atomicAdd(&g_ctr, 1u) / NCTA + 1u);
    else {
      __nanosleep(D3);
#pragma unroll 1
      for (int t = 0; t < 5; t++) {
        mbar_init(bar + t * 8, 1);
        asm volatile("fence.mbarrier_init.release.cluster;" ::: "memory");
        load(t, t);
      }
      tma_load_2d(sb + wp, &P.mwphi, bar, 0, 128 * j);
    }
  }
  __syncthreads();
  const unsigned tag = get_tag<false>(sb);
  if (w == 2) {
    int it = 0;
    while ((int)(ld_flag(&g_ctr) - tag * NCTA) < 0) { if (++it > (1 << 22)) __trap(); }
    return;
  }
  Ring r = {4, 1};
  float d[64] = {}, cs[32] = {};
  auto fold = [&]() {
    mbar_wait(bar + r.s * 8, r.ph);
    wgmma_fence();
#pragma unroll
    for (int q = 0; q < 8; q++)
      wgmma_ss_n32(reinterpret_cast<float (&)[16]>(d[16 * (q >> 1)]), desc_lo(SB + ring + r.s * SLOT, 16) + (q >> 2) * 512 + (q & 3) * 2, desc_lo(SB + wp, 512) + q * 64, q & 1);
    wgmma_commit();
  };
  const int row = (tid >> 5) * 16 + (lane >> 2);
#pragma unroll 1
  for (int t = -1; t < 32; t++) {
    uint32_t f[32];
#pragma unroll
    for (int i = 0; i < 32; i++) { f[i] = pack2(d[2 * i], d[2 * i + 1]); cs[i & 30] += d[2 * i]; cs[i | 1] += d[2 * i + 1]; }
    wg_bar(w);
    if (tid == 0 && t >= 0 && t < 27) load(t + 5, r.s);
    __syncwarp();
    if (t < 31) adv<5>(r);
    fold();
    if (part(t) == 0 && t >= 0) {
#pragma unroll
      for (int q = 0; q < 8; q++)
        g_wf[0][j][t & 15][(q >> 2) * 512 + (row + 8 * (q & 1)) * 8 + (((q & 2) * 2 + (lane & 3)) ^ (lane >> 2))] =
            make_uint4(f[4 * (q & 6) + (q & 1)], f[4 * (q & 6) + (q & 1) + 2], f[4 * (q & 6) + (q & 1) + 4], f[4 * (q & 6) + (q & 1) + 6]);
    }
    wgmma_wait<0>();
    fence_regs(d);
    if ((t & 15) == 15) {
      if (t >= 0) {
        const uint32_t red = sb + ring + 5 * SLOT;
#pragma unroll
        for (int i = 0; i < 8; i++) sts128(red + (tid >> 2) * 512 + (i >> 1) * 128 + (lane & 3) * 32 + (i & 1) * 16, __float_as_uint(cs[4 * i]), __float_as_uint(cs[4 * i + 1]), __float_as_uint(cs[4 * i + 2]), __float_as_uint(cs[4 * i + 3]));
        wg_bar(w);
        float a = 0.f;
#pragma unroll 4
        for (int i = 0; i < 32; i++) a += lds32f(red + i * 512 + tid * 4);
        g_cs[1][0][part(t) * 1024 + j * 128 + tid] = a;
        wg_bar(w);
        if (tid == 0) {
          fence_gpu();
          st_flag(&g_csflag[1][j][part(t)], tag);
        }
        __syncwarp();
      }
#pragma unroll
      for (int i = 0; i < 32; i++) cs[i] = 0.f;
    }
  }
}

__global__ void __launch_bounds__(NTHREADS, 1) fused_kernel(const __grid_constant__ Params P) {
  extern __shared__ __align__(1024) uint8_t smem_raw[];
  constexpr uint32_t sb = SB;
  const int tid = threadIdx.x;
  const unsigned vb = vblock();
  if (vb >= 128) { spare(P, sb, vb - 128); return; }
  const int warp = __shfl_sync(0xffffffffu, tid >> 5, 0);
  if (elect()) {
    if (warp == 11) { prefetch_map(&P.mx); prefetch_map(&P.mw[0]); if (smem_u32(smem_raw) != SB) __trap(); }
    if (warp < 8) {
#pragma unroll
      for (int i = 0; i < 8; i++) mbar_init(sb + OFF_BAR + (warp * 8 + i) * 8, warp == 2 || warp == 3 ? 2 : (warp == 4 ? 8 : 1));
    }
    asm volatile("fence.mbarrier_init.release.cluster;" ::: "memory");
    if (warp < 2) {
      const int j = cta_j(vb);
#pragma unroll 1
      for (int i = 0; i < (warp == 0 ? PRE_B : PRE_A); i++) {
        const uint32_t bar = sb + BAR_FULLB + warp * 64 + i * 8;
        mbar_expect_tx(bar, SLOT);
        if (warp == 0) tma_load_w(sb + OFF_B + i * SLOT, &P.mw[0], bar, 1024 + (i & 1) * 1024 + 128 * j, kv_order(i >> 1, j, 0));
        else tma_load_3d(sb + OFF_A + i * SLOT, &P.mx, bar, kv_order(i, j, 0) * 64, cta_m(vb) * 64, 0);
      }
    }
  }
  if (tid == 0) TS(6, 0);
  __syncthreads();
  if (tid == 0) TS(6, 2);
  if (warp < 4) {
    reg_dealloc<PREGS>();
    if (warp & 2) helper(P, sb, warp & 1, vb);
    else if (warp & 1) a_loader(P, sb, vb);
    else b_producer(P, sb, vb);
  } else {
    reg_alloc<CREGS>();
    consumer(P, sb, (warp >> 2) - 1, vb);
  }
}

typedef CUresult (*EncodeFn)(CUtensorMap*, CUtensorMapDataType, cuuint32_t, void*, const cuuint64_t*, const cuuint64_t*,
                             const cuuint32_t*, const cuuint32_t*, CUtensorMapInterleave, CUtensorMapSwizzle,
                             CUtensorMapL2promotion, CUtensorMapFloatOOBfill);

void encode(EncodeFn fn, CUtensorMap* m, const void* ptr, int rank, const cuuint64_t* dims, const cuuint64_t* strides,
            const cuuint32_t* box, CUtensorMapSwizzle swz) {
  const cuuint32_t es[5] = {1, 1, 1, 1, 1};
  fn(m, CU_TENSOR_MAP_DATA_TYPE_BFLOAT16, rank, const_cast<void*>(ptr), dims, strides, box, es, CU_TENSOR_MAP_INTERLEAVE_NONE,
     swz, CU_TENSOR_MAP_L2_PROMOTION_L2_256B, CU_TENSOR_MAP_FLOAT_OOB_FILL_NONE);
}
void encode_w(EncodeFn fn, CUtensorMap* m, const void* ptr, int ncols, bool perm) {
  const cuuint64_t p = (cuuint64_t)ncols * 2, d[5] = {(cuuint64_t)ncols, 2, 4, 4, 32}, s[4] = {p, (perm ? 8 : 2) * p, (perm ? 2 : 8) * p, 32 * p};
  const cuuint32_t box[5] = {64, 2, 4, 4, 2};
  encode(fn, m, ptr, 5, d, s, box, CU_TENSOR_MAP_SWIZZLE_128B);
}

void encode_cs(EncodeFn fn, CUtensorMap* m, const void* ptr, int ncols) {
  const cuuint64_t d[2] = {(cuuint64_t)ncols, 1024}, s[1] = {(cuuint64_t)ncols * 2};
  const cuuint32_t box[2] = {32, 64};
  encode(fn, m, ptr, 2, d, s, box, CU_TENSOR_MAP_SWIZZLE_NONE);
}

}

extern "C" void kernel_launch(void* const* d_in, const int* in_sizes, int n_in, void* d_out, int out_size) {
  (void)in_sizes; (void)n_in; (void)out_size;
  void* fnp = nullptr;
  cudaDriverEntryPointQueryResult q;
  cudaGetDriverEntryPoint("cuTensorMapEncodeTiled", &fnp, cudaEnableDefault, &q);
  EncodeFn fn = (EncodeFn)fnp;
  Params P;
  {
    const cuuint64_t dims[3] = {1024, 1024, 2}, strides[2] = {4096, 2048};
    const cuuint32_t box[3] = {64, 64, 2};
    encode(fn, &P.mx, d_in[0], 3, dims, strides, box, CU_TENSOR_MAP_SWIZZLE_128B);
  }
  P.out = (uint4*)d_out;
  encode_w(fn, &P.mw[0], d_in[1], 3072, false);
  encode_w(fn, &P.mw[1], d_in[4], 3072, true);
  encode_w(fn, &P.mw[2], d_in[1], 3072, true);
  encode_w(fn, &P.mwo[0], d_in[2], 1024, true);
  encode_w(fn, &P.mwo[1], d_in[6], 1024, false);
  encode_cs(fn, &P.mcs[0], d_in[1], 3072);
  encode_cs(fn, &P.mcs[1], d_in[4], 3072);
  {
    const cuuint64_t dims[2] = {32, 1024}, strides[1] = {64};
    const cuuint32_t box[2] = {32, 128};
    encode(fn, &P.mwphi, d_in[5], 2, dims, strides, box, CU_TENSOR_MAP_SWIZZLE_64B);
  }
  cudaFuncSetAttribute(fused_kernel, cudaFuncAttributeMaxDynamicSharedMemorySize, SMEM_BYTES);
  fused_kernel<<<NCTA, NTHREADS, SMEM_BYTES, cudaStreamPerThread>>>(P);
}
```

```cpp
#include <cuda_runtime.h>
#include <cuda_bf16.h>
#include <cuda.h>
#include <stdint.h>

namespace {

__device__ __forceinline__ void wgmma_ss_n256(float (&d)[128], uint32_t da, uint32_t ha, uint32_t db, int sd) {
  asm volatile("{\n.reg .pred p;\n.reg .b64 a, b;\nsetp.ne.b32 p, %130, 0;\nmov.b64 a, {%128, %131};\nmov.b64 b, {%129, 0x40000040};\n"
    "wgmma.mma_async.sync.aligned.m64n256k16.f32.bf16.bf16 {%0,%1,%2,%3,%4,%5,%6,%7,%8,%9,%10,%11,%12,%13,%14,%15,%16,%17,%18,%19,%20,%21,%22,%23,%24,%25,%26,%27,%28,%29,%30,%31,%32,%33,%34,%35,%36,%37,%38,%39,%40,%41,%42,%43,%44,%45,%46,%47,%48,%49,%50,%51,%52,%53,%54,%55,%56,%57,%58,%59,%60,%61,%62,%63,%64,%65,%66,%67,%68,%69,%70,%71,%72,%73,%74,%75,%76,%77,%78,%79,%80,%81,%82,%83,%84,%85,%86,%87,%88,%89,%90,%91,%92,%93,%94,%95,%96,%97,%98,%99,%100,%101,%102,%103,%104,%105,%106,%107,%108,%109,%110,%111,%112,%113,%114,%115,%116,%117,%118,%119,%120,%121,%122,%123,%124,%125,%126,%127}, a, b, p, 1, 1, 0, 1;\n}\n"
    : "+f"(d[0]),"+f"(d[1]),"+f"(d[2]),"+f"(d[3]),"+f"(d[4]),"+f"(d[5]),"+f"(d[6]),"+f"(d[7]),"+f"(d[8]),"+f"(d[9]),"+f"(d[10]),"+f"(d[11]),"+f"(d[12]),"+f"(d[13]),"+f"(d[14]),"+f"(d[15]),"+f"(d[16]),"+f"(d[17]),"+f"(d[18]),"+f"(d[19]),"+f"(d[20]),"+f"(d[21]),"+f"(d[22]),"+f"(d[23]),"+f"(d[24]),"+f"(d[25]),"+f"(d[26]),"+f"(d[27]),"+f"(d[28]),"+f"(d[29]),"+f"(d[30]),"+f"(d[31]),"+f"(d[32]),"+f"(d[33]),"+f"(d[34]),"+f"(d[35]),"+f"(d[36]),"+f"(d[37]),"+f"(d[38]),"+f"(d[39]),"+f"(d[40]),"+f"(d[41]),"+f"(d[42]),"+f"(d[43]),"+f"(d[44]),"+f"(d[45]),"+f"(d[46]),"+f"(d[47]),"+f"(d[48]),"+f"(d[49]),"+f"(d[50]),"+f"(d[51]),"+f"(d[52]),"+f"(d[53]),"+f"(d[54]),"+f"(d[55]),"+f"(d[56]),"+f"(d[57]),"+f"(d[58]),"+f"(d[59]),"+f"(d[60]),"+f"(d[61]),"+f"(d[62]),"+f"(d[63]),"+f"(d[64]),"+f"(d[65]),"+f"(d[66]),"+f"(d[67]),"+f"(d[68]),"+f"(d[69]),"+f"(d[70]),"+f"(d[71]),"+f"(d[72]),"+f"(d[73]),"+f"(d[74]),"+f"(d[75]),"+f"(d[76]),"+f"(d[77]),"+f"(d[78]),"+f"(d[79]),"+f"(d[80]),"+f"(d[81]),"+f"(d[82]),"+f"(d[83]),"+f"(d[84]),"+f"(d[85]),"+f"(d[86]),"+f"(d[87]),"+f"(d[88]),"+f"(d[89]),"+f"(d[90]),"+f"(d[91]),"+f"(d[92]),"+f"(d[93]),"+f"(d[94]),"+f"(d[95]),"+f"(d[96]),"+f"(d[97]),"+f"(d[98]),"+f"(d[99]),"+f"(d[100]),"+f"(d[101]),"+f"(d[102]),"+f"(d[103]),"+f"(d[104]),"+f"(d[105]),"+f"(d[106]),"+f"(d[107]),"+f"(d[108]),"+f"(d[109]),"+f"(d[110]),"+f"(d[111]),"+f"(d[112]),"+f"(d[113]),"+f"(d[114]),"+f"(d[115]),"+f"(d[116]),"+f"(d[117]),"+f"(d[118]),"+f"(d[119]),"+f"(d[120]),"+f"(d[121]),"+f"(d[122]),"+f"(d[123]),"+f"(d[124]),"+f"(d[125]),"+f"(d[126]),"+f"(d[127])
    : "r"(da), "r"(db), "r"(sd), "r"(ha));
}
__device__ __forceinline__ void wgmma_ss_n128(float (&d)[64], uint32_t da, uint32_t ha, uint32_t db, int sd) {
  asm volatile("{\n.reg .pred p;\n.reg .b64 a, b;\nsetp.ne.b32 p, %66, 0;\nmov.b64 a, {%64, %67};\nmov.b64 b, {%65, 0x40000040};\n"
    "wgmma.mma_async.sync.aligned.m64n128k16.f32.bf16.bf16 {%0,%1,%2,%3,%4,%5,%6,%7,%8,%9,%10,%11,%12,%13,%14,%15,%16,%17,%18,%19,%20,%21,%22,%23,%24,%25,%26,%27,%28,%29,%30,%31,%32,%33,%34,%35,%36,%37,%38,%39,%40,%41,%42,%43,%44,%45,%46,%47,%48,%49,%50,%51,%52,%53,%54,%55,%56,%57,%58,%59,%60,%61,%62,%63}, a, b, p, 1, 1, 0, 1;\n}\n"
    : "+f"(d[0]),"+f"(d[1]),"+f"(d[2]),"+f"(d[3]),"+f"(d[4]),"+f"(d[5]),"+f"(d[6]),"+f"(d[7]),"+f"(d[8]),"+f"(d[9]),"+f"(d[10]),"+f"(d[11]),"+f"(d[12]),"+f"(d[13]),"+f"(d[14]),"+f"(d[15]),"+f"(d[16]),"+f"(d[17]),"+f"(d[18]),"+f"(d[19]),"+f"(d[20]),"+f"(d[21]),"+f"(d[22]),"+f"(d[23]),"+f"(d[24]),"+f"(d[25]),"+f"(d[26]),"+f"(d[27]),"+f"(d[28]),"+f"(d[29]),"+f"(d[30]),"+f"(d[31]),"+f"(d[32]),"+f"(d[33]),"+f"(d[34]),"+f"(d[35]),"+f"(d[36]),"+f"(d[37]),"+f"(d[38]),"+f"(d[39]),"+f"(d[40]),"+f"(d[41]),"+f"(d[42]),"+f"(d[43]),"+f"(d[44]),"+f"(d[45]),"+f"(d[46]),"+f"(d[47]),"+f"(d[48]),"+f"(d[49]),"+f"(d[50]),"+f"(d[51]),"+f"(d[52]),"+f"(d[53]),"+f"(d[54]),"+f"(d[55]),"+f"(d[56]),"+f"(d[57]),"+f"(d[58]),"+f"(d[59]),"+f"(d[60]),"+f"(d[61]),"+f"(d[62]),"+f"(d[63])
    : "r"(da), "r"(db), "r"(sd), "r"(ha));
}
__device__ __forceinline__ void wgmma_ss_n40_tt(float (&d)[20], uint32_t da, uint32_t db, int sd) {
  asm volatile("{\n.reg .pred p;\n.reg .b64 a, b;\nsetp.ne.b32 p, %22, 0;\nmov.b64 a, {%20, 0x40000040};\nmov.b64 b, {%21, 0x8};\n"
    "wgmma.mma_async.sync.aligned.m64n40k16.f32.bf16.bf16 {%0,%1,%2,%3,%4,%5,%6,%7,%8,%9,%10,%11,%12,%13,%14,%15,%16,%17,%18,%19}, a, b, p, 1, 1, 1, 1;\n}\n"
    : "+f"(d[0]),"+f"(d[1]),"+f"(d[2]),"+f"(d[3]),"+f"(d[4]),"+f"(d[5]),"+f"(d[6]),"+f"(d[7]),"+f"(d[8]),"+f"(d[9]),"+f"(d[10]),"+f"(d[11]),"+f"(d[12]),"+f"(d[13]),"+f"(d[14]),"+f"(d[15]),"+f"(d[16]),"+f"(d[17]),"+f"(d[18]),"+f"(d[19])
    : "r"(da), "r"(db), "r"(sd));
}
__device__ __forceinline__ void wgmma_ss_n32(float (&d)[16], uint32_t da, uint32_t db, int sd) {
  asm volatile("{\n.reg .pred p;\n.reg .b64 a, b;\nsetp.ne.b32 p, %18, 0;\nmov.b64 a, {%16, 0x40000040};\nmov.b64 b, {%17, 0x80000020};\n"
    "wgmma.mma_async.sync.aligned.m64n32k16.f32.bf16.bf16 {%0,%1,%2,%3,%4,%5,%6,%7,%8,%9,%10,%11,%12,%13,%14,%15}, a, b, p, 1, 1, 0, 1;\n}\n"
    : "+f"(d[0]),"+f"(d[1]),"+f"(d[2]),"+f"(d[3]),"+f"(d[4]),"+f"(d[5]),"+f"(d[6]),"+f"(d[7]),"+f"(d[8]),"+f"(d[9]),"+f"(d[10]),"+f"(d[11]),"+f"(d[12]),"+f"(d[13]),"+f"(d[14]),"+f"(d[15])
    : "r"(da), "r"(db), "r"(sd));
}
__device__ __forceinline__ void wgmma_rs_n40(float (&d)[20], uint32_t a0, uint32_t a1, uint32_t a2, uint32_t a3, uint32_t db, int sd) {
  asm volatile("{\n.reg .pred p;\n.reg .b64 b;\nsetp.ne.b32 p, %25, 0;\nmov.b64 b, {%24, 0x10};\n"
    "wgmma.mma_async.sync.aligned.m64n40k16.f32.bf16.bf16 {%0,%1,%2,%3,%4,%5,%6,%7,%8,%9,%10,%11,%12,%13,%14,%15,%16,%17,%18,%19}, {%20,%21,%22,%23}, b, p, 1, 1, 1;\n}\n"
    : "+f"(d[0]),"+f"(d[1]),"+f"(d[2]),"+f"(d[3]),"+f"(d[4]),"+f"(d[5]),"+f"(d[6]),"+f"(d[7]),"+f"(d[8]),"+f"(d[9]),"+f"(d[10]),"+f"(d[11]),"+f"(d[12]),"+f"(d[13]),"+f"(d[14]),"+f"(d[15]),"+f"(d[16]),"+f"(d[17]),"+f"(d[18]),"+f"(d[19])
    : "r"(a0), "r"(a1), "r"(a2), "r"(a3), "r"(db), "r"(sd));
}
__device__ __forceinline__ void wgmma_r1_n256(float (&d)[128], uint32_t da, uint32_t db, int sd) {
  asm volatile("{\n.reg .pred p;\n.reg .b64 a, b;\nsetp.ne.b32 p, %130, 0;\nmov.b64 a, {%128, 0x8};\nmov.b64 b, {%129, 0x6};\n"
    "wgmma.mma_async.sync.aligned.m64n256k16.f32.bf16.bf16 {%0,%1,%2,%3,%4,%5,%6,%7,%8,%9,%10,%11,%12,%13,%14,%15,%16,%17,%18,%19,%20,%21,%22,%23,%24,%25,%26,%27,%28,%29,%30,%31,%32,%33,%34,%35,%36,%37,%38,%39,%40,%41,%42,%43,%44,%45,%46,%47,%48,%49,%50,%51,%52,%53,%54,%55,%56,%57,%58,%59,%60,%61,%62,%63,%64,%65,%66,%67,%68,%69,%70,%71,%72,%73,%74,%75,%76,%77,%78,%79,%80,%81,%82,%83,%84,%85,%86,%87,%88,%89,%90,%91,%92,%93,%94,%95,%96,%97,%98,%99,%100,%101,%102,%103,%104,%105,%106,%107,%108,%109,%110,%111,%112,%113,%114,%115,%116,%117,%118,%119,%120,%121,%122,%123,%124,%125,%126,%127}, a, b, p, 1, 1, 0, 1;\n}\n"
    : "+f"(d[0]),"+f"(d[1]),"+f"(d[2]),"+f"(d[3]),"+f"(d[4]),"+f"(d[5]),"+f"(d[6]),"+f"(d[7]),"+f"(d[8]),"+f"(d[9]),"+f"(d[10]),"+f"(d[11]),"+f"(d[12]),"+f"(d[13]),"+f"(d[14]),"+f"(d[15]),"+f"(d[16]),"+f"(d[17]),"+f"(d[18]),"+f"(d[19]),"+f"(d[20]),"+f"(d[21]),"+f"(d[22]),"+f"(d[23]),"+f"(d[24]),"+f"(d[25]),"+f"(d[26]),"+f"(d[27]),"+f"(d[28]),"+f"(d[29]),"+f"(d[30]),"+f"(d[31]),"+f"(d[32]),"+f"(d[33]),"+f"(d[34]),"+f"(d[35]),"+f"(d[36]),"+f"(d[37]),"+f"(d[38]),"+f"(d[39]),"+f"(d[40]),"+f"(d[41]),"+f"(d[42]),"+f"(d[43]),"+f"(d[44]),"+f"(d[45]),"+f"(d[46]),"+f"(d[47]),"+f"(d[48]),"+f"(d[49]),"+f"(d[50]),"+f"(d[51]),"+f"(d[52]),"+f"(d[53]),"+f"(d[54]),"+f"(d[55]),"+f"(d[56]),"+f"(d[57]),"+f"(d[58]),"+f"(d[59]),"+f"(d[60]),"+f"(d[61]),"+f"(d[62]),"+f"(d[63]),"+f"(d[64]),"+f"(d[65]),"+f"(d[66]),"+f"(d[67]),"+f"(d[68]),"+f"(d[69]),"+f"(d[70]),"+f"(d[71]),"+f"(d[72]),"+f"(d[73]),"+f"(d[74]),"+f"(d[75]),"+f"(d[76]),"+f"(d[77]),"+f"(d[78]),"+f"(d[79]),"+f"(d[80]),"+f"(d[81]),"+f"(d[82]),"+f"(d[83]),"+f"(d[84]),"+f"(d[85]),"+f"(d[86]),"+f"(d[87]),"+f"(d[88]),"+f"(d[89]),"+f"(d[90]),"+f"(d[91]),"+f"(d[92]),"+f"(d[93]),"+f"(d[94]),"+f"(d[95]),"+f"(d[96]),"+f"(d[97]),"+f"(d[98]),"+f"(d[99]),"+f"(d[100]),"+f"(d[101]),"+f"(d[102]),"+f"(d[103]),"+f"(d[104]),"+f"(d[105]),"+f"(d[106]),"+f"(d[107]),"+f"(d[108]),"+f"(d[109]),"+f"(d[110]),"+f"(d[111]),"+f"(d[112]),"+f"(d[113]),"+f"(d[114]),"+f"(d[115]),"+f"(d[116]),"+f"(d[117]),"+f"(d[118]),"+f"(d[119]),"+f"(d[120]),"+f"(d[121]),"+f"(d[122]),"+f"(d[123]),"+f"(d[124]),"+f"(d[125]),"+f"(d[126]),"+f"(d[127])
    : "r"(da), "r"(db), "r"(sd));
}
__device__ __forceinline__ void wgmma_r1_n128(float (&d)[64], uint32_t da, uint32_t db, int sd) {
  asm volatile("{\n.reg .pred p;\n.reg .b64 a, b;\nsetp.ne.b32 p, %66, 0;\nmov.b64 a, {%64, 0x8};\nmov.b64 b, {%65, 0x6};\n"
    "wgmma.mma_async.sync.aligned.m64n128k16.f32.bf16.bf16 {%0,%1,%2,%3,%4,%5,%6,%7,%8,%9,%10,%11,%12,%13,%14,%15,%16,%17,%18,%19,%20,%21,%22,%23,%24,%25,%26,%27,%28,%29,%30,%31,%32,%33,%34,%35,%36,%37,%38,%39,%40,%41,%42,%43,%44,%45,%46,%47,%48,%49,%50,%51,%52,%53,%54,%55,%56,%57,%58,%59,%60,%61,%62,%63}, a, b, p, 1, 1, 0, 1;\n}\n"
    : "+f"(d[0]),"+f"(d[1]),"+f"(d[2]),"+f"(d[3]),"+f"(d[4]),"+f"(d[5]),"+f"(d[6]),"+f"(d[7]),"+f"(d[8]),"+f"(d[9]),"+f"(d[10]),"+f"(d[11]),"+f"(d[12]),"+f"(d[13]),"+f"(d[14]),"+f"(d[15]),"+f"(d[16]),"+f"(d[17]),"+f"(d[18]),"+f"(d[19]),"+f"(d[20]),"+f"(d[21]),"+f"(d[22]),"+f"(d[23]),"+f"(d[24]),"+f"(d[25]),"+f"(d[26]),"+f"(d[27]),"+f"(d[28]),"+f"(d[29]),"+f"(d[30]),"+f"(d[31]),"+f"(d[32]),"+f"(d[33]),"+f"(d[34]),"+f"(d[35]),"+f"(d[36]),"+f"(d[37]),"+f"(d[38]),"+f"(d[39]),"+f"(d[40]),"+f"(d[41]),"+f"(d[42]),"+f"(d[43]),"+f"(d[44]),"+f"(d[45]),"+f"(d[46]),"+f"(d[47]),"+f"(d[48]),"+f"(d[49]),"+f"(d[50]),"+f"(d[51]),"+f"(d[52]),"+f"(d[53]),"+f"(d[54]),"+f"(d[55]),"+f"(d[56]),"+f"(d[57]),"+f"(d[58]),"+f"(d[59]),"+f"(d[60]),"+f"(d[61]),"+f"(d[62]),"+f"(d[63])
    : "r"(da), "r"(db), "r"(sd));
}

__device__ __forceinline__ uint32_t smem_u32(const void* p) { return (uint32_t)__cvta_generic_to_shared(p); }
__device__ __forceinline__ void mbar_init(uint32_t bar, uint32_t cnt) { asm volatile("mbarrier.init.shared::cta.b64 [%0], %1;" ::"r"(bar), "r"(cnt)); }
__device__ __forceinline__ void mbar_expect_tx(uint32_t bar, uint32_t bytes) { asm volatile("mbarrier.arrive.expect_tx.shared::cta.b64 _, [%0], %1;" ::"r"(bar), "r"(bytes) : "memory"); }
__device__ __forceinline__ void mbar_arrive(uint32_t bar) { asm volatile("mbarrier.arrive.shared::cta.b64 _, [%0];" ::"r"(bar) : "memory"); }
__device__ __forceinline__ void mbar_arrive_n(uint32_t bar, uint32_t n) { asm volatile("mbarrier.arrive.shared::cta.b64 _, [%0], %1;" ::"r"(bar), "r"(n) : "memory"); }
__device__ __forceinline__ void mbar_wait(uint32_t bar, uint32_t parity) {
  asm volatile("{\n.reg .pred p;\nLAB_WAIT:\nmbarrier.try_wait.parity.shared::cta.b64 p, [%0], %1;\n@p bra DONE;\nbra LAB_WAIT;\nDONE:\n}" ::"r"(bar), "r"(parity) : "memory");
}
__device__ __forceinline__ void mbar_wait2(uint32_t a, uint32_t pa, uint32_t b, uint32_t pb) {
  asm volatile("{\n.reg .pred p, q;\nLAB_WAIT:\nmbarrier.try_wait.parity.shared::cta.b64 p, [%0], %1;\nmbarrier.try_wait.parity.shared::cta.b64 q, [%2], %3;\n"
               "and.pred p, p, q;\n@p bra DONE;\nbra LAB_WAIT;\nDONE:\n}" ::"r"(a), "r"(pa), "r"(b), "r"(pb) : "memory");
}
__device__ __forceinline__ void mbar_wait3(uint32_t a, uint32_t pa, uint32_t b, uint32_t pb) {
  asm volatile("{\n.reg .pred p, q, r;\nLAB_WAIT:\nmbarrier.try_wait.parity.shared::cta.b64 p, [%0], %1;\nmbarrier.try_wait.parity.shared::cta.b64 q, [%2], %3;\n"
               "mbarrier.try_wait.parity.shared::cta.b64 r, [%2+8], %3;\nand.pred p, p, q;\nand.pred p, p, r;\n@p bra DONE;\nbra LAB_WAIT;\nDONE:\n}" ::"r"(a), "r"(pa), "r"(b), "r"(pb) : "memory");
}
__device__ __forceinline__ bool mbar_probe2(uint32_t a, uint32_t pa, uint32_t b, uint32_t pb) {
  uint32_t ok;
  asm volatile("{\n.reg .pred p, q;\nmbarrier.test_wait.parity.shared::cta.b64 p, [%1], %2;\nmbarrier.test_wait.parity.shared::cta.b64 q, [%3], %4;\n"
               "and.pred p, p, q;\nselp.u32 %0, 1, 0, p;\n}" : "=r"(ok) : "r"(a), "r"(pa), "r"(b), "r"(pb) : "memory");
  return ok != 0;
}
__device__ __forceinline__ void tma_load_3d(uint32_t dst, const CUtensorMap* tm, uint32_t bar, int c0, int c1, int c2) {
  asm volatile("cp.async.bulk.tensor.3d.shared::cluster.global.mbarrier::complete_tx::bytes [%0], [%1, {%3, %4, %5}], [%2];"
               ::"r"(dst), "l"(tm), "r"(bar), "r"(c0), "r"(c1), "r"(c2) : "memory");
}
__device__ __forceinline__ void tma_load_2d(uint32_t dst, const CUtensorMap* tm, uint32_t bar, int c0, int c1) {
  asm volatile("cp.async.bulk.tensor.2d.shared::cluster.global.mbarrier::complete_tx::bytes [%0], [%1, {%3, %4}], [%2];"
               ::"r"(dst), "l"(tm), "r"(bar), "r"(c0), "r"(c1) : "memory");
}
__device__ __forceinline__ void tma_load_w(uint32_t dst, const CUtensorMap* tm, uint32_t bar, int col, int kb) {
#pragma unroll
  for (int q = 0; q < 2; q++)
    asm volatile("cp.async.bulk.tensor.5d.shared::cluster.global.mbarrier::complete_tx::bytes [%0], [%1, {%3, %4, %4, %4, %5}], [%2];"
                 ::"r"(dst + q * 8192), "l"(tm), "r"(bar), "r"(col + q * 64), "r"(0), "r"(2 * kb) : "memory");
}
__device__ __forceinline__ void tma_prefetch_w(const CUtensorMap* tm, int col, int kb) {
#pragma unroll
  for (int q = 0; q < 2; q++)
    asm volatile("cp.async.bulk.prefetch.tensor.5d.L2.global [%0, {%1, %2, %2, %2, %3}];" ::"l"(tm), "r"(col + q * 64), "r"(0), "r"(2 * kb) : "memory");
}
__device__ __forceinline__ void bulk_load(uint32_t dst, const void* g, uint32_t bytes, uint32_t bar) {
  asm volatile("cp.async.bulk.shared::cluster.global.mbarrier::complete_tx::bytes [%0], [%1], %2, [%3];" ::"r"(dst), "l"(g), "r"(bytes), "r"(bar) : "memory");
}
__device__ __forceinline__ void prefetch_map(const CUtensorMap* tm) { asm volatile("prefetch.tensormap [%0];" ::"l"(tm) : "memory"); }
__device__ __forceinline__ void fence_async_smem() { asm volatile("fence.proxy.async.shared::cta;" ::: "memory"); }
__device__ __forceinline__ void fence_async_global() { asm volatile("fence.proxy.async.global;" ::: "memory"); }
__device__ __forceinline__ void fence_gpu() { asm volatile("fence.release.gpu;" ::: "memory"); }
__device__ __forceinline__ void st_flag(unsigned* p, unsigned v) { asm volatile("st.relaxed.gpu.global.u32 [%0], %1;" ::"l"(p), "r"(v) : "memory"); }
__device__ __forceinline__ unsigned ld_flag(const unsigned* p) { unsigned v; asm volatile("ld.relaxed.gpu.global.u32 %0, [%1];" : "=r"(v) : "l"(p) : "memory"); return v; }
__device__ __forceinline__ uint4 ldcg4(const void* p) { uint4 v; asm volatile("ld.global.cg.v4.u32 {%0,%1,%2,%3}, [%4];" : "=r"(v.x), "=r"(v.y), "=r"(v.z), "=r"(v.w) : "l"(p)); return v; }
__device__ __forceinline__ uint4 ld_pkt(const uint4* p) {
  uint4 v; asm volatile("{\n.reg .b128 t;\nld.relaxed.gpu.global.b128 t, [%4];\nmov.b128 {%0,%1,%2,%3}, t;\n}" : "=r"(v.x), "=r"(v.y), "=r"(v.z), "=r"(v.w) : "l"(p) : "memory"); return v;
}
__device__ __forceinline__ void st_pkt(uint4* p, uint32_t a, uint32_t b, uint32_t c, uint32_t tag) {
  asm volatile("{\n.reg .b128 t;\nmov.b128 t, {%1,%2,%3,%4};\nst.relaxed.gpu.global.b128 [%0], t;\n}" ::"l"(p), "r"(a), "r"(b), "r"(c), "r"(tag) : "memory");
}
__device__ __forceinline__ void st_v4(uint4* p, uint32_t a, uint32_t b, uint32_t c, uint32_t d) { asm volatile("st.relaxed.gpu.global.v4.u32 [%0], {%1,%2,%3,%4};" ::"l"(p), "r"(a), "r"(b), "r"(c), "r"(d) : "memory"); }
__device__ __forceinline__ void stg128(uint4* p, uint4 v) { asm volatile("st.global.v4.u32 [%0], {%1,%2,%3,%4};" ::"l"(p), "r"(v.x), "r"(v.y), "r"(v.z), "r"(v.w) : "memory"); }
__device__ __forceinline__ void sts32(uint32_t addr, uint32_t a) { asm volatile("st.shared.u32 [%0], %1;" ::"r"(addr), "r"(a) : "memory"); }
__device__ __forceinline__ void sts64(uint32_t addr, uint32_t a, uint32_t b) { asm volatile("st.shared.v2.u32 [%0], {%1,%2};" ::"r"(addr), "r"(a), "r"(b) : "memory"); }
__device__ __forceinline__ uint32_t mul2(uint32_t a, uint32_t b) { uint32_t r; asm("mul.rn.bf16x2 %0, %1, %2;" : "=r"(r) : "r"(a), "r"(b)); return r; }
__device__ __forceinline__ uint32_t add2(uint32_t a, uint32_t b) { uint32_t r; asm("add.rn.bf16x2 %0, %1, %2;" : "=r"(r) : "r"(a), "r"(b)); return r; }
__device__ __forceinline__ bool elect() {
  uint32_t p; asm volatile("{\n.reg .pred q;\nelect.sync _|q, 0xffffffff;\nselp.u32 %0, 1, 0, q;\n}" : "=r"(p)); return p != 0;
}
__device__ __forceinline__ void wgmma_fence() { asm volatile("wgmma.fence.sync.aligned;" ::: "memory"); }
__device__ __forceinline__ void wgmma_commit() { asm volatile("wgmma.commit_group.sync.aligned;" ::: "memory"); }
template <int N> __device__ __forceinline__ void wgmma_wait() { asm volatile("wgmma.wait_group.sync.aligned %0;" ::"n"(N) : "memory"); }
template <int N> __device__ __forceinline__ void fence_regs(float (&d)[N]) {
#pragma unroll
  for (int i = 0; i < N; i++) asm volatile("" : "+f"(d[i])::"memory");
}
template <int R> __device__ __forceinline__ void reg_alloc() { asm volatile("setmaxnreg.inc.sync.aligned.u32 %0;" ::"n"(R)); }
template <int R> __device__ __forceinline__ void reg_dealloc() { asm volatile("setmaxnreg.dec.sync.aligned.u32 %0;" ::"n"(R)); }
__device__ __forceinline__ void wg_bar(int w) { asm volatile("bar.sync %0, 128;" ::"r"(w + 1) : "memory"); }
__device__ __forceinline__ constexpr uint32_t desc_lo(uint32_t addr, uint32_t lbo) { return (addr >> 4) + ((lbo >> 4) << 16); }
__device__ __forceinline__ uint32_t pack2(float lo, float hi) { uint32_t r; asm("cvt.rn.bf16x2.f32 %0, %1, %2;" : "=r"(r) : "f"(hi), "f"(lo)); return r; }
__device__ __forceinline__ float lo16(uint32_t v) { return __uint_as_float(v << 16); }
__device__ __forceinline__ float hi16(uint32_t v) { return __uint_as_float(v & 0xFFFF0000u); }
__device__ __forceinline__ float ex2(float x) { float r; asm("ex2.approx.ftz.f32 %0, %1;" : "=f"(r) : "f"(x)); return r; }
__device__ __forceinline__ float rcp(float x) { float r; asm("rcp.approx.ftz.f32 %0, %1;" : "=f"(r) : "f"(x)); return r; }
__device__ __forceinline__ uint32_t movm(uint32_t a) { uint32_t d; asm volatile("movmatrix.sync.aligned.m8n8.trans.b16 %0, %1;" : "=r"(d) : "r"(a)); return d; }
__device__ __forceinline__ void stsm4(uint32_t addr, uint32_t a, uint32_t b, uint32_t c, uint32_t d) {
  asm volatile("stmatrix.sync.aligned.m8n8.x4.shared.b16 [%0], {%1,%2,%3,%4};" ::"r"(addr), "r"(a), "r"(b), "r"(c), "r"(d) : "memory");
}
__device__ __forceinline__ void ldsm4(uint32_t addr, uint32_t (&r)[4]) {
  asm volatile("ldmatrix.sync.aligned.m8n8.x4.shared.b16 {%0,%1,%2,%3}, [%4];" : "=r"(r[0]), "=r"(r[1]), "=r"(r[2]), "=r"(r[3]) : "r"(addr) : "memory");
}
__device__ __forceinline__ void sts128(uint32_t addr, uint32_t a, uint32_t b, uint32_t c, uint32_t d) {
  asm volatile("st.shared.v4.u32 [%0], {%1,%2,%3,%4};" ::"r"(addr), "r"(a), "r"(b), "r"(c), "r"(d) : "memory");
}
__device__ __forceinline__ void lds128(uint32_t addr, uint32_t& a, uint32_t& b, uint32_t& c, uint32_t& d) {
  asm volatile("ld.shared.v4.u32 {%0,%1,%2,%3}, [%4];" : "=r"(a), "=r"(b), "=r"(c), "=r"(d) : "r"(addr) : "memory");
}
__device__ __forceinline__ float lds32f(uint32_t addr) { float v; asm volatile("ld.shared.f32 %0, [%1];" : "=f"(v) : "r"(addr) : "memory"); return v; }
__device__ __forceinline__ float2 lds64f(uint32_t addr) { float2 v; asm volatile("ld.shared.v2.f32 {%0,%1}, [%2];" : "=f"(v.x), "=f"(v.y) : "r"(addr) : "memory"); return v; }
__device__ __forceinline__ void mma16816(float (&d)[4], uint32_t a0, uint32_t a1, uint32_t a2, uint32_t a3, uint32_t b0, uint32_t b1) {
  asm("mma.sync.aligned.m16n8k16.row.col.f32.bf16.bf16.f32 {%0,%1,%2,%3}, {%4,%5,%6,%7}, {%8,%9}, {%0,%1,%2,%3};"
      : "+f"(d[0]), "+f"(d[1]), "+f"(d[2]), "+f"(d[3]) : "r"(a0), "r"(a1), "r"(a2), "r"(a3), "r"(b0), "r"(b1));
}
__device__ __forceinline__ void mma1688(float (&d)[4], uint32_t a0, uint32_t a1, uint32_t b0) {
  asm("mma.sync.aligned.m16n8k8.row.col.f32.bf16.bf16.f32 {%0,%1,%2,%3}, {%4,%5}, {%6}, {%0,%1,%2,%3};"
      : "+f"(d[0]), "+f"(d[1]), "+f"(d[2]), "+f"(d[3]) : "r"(a0), "r"(a1), "r"(b0));
}

__device__ __forceinline__ float qsum(float v) { v += __shfl_xor_sync(0xffffffffu, v, 1); v += __shfl_xor_sync(0xffffffffu, v, 2); return v; }

constexpr int NCTA = 132;
#define NB_ 6
#define NA_ 5
constexpr int NB = NB_;
constexpr int NA = NA_;
constexpr uint32_t SLOT = 16384;
constexpr uint32_t SB = 1024;
constexpr uint32_t OFF_B = 0;
constexpr uint32_t OFF_A = NB * SLOT;
constexpr uint32_t OFF_S = OFF_A + NA * SLOT;
constexpr uint32_t OFF_T = OFF_S + 20480;
constexpr uint32_t OFF_CS = OFF_T + 24576;
constexpr uint32_t OFF_MR = OFF_CS + 4640;
constexpr uint32_t OFF_BAR = OFF_MR + 512;
constexpr uint32_t OFF_MA = OFF_S, OFF_MB = OFF_CS - 2048;
constexpr uint32_t BAR_FULLB = OFF_BAR;
constexpr uint32_t BAR_FULLA = BAR_FULLB + 64;
constexpr uint32_t BAR_EMPTYB = BAR_FULLA + 64;
constexpr uint32_t BAR_EMPTYA = BAR_EMPTYB + 64;
constexpr uint32_t BAR_SIGP = BAR_EMPTYA + 64;
constexpr uint32_t BAR_SIGT = BAR_SIGP + 24;
constexpr uint32_t BAR_STAT = BAR_SIGP + 64;
constexpr uint32_t BAR_HALO = BAR_STAT + 16;
constexpr uint32_t BAR_CS = BAR_HALO + 8;
constexpr uint32_t BAR_WPHI = BAR_CS + 16;
constexpr uint32_t BAR_KV = BAR_WPHI + 8;
constexpr uint32_t BAR_STG = BAR_KV + 16;
constexpr uint32_t BAR_EPOCH = BAR_STG + 48;
constexpr uint32_t BAR_LAND = OFF_BAR + 7 * 64;
constexpr uint32_t OFF_EPOCH = OFF_BAR + 8 * 64;
static_assert(BAR_EPOCH < BAR_LAND, "barriers");
constexpr uint32_t SMEM_BYTES = OFF_EPOCH + 8;
static_assert(SMEM_BYTES <= 232448 && NB % 2 == 0 && NB <= 8 && NA <= 6, "smem");

#define CREGS 224
#define PREGS 56
#define PF1 19
#define PF2 21
#define PRE_A 2
#define PRE_B 4
#define CSB 4
#define CSNEED 0xF003u
#define XR 1
#define PS0 1
#define PS1 3
#define PSW 0
#define SD 1000
#define QORD 8
#define KSPLIT 12
#define KEEP 16
#define NJ 3
#define KSL 1000
#define PSL 0
#define KVS 12
#define D2 2000
#define D3 1500
#define G0 50
#define MAP 3
#define PMAP 0x76321450u
#define PW 1
#define XA 3
#define XS 1
#define CP 500
#define CD 0
#define S0 500
#define NS 2
#define XO 0
#define SW 2
#define SA 1
#define SB_ 4
#define XD 500
#define ND0 1
#define KB 8
#define DEFER 3
#define DEFL 2
#define TSK 3
#define TSL 3
constexpr int NTHREADS = 384;

struct Params {
  CUtensorMap mx;
  CUtensorMap mw[3];
  CUtensorMap mwo[2];
  CUtensorMap mcs[2];
  CUtensorMap mwphi;
  uint4* out;
};

#define XBUF(L) 1
__device__ __align__(256) uint4 g_img[XBUF(3) + 1][16][16][1024];
__device__ __forceinline__ uint32_t img_code(bool isx, int L) { return isx ? (L & 1) | (L & 2) << 15 : ~L & 1; }
__device__ __forceinline__ uint32_t img_mask(bool isx) { return isx ? 0x10001u : 1u; }
__device__ __align__(256) uint4 g_wf[2][8][16][1024];
__device__ __align__(256) uint4 g_stats[16][2][8][32];
__device__ __align__(256) uint4 g_halo[16][8][2][256];
__device__ __align__(256) float g_cs[2][2][3072];
__device__ __align__(256) uint4 g_kvpart[8][16][2][544];
__device__ __align__(256) uint4 g_kvfin[8][16][80];
__device__ __align__(256) unsigned g_hint[7][16][32];
__device__ __align__(256) unsigned g_hflag[2][16][8][32];
__device__ __align__(256) unsigned g_kvfflag[2][8][2][32];
__device__ __align__(256) unsigned g_csflag[2][8][32];
__device__ __align__(256) unsigned g_kflag[8][32];
__device__ unsigned g_ctr;
__device__ __forceinline__ unsigned vblock() {
  unsigned s;
  asm volatile("mov.u32 %0, %%smid;" : "=r"(s));
  const unsigned r = s & 1;
  s >>= 1;
  const unsigned t = s - 32, q = (t * 37) >> 8;
  const unsigned hi = s < 60 ? 12 + (t - 7 * q) * 8 + q : (s < 62 ? s + 4 : s - 58);
  unsigned b = 2 * (s < 32 ? (s & 7) * 8 + (s >> 3) : hi) + r;
  if (b < 128) b = (b & 15) | ((PMAP >> ((b >> 4) * 4)) & 7) << 4;
  if (s >= 62) b = 8 + 4 * r + s - 62;
  unsigned n;
  asm volatile("mov.u32 %0, %%nsmid;" : "=r"(n));
  return __shfl_sync(0xffffffffu, n == NCTA ? b : blockIdx.x, 0);
}
#define TS(who, id) do {} while (0)
#define TSW(id) do {} while (0)

#define TSMASK 0xFFFF
#define TSL_(a) do { if ((TSMASK >> (a)) & 1) TSW((a) + L * 12); } while (0)
__device__ __forceinline__ int cta_m(unsigned b) { return ((b >> 2) & 12) | (b & 3); }
__device__ __forceinline__ int cta_j(unsigned b) { return ((b >> 2) & 3) | ((b >> 4) & 4); }
struct Ring { uint32_t s, ph; };
template <int N> __device__ __forceinline__ void adv(Ring& r) { if (++r.s == N) { r.s = 0; r.ph ^= 1; } }
template <int N> __device__ __forceinline__ void rewind2(Ring& r) { if (r.s < 2) { r.s += N - 2; r.ph ^= 1; } else r.s -= 2; }
__device__ __forceinline__ int other_tile(int t, int j) { return (t == (j | 4) ? 7 : t) ^ (~j & 4); }
__device__ __forceinline__ int q_order(int i, int j) { return 2 * (i >= 14 ? j : other_tile(i >> 1, j)) + (i & 1); }
__device__ __forceinline__ int o_order(int i, int j) {
  if (i < 2) return 2 * j + i;
  const int odd = i >= 9;
  return 2 * other_tile(i - 2 - 7 * odd, j) + odd;
}
__device__ __forceinline__ int kv_order(int i, int j, int L) { return L > 0 ? o_order(i, j) : (i + 14 + 2 * (j & 4)) & 15; }

__device__ __forceinline__ unsigned poll_flags(const unsigned* f, int n, unsigned need, unsigned tag) {
  const int lane = threadIdx.x & 31;
  unsigned mask; int it = 0;
  do {
    unsigned v = lane < n ? ld_flag(f + lane) : 0u;
    mask = __ballot_sync(0xffffffffu, lane < n && v == tag);
    if (++it > (1 << 22)) __trap();
  } while ((mask & need) != need);
  fence_async_global();
  return mask;
}
template <bool WAIT = true>
__device__ __forceinline__ unsigned get_tag(uint32_t sb) {
  if (WAIT) mbar_wait(sb + BAR_EPOCH, 0);
  unsigned t; asm volatile("ld.shared.u32 %0, [%1];" : "=r"(t) : "r"(sb + OFF_EPOCH) : "memory");
  return t;
}

__device__ __forceinline__ int lane_id() { int l; asm volatile("mov.u32 %0, %%laneid;" : "=r"(l)); return l; }
__device__ __forceinline__ unsigned seq4(unsigned tag, int L) { return 8u | ((tag & 1u) << 2) | (unsigned)L; }
constexpr float LOG2E = 1.4426950408889634f;

__device__ __forceinline__ float bb_fence(int never, const void* p = &g_ctr, uint32_t keep = 0) {
  while (never < 0) never = ld_flag((const unsigned*)p) + keep;
  return __int_as_float(never >> 30);
}
__device__ __forceinline__ uint32_t solid(uint32_t v) { return __shfl_sync(0xffffffffu, v, threadIdx.x & 31); }
template <class T> __device__ __forceinline__ T* solid(T* p) { return (T*)__shfl_sync(0xffffffffu, (unsigned long long)p, threadIdx.x & 31); }
constexpr uint32_t HA128 = 0x40000040u, HA64 = 0x80000040u;
struct Ctx {
  static constexpr uint32_t sb = SB;
  uint32_t ab, da0;
  int w, warp, lane, g, c;
  int goff;
  __device__ __forceinline__ int m() const { return goff >> 14; }
  __device__ __forceinline__ int j() const { return (goff >> 4) & 7; }
  bool elected;
  Ring ra, rb;
  uint32_t pa, pb;
  uint32_t ha, k2;
  uint32_t mrow, mxor, mhi;
  __device__ __forceinline__ uint32_t aslot(uint32_t s) const { return ab + s * SLOT; }
  __device__ __forceinline__ uint32_t fullA(uint32_t s) const { return sb + BAR_FULLA + s * 8; }
  __device__ __forceinline__ uint32_t fullB(uint32_t s) const { return sb + BAR_FULLB + s * 8; }
  __device__ __forceinline__ void releaseA(uint32_t s) const { if (elected) mbar_arrive(sb + BAR_EMPTYA + s * 8); }
  __device__ __forceinline__ void releaseB(uint32_t s) const { if (elected) mbar_arrive(sb + BAR_EMPTYB + s * 8); }
  __device__ __forceinline__ uint32_t maddr(uint32_t tile, uint32_t ch) const { return tile + mrow + (((ch + mhi) ^ mxor) << 4); }
  __device__ __forceinline__ uint32_t oo() const { return warp * 128 + g * 4 + (c ^ (g >> 1)); }
  __device__ __forceinline__ uint4* img(int b, int hp) const { return ip + (b * 256 + hp) * 1024; }
  uint4* ip;
  uint32_t so;
  __device__ __forceinline__ uint32_t held(int i) const { return ra.s + i < 2 ? ra.s + i + NA - 2 : ra.s + i - 2; }
};

template <int N, bool FIRST, bool O = true>
__device__ __forceinline__ void gemm_issue(float (&acc)[N / 2], Ctx& x, bool ready = false) {
  if (!ready) {
    if (N == 256) mbar_wait3(x.fullA(x.ra.s), x.ra.ph, x.fullB(x.rb.s), x.rb.ph);
    else mbar_wait2(x.fullA(x.ra.s), x.ra.ph, x.fullB(x.rb.s), x.rb.ph);
  }
  const uint32_t da = x.da0 + x.ra.s * (SLOT / 16), db = desc_lo(SB + OFF_B, 8192) + x.rb.s * (SLOT / 16);
  wgmma_fence();
#pragma unroll
  for (int k = 0; k < 4; k++) {
    const uint32_t a = da + (k >> 1) * (O ? 32 : x.k2) + (k & 1) * 2, ha = O ? HA64 : x.ha;
    if constexpr (N == 256) wgmma_ss_n256(acc, a, ha, db + 128 * k, !(FIRST && k == 0));
    else wgmma_ss_n128(acc, a, ha, db + 128 * k, !(FIRST && k == 0));
  }
  wgmma_commit();
}
template <int N>
__device__ __forceinline__ void gemm_next(Ctx& x) {
  x.pa = x.ra.s; x.pb = x.rb.s;
  if (N == 256) x.rb.s++;
  adv<NA>(x.ra); adv<NB>(x.rb);
}
template <int N>
__device__ __forceinline__ void gemm_release(Ctx& x, bool relA) {
  if (relA) x.releaseA(x.pa);
  x.releaseB(x.pb);
  if (N == 256) x.releaseB(x.pb + 1);
}
template <int N>
__device__ __forceinline__ void gemm_retire(Ctx& x, bool relA) { wgmma_wait<1>(); gemm_release<N>(x, relA); gemm_next<N>(x); }
template <bool O = true>
__device__ __forceinline__ void gemm_run(float (&acc)[64], Ctx& x, int n, int hold, int n4 = 0) {
  bool ready = false;
#pragma unroll 1
  for (; n > 0; n--) {
    gemm_issue<128, false, O>(acc, x, ready);
    const uint32_t pa = x.pa, pb = x.pb;
    gemm_next<128>(x);
    ready = mbar_probe2(x.fullA(x.ra.s), x.ra.ph, x.fullB(x.rb.s), x.rb.ph);
    wgmma_wait<1>();
    if (n > hold) x.releaseA(pa);
    x.releaseB(pb);
  }
}
__device__ __forceinline__ void gemm_end(float (&acc)[64], Ctx& x) { wgmma_wait<0>(); fence_regs(acc); gemm_release<128>(x, false); }

__device__ __forceinline__ void rows_load(uint4* r, uint32_t tile, const Ctx& x) {
#pragma unroll
  for (int q = 0; q < 4; q++) {
    const uint32_t row = x.warp * 16 + 4 * q + (x.lane >> 3);
    lds128(tile + row * 128 + (((x.lane & 7) ^ (row & 7)) << 4), r[q].x, r[q].y, r[q].z, r[q].w);
  }
}
__device__ __forceinline__ void rows_store(const uint4* r, uint4* g) {
#pragma unroll
  for (int q = 0; q < 4; q++) stg128(g + q * 1024, r[q]);
}
__device__ __forceinline__ void publish(int id, const Ctx& x) { __syncwarp(); if (x.lane == 0) mbar_arrive(x.sb + BAR_SIGP + id * 8); }
__device__ __forceinline__ uint32_t img_tag(uint32_t v, bool isx, int L, const Ctx& x) {
  const uint32_t mk = ((x.lane ^ (x.warp * 4)) & 7) ? 0u : img_mask(isx);
  return (v & ~mk) | (img_code(isx, L) & mk);
}
__device__ __forceinline__ void img_tag(uint4 (&r)[4], bool isx, int L, const Ctx& x) {
#pragma unroll
  for (int q = 0; q < 4; q++) { uint32_t& v = q == 0 ? r[q].x : (q == 1 ? r[q].y : (q == 2 ? r[q].z : r[q].w)); v = img_tag(v, isx, L, x); }
}
__device__ __forceinline__ void img_store(const uint4 (&r)[4], uint4* g) {
#pragma unroll
  for (int q = 0; q < 4; q++) stg128(g + q * 32, r[q]);
}
__device__ __forceinline__ void img_sts(const uint4 (&r)[4], uint32_t tile, const Ctx& x) {
#pragma unroll
  for (int q = 0; q < 4; q++) sts128(tile + x.so + q * 512, r[q].x, r[q].y, r[q].z, r[q].w);
}
__device__ __forceinline__ void img_load(uint32_t (&v)[16], uint32_t tile, const Ctx& x) {
#pragma unroll
  for (int q = 0; q < 4; q++) lds128(tile + x.so + q * 512, v[4 * q], v[4 * q + 1], v[4 * q + 2], v[4 * q + 3]);
}
__device__ __forceinline__ void img_unpack(float* a, const uint32_t (&v)[16]) {
#pragma unroll
  for (int q = 0; q < 16; q++) { a[4 * (q & 7) + 2 * (q >> 3)] = lo16(v[q]); a[4 * (q & 7) + 2 * (q >> 3) + 1] = hi16(v[q]); }
}

template <int N>
__device__ __forceinline__ void stats_acc(const float* a, float (&t)[4]) {
#pragma unroll
  for (int i = 0; i < N; i++) { t[i & 2] += a[i]; t[(i & 2) + 1] = fmaf(a[i], a[i], t[(i & 2) + 1]); }
}
__device__ __forceinline__ void stats_send(float (&t)[4], int L, const Ctx& x) {
  const unsigned seq = seq4(get_tag<false>(x.sb), L);
#pragma unroll
  for (int q = 0; q < 4; q++) t[q] = qsum(t[q]);
  if (x.c == 0) st_pkt(&g_stats[x.m()][x.w][x.j()][x.warp * 8 + x.g], __float_as_uint(t[0]), __float_as_uint(t[1]), __float_as_uint(t[2]), (__float_as_uint(t[3]) & ~15u) | seq);
}
__device__ __forceinline__ void out_epilogue(const float (&acc)[64], uint4 (&r1)[4], float (&t)[4], uint4* g, int L, Ctx& x) {
  const uint32_t t0 = x.aslot(x.ra.s), t1 = x.aslot(x.ra.s + 1 == NA ? 0 : x.ra.s + 1);
  if (L == 3) {
#pragma unroll
    for (int p = 0; p < 8; p++) {
      stsm4(x.maddr(p < 4 ? t0 : t1, (p & 3) * 2), pack2(acc[8 * p], acc[8 * p + 1]), pack2(acc[8 * p + 2], acc[8 * p + 3]),
            pack2(acc[8 * p + 4], acc[8 * p + 5]), pack2(acc[8 * p + 6], acc[8 * p + 7]));
      if ((p & 3) == 3) { uint4 r[4]; __syncwarp(); rows_load(r, p < 4 ? t0 : t1, x); rows_store(r, g + (p >> 2) * 8); }
    }
  } else {
    auto pack16 = [&](uint4 (&r)[4], const float* a) {
#pragma unroll
      for (int q = 0; q < 4; q++) { const float* u = a + 16 * (q & 1) + (q & 2); r[q] = make_uint4(pack2(u[0], u[1]), pack2(u[4], u[5]), pack2(u[8], u[9]), pack2(u[12], u[13])); }
    };
    uint4 r0[4];
    pack16(r0, acc);
    img_tag(r0, true, L + 1, x);
    img_store(r0, x.img(XBUF(L + 1), 0));
    publish(1, x);
    const float z = bb_fence(x.goff);
    img_sts(r0, t0, x);
    pack16(r1, acc + 32);
    img_tag(r1, true, L + 1, x);
    img_sts(r1, t1, x);
    float u[4] = {z, z, z, z}, v[4] = {z, z, z, z};
    stats_acc<32>(acc, v);
    stats_acc<32>(acc + 32, u);
#pragma unroll
    for (int q = 0; q < 4; q++) t[q] = u[q] + v[q];
    mbar_wait2(x.fullB(x.rb.s), x.rb.ph, x.fullB(x.rb.s + 1), x.rb.ph);
    fence_async_smem();
    asm volatile("bar.sync %0, %1;" ::"r"(L == 1 ? x.w + 1 : 3), "r"(L == 1 ? 128 : 256) : "memory");
  }
}

struct Stats { float rstd0, rstd1; };
__device__ __forceinline__ Stats load_stats(int half, const Ctx& x) {
  const float2 u = lds64f(x.sb + OFF_MR + half * 256 + (x.warp * 8 + x.g) * 8);
  return {u.x, u.y};
}

template <int NH, int NK, class F>
__device__ __forceinline__ void hedgehog_scale(float* t, const Stats& st, const uint32_t* keep, F use) {
#pragma unroll
  for (int q = 0; q < 16 * NH; q++) t[q] *= ((q & 2) ? st.rstd1 : st.rstd0) * LOG2E;
  use();
  float m[4];
#pragma unroll
  for (int q = 0; q < 4 * NH; q++) {
    const float v = fmaxf(fmaxf(fabsf(t[4 * q]), fabsf(t[4 * q + 1])), fmaxf(fabsf(t[4 * q + 2]), fabsf(t[4 * q + 3])));
    m[q & 3] = q < 4 ? v : fmaxf(m[q & 3], v);
  }
  if (__builtin_expect(__any_sync(0xffffffffu, fmaxf(fmaxf(m[0], m[1]), fmaxf(m[2], m[3])) > 58.f), 0)) {
    float z[16 * NH + NK];
#pragma unroll
    for (int q = 0; q < 16 * NH + NK; q++) z[q] = q < 16 * NH ? t[q % (16 * NH)] : __uint_as_float(keep[q & 15]);
#pragma unroll 1
    for (int r = 0; r < 2 * NH; r++) {
      float hi = -INFINITY, lo = INFINITY;
#pragma unroll 1
      for (int i = 0; i < 16; i++) {
        const int k = (i & 6) * 2 + (i & 1) + (r & 1) * 2 + (r & 2) * 8;
        const float v = z[k];
        if (i < 8) { hi = fmaxf(hi, v); lo = fminf(lo, v); }
        else z[k] = v - fminf(fmaxf(v, lo), hi);
        if (i == 7) {
#pragma unroll 1
          for (int d = 1; d <= 2; d++) { hi = fmaxf(hi, __shfl_xor_sync(0xffffffffu, hi, d)); lo = fminf(lo, __shfl_xor_sync(0xffffffffu, lo, d)); }
          const float mid = 0.5f * hi + 0.5f * lo;
          hi = fmaxf(hi - 58.f, mid); lo = fminf(lo + 58.f, mid);
        }
      }
    }
#pragma unroll
    for (int q = 0; q < 16 * NH; q++) t[q] = z[q];
    use();
  }
}
__device__ __forceinline__ void dual_exp(const float* t, uint32_t (&f)[18], int never) {
  float e[KSPLIT];
#pragma unroll
  for (int q = 0; q < KSPLIT; q++) e[q] = ex2(q < 16 ? t[q] : -t[q & 15]);
  while (never < 0) {
#pragma unroll
    for (int i = 0; i < KSPLIT; i += 4) asm volatile("ld.shared.v4.f32 {%0,%1,%2,%3}, [%4];" : "=f"(e[i]), "=f"(e[i + 1]), "=f"(e[i + 2]), "=f"(e[i + 3]) : "r"(never + i) : "memory");
    never += __float_as_int(e[0]);
  }
#pragma unroll
  for (int q = 0; q < KSPLIT; q += 2) f[q >> 1] = pack2(e[q], e[q + 1]);
#pragma unroll
  for (int q = KSPLIT; q < 32; q += 2) f[q >> 1] = q < 16 ? pack2(ex2(t[q]), ex2(t[q + 1])) : pack2(ex2(-t[q & 15]), ex2(-t[(q & 15) + 1]));
#pragma unroll
  for (int sg = 0; sg < 2; sg++) {
    const uint32_t* u = f + 8 * sg;
    const uint32_t a = add2(add2(u[0], u[2]), add2(u[4], u[6])), b = add2(add2(u[1], u[3]), add2(u[5], u[7]));
    f[16 + sg] = add2(__byte_perm(a, b, 0x5410), __byte_perm(a, b, 0x7632));
  }
}
__device__ __forceinline__ void dual_exp_rcp(const float* t, uint32_t (&f)[16]) {
#pragma unroll
  for (int q = 0; q < 8; q++) {
    const float a = ex2(t[2 * q]), b = ex2(t[2 * q + 1]), r = rcp(a * b);
    f[q] = pack2(a, b); f[8 + q] = pack2(r * b, r * a);
  }
}
__device__ __forceinline__ void cta_bar() { asm volatile("bar.sync 3, 256;" ::: "memory"); }

template <int N> __device__ __forceinline__ void pin(const uint32_t* v, uint32_t addr) {
#pragma unroll
  for (int i = 0; i < N; i += 4)
    asm volatile("{\n.reg .pred p;\nsetp.eq.u32 p, %0, 0;\n@p st.shared.v4.u32 [%0], {%1,%2,%3,%4};\n}" ::"r"(addr), "r"(v[i]), "r"(v[i + 1]), "r"(v[i + 2]), "r"(v[i + 3]) : "memory");
}

__device__ __forceinline__ void consumer(const Params& P, uint32_t sb, int w, unsigned vb) {
  Ctx x;
  x.w = w;
  x.ab = sb + OFF_A + w * 8192; x.da0 = desc_lo(SB + OFF_A, 16) + w * 512;
  x.lane = threadIdx.x & 31; x.warp = __shfl_sync(0xffffffffu, (threadIdx.x >> 5) & 3, 0); x.g = x.lane >> 2; x.c = x.lane & 3;
  x.goff = (cta_m(vb) * 128 + w) * 128 + cta_j(vb) * 16;
  asm volatile("" : "+r"(x.goff));
  x.elected = (threadIdx.x & 127) == 0;
  x.ra = {0, 0}; x.rb = {0, 0}; x.pa = x.pb = 0;
  {
    const uint32_t row = x.warp * 16 + (x.lane & 15);
    x.mrow = row * 128; x.mxor = row & 7; x.mhi = x.lane >> 4;
  }
  const int goff = x.goff;
  x.ip = solid(&g_img[0][x.m()][2 * x.j()][w * 512 + x.oo()]);
  x.so = solid(16 * x.oo());
  uint4 r1[4];
  float ts[4] = {0.f, 0.f, 0.f, 0.f};
#pragma unroll
  for (int i = 0; i < 4; i++) r1[i] = make_uint4(0, 0, 0, 0);
  TSW(0);
  mbar_wait3(x.fullA(0), 0, x.fullB(0), 0);
#pragma unroll 1
  for (int L = 0; L < 4; L++) {
    float acc[64];
    constexpr uint32_t dcs = desc_lo(SB + OFF_CS, 0);
    if ((L & 1) == 0) {
    float kv[128];
    x.ha = L ? HA64 : HA128; x.k2 = L ? 32 : 4;
    gemm_issue<256, true, false>(kv, x, true); gemm_next<256>(x);
    {
      int i = 1;
#pragma unroll 1
      for (int seg = L ? NS - 1 : 0; seg <= NS; seg++) {
        const int end = seg < NS ? (L == 0 ? 3 + SA * ((x.j() + SW * w) & 3) + SB_ * seg : XA + 1) : 14 + L;
#pragma unroll 1
        do {
          gemm_issue<256, false, false>(kv, x);
          gemm_retire<256>(x, true);
          i++;
          if (i == 5) TSL_(8);
          if (i == 11) TSL_(10);
        } while (i != end);
        if (seg < NS && L == 0) {
          uint32_t v[16];
          float a[32];
#pragma unroll
          for (int q = 0; q < 4; q++) ldsm4(x.maddr(x.aslot(x.pa), 2 * q), reinterpret_cast<uint32_t (&)[4]>(v[4 * q]));
#pragma unroll
          for (int q = 0; q < 16; q++) { a[2 * q] = lo16(v[q]); a[2 * q + 1] = hi16(v[q]); }
          stats_acc<32>(a, ts);
          fence_regs(ts);
          wg_bar(w);
        }
        if (seg == NS - 1) {
          if (L > 0) { img_store(r1, x.img(XBUF(L), 1)); publish(2, x); }
          mbar_wait(sb + BAR_EPOCH, 0);
          stats_send(ts, L, x);
        }
      }
    }
      const Ring kt = x.ra;
      if (L == 0) adv<NA>(x.ra);
#pragma unroll 1
      for (int h = L; h < 2; h++) {
        float d[16];
        mbar_wait2(x.fullA(kt.s), kt.ph, sb + BAR_WPHI, 0);
        wgmma_fence();
#pragma unroll
        for (int q = 0; q < 2; q++) wgmma_ss_n32(d, x.da0 + kt.s * (SLOT / 16) + h * 4 + q * 2, desc_lo(SB + OFF_S + 4096, 512) + w * 256 + h * 128 + q * 64, q);
        wgmma_commit();
        gemm_issue<256, false, false>(kv, x);
        gemm_retire<256>(x, true);
        if (h) x.releaseA(kt.s);
        fence_regs(d);
        uint4* dst = &g_wf[1][x.j()][x.m()][w * 512 + (x.warp * 16 + x.g) * 8 + ((h * 4 + x.c) ^ x.g)];
        dst[0] = make_uint4(pack2(d[0], d[1]), pack2(d[4], d[5]), pack2(d[8], d[9]), pack2(d[12], d[13]));
        dst[64] = make_uint4(pack2(d[2], d[3]), pack2(d[6], d[7]), pack2(d[10], d[11]), pack2(d[14], d[15]));
      }
      const uint32_t dm = desc_lo(SB + OFF_MA, 0) + w * 64;
      mbar_wait2(sb + BAR_STAT, 0, sb + BAR_CS, 0);
      wgmma_fence();
      wgmma_r1_n256(kv, dm, dcs + 96, 1);
      wgmma_commit();
      const Stats st = load_stats(w, x);
      mbar_wait2(x.fullA(x.ra.s), x.ra.ph, x.fullB(x.rb.s), x.rb.ph);
      wgmma_wait<0>();
      fence_regs(kv);
      gemm_release<256>(x, true);
      TSL_(2);
      uint32_t P0[32], P1[32], PH[32];
#pragma unroll
      for (int t = 0; t < 16; t++) { P0[t] = pack2(kv[4 * t] * st.rstd0, kv[4 * t + 1] * st.rstd0); P1[t] = pack2(kv[4 * t + 2] * st.rstd1, kv[4 * t + 3] * st.rstd1); }
      pin<16>(P0, x.mrow + 16);
      {
#pragma unroll
        for (int q = 0; q < 4; q++) sts128((x.warp < 3 ? sb + OFF_T + w * 12288 + x.warp * 4096 : sb + OFF_S + 16384 + w * 2048) + x.lane * 16 + q * 512, P1[4 * q], P1[4 * q + 1], P1[4 * q + 2], P1[4 * q + 3]);
      }
      wgmma_fence();
      wgmma_r1_n128(acc, dm, dcs, 0);
      gemm_issue<128, false, false>(acc, x, PW & 1); gemm_next<128>(x);
      TSL_(3);
#pragma unroll
      for (int s = 0; s < 4; s++) {
#pragma unroll
        for (int t = 16 + 8 * (s & 1); t < 24 + 8 * (s & 1); t++) {
          if (s < 2) P1[t] = movm(pack2(kv[4 * t + 2] * st.rstd1, kv[4 * t + 3] * st.rstd1));
          else P0[t] = movm(pack2(kv[4 * t] * st.rstd0, kv[4 * t + 1] * st.rstd0));
        }
        if (s < 3) { gemm_issue<128, false, false>(acc, x); gemm_retire<128>(x, true); }
        if (s == 1) {
          if (x.warp < 3) {
#pragma unroll
            for (int q = 4; q < 8; q++) sts128(sb + OFF_T + w * 12288 + x.warp * 4096 + x.lane * 16 + q * 512, P1[4 * q], P1[4 * q + 1], P1[4 * q + 2], P1[4 * q + 3]);
          } else {
            uint4* dst = &g_halo[x.m()][x.j()][w][x.lane];
#pragma unroll
            for (int q = 0; q < 8; q++) dst[q * 32] = make_uint4(P1[4 * q], P1[4 * q + 1], P1[4 * q + 2], P1[4 * q + 3]);
          }
          publish(3, x);
          gemm_issue<128, false, false>(acc, x);
          gemm_retire<128>(x, true);
        }
      }
      TSL_(4);
      gemm_run<false>(acc, x, 10, 0);
      gemm_issue<128, false, false>(acc, x);
      {
        wg_bar(w);
        uint32_t tr = sb + OFF_T + w * 12288 + (x.warp - 1) * 4096;
        if (x.warp == 0) {
          tr = x.m() > 0 ? sb + OFF_S + 8192 + w * 4096 : tr + 4096;
          if (x.m() > 0) mbar_wait(sb + BAR_HALO, L >> 1);
        }
#pragma unroll
        for (int q = 0; q < 8; q++) lds128(tr + x.lane * 16 + q * 512, PH[4 * q], PH[4 * q + 1], PH[4 * q + 2], PH[4 * q + 3]);
      }
      gemm_retire<128>(x, false);
      gemm_end(acc, x);
      TSL_(5);
      const bool first = (x.m() == 0) && (x.warp == 0);
      const bool hi0 = 2 * x.c > x.g, hi1 = 2 * x.c + 1 > x.g;
      const uint32_t mhi = (hi0 ? 0xFFFFu : 0u) | (hi1 ? 0xFFFF0000u : 0u);
      const float sc0 = st.rstd0 * (0.17677669529663687f * LOG2E), sc1 = st.rstd1 * (0.17677669529663687f * LOG2E);
#pragma unroll
      for (int hp = 0; hp < 2; hp++) {
        const uint32_t tile = x.aslot(x.held(hp));
        uint32_t px[2], py[2];
        float s[2][3][4];
#pragma unroll
        for (int u = 0; u < 2; u++) {
#pragma unroll
          for (int q = 0; q < 12; q++) s[u][q >> 2][q & 3] = 0.f;
#pragma unroll
          for (int ks = 0; ks < 2; ks++) {
            const int t = 8 * hp + 4 * u + 2 * ks;
            const uint32_t a0 = pack2(acc[4 * t], acc[4 * t + 1]), a1 = pack2(acc[4 * t + 2], acc[4 * t + 3]);
            const uint32_t a2 = pack2(acc[4 * t + 4], acc[4 * t + 5]), a3 = pack2(acc[4 * t + 6], acc[4 * t + 7]);
            mma16816(s[u][0], a0, a1, a2, a3, PH[t], PH[t + 1]);
            mma16816(s[u][1], a0, a1, a2, a3, P0[t], P0[t + 1]);
            mma16816(s[u][2], a0, a1, a2, a3, P1[t], P1[t + 1]);
          }
        }
        float e[2][4], r[2][2];
#pragma unroll
        for (int u = 0; u < 2; u++) {
          e[u][0] = (hi0 ? s[u][0][0] : s[u][1][0]) * sc0; e[u][1] = (hi1 ? s[u][0][1] : s[u][1][1]) * sc0;
          e[u][2] = (hi0 ? s[u][1][2] : s[u][2][2]) * sc1; e[u][3] = (hi1 ? s[u][1][3] : s[u][2][3]) * sc1;
          if (first) { if (hi0) e[u][0] = -1e30f; if (hi1) e[u][1] = -1e30f; }
          r[u][0] = fmaxf(e[u][0], e[u][1]); r[u][1] = fmaxf(e[u][2], e[u][3]);
        }
#pragma unroll
        for (int d = 1; d <= 2; d++)
#pragma unroll
          for (int q = 0; q < 4; q++) r[q >> 1][q & 1] = fmaxf(r[q >> 1][q & 1], __shfl_xor_sync(0xffffffffu, r[q >> 1][q & 1], d));
#pragma unroll
        for (int u = 0; u < 2; u++) {
#pragma unroll
          for (int q = 0; q < 4; q++) e[u][q] = ex2(e[u][q] - r[u][q >> 1]);
          r[u][0] = e[u][0] + e[u][1]; r[u][1] = e[u][2] + e[u][3];
        }
#pragma unroll
        for (int d = 1; d <= 2; d++)
#pragma unroll
          for (int q = 0; q < 4; q++) r[q >> 1][q & 1] += __shfl_xor_sync(0xffffffffu, r[q >> 1][q & 1], d);
#pragma unroll
        for (int u = 0; u < 2; u++) {
          const float rx = rcp(r[u][0]), ry = rcp(r[u][1]);
          px[u] = pack2(e[u][0] * rx, e[u][1] * rx); py[u] = pack2(e[u][2] * ry, e[u][3] * ry);
        }
        uint32_t o[8][2];
        uint4 ro[4];
#pragma unroll
        for (int q = 0; q < 8; q++) {
          float d[4] = {0.f, 0.f, 0.f, 0.f};
          const int t = 16 + 8 * hp + q, u = q >> 2;
          mma16816(d, px[u] & mhi, 0u, px[u] & ~mhi, py[u] & mhi, PH[t], P0[t]);
          mma1688(d, 0u, py[u] & ~mhi, P1[t]);
          o[q][0] = pack2(d[0], d[1]); o[q][1] = pack2(d[2], d[3]);
        }
#pragma unroll
        for (int q = 0; q < 4; q++) ro[q] = make_uint4(o[4 * (q & 1)][q >> 1], o[4 * (q & 1) + 1][q >> 1], o[4 * (q & 1) + 2][q >> 1], o[4 * (q & 1) + 3][q >> 1]);
        img_tag(ro, false, 0, x);
        img_store(ro, x.img(0, hp));
        if (hp == 0) publish(0, x);
        uint32_t xs[16];
        if (L) img_load(xs, tile, x);
        else {
#pragma unroll
          for (int q = 0; q < 4; q++) {
            uint32_t v[4];
            ldsm4(x.maddr(tile, 2 * q), v);
            xs[2 * q] = v[0]; xs[8 + 2 * q] = v[1]; xs[2 * q + 1] = v[2]; xs[9 + 2 * q] = v[3];
          }
          __syncwarp();
        }
        img_sts(ro, tile, x);
        img_unpack(acc + 32 * hp, xs);
      }
    } else {
      float kv[128];
      float (&kv0)[64] = reinterpret_cast<float (&)[64]>(kv[0]);
      float (&kv1)[64] = reinterpret_cast<float (&)[64]>(kv[64]);
      auto mma8 = [&](uint32_t as, uint32_t bs, int i, bool fence) {
        const uint32_t da = desc_lo(SB + OFF_A, 16) + as * (SLOT / 16), db = desc_lo(SB + OFF_B, 8192) + bs * (SLOT / 16);
        if (fence) wgmma_fence();
#pragma unroll
        for (int k = 0; k < 4; k++) {
          wgmma_ss_n128(kv0, da + (k >> 1) * 32 + (k & 1) * 2, HA64, db + 128 * k, i + k);
          wgmma_ss_n128(kv1, da + 512 + (k >> 1) * 32 + (k & 1) * 2, HA64, db + 128 * k, i + k);
        }
        wgmma_commit();
      };
      constexpr uint32_t dm = desc_lo(SB + OFF_MB, 0);
      auto relB = [&](uint32_t s) { mbar_arrive_n(sb + BAR_EMPTYB + s * 8, 2); };
      auto skip = [&]() {
#pragma unroll
        for (int q = 0; q < 6 - NJ; q++) adv<NA>(x.ra);
        x.rb.s = w ? (2 + NJ) % 6 : 4;
        if (!w && NJ < 4) x.rb.ph ^= 1;
      };
      static_assert(NA == 5 && NB == 6, "ring arithmetic");
      mma8(x.ra.s, x.rb.s + w, 0, true);
      gemm_next<256>(x);
#pragma unroll 1
      for (int i = 1; i < NJ; i++) {
        mbar_wait2(x.fullA(x.ra.s), x.ra.ph, x.fullB(x.rb.s + w), x.rb.ph);
        mma8(x.ra.s, x.rb.s + w, 1, true);
        if (!XO && i == XR) { img_store(r1, x.img(XBUF(L), 1)); publish(2, x); }
        if (!XO && i == XS) stats_send(ts, L, x);
        wgmma_wait<1>();
        if (x.elected) { x.releaseA(x.pa); relB(x.pb + w); }
        gemm_next<256>(x);
        if (XO && i == XR) { img_store(r1, x.img(XBUF(L), 1)); publish(2, x); stats_send(ts, L, x); }
      }
      if (w) {
        wgmma_wait<0>();
        if (x.elected) { x.releaseA(x.pa); relB(x.pb + 1); }
        skip();
        asm volatile("bar.sync 7, 256;" ::: "memory");
      }
      TSL_(8);
      {
        const int t = lane_id() + 32 * x.warp;
        uint32_t mask = t < 2 ? ((w ? (t ? 0xFF3Fu : 0x3FFFu) : 0xFFFFu) >> (NJ - 1)) & (w ? ~1u : ~0u) : 0u, cnt = 1 + t;
        bool ready = false;
#pragma unroll 1
        for (int i = NJ; i < 16; i++) {
          if (!ready) mbar_wait2(x.fullA(x.ra.s), x.ra.ph, x.fullB(x.rb.s), x.rb.ph);
          mma8(x.ra.s, x.rb.s, 1, true);
          const uint32_t bar = sb + (t ? BAR_EMPTYB + x.pb * 8 : BAR_EMPTYA + x.pa * 8);
          gemm_next<128>(x);
          if (w && (i | 4) == 15) x.rb.s = 4;
          ready = mbar_probe2(x.fullA(x.ra.s), x.ra.ph, x.fullB(x.rb.s), x.rb.ph);
          wgmma_wait<1>();
          if (mask & 1) mbar_arrive_n(bar, cnt);
          mask >>= 1; cnt = 2;
          if (i == 8 && w) asm volatile("bar.arrive 9, 256;" ::: "memory");
          if (i == 9) TSL_(10);
        }
        mbar_wait2(sb + BAR_STAT, 1, sb + BAR_CS + 8, 0);
        wgmma_fence();
        wgmma_r1_n128(kv0, dm, dcs + 96 + 96 * w, 1);
        wgmma_r1_n128(kv1, dm + 64, dcs + 96 + 96 * w, 1);
        wgmma_commit();
        if (w == 0) asm volatile("bar.arrive 7, 256;" ::: "memory");
        wgmma_wait<1>();
        if (mask & 1) mbar_arrive_n(sb + (t ? BAR_EMPTYB + x.pb * 8 : BAR_EMPTYA + x.pa * 8), 2);
      }
      const Stats s0 = load_stats(0, x), s1 = load_stats(1, x), st = w ? s1 : s0;
      if (w == 0) skip();
      const uint32_t h0 = x.held(0), h1 = x.held(1);
      auto vreg = [&](int ks) { return ks < 6 ? OFF_A + (ks < 3 ? h0 * SLOT : h1 * SLOT - 15360) + ks * 5120 : OFF_S + 2048 + ks * 5120; };
      uint32_t tV[2], uu[4];
#pragma unroll
      for (int hf = 0; hf < 2; hf++) {
        tV[hf] = sb + vreg(4 * hf + x.warp) + ((x.lane >> 3) & 1) * 2560 + (x.lane & 7) * 16 + x.mhi * 128;
        const float i0 = rcp(hf ? s1.rstd0 : s0.rstd0), i1 = rcp(hf ? s1.rstd1 : s0.rstd1);
        const uint32_t h = pack2(i0, i1);
        uu[2 * hf] = pack2(lo16(h), i0 - lo16(h)); uu[2 * hf + 1] = pack2(hi16(h), i1 - hi16(h));
        asm volatile("" : "+r"(tV[hf]), "+r"(uu[2 * hf]), "+r"(uu[2 * hf + 1])::"memory");
      }
      wgmma_wait<0>();
      fence_regs(kv);
      TSL_(2);
      if (w == 0) {
        uint32_t f[2][18], ad[4];
#pragma unroll
        for (int q = 0; q < 18; q++) f[1][q] = 0u;
#pragma unroll
        for (int q = 0; q < 4; q++) ad[q] = x.maddr(sb + OFF_S, 2 * q);
        auto norm = [&](int un) {
          uint32_t* u = f[un & 1];
          const Stats& sn = (un & 2) ? s1 : s0;
#pragma unroll
          for (int sg = 0; sg < 2; sg++) {
            uint32_t v = u[16 + sg];
            v = add2(v, __shfl_xor_sync(0xffffffffu, v, 1)); v = add2(v, __shfl_xor_sync(0xffffffffu, v, 2));
            const float a = rcp(lo16(v)) * sn.rstd0, b = rcp(hi16(v)) * sn.rstd1;
            const uint32_t r0 = pack2(a, a), r1_ = pack2(b, b);
#pragma unroll
            for (int q = 8 * sg; q < 8 * sg + 8; q++) u[q] = mul2(u[q], (q & 1) ? r1_ : r0);
#pragma unroll
            for (int q = 2 * sg; q < 2 * sg + 2; q++) stsm4(ad[q] + (un & 1) * SLOT + (un >> 1) * 8192, u[4 * q], u[4 * q + 1], u[4 * q + 2], u[4 * q + 3]);
          }
        };
        auto unit = [&](int un) { return kv + ((un >> 1) & 1) * 64 + (un & 1) * 16 + (un >> 2) * 32; };
        hedgehog_scale<1, 0>(kv, s0, nullptr, [] {});
#pragma unroll 1
        for (int it = 0;; it++) {
#pragma unroll
          for (int un = 0; un < 4; un++) {
            if (un == 1) {
              if (it) asm volatile("bar.sync 9, 256;" ::: "memory");
#pragma unroll
              for (int q = 0; q < 4; q++) ad[q] -= it * (OFF_S - OFF_B - 2 * SLOT);
            }
            norm((un + 3) & 3);
            dual_exp(unit(un), f[un & 1], x.goff);
            hedgehog_scale<1, KEEP>(unit(un + 1), ((un + 1) & 2) ? s1 : s0, f[(un + 1) & 1], [] {});
          }
          if (it) break;
#pragma unroll
          for (int q = 0; q < 32; q++) {
            asm volatile("mov.b32 %0, %1;" : "=f"(kv[q]) : "f"(kv[q + 32]));
            asm volatile("mov.b32 %0, %1;" : "=f"(kv[q + 64]) : "f"(kv[q + 96]));
            if (q < 16) kv[32 + q] = 0.f;
          }
        }
        norm(3);
        TSL_(3);
      } else {
        wg_bar(w);
#pragma unroll
        for (int hf = 0; hf < 2; hf++) {
          stsm4(tV[hf] + 512 + x.mhi * 512, uu[2 * hf], uu[2 * hf + 1], uu[2 * hf], uu[2 * hf + 1]);
          stsm4(tV[hf] + 1792 + x.mhi * 512, uu[2 * hf], uu[2 * hf + 1], uu[2 * hf], uu[2 * hf + 1]);
#pragma unroll
          for (int q = 0; q < 8; q++) {
            const float* u = kv + 64 * hf + 8 * q;
            stsm4(tV[hf] + (q >> 1) * 640 + (q & 1) * 256, pack2(u[0], u[1]), pack2(u[2], u[3]), pack2(u[4], u[5]), pack2(u[6], u[7]));
          }
        }
        TSL_(3);
      }
      {
        float d[2][20];
        uint4* dst = &g_kvpart[x.j()][w * 4 + x.warp][0][x.m() * 32 + x.lane];
        unsigned* dz = reinterpret_cast<unsigned*>(&g_kvpart[x.j()][w * 4 + x.warp][x.c & 1][512]) + x.m() * 8 + x.g;
        fence_async_smem();
        cta_bar();
        TSL_(11);
        uint32_t pk[9];
        auto prep = [&](float (&u)[20]) {
          fence_regs(u);
#pragma unroll
          for (int q = 0; q < 8; q++) pk[q] = pack2(u[((q >> 1) & 2) + 4 * (q & 3)], u[((q >> 1) & 2) + 4 * (q & 3) + 1]);
          pk[8] = __float_as_uint((x.c & 1) ? u[18] + u[19] : u[16] + u[17]);
#pragma unroll
          for (int q = 0; q < 9; q += 4) pk[q] = (pk[q] & ~1u) | (L == 1);
        };
        auto send = [&](int hp) {
          st_v4(dst + hp * 16 * 544, pk[0], pk[1], pk[2], pk[3]); st_v4(dst + (hp * 16 + 1) * 544, pk[4], pk[5], pk[6], pk[7]);
          st_flag(dz + hp * 16 * 544 * 4, pk[8]);
        };
        wgmma_fence();
#pragma unroll
        for (int q = 0; q < 17; q++) {
          if (q < 16) wgmma_ss_n40_tt(d[q >> 3], desc_lo(SB + (q < 8 ? OFF_S : OFF_B + 2 * SLOT), 1024) + w * (SLOT / 16) + 128 * (q & 7), desc_lo(SB + vreg(q & 7), 2560) + (w + (q >> 3) * 2) * 40, q & 7);
          else wgmma_r1_n128(acc, dm + w * 64, dcs, 0);
          if (q == 7 || q == KVS || q == 16) wgmma_commit();
          if (q == KVS) { mbar_wait2(x.fullA(x.ra.s), x.ra.ph, x.fullB(x.rb.s), x.rb.ph); wgmma_wait<1>(); prep(d[0]); send(0); bb_fence(x.goff); wgmma_fence(); }
        }
        gemm_issue<128, false>(acc, x, true); gemm_next<128>(x);
        wgmma_wait<1>();
        x.releaseA(h0); x.releaseA(h1); x.releaseB(2); x.releaseB(3);
        if (x.lane == 0) mbar_arrive(sb + BAR_SIGT);
        prep(d[1]);
        TSL_(4);
#pragma unroll 1
        for (int seg = 0; seg < 2; seg++) {
          const int n0 = w ? PS1 : PS0;
          gemm_run(acc, x, seg ? 15 - n0 : n0, seg, seg ? L : 0);
          if (seg == 0) send(1);
        }
      }
      gemm_end(acc, x);
      TSL_(5);
      {
        float dp[2][20], dn[2][20];
        uint32_t f[4][16];
        auto mma = [&](int h) {
          if (!(h & 1)) mbar_wait(sb + BAR_KV + h * 4, L >> 1);
          if (h == 0) TSL_(9);
          const uint32_t db = desc_lo(SB + OFF_S + h * 5120, 128);
          const uint32_t (&a)[16] = f[h];
          wgmma_fence();
          wgmma_rs_n40(dp[h & 1], a[0], a[1], a[2], a[3], db, 0);
          wgmma_rs_n40(dn[h & 1], a[8], a[9], a[10], a[11], db + 160, 0);
          wgmma_rs_n40(dp[h & 1], a[4], a[5], a[6], a[7], db + 80, 1);
          wgmma_rs_n40(dn[h & 1], a[12], a[13], a[14], a[15], db + 240, 1);
          wgmma_commit();
        };
        uint32_t xr[16];
        auto fin = [&](int h) {
          const uint32_t tile = x.aslot(x.held(h >> 1));
          if (!(h & 1)) img_load(xr, tile, x);
          float (&u)[20] = dp[h & 1];
          float (&v)[20] = dn[h & 1];
          fence_regs(u); fence_regs(v);
#pragma unroll
          for (int r = 0; r < 2; r++) {
            const float sp = u[16 + 2 * r], sn = v[16 + 2 * r];
            const float id = rcp(fmaf(fmaf(sp, L == 1 ? 0.065536f * 128 / 129 : 0.065536f, u[17 + 2 * r]), sn, v[17 + 2 * r] * sp)), aa = sn * id, cc = sp * id;
            uint32_t o[4];
#pragma unroll
            for (int t = 0; t < 4; t++) o[t] = pack2(fmaf(u[4 * t + 2 * r], aa, v[4 * t + 2 * r] * cc), fmaf(u[4 * t + 2 * r + 1], aa, v[4 * t + 2 * r + 1] * cc));
            o[2 * r + (h & 1)] = img_tag(o[2 * r + (h & 1)], false, 1, x);
            stg128(x.img(0, h >> 1) + r * 64 + (h & 1) * 32, make_uint4(o[0], o[1], o[2], o[3]));
            sts128(tile + r * 1024 + (h & 1) * 512 + x.so, o[0], o[1], o[2], o[3]);
          }
          if (h & 1) { if (h == 1) publish(0, x); img_unpack(acc + 16 * (h - 1), xr); }
        };
        auto scale = [&](int h) { hedgehog_scale<1, 0>(acc + 16 * h, st, nullptr, [] {}); };
        auto ex = [&](int h) { dual_exp_rcp(acc + 16 * h, f[h]); };
        Stats sq = st;
#pragma unroll
        for (int h = 0; h < 4; h += 2) {
          hedgehog_scale<2, 0>(acc + 16 * h, sq, nullptr, [&] { ex(h); });
          mma(h);
          ex(h + 1); wgmma_wait<0>(); fin(h);
          if (h == 0) bb_fence(x.goff);
          mma(h + 1);
          wgmma_wait<0>(); fin(h + 1);
          if (h == 0) { const float z = bb_fence(x.goff); sq.rstd1 += z; if (QORD == 7) sq.rstd0 += z; }
        }
      }
    }
    if (PW & 2) { mbar_wait(x.fullB(x.rb.s), x.rb.ph); fence_regs(acc); }
    fence_async_smem();
    wg_bar(w);
    TSL_(6);
    rewind2<NA>(x.ra);
    gemm_issue<128, false>(acc, x, PW & 2); gemm_next<128>(x);
    uint4* out = solid(P.out + goff + (x.warp * 16 + (x.lane >> 3)) * 256 + (x.lane & 7));
#pragma unroll 1
    for (int seg = L >= TSL ? 0 : 1; seg < 2; seg++) {
      gemm_run(acc, x, L >= TSL ? (seg ? TSK : 15 - TSK) : 15, seg, 10 + L);
      if (L >= TSL) {
        if (seg == 0 && w == 1) asm volatile("bar.sync 6, 256;" ::: "memory");
        if (seg == 1 && w == 0) asm volatile("bar.arrive 6, 256;" ::: "memory");
      }
    }
    gemm_end(acc, x);
    TSL_(7);
    rewind2<NA>(x.ra);
    out_epilogue(acc, r1, ts, out, L, x);
    TSL_(13);
  }
}

typedef unsigned long long u64;
template <class T> __device__ __forceinline__ T* early(T* p) { return (T*)__shfl_xor_sync(0xffffffffu, (u64)p, 1); }
__device__ __forceinline__ void pause(uint32_t GAP) {
  if (GAP) { uint32_t t0, t; asm volatile("mov.u32 %0, %%clock;" : "=r"(t0)); do { asm volatile("mov.u32 %0, %%clock;" : "=r"(t)); } while (t - t0 < GAP); }
}
__device__ __forceinline__ u64 order_table(int kind, int j) {
  const int i = threadIdx.x & 15;
  const unsigned v = (unsigned)(kind == 2 ? q_order(i, j) : kv_order(i, j, kind)) << (4 * (i & 7));
  return (u64)__reduce_or_sync(0xffffffffu, i < 8 ? 0u : v) << 32 | __reduce_or_sync(0xffffffffu, i < 8 ? v : 0u);
}

__device__ __forceinline__ void b_producer(const Params& P, uint32_t sb, unsigned vb) {
  const int j = cta_j(vb);
  const u64 t0 = order_table(0, j), t1 = order_table(1, j), t2 = order_table(2, j);
  Ring r = {PRE_B % NB, PRE_B < NB};
#pragma unroll 1
  for (int sg = 0; sg < 20; sg++) {
    const int L = sg / 5, p = sg - 5 * L, wt = L & 1;
    int n = p >= 3 ? 16 : (wt ? (p ? 16 - NJ : 2 * NJ) : (p ? 0 : (L ? 32 : 32 - PRE_B)));
    u64 tab = p == 3 ? t2 : (sg == 0 ? t0 >> (2 * PRE_B) : (p == 1 || p == 2 ? t1 >> (4 * NJ) : t1));
    const CUtensorMap* tm = p == 4 ? &P.mwo[wt] : &P.mw[wt ? 1 : L];
    const uint4* img = &g_wf[p != 3][j][0][0];
    int col = (p >= 3 ? 0 : (p == 2 ? 2048 : 1024)) + 128 * j;
    const int flip = p == 0 ? 3072 : 0;
    const bool fold = wt && p != 4;
    if (sg == 5 || sg == 8) { mbar_wait(sb + (sg == 5 ? BAR_WPHI : BAR_CS + 8), sg == 5); fence_async_global(); }
    if (DEFER && p == 4 && ((DEFL >> wt) & 1)) {
      Ring q = r;
      for (int u = 0; u < DEFER; u++) adv<NB>(q);
      mbar_wait(sb + BAR_EMPTYB + q.s * 8, q.ph);
    }
#pragma unroll 1
    for (; n > 0; n--) {
      const int kb = (int)tab & 15;
      mbar_wait(sb + BAR_EMPTYB + r.s * 8, r.ph);
      if (elect()) {
        mbar_expect_tx(sb + BAR_FULLB + r.s * 8, SLOT);
        if (fold && col < 2048) bulk_load(sb + OFF_B + r.s * SLOT, img + kb * 1024, SLOT, sb + BAR_FULLB + r.s * 8);
        else tma_load_w(sb + OFF_B + r.s * SLOT, tm, sb + BAR_FULLB + r.s * 8, col, kb);
      }
      adv<NB>(r);
      if (p == 2 && (n | 4) == 5) r.s = 4;
      col ^= flip;
      if (!(col & flip & 2048)) tab >>= 4;
    }
  }
}

__device__ __forceinline__ void a_loader(const Params& P, uint32_t sb, unsigned vb) {
  const int j = cta_j(vb), m = cta_m(vb);
  const u64 t1 = order_table(1, j), t2 = order_table(2, j);
  Ring r = {PRE_A % NA, PRE_A < NA};
  {
    u64 tab = order_table(0, j) >> (4 * PRE_A);
#pragma unroll 1
    for (int i = PRE_A; i < 33; i++) {
      if (i == 17) tab = t2;
      mbar_wait(sb + BAR_EMPTYA + r.s * 8, r.ph);
      if (elect()) {
        mbar_expect_tx(sb + BAR_FULLA + r.s * 8, SLOT);
        if (i != 14) tma_load_3d(sb + OFF_A + r.s * SLOT, &P.mx, sb + BAR_FULLA + r.s * 8, ((int)tab & 15) * 64, m * 64, 0);
        else {
          tma_load_w(sb + OFF_A + r.s * SLOT, &P.mw[1], sb + BAR_FULLA + r.s * 8, 1024 + 128 * j, m);
          mbar_expect_tx(sb + BAR_WPHI, 8192); tma_load_2d(sb + OFF_S + 4096, &P.mwphi, sb + BAR_WPHI, 0, 128 * j);
        }
        if (i == PF1 || i == PF2) tma_prefetch_w(&P.mwo[i == PF2], 128 * j, m);
      }
      adv<NA>(r);
      if (i != 14) tab >>= 4;
    }
  }
  const unsigned tag = get_tag(sb);
  unsigned kph = 0;
#pragma unroll 1
  for (int sg = 0; sg < 13; sg++) {
    const int L = sg >> 2, p = sg & 3;
    if (p == 0 && (L & 1)) {
#pragma unroll 1
      for (int h = 0; h < 2; h++) {
        poll_flags(&g_kvfflag[L >> 1][j][h][0], 16, 0xFFFFu, tag);
        TS(4, h ? 14 + L : 26 + L);
        for (int it = 0;; it++) {
          if (elect()) { mbar_expect_tx(sb + BAR_STAT + 8, 10240); bulk_load(sb + OFF_S + h * 10240, &g_kvfin[j][8 * h][0], 10240, sb + BAR_STAT + 8); }
          mbar_wait(sb + BAR_STAT + 8, kph);
          kph ^= 1;
          uint32_t a = 1u, o = 0u;
#pragma unroll
          for (int u = 0; u < 20; u++) { const uint32_t v = __float_as_uint(lds32f(sb + OFF_S + h * 10240 + u * 512 + (threadIdx.x & 31) * 16)); a &= v; o |= v; }
          if (__all_sync(0xffffffffu, (L == 1 ? a : ~o) & 1u)) break;
          fence_async_smem();
          if (it > (1 << 16)) __trap();
        }
        if (elect()) mbar_arrive(sb + BAR_KV + h * 8);
        TS(4, h ? 30 + L : (L == 1 ? 20 : 25));
      }
    }
    int n = p < 2 ? 14 : (p == 2 ? ((L & 1) ? 0 : 16 - NJ) : 16);
    u64 tab = p == 3 ? t2 : t1 >> (p < 2 ? 8 : 4 * NJ);
    const uint4* img = &g_img[p ? XBUF(L + 1) : 0][m][0][0];
#pragma unroll 1
    for (; n > 0; n--) {
      const uint4* src = early(img + ((int)tab & 15) * 1024);
      const uint32_t bar = sb + (p < 2 ? BAR_LAND : BAR_FULLA) + r.s * 8;
      mbar_wait(sb + BAR_EMPTYA + r.s * 8, r.ph);
      if (elect()) mbar_expect_tx(bar, SLOT);
      if (p < 2 && n == 14) {
        const int lane = threadIdx.x & 31;
        const unsigned* f = &g_hint[2 * L + p][(m & 14) + ((lane >> 3) & 1)][(~j & 4) + (lane & ND0)];
        mbar_wait(sb + BAR_SIGP + p * 8, L & 1);
        int it = 0;
        while (!__all_sync(0xffffffffu, ld_flag(f) == tag)) { if (++it > (1 << 22)) __trap(); }
        TS(2, p == 0 ? 5 + L * 8 : 9 + L * 8);
      }
      if (elect()) bulk_load(sb + OFF_A + r.s * SLOT, src, SLOT, bar);
      adv<NA>(r);
      tab >>= 4;
      pause(p < 2 && n > 10 ? G0 : 0);
    }
  }
}

__device__ __forceinline__ uint2 sum_packets(float (&a)[8], uint32_t addr, int n) {
  uint2 ok = make_uint2(~0u, 0u);
#pragma unroll 1
  for (int b = 0; b < n; b += KB) {
    uint4 v[KB];
#pragma unroll
    for (int u = 0; u < KB; u++) lds128(addr + (b + u) * 512, v[u].x, v[u].y, v[u].z, v[u].w);
#pragma unroll
    for (int u = 0; u < KB; u++) {
      ok.x &= v[u].x; ok.y |= v[u].x;
      a[0] += lo16(v[u].x); a[1] += hi16(v[u].x); a[2] += lo16(v[u].y); a[3] += hi16(v[u].y);
      a[4] += lo16(v[u].z); a[5] += hi16(v[u].z); a[6] += lo16(v[u].w); a[7] += hi16(v[u].w);
    }
  }
  return ok;
}
__device__ __forceinline__ void helper_bar() { asm volatile("bar.sync 4, 64;" ::: "memory"); }
__device__ __forceinline__ void helper(const Params& P, uint32_t sb, int w, unsigned vb) {
  const int j = cta_j(vb), m = cta_m(vb);
  if (w == 0) {
    if (elect()) {
      const unsigned t = atomicAdd(&g_ctr, 1u) / NCTA + 1u;
      asm volatile("st.shared.u32 [%0], %1;" ::"r"(sb + OFF_EPOCH), "r"(t) : "memory");
      mbar_arrive(sb + BAR_EPOCH);
    }
  }
  const unsigned tag = get_tag(sb);
  mbar_wait(sb + BAR_FULLB + 24, 0);
  const uint32_t stg = sb + OFF_T + w * 12288, stb = sb + BAR_STG + w * 24;
  Ring rs = {0, 0};
  uint32_t vs = 33 % NA, vph = 0;
  auto cs_image = [&](int L) {
      const int lane = lane_id();
      poll_flags(&g_csflag[L][j][0], 16, L ? CSNEED : 0xFFFu, tag);
#pragma unroll
      for (int p = 0; p < 3; p++) {
        const uint4 u = ldcg4(&g_cs[L][0][p * 1024 + 128 * j + lane * 4]), v = ldcg4(&g_cs[L][1][p * 1024 + 128 * j + lane * 4]);
        const float c0 = __uint_as_float(u.x) + __uint_as_float(v.x), c1 = __uint_as_float(u.y) + __uint_as_float(v.y);
        const float c2 = __uint_as_float(u.z) + __uint_as_float(v.z), c3 = __uint_as_float(u.w) + __uint_as_float(v.w);
        const uint32_t h0 = pack2(c0, c1), h1 = pack2(c2, c3), dst = sb + OFF_CS + (p * 16 + (lane >> 1)) * 96 + L * 48 + (lane & 1) * 8;
        sts64(dst, h0, h1); sts64(dst + 16, pack2(c0 - lo16(h0), c1 - hi16(h0)), pack2(c2 - lo16(h1), c3 - hi16(h1))); sts64(dst + 32, h0, h1);
        if (L == 0) { sts64(dst + 48, 0u, 0u); sts64(dst + 64, 0u, 0u); sts64(dst + 80, 0u, 0u); }
      }
      if (L == 0 && lane < 4) sts64(sb + OFF_CS + 4608 + lane * 8, 0u, 0u);
      fence_async_smem();
      __syncwarp();
      if (elect()) mbar_arrive(sb + BAR_CS + L * 8);
      TS(4, 2 + L * 2);
  };
#pragma unroll 1
  for (int L = 0; L < 4; L++) {
    const int lane = lane_id();
    if (L == 0) {
      {
        const int wt = m >= 12, col = ((0x2021 >> (m & 12)) & 3) * 1024 + 128 * j + (m & 3) * 32;
        const CUtensorMap* tm = &P.mcs[wt];
        __nanosleep(wt ? D2 : CD);
        constexpr int nb = 8;
        float a[8] = {0.f, 0.f, 0.f, 0.f, 0.f, 0.f, 0.f, 0.f};
#pragma unroll 1
        for (int b = -3; b < nb; b++) {
          if (b >= 0) {
            mbar_wait(stb + rs.s * 8, rs.ph);
            sum_packets(a, stg + rs.s * 4096 + lane * 16, 8);
            fence_async_smem();
            __syncwarp();
          }
          const uint32_t sl = b < 0 ? (rs.s + b + 3) % 3 : rs.s;
          if (b + 3 < nb && elect()) { mbar_expect_tx(stb + sl * 8, 4096); tma_load_2d(stg + sl * 4096, tm, stb + sl * 8, col, (w * (16 - nb) + b + 3) * 64); }
          if (b >= 0) adv<3>(rs); else pause(CP);
        }
#pragma unroll
        for (int u = 0; u < 8; u++) {
          a[u] += __shfl_xor_sync(0xffffffffu, a[u], 4); a[u] += __shfl_xor_sync(0xffffffffu, a[u], 8); a[u] += __shfl_xor_sync(0xffffffffu, a[u], 16);
        }
        if (lane < 4) {
          float4* dst = reinterpret_cast<float4*>(&g_cs[wt][w][col + lane * 8]);
          dst[0] = make_float4(a[0], a[1], a[2], a[3]); dst[1] = make_float4(a[4], a[5], a[6], a[7]);
        }
        helper_bar();
        if (w == 0 && elect()) { fence_gpu(); st_flag(&g_csflag[wt][j][m], tag); }
      }
      if (w == 0) TS(4, 1 + L * 2);
    }
    if (w == (L == 0)) {
      if (L > 0) {
        mbar_wait(sb + BAR_SIGP + 16, (L - 1) & 1);
        fence_async_global();
        __nanosleep(SD);
      }
      else if (S0) { mbar_wait(sb + BAR_WPHI, 0); __nanosleep(S0); }
#pragma unroll 1
      for (int p = 0; p < 2; p++) {
        uint4 v[8];
        for (int it = 0;; it++) {
          bool ok = true;
#pragma unroll
          for (int t = 0; t < 8; t++) v[t] = ld_pkt(&g_stats[m][p][t][lane]);
#pragma unroll
          for (int t = 0; t < 8; t++) ok = ok && (v[t].w & 15u) == seq4(tag, L);
          if (__all_sync(0xffffffffu, ok)) break;
          __nanosleep(200);
          if (it > (1 << 20)) __trap();
        }
        float s0 = 0.f, q0 = 0.f, s1 = 0.f, q1 = 0.f;
#pragma unroll
        for (int t = 0; t < 8; t++) { s0 += __uint_as_float(v[t].x); q0 += __uint_as_float(v[t].y); s1 += __uint_as_float(v[t].z); q1 += __uint_as_float(v[t].w & ~15u); }
        s0 *= (1.f / 1024); s1 *= (1.f / 1024);
        sts64(sb + OFF_MR + p * 256 + lane * 8, __float_as_uint(rsqrtf(fmaxf(q0 * (1.f / 1024) - s0 * s0, 0.f) + 1e-5f)),
              __float_as_uint(rsqrtf(fmaxf(q1 * (1.f / 1024) - s1 * s1, 0.f) + 1e-5f)));
#pragma unroll
        for (int r = 0; r < 2; r++) {
          const float v = -0.5f * (r ? s1 : s0);
          const uint32_t hh = pack2(v, v), hl = pack2(v, v - lo16(hh));
          const bool b = L & 1;
          sts128(sb + (b ? OFF_MB : OFF_MA) + p * 1024 + (lane >> 3) * 256 + r * 128 + (lane & 7) * 16, b ? 0u : hh, b ? hh << 16 : hl >> 16, b ? hl : 0u, 0u);
        }
      }
      fence_async_smem();
      __syncwarp();
      if (elect()) {
        mbar_arrive(sb + BAR_STAT);
      }
      TS(2, 0 + L * 8);
    }
    if (L < 2 && w == 0) cs_image(L);
    if (L & 1) {
      const uint32_t flip = L == 1 ? 0u : 1u;
      mbar_wait(sb + BAR_SIGT, 1);
      {
        int it = 0;
        if (PSL) __nanosleep(m < 8 ? PSL : PSL + 600);
        while (!__all_sync(0xffffffffu, (ld_flag(reinterpret_cast<const unsigned*>(&g_kvpart[j][m][w][512]) + (lane & 15) * 8) ^ flip) & 1u)) { if (PSL) __nanosleep(100); if (++it > (1 << 22)) __trap(); }
        fence_async_global();
      }
      if (w == 0) TS(4, 6 + L * 2);
      float a[8], z;
      for (int it = 0;; it++) {
        if (elect()) { mbar_expect_tx(stb + rs.s * 8, 8704); bulk_load(stg, &g_kvpart[j][m][w][0], 8704, stb + rs.s * 8); }
        mbar_wait(stb + rs.s * 8, rs.ph);
        if (w == 0) TS(4, 21 + L);
        adv<3>(rs);
#pragma unroll
        for (int u = 0; u < 8; u++) a[u] = 0.f;
        z = 0.f;
        uint32_t ok = 1u;
#pragma unroll
        for (int u = 0; u < 4; u++) { const float v = lds32f(stg + 8192 + u * 128 + (lane & 3) * 32 + (lane >> 2) * 4); z += v; ok &= __float_as_uint(v) ^ flip; }
        const uint2 tg = sum_packets(a, stg + lane * 16, 16);
        ok &= flip ? ~tg.y : tg.x;
        if (__all_sync(0xffffffffu, ok & 1u)) break;
        fence_async_smem();
        if (it > (1 << 16)) __trap();
      }
      {
        uint4* img = &g_kvfin[j][m][w * 8 + (lane >> 2)];
        uint32_t a0 = __float_as_uint(a[0]) >> 16;
        a0 += ~(a0 ^ flip) & 1u;
        st_v4(img + (lane & 3) * 16, __byte_perm(a0, pack2(0.f, a[1]), 0x7610), pack2(a[2], a[3]), pack2(a[4], a[5]), pack2(a[6], a[7]));
        const uint32_t cz = pack2(0.f, qsum(z)) | (0x3781u ^ flip);
        if (!(lane & 3)) st_v4(img + 64, cz, cz, cz, cz);
        __syncwarp();
        if (elect()) st_flag(&g_kvfflag[L >> 1][j][m >> 3][(m & 7) * 2 + w], tag);
      }
      if (w == 0) TS(4, 7 + L * 2);
    } else {
      mbar_wait(sb + BAR_SIGT, 0);
      if (w == 0) {
        if (elect()) { fence_gpu(); st_flag(&g_hflag[L >> 1][m][j][0], tag); st_flag(&g_kflag[j][m], tag); }
        if (L == 0) {
          __nanosleep(KSL);
          poll_flags(&g_kflag[j][0], 16, 0xFFFFu, tag);
          if (elect()) mbar_arrive(sb + BAR_WPHI);
        }
      } else if (m > 0) {
        poll_flags(&g_hflag[L >> 1][m - 1][j][0], 1, 1u, tag);
        if (elect()) { mbar_expect_tx(sb + BAR_HALO, 8192); bulk_load(sb + OFF_S + 8192, &g_halo[m - 1][j][0][0], 8192, sb + BAR_HALO); }
        TS(2, 2 + L * 8);
      }
    }
    if (w == 0) {
#pragma unroll 1
      for (int e = 0; e < (L < 3 ? 2 : 1); e++) {
        unsigned* flag = early(&g_hint[2 * L + e][m][j]);
        mbar_wait(sb + BAR_SIGP + e * 8, L & 1);
        TS(2, (e ? 6 : 3) + L * 8);
        pause(XD);
        if (elect()) st_flag(flag, tag);
      }
    } else {
#pragma unroll 1
      for (int i = 0; i < (L < 3 ? 28 : 14); i++) {
        const bool isx = i >= 14;
        const uint32_t a = sb + OFF_A + vs * SLOT + lane * 128 + ((lane >> 4) * 4 + (lane & 3)) * 16 + (lane & 12), code = img_code(isx, L + isx);
        for (int it = 0;; it++) {
          mbar_wait(sb + BAR_LAND + vs * 8, (vph >> vs) & 1);
          vph ^= 1u << vs;
          uint32_t bad = 0;
#pragma unroll
          for (int u = 0; u < 4; u++) bad |= __float_as_uint(lds32f(a + u * 4096)) ^ code;
          if (__all_sync(0xffffffffu, !(bad & img_mask(isx)))) break;
          if (it > (1 << 16)) __trap();
          fence_async_smem();
          if (elect()) {
            mbar_expect_tx(sb + BAR_LAND + vs * 8, SLOT);
            bulk_load(sb + OFF_A + vs * SLOT, &g_img[isx ? XBUF(L + 1) : 0][m][o_order(i - 14 * isx + 2, j)][0], SLOT, sb + BAR_LAND + vs * 8);
          }
        }
        if (elect()) mbar_arrive(sb + BAR_FULLA + vs * 8);
        if (++vs == NA) vs = 0;
      }
      vs = (vs + ((L & 1) ? 16 : 32 - NJ)) % NA;
    }
  }
}

__device__ __forceinline__ void spare(const Params& P, uint32_t sb, int id) {
  const int tid = threadIdx.x & 127, w = __shfl_sync(0xffffffffu, threadIdx.x >> 7, 0), lane = tid & 31, j = 2 * id + w;
  const uint32_t ring = w * 6 * SLOT, wp = 12 * SLOT + w * 8192, bar = sb + 13 * SLOT + w * 64;
  auto part = [&](int t) { return (t >> 4) ^ w; };
  auto load = [&](int t, uint32_t sl) {
    mbar_expect_tx(bar + sl * 8, t == 0 ? SLOT + 8192 : SLOT);
    tma_load_w(sb + ring + sl * SLOT, &P.mw[1], bar + sl * 8, part(t) * 1024 + 128 * j, t & 15);
  };
  if (tid == 0) {
    if (w == 2) sts32(sb + OFF_EPOCH, atomicAdd(&g_ctr, 1u) / NCTA + 1u);
    else {
      __nanosleep(D3);
#pragma unroll 1
      for (int t = 0; t < 5; t++) {
        mbar_init(bar + t * 8, 1);
        asm volatile("fence.mbarrier_init.release.cluster;" ::: "memory");
        load(t, t);
      }
      tma_load_2d(sb + wp, &P.mwphi, bar, 0, 128 * j);
    }
  }
  __syncthreads();
  const unsigned tag = get_tag<false>(sb);
  if (w == 2) {
    int it = 0;
    while ((int)(ld_flag(&g_ctr) - tag * NCTA) < 0) { if (++it > (1 << 22)) __trap(); }
    return;
  }
  Ring r = {4, 1};
  float d[64] = {}, cs[32] = {};
  auto fold = [&]() {
    mbar_wait(bar + r.s * 8, r.ph);
    wgmma_fence();
#pragma unroll
    for (int q = 0; q < 8; q++)
      wgmma_ss_n32(reinterpret_cast<float (&)[16]>(d[16 * (q >> 1)]), desc_lo(SB + ring + r.s * SLOT, 16) + (q >> 2) * 512 + (q & 3) * 2, desc_lo(SB + wp, 512) + q * 64, q & 1);
    wgmma_commit();
  };
  const int row = (tid >> 5) * 16 + (lane >> 2);
#pragma unroll 1
  for (int t = -1; t < 32; t++) {
    uint32_t f[32];
#pragma unroll
    for (int i = 0; i < 32; i++) { f[i] = pack2(d[2 * i], d[2 * i + 1]); cs[i & 30] += d[2 * i]; cs[i | 1] += d[2 * i + 1]; }
    wg_bar(w);
    if (tid == 0 && t >= 0 && t < 27) load(t + 5, r.s);
    __syncwarp();
    if (t < 31) adv<5>(r);
    fold();
    if (part(t) == 0 && t >= 0) {
#pragma unroll
      for (int q = 0; q < 8; q++)
        g_wf[0][j][t & 15][(q >> 2) * 512 + (row + 8 * (q & 1)) * 8 + (((q & 2) * 2 + (lane & 3)) ^ (lane >> 2))] =
            make_uint4(f[4 * (q & 6) + (q & 1)], f[4 * (q & 6) + (q & 1) + 2], f[4 * (q & 6) + (q & 1) + 4], f[4 * (q & 6) + (q & 1) + 6]);
    }
    wgmma_wait<0>();
    fence_regs(d);
    if ((t & 15) == 15) {
      if (t >= 0) {
        const uint32_t red = sb + ring + 5 * SLOT;
#pragma unroll
        for (int i = 0; i < 8; i++) sts128(red + (tid >> 2) * 512 + (i >> 1) * 128 + (lane & 3) * 32 + (i & 1) * 16, __float_as_uint(cs[4 * i]), __float_as_uint(cs[4 * i + 1]), __float_as_uint(cs[4 * i + 2]), __float_as_uint(cs[4 * i + 3]));
        wg_bar(w);
        float a = 0.f;
#pragma unroll 4
        for (int i = 0; i < 32; i++) a += lds32f(red + i * 512 + tid * 4);
        g_cs[1][0][part(t) * 1024 + j * 128 + tid] = a;
        wg_bar(w);
        if (tid == 0) {
          fence_gpu();
          st_flag(&g_csflag[1][j][part(t)], tag);
        }
        __syncwarp();
      }
#pragma unroll
      for (int i = 0; i < 32; i++) cs[i] = 0.f;
    }
  }
}

__global__ void __launch_bounds__(NTHREADS, 1) fused_kernel(const __grid_constant__ Params P) {
  extern __shared__ __align__(1024) uint8_t smem_raw[];
  constexpr uint32_t sb = SB;
  const int tid = threadIdx.x;
  const unsigned vb = vblock();
  if (vb >= 128) { spare(P, sb, vb - 128); return; }
  const int warp = __shfl_sync(0xffffffffu, tid >> 5, 0);
  if (elect()) {
    if (warp == 11) { prefetch_map(&P.mx); prefetch_map(&P.mw[0]); if (smem_u32(smem_raw) != SB) __trap(); }
    if (warp < 8) {
#pragma unroll
      for (int i = 0; i < 8; i++) mbar_init(sb + OFF_BAR + (warp * 8 + i) * 8, warp == 2 || warp == 3 ? 2 : (warp == 4 ? 8 : 1));
    }
    asm volatile("fence.mbarrier_init.release.cluster;" ::: "memory");
    if (warp < 2) {
      const int j = cta_j(vb);
#pragma unroll 1
      for (int i = 0; i < (warp == 0 ? PRE_B : PRE_A); i++) {
        const uint32_t bar = sb + BAR_FULLB + warp * 64 + i * 8;
        mbar_expect_tx(bar, SLOT);
        if (warp == 0) tma_load_w(sb + OFF_B + i * SLOT, &P.mw[0], bar, 1024 + (i & 1) * 1024 + 128 * j, kv_order(i >> 1, j, 0));
        else tma_load_3d(sb + OFF_A + i * SLOT, &P.mx, bar, kv_order(i, j, 0) * 64, cta_m(vb) * 64, 0);
      }
    }
  }
  if (tid == 0) TS(6, 0);
  __syncthreads();
  if (tid == 0) TS(6, 2);
  if (warp < 4) {
    reg_dealloc<PREGS>();
    if (warp & 2) helper(P, sb, warp & 1, vb);
    else if (warp & 1) a_loader(P, sb, vb);
    else b_producer(P, sb, vb);
  } else {
    reg_alloc<CREGS>();
    consumer(P, sb, (warp >> 2) - 1, vb);
  }
}

typedef CUresult (*EncodeFn)(CUtensorMap*, CUtensorMapDataType, cuuint32_t, void*, const cuuint64_t*, const cuuint64_t*,
                             const cuuint32_t*, const cuuint32_t*, CUtensorMapInterleave, CUtensorMapSwizzle,
                             CUtensorMapL2promotion, CUtensorMapFloatOOBfill);

void encode(EncodeFn fn, CUtensorMap* m, const void* ptr, int rank, const cuuint64_t* dims, const cuuint64_t* strides,
            const cuuint32_t* box, CUtensorMapSwizzle swz) {
  const cuuint32_t es[5] = {1, 1, 1, 1, 1};
  fn(m, CU_TENSOR_MAP_DATA_TYPE_BFLOAT16, rank, const_cast<void*>(ptr), dims, strides, box, es, CU_TENSOR_MAP_INTERLEAVE_NONE,
     swz, CU_TENSOR_MAP_L2_PROMOTION_L2_256B, CU_TENSOR_MAP_FLOAT_OOB_FILL_NONE);
}
void encode_w(EncodeFn fn, CUtensorMap* m, const void* ptr, int ncols, bool perm) {
  const cuuint64_t p = (cuuint64_t)ncols * 2, d[5] = {(cuuint64_t)ncols, 2, 4, 4, 32}, s[4] = {p, (perm ? 8 : 2) * p, (perm ? 2 : 8) * p, 32 * p};
  const cuuint32_t box[5] = {64, 2, 4, 4, 2};
  encode(fn, m, ptr, 5, d, s, box, CU_TENSOR_MAP_SWIZZLE_128B);
}

void encode_cs(EncodeFn fn, CUtensorMap* m, const void* ptr, int ncols) {
  const cuuint64_t d[2] = {(cuuint64_t)ncols, 1024}, s[1] = {(cuuint64_t)ncols * 2};
  const cuuint32_t box[2] = {32, 64};
  encode(fn, m, ptr, 2, d, s, box, CU_TENSOR_MAP_SWIZZLE_NONE);
}

}

extern "C" void kernel_launch(void* const* d_in, const int* in_sizes, int n_in, void* d_out, int out_size) {
  (void)in_sizes; (void)n_in; (void)out_size;
  void* fnp = nullptr;
  cudaDriverEntryPointQueryResult q;
  cudaGetDriverEntryPoint("cuTensorMapEncodeTiled", &fnp, cudaEnableDefault, &q);
  EncodeFn fn = (EncodeFn)fnp;
  Params P;
  {
    const cuuint64_t dims[3] = {1024, 1024, 2}, strides[2] = {4096, 2048};
    const cuuint32_t box[3] = {64, 64, 2};
    encode(fn, &P.mx, d_in[0], 3, dims, strides, box, CU_TENSOR_MAP_SWIZZLE_128B);
  }
  P.out = (uint4*)d_out;
  encode_w(fn, &P.mw[0], d_in[1], 3072, false);
  encode_w(fn, &P.mw[1], d_in[4], 3072, true);
  encode_w(fn, &P.mw[2], d_in[1], 3072, true);
  encode_w(fn, &P.mwo[0], d_in[2], 1024, true);
  encode_w(fn, &P.mwo[1], d_in[6], 1024, false);
  encode_cs(fn, &P.mcs[0], d_in[1], 3072);
  encode_cs(fn, &P.mcs[1], d_in[4], 3072);
  {
    const cuuint64_t dims[2] = {32, 1024}, strides[1] = {64};
    const cuuint32_t box[2] = {32, 128};
    encode(fn, &P.mwphi, d_in[5], 2, dims, strides, box, CU_TENSOR_MAP_SWIZZLE_64B);
  }
  cudaFuncSetAttribute(fused_kernel, cudaFuncAttributeMaxDynamicSharedMemorySize, SMEM_BYTES);
  fused_kernel<<<NCTA, NTHREADS, SMEM_BYTES, cudaStreamPerThread>>>(P);
}
```

```cpp
#include <cuda_runtime.h>
#include <cuda_bf16.h>
#include <cuda.h>
#include <stdint.h>

namespace {

__device__ __forceinline__ void wgmma_ss_n256(float (&d)[128], uint32_t da, uint32_t ha, uint32_t db, int sd) {
  asm volatile("{\n.reg .pred p;\n.reg .b64 a, b;\nsetp.ne.b32 p, %130, 0;\nmov.b64 a, {%128, %131};\nmov.b64 b, {%129, 0x40000040};\n"
    "wgmma.mma_async.sync.aligned.m64n256k16.f32.bf16.bf16 {%0,%1,%2,%3,%4,%5,%6,%7,%8,%9,%10,%11,%12,%13,%14,%15,%16,%17,%18,%19,%20,%21,%22,%23,%24,%25,%26,%27,%28,%29,%30,%31,%32,%33,%34,%35,%36,%37,%38,%39,%40,%41,%42,%43,%44,%45,%46,%47,%48,%49,%50,%51,%52,%53,%54,%55,%56,%57,%58,%59,%60,%61,%62,%63,%64,%65,%66,%67,%68,%69,%70,%71,%72,%73,%74,%75,%76,%77,%78,%79,%80,%81,%82,%83,%84,%85,%86,%87,%88,%89,%90,%91,%92,%93,%94,%95,%96,%97,%98,%99,%100,%101,%102,%103,%104,%105,%106,%107,%108,%109,%110,%111,%112,%113,%114,%115,%116,%117,%118,%119,%120,%121,%122,%123,%124,%125,%126,%127}, a, b, p, 1, 1, 0, 1;\n}\n"
    : "+f"(d[0]),"+f"(d[1]),"+f"(d[2]),"+f"(d[3]),"+f"(d[4]),"+f"(d[5]),"+f"(d[6]),"+f"(d[7]),"+f"(d[8]),"+f"(d[9]),"+f"(d[10]),"+f"(d[11]),"+f"(d[12]),"+f"(d[13]),"+f"(d[14]),"+f"(d[15]),"+f"(d[16]),"+f"(d[17]),"+f"(d[18]),"+f"(d[19]),"+f"(d[20]),"+f"(d[21]),"+f"(d[22]),"+f"(d[23]),"+f"(d[24]),"+f"(d[25]),"+f"(d[26]),"+f"(d[27]),"+f"(d[28]),"+f"(d[29]),"+f"(d[30]),"+f"(d[31]),"+f"(d[32]),"+f"(d[33]),"+f"(d[34]),"+f"(d[35]),"+f"(d[36]),"+f"(d[37]),"+f"(d[38]),"+f"(d[39]),"+f"(d[40]),"+f"(d[41]),"+f"(d[42]),"+f"(d[43]),"+f"(d[44]),"+f"(d[45]),"+f"(d[46]),"+f"(d[47]),"+f"(d[48]),"+f"(d[49]),"+f"(d[50]),"+f"(d[51]),"+f"(d[52]),"+f"(d[53]),"+f"(d[54]),"+f"(d[55]),"+f"(d[56]),"+f"(d[57]),"+f"(d[58]),"+f"(d[59]),"+f"(d[60]),"+f"(d[61]),"+f"(d[62]),"+f"(d[63]),"+f"(d[64]),"+f"(d[65]),"+f"(d[66]),"+f"(d[67]),"+f"(d[68]),"+f"(d[69]),"+f"(d[70]),"+f"(d[71]),"+f"(d[72]),"+f"(d[73]),"+f"(d[74]),"+f"(d[75]),"+f"(d[76]),"+f"(d[77]),"+f"(d[78]),"+f"(d[79]),"+f"(d[80]),"+f"(d[81]),"+f"(d[82]),"+f"(d[83]),"+f"(d[84]),"+f"(d[85]),"+f"(d[86]),"+f"(d[87]),"+f"(d[88]),"+f"(d[89]),"+f"(d[90]),"+f"(d[91]),"+f"(d[92]),"+f"(d[93]),"+f"(d[94]),"+f"(d[95]),"+f"(d[96]),"+f"(d[97]),"+f"(d[98]),"+f"(d[99]),"+f"(d[100]),"+f"(d[101]),"+f"(d[102]),"+f"(d[103]),"+f"(d[104]),"+f"(d[105]),"+f"(d[106]),"+f"(d[107]),"+f"(d[108]),"+f"(d[109]),"+f"(d[110]),"+f"(d[111]),"+f"(d[112]),"+f"(d[113]),"+f"(d[114]),"+f"(d[115]),"+f"(d[116]),"+f"(d[117]),"+f"(d[118]),"+f"(d[119]),"+f"(d[120]),"+f"(d[121]),"+f"(d[122]),"+f"(d[123]),"+f"(d[124]),"+f"(d[125]),"+f"(d[126]),"+f"(d[127])
    : "r"(da), "r"(db), "r"(sd), "r"(ha));
}
__device__ __forceinline__ void wgmma_ss_n128(float (&d)[64], uint32_t da, uint32_t ha, uint32_t db, int sd) {
  asm volatile("{\n.reg .pred p;\n.reg .b64 a, b;\nsetp.ne.b32 p, %66, 0;\nmov.b64 a, {%64, %67};\nmov.b64 b, {%65, 0x40000040};\n"
    "wgmma.mma_async.sync.aligned.m64n128k16.f32.bf16.bf16 {%0,%1,%2,%3,%4,%5,%6,%7,%8,%9,%10,%11,%12,%13,%14,%15,%16,%17,%18,%19,%20,%21,%22,%23,%24,%25,%26,%27,%28,%29,%30,%31,%32,%33,%34,%35,%36,%37,%38,%39,%40,%41,%42,%43,%44,%45,%46,%47,%48,%49,%50,%51,%52,%53,%54,%55,%56,%57,%58,%59,%60,%61,%62,%63}, a, b, p, 1, 1, 0, 1;\n}\n"
    : "+f"(d[0]),"+f"(d[1]),"+f"(d[2]),"+f"(d[3]),"+f"(d[4]),"+f"(d[5]),"+f"(d[6]),"+f"(d[7]),"+f"(d[8]),"+f"(d[9]),"+f"(d[10]),"+f"(d[11]),"+f"(d[12]),"+f"(d[13]),"+f"(d[14]),"+f"(d[15]),"+f"(d[16]),"+f"(d[17]),"+f"(d[18]),"+f"(d[19]),"+f"(d[20]),"+f"(d[21]),"+f"(d[22]),"+f"(d[23]),"+f"(d[24]),"+f"(d[25]),"+f"(d[26]),"+f"(d[27]),"+f"(d[28]),"+f"(d[29]),"+f"(d[30]),"+f"(d[31]),"+f"(d[32]),"+f"(d[33]),"+f"(d[34]),"+f"(d[35]),"+f"(d[36]),"+f"(d[37]),"+f"(d[38]),"+f"(d[39]),"+f"(d[40]),"+f"(d[41]),"+f"(d[42]),"+f"(d[43]),"+f"(d[44]),"+f"(d[45]),"+f"(d[46]),"+f"(d[47]),"+f"(d[48]),"+f"(d[49]),"+f"(d[50]),"+f"(d[51]),"+f"(d[52]),"+f"(d[53]),"+f"(d[54]),"+f"(d[55]),"+f"(d[56]),"+f"(d[57]),"+f"(d[58]),"+f"(d[59]),"+f"(d[60]),"+f"(d[61]),"+f"(d[62]),"+f"(d[63])
    : "r"(da), "r"(db), "r"(sd), "r"(ha));
}
__device__ __forceinline__ void wgmma_ss_n40_tt(float (&d)[20], uint32_t da, uint32_t db, int sd) {
  asm volatile("{\n.reg .pred p;\n.reg .b64 a, b;\nsetp.ne.b32 p, %22, 0;\nmov.b64 a, {%20, 0x40000040};\nmov.b64 b, {%21, 0x8};\n"
    "wgmma.mma_async.sync.aligned.m64n40k16.f32.bf16.bf16 {%0,%1,%2,%3,%4,%5,%6,%7,%8,%9,%10,%11,%12,%13,%14,%15,%16,%17,%18,%19}, a, b, p, 1, 1, 1, 1;\n}\n"
    : "+f"(d[0]),"+f"(d[1]),"+f"(d[2]),"+f"(d[3]),"+f"(d[4]),"+f"(d[5]),"+f"(d[6]),"+f"(d[7]),"+f"(d[8]),"+f"(d[9]),"+f"(d[10]),"+f"(d[11]),"+f"(d[12]),"+f"(d[13]),"+f"(d[14]),"+f"(d[15]),"+f"(d[16]),"+f"(d[17]),"+f"(d[18]),"+f"(d[19])
    : "r"(da), "r"(db), "r"(sd));
}
__device__ __forceinline__ void wgmma_ss_n32(float (&d)[16], uint32_t da, uint32_t db, int sd) {
  asm volatile("{\n.reg .pred p;\n.reg .b64 a, b;\nsetp.ne.b32 p, %18, 0;\nmov.b64 a, {%16, 0x40000040};\nmov.b64 b, {%17, 0x80000020};\n"
    "wgmma.mma_async.sync.aligned.m64n32k16.f32.bf16.bf16 {%0,%1,%2,%3,%4,%5,%6,%7,%8,%9,%10,%11,%12,%13,%14,%15}, a, b, p, 1, 1, 0, 1;\n}\n"
    : "+f"(d[0]),"+f"(d[1]),"+f"(d[2]),"+f"(d[3]),"+f"(d[4]),"+f"(d[5]),"+f"(d[6]),"+f"(d[7]),"+f"(d[8]),"+f"(d[9]),"+f"(d[10]),"+f"(d[11]),"+f"(d[12]),"+f"(d[13]),"+f"(d[14]),"+f"(d[15])
    : "r"(da), "r"(db), "r"(sd));
}
__device__ __forceinline__ void wgmma_rs_n40(float (&d)[20], uint32_t a0, uint32_t a1, uint32_t a2, uint32_t a3, uint32_t db, int sd) {
  asm volatile("{\n.reg .pred p;\n.reg .b64 b;\nsetp.ne.b32 p, %25, 0;\nmov.b64 b, {%24, 0x10};\n"
    "wgmma.mma_async.sync.aligned.m64n40k16.f32.bf16.bf16 {%0,%1,%2,%3,%4,%5,%6,%7,%8,%9,%10,%11,%12,%13,%14,%15,%16,%17,%18,%19}, {%20,%21,%22,%23}, b, p, 1, 1, 1;\n}\n"
    : "+f"(d[0]),"+f"(d[1]),"+f"(d[2]),"+f"(d[3]),"+f"(d[4]),"+f"(d[5]),"+f"(d[6]),"+f"(d[7]),"+f"(d[8]),"+f"(d[9]),"+f"(d[10]),"+f"(d[11]),"+f"(d[12]),"+f"(d[13]),"+f"(d[14]),"+f"(d[15]),"+f"(d[16]),"+f"(d[17]),"+f"(d[18]),"+f"(d[19])
    : "r"(a0), "r"(a1), "r"(a2), "r"(a3), "r"(db), "r"(sd));
}
__device__ __forceinline__ void wgmma_r1_n256(float (&d)[128], uint32_t da, uint32_t db, int sd) {
  asm volatile("{\n.reg .pred p;\n.reg .b64 a, b;\nsetp.ne.b32 p, %130, 0;\nmov.b64 a, {%128, 0x8};\nmov.b64 b, {%129, 0x6};\n"
    "wgmma.mma_async.sync.aligned.m64n256k16.f32.bf16.bf16 {%0,%1,%2,%3,%4,%5,%6,%7,%8,%9,%10,%11,%12,%13,%14,%15,%16,%17,%18,%19,%20,%21,%22,%23,%24,%25,%26,%27,%28,%29,%30,%31,%32,%33,%34,%35,%36,%37,%38,%39,%40,%41,%42,%43,%44,%45,%46,%47,%48,%49,%50,%51,%52,%53,%54,%55,%56,%57,%58,%59,%60,%61,%62,%63,%64,%65,%66,%67,%68,%69,%70,%71,%72,%73,%74,%75,%76,%77,%78,%79,%80,%81,%82,%83,%84,%85,%86,%87,%88,%89,%90,%91,%92,%93,%94,%95,%96,%97,%98,%99,%100,%101,%102,%103,%104,%105,%106,%107,%108,%109,%110,%111,%112,%113,%114,%115,%116,%117,%118,%119,%120,%121,%122,%123,%124,%125,%126,%127}, a, b, p, 1, 1, 0, 1;\n}\n"
    : "+f"(d[0]),"+f"(d[1]),"+f"(d[2]),"+f"(d[3]),"+f"(d[4]),"+f"(d[5]),"+f"(d[6]),"+f"(d[7]),"+f"(d[8]),"+f"(d[9]),"+f"(d[10]),"+f"(d[11]),"+f"(d[12]),"+f"(d[13]),"+f"(d[14]),"+f"(d[15]),"+f"(d[16]),"+f"(d[17]),"+f"(d[18]),"+f"(d[19]),"+f"(d[20]),"+f"(d[21]),"+f"(d[22]),"+f"(d[23]),"+f"(d[24]),"+f"(d[25]),"+f"(d[26]),"+f"(d[27]),"+f"(d[28]),"+f"(d[29]),"+f"(d[30]),"+f"(d[31]),"+f"(d[32]),"+f"(d[33]),"+f"(d[34]),"+f"(d[35]),"+f"(d[36]),"+f"(d[37]),"+f"(d[38]),"+f"(d[39]),"+f"(d[40]),"+f"(d[41]),"+f"(d[42]),"+f"(d[43]),"+f"(d[44]),"+f"(d[45]),"+f"(d[46]),"+f"(d[47]),"+f"(d[48]),"+f"(d[49]),"+f"(d[50]),"+f"(d[51]),"+f"(d[52]),"+f"(d[53]),"+f"(d[54]),"+f"(d[55]),"+f"(d[56]),"+f"(d[57]),"+f"(d[58]),"+f"(d[59]),"+f"(d[60]),"+f"(d[61]),"+f"(d[62]),"+f"(d[63]),"+f"(d[64]),"+f"(d[65]),"+f"(d[66]),"+f"(d[67]),"+f"(d[68]),"+f"(d[69]),"+f"(d[70]),"+f"(d[71]),"+f"(d[72]),"+f"(d[73]),"+f"(d[74]),"+f"(d[75]),"+f"(d[76]),"+f"(d[77]),"+f"(d[78]),"+f"(d[79]),"+f"(d[80]),"+f"(d[81]),"+f"(d[82]),"+f"(d[83]),"+f"(d[84]),"+f"(d[85]),"+f"(d[86]),"+f"(d[87]),"+f"(d[88]),"+f"(d[89]),"+f"(d[90]),"+f"(d[91]),"+f"(d[92]),"+f"(d[93]),"+f"(d[94]),"+f"(d[95]),"+f"(d[96]),"+f"(d[97]),"+f"(d[98]),"+f"(d[99]),"+f"(d[100]),"+f"(d[101]),"+f"(d[102]),"+f"(d[103]),"+f"(d[104]),"+f"(d[105]),"+f"(d[106]),"+f"(d[107]),"+f"(d[108]),"+f"(d[109]),"+f"(d[110]),"+f"(d[111]),"+f"(d[112]),"+f"(d[113]),"+f"(d[114]),"+f"(d[115]),"+f"(d[116]),"+f"(d[117]),"+f"(d[118]),"+f"(d[119]),"+f"(d[120]),"+f"(d[121]),"+f"(d[122]),"+f"(d[123]),"+f"(d[124]),"+f"(d[125]),"+f"(d[126]),"+f"(d[127])
    : "r"(da), "r"(db), "r"(sd));
}
__device__ __forceinline__ void wgmma_r1_n128(float (&d)[64], uint32_t da, uint32_t db, int sd) {
  asm volatile("{\n.reg .pred p;\n.reg .b64 a, b;\nsetp.ne.b32 p, %66, 0;\nmov.b64 a, {%64, 0x8};\nmov.b64 b, {%65, 0x6};\n"
    "wgmma.mma_async.sync.aligned.m64n128k16.f32.bf16.bf16 {%0,%1,%2,%3,%4,%5,%6,%7,%8,%9,%10,%11,%12,%13,%14,%15,%16,%17,%18,%19,%20,%21,%22,%23,%24,%25,%26,%27,%28,%29,%30,%31,%32,%33,%34,%35,%36,%37,%38,%39,%40,%41,%42,%43,%44,%45,%46,%47,%48,%49,%50,%51,%52,%53,%54,%55,%56,%57,%58,%59,%60,%61,%62,%63}, a, b, p, 1, 1, 0, 1;\n}\n"
    : "+f"(d[0]),"+f"(d[1]),"+f"(d[2]),"+f"(d[3]),"+f"(d[4]),"+f"(d[5]),"+f"(d[6]),"+f"(d[7]),"+f"(d[8]),"+f"(d[9]),"+f"(d[10]),"+f"(d[11]),"+f"(d[12]),"+f"(d[13]),"+f"(d[14]),"+f"(d[15]),"+f"(d[16]),"+f"(d[17]),"+f"(d[18]),"+f"(d[19]),"+f"(d[20]),"+f"(d[21]),"+f"(d[22]),"+f"(d[23]),"+f"(d[24]),"+f"(d[25]),"+f"(d[26]),"+f"(d[27]),"+f"(d[28]),"+f"(d[29]),"+f"(d[30]),"+f"(d[31]),"+f"(d[32]),"+f"(d[33]),"+f"(d[34]),"+f"(d[35]),"+f"(d[36]),"+f"(d[37]),"+f"(d[38]),"+f"(d[39]),"+f"(d[40]),"+f"(d[41]),"+f"(d[42]),"+f"(d[43]),"+f"(d[44]),"+f"(d[45]),"+f"(d[46]),"+f"(d[47]),"+f"(d[48]),"+f"(d[49]),"+f"(d[50]),"+f"(d[51]),"+f"(d[52]),"+f"(d[53]),"+f"(d[54]),"+f"(d[55]),"+f"(d[56]),"+f"(d[57]),"+f"(d[58]),"+f"(d[59]),"+f"(d[60]),"+f"(d[61]),"+f"(d[62]),"+f"(d[63])
    : "r"(da), "r"(db), "r"(sd));
}

__device__ __forceinline__ uint32_t smem_u32(const void* p) { return (uint32_t)__cvta_generic_to_shared(p); }
__device__ __forceinline__ void mbar_init(uint32_t bar, uint32_t cnt) { asm volatile("mbarrier.init.shared::cta.b64 [%0], %1;" ::"r"(bar), "r"(cnt)); }
__device__ __forceinline__ void mbar_expect_tx(uint32_t bar, uint32_t bytes) { asm volatile("mbarrier.arrive.expect_tx.shared::cta.b64 _, [%0], %1;" ::"r"(bar), "r"(bytes) : "memory"); }
__device__ __forceinline__ void mbar_arrive(uint32_t bar) { asm volatile("mbarrier.arrive.shared::cta.b64 _, [%0];" ::"r"(bar) : "memory"); }
__device__ __forceinline__ void mbar_arrive_n(uint32_t bar, uint32_t n) { asm volatile("mbarrier.arrive.shared::cta.b64 _, [%0], %1;" ::"r"(bar), "r"(n) : "memory"); }
__device__ __forceinline__ void mbar_wait(uint32_t bar, uint32_t parity) {
  asm volatile("{\n.reg .pred p;\nLAB_WAIT:\nmbarrier.try_wait.parity.shared::cta.b64 p, [%0], %1;\n@p bra DONE;\nbra LAB_WAIT;\nDONE:\n}" ::"r"(bar), "r"(parity) : "memory");
}
__device__ __forceinline__ void mbar_wait2(uint32_t a, uint32_t pa, uint32_t b, uint32_t pb) {
  asm volatile("{\n.reg .pred p, q;\nLAB_WAIT:\nmbarrier.try_wait.parity.shared::cta.b64 p, [%0], %1;\nmbarrier.try_wait.parity.shared::cta.b64 q, [%2], %3;\n"
               "and.pred p, p, q;\n@p bra DONE;\nbra LAB_WAIT;\nDONE:\n}" ::"r"(a), "r"(pa), "r"(b), "r"(pb) : "memory");
}
__device__ __forceinline__ void mbar_wait3(uint32_t a, uint32_t pa, uint32_t b, uint32_t pb) {
  asm volatile("{\n.reg .pred p, q, r;\nLAB_WAIT:\nmbarrier.try_wait.parity.shared::cta.b64 p, [%0], %1;\nmbarrier.try_wait.parity.shared::cta.b64 q, [%2], %3;\n"
               "mbarrier.try_wait.parity.shared::cta.b64 r, [%2+8], %3;\nand.pred p, p, q;\nand.pred p, p, r;\n@p bra DONE;\nbra LAB_WAIT;\nDONE:\n}" ::"r"(a), "r"(pa), "r"(b), "r"(pb) : "memory");
}
__device__ __forceinline__ bool mbar_probe2(uint32_t a, uint32_t pa, uint32_t b, uint32_t pb) {
  uint32_t ok;
  asm volatile("{\n.reg .pred p, q;\nmbarrier.test_wait.parity.shared::cta.b64 p, [%1], %2;\nmbarrier.test_wait.parity.shared::cta.b64 q, [%3], %4;\n"
               "and.pred p, p, q;\nselp.u32 %0, 1, 0, p;\n}" : "=r"(ok) : "r"(a), "r"(pa), "r"(b), "r"(pb) : "memory");
  return ok != 0;
}
__device__ __forceinline__ void tma_load_3d(uint32_t dst, const CUtensorMap* tm, uint32_t bar, int c0, int c1, int c2) {
  asm volatile("cp.async.bulk.tensor.3d.shared::cluster.global.mbarrier::complete_tx::bytes [%0], [%1, {%3, %4, %5}], [%2];"
               ::"r"(dst), "l"(tm), "r"(bar), "r"(c0), "r"(c1), "r"(c2) : "memory");
}
__device__ __forceinline__ void tma_load_2d(uint32_t dst, const CUtensorMap* tm, uint32_t bar, int c0, int c1) {
  asm volatile("cp.async.bulk.tensor.2d.shared::cluster.global.mbarrier::complete_tx::bytes [%0], [%1, {%3, %4}], [%2];"
               ::"r"(dst), "l"(tm), "r"(bar), "r"(c0), "r"(c1) : "memory");
}
__device__ __forceinline__ void tma_load_w(uint32_t dst, const CUtensorMap* tm, uint32_t bar, int col, int kb) {
#pragma unroll
  for (int q = 0; q < 2; q++)
    asm volatile("cp.async.bulk.tensor.5d.shared::cluster.global.mbarrier::complete_tx::bytes [%0], [%1, {%3, %4, %4, %4, %5}], [%2];"
                 ::"r"(dst + q * 8192), "l"(tm), "r"(bar), "r"(col + q * 64), "r"(0), "r"(2 * kb) : "memory");
}
__device__ __forceinline__ void tma_prefetch_w(const CUtensorMap* tm, int col, int kb) {
#pragma unroll
  for (int q = 0; q < 2; q++)
    asm volatile("cp.async.bulk.prefetch.tensor.5d.L2.global [%0, {%1, %2, %2, %2, %3}];" ::"l"(tm), "r"(col + q * 64), "r"(0), "r"(2 * kb) : "memory");
}
__device__ __forceinline__ void bulk_load(uint32_t dst, const void* g, uint32_t bytes, uint32_t bar) {
  asm volatile("cp.async.bulk.shared::cluster.global.mbarrier::complete_tx::bytes [%0], [%1], %2, [%3];" ::"r"(dst), "l"(g), "r"(bytes), "r"(bar) : "memory");
}
__device__ __forceinline__ void prefetch_map(const CUtensorMap* tm) { asm volatile("prefetch.tensormap [%0];" ::"l"(tm) : "memory"); }
__device__ __forceinline__ void fence_async_smem() { asm volatile("fence.proxy.async.shared::cta;" ::: "memory"); }
__device__ __forceinline__ void fence_async_global() { asm volatile("fence.proxy.async.global;" ::: "memory"); }
__device__ __forceinline__ void fence_gpu() { asm volatile("fence.release.gpu;" ::: "memory"); }
__device__ __forceinline__ void st_flag(unsigned* p, unsigned v) { asm volatile("st.relaxed.gpu.global.u32 [%0], %1;" ::"l"(p), "r"(v) : "memory"); }
__device__ __forceinline__ unsigned ld_flag(const unsigned* p) { unsigned v; asm volatile("ld.relaxed.gpu.global.u32 %0, [%1];" : "=r"(v) : "l"(p) : "memory"); return v; }
__device__ __forceinline__ uint4 ldcg4(const void* p) { uint4 v; asm volatile("ld.global.cg.v4.u32 {%0,%1,%2,%3}, [%4];" : "=r"(v.x), "=r"(v.y), "=r"(v.z), "=r"(v.w) : "l"(p)); return v; }
__device__ __forceinline__ uint4 ld_pkt(const uint4* p) {
  uint4 v; asm volatile("{\n.reg .b128 t;\nld.relaxed.gpu.global.b128 t, [%4];\nmov.b128 {%0,%1,%2,%3}, t;\n}" : "=r"(v.x), "=r"(v.y), "=r"(v.z), "=r"(v.w) : "l"(p) : "memory"); return v;
}
__device__ __forceinline__ void st_pkt(uint4* p, uint32_t a, uint32_t b, uint32_t c, uint32_t tag) {
  asm volatile("{\n.reg .b128 t;\nmov.b128 t, {%1,%2,%3,%4};\nst.relaxed.gpu.global.b128 [%0], t;\n}" ::"l"(p), "r"(a), "r"(b), "r"(c), "r"(tag) : "memory");
}
__device__ __forceinline__ void st_v4(uint4* p, uint32_t a, uint32_t b, uint32_t c, uint32_t d) { asm volatile("st.relaxed.gpu.global.v4.u32 [%0], {%1,%2,%3,%4};" ::"l"(p), "r"(a), "r"(b), "r"(c), "r"(d) : "memory"); }
__device__ __forceinline__ void stg128(uint4* p, uint4 v) { asm volatile("st.global.v4.u32 [%0], {%1,%2,%3,%4};" ::"l"(p), "r"(v.x), "r"(v.y), "r"(v.z), "r"(v.w) : "memory"); }
__device__ __forceinline__ void sts32(uint32_t addr, uint32_t a) { asm volatile("st.shared.u32 [%0], %1;" ::"r"(addr), "r"(a) : "memory"); }
__device__ __forceinline__ void sts64(uint32_t addr, uint32_t a, uint32_t b) { asm volatile("st.shared.v2.u32 [%0], {%1,%2};" ::"r"(addr), "r"(a), "r"(b) : "memory"); }
__device__ __forceinline__ uint32_t mul2(uint32_t a, uint32_t b) { uint32_t r; asm("mul.rn.bf16x2 %0, %1, %2;" : "=r"(r) : "r"(a), "r"(b)); return r; }
__device__ __forceinline__ uint32_t add2(uint32_t a, uint32_t b) { uint32_t r; asm("add.rn.bf16x2 %0, %1, %2;" : "=r"(r) : "r"(a), "r"(b)); return r; }
__device__ __forceinline__ bool elect() {
  uint32_t p; asm volatile("{\n.reg .pred q;\nelect.sync _|q, 0xffffffff;\nselp.u32 %0, 1, 0, q;\n}" : "=r"(p)); return p != 0;
}
__device__ __forceinline__ void wgmma_fence() { asm volatile("wgmma.fence.sync.aligned;" ::: "memory"); }
__device__ __forceinline__ void wgmma_commit() { asm volatile("wgmma.commit_group.sync.aligned;" ::: "memory"); }
template <int N> __device__ __forceinline__ void wgmma_wait() { asm volatile("wgmma.wait_group.sync.aligned %0;" ::"n"(N) : "memory"); }
template <int N> __device__ __forceinline__ void fence_regs(float (&d)[N]) {
#pragma unroll
  for (int i = 0; i < N; i++) asm volatile("" : "+f"(d[i])::"memory");
}
template <int R> __device__ __forceinline__ void reg_alloc() { asm volatile("setmaxnreg.inc.sync.aligned.u32 %0;" ::"n"(R)); }
template <int R> __device__ __forceinline__ void reg_dealloc() { asm volatile("setmaxnreg.dec.sync.aligned.u32 %0;" ::"n"(R)); }
__device__ __forceinline__ void wg_bar(int w) { asm volatile("bar.sync %0, 128;" ::"r"(w + 1) : "memory"); }
__device__ __forceinline__ constexpr uint32_t desc_lo(uint32_t addr, uint32_t lbo) { return (addr >> 4) + ((lbo >> 4) << 16); }
__device__ __forceinline__ uint32_t pack2(float lo, float hi) { uint32_t r; asm("cvt.rn.bf16x2.f32 %0, %1, %2;" : "=r"(r) : "f"(hi), "f"(lo)); return r; }
__device__ __forceinline__ float lo16(uint32_t v) { return __uint_as_float(v << 16); }
__device__ __forceinline__ float hi16(uint32_t v) { return __uint_as_float(v & 0xFFFF0000u); }
__device__ __forceinline__ float ex2(float x) { float r; asm("ex2.approx.ftz.f32 %0, %1;" : "=f"(r) : "f"(x)); return r; }
__device__ __forceinline__ float rcp(float x) { float r; asm("rcp.approx.ftz.f32 %0, %1;" : "=f"(r) : "f"(x)); return r; }
__device__ __forceinline__ uint32_t movm(uint32_t a) { uint32_t d; asm volatile("movmatrix.sync.aligned.m8n8.trans.b16 %0, %1;" : "=r"(d) : "r"(a)); return d; }
__device__ __forceinline__ void stsm4(uint32_t addr, uint32_t a, uint32_t b, uint32_t c, uint32_t d) {
  asm volatile("stmatrix.sync.aligned.m8n8.x4.shared.b16 [%0], {%1,%2,%3,%4};" ::"r"(addr), "r"(a), "r"(b), "r"(c), "r"(d) : "memory");
}
__device__ __forceinline__ void ldsm4(uint32_t addr, uint32_t (&r)[4]) {
  asm volatile("ldmatrix.sync.aligned.m8n8.x4.shared.b16 {%0,%1,%2,%3}, [%4];" : "=r"(r[0]), "=r"(r[1]), "=r"(r[2]), "=r"(r[3]) : "r"(addr) : "memory");
}
__device__ __forceinline__ void sts128(uint32_t addr, uint32_t a, uint32_t b, uint32_t c, uint32_t d) {
  asm volatile("st.shared.v4.u32 [%0], {%1,%2,%3,%4};" ::"r"(addr), "r"(a), "r"(b), "r"(c), "r"(d) : "memory");
}
__device__ __forceinline__ void lds128(uint32_t addr, uint32_t& a, uint32_t& b, uint32_t& c, uint32_t& d) {
  asm volatile("ld.shared.v4.u32 {%0,%1,%2,%3}, [%4];" : "=r"(a), "=r"(b), "=r"(c), "=r"(d) : "r"(addr) : "memory");
}
__device__ __forceinline__ float lds32f(uint32_t addr) { float v; asm volatile("ld.shared.f32 %0, [%1];" : "=f"(v) : "r"(addr) : "memory"); return v; }
__device__ __forceinline__ float2 lds64f(uint32_t addr) { float2 v; asm volatile("ld.shared.v2.f32 {%0,%1}, [%2];" : "=f"(v.x), "=f"(v.y) : "r"(addr) : "memory"); return v; }
__device__ __forceinline__ void mma16816(float (&d)[4], uint32_t a0, uint32_t a1, uint32_t a2, uint32_t a3, uint32_t b0, uint32_t b1) {
  asm("mma.sync.aligned.m16n8k16.row.col.f32.bf16.bf16.f32 {%0,%1,%2,%3}, {%4,%5,%6,%7}, {%8,%9}, {%0,%1,%2,%3};"
      : "+f"(d[0]), "+f"(d[1]), "+f"(d[2]), "+f"(d[3]) : "r"(a0), "r"(a1), "r"(a2), "r"(a3), "r"(b0), "r"(b1));
}
__device__ __forceinline__ void mma1688(float (&d)[4], uint32_t a0, uint32_t a1, uint32_t b0) {
  asm("mma.sync.aligned.m16n8k8.row.col.f32.bf16.bf16.f32 {%0,%1,%2,%3}, {%4,%5}, {%6}, {%0,%1,%2,%3};"
      : "+f"(d[0]), "+f"(d[1]), "+f"(d[2]), "+f"(d[3]) : "r"(a0), "r"(a1), "r"(b0));
}

__device__ __forceinline__ float qsum(float v) { v += __shfl_xor_sync(0xffffffffu, v, 1); v += __shfl_xor_sync(0xffffffffu, v, 2); return v; }

constexpr int NCTA = 132;
#define NB_ 6
#define NA_ 5
constexpr int NB = NB_;
constexpr int NA = NA_;
constexpr uint32_t SLOT = 16384;
constexpr uint32_t SB = 1024;
constexpr uint32_t OFF_B = 0;
constexpr uint32_t OFF_A = NB * SLOT;
constexpr uint32_t OFF_S = OFF_A + NA * SLOT;
constexpr uint32_t OFF_T = OFF_S + 20480;
constexpr uint32_t OFF_CS = OFF_T + 24576;
constexpr uint32_t OFF_MR = OFF_CS + 4640;
constexpr uint32_t OFF_BAR = OFF_MR + 512;
constexpr uint32_t OFF_MA = OFF_S, OFF_MB = OFF_CS - 2048;
constexpr uint32_t BAR_FULLB = OFF_BAR;
constexpr uint32_t BAR_FULLA = BAR_FULLB + 64;
constexpr uint32_t BAR_EMPTYB = BAR_FULLA + 64;
constexpr uint32_t BAR_EMPTYA = BAR_EMPTYB + 64;
constexpr uint32_t BAR_SIGP = BAR_EMPTYA + 64;
constexpr uint32_t BAR_SIGT = BAR_SIGP + 24;
constexpr uint32_t BAR_STAT = BAR_SIGP + 64;
constexpr uint32_t BAR_HALO = BAR_STAT + 16;
constexpr uint32_t BAR_CS = BAR_HALO + 8;
constexpr uint32_t BAR_WPHI = BAR_CS + 16;
constexpr uint32_t BAR_KV = BAR_WPHI + 8;
constexpr uint32_t BAR_STG = BAR_KV + 16;
constexpr uint32_t BAR_EPOCH = BAR_STG + 48;
constexpr uint32_t BAR_LAND = OFF_BAR + 7 * 64;
constexpr uint32_t OFF_EPOCH = OFF_BAR + 8 * 64;
static_assert(BAR_EPOCH < BAR_LAND, "barriers");
constexpr uint32_t SMEM_BYTES = OFF_EPOCH + 8;
static_assert(SMEM_BYTES <= 232448 && NB % 2 == 0 && NB <= 8 && NA <= 6, "smem");

#define CREGS 224
#define PREGS 56
#define PF1 19
#define PF2 21
#define PRE_A 2
#define PRE_B 4
#define CSB 4
#define CSNEED 0xF003u
#define XR 1
#define PS0 1
#define PS1 3
#define PSW 0
#define SD 1000
#define KSPLIT 12
#define KEEP 16
#define NJ 3
#define KSL 1000
#define PSL 0
#define KVS 12
#define D2 2000
#define D3 1500
#define G0 50
#define MAP 3
#define PMAP 0x76321450u
#define PW 1
#define XA 3
#define XS 1
#define CP 500
#define CD 0
#define S0 500
#define NS 2
#define XO 0
#define SW 2
#define SA 1
#define SB_ 4
#define XD 500
#define ND0 1
#define KC 8
#define CO 0
#define SE 500
#define DEFER 3
#define DEFL 2
#define TSK 3
#define TSL 3
constexpr int NTHREADS = 384;

struct Params {
  CUtensorMap mx;
  CUtensorMap mw[3];
  CUtensorMap mwo[2];
  CUtensorMap mcs[2];
  CUtensorMap mwphi;
  uint4* out;
};

#define XBUF(L) 1
__device__ __align__(256) uint4 g_img[XBUF(3) + 1][16][16][1024];
__device__ __forceinline__ uint32_t img_code(bool isx, int L) { return isx ? (L & 1) | (L & 2) << 15 : ~L & 1; }
__device__ __forceinline__ uint32_t img_mask(bool isx) { return isx ? 0x10001u : 1u; }
__device__ __align__(256) uint4 g_wf[2][8][16][1024];
__device__ __align__(256) uint4 g_stats[16][2][8][32];
__device__ __align__(256) uint4 g_halo[16][8][2][256];
__device__ __align__(256) float g_cs[2][2][3072];
__device__ __align__(256) uint4 g_kvpart[8][16][2][544];
__device__ __align__(256) uint4 g_kvfin[8][16][80];
__device__ __align__(256) unsigned g_hint[7][16][32];
__device__ __align__(256) unsigned g_hflag[2][16][8][32];
__device__ __align__(256) unsigned g_kvfflag[2][8][2][32];
__device__ __align__(256) unsigned g_csflag[2][8][32];
__device__ __align__(256) unsigned g_kflag[8][32];
__device__ unsigned g_ctr;
__device__ __forceinline__ unsigned vblock() {
  unsigned s;
  asm volatile("mov.u32 %0, %%smid;" : "=r"(s));
  const unsigned r = s & 1;
  s >>= 1;
  const unsigned t = s - 32, q = (t * 37) >> 8;
  const unsigned hi = s < 60 ? 12 + (t - 7 * q) * 8 + q : (s < 62 ? s + 4 : s - 58);
  unsigned b = 2 * (s < 32 ? (s & 7) * 8 + (s >> 3) : hi) + r;
  if (b < 128) b = (b & 15) | ((PMAP >> ((b >> 4) * 4)) & 7) << 4;
  if (s >= 62) b = 8 + 4 * r + s - 62;
  unsigned n;
  asm volatile("mov.u32 %0, %%nsmid;" : "=r"(n));
  return __shfl_sync(0xffffffffu, n == NCTA ? b : blockIdx.x, 0);
}
#define TS(who, id) do {} while (0)
#define TSW(id) do {} while (0)

#define TSMASK 0xFFFF
#define TSL_(a) do { if ((TSMASK >> (a)) & 1) TSW((a) + L * 12); } while (0)
__device__ __forceinline__ int cta_m(unsigned b) { return ((b >> 2) & 12) | (b & 3); }
__device__ __forceinline__ int cta_j(unsigned b) { return ((b >> 2) & 3) | ((b >> 4) & 4); }
struct Ring { uint32_t s, ph; };
template <int N> __device__ __forceinline__ void adv(Ring& r) { if (++r.s == N) { r.s = 0; r.ph ^= 1; } }
template <int N> __device__ __forceinline__ void rewind2(Ring& r) { if (r.s < 2) { r.s += N - 2; r.ph ^= 1; } else r.s -= 2; }
__device__ __forceinline__ int other_tile(int t, int j) { return (t == (j | 4) ? 7 : t) ^ (~j & 4); }
__device__ __forceinline__ int q_order(int i, int j) { return 2 * (i >= 14 ? j : other_tile(i >> 1, j)) + (i & 1); }
__device__ __forceinline__ int o_order(int i, int j) {
  if (i < 2) return 2 * j + i;
  const int odd = i >= 9;
  return 2 * other_tile(i - 2 - 7 * odd, j) + odd;
}
__device__ __forceinline__ int kv_order(int i, int j, int L) { return L > 0 ? o_order(i, j) : (i + 14 + 2 * (j & 4)) & 15; }

__device__ __forceinline__ unsigned poll_flags(const unsigned* f, int n, unsigned need, unsigned tag) {
  const int lane = threadIdx.x & 31;
  unsigned mask; int it = 0;
  do {
    unsigned v = lane < n ? ld_flag(f + lane) : 0u;
    mask = __ballot_sync(0xffffffffu, lane < n && v == tag);
    if (++it > (1 << 22)) __trap();
  } while ((mask & need) != need);
  fence_async_global();
  return mask;
}
template <bool WAIT = true>
__device__ __forceinline__ unsigned get_tag(uint32_t sb) {
  if (WAIT) mbar_wait(sb + BAR_EPOCH, 0);
  unsigned t; asm volatile("ld.shared.u32 %0, [%1];" : "=r"(t) : "r"(sb + OFF_EPOCH) : "memory");
  return t;
}

__device__ __forceinline__ int lane_id() { int l; asm volatile("mov.u32 %0, %%laneid;" : "=r"(l)); return l; }
__device__ __forceinline__ unsigned seq4(unsigned tag, int L) { return 8u | ((tag & 1u) << 2) | (unsigned)L; }
constexpr float LOG2E = 1.4426950408889634f;

__device__ __forceinline__ float bb_fence(int never, const void* p = &g_ctr, uint32_t keep = 0) {
  while (never < 0) never = ld_flag((const unsigned*)p) + keep;
  return __int_as_float(never >> 30);
}
__device__ __forceinline__ uint32_t solid(uint32_t v) { return __shfl_sync(0xffffffffu, v, threadIdx.x & 31); }
template <class T> __device__ __forceinline__ T* solid(T* p) { return (T*)__shfl_sync(0xffffffffu, (unsigned long long)p, threadIdx.x & 31); }
constexpr uint32_t HA128 = 0x40000040u, HA64 = 0x80000040u;
struct Ctx {
  static constexpr uint32_t sb = SB;
  uint32_t ab, da0;
  int w, warp, lane, g, c;
  int goff;
  __device__ __forceinline__ int m() const { return goff >> 14; }
  __device__ __forceinline__ int j() const { return (goff >> 4) & 7; }
  bool elected;
  Ring ra, rb;
  uint32_t pa, pb;
  uint32_t ha, k2;
  uint32_t mrow, mxor, mhi;
  __device__ __forceinline__ uint32_t aslot(uint32_t s) const { return ab + s * SLOT; }
  __device__ __forceinline__ uint32_t fullA(uint32_t s) const { return sb + BAR_FULLA + s * 8; }
  __device__ __forceinline__ uint32_t fullB(uint32_t s) const { return sb + BAR_FULLB + s * 8; }
  __device__ __forceinline__ void releaseA(uint32_t s) const { if (elected) mbar_arrive(sb + BAR_EMPTYA + s * 8); }
  __device__ __forceinline__ void releaseB(uint32_t s) const { if (elected) mbar_arrive(sb + BAR_EMPTYB + s * 8); }
  __device__ __forceinline__ uint32_t maddr(uint32_t tile, uint32_t ch) const { return tile + mrow + (((ch + mhi) ^ mxor) << 4); }
  __device__ __forceinline__ uint32_t oo() const { return warp * 128 + g * 4 + (c ^ (g >> 1)); }
  __device__ __forceinline__ uint4* img(int b, int hp) const { return ip + (b * 256 + hp) * 1024; }
  uint4* ip;
  uint32_t so;
  __device__ __forceinline__ uint32_t held(int i) const { return ra.s + i < 2 ? ra.s + i + NA - 2 : ra.s + i - 2; }
};

template <int N, bool FIRST, bool O = true>
__device__ __forceinline__ void gemm_issue(float (&acc)[N / 2], Ctx& x, bool ready = false) {
  if (!ready) {
    if (N == 256) mbar_wait3(x.fullA(x.ra.s), x.ra.ph, x.fullB(x.rb.s), x.rb.ph);
    else mbar_wait2(x.fullA(x.ra.s), x.ra.ph, x.fullB(x.rb.s), x.rb.ph);
  }
  const uint32_t da = x.da0 + x.ra.s * (SLOT / 16), db = desc_lo(SB + OFF_B, 8192) + x.rb.s * (SLOT / 16);
  wgmma_fence();
#pragma unroll
  for (int k = 0; k < 4; k++) {
    const uint32_t a = da + (k >> 1) * (O ? 32 : x.k2) + (k & 1) * 2, ha = O ? HA64 : x.ha;
    if constexpr (N == 256) wgmma_ss_n256(acc, a, ha, db + 128 * k, !(FIRST && k == 0));
    else wgmma_ss_n128(acc, a, ha, db + 128 * k, !(FIRST && k == 0));
  }
  wgmma_commit();
}
template <int N>
__device__ __forceinline__ void gemm_next(Ctx& x) {
  x.pa = x.ra.s; x.pb = x.rb.s;
  if (N == 256) x.rb.s++;
  adv<NA>(x.ra); adv<NB>(x.rb);
}
template <int N>
__device__ __forceinline__ void gemm_release(Ctx& x, bool relA) {
  if (relA) x.releaseA(x.pa);
  x.releaseB(x.pb);
  if (N == 256) x.releaseB(x.pb + 1);
}
template <int N>
__device__ __forceinline__ void gemm_retire(Ctx& x, bool relA) { wgmma_wait<1>(); gemm_release<N>(x, relA); gemm_next<N>(x); }
template <bool O = true>
__device__ __forceinline__ void gemm_run(float (&acc)[64], Ctx& x, int n, int hold, int n4 = 0) {
  bool ready = false;
#pragma unroll 1
  for (; n > 0; n--) {
    gemm_issue<128, false, O>(acc, x, ready);
    const uint32_t pa = x.pa, pb = x.pb;
    gemm_next<128>(x);
    ready = mbar_probe2(x.fullA(x.ra.s), x.ra.ph, x.fullB(x.rb.s), x.rb.ph);
    wgmma_wait<1>();
    if (n > hold) x.releaseA(pa);
    x.releaseB(pb);
  }
}
__device__ __forceinline__ void gemm_end(float (&acc)[64], Ctx& x) { wgmma_wait<0>(); fence_regs(acc); gemm_release<128>(x, false); }

__device__ __forceinline__ void rows_load(uint4* r, uint32_t tile, const Ctx& x) {
#pragma unroll
  for (int q = 0; q < 4; q++) {
    const uint32_t row = x.warp * 16 + 4 * q + (x.lane >> 3);
    lds128(tile + row * 128 + (((x.lane & 7) ^ (row & 7)) << 4), r[q].x, r[q].y, r[q].z, r[q].w);
  }
}
__device__ __forceinline__ void rows_store(const uint4* r, uint4* g) {
#pragma unroll
  for (int q = 0; q < 4; q++) stg128(g + q * 1024, r[q]);
}
__device__ __forceinline__ void publish(int id, const Ctx& x) { __syncwarp(); if (x.lane == 0) mbar_arrive(x.sb + BAR_SIGP + id * 8); }
__device__ __forceinline__ uint32_t img_tag(uint32_t v, bool isx, int L, const Ctx& x) {
  const uint32_t mk = ((x.lane ^ (x.warp * 4)) & 7) ? 0u : img_mask(isx);
  return (v & ~mk) | (img_code(isx, L) & mk);
}
__device__ __forceinline__ void img_tag(uint4 (&r)[4], bool isx, int L, const Ctx& x) {
#pragma unroll
  for (int q = 0; q < 4; q++) { uint32_t& v = q == 0 ? r[q].x : (q == 1 ? r[q].y : (q == 2 ? r[q].z : r[q].w)); v = img_tag(v, isx, L, x); }
}
__device__ __forceinline__ void img_store(const uint4 (&r)[4], uint4* g) {
#pragma unroll
  for (int q = 0; q < 4; q++) stg128(g + q * 32, r[q]);
}
__device__ __forceinline__ void img_sts(const uint4 (&r)[4], uint32_t tile, const Ctx& x) {
#pragma unroll
  for (int q = 0; q < 4; q++) sts128(tile + x.so + q * 512, r[q].x, r[q].y, r[q].z, r[q].w);
}
__device__ __forceinline__ void img_load(uint32_t (&v)[16], uint32_t tile, const Ctx& x) {
#pragma unroll
  for (int q = 0; q < 4; q++) lds128(tile + x.so + q * 512, v[4 * q], v[4 * q + 1], v[4 * q + 2], v[4 * q + 3]);
}
__device__ __forceinline__ void img_unpack(float* a, const uint32_t (&v)[16]) {
#pragma unroll
  for (int q = 0; q < 16; q++) { a[4 * (q & 7) + 2 * (q >> 3)] = lo16(v[q]); a[4 * (q & 7) + 2 * (q >> 3) + 1] = hi16(v[q]); }
}

template <int N>
__device__ __forceinline__ void stats_acc(const float* a, float (&t)[4]) {
#pragma unroll
  for (int i = 0; i < N; i++) { t[i & 2] += a[i]; t[(i & 2) + 1] = fmaf(a[i], a[i], t[(i & 2) + 1]); }
}
__device__ __forceinline__ void stats_send(float (&t)[4], int L, const Ctx& x) {
  const unsigned seq = seq4(get_tag<false>(x.sb), L);
#pragma unroll
  for (int q = 0; q < 4; q++) t[q] = qsum(t[q]);
  if (x.c == 0) st_pkt(&g_stats[x.m()][x.w][x.j()][x.warp * 8 + x.g], __float_as_uint(t[0]), __float_as_uint(t[1]), __float_as_uint(t[2]), (__float_as_uint(t[3]) & ~15u) | seq);
}
__device__ __forceinline__ void out_epilogue(const float (&acc)[64], uint4 (&r1)[4], float (&t)[4], uint4* g, int L, Ctx& x) {
  const uint32_t t0 = x.aslot(x.ra.s), t1 = x.aslot(x.ra.s + 1 == NA ? 0 : x.ra.s + 1);
  if (L == 3) {
#pragma unroll
    for (int p = 0; p < 8; p++) {
      stsm4(x.maddr(p < 4 ? t0 : t1, (p & 3) * 2), pack2(acc[8 * p], acc[8 * p + 1]), pack2(acc[8 * p + 2], acc[8 * p + 3]),
            pack2(acc[8 * p + 4], acc[8 * p + 5]), pack2(acc[8 * p + 6], acc[8 * p + 7]));
      if ((p & 3) == 3) { uint4 r[4]; __syncwarp(); rows_load(r, p < 4 ? t0 : t1, x); rows_store(r, g + (p >> 2) * 8); }
    }
  } else {
    auto pack16 = [&](uint4 (&r)[4], const float* a) {
#pragma unroll
      for (int q = 0; q < 4; q++) { const float* u = a + 16 * (q & 1) + (q & 2); r[q] = make_uint4(pack2(u[0], u[1]), pack2(u[4], u[5]), pack2(u[8], u[9]), pack2(u[12], u[13])); }
    };
    uint4 r0[4];
    pack16(r0, acc);
    img_tag(r0, true, L + 1, x);
    img_store(r0, x.img(XBUF(L + 1), 0));
    publish(1, x);
    const float z = bb_fence(x.goff);
    img_sts(r0, t0, x);
    pack16(r1, acc + 32);
    img_tag(r1, true, L + 1, x);
    img_sts(r1, t1, x);
    float u[4] = {z, z, z, z}, v[4] = {z, z, z, z};
    stats_acc<32>(acc, v);
    stats_acc<32>(acc + 32, u);
#pragma unroll
    for (int q = 0; q < 4; q++) t[q] = u[q] + v[q];
    mbar_wait2(x.fullB(x.rb.s), x.rb.ph, x.fullB(x.rb.s + 1), x.rb.ph);
    fence_async_smem();
    asm volatile("bar.sync %0, %1;" ::"r"(L == 1 ? x.w + 1 : 3), "r"(L == 1 ? 128 : 256) : "memory");
  }
}

struct Stats { float rstd0, rstd1; };
__device__ __forceinline__ Stats load_stats(int half, const Ctx& x) {
  const float2 u = lds64f(x.sb + OFF_MR + half * 256 + (x.warp * 8 + x.g) * 8);
  return {u.x, u.y};
}

template <int NH, int NK, class F>
__device__ __forceinline__ void hedgehog_scale(float* t, const Stats& st, const uint32_t* keep, F use) {
#pragma unroll
  for (int q = 0; q < 16 * NH; q++) t[q] *= ((q & 2) ? st.rstd1 : st.rstd0) * LOG2E;
  use();
  float m[4];
#pragma unroll
  for (int q = 0; q < 4 * NH; q++) {
    const float v = fmaxf(fmaxf(fabsf(t[4 * q]), fabsf(t[4 * q + 1])), fmaxf(fabsf(t[4 * q + 2]), fabsf(t[4 * q + 3])));
    m[q & 3] = q < 4 ? v : fmaxf(m[q & 3], v);
  }
  if (__builtin_expect(__any_sync(0xffffffffu, fmaxf(fmaxf(m[0], m[1]), fmaxf(m[2], m[3])) > 58.f), 0)) {
    float z[16 * NH + NK];
#pragma unroll
    for (int q = 0; q < 16 * NH + NK; q++) z[q] = q < 16 * NH ? t[q % (16 * NH)] : __uint_as_float(keep[q & 15]);
#pragma unroll 1
    for (int r = 0; r < 2 * NH; r++) {
      float hi = -INFINITY, lo = INFINITY;
#pragma unroll 1
      for (int i = 0; i < 16; i++) {
        const int k = (i & 6) * 2 + (i & 1) + (r & 1) * 2 + (r & 2) * 8;
        const float v = z[k];
        if (i < 8) { hi = fmaxf(hi, v); lo = fminf(lo, v); }
        else z[k] = v - fminf(fmaxf(v, lo), hi);
        if (i == 7) {
#pragma unroll 1
          for (int d = 1; d <= 2; d++) { hi = fmaxf(hi, __shfl_xor_sync(0xffffffffu, hi, d)); lo = fminf(lo, __shfl_xor_sync(0xffffffffu, lo, d)); }
          const float mid = 0.5f * hi + 0.5f * lo;
          hi = fmaxf(hi - 58.f, mid); lo = fminf(lo + 58.f, mid);
        }
      }
    }
#pragma unroll
    for (int q = 0; q < 16 * NH; q++) t[q] = z[q];
    use();
  }
}
__device__ __forceinline__ void dual_exp(const float* t, uint32_t (&f)[18], int never) {
  float e[KSPLIT];
#pragma unroll
  for (int q = 0; q < KSPLIT; q++) e[q] = ex2(q < 16 ? t[q] : -t[q & 15]);
  while (never < 0) {
#pragma unroll
    for (int i = 0; i < KSPLIT; i += 4) asm volatile("ld.shared.v4.f32 {%0,%1,%2,%3}, [%4];" : "=f"(e[i]), "=f"(e[i + 1]), "=f"(e[i + 2]), "=f"(e[i + 3]) : "r"(never + i) : "memory");
    never += __float_as_int(e[0]);
  }
#pragma unroll
  for (int q = 0; q < KSPLIT; q += 2) f[q >> 1] = pack2(e[q], e[q + 1]);
#pragma unroll
  for (int q = KSPLIT; q < 32; q += 2) f[q >> 1] = q < 16 ? pack2(ex2(t[q]), ex2(t[q + 1])) : pack2(ex2(-t[q & 15]), ex2(-t[(q & 15) + 1]));
#pragma unroll
  for (int sg = 0; sg < 2; sg++) {
    const uint32_t* u = f + 8 * sg;
    const uint32_t a = add2(add2(u[0], u[2]), add2(u[4], u[6])), b = add2(add2(u[1], u[3]), add2(u[5], u[7]));
    f[16 + sg] = add2(__byte_perm(a, b, 0x5410), __byte_perm(a, b, 0x7632));
  }
}
__device__ __forceinline__ void dual_exp_rcp(const float* t, uint32_t (&f)[16]) {
#pragma unroll
  for (int q = 0; q < 8; q++) {
    const float a = ex2(t[2 * q]), b = ex2(t[2 * q + 1]), r = rcp(a * b);
    f[q] = pack2(a, b); f[8 + q] = pack2(r * b, r * a);
  }
}
__device__ __forceinline__ void cta_bar() { asm volatile("bar.sync 3, 256;" ::: "memory"); }

template <int N> __device__ __forceinline__ void pin(const uint32_t* v, uint32_t addr) {
#pragma unroll
  for (int i = 0; i < N; i += 4)
    asm volatile("{\n.reg .pred p;\nsetp.eq.u32 p, %0, 0;\n@p st.shared.v4.u32 [%0], {%1,%2,%3,%4};\n}" ::"r"(addr), "r"(v[i]), "r"(v[i + 1]), "r"(v[i + 2]), "r"(v[i + 3]) : "memory");
}

__device__ __forceinline__ void consumer(const Params& P, uint32_t sb, int w, unsigned vb) {
  Ctx x;
  x.w = w;
  x.ab = sb + OFF_A + w * 8192; x.da0 = desc_lo(SB + OFF_A, 16) + w * 512;
  x.lane = threadIdx.x & 31; x.warp = __shfl_sync(0xffffffffu, (threadIdx.x >> 5) & 3, 0); x.g = x.lane >> 2; x.c = x.lane & 3;
  x.goff = (cta_m(vb) * 128 + w) * 128 + cta_j(vb) * 16;
  asm volatile("" : "+r"(x.goff));
  x.elected = (threadIdx.x & 127) == 0;
  x.ra = {0, 0}; x.rb = {0, 0}; x.pa = x.pb = 0;
  {
    const uint32_t row = x.warp * 16 + (x.lane & 15);
    x.mrow = row * 128; x.mxor = row & 7; x.mhi = x.lane >> 4;
  }
  const int goff = x.goff;
  x.ip = solid(&g_img[0][x.m()][2 * x.j()][w * 512 + x.oo()]);
  x.so = solid(16 * x.oo());
  uint4 r1[4];
  float ts[4] = {0.f, 0.f, 0.f, 0.f};
#pragma unroll
  for (int i = 0; i < 4; i++) r1[i] = make_uint4(0, 0, 0, 0);
  TSW(0);
  mbar_wait3(x.fullA(0), 0, x.fullB(0), 0);
#pragma unroll 1
  for (int L = 0; L < 4; L++) {
    float acc[64];
    constexpr uint32_t dcs = desc_lo(SB + OFF_CS, 0);
    if ((L & 1) == 0) {
    float kv[128];
    x.ha = L ? HA64 : HA128; x.k2 = L ? 32 : 4;
    gemm_issue<256, true, false>(kv, x, true); gemm_next<256>(x);
    {
      int i = 1;
#pragma unroll 1
      for (int seg = L ? NS - 1 : 0; seg <= NS; seg++) {
        const int end = seg < NS ? (L == 0 ? 3 + SA * ((x.j() + SW * w) & 3) + SB_ * seg : XA + 1) : 14 + L;
#pragma unroll 1
        do {
          gemm_issue<256, false, false>(kv, x);
          gemm_retire<256>(x, true);
          i++;
          if (i == 5) TSL_(8);
          if (i == 11) TSL_(10);
        } while (i != end);
        if (seg < NS && L == 0) {
          uint32_t v[16];
          float a[32];
#pragma unroll
          for (int q = 0; q < 4; q++) ldsm4(x.maddr(x.aslot(x.pa), 2 * q), reinterpret_cast<uint32_t (&)[4]>(v[4 * q]));
#pragma unroll
          for (int q = 0; q < 16; q++) { a[2 * q] = lo16(v[q]); a[2 * q + 1] = hi16(v[q]); }
          stats_acc<32>(a, ts);
          fence_regs(ts);
          wg_bar(w);
        }
        if (seg == NS - 1) {
          if (L > 0) { img_store(r1, x.img(XBUF(L), 1)); publish(2, x); }
          mbar_wait(sb + BAR_EPOCH, 0);
          stats_send(ts, L, x);
        }
      }
    }
      const Ring kt = x.ra;
      if (L == 0) adv<NA>(x.ra);
#pragma unroll 1
      for (int h = L; h < 2; h++) {
        float d[16];
        mbar_wait2(x.fullA(kt.s), kt.ph, sb + BAR_WPHI, 0);
        wgmma_fence();
#pragma unroll
        for (int q = 0; q < 2; q++) wgmma_ss_n32(d, x.da0 + kt.s * (SLOT / 16) + h * 4 + q * 2, desc_lo(SB + OFF_S + 4096, 512) + w * 256 + h * 128 + q * 64, q);
        wgmma_commit();
        gemm_issue<256, false, false>(kv, x);
        gemm_retire<256>(x, true);
        if (h) x.releaseA(kt.s);
        fence_regs(d);
        uint4* dst = &g_wf[1][x.j()][x.m()][w * 512 + (x.warp * 16 + x.g) * 8 + ((h * 4 + x.c) ^ x.g)];
        dst[0] = make_uint4(pack2(d[0], d[1]), pack2(d[4], d[5]), pack2(d[8], d[9]), pack2(d[12], d[13]));
        dst[64] = make_uint4(pack2(d[2], d[3]), pack2(d[6], d[7]), pack2(d[10], d[11]), pack2(d[14], d[15]));
      }
      const uint32_t dm = desc_lo(SB + OFF_MA, 0) + w * 64;
      mbar_wait2(sb + BAR_STAT, 0, sb + BAR_CS, 0);
      wgmma_fence();
      wgmma_r1_n256(kv, dm, dcs + 96, 1);
      wgmma_commit();
      const Stats st = load_stats(w, x);
      mbar_wait2(x.fullA(x.ra.s), x.ra.ph, x.fullB(x.rb.s), x.rb.ph);
      wgmma_wait<0>();
      fence_regs(kv);
      gemm_release<256>(x, true);
      TSL_(2);
      uint32_t P0[32], P1[32], PH[32];
#pragma unroll
      for (int t = 0; t < 16; t++) { P0[t] = pack2(kv[4 * t] * st.rstd0, kv[4 * t + 1] * st.rstd0); P1[t] = pack2(kv[4 * t + 2] * st.rstd1, kv[4 * t + 3] * st.rstd1); }
      pin<16>(P0, x.mrow + 16);
      {
#pragma unroll
        for (int q = 0; q < 4; q++) sts128((x.warp < 3 ? sb + OFF_T + w * 12288 + x.warp * 4096 : sb + OFF_S + 16384 + w * 2048) + x.lane * 16 + q * 512, P1[4 * q], P1[4 * q + 1], P1[4 * q + 2], P1[4 * q + 3]);
      }
      wgmma_fence();
      wgmma_r1_n128(acc, dm, dcs, 0);
      gemm_issue<128, false, false>(acc, x, PW & 1); gemm_next<128>(x);
      TSL_(3);
#pragma unroll
      for (int s = 0; s < 4; s++) {
#pragma unroll
        for (int t = 16 + 8 * (s & 1); t < 24 + 8 * (s & 1); t++) {
          if (s < 2) P1[t] = movm(pack2(kv[4 * t + 2] * st.rstd1, kv[4 * t + 3] * st.rstd1));
          else P0[t] = movm(pack2(kv[4 * t] * st.rstd0, kv[4 * t + 1] * st.rstd0));
        }
        if (s < 3) { gemm_issue<128, false, false>(acc, x); gemm_retire<128>(x, true); }
        if (s == 1) {
          if (x.warp < 3) {
#pragma unroll
            for (int q = 4; q < 8; q++) sts128(sb + OFF_T + w * 12288 + x.warp * 4096 + x.lane * 16 + q * 512, P1[4 * q], P1[4 * q + 1], P1[4 * q + 2], P1[4 * q + 3]);
          } else {
            uint4* dst = &g_halo[x.m()][x.j()][w][x.lane];
#pragma unroll
            for (int q = 0; q < 8; q++) dst[q * 32] = make_uint4(P1[4 * q], P1[4 * q + 1], P1[4 * q + 2], P1[4 * q + 3]);
          }
          publish(3, x);
          gemm_issue<128, false, false>(acc, x);
          gemm_retire<128>(x, true);
        }
      }
      TSL_(4);
      gemm_run<false>(acc, x, 10, 0);
      gemm_issue<128, false, false>(acc, x);
      {
        wg_bar(w);
        uint32_t tr = sb + OFF_T + w * 12288 + (x.warp - 1) * 4096;
        if (x.warp == 0) {
          tr = x.m() > 0 ? sb + OFF_S + 8192 + w * 4096 : tr + 4096;
          if (x.m() > 0) mbar_wait(sb + BAR_HALO, L >> 1);
        }
#pragma unroll
        for (int q = 0; q < 8; q++) lds128(tr + x.lane * 16 + q * 512, PH[4 * q], PH[4 * q + 1], PH[4 * q + 2], PH[4 * q + 3]);
      }
      gemm_retire<128>(x, false);
      gemm_end(acc, x);
      TSL_(5);
      const bool first = (x.m() == 0) && (x.warp == 0);
      const bool hi0 = 2 * x.c > x.g, hi1 = 2 * x.c + 1 > x.g;
      const uint32_t mhi = (hi0 ? 0xFFFFu : 0u) | (hi1 ? 0xFFFF0000u : 0u);
      const float sc0 = st.rstd0 * (0.17677669529663687f * LOG2E), sc1 = st.rstd1 * (0.17677669529663687f * LOG2E);
#pragma unroll
      for (int hp = 0; hp < 2; hp++) {
        const uint32_t tile = x.aslot(x.held(hp));
        uint32_t px[2], py[2];
        float s[2][3][4];
#pragma unroll
        for (int u = 0; u < 2; u++) {
#pragma unroll
          for (int q = 0; q < 12; q++) s[u][q >> 2][q & 3] = 0.f;
#pragma unroll
          for (int ks = 0; ks < 2; ks++) {
            const int t = 8 * hp + 4 * u + 2 * ks;
            const uint32_t a0 = pack2(acc[4 * t], acc[4 * t + 1]), a1 = pack2(acc[4 * t + 2], acc[4 * t + 3]);
            const uint32_t a2 = pack2(acc[4 * t + 4], acc[4 * t + 5]), a3 = pack2(acc[4 * t + 6], acc[4 * t + 7]);
            mma16816(s[u][0], a0, a1, a2, a3, PH[t], PH[t + 1]);
            mma16816(s[u][1], a0, a1, a2, a3, P0[t], P0[t + 1]);
            mma16816(s[u][2], a0, a1, a2, a3, P1[t], P1[t + 1]);
          }
        }
        float e[2][4], r[2][2];
#pragma unroll
        for (int u = 0; u < 2; u++) {
          e[u][0] = (hi0 ? s[u][0][0] : s[u][1][0]) * sc0; e[u][1] = (hi1 ? s[u][0][1] : s[u][1][1]) * sc0;
          e[u][2] = (hi0 ? s[u][1][2] : s[u][2][2]) * sc1; e[u][3] = (hi1 ? s[u][1][3] : s[u][2][3]) * sc1;
          if (first) { if (hi0) e[u][0] = -1e30f; if (hi1) e[u][1] = -1e30f; }
          r[u][0] = fmaxf(e[u][0], e[u][1]); r[u][1] = fmaxf(e[u][2], e[u][3]);
        }
#pragma unroll
        for (int d = 1; d <= 2; d++)
#pragma unroll
          for (int q = 0; q < 4; q++) r[q >> 1][q & 1] = fmaxf(r[q >> 1][q & 1], __shfl_xor_sync(0xffffffffu, r[q >> 1][q & 1], d));
#pragma unroll
        for (int u = 0; u < 2; u++) {
#pragma unroll
          for (int q = 0; q < 4; q++) e[u][q] = ex2(e[u][q] - r[u][q >> 1]);
          r[u][0] = e[u][0] + e[u][1]; r[u][1] = e[u][2] + e[u][3];
        }
#pragma unroll
        for (int d = 1; d <= 2; d++)
#pragma unroll
          for (int q = 0; q < 4; q++) r[q >> 1][q & 1] += __shfl_xor_sync(0xffffffffu, r[q >> 1][q & 1], d);
#pragma unroll
        for (int u = 0; u < 2; u++) {
          const float rx = rcp(r[u][0]), ry = rcp(r[u][1]);
          px[u] = pack2(e[u][0] * rx, e[u][1] * rx); py[u] = pack2(e[u][2] * ry, e[u][3] * ry);
        }
        uint32_t o[8][2];
        uint4 ro[4];
#pragma unroll
        for (int q = 0; q < 8; q++) {
          float d[4] = {0.f, 0.f, 0.f, 0.f};
          const int t = 16 + 8 * hp + q, u = q >> 2;
          mma16816(d, px[u] & mhi, 0u, px[u] & ~mhi, py[u] & mhi, PH[t], P0[t]);
          mma1688(d, 0u, py[u] & ~mhi, P1[t]);
          o[q][0] = pack2(d[0], d[1]); o[q][1] = pack2(d[2], d[3]);
        }
#pragma unroll
        for (int q = 0; q < 4; q++) ro[q] = make_uint4(o[4 * (q & 1)][q >> 1], o[4 * (q & 1) + 1][q >> 1], o[4 * (q & 1) + 2][q >> 1], o[4 * (q & 1) + 3][q >> 1]);
        img_tag(ro, false, 0, x);
        img_store(ro, x.img(0, hp));
        if (hp == 0) publish(0, x);
        uint32_t xs[16];
        if (L) img_load(xs, tile, x);
        else {
#pragma unroll
          for (int q = 0; q < 4; q++) {
            uint32_t v[4];
            ldsm4(x.maddr(tile, 2 * q), v);
            xs[2 * q] = v[0]; xs[8 + 2 * q] = v[1]; xs[2 * q + 1] = v[2]; xs[9 + 2 * q] = v[3];
          }
          __syncwarp();
        }
        img_sts(ro, tile, x);
        img_unpack(acc + 32 * hp, xs);
      }
    } else {
      float kv[128];
      float (&kv0)[64] = reinterpret_cast<float (&)[64]>(kv[0]);
      float (&kv1)[64] = reinterpret_cast<float (&)[64]>(kv[64]);
      auto mma8 = [&](uint32_t as, uint32_t bs, int i, bool fence) {
        const uint32_t da = desc_lo(SB + OFF_A, 16) + as * (SLOT / 16), db = desc_lo(SB + OFF_B, 8192) + bs * (SLOT / 16);
        if (fence) wgmma_fence();
#pragma unroll
        for (int k = 0; k < 4; k++) {
          wgmma_ss_n128(kv0, da + (k >> 1) * 32 + (k & 1) * 2, HA64, db + 128 * k, i + k);
          wgmma_ss_n128(kv1, da + 512 + (k >> 1) * 32 + (k & 1) * 2, HA64, db + 128 * k, i + k);
        }
        wgmma_commit();
      };
      constexpr uint32_t dm = desc_lo(SB + OFF_MB, 0);
      auto relB = [&](uint32_t s) { mbar_arrive_n(sb + BAR_EMPTYB + s * 8, 2); };
      auto skip = [&]() {
#pragma unroll
        for (int q = 0; q < 6 - NJ; q++) adv<NA>(x.ra);
        x.rb.s = w ? (2 + NJ) % 6 : 4;
        if (!w && NJ < 4) x.rb.ph ^= 1;
      };
      static_assert(NA == 5 && NB == 6, "ring arithmetic");
      mma8(x.ra.s, x.rb.s + w, 0, true);
      gemm_next<256>(x);
#pragma unroll 1
      for (int i = 1; i < NJ; i++) {
        mbar_wait2(x.fullA(x.ra.s), x.ra.ph, x.fullB(x.rb.s + w), x.rb.ph);
        mma8(x.ra.s, x.rb.s + w, 1, true);
        if (!XO && i == XR) { img_store(r1, x.img(XBUF(L), 1)); publish(2, x); }
        if (!XO && i == XS) stats_send(ts, L, x);
        wgmma_wait<1>();
        if (x.elected) { x.releaseA(x.pa); relB(x.pb + w); }
        gemm_next<256>(x);
        if (XO && i == XR) { img_store(r1, x.img(XBUF(L), 1)); publish(2, x); stats_send(ts, L, x); }
      }
      if (w) {
        wgmma_wait<0>();
        if (x.elected) { x.releaseA(x.pa); relB(x.pb + 1); }
        skip();
        asm volatile("bar.sync 7, 256;" ::: "memory");
      }
      TSL_(8);
      {
        const int t = lane_id() + 32 * x.warp;
        uint32_t mask = t < 2 ? ((w ? (t ? 0xFF3Fu : 0x3FFFu) : 0xFFFFu) >> (NJ - 1)) & (w ? ~1u : ~0u) : 0u, cnt = 1 + t;
        bool ready = false;
#pragma unroll 1
        for (int i = NJ; i < 16; i++) {
          if (!ready) mbar_wait2(x.fullA(x.ra.s), x.ra.ph, x.fullB(x.rb.s), x.rb.ph);
          mma8(x.ra.s, x.rb.s, 1, true);
          const uint32_t bar = sb + (t ? BAR_EMPTYB + x.pb * 8 : BAR_EMPTYA + x.pa * 8);
          gemm_next<128>(x);
          if (w && (i | 4) == 15) x.rb.s = 4;
          ready = mbar_probe2(x.fullA(x.ra.s), x.ra.ph, x.fullB(x.rb.s), x.rb.ph);
          wgmma_wait<1>();
          if (mask & 1) mbar_arrive_n(bar, cnt);
          mask >>= 1; cnt = 2;
          if (i == 8 && w) asm volatile("bar.arrive 9, 256;" ::: "memory");
          if (i == 9) TSL_(10);
        }
        mbar_wait2(sb + BAR_STAT, 1, sb + BAR_CS + 8, 0);
        wgmma_fence();
        wgmma_r1_n128(kv0, dm, dcs + 96 + 96 * w, 1);
        wgmma_r1_n128(kv1, dm + 64, dcs + 96 + 96 * w, 1);
        wgmma_commit();
        if (w == 0) asm volatile("bar.arrive 7, 256;" ::: "memory");
        wgmma_wait<1>();
        if (mask & 1) mbar_arrive_n(sb + (t ? BAR_EMPTYB + x.pb * 8 : BAR_EMPTYA + x.pa * 8), 2);
      }
      const Stats s0 = load_stats(0, x), s1 = load_stats(1, x), st = w ? s1 : s0;
      if (w == 0) skip();
      const uint32_t h0 = x.held(0), h1 = x.held(1);
      auto vreg = [&](int ks) { return ks < 6 ? OFF_A + (ks < 3 ? h0 * SLOT : h1 * SLOT - 15360) + ks * 5120 : OFF_S + 2048 + ks * 5120; };
      uint32_t tV[2], uu[4];
#pragma unroll
      for (int hf = 0; hf < 2; hf++) {
        tV[hf] = sb + vreg(4 * hf + x.warp) + ((x.lane >> 3) & 1) * 2560 + (x.lane & 7) * 16 + x.mhi * 128;
        const float i0 = rcp(hf ? s1.rstd0 : s0.rstd0), i1 = rcp(hf ? s1.rstd1 : s0.rstd1);
        const uint32_t h = pack2(i0, i1);
        uu[2 * hf] = pack2(lo16(h), i0 - lo16(h)); uu[2 * hf + 1] = pack2(hi16(h), i1 - hi16(h));
        asm volatile("" : "+r"(tV[hf]), "+r"(uu[2 * hf]), "+r"(uu[2 * hf + 1])::"memory");
      }
      wgmma_wait<0>();
      fence_regs(kv);
      TSL_(2);
      if (w == 0) {
        uint32_t f[2][18], ad[4];
#pragma unroll
        for (int q = 0; q < 18; q++) f[1][q] = 0u;
#pragma unroll
        for (int q = 0; q < 4; q++) ad[q] = x.maddr(sb + OFF_S, 2 * q);
        auto norm = [&](int un) {
          uint32_t* u = f[un & 1];
          const Stats& sn = (un & 2) ? s1 : s0;
#pragma unroll
          for (int sg = 0; sg < 2; sg++) {
            uint32_t v = u[16 + sg];
            v = add2(v, __shfl_xor_sync(0xffffffffu, v, 1)); v = add2(v, __shfl_xor_sync(0xffffffffu, v, 2));
            const float a = rcp(lo16(v)) * sn.rstd0, b = rcp(hi16(v)) * sn.rstd1;
            const uint32_t r0 = pack2(a, a), r1_ = pack2(b, b);
#pragma unroll
            for (int q = 8 * sg; q < 8 * sg + 8; q++) u[q] = mul2(u[q], (q & 1) ? r1_ : r0);
#pragma unroll
            for (int q = 2 * sg; q < 2 * sg + 2; q++) stsm4(ad[q] + (un & 1) * SLOT + (un >> 1) * 8192, u[4 * q], u[4 * q + 1], u[4 * q + 2], u[4 * q + 3]);
          }
        };
        auto unit = [&](int un) { return kv + ((un >> 1) & 1) * 64 + (un & 1) * 16 + (un >> 2) * 32; };
        hedgehog_scale<1, 0>(kv, s0, nullptr, [] {});
#pragma unroll 1
        for (int it = 0;; it++) {
#pragma unroll
          for (int un = 0; un < 4; un++) {
            if (un == 1) {
              if (it) asm volatile("bar.sync 9, 256;" ::: "memory");
#pragma unroll
              for (int q = 0; q < 4; q++) ad[q] -= it * (OFF_S - OFF_B - 2 * SLOT);
            }
            norm((un + 3) & 3);
            dual_exp(unit(un), f[un & 1], x.goff);
            hedgehog_scale<1, KEEP>(unit(un + 1), ((un + 1) & 2) ? s1 : s0, f[(un + 1) & 1], [] {});
          }
          if (it) break;
#pragma unroll
          for (int q = 0; q < 32; q++) {
            asm volatile("mov.b32 %0, %1;" : "=f"(kv[q]) : "f"(kv[q + 32]));
            asm volatile("mov.b32 %0, %1;" : "=f"(kv[q + 64]) : "f"(kv[q + 96]));
            if (q < 16) kv[32 + q] = 0.f;
          }
        }
        norm(3);
        TSL_(3);
      } else {
        wg_bar(w);
#pragma unroll
        for (int hf = 0; hf < 2; hf++) {
          stsm4(tV[hf] + 512 + x.mhi * 512, uu[2 * hf], uu[2 * hf + 1], uu[2 * hf], uu[2 * hf + 1]);
          stsm4(tV[hf] + 1792 + x.mhi * 512, uu[2 * hf], uu[2 * hf + 1], uu[2 * hf], uu[2 * hf + 1]);
#pragma unroll
          for (int q = 0; q < 8; q++) {
            const float* u = kv + 64 * hf + 8 * q;
            stsm4(tV[hf] + (q >> 1) * 640 + (q & 1) * 256, pack2(u[0], u[1]), pack2(u[2], u[3]), pack2(u[4], u[5]), pack2(u[6], u[7]));
          }
        }
        TSL_(3);
      }
      {
        float d[2][20];
        uint4* dst = &g_kvpart[x.j()][w * 4 + x.warp][0][x.m() * 32 + x.lane];
        unsigned* dz = reinterpret_cast<unsigned*>(&g_kvpart[x.j()][w * 4 + x.warp][x.c & 1][512]) + x.m() * 8 + x.g;
        fence_async_smem();
        cta_bar();
        TSL_(11);
        uint32_t pk[9];
        auto prep = [&](float (&u)[20]) {
          fence_regs(u);
#pragma unroll
          for (int q = 0; q < 8; q++) pk[q] = pack2(u[((q >> 1) & 2) + 4 * (q & 3)], u[((q >> 1) & 2) + 4 * (q & 3) + 1]);
          pk[8] = __float_as_uint((x.c & 1) ? u[18] + u[19] : u[16] + u[17]);
#pragma unroll
          for (int q = 0; q < 9; q += 4) pk[q] = (pk[q] & ~1u) | (L == 1);
        };
        auto send = [&](int hp) {
          st_v4(dst + hp * 16 * 544, pk[0], pk[1], pk[2], pk[3]); st_v4(dst + (hp * 16 + 1) * 544, pk[4], pk[5], pk[6], pk[7]);
          st_flag(dz + hp * 16 * 544 * 4, pk[8]);
        };
        wgmma_fence();
#pragma unroll
        for (int q = 0; q < 17; q++) {
          if (q < 16) wgmma_ss_n40_tt(d[q >> 3], desc_lo(SB + (q < 8 ? OFF_S : OFF_B + 2 * SLOT), 1024) + w * (SLOT / 16) + 128 * (q & 7), desc_lo(SB + vreg(q & 7), 2560) + (w + (q >> 3) * 2) * 40, q & 7);
          else wgmma_r1_n128(acc, dm + w * 64, dcs, 0);
          if (q == 7 || q == KVS || q == 16) wgmma_commit();
          if (q == KVS) { mbar_wait2(x.fullA(x.ra.s), x.ra.ph, x.fullB(x.rb.s), x.rb.ph); wgmma_wait<1>(); prep(d[0]); send(0); bb_fence(x.goff); wgmma_fence(); }
        }
        gemm_issue<128, false>(acc, x, true); gemm_next<128>(x);
        wgmma_wait<1>();
        x.releaseA(h0); x.releaseA(h1); x.releaseB(2); x.releaseB(3);
        if (x.lane == 0) mbar_arrive(sb + BAR_SIGT);
        prep(d[1]);
        TSL_(4);
#pragma unroll 1
        for (int seg = 0; seg < 2; seg++) {
          const int n0 = w ? PS1 : PS0;
          gemm_run(acc, x, seg ? 15 - n0 : n0, seg, seg ? L : 0);
          if (seg == 0) send(1);
        }
      }
      gemm_end(acc, x);
      TSL_(5);
      {
        float dp[2][20], dn[2][20];
        uint32_t f[4][16];
        auto mma = [&](int h) {
          if (!(h & 1)) mbar_wait(sb + BAR_KV + h * 4, L >> 1);
          if (h == 0) TSL_(9);
          const uint32_t db = desc_lo(SB + OFF_S + h * 5120, 128);
          const uint32_t (&a)[16] = f[h];
          wgmma_fence();
          wgmma_rs_n40(dp[h & 1], a[0], a[1], a[2], a[3], db, 0);
          wgmma_rs_n40(dn[h & 1], a[8], a[9], a[10], a[11], db + 160, 0);
          wgmma_rs_n40(dp[h & 1], a[4], a[5], a[6], a[7], db + 80, 1);
          wgmma_rs_n40(dn[h & 1], a[12], a[13], a[14], a[15], db + 240, 1);
          wgmma_commit();
        };
        uint32_t xr[16];
        auto fin = [&](int h) {
          const uint32_t tile = x.aslot(x.held(h >> 1));
          if (!(h & 1)) img_load(xr, tile, x);
          float (&u)[20] = dp[h & 1];
          float (&v)[20] = dn[h & 1];
          fence_regs(u); fence_regs(v);
#pragma unroll
          for (int r = 0; r < 2; r++) {
            const float sp = u[16 + 2 * r], sn = v[16 + 2 * r];
            const float id = rcp(fmaf(fmaf(sp, L == 1 ? 0.065536f * 128 / 129 : 0.065536f, u[17 + 2 * r]), sn, v[17 + 2 * r] * sp)), aa = sn * id, cc = sp * id;
            uint32_t o[4];
#pragma unroll
            for (int t = 0; t < 4; t++) o[t] = pack2(fmaf(u[4 * t + 2 * r], aa, v[4 * t + 2 * r] * cc), fmaf(u[4 * t + 2 * r + 1], aa, v[4 * t + 2 * r + 1] * cc));
            o[2 * r + (h & 1)] = img_tag(o[2 * r + (h & 1)], false, 1, x);
            stg128(x.img(0, h >> 1) + r * 64 + (h & 1) * 32, make_uint4(o[0], o[1], o[2], o[3]));
            sts128(tile + r * 1024 + (h & 1) * 512 + x.so, o[0], o[1], o[2], o[3]);
          }
          if (h & 1) { if (h == 1) publish(0, x); img_unpack(acc + 16 * (h - 1), xr); }
        };
        auto ex = [&](int h) { dual_exp_rcp(acc + 16 * h, f[h]); };
        Stats sq = st;
#pragma unroll
        for (int h = 0; h < 4; h += 2) {
          hedgehog_scale<2, 0>(acc + 16 * h, sq, nullptr, [&] { ex(h); });
          mma(h);
          ex(h + 1); wgmma_wait<0>(); fin(h);
          if (h == 0) bb_fence(x.goff);
          mma(h + 1);
          wgmma_wait<0>(); fin(h + 1);
          if (h == 0) sq.rstd1 += bb_fence(x.goff);
        }
      }
    }
    if (PW & 2) { mbar_wait(x.fullB(x.rb.s), x.rb.ph); fence_regs(acc); }
    fence_async_smem();
    wg_bar(w);
    TSL_(6);
    rewind2<NA>(x.ra);
    gemm_issue<128, false>(acc, x, PW & 2); gemm_next<128>(x);
    uint4* out = solid(P.out + goff + (x.warp * 16 + (x.lane >> 3)) * 256 + (x.lane & 7));
#pragma unroll 1
    for (int seg = L >= TSL ? 0 : 1; seg < 2; seg++) {
      gemm_run(acc, x, L >= TSL ? (seg ? TSK : 15 - TSK) : 15, seg, 10 + L);
      if (L >= TSL) {
        if (seg == 0 && w == 1) asm volatile("bar.sync 6, 256;" ::: "memory");
        if (seg == 1 && w == 0) asm volatile("bar.arrive 6, 256;" ::: "memory");
      }
    }
    gemm_end(acc, x);
    TSL_(7);
    rewind2<NA>(x.ra);
    out_epilogue(acc, r1, ts, out, L, x);
    TSL_(13);
  }
}

typedef unsigned long long u64;
template <class T> __device__ __forceinline__ T* early(T* p) { return (T*)__shfl_xor_sync(0xffffffffu, (u64)p, 1); }
__device__ __forceinline__ void pause(uint32_t GAP) {
  if (GAP) { uint32_t t0, t; asm volatile("mov.u32 %0, %%clock;" : "=r"(t0)); do { asm volatile("mov.u32 %0, %%clock;" : "=r"(t)); } while (t - t0 < GAP); }
}
__device__ __forceinline__ u64 order_table(int kind, int j) {
  const int i = threadIdx.x & 15;
  const unsigned v = (unsigned)(kind == 2 ? q_order(i, j) : kv_order(i, j, kind)) << (4 * (i & 7));
  return (u64)__reduce_or_sync(0xffffffffu, i < 8 ? 0u : v) << 32 | __reduce_or_sync(0xffffffffu, i < 8 ? v : 0u);
}

__device__ __forceinline__ void b_producer(const Params& P, uint32_t sb, unsigned vb) {
  const int j = cta_j(vb);
  const u64 t0 = order_table(0, j), t1 = order_table(1, j), t2 = order_table(2, j);
  Ring r = {PRE_B % NB, PRE_B < NB};
#pragma unroll 1
  for (int sg = 0; sg < 20; sg++) {
    const int L = sg / 5, p = sg - 5 * L, wt = L & 1;
    int n = p >= 3 ? 16 : (wt ? (p ? 16 - NJ : 2 * NJ) : (p ? 0 : (L ? 32 : 32 - PRE_B)));
    u64 tab = p == 3 ? t2 : (sg == 0 ? t0 >> (2 * PRE_B) : (p == 1 || p == 2 ? t1 >> (4 * NJ) : t1));
    const CUtensorMap* tm = p == 4 ? &P.mwo[wt] : &P.mw[wt ? 1 : L];
    const uint4* img = &g_wf[p != 3][j][0][0];
    int col = (p >= 3 ? 0 : (p == 2 ? 2048 : 1024)) + 128 * j;
    const int flip = p == 0 ? 3072 : 0;
    const bool fold = wt && p != 4;
    if (sg == 5 || sg == 8) { mbar_wait(sb + (sg == 5 ? BAR_WPHI : BAR_CS + 8), sg == 5); fence_async_global(); }
    if (DEFER && p == 4 && ((DEFL >> wt) & 1)) {
      Ring q = r;
      for (int u = 0; u < DEFER; u++) adv<NB>(q);
      mbar_wait(sb + BAR_EMPTYB + q.s * 8, q.ph);
    }
#pragma unroll 1
    for (; n > 0; n--) {
      const int kb = (int)tab & 15;
      mbar_wait(sb + BAR_EMPTYB + r.s * 8, r.ph);
      if (elect()) {
        mbar_expect_tx(sb + BAR_FULLB + r.s * 8, SLOT);
        if (fold && col < 2048) bulk_load(sb + OFF_B + r.s * SLOT, img + kb * 1024, SLOT, sb + BAR_FULLB + r.s * 8);
        else tma_load_w(sb + OFF_B + r.s * SLOT, tm, sb + BAR_FULLB + r.s * 8, col, kb);
      }
      adv<NB>(r);
      if (p == 2 && (n | 4) == 5) r.s = 4;
      col ^= flip;
      if (!(col & flip & 2048)) tab >>= 4;
    }
  }
}

__device__ __forceinline__ void a_loader(const Params& P, uint32_t sb, unsigned vb) {
  const int j = cta_j(vb), m = cta_m(vb);
  const u64 t1 = order_table(1, j), t2 = order_table(2, j);
  Ring r = {PRE_A % NA, PRE_A < NA};
  {
    u64 tab = order_table(0, j) >> (4 * PRE_A);
#pragma unroll 1
    for (int i = PRE_A; i < 33; i++) {
      if (i == 17) tab = t2;
      mbar_wait(sb + BAR_EMPTYA + r.s * 8, r.ph);
      if (elect()) {
        mbar_expect_tx(sb + BAR_FULLA + r.s * 8, SLOT);
        if (i != 14) tma_load_3d(sb + OFF_A + r.s * SLOT, &P.mx, sb + BAR_FULLA + r.s * 8, ((int)tab & 15) * 64, m * 64, 0);
        else {
          tma_load_w(sb + OFF_A + r.s * SLOT, &P.mw[1], sb + BAR_FULLA + r.s * 8, 1024 + 128 * j, m);
          mbar_expect_tx(sb + BAR_WPHI, 8192); tma_load_2d(sb + OFF_S + 4096, &P.mwphi, sb + BAR_WPHI, 0, 128 * j);
        }
        if (i == PF1 || i == PF2) tma_prefetch_w(&P.mwo[i == PF2], 128 * j, m);
      }
      adv<NA>(r);
      if (i != 14) tab >>= 4;
    }
  }
  const unsigned tag = get_tag(sb);
  unsigned kph = 0;
#pragma unroll 1
  for (int sg = 0; sg < 13; sg++) {
    const int L = sg >> 2, p = sg & 3;
    if (p == 0 && (L & 1)) {
#pragma unroll 1
      for (int h = 0; h < 2; h++) {
        poll_flags(&g_kvfflag[L >> 1][j][h][0], 16, 0xFFFFu, tag);
        TS(4, h ? 14 + L : 26 + L);
        for (int it = 0;; it++) {
          if (elect()) { mbar_expect_tx(sb + BAR_STAT + 8, 10240); bulk_load(sb + OFF_S + h * 10240, &g_kvfin[j][8 * h][0], 10240, sb + BAR_STAT + 8); }
          mbar_wait(sb + BAR_STAT + 8, kph);
          kph ^= 1;
          uint32_t a = 1u, o = 0u;
#pragma unroll
          for (int u = 0; u < 20; u++) { const uint32_t v = __float_as_uint(lds32f(sb + OFF_S + h * 10240 + u * 512 + (threadIdx.x & 31) * 16)); a &= v; o |= v; }
          if (__all_sync(0xffffffffu, (L == 1 ? a : ~o) & 1u)) break;
          fence_async_smem();
          if (it > (1 << 16)) __trap();
        }
        if (elect()) mbar_arrive(sb + BAR_KV + h * 8);
        TS(4, h ? 30 + L : (L == 1 ? 20 : 25));
      }
    }
    int n = p < 2 ? 14 : (p == 2 ? ((L & 1) ? 0 : 16 - NJ) : 16);
    u64 tab = p == 3 ? t2 : t1 >> (p < 2 ? 8 : 4 * NJ);
    const uint4* img = &g_img[p ? XBUF(L + 1) : 0][m][0][0];
#pragma unroll 1
    for (; n > 0; n--) {
      const uint4* src = early(img + ((int)tab & 15) * 1024);
      const uint32_t bar = sb + (p < 2 ? BAR_LAND : BAR_FULLA) + r.s * 8;
      mbar_wait(sb + BAR_EMPTYA + r.s * 8, r.ph);
      if (elect()) mbar_expect_tx(bar, SLOT);
      if (p < 2 && n == 14) {
        const int lane = threadIdx.x & 31;
        const unsigned* f = &g_hint[2 * L + p][(m & 14) + ((lane >> 3) & 1)][(~j & 4) + (lane & ND0)];
        mbar_wait(sb + BAR_SIGP + p * 8, L & 1);
        int it = 0;
        while (!__all_sync(0xffffffffu, ld_flag(f) == tag)) { if (++it > (1 << 22)) __trap(); }
        TS(2, p == 0 ? 5 + L * 8 : 9 + L * 8);
      }
      if (elect()) bulk_load(sb + OFF_A + r.s * SLOT, src, SLOT, bar);
      adv<NA>(r);
      tab >>= 4;
      pause(p < 2 && n > 10 ? G0 : 0);
    }
  }
}

template <int KB>
__device__ __forceinline__ uint2 sum_packets(float (&a)[8], uint32_t addr, int n) {
  uint2 ok = make_uint2(~0u, 0u);
#pragma unroll 1
  for (int b = 0; b < n; b += KB) {
    uint4 v[KB];
#pragma unroll
    for (int u = 0; u < KB; u++) lds128(addr + (b + u) * 512, v[u].x, v[u].y, v[u].z, v[u].w);
#pragma unroll
    for (int u = 0; u < KB; u++) {
      ok.x &= v[u].x; ok.y |= v[u].x;
      a[0] += lo16(v[u].x); a[1] += hi16(v[u].x); a[2] += lo16(v[u].y); a[3] += hi16(v[u].y);
      a[4] += lo16(v[u].z); a[5] += hi16(v[u].z); a[6] += lo16(v[u].w); a[7] += hi16(v[u].w);
    }
  }
  return ok;
}
__device__ __forceinline__ void helper_bar() { asm volatile("bar.sync 4, 64;" ::: "memory"); }
__device__ __forceinline__ void helper(const Params& P, uint32_t sb, int w, unsigned vb) {
  const int j = cta_j(vb), m = cta_m(vb);
  if (w == 0) {
    if (elect()) {
      const unsigned t = atomicAdd(&g_ctr, 1u) / NCTA + 1u;
      asm volatile("st.shared.u32 [%0], %1;" ::"r"(sb + OFF_EPOCH), "r"(t) : "memory");
      mbar_arrive(sb + BAR_EPOCH);
    }
  }
  const unsigned tag = get_tag(sb);
  mbar_wait(sb + BAR_FULLB + 24, 0);
  const uint32_t stg = sb + OFF_T + w * 12288, stb = sb + BAR_STG + w * 24;
  Ring rs = {0, 0};
  uint32_t vs = 33 % NA, vph = 0;
  auto cs_image = [&](int L) {
      const int lane = lane_id();
      poll_flags(&g_csflag[L][j][0], 16, L ? CSNEED : 0xFFFu, tag);
#pragma unroll
      for (int p = 0; p < 3; p++) {
        const uint4 u = ldcg4(&g_cs[L][0][p * 1024 + 128 * j + lane * 4]), v = ldcg4(&g_cs[L][1][p * 1024 + 128 * j + lane * 4]);
        const float c0 = __uint_as_float(u.x) + __uint_as_float(v.x), c1 = __uint_as_float(u.y) + __uint_as_float(v.y);
        const float c2 = __uint_as_float(u.z) + __uint_as_float(v.z), c3 = __uint_as_float(u.w) + __uint_as_float(v.w);
        const uint32_t h0 = pack2(c0, c1), h1 = pack2(c2, c3), dst = sb + OFF_CS + (p * 16 + (lane >> 1)) * 96 + L * 48 + (lane & 1) * 8;
        sts64(dst, h0, h1); sts64(dst + 16, pack2(c0 - lo16(h0), c1 - hi16(h0)), pack2(c2 - lo16(h1), c3 - hi16(h1))); sts64(dst + 32, h0, h1);
        if (L == 0) { sts64(dst + 48, 0u, 0u); sts64(dst + 64, 0u, 0u); sts64(dst + 80, 0u, 0u); }
      }
      if (L == 0 && lane < 4) sts64(sb + OFF_CS + 4608 + lane * 8, 0u, 0u);
      fence_async_smem();
      __syncwarp();
      if (elect()) mbar_arrive(sb + BAR_CS + L * 8);
      TS(4, 2 + L * 2);
  };
#pragma unroll 1
  for (int L = 0; L < 4; L++) {
    const int lane = lane_id();
    if (L == 0) {
      {
        const int wt = m >= 12, col = ((0x2021 >> (m & 12)) & 3) * 1024 + 128 * j + (m & 3) * 32;
        const CUtensorMap* tm = &P.mcs[wt];
        __nanosleep(wt ? D2 : CD);
        constexpr int nb = 8;
        float a[8] = {0.f, 0.f, 0.f, 0.f, 0.f, 0.f, 0.f, 0.f};
#pragma unroll 1
        for (int b = -3; b < nb; b++) {
          if (b >= 0) {
            mbar_wait(stb + rs.s * 8, rs.ph);
            sum_packets<KC>(a, stg + rs.s * 4096 + lane * 16, 8);
            fence_async_smem();
            __syncwarp();
          }
          const uint32_t sl = b < 0 ? (rs.s + b + 3) % 3 : rs.s;
          if (b + 3 < nb && elect()) { mbar_expect_tx(stb + sl * 8, 4096); tma_load_2d(stg + sl * 4096, tm, stb + sl * 8, col, (w * (16 - nb) + b + 3) * 64); }
          if (b >= 0) adv<3>(rs); else pause(CP);
        }
#pragma unroll 1
        for (int d = 4; d < 32; d *= 2)
#pragma unroll
          for (int u = 0; u < 8; u++) a[u] += __shfl_xor_sync(0xffffffffu, a[u], d);
        if (lane < 4) {
          float4* dst = reinterpret_cast<float4*>(&g_cs[wt][w][col + lane * 8]);
          dst[0] = make_float4(a[0], a[1], a[2], a[3]); dst[1] = make_float4(a[4], a[5], a[6], a[7]);
        }
        helper_bar();
        if (w == 0 && elect()) { fence_gpu(); st_flag(&g_csflag[wt][j][m], tag); }
      }
      if (w == 0) TS(4, 1 + L * 2);
    }
    if (L > 0 && w == 0) {
      mbar_wait(sb + BAR_SIGP + 16, (L - 1) & 1);
      fence_async_global();
      __nanosleep(CO && L == 1 ? SE : SD);
    }
    if (CO && L < 2 && w == 0) cs_image(L);
    if (w == (L == 0)) {
      if (L == 0) { mbar_wait(sb + BAR_WPHI, 0); __nanosleep(S0); }
#pragma unroll 1
      for (int p = 0; p < 2; p++) {
        uint4 v[8];
        for (int it = 0;; it++) {
          bool ok = true;
#pragma unroll
          for (int t = 0; t < 8; t++) v[t] = ld_pkt(&g_stats[m][p][t][lane]);
#pragma unroll
          for (int t = 0; t < 8; t++) ok = ok && (v[t].w & 15u) == seq4(tag, L);
          if (__all_sync(0xffffffffu, ok)) break;
          __nanosleep(200);
          if (it > (1 << 20)) __trap();
        }
        float s0 = 0.f, q0 = 0.f, s1 = 0.f, q1 = 0.f;
#pragma unroll
        for (int t = 0; t < 8; t++) { s0 += __uint_as_float(v[t].x); q0 += __uint_as_float(v[t].y); s1 += __uint_as_float(v[t].z); q1 += __uint_as_float(v[t].w & ~15u); }
        s0 *= (1.f / 1024); s1 *= (1.f / 1024);
        sts64(sb + OFF_MR + p * 256 + lane * 8, __float_as_uint(rsqrtf(fmaxf(q0 * (1.f / 1024) - s0 * s0, 0.f) + 1e-5f)),
              __float_as_uint(rsqrtf(fmaxf(q1 * (1.f / 1024) - s1 * s1, 0.f) + 1e-5f)));
#pragma unroll
        for (int r = 0; r < 2; r++) {
          const float v = -0.5f * (r ? s1 : s0);
          const uint32_t hh = pack2(v, v), hl = pack2(v, v - lo16(hh));
          const bool b = L & 1;
          sts128(sb + (b ? OFF_MB : OFF_MA) + p * 1024 + (lane >> 3) * 256 + r * 128 + (lane & 7) * 16, b ? 0u : hh, b ? hh << 16 : hl >> 16, b ? hl : 0u, 0u);
        }
      }
      fence_async_smem();
      __syncwarp();
      if (elect()) {
        mbar_arrive(sb + BAR_STAT);
      }
      TS(2, 0 + L * 8);
    }
    if (!CO && L < 2 && w == 0) cs_image(L);
    if (L & 1) {
      const uint32_t flip = L == 1 ? 0u : 1u;
      mbar_wait(sb + BAR_SIGT, 1);
      {
        int it = 0;
        if (PSL) __nanosleep(m < 8 ? PSL : PSL + 600);
        while (!__all_sync(0xffffffffu, (ld_flag(reinterpret_cast<const unsigned*>(&g_kvpart[j][m][w][512]) + (lane & 15) * 8) ^ flip) & 1u)) { if (PSL) __nanosleep(100); if (++it > (1 << 22)) __trap(); }
        fence_async_global();
      }
      if (w == 0) TS(4, 6 + L * 2);
      float a[8], z;
      for (int it = 0;; it++) {
        if (elect()) { mbar_expect_tx(stb + rs.s * 8, 8704); bulk_load(stg, &g_kvpart[j][m][w][0], 8704, stb + rs.s * 8); }
        mbar_wait(stb + rs.s * 8, rs.ph);
        if (w == 0) TS(4, 21 + L);
        adv<3>(rs);
#pragma unroll
        for (int u = 0; u < 8; u++) a[u] = 0.f;
        z = 0.f;
        uint32_t ok = 1u;
#pragma unroll
        for (int u = 0; u < 4; u++) { const float v = lds32f(stg + 8192 + u * 128 + (lane & 3) * 32 + (lane >> 2) * 4); z += v; ok &= __float_as_uint(v) ^ flip; }
        const uint2 tg = sum_packets<8>(a, stg + lane * 16, 16);
        ok &= flip ? ~tg.y : tg.x;
        if (__all_sync(0xffffffffu, ok & 1u)) break;
        fence_async_smem();
        if (it > (1 << 16)) __trap();
      }
      {
        uint4* img = &g_kvfin[j][m][w * 8 + (lane >> 2)];
        uint32_t a0 = __float_as_uint(a[0]) >> 16;
        a0 += ~(a0 ^ flip) & 1u;
        st_v4(img + (lane & 3) * 16, __byte_perm(a0, pack2(0.f, a[1]), 0x7610), pack2(a[2], a[3]), pack2(a[4], a[5]), pack2(a[6], a[7]));
        const uint32_t cz = pack2(0.f, qsum(z)) | (0x3781u ^ flip);
        if (!(lane & 3)) st_v4(img + 64, cz, cz, cz, cz);
        __syncwarp();
        if (elect()) st_flag(&g_kvfflag[L >> 1][j][m >> 3][(m & 7) * 2 + w], tag);
      }
      if (w == 0) TS(4, 7 + L * 2);
    } else {
      mbar_wait(sb + BAR_SIGT, 0);
      if (w == 0) {
        if (elect()) { fence_gpu(); st_flag(&g_hflag[L >> 1][m][j][0], tag); st_flag(&g_kflag[j][m], tag); }
        if (L == 0) {
          __nanosleep(KSL);
          poll_flags(&g_kflag[j][0], 16, 0xFFFFu, tag);
          if (elect()) mbar_arrive(sb + BAR_WPHI);
        }
      } else if (m > 0) {
        poll_flags(&g_hflag[L >> 1][m - 1][j][0], 1, 1u, tag);
        if (elect()) { mbar_expect_tx(sb + BAR_HALO, 8192); bulk_load(sb + OFF_S + 8192, &g_halo[m - 1][j][0][0], 8192, sb + BAR_HALO); }
        TS(2, 2 + L * 8);
      }
    }
    if (w == 0) {
#pragma unroll 1
      for (int e = 0; e < (L < 3 ? 2 : 1); e++) {
        unsigned* flag = early(&g_hint[2 * L + e][m][j]);
        mbar_wait(sb + BAR_SIGP + e * 8, L & 1);
        TS(2, (e ? 6 : 3) + L * 8);
        pause(XD);
        if (elect()) st_flag(flag, tag);
      }
    } else {
#pragma unroll 1
      for (int i = 0; i < (L < 3 ? 28 : 14); i++) {
        const bool isx = i >= 14;
        const uint32_t a = sb + OFF_A + vs * SLOT + lane * 128 + ((lane >> 4) * 4 + (lane & 3)) * 16 + (lane & 12), code = img_code(isx, L + isx);
        for (int it = 0;; it++) {
          mbar_wait(sb + BAR_LAND + vs * 8, (vph >> vs) & 1);
          vph ^= 1u << vs;
          uint32_t bad = 0;
#pragma unroll
          for (int u = 0; u < 4; u++) bad |= __float_as_uint(lds32f(a + u * 4096)) ^ code;
          if (__all_sync(0xffffffffu, !(bad & img_mask(isx)))) break;
          if (it > (1 << 16)) __trap();
          fence_async_smem();
          if (elect()) {
            mbar_expect_tx(sb + BAR_LAND + vs * 8, SLOT);
            bulk_load(sb + OFF_A + vs * SLOT, &g_img[isx ? XBUF(L + 1) : 0][m][o_order(i - 14 * isx + 2, j)][0], SLOT, sb + BAR_LAND + vs * 8);
          }
        }
        if (elect()) mbar_arrive(sb + BAR_FULLA + vs * 8);
        if (++vs == NA) vs = 0;
      }
      vs = (vs + ((L & 1) ? 16 : 32 - NJ)) % NA;
    }
  }
}

__device__ __forceinline__ void spare(const Params& P, uint32_t sb, int id) {
  const int tid = threadIdx.x & 127, warp = __shfl_sync(0xffffffffu, threadIdx.x >> 5, 0), w = warp >> 2, lane = tid & 31, j = 2 * id + w;
  const uint32_t ring = w * 6 * SLOT, wp = 12 * SLOT + w * 8192, bar = sb + 13 * SLOT + w * 64;
  auto part = [&](int t) { return (t >> 4) ^ w; };
  auto load = [&](int t, uint32_t sl) {
    mbar_expect_tx(bar + sl * 8, t == 0 ? SLOT + 8192 : SLOT);
    tma_load_w(sb + ring + sl * SLOT, &P.mw[1], bar + sl * 8, part(t) * 1024 + 128 * j, t & 15);
  };
  if (!(warp & 3) && elect()) {
    if (w == 2) sts32(sb + OFF_EPOCH, atomicAdd(&g_ctr, 1u) / NCTA + 1u);
    else {
      __nanosleep(D3);
#pragma unroll 1
      for (int t = 0; t < 5; t++) {
        mbar_init(bar + t * 8, 1);
        asm volatile("fence.mbarrier_init.release.cluster;" ::: "memory");
        load(t, t);
      }
      tma_load_2d(sb + wp, &P.mwphi, bar, 0, 128 * j);
    }
  }
  __syncthreads();
  const unsigned tag = get_tag<false>(sb);
  if (w == 2) {
    int it = 0;
    while ((int)(ld_flag(&g_ctr) - tag * NCTA) < 0) { if (++it > (1 << 22)) __trap(); }
    return;
  }
  Ring r = {4, 1};
  float d[64] = {}, cs[32] = {};
  auto fold = [&]() {
    mbar_wait(bar + r.s * 8, r.ph);
    wgmma_fence();
#pragma unroll
    for (int q = 0; q < 8; q++)
      wgmma_ss_n32(reinterpret_cast<float (&)[16]>(d[16 * (q >> 1)]), desc_lo(SB + ring + r.s * SLOT, 16) + (q >> 2) * 512 + (q & 3) * 2, desc_lo(SB + wp, 512) + q * 64, q & 1);
    wgmma_commit();
  };
  const int row = (tid >> 5) * 16 + (lane >> 2);
#pragma unroll 1
  for (int t = -1; t < 32; t++) {
    uint32_t f[32];
#pragma unroll
    for (int i = 0; i < 32; i++) { f[i] = pack2(d[2 * i], d[2 * i + 1]); cs[i & 30] += d[2 * i]; cs[i | 1] += d[2 * i + 1]; }
    wg_bar(w);
    const uint32_t sl = r.s;
    if (t < 31) adv<5>(r);
    fold();
    if (!(warp & 3) && t >= 0 && t < 27 && elect()) load(t + 5, sl);
    if (part(t) == 0 && t >= 0) {
#pragma unroll
      for (int q = 0; q < 8; q++)
        g_wf[0][j][t & 15][(q >> 2) * 512 + (row + 8 * (q & 1)) * 8 + (((q & 2) * 2 + (lane & 3)) ^ (lane >> 2))] =
            make_uint4(f[4 * (q & 6) + (q & 1)], f[4 * (q & 6) + (q & 1) + 2], f[4 * (q & 6) + (q & 1) + 4], f[4 * (q & 6) + (q & 1) + 6]);
    }
    wgmma_wait<0>();
    fence_regs(d);
    if ((t & 15) == 15) {
      if (t >= 0) {
        const uint32_t red = sb + ring + 5 * SLOT;
#pragma unroll
        for (int i = 0; i < 8; i++) sts128(red + (tid >> 2) * 512 + (i >> 1) * 128 + (lane & 3) * 32 + (i & 1) * 16, __float_as_uint(cs[4 * i]), __float_as_uint(cs[4 * i + 1]), __float_as_uint(cs[4 * i + 2]), __float_as_uint(cs[4 * i + 3]));
        wg_bar(w);
        float a = 0.f;
#pragma unroll 4
        for (int i = 0; i < 32; i++) a += lds32f(red + i * 512 + tid * 4);
        g_cs[1][0][part(t) * 1024 + j * 128 + tid] = a;
        wg_bar(w);
        if (tid == 0) {
          fence_gpu();
          st_flag(&g_csflag[1][j][part(t)], tag);
        }
        __syncwarp();
      }
#pragma unroll
      for (int i = 0; i < 32; i++) cs[i] = 0.f;
    }
  }
}

__global__ void __launch_bounds__(NTHREADS, 1) fused_kernel(const __grid_constant__ Params P) {
  extern __shared__ __align__(1024) uint8_t smem_raw[];
  constexpr uint32_t sb = SB;
  const int tid = threadIdx.x;
  const unsigned vb = vblock();
  if (vb >= 128) { spare(P, sb, vb - 128); return; }
  const int warp = __shfl_sync(0xffffffffu, tid >> 5, 0);
  if (elect()) {
    if (warp == 11) { prefetch_map(&P.mx); prefetch_map(&P.mw[0]); if (smem_u32(smem_raw) != SB) __trap(); }
    if (warp < 8) {
#pragma unroll
      for (int i = 0; i < 8; i++) mbar_init(sb + OFF_BAR + (warp * 8 + i) * 8, warp == 2 || warp == 3 ? 2 : (warp == 4 ? 8 : 1));
    }
    asm volatile("fence.mbarrier_init.release.cluster;" ::: "memory");
    if (warp < 2) {
      const int j = cta_j(vb);
#pragma unroll 1
      for (int i = 0; i < (warp == 0 ? PRE_B : PRE_A); i++) {
        const uint32_t bar = sb + BAR_FULLB + warp * 64 + i * 8;
        mbar_expect_tx(bar, SLOT);
        if (warp == 0) tma_load_w(sb + OFF_B + i * SLOT, &P.mw[0], bar, 1024 + (i & 1) * 1024 + 128 * j, kv_order(i >> 1, j, 0));
        else tma_load_3d(sb + OFF_A + i * SLOT, &P.mx, bar, kv_order(i, j, 0) * 64, cta_m(vb) * 64, 0);
      }
    }
  }
  if (tid == 0) TS(6, 0);
  __syncthreads();
  if (tid == 0) TS(6, 2);
  if (warp < 4) {
    reg_dealloc<PREGS>();
    if (warp & 2) helper(P, sb, warp & 1, vb);
    else if (warp & 1) a_loader(P, sb, vb);
    else b_producer(P, sb, vb);
  } else {
    reg_alloc<CREGS>();
    consumer(P, sb, (warp >> 2) - 1, vb);
  }
}

typedef CUresult (*EncodeFn)(CUtensorMap*, CUtensorMapDataType, cuuint32_t, void*, const cuuint64_t*, const cuuint64_t*,
                             const cuuint32_t*, const cuuint32_t*, CUtensorMapInterleave, CUtensorMapSwizzle,
                             CUtensorMapL2promotion, CUtensorMapFloatOOBfill);

void encode(EncodeFn fn, CUtensorMap* m, const void* ptr, int rank, const cuuint64_t* dims, const cuuint64_t* strides,
            const cuuint32_t* box, CUtensorMapSwizzle swz) {
  const cuuint32_t es[5] = {1, 1, 1, 1, 1};
  fn(m, CU_TENSOR_MAP_DATA_TYPE_BFLOAT16, rank, const_cast<void*>(ptr), dims, strides, box, es, CU_TENSOR_MAP_INTERLEAVE_NONE,
     swz, CU_TENSOR_MAP_L2_PROMOTION_L2_256B, CU_TENSOR_MAP_FLOAT_OOB_FILL_NONE);
}
void encode_w(EncodeFn fn, CUtensorMap* m, const void* ptr, int ncols, bool perm) {
  const cuuint64_t p = (cuuint64_t)ncols * 2, d[5] = {(cuuint64_t)ncols, 2, 4, 4, 32}, s[4] = {p, (perm ? 8 : 2) * p, (perm ? 2 : 8) * p, 32 * p};
  const cuuint32_t box[5] = {64, 2, 4, 4, 2};
  encode(fn, m, ptr, 5, d, s, box, CU_TENSOR_MAP_SWIZZLE_128B);
}

void encode_cs(EncodeFn fn, CUtensorMap* m, const void* ptr, int ncols) {
  const cuuint64_t d[2] = {(cuuint64_t)ncols, 1024}, s[1] = {(cuuint64_t)ncols * 2};
  const cuuint32_t box[2] = {32, 64};
  encode(fn, m, ptr, 2, d, s, box, CU_TENSOR_MAP_SWIZZLE_NONE);
}

}

extern "C" void kernel_launch(void* const* d_in, const int* in_sizes, int n_in, void* d_out, int out_size) {
  (void)in_sizes; (void)n_in; (void)out_size;
  void* fnp = nullptr;
  cudaDriverEntryPointQueryResult q;
  cudaGetDriverEntryPoint("cuTensorMapEncodeTiled", &fnp, cudaEnableDefault, &q);
  EncodeFn fn = (EncodeFn)fnp;
  Params P;
  {
    const cuuint64_t dims[3] = {1024, 1024, 2}, strides[2] = {4096, 2048};
    const cuuint32_t box[3] = {64, 64, 2};
    encode(fn, &P.mx, d_in[0], 3, dims, strides, box, CU_TENSOR_MAP_SWIZZLE_128B);
  }
  P.out = (uint4*)d_out;
  encode_w(fn, &P.mw[0], d_in[1], 3072, false);
  encode_w(fn, &P.mw[1], d_in[4], 3072, true);
  encode_w(fn, &P.mw[2], d_in[1], 3072, true);
  encode_w(fn, &P.mwo[0], d_in[2], 1024, true);
  encode_w(fn, &P.mwo[1], d_in[6], 1024, false);
  encode_cs(fn, &P.mcs[0], d_in[1], 3072);
  encode_cs(fn, &P.mcs[1], d_in[4], 3072);
  {
    const cuuint64_t dims[2] = {32, 1024}, strides[1] = {64};
    const cuuint32_t box[2] = {32, 128};
    encode(fn, &P.mwphi, d_in[5], 2, dims, strides, box, CU_TENSOR_MAP_SWIZZLE_64B);
  }
  cudaFuncSetAttribute(fused_kernel, cudaFuncAttributeMaxDynamicSharedMemorySize, SMEM_BYTES);
  fused_kernel<<<NCTA, NTHREADS, SMEM_BYTES, cudaStreamPerThread>>>(P);
}
```

```cpp
#include <cuda_runtime.h>
#include <cuda_bf16.h>
#include <cuda.h>
#include <stdint.h>

namespace {

__device__ __forceinline__ void wgmma_ss_n256(float (&d)[128], uint32_t da, uint32_t ha, uint32_t db, int sd) {
  asm volatile("{\n.reg .pred p;\n.reg .b64 a, b;\nsetp.ne.b32 p, %130, 0;\nmov.b64 a, {%128, %131};\nmov.b64 b, {%129, 0x40000040};\n"
    "wgmma.mma_async.sync.aligned.m64n256k16.f32.bf16.bf16 {%0,%1,%2,%3,%4,%5,%6,%7,%8,%9,%10,%11,%12,%13,%14,%15,%16,%17,%18,%19,%20,%21,%22,%23,%24,%25,%26,%27,%28,%29,%30,%31,%32,%33,%34,%35,%36,%37,%38,%39,%40,%41,%42,%43,%44,%45,%46,%47,%48,%49,%50,%51,%52,%53,%54,%55,%56,%57,%58,%59,%60,%61,%62,%63,%64,%65,%66,%67,%68,%69,%70,%71,%72,%73,%74,%75,%76,%77,%78,%79,%80,%81,%82,%83,%84,%85,%86,%87,%88,%89,%90,%91,%92,%93,%94,%95,%96,%97,%98,%99,%100,%101,%102,%103,%104,%105,%106,%107,%108,%109,%110,%111,%112,%113,%114,%115,%116,%117,%118,%119,%120,%121,%122,%123,%124,%125,%126,%127}, a, b, p, 1, 1, 0, 1;\n}\n"
    : "+f"(d[0]),"+f"(d[1]),"+f"(d[2]),"+f"(d[3]),"+f"(d[4]),"+f"(d[5]),"+f"(d[6]),"+f"(d[7]),"+f"(d[8]),"+f"(d[9]),"+f"(d[10]),"+f"(d[11]),"+f"(d[12]),"+f"(d[13]),"+f"(d[14]),"+f"(d[15]),"+f"(d[16]),"+f"(d[17]),"+f"(d[18]),"+f"(d[19]),"+f"(d[20]),"+f"(d[21]),"+f"(d[22]),"+f"(d[23]),"+f"(d[24]),"+f"(d[25]),"+f"(d[26]),"+f"(d[27]),"+f"(d[28]),"+f"(d[29]),"+f"(d[30]),"+f"(d[31]),"+f"(d[32]),"+f"(d[33]),"+f"(d[34]),"+f"(d[35]),"+f"(d[36]),"+f"(d[37]),"+f"(d[38]),"+f"(d[39]),"+f"(d[40]),"+f"(d[41]),"+f"(d[42]),"+f"(d[43]),"+f"(d[44]),"+f"(d[45]),"+f"(d[46]),"+f"(d[47]),"+f"(d[48]),"+f"(d[49]),"+f"(d[50]),"+f"(d[51]),"+f"(d[52]),"+f"(d[53]),"+f"(d[54]),"+f"(d[55]),"+f"(d[56]),"+f"(d[57]),"+f"(d[58]),"+f"(d[59]),"+f"(d[60]),"+f"(d[61]),"+f"(d[62]),"+f"(d[63]),"+f"(d[64]),"+f"(d[65]),"+f"(d[66]),"+f"(d[67]),"+f"(d[68]),"+f"(d[69]),"+f"(d[70]),"+f"(d[71]),"+f"(d[72]),"+f"(d[73]),"+f"(d[74]),"+f"(d[75]),"+f"(d[76]),"+f"(d[77]),"+f"(d[78]),"+f"(d[79]),"+f"(d[80]),"+f"(d[81]),"+f"(d[82]),"+f"(d[83]),"+f"(d[84]),"+f"(d[85]),"+f"(d[86]),"+f"(d[87]),"+f"(d[88]),"+f"(d[89]),"+f"(d[90]),"+f"(d[91]),"+f"(d[92]),"+f"(d[93]),"+f"(d[94]),"+f"(d[95]),"+f"(d[96]),"+f"(d[97]),"+f"(d[98]),"+f"(d[99]),"+f"(d[100]),"+f"(d[101]),"+f"(d[102]),"+f"(d[103]),"+f"(d[104]),"+f"(d[105]),"+f"(d[106]),"+f"(d[107]),"+f"(d[108]),"+f"(d[109]),"+f"(d[110]),"+f"(d[111]),"+f"(d[112]),"+f"(d[113]),"+f"(d[114]),"+f"(d[115]),"+f"(d[116]),"+f"(d[117]),"+f"(d[118]),"+f"(d[119]),"+f"(d[120]),"+f"(d[121]),"+f"(d[122]),"+f"(d[123]),"+f"(d[124]),"+f"(d[125]),"+f"(d[126]),"+f"(d[127])
    : "r"(da), "r"(db), "r"(sd), "r"(ha));
}
__device__ __forceinline__ void wgmma_ss_n128(float (&d)[64], uint32_t da, uint32_t ha, uint32_t db, int sd) {
  asm volatile("{\n.reg .pred p;\n.reg .b64 a, b;\nsetp.ne.b32 p, %66, 0;\nmov.b64 a, {%64, %67};\nmov.b64 b, {%65, 0x40000040};\n"
    "wgmma.mma_async.sync.aligned.m64n128k16.f32.bf16.bf16 {%0,%1,%2,%3,%4,%5,%6,%7,%8,%9,%10,%11,%12,%13,%14,%15,%16,%17,%18,%19,%20,%21,%22,%23,%24,%25,%26,%27,%28,%29,%30,%31,%32,%33,%34,%35,%36,%37,%38,%39,%40,%41,%42,%43,%44,%45,%46,%47,%48,%49,%50,%51,%52,%53,%54,%55,%56,%57,%58,%59,%60,%61,%62,%63}, a, b, p, 1, 1, 0, 1;\n}\n"
    : "+f"(d[0]),"+f"(d[1]),"+f"(d[2]),"+f"(d[3]),"+f"(d[4]),"+f"(d[5]),"+f"(d[6]),"+f"(d[7]),"+f"(d[8]),"+f"(d[9]),"+f"(d[10]),"+f"(d[11]),"+f"(d[12]),"+f"(d[13]),"+f"(d[14]),"+f"(d[15]),"+f"(d[16]),"+f"(d[17]),"+f"(d[18]),"+f"(d[19]),"+f"(d[20]),"+f"(d[21]),"+f"(d[22]),"+f"(d[23]),"+f"(d[24]),"+f"(d[25]),"+f"(d[26]),"+f"(d[27]),"+f"(d[28]),"+f"(d[29]),"+f"(d[30]),"+f"(d[31]),"+f"(d[32]),"+f"(d[33]),"+f"(d[34]),"+f"(d[35]),"+f"(d[36]),"+f"(d[37]),"+f"(d[38]),"+f"(d[39]),"+f"(d[40]),"+f"(d[41]),"+f"(d[42]),"+f"(d[43]),"+f"(d[44]),"+f"(d[45]),"+f"(d[46]),"+f"(d[47]),"+f"(d[48]),"+f"(d[49]),"+f"(d[50]),"+f"(d[51]),"+f"(d[52]),"+f"(d[53]),"+f"(d[54]),"+f"(d[55]),"+f"(d[56]),"+f"(d[57]),"+f"(d[58]),"+f"(d[59]),"+f"(d[60]),"+f"(d[61]),"+f"(d[62]),"+f"(d[63])
    : "r"(da), "r"(db), "r"(sd), "r"(ha));
}
__device__ __forceinline__ void wgmma_ss_n40_tt(float (&d)[20], uint32_t da, uint32_t db, int sd) {
  asm volatile("{\n.reg .pred p;\n.reg .b64 a, b;\nsetp.ne.b32 p, %22, 0;\nmov.b64 a, {%20, 0x40000040};\nmov.b64 b, {%21, 0x8};\n"
    "wgmma.mma_async.sync.aligned.m64n40k16.f32.bf16.bf16 {%0,%1,%2,%3,%4,%5,%6,%7,%8,%9,%10,%11,%12,%13,%14,%15,%16,%17,%18,%19}, a, b, p, 1, 1, 1, 1;\n}\n"
    : "+f"(d[0]),"+f"(d[1]),"+f"(d[2]),"+f"(d[3]),"+f"(d[4]),"+f"(d[5]),"+f"(d[6]),"+f"(d[7]),"+f"(d[8]),"+f"(d[9]),"+f"(d[10]),"+f"(d[11]),"+f"(d[12]),"+f"(d[13]),"+f"(d[14]),"+f"(d[15]),"+f"(d[16]),"+f"(d[17]),"+f"(d[18]),"+f"(d[19])
    : "r"(da), "r"(db), "r"(sd));
}
__device__ __forceinline__ void wgmma_ss_n32(float (&d)[16], uint32_t da, uint32_t db, int sd) {
  asm volatile("{\n.reg .pred p;\n.reg .b64 a, b;\nsetp.ne.b32 p, %18, 0;\nmov.b64 a, {%16, 0x40000040};\nmov.b64 b, {%17, 0x80000020};\n"
    "wgmma.mma_async.sync.aligned.m64n32k16.f32.bf16.bf16 {%0,%1,%2,%3,%4,%5,%6,%7,%8,%9,%10,%11,%12,%13,%14,%15}, a, b, p, 1, 1, 0, 1;\n}\n"
    : "+f"(d[0]),"+f"(d[1]),"+f"(d[2]),"+f"(d[3]),"+f"(d[4]),"+f"(d[5]),"+f"(d[6]),"+f"(d[7]),"+f"(d[8]),"+f"(d[9]),"+f"(d[10]),"+f"(d[11]),"+f"(d[12]),"+f"(d[13]),"+f"(d[14]),"+f"(d[15])
    : "r"(da), "r"(db), "r"(sd));
}
__device__ __forceinline__ void wgmma_rs_n40(float (&d)[20], uint32_t a0, uint32_t a1, uint32_t a2, uint32_t a3, uint32_t db, int sd) {
  asm volatile("{\n.reg .pred p;\n.reg .b64 b;\nsetp.ne.b32 p, %25, 0;\nmov.b64 b, {%24, 0x10};\n"
    "wgmma.mma_async.sync.aligned.m64n40k16.f32.bf16.bf16 {%0,%1,%2,%3,%4,%5,%6,%7,%8,%9,%10,%11,%12,%13,%14,%15,%16,%17,%18,%19}, {%20,%21,%22,%23}, b, p, 1, 1, 1;\n}\n"
    : "+f"(d[0]),"+f"(d[1]),"+f"(d[2]),"+f"(d[3]),"+f"(d[4]),"+f"(d[5]),"+f"(d[6]),"+f"(d[7]),"+f"(d[8]),"+f"(d[9]),"+f"(d[10]),"+f"(d[11]),"+f"(d[12]),"+f"(d[13]),"+f"(d[14]),"+f"(d[15]),"+f"(d[16]),"+f"(d[17]),"+f"(d[18]),"+f"(d[19])
    : "r"(a0), "r"(a1), "r"(a2), "r"(a3), "r"(db), "r"(sd));
}
__device__ __forceinline__ void wgmma_r1_n256(float (&d)[128], uint32_t da, uint32_t db, int sd) {
  asm volatile("{\n.reg .pred p;\n.reg .b64 a, b;\nsetp.ne.b32 p, %130, 0;\nmov.b64 a, {%128, 0x8};\nmov.b64 b, {%129, 0x6};\n"
    "wgmma.mma_async.sync.aligned.m64n256k16.f32.bf16.bf16 {%0,%1,%2,%3,%4,%5,%6,%7,%8,%9,%10,%11,%12,%13,%14,%15,%16,%17,%18,%19,%20,%21,%22,%23,%24,%25,%26,%27,%28,%29,%30,%31,%32,%33,%34,%35,%36,%37,%38,%39,%40,%41,%42,%43,%44,%45,%46,%47,%48,%49,%50,%51,%52,%53,%54,%55,%56,%57,%58,%59,%60,%61,%62,%63,%64,%65,%66,%67,%68,%69,%70,%71,%72,%73,%74,%75,%76,%77,%78,%79,%80,%81,%82,%83,%84,%85,%86,%87,%88,%89,%90,%91,%92,%93,%94,%95,%96,%97,%98,%99,%100,%101,%102,%103,%104,%105,%106,%107,%108,%109,%110,%111,%112,%113,%114,%115,%116,%117,%118,%119,%120,%121,%122,%123,%124,%125,%126,%127}, a, b, p, 1, 1, 0, 1;\n}\n"
    : "+f"(d[0]),"+f"(d[1]),"+f"(d[2]),"+f"(d[3]),"+f"(d[4]),"+f"(d[5]),"+f"(d[6]),"+f"(d[7]),"+f"(d[8]),"+f"(d[9]),"+f"(d[10]),"+f"(d[11]),"+f"(d[12]),"+f"(d[13]),"+f"(d[14]),"+f"(d[15]),"+f"(d[16]),"+f"(d[17]),"+f"(d[18]),"+f"(d[19]),"+f"(d[20]),"+f"(d[21]),"+f"(d[22]),"+f"(d[23]),"+f"(d[24]),"+f"(d[25]),"+f"(d[26]),"+f"(d[27]),"+f"(d[28]),"+f"(d[29]),"+f"(d[30]),"+f"(d[31]),"+f"(d[32]),"+f"(d[33]),"+f"(d[34]),"+f"(d[35]),"+f"(d[36]),"+f"(d[37]),"+f"(d[38]),"+f"(d[39]),"+f"(d[40]),"+f"(d[41]),"+f"(d[42]),"+f"(d[43]),"+f"(d[44]),"+f"(d[45]),"+f"(d[46]),"+f"(d[47]),"+f"(d[48]),"+f"(d[49]),"+f"(d[50]),"+f"(d[51]),"+f"(d[52]),"+f"(d[53]),"+f"(d[54]),"+f"(d[55]),"+f"(d[56]),"+f"(d[57]),"+f"(d[58]),"+f"(d[59]),"+f"(d[60]),"+f"(d[61]),"+f"(d[62]),"+f"(d[63]),"+f"(d[64]),"+f"(d[65]),"+f"(d[66]),"+f"(d[67]),"+f"(d[68]),"+f"(d[69]),"+f"(d[70]),"+f"(d[71]),"+f"(d[72]),"+f"(d[73]),"+f"(d[74]),"+f"(d[75]),"+f"(d[76]),"+f"(d[77]),"+f"(d[78]),"+f"(d[79]),"+f"(d[80]),"+f"(d[81]),"+f"(d[82]),"+f"(d[83]),"+f"(d[84]),"+f"(d[85]),"+f"(d[86]),"+f"(d[87]),"+f"(d[88]),"+f"(d[89]),"+f"(d[90]),"+f"(d[91]),"+f"(d[92]),"+f"(d[93]),"+f"(d[94]),"+f"(d[95]),"+f"(d[96]),"+f"(d[97]),"+f"(d[98]),"+f"(d[99]),"+f"(d[100]),"+f"(d[101]),"+f"(d[102]),"+f"(d[103]),"+f"(d[104]),"+f"(d[105]),"+f"(d[106]),"+f"(d[107]),"+f"(d[108]),"+f"(d[109]),"+f"(d[110]),"+f"(d[111]),"+f"(d[112]),"+f"(d[113]),"+f"(d[114]),"+f"(d[115]),"+f"(d[116]),"+f"(d[117]),"+f"(d[118]),"+f"(d[119]),"+f"(d[120]),"+f"(d[121]),"+f"(d[122]),"+f"(d[123]),"+f"(d[124]),"+f"(d[125]),"+f"(d[126]),"+f"(d[127])
    : "r"(da), "r"(db), "r"(sd));
}
__device__ __forceinline__ void wgmma_r1_n128(float (&d)[64], uint32_t da, uint32_t db, int sd) {
  asm volatile("{\n.reg .pred p;\n.reg .b64 a, b;\nsetp.ne.b32 p, %66, 0;\nmov.b64 a, {%64, 0x8};\nmov.b64 b, {%65, 0x6};\n"
    "wgmma.mma_async.sync.aligned.m64n128k16.f32.bf16.bf16 {%0,%1,%2,%3,%4,%5,%6,%7,%8,%9,%10,%11,%12,%13,%14,%15,%16,%17,%18,%19,%20,%21,%22,%23,%24,%25,%26,%27,%28,%29,%30,%31,%32,%33,%34,%35,%36,%37,%38,%39,%40,%41,%42,%43,%44,%45,%46,%47,%48,%49,%50,%51,%52,%53,%54,%55,%56,%57,%58,%59,%60,%61,%62,%63}, a, b, p, 1, 1, 0, 1;\n}\n"
    : "+f"(d[0]),"+f"(d[1]),"+f"(d[2]),"+f"(d[3]),"+f"(d[4]),"+f"(d[5]),"+f"(d[6]),"+f"(d[7]),"+f"(d[8]),"+f"(d[9]),"+f"(d[10]),"+f"(d[11]),"+f"(d[12]),"+f"(d[13]),"+f"(d[14]),"+f"(d[15]),"+f"(d[16]),"+f"(d[17]),"+f"(d[18]),"+f"(d[19]),"+f"(d[20]),"+f"(d[21]),"+f"(d[22]),"+f"(d[23]),"+f"(d[24]),"+f"(d[25]),"+f"(d[26]),"+f"(d[27]),"+f"(d[28]),"+f"(d[29]),"+f"(d[30]),"+f"(d[31]),"+f"(d[32]),"+f"(d[33]),"+f"(d[34]),"+f"(d[35]),"+f"(d[36]),"+f"(d[37]),"+f"(d[38]),"+f"(d[39]),"+f"(d[40]),"+f"(d[41]),"+f"(d[42]),"+f"(d[43]),"+f"(d[44]),"+f"(d[45]),"+f"(d[46]),"+f"(d[47]),"+f"(d[48]),"+f"(d[49]),"+f"(d[50]),"+f"(d[51]),"+f"(d[52]),"+f"(d[53]),"+f"(d[54]),"+f"(d[55]),"+f"(d[56]),"+f"(d[57]),"+f"(d[58]),"+f"(d[59]),"+f"(d[60]),"+f"(d[61]),"+f"(d[62]),"+f"(d[63])
    : "r"(da), "r"(db), "r"(sd));
}

__device__ __forceinline__ uint32_t smem_u32(const void* p) { return (uint32_t)__cvta_generic_to_shared(p); }
__device__ __forceinline__ void mbar_init(uint32_t bar, uint32_t cnt) { asm volatile("mbarrier.init.shared::cta.b64 [%0], %1;" ::"r"(bar), "r"(cnt)); }
__device__ __forceinline__ void mbar_expect_tx(uint32_t bar, uint32_t bytes) { asm volatile("mbarrier.arrive.expect_tx.shared::cta.b64 _, [%0], %1;" ::"r"(bar), "r"(bytes) : "memory"); }
__device__ __forceinline__ void mbar_arrive(uint32_t bar) { asm volatile("mbarrier.arrive.shared::cta.b64 _, [%0];" ::"r"(bar) : "memory"); }
__device__ __forceinline__ void mbar_arrive_n(uint32_t bar, uint32_t n) { asm volatile("mbarrier.arrive.shared::cta.b64 _, [%0], %1;" ::"r"(bar), "r"(n) : "memory"); }
__device__ __forceinline__ void mbar_wait(uint32_t bar, uint32_t parity) {
  asm volatile("{\n.reg .pred p;\nLAB_WAIT:\nmbarrier.try_wait.parity.shared::cta.b64 p, [%0], %1;\n@p bra DONE;\nbra LAB_WAIT;\nDONE:\n}" ::"r"(bar), "r"(parity) : "memory");
}
__device__ __forceinline__ void mbar_wait2(uint32_t a, uint32_t pa, uint32_t b, uint32_t pb) {
  asm volatile("{\n.reg .pred p, q;\nLAB_WAIT:\nmbarrier.try_wait.parity.shared::cta.b64 p, [%0], %1;\nmbarrier.try_wait.parity.shared::cta.b64 q, [%2], %3;\n"
               "and.pred p, p, q;\n@p bra DONE;\nbra LAB_WAIT;\nDONE:\n}" ::"r"(a), "r"(pa), "r"(b), "r"(pb) : "memory");
}
__device__ __forceinline__ void mbar_wait3(uint32_t a, uint32_t pa, uint32_t b, uint32_t pb) {
  asm volatile("{\n.reg .pred p, q, r;\nLAB_WAIT:\nmbarrier.try_wait.parity.shared::cta.b64 p, [%0], %1;\nmbarrier.try_wait.parity.shared::cta.b64 q, [%2], %3;\n"
               "mbarrier.try_wait.parity.shared::cta.b64 r, [%2+8], %3;\nand.pred p, p, q;\nand.pred p, p, r;\n@p bra DONE;\nbra LAB_WAIT;\nDONE:\n}" ::"r"(a), "r"(pa), "r"(b), "r"(pb) : "memory");
}
__device__ __forceinline__ bool mbar_probe2(uint32_t a, uint32_t pa, uint32_t b, uint32_t pb) {
  uint32_t ok;
  asm volatile("{\n.reg .pred p, q;\nmbarrier.test_wait.parity.shared::cta.b64 p, [%1], %2;\nmbarrier.test_wait.parity.shared::cta.b64 q, [%3], %4;\n"
               "and.pred p, p, q;\nselp.u32 %0, 1, 0, p;\n}" : "=r"(ok) : "r"(a), "r"(pa), "r"(b), "r"(pb) : "memory");
  return ok != 0;
}
__device__ __forceinline__ void tma_load_3d(uint32_t dst, const CUtensorMap* tm, uint32_t bar, int c0, int c1, int c2) {
  asm volatile("cp.async.bulk.tensor.3d.shared::cluster.global.mbarrier::complete_tx::bytes [%0], [%1, {%3, %4, %5}], [%2];"
               ::"r"(dst), "l"(tm), "r"(bar), "r"(c0), "r"(c1), "r"(c2) : "memory");
}
__device__ __forceinline__ void tma_load_2d(uint32_t dst, const CUtensorMap* tm, uint32_t bar, int c0, int c1) {
  asm volatile("cp.async.bulk.tensor.2d.shared::cluster.global.mbarrier::complete_tx::bytes [%0], [%1, {%3, %4}], [%2];"
               ::"r"(dst), "l"(tm), "r"(bar), "r"(c0), "r"(c1) : "memory");
}
__device__ __forceinline__ void tma_load_w(uint32_t dst, const CUtensorMap* tm, uint32_t bar, int col, int kb) {
#pragma unroll
  for (int q = 0; q < 2; q++)
    asm volatile("cp.async.bulk.tensor.5d.shared::cluster.global.mbarrier::complete_tx::bytes [%0], [%1, {%3, %4, %4, %4, %5}], [%2];"
                 ::"r"(dst + q * 8192), "l"(tm), "r"(bar), "r"(col + q * 64), "r"(0), "r"(2 * kb) : "memory");
}
__device__ __forceinline__ void tma_prefetch_w(const CUtensorMap* tm, int col, int kb) {
#pragma unroll
  for (int q = 0; q < 2; q++)
    asm volatile("cp.async.bulk.prefetch.tensor.5d.L2.global [%0, {%1, %2, %2, %2, %3}];" ::"l"(tm), "r"(col + q * 64), "r"(0), "r"(2 * kb) : "memory");
}
__device__ __forceinline__ void bulk_load(uint32_t dst, const void* g, uint32_t bytes, uint32_t bar) {
  asm volatile("cp.async.bulk.shared::cluster.global.mbarrier::complete_tx::bytes [%0], [%1], %2, [%3];" ::"r"(dst), "l"(g), "r"(bytes), "r"(bar) : "memory");
}
__device__ __forceinline__ void prefetch_map(const CUtensorMap* tm) { asm volatile("prefetch.tensormap [%0];" ::"l"(tm) : "memory"); }
__device__ __forceinline__ void fence_async_smem() { asm volatile("fence.proxy.async.shared::cta;" ::: "memory"); }
__device__ __forceinline__ void fence_async_global() { asm volatile("fence.proxy.async.global;" ::: "memory"); }
__device__ __forceinline__ void fence_gpu() { asm volatile("fence.release.gpu;" ::: "memory"); }
__device__ __forceinline__ void st_flag(unsigned* p, unsigned v) { asm volatile("st.relaxed.gpu.global.u32 [%0], %1;" ::"l"(p), "r"(v) : "memory"); }
__device__ __forceinline__ unsigned ld_flag(const unsigned* p) { unsigned v; asm volatile("ld.relaxed.gpu.global.u32 %0, [%1];" : "=r"(v) : "l"(p) : "memory"); return v; }
__device__ __forceinline__ uint4 ldcg4(const void* p) { uint4 v; asm volatile("ld.global.cg.v4.u32 {%0,%1,%2,%3}, [%4];" : "=r"(v.x), "=r"(v.y), "=r"(v.z), "=r"(v.w) : "l"(p)); return v; }
__device__ __forceinline__ uint4 ld_pkt(const uint4* p) {
  uint4 v; asm volatile("{\n.reg .b128 t;\nld.relaxed.gpu.global.b128 t, [%4];\nmov.b128 {%0,%1,%2,%3}, t;\n}" : "=r"(v.x), "=r"(v.y), "=r"(v.z), "=r"(v.w) : "l"(p) : "memory"); return v;
}
__device__ __forceinline__ void st_pkt(uint4* p, uint32_t a, uint32_t b, uint32_t c, uint32_t tag) {
  asm volatile("{\n.reg .b128 t;\nmov.b128 t, {%1,%2,%3,%4};\nst.relaxed.gpu.global.b128 [%0], t;\n}" ::"l"(p), "r"(a), "r"(b), "r"(c), "r"(tag) : "memory");
}
__device__ __forceinline__ void st_v4(uint4* p, uint32_t a, uint32_t b, uint32_t c, uint32_t d) { asm volatile("st.relaxed.gpu.global.v4.u32 [%0], {%1,%2,%3,%4};" ::"l"(p), "r"(a), "r"(b), "r"(c), "r"(d) : "memory"); }
__device__ __forceinline__ void stg128(uint4* p, uint4 v) { asm volatile("st.global.v4.u32 [%0], {%1,%2,%3,%4};" ::"l"(p), "r"(v.x), "r"(v.y), "r"(v.z), "r"(v.w) : "memory"); }
__device__ __forceinline__ void sts32(uint32_t addr, uint32_t a) { asm volatile("st.shared.u32 [%0], %1;" ::"r"(addr), "r"(a) : "memory"); }
__device__ __forceinline__ void sts64(uint32_t addr, uint32_t a, uint32_t b) { asm volatile("st.shared.v2.u32 [%0], {%1,%2};" ::"r"(addr), "r"(a), "r"(b) : "memory"); }
__device__ __forceinline__ uint32_t mul2(uint32_t a, uint32_t b) { uint32_t r; asm("mul.rn.bf16x2 %0, %1, %2;" : "=r"(r) : "r"(a), "r"(b)); return r; }
__device__ __forceinline__ uint32_t add2(uint32_t a, uint32_t b) { uint32_t r; asm("add.rn.bf16x2 %0, %1, %2;" : "=r"(r) : "r"(a), "r"(b)); return r; }
__device__ __forceinline__ bool elect() {
  uint32_t p; asm volatile("{\n.reg .pred q;\nelect.sync _|q, 0xffffffff;\nselp.u32 %0, 1, 0, q;\n}" : "=r"(p)); return p != 0;
}
__device__ __forceinline__ void wgmma_fence() { asm volatile("wgmma.fence.sync.aligned;" ::: "memory"); }
__device__ __forceinline__ void wgmma_commit() { asm volatile("wgmma.commit_group.sync.aligned;" ::: "memory"); }
template <int N> __device__ __forceinline__ void wgmma_wait() { asm volatile("wgmma.wait_group.sync.aligned %0;" ::"n"(N) : "memory"); }
template <int N> __device__ __forceinline__ void fence_regs(float (&d)[N]) {
#pragma unroll
  for (int i = 0; i < N; i++) asm volatile("" : "+f"(d[i])::"memory");
}
template <int R> __device__ __forceinline__ void reg_alloc() { asm volatile("setmaxnreg.inc.sync.aligned.u32 %0;" ::"n"(R)); }
template <int R> __device__ __forceinline__ void reg_dealloc() { asm volatile("setmaxnreg.dec.sync.aligned.u32 %0;" ::"n"(R)); }
__device__ __forceinline__ void wg_bar(int w) { asm volatile("bar.sync %0, 128;" ::"r"(w + 1) : "memory"); }
__device__ __forceinline__ constexpr uint32_t desc_lo(uint32_t addr, uint32_t lbo) { return (addr >> 4) + ((lbo >> 4) << 16); }
__device__ __forceinline__ uint32_t pack2(float lo, float hi) { uint32_t r; asm("cvt.rn.bf16x2.f32 %0, %1, %2;" : "=r"(r) : "f"(hi), "f"(lo)); return r; }
__device__ __forceinline__ float lo16(uint32_t v) { return __uint_as_float(v << 16); }
__device__ __forceinline__ float hi16(uint32_t v) { return __uint_as_float(v & 0xFFFF0000u); }
__device__ __forceinline__ float ex2(float x) { float r; asm("ex2.approx.ftz.f32 %0, %1;" : "=f"(r) : "f"(x)); return r; }
__device__ __forceinline__ float rcp(float x) { float r; asm("rcp.approx.ftz.f32 %0, %1;" : "=f"(r) : "f"(x)); return r; }
__device__ __forceinline__ uint32_t movm(uint32_t a) { uint32_t d; asm volatile("movmatrix.sync.aligned.m8n8.trans.b16 %0, %1;" : "=r"(d) : "r"(a)); return d; }
__device__ __forceinline__ void stsm4(uint32_t addr, uint32_t a, uint32_t b, uint32_t c, uint32_t d) {
  asm volatile("stmatrix.sync.aligned.m8n8.x4.shared.b16 [%0], {%1,%2,%3,%4};" ::"r"(addr), "r"(a), "r"(b), "r"(c), "r"(d) : "memory");
}
__device__ __forceinline__ void ldsm4(uint32_t addr, uint32_t (&r)[4]) {
  asm volatile("ldmatrix.sync.aligned.m8n8.x4.shared.b16 {%0,%1,%2,%3}, [%4];" : "=r"(r[0]), "=r"(r[1]), "=r"(r[2]), "=r"(r[3]) : "r"(addr) : "memory");
}
__device__ __forceinline__ void sts128(uint32_t addr, uint32_t a, uint32_t b, uint32_t c, uint32_t d) {
  asm volatile("st.shared.v4.u32 [%0], {%1,%2,%3,%4};" ::"r"(addr), "r"(a), "r"(b), "r"(c), "r"(d) : "memory");
}
__device__ __forceinline__ void lds128(uint32_t addr, uint32_t& a, uint32_t& b, uint32_t& c, uint32_t& d) {
  asm volatile("ld.shared.v4.u32 {%0,%1,%2,%3}, [%4];" : "=r"(a), "=r"(b), "=r"(c), "=r"(d) : "r"(addr) : "memory");
}
__device__ __forceinline__ float lds32f(uint32_t addr) { float v; asm volatile("ld.shared.f32 %0, [%1];" : "=f"(v) : "r"(addr) : "memory"); return v; }
__device__ __forceinline__ float2 lds64f(uint32_t addr) { float2 v; asm volatile("ld.shared.v2.f32 {%0,%1}, [%2];" : "=f"(v.x), "=f"(v.y) : "r"(addr) : "memory"); return v; }
__device__ __forceinline__ void mma16816(float (&d)[4], uint32_t a0, uint32_t a1, uint32_t a2, uint32_t a3, uint32_t b0, uint32_t b1) {
  asm("mma.sync.aligned.m16n8k16.row.col.f32.bf16.bf16.f32 {%0,%1,%2,%3}, {%4,%5,%6,%7}, {%8,%9}, {%0,%1,%2,%3};"
      : "+f"(d[0]), "+f"(d[1]), "+f"(d[2]), "+f"(d[3]) : "r"(a0), "r"(a1), "r"(a2), "r"(a3), "r"(b0), "r"(b1));
}
__device__ __forceinline__ void mma1688(float (&d)[4], uint32_t a0, uint32_t a1, uint32_t b0) {
  asm("mma.sync.aligned.m16n8k8.row.col.f32.bf16.bf16.f32 {%0,%1,%2,%3}, {%4,%5}, {%6}, {%0,%1,%2,%3};"
      : "+f"(d[0]), "+f"(d[1]), "+f"(d[2]), "+f"(d[3]) : "r"(a0), "r"(a1), "r"(b0));
}

__device__ __forceinline__ float qsum(float v) { v += __shfl_xor_sync(0xffffffffu, v, 1); v += __shfl_xor_sync(0xffffffffu, v, 2); return v; }

constexpr int NCTA = 132;
#define NB_ 6
#define NA_ 5
constexpr int NB = NB_;
constexpr int NA = NA_;
constexpr uint32_t SLOT = 16384;
constexpr uint32_t SB = 1024;
constexpr uint32_t OFF_B = 0;
constexpr uint32_t OFF_A = NB * SLOT;
constexpr uint32_t OFF_S = OFF_A + NA * SLOT;
constexpr uint32_t OFF_T = OFF_S + 20480;
constexpr uint32_t OFF_CS = OFF_T + 24576;
constexpr uint32_t OFF_MR = OFF_CS + 4640;
constexpr uint32_t OFF_BAR = OFF_MR + 512;
constexpr uint32_t OFF_MA = OFF_S, OFF_MB = OFF_CS - 2048;
constexpr uint32_t BAR_FULLB = OFF_BAR;
constexpr uint32_t BAR_FULLA = BAR_FULLB + 64;
constexpr uint32_t BAR_EMPTYB = BAR_FULLA + 64;
constexpr uint32_t BAR_EMPTYA = BAR_EMPTYB + 64;
constexpr uint32_t BAR_SIGP = BAR_EMPTYA + 64;
constexpr uint32_t BAR_SIGT = BAR_SIGP + 24;
constexpr uint32_t BAR_STAT = BAR_SIGP + 64;
constexpr uint32_t BAR_HALO = BAR_STAT + 16;
constexpr uint32_t BAR_CS = BAR_HALO + 8;
constexpr uint32_t BAR_WPHI = BAR_CS + 16;
constexpr uint32_t BAR_KV = BAR_WPHI + 8;
constexpr uint32_t BAR_STG = BAR_KV + 16;
constexpr uint32_t BAR_EPOCH = BAR_STG + 48;
constexpr uint32_t BAR_LAND = OFF_BAR + 7 * 64;
constexpr uint32_t OFF_EPOCH = OFF_BAR + 8 * 64;
static_assert(BAR_EPOCH < BAR_LAND, "barriers");
constexpr uint32_t SMEM_BYTES = OFF_EPOCH + 8;
static_assert(SMEM_BYTES <= 232448 && NB % 2 == 0 && NB <= 8 && NA <= 6, "smem");

#define CREGS 224
#define PREGS 56
#define PF1 19
#define PF2 21
#define PRE_A 2
#define PRE_B 4
#define CSB 4
#define CSNEED 0xF003u
#define XR 1
#define PS0 1
#define PS1 3
#define PSW 0
#define SD 1000
#define KSPLIT 12
#define KEEP 16
#define NJ 3
#define KSL 1000
#define PSL 0
#define KVS 12
#define D2 2000
#define D3 1500
#define G0 50
#define MAP 3
#define PMAP 0x76321450u
#define PW 1
#define XA 3
#define XS 1
#define CP 500
#define CD 0
#define S0 500
#define NS 2
#define XO 0
#define SW 2
#define SA 1
#define SB_ 4
#define XD 500
#define ND0 1
#define KC 8
#define CO 0
#define SE 500
#define PD 0
#define DEFER 3
#define DEFL 2
#define TSK 3
#define TSL 3
constexpr int NTHREADS = 384;

struct Params {
  CUtensorMap mx;
  CUtensorMap mw[3];
  CUtensorMap mwo[2];
  CUtensorMap mcs[2];
  CUtensorMap mwphi;
  uint4* out;
};

#define XBUF(L) 1
__device__ __align__(256) uint4 g_img[XBUF(3) + 1][16][16][1024];
__device__ __forceinline__ uint32_t img_code(bool isx, int L) { return isx ? (L & 1) | (L & 2) << 15 : ~L & 1; }
__device__ __forceinline__ uint32_t img_mask(bool isx) { return isx ? 0x10001u : 1u; }
__device__ __align__(256) uint4 g_wf[2][8][16][1024];
__device__ __align__(256) uint4 g_stats[16][2][8][32];
__device__ __align__(256) uint4 g_halo[16][8][2][256];
__device__ __align__(256) float g_cs[2][2][3072];
__device__ __align__(256) uint4 g_kvpart[8][16][2][544];
__device__ __align__(256) uint4 g_kvfin[8][16][80];
__device__ __align__(256) unsigned g_hint[16][32];
__device__ __align__(256) unsigned g_hflag[2][16][8][32];
__device__ __align__(256) unsigned g_kvfflag[2][8][2][32];
__device__ __align__(256) unsigned g_csflag[2][8][32];
__device__ __align__(256) unsigned g_kflag[8][32];
__device__ unsigned g_ctr;
__device__ __forceinline__ unsigned vblock() {
  unsigned s;
  asm volatile("mov.u32 %0, %%smid;" : "=r"(s));
  const unsigned r = s & 1;
  s >>= 1;
  const unsigned t = s - 32, q = (t * 37) >> 8;
  const unsigned hi = s < 60 ? 12 + (t - 7 * q) * 8 + q : (s < 62 ? s + 4 : s - 58);
  unsigned b = 2 * (s < 32 ? (s & 7) * 8 + (s >> 3) : hi) + r;
  if (b < 128) b = (b & 15) | ((PMAP >> ((b >> 4) * 4)) & 7) << 4;
  if (s >= 62) b = 8 + 4 * r + s - 62;
  unsigned n;
  asm volatile("mov.u32 %0, %%nsmid;" : "=r"(n));
  return __shfl_sync(0xffffffffu, n == NCTA ? b : blockIdx.x, 0);
}
#define TS(who, id) do {} while (0)
#define TSW(id) do {} while (0)

#define TSH(id) do {} while (0)
#define TSMASK 0xFFFF
#define TSL_(a) do { if ((TSMASK >> (a)) & 1) TSW((a) + L * 12); } while (0)
__device__ __forceinline__ int cta_m(unsigned b) { return ((b >> 2) & 12) | (b & 3); }
__device__ __forceinline__ int cta_j(unsigned b) { return ((b >> 2) & 3) | ((b >> 4) & 4); }
struct Ring { uint32_t s, ph; };
template <int N> __device__ __forceinline__ void adv(Ring& r) { if (++r.s == N) { r.s = 0; r.ph ^= 1; } }
template <int N> __device__ __forceinline__ void rewind2(Ring& r) { if (r.s < 2) { r.s += N - 2; r.ph ^= 1; } else r.s -= 2; }
__device__ __forceinline__ int other_tile(int t, int j) { return (t == (j | 4) ? 7 : t) ^ (~j & 4); }
__device__ __forceinline__ int q_order(int i, int j) { return 2 * (i >= 14 ? j : other_tile(i >> 1, j)) + (i & 1); }
__device__ __forceinline__ int o_order(int i, int j) {
  if (i < 2) return 2 * j + i;
  const int odd = i >= 9;
  return 2 * other_tile(i - 2 - 7 * odd, j) + odd;
}
__device__ __forceinline__ int kv_order(int i, int j, int L) { return L > 0 ? o_order(i, j) : (i + 14 + 2 * (j & 4)) & 15; }

__device__ __forceinline__ unsigned poll_flags(const unsigned* f, int n, unsigned need, unsigned tag) {
  const int lane = threadIdx.x & 31;
  unsigned mask; int it = 0;
  do {
    unsigned v = lane < n ? ld_flag(f + lane) : 0u;
    mask = __ballot_sync(0xffffffffu, lane < n && v == tag);
    if (++it > (1 << 22)) __trap();
  } while ((mask & need) != need);
  fence_async_global();
  return mask;
}
template <bool WAIT = true>
__device__ __forceinline__ unsigned get_tag(uint32_t sb) {
  if (WAIT) mbar_wait(sb + BAR_EPOCH, 0);
  unsigned t; asm volatile("ld.shared.u32 %0, [%1];" : "=r"(t) : "r"(sb + OFF_EPOCH) : "memory");
  return t;
}

__device__ __forceinline__ int lane_id() { int l; asm volatile("mov.u32 %0, %%laneid;" : "=r"(l)); return l; }
__device__ __forceinline__ unsigned seq4(unsigned tag, int L) { return 8u | ((tag & 1u) << 2) | (unsigned)L; }
constexpr float LOG2E = 1.4426950408889634f;

__device__ __forceinline__ float bb_fence(int never, const void* p = &g_ctr, uint32_t keep = 0) {
  while (never < 0) never = ld_flag((const unsigned*)p) + keep;
  return __int_as_float(never >> 30);
}
__device__ __forceinline__ uint32_t solid(uint32_t v) { return __shfl_sync(0xffffffffu, v, threadIdx.x & 31); }
template <class T> __device__ __forceinline__ T* solid(T* p) { return (T*)__shfl_sync(0xffffffffu, (unsigned long long)p, threadIdx.x & 31); }
constexpr uint32_t HA128 = 0x40000040u, HA64 = 0x80000040u;
struct Ctx {
  static constexpr uint32_t sb = SB;
  uint32_t ab, da0;
  int w, warp, lane, g, c;
  int goff;
  __device__ __forceinline__ int m() const { return goff >> 14; }
  __device__ __forceinline__ int j() const { return (goff >> 4) & 7; }
  bool elected;
  Ring ra, rb;
  uint32_t pa, pb;
  uint32_t ha, k2;
  uint32_t mrow, mxor, mhi;
  __device__ __forceinline__ uint32_t aslot(uint32_t s) const { return ab + s * SLOT; }
  __device__ __forceinline__ uint32_t fullA(uint32_t s) const { return sb + BAR_FULLA + s * 8; }
  __device__ __forceinline__ uint32_t fullB(uint32_t s) const { return sb + BAR_FULLB + s * 8; }
  __device__ __forceinline__ void releaseA(uint32_t s) const { if (elected) mbar_arrive(sb + BAR_EMPTYA + s * 8); }
  __device__ __forceinline__ void releaseB(uint32_t s) const { if (elected) mbar_arrive(sb + BAR_EMPTYB + s * 8); }
  __device__ __forceinline__ uint32_t maddr(uint32_t tile, uint32_t ch) const { return tile + mrow + (((ch + mhi) ^ mxor) << 4); }
  __device__ __forceinline__ uint32_t oo() const { return warp * 128 + g * 4 + (c ^ (g >> 1)); }
  __device__ __forceinline__ uint4* img(int b, int hp) const { return ip + (b * 256 + hp) * 1024; }
  uint4* ip;
  uint32_t so;
  __device__ __forceinline__ uint32_t held(int i) const { return ra.s + i < 2 ? ra.s + i + NA - 2 : ra.s + i - 2; }
};

template <int N, bool FIRST, bool O = true>
__device__ __forceinline__ void gemm_issue(float (&acc)[N / 2], Ctx& x, bool ready = false) {
  if (!ready) {
    if (N == 256) mbar_wait3(x.fullA(x.ra.s), x.ra.ph, x.fullB(x.rb.s), x.rb.ph);
    else mbar_wait2(x.fullA(x.ra.s), x.ra.ph, x.fullB(x.rb.s), x.rb.ph);
  }
  const uint32_t da = x.da0 + x.ra.s * (SLOT / 16), db = desc_lo(SB + OFF_B, 8192) + x.rb.s * (SLOT / 16);
  wgmma_fence();
#pragma unroll
  for (int k = 0; k < 4; k++) {
    const uint32_t a = da + (k >> 1) * (O ? 32 : x.k2) + (k & 1) * 2, ha = O ? HA64 : x.ha;
    if constexpr (N == 256) wgmma_ss_n256(acc, a, ha, db + 128 * k, !(FIRST && k == 0));
    else wgmma_ss_n128(acc, a, ha, db + 128 * k, !(FIRST && k == 0));
  }
  wgmma_commit();
}
template <int N>
__device__ __forceinline__ void gemm_next(Ctx& x) {
  x.pa = x.ra.s; x.pb = x.rb.s;
  if (N == 256) x.rb.s++;
  adv<NA>(x.ra); adv<NB>(x.rb);
}
template <int N>
__device__ __forceinline__ void gemm_release(Ctx& x, bool relA) {
  if (relA) x.releaseA(x.pa);
  x.releaseB(x.pb);
  if (N == 256) x.releaseB(x.pb + 1);
}
template <int N>
__device__ __forceinline__ void gemm_retire(Ctx& x, bool relA) { wgmma_wait<1>(); gemm_release<N>(x, relA); gemm_next<N>(x); }
template <bool O = true>
__device__ __forceinline__ void gemm_run(float (&acc)[64], Ctx& x, int n, int hold, int n4 = 0) {
  bool ready = false;
#pragma unroll 1
  for (; n > 0; n--) {
    gemm_issue<128, false, O>(acc, x, ready);
    const uint32_t pa = x.pa, pb = x.pb;
    gemm_next<128>(x);
    ready = mbar_probe2(x.fullA(x.ra.s), x.ra.ph, x.fullB(x.rb.s), x.rb.ph);
    wgmma_wait<1>();
    if (n > hold) x.releaseA(pa);
    x.releaseB(pb);
  }
}
__device__ __forceinline__ void gemm_end(float (&acc)[64], Ctx& x) { wgmma_wait<0>(); fence_regs(acc); gemm_release<128>(x, false); }

__device__ __forceinline__ void rows_load(uint4* r, uint32_t tile, const Ctx& x) {
#pragma unroll
  for (int q = 0; q < 4; q++) {
    const uint32_t row = x.warp * 16 + 4 * q + (x.lane >> 3);
    lds128(tile + row * 128 + (((x.lane & 7) ^ (row & 7)) << 4), r[q].x, r[q].y, r[q].z, r[q].w);
  }
}
__device__ __forceinline__ void rows_store(const uint4* r, uint4* g) {
#pragma unroll
  for (int q = 0; q < 4; q++) stg128(g + q * 1024, r[q]);
}
__device__ __forceinline__ void publish(int id, const Ctx& x) { __syncwarp(); if (x.lane == 0) mbar_arrive(x.sb + BAR_SIGP + id * 8); }
__device__ __forceinline__ uint32_t img_tag(uint32_t v, bool isx, int L, const Ctx& x) {
  const uint32_t mk = ((x.lane ^ (x.warp * 4)) & 7) ? 0u : img_mask(isx);
  return (v & ~mk) | (img_code(isx, L) & mk);
}
__device__ __forceinline__ void img_tag(uint4 (&r)[4], bool isx, int L, const Ctx& x) {
#pragma unroll
  for (int q = 0; q < 4; q++) { uint32_t& v = q == 0 ? r[q].x : (q == 1 ? r[q].y : (q == 2 ? r[q].z : r[q].w)); v = img_tag(v, isx, L, x); }
}
__device__ __forceinline__ void img_store(const uint4 (&r)[4], uint4* g) {
#pragma unroll
  for (int q = 0; q < 4; q++) stg128(g + q * 32, r[q]);
}
__device__ __forceinline__ void img_sts(const uint4 (&r)[4], uint32_t tile, const Ctx& x) {
#pragma unroll
  for (int q = 0; q < 4; q++) sts128(tile + x.so + q * 512, r[q].x, r[q].y, r[q].z, r[q].w);
}
__device__ __forceinline__ void img_load(uint32_t (&v)[16], uint32_t tile, const Ctx& x) {
#pragma unroll
  for (int q = 0; q < 4; q++) lds128(tile + x.so + q * 512, v[4 * q], v[4 * q + 1], v[4 * q + 2], v[4 * q + 3]);
}
__device__ __forceinline__ void img_unpack(float* a, const uint32_t (&v)[16]) {
#pragma unroll
  for (int q = 0; q < 16; q++) { a[4 * (q & 7) + 2 * (q >> 3)] = lo16(v[q]); a[4 * (q & 7) + 2 * (q >> 3) + 1] = hi16(v[q]); }
}

template <int N>
__device__ __forceinline__ void stats_acc(const float* a, float (&t)[4]) {
#pragma unroll
  for (int i = 0; i < N; i++) { t[i & 2] += a[i]; t[(i & 2) + 1] = fmaf(a[i], a[i], t[(i & 2) + 1]); }
}
__device__ __forceinline__ void stats_send(float (&t)[4], int L, const Ctx& x) {
  const unsigned seq = seq4(get_tag<false>(x.sb), L);
#pragma unroll
  for (int q = 0; q < 4; q++) t[q] = qsum(t[q]);
  if (x.c == 0) st_pkt(&g_stats[x.m()][x.w][x.j()][x.warp * 8 + x.g], __float_as_uint(t[0]), __float_as_uint(t[1]), __float_as_uint(t[2]), (__float_as_uint(t[3]) & ~15u) | seq);
}
__device__ __forceinline__ void out_epilogue(const float (&acc)[64], uint4 (&r1)[4], float (&t)[4], uint4* g, int L, Ctx& x) {
  const uint32_t t0 = x.aslot(x.ra.s), t1 = x.aslot(x.ra.s + 1 == NA ? 0 : x.ra.s + 1);
  if (L == 3) {
#pragma unroll
    for (int p = 0; p < 8; p++) {
      stsm4(x.maddr(p < 4 ? t0 : t1, (p & 3) * 2), pack2(acc[8 * p], acc[8 * p + 1]), pack2(acc[8 * p + 2], acc[8 * p + 3]),
            pack2(acc[8 * p + 4], acc[8 * p + 5]), pack2(acc[8 * p + 6], acc[8 * p + 7]));
      if ((p & 3) == 3) { uint4 r[4]; __syncwarp(); rows_load(r, p < 4 ? t0 : t1, x); rows_store(r, g + (p >> 2) * 8); }
    }
  } else {
    auto pack16 = [&](uint4 (&r)[4], const float* a) {
#pragma unroll
      for (int q = 0; q < 4; q++) { const float* u = a + 16 * (q & 1) + (q & 2); r[q] = make_uint4(pack2(u[0], u[1]), pack2(u[4], u[5]), pack2(u[8], u[9]), pack2(u[12], u[13])); }
    };
    uint4 r0[4];
    pack16(r0, acc);
    img_tag(r0, true, L + 1, x);
    img_store(r0, x.img(XBUF(L + 1), 0));
    publish(1, x);
    const float z = bb_fence(x.goff);
    img_sts(r0, t0, x);
    pack16(r1, acc + 32);
    img_tag(r1, true, L + 1, x);
    img_sts(r1, t1, x);
    float u[4] = {z, z, z, z}, v[4] = {z, z, z, z};
    stats_acc<32>(acc, v);
    stats_acc<32>(acc + 32, u);
#pragma unroll
    for (int q = 0; q < 4; q++) t[q] = u[q] + v[q];
    mbar_wait2(x.fullB(x.rb.s), x.rb.ph, x.fullB(x.rb.s + 1), x.rb.ph);
    fence_async_smem();
    asm volatile("bar.sync %0, %1;" ::"r"(L == 1 ? x.w + 1 : 3), "r"(L == 1 ? 128 : 256) : "memory");
  }
}

struct Stats { float rstd0, rstd1; };
__device__ __forceinline__ Stats load_stats(int half, const Ctx& x) {
  const float2 u = lds64f(x.sb + OFF_MR + half * 256 + (x.warp * 8 + x.g) * 8);
  return {u.x, u.y};
}

template <int NH, int NK, class F>
__device__ __forceinline__ void hedgehog_scale(float* t, const Stats& st, const uint32_t* keep, F use) {
#pragma unroll
  for (int q = 0; q < 16 * NH; q++) t[q] *= ((q & 2) ? st.rstd1 : st.rstd0) * LOG2E;
  use();
  float m[4];
#pragma unroll
  for (int q = 0; q < 4 * NH; q++) {
    const float v = fmaxf(fmaxf(fabsf(t[4 * q]), fabsf(t[4 * q + 1])), fmaxf(fabsf(t[4 * q + 2]), fabsf(t[4 * q + 3])));
    m[q & 3] = q < 4 ? v : fmaxf(m[q & 3], v);
  }
  if (__builtin_expect(__any_sync(0xffffffffu, fmaxf(fmaxf(m[0], m[1]), fmaxf(m[2], m[3])) > 58.f), 0)) {
    float z[16 * NH + NK];
#pragma unroll
    for (int q = 0; q < 16 * NH + NK; q++) z[q] = q < 16 * NH ? t[q % (16 * NH)] : __uint_as_float(keep[q & 15]);
#pragma unroll 1
    for (int r = 0; r < 2 * NH; r++) {
      float hi = -INFINITY, lo = INFINITY;
#pragma unroll 1
      for (int i = 0; i < 16; i++) {
        const int k = (i & 6) * 2 + (i & 1) + (r & 1) * 2 + (r & 2) * 8;
        const float v = z[k];
        if (i < 8) { hi = fmaxf(hi, v); lo = fminf(lo, v); }
        else z[k] = v - fminf(fmaxf(v, lo), hi);
        if (i == 7) {
#pragma unroll 1
          for (int d = 1; d <= 2; d++) { hi = fmaxf(hi, __shfl_xor_sync(0xffffffffu, hi, d)); lo = fminf(lo, __shfl_xor_sync(0xffffffffu, lo, d)); }
          const float mid = 0.5f * hi + 0.5f * lo;
          hi = fmaxf(hi - 58.f, mid); lo = fminf(lo + 58.f, mid);
        }
      }
    }
#pragma unroll
    for (int q = 0; q < 16 * NH; q++) t[q] = z[q];
    use();
  }
}
__device__ __forceinline__ void dual_exp(const float* t, uint32_t (&f)[18], int never) {
  float e[KSPLIT];
#pragma unroll
  for (int q = 0; q < KSPLIT; q++) e[q] = ex2(q < 16 ? t[q] : -t[q & 15]);
  while (never < 0) {
#pragma unroll
    for (int i = 0; i < KSPLIT; i += 4) asm volatile("ld.shared.v4.f32 {%0,%1,%2,%3}, [%4];" : "=f"(e[i]), "=f"(e[i + 1]), "=f"(e[i + 2]), "=f"(e[i + 3]) : "r"(never + i) : "memory");
    never += __float_as_int(e[0]);
  }
#pragma unroll
  for (int q = 0; q < KSPLIT; q += 2) f[q >> 1] = pack2(e[q], e[q + 1]);
#pragma unroll
  for (int q = KSPLIT; q < 32; q += 2) f[q >> 1] = q < 16 ? pack2(ex2(t[q]), ex2(t[q + 1])) : pack2(ex2(-t[q & 15]), ex2(-t[(q & 15) + 1]));
#pragma unroll
  for (int sg = 0; sg < 2; sg++) {
    const uint32_t* u = f + 8 * sg;
    const uint32_t a = add2(add2(u[0], u[2]), add2(u[4], u[6])), b = add2(add2(u[1], u[3]), add2(u[5], u[7]));
    f[16 + sg] = add2(__byte_perm(a, b, 0x5410), __byte_perm(a, b, 0x7632));
  }
}
__device__ __forceinline__ void dual_exp_rcp(const float* t, uint32_t (&f)[16]) {
#pragma unroll
  for (int q = 0; q < 8; q++) {
    const float a = ex2(t[2 * q]), b = ex2(t[2 * q + 1]), r = rcp(a * b);
    f[q] = pack2(a, b); f[8 + q] = pack2(r * b, r * a);
  }
}
__device__ __forceinline__ void cta_bar() { asm volatile("bar.sync 3, 256;" ::: "memory"); }

template <int N> __device__ __forceinline__ void pin(const uint32_t* v, uint32_t addr) {
#pragma unroll
  for (int i = 0; i < N; i += 4)
    asm volatile("{\n.reg .pred p;\nsetp.eq.u32 p, %0, 0;\n@p st.shared.v4.u32 [%0], {%1,%2,%3,%4};\n}" ::"r"(addr), "r"(v[i]), "r"(v[i + 1]), "r"(v[i + 2]), "r"(v[i + 3]) : "memory");
}

__device__ __forceinline__ void consumer(const Params& P, uint32_t sb, int w, unsigned vb) {
  Ctx x;
  x.w = w;
  x.ab = sb + OFF_A + w * 8192; x.da0 = desc_lo(SB + OFF_A, 16) + w * 512;
  x.lane = threadIdx.x & 31; x.warp = __shfl_sync(0xffffffffu, (threadIdx.x >> 5) & 3, 0); x.g = x.lane >> 2; x.c = x.lane & 3;
  x.goff = (cta_m(vb) * 128 + w) * 128 + cta_j(vb) * 16;
  asm volatile("" : "+r"(x.goff));
  x.elected = (threadIdx.x & 127) == 0;
  x.ra = {0, 0}; x.rb = {0, 0}; x.pa = x.pb = 0;
  {
    const uint32_t row = x.warp * 16 + (x.lane & 15);
    x.mrow = row * 128; x.mxor = row & 7; x.mhi = x.lane >> 4;
  }
  const int goff = x.goff;
  x.ip = solid(&g_img[0][x.m()][2 * x.j()][w * 512 + x.oo()]);
  x.so = solid(16 * x.oo());
  uint4 r1[4];
  float ts[4] = {0.f, 0.f, 0.f, 0.f};
#pragma unroll
  for (int i = 0; i < 4; i++) r1[i] = make_uint4(0, 0, 0, 0);
  TSW(0);
  mbar_wait3(x.fullA(0), 0, x.fullB(0), 0);
#pragma unroll 1
  for (int L = 0; L < 4; L++) {
    float acc[64];
    constexpr uint32_t dcs = desc_lo(SB + OFF_CS, 0);
    if ((L & 1) == 0) {
    float kv[128];
    x.ha = L ? HA64 : HA128; x.k2 = L ? 32 : 4;
    gemm_issue<256, true, false>(kv, x, true); gemm_next<256>(x);
    {
      int i = 1;
#pragma unroll 1
      for (int seg = L ? NS - 1 : 0; seg <= NS; seg++) {
        const int end = seg < NS ? (L == 0 ? 3 + SA * ((x.j() + SW * w) & 3) + SB_ * seg : XA + 1) : 14 + L;
#pragma unroll 1
        do {
          gemm_issue<256, false, false>(kv, x);
          gemm_retire<256>(x, true);
          i++;
          if (i == 5) TSL_(8);
          if (i == 11) TSL_(10);
        } while (i != end);
        if (seg < NS && L == 0) {
          uint32_t v[16];
          float a[32];
#pragma unroll
          for (int q = 0; q < 4; q++) ldsm4(x.maddr(x.aslot(x.pa), 2 * q), reinterpret_cast<uint32_t (&)[4]>(v[4 * q]));
#pragma unroll
          for (int q = 0; q < 16; q++) { a[2 * q] = lo16(v[q]); a[2 * q + 1] = hi16(v[q]); }
          stats_acc<32>(a, ts);
          fence_regs(ts);
          wg_bar(w);
        }
        if (seg == NS - 1) {
          if (L > 0) { img_store(r1, x.img(XBUF(L), 1)); publish(2, x); }
          mbar_wait(sb + BAR_EPOCH, 0);
          stats_send(ts, L, x);
        }
      }
    }
      const Ring kt = x.ra;
      if (L == 0) adv<NA>(x.ra);
#pragma unroll 1
      for (int h = L; h < 2; h++) {
        float d[16];
        mbar_wait2(x.fullA(kt.s), kt.ph, sb + BAR_WPHI, 0);
        wgmma_fence();
#pragma unroll
        for (int q = 0; q < 2; q++) wgmma_ss_n32(d, x.da0 + kt.s * (SLOT / 16) + h * 4 + q * 2, desc_lo(SB + OFF_S + 4096, 512) + w * 256 + h * 128 + q * 64, q);
        wgmma_commit();
        gemm_issue<256, false, false>(kv, x);
        gemm_retire<256>(x, true);
        if (h) x.releaseA(kt.s);
        fence_regs(d);
        uint4* dst = &g_wf[1][x.j()][x.m()][w * 512 + (x.warp * 16 + x.g) * 8 + ((h * 4 + x.c) ^ x.g)];
        dst[0] = make_uint4(pack2(d[0], d[1]), pack2(d[4], d[5]), pack2(d[8], d[9]), pack2(d[12], d[13]));
        dst[64] = make_uint4(pack2(d[2], d[3]), pack2(d[6], d[7]), pack2(d[10], d[11]), pack2(d[14], d[15]));
      }
      const uint32_t dm = desc_lo(SB + OFF_MA, 0) + w * 64;
      mbar_wait2(sb + BAR_STAT, 0, sb + BAR_CS, 0);
      wgmma_fence();
      wgmma_r1_n256(kv, dm, dcs + 96, 1);
      wgmma_commit();
      const Stats st = load_stats(w, x);
      mbar_wait2(x.fullA(x.ra.s), x.ra.ph, x.fullB(x.rb.s), x.rb.ph);
      wgmma_wait<0>();
      fence_regs(kv);
      gemm_release<256>(x, true);
      TSL_(2);
      uint32_t P0[32], P1[32], PH[32];
#pragma unroll
      for (int t = 0; t < 16; t++) { P0[t] = pack2(kv[4 * t] * st.rstd0, kv[4 * t + 1] * st.rstd0); P1[t] = pack2(kv[4 * t + 2] * st.rstd1, kv[4 * t + 3] * st.rstd1); }
      pin<16>(P0, x.mrow + 16);
      {
#pragma unroll
        for (int q = 0; q < 4; q++) sts128((x.warp < 3 ? sb + OFF_T + w * 12288 + x.warp * 4096 : sb + OFF_S + 16384 + w * 2048) + x.lane * 16 + q * 512, P1[4 * q], P1[4 * q + 1], P1[4 * q + 2], P1[4 * q + 3]);
      }
      wgmma_fence();
      wgmma_r1_n128(acc, dm, dcs, 0);
      gemm_issue<128, false, false>(acc, x, PW & 1); gemm_next<128>(x);
      TSL_(3);
#pragma unroll
      for (int s = 0; s < 4; s++) {
#pragma unroll
        for (int t = 16 + 8 * (s & 1); t < 24 + 8 * (s & 1); t++) {
          if (s < 2) P1[t] = movm(pack2(kv[4 * t + 2] * st.rstd1, kv[4 * t + 3] * st.rstd1));
          else P0[t] = movm(pack2(kv[4 * t] * st.rstd0, kv[4 * t + 1] * st.rstd0));
        }
        if (s < 3) { gemm_issue<128, false, false>(acc, x); gemm_retire<128>(x, true); }
        if (s == 1) {
          if (x.warp < 3) {
#pragma unroll
            for (int q = 4; q < 8; q++) sts128(sb + OFF_T + w * 12288 + x.warp * 4096 + x.lane * 16 + q * 512, P1[4 * q], P1[4 * q + 1], P1[4 * q + 2], P1[4 * q + 3]);
          } else {
            uint4* dst = &g_halo[x.m()][x.j()][w][x.lane];
#pragma unroll
            for (int q = 0; q < 8; q++) dst[q * 32] = make_uint4(P1[4 * q], P1[4 * q + 1], P1[4 * q + 2], P1[4 * q + 3]);
          }
          publish(3, x);
          gemm_issue<128, false, false>(acc, x);
          gemm_retire<128>(x, true);
        }
      }
      TSL_(4);
      gemm_run<false>(acc, x, 10, 0);
      gemm_issue<128, false, false>(acc, x);
      {
        wg_bar(w);
        uint32_t tr = sb + OFF_T + w * 12288 + (x.warp - 1) * 4096;
        if (x.warp == 0) {
          tr = x.m() > 0 ? sb + OFF_S + 8192 + w * 4096 : tr + 4096;
          if (x.m() > 0) mbar_wait(sb + BAR_HALO, L >> 1);
        }
#pragma unroll
        for (int q = 0; q < 8; q++) lds128(tr + x.lane * 16 + q * 512, PH[4 * q], PH[4 * q + 1], PH[4 * q + 2], PH[4 * q + 3]);
      }
      gemm_retire<128>(x, false);
      gemm_end(acc, x);
      TSL_(5);
      const bool first = (x.m() == 0) && (x.warp == 0);
      const bool hi0 = 2 * x.c > x.g, hi1 = 2 * x.c + 1 > x.g;
      const uint32_t mhi = (hi0 ? 0xFFFFu : 0u) | (hi1 ? 0xFFFF0000u : 0u);
      const float sc0 = st.rstd0 * (0.17677669529663687f * LOG2E), sc1 = st.rstd1 * (0.17677669529663687f * LOG2E);
#pragma unroll
      for (int hp = 0; hp < 2; hp++) {
        const uint32_t tile = x.aslot(x.held(hp));
        uint32_t px[2], py[2];
        float s[2][3][4];
#pragma unroll
        for (int u = 0; u < 2; u++) {
#pragma unroll
          for (int q = 0; q < 12; q++) s[u][q >> 2][q & 3] = 0.f;
#pragma unroll
          for (int ks = 0; ks < 2; ks++) {
            const int t = 8 * hp + 4 * u + 2 * ks;
            const uint32_t a0 = pack2(acc[4 * t], acc[4 * t + 1]), a1 = pack2(acc[4 * t + 2], acc[4 * t + 3]);
            const uint32_t a2 = pack2(acc[4 * t + 4], acc[4 * t + 5]), a3 = pack2(acc[4 * t + 6], acc[4 * t + 7]);
            mma16816(s[u][0], a0, a1, a2, a3, PH[t], PH[t + 1]);
            mma16816(s[u][1], a0, a1, a2, a3, P0[t], P0[t + 1]);
            mma16816(s[u][2], a0, a1, a2, a3, P1[t], P1[t + 1]);
          }
        }
        float e[2][4], r[2][2];
#pragma unroll
        for (int u = 0; u < 2; u++) {
          e[u][0] = (hi0 ? s[u][0][0] : s[u][1][0]) * sc0; e[u][1] = (hi1 ? s[u][0][1] : s[u][1][1]) * sc0;
          e[u][2] = (hi0 ? s[u][1][2] : s[u][2][2]) * sc1; e[u][3] = (hi1 ? s[u][1][3] : s[u][2][3]) * sc1;
          if (first) { if (hi0) e[u][0] = -1e30f; if (hi1) e[u][1] = -1e30f; }
          r[u][0] = fmaxf(e[u][0], e[u][1]); r[u][1] = fmaxf(e[u][2], e[u][3]);
        }
#pragma unroll
        for (int d = 1; d <= 2; d++)
#pragma unroll
          for (int q = 0; q < 4; q++) r[q >> 1][q & 1] = fmaxf(r[q >> 1][q & 1], __shfl_xor_sync(0xffffffffu, r[q >> 1][q & 1], d));
#pragma unroll
        for (int u = 0; u < 2; u++) {
#pragma unroll
          for (int q = 0; q < 4; q++) e[u][q] = ex2(e[u][q] - r[u][q >> 1]);
          r[u][0] = e[u][0] + e[u][1]; r[u][1] = e[u][2] + e[u][3];
        }
#pragma unroll
        for (int d = 1; d <= 2; d++)
#pragma unroll
          for (int q = 0; q < 4; q++) r[q >> 1][q & 1] += __shfl_xor_sync(0xffffffffu, r[q >> 1][q & 1], d);
#pragma unroll
        for (int u = 0; u < 2; u++) {
          const float rx = rcp(r[u][0]), ry = rcp(r[u][1]);
          px[u] = pack2(e[u][0] * rx, e[u][1] * rx); py[u] = pack2(e[u][2] * ry, e[u][3] * ry);
        }
        uint32_t o[8][2];
        uint4 ro[4];
#pragma unroll
        for (int q = 0; q < 8; q++) {
          float d[4] = {0.f, 0.f, 0.f, 0.f};
          const int t = 16 + 8 * hp + q, u = q >> 2;
          mma16816(d, px[u] & mhi, 0u, px[u] & ~mhi, py[u] & mhi, PH[t], P0[t]);
          mma1688(d, 0u, py[u] & ~mhi, P1[t]);
          o[q][0] = pack2(d[0], d[1]); o[q][1] = pack2(d[2], d[3]);
        }
#pragma unroll
        for (int q = 0; q < 4; q++) ro[q] = make_uint4(o[4 * (q & 1)][q >> 1], o[4 * (q & 1) + 1][q >> 1], o[4 * (q & 1) + 2][q >> 1], o[4 * (q & 1) + 3][q >> 1]);
        img_tag(ro, false, 0, x);
        img_store(ro, x.img(0, hp));
        if (hp == 0) publish(0, x);
        uint32_t xs[16];
        if (L) img_load(xs, tile, x);
        else {
#pragma unroll
          for (int q = 0; q < 4; q++) {
            uint32_t v[4];
            ldsm4(x.maddr(tile, 2 * q), v);
            xs[2 * q] = v[0]; xs[8 + 2 * q] = v[1]; xs[2 * q + 1] = v[2]; xs[9 + 2 * q] = v[3];
          }
          __syncwarp();
        }
        img_sts(ro, tile, x);
        img_unpack(acc + 32 * hp, xs);
      }
    } else {
      float kv[128];
      float (&kv0)[64] = reinterpret_cast<float (&)[64]>(kv[0]);
      float (&kv1)[64] = reinterpret_cast<float (&)[64]>(kv[64]);
      auto mma8 = [&](uint32_t as, uint32_t bs, int i, bool fence) {
        const uint32_t da = desc_lo(SB + OFF_A, 16) + as * (SLOT / 16), db = desc_lo(SB + OFF_B, 8192) + bs * (SLOT / 16);
        if (fence) wgmma_fence();
#pragma unroll
        for (int k = 0; k < 4; k++) {
          wgmma_ss_n128(kv0, da + (k >> 1) * 32 + (k & 1) * 2, HA64, db + 128 * k, i + k);
          wgmma_ss_n128(kv1, da + 512 + (k >> 1) * 32 + (k & 1) * 2, HA64, db + 128 * k, i + k);
        }
        wgmma_commit();
      };
      constexpr uint32_t dm = desc_lo(SB + OFF_MB, 0);
      auto relB = [&](uint32_t s) { mbar_arrive_n(sb + BAR_EMPTYB + s * 8, 2); };
      auto skip = [&]() {
#pragma unroll
        for (int q = 0; q < 6 - NJ; q++) adv<NA>(x.ra);
        x.rb.s = w ? (2 + NJ) % 6 : 4;
        if (!w && NJ < 4) x.rb.ph ^= 1;
      };
      static_assert(NA == 5 && NB == 6, "ring arithmetic");
      mma8(x.ra.s, x.rb.s + w, 0, true);
      gemm_next<256>(x);
#pragma unroll 1
      for (int i = 1; i < NJ; i++) {
        mbar_wait2(x.fullA(x.ra.s), x.ra.ph, x.fullB(x.rb.s + w), x.rb.ph);
        mma8(x.ra.s, x.rb.s + w, 1, true);
        if (!XO && i == XR) { img_store(r1, x.img(XBUF(L), 1)); publish(2, x); }
        if (!XO && i == XS) stats_send(ts, L, x);
        wgmma_wait<1>();
        if (x.elected) { x.releaseA(x.pa); relB(x.pb + w); }
        gemm_next<256>(x);
        if (XO && i == XR) { img_store(r1, x.img(XBUF(L), 1)); publish(2, x); stats_send(ts, L, x); }
      }
      if (w) {
        wgmma_wait<0>();
        if (x.elected) { x.releaseA(x.pa); relB(x.pb + 1); }
        skip();
        asm volatile("bar.sync 7, 256;" ::: "memory");
      }
      TSL_(8);
      {
        const int t = lane_id() + 32 * x.warp;
        uint32_t mask = t < 2 ? ((w ? (t ? 0xFF3Fu : 0x3FFFu) : 0xFFFFu) >> (NJ - 1)) & (w ? ~1u : ~0u) : 0u, cnt = 1 + t;
        bool ready = false;
#pragma unroll 1
        for (int i = NJ; i < 16; i++) {
          if (!ready) mbar_wait2(x.fullA(x.ra.s), x.ra.ph, x.fullB(x.rb.s), x.rb.ph);
          mma8(x.ra.s, x.rb.s, 1, true);
          const uint32_t bar = sb + (t ? BAR_EMPTYB + x.pb * 8 : BAR_EMPTYA + x.pa * 8);
          gemm_next<128>(x);
          if (w && (i | 4) == 15) x.rb.s = 4;
          ready = mbar_probe2(x.fullA(x.ra.s), x.ra.ph, x.fullB(x.rb.s), x.rb.ph);
          wgmma_wait<1>();
          if (mask & 1) mbar_arrive_n(bar, cnt);
          mask >>= 1; cnt = 2;
          if (i == 8 && w) asm volatile("bar.arrive 9, 256;" ::: "memory");
          if (i == 9) TSL_(10);
        }
        mbar_wait2(sb + BAR_STAT, 1, sb + BAR_CS + 8, 0);
        wgmma_fence();
        wgmma_r1_n128(kv0, dm, dcs + 96 + 96 * w, 1);
        wgmma_r1_n128(kv1, dm + 64, dcs + 96 + 96 * w, 1);
        wgmma_commit();
        if (w == 0) asm volatile("bar.arrive 7, 256;" ::: "memory");
        wgmma_wait<1>();
        if (mask & 1) mbar_arrive_n(sb + (t ? BAR_EMPTYB + x.pb * 8 : BAR_EMPTYA + x.pa * 8), 2);
      }
      const Stats s0 = load_stats(0, x), s1 = load_stats(1, x), st = w ? s1 : s0;
      if (w == 0) skip();
      const uint32_t h0 = x.held(0), h1 = x.held(1);
      auto vreg = [&](int ks) { return ks < 6 ? OFF_A + (ks < 3 ? h0 * SLOT : h1 * SLOT - 15360) + ks * 5120 : OFF_S + 2048 + ks * 5120; };
      uint32_t tV[2], uu[4];
#pragma unroll
      for (int hf = 0; hf < 2; hf++) {
        tV[hf] = sb + vreg(4 * hf + x.warp) + ((x.lane >> 3) & 1) * 2560 + (x.lane & 7) * 16 + x.mhi * 128;
        const float i0 = rcp(hf ? s1.rstd0 : s0.rstd0), i1 = rcp(hf ? s1.rstd1 : s0.rstd1);
        const uint32_t h = pack2(i0, i1);
        uu[2 * hf] = pack2(lo16(h), i0 - lo16(h)); uu[2 * hf + 1] = pack2(hi16(h), i1 - hi16(h));
        asm volatile("" : "+r"(tV[hf]), "+r"(uu[2 * hf]), "+r"(uu[2 * hf + 1])::"memory");
      }
      wgmma_wait<0>();
      fence_regs(kv);
      TSL_(2);
      if (w == 0) {
        uint32_t f[2][18], ad[4];
#pragma unroll
        for (int q = 0; q < 18; q++) f[1][q] = 0u;
#pragma unroll
        for (int q = 0; q < 4; q++) ad[q] = x.maddr(sb + OFF_S, 2 * q);
        auto norm = [&](int un) {
          uint32_t* u = f[un & 1];
          const Stats& sn = (un & 2) ? s1 : s0;
#pragma unroll
          for (int sg = 0; sg < 2; sg++) {
            uint32_t v = u[16 + sg];
            v = add2(v, __shfl_xor_sync(0xffffffffu, v, 1)); v = add2(v, __shfl_xor_sync(0xffffffffu, v, 2));
            const float a = rcp(lo16(v)) * sn.rstd0, b = rcp(hi16(v)) * sn.rstd1;
            const uint32_t r0 = pack2(a, a), r1_ = pack2(b, b);
#pragma unroll
            for (int q = 8 * sg; q < 8 * sg + 8; q++) u[q] = mul2(u[q], (q & 1) ? r1_ : r0);
#pragma unroll
            for (int q = 2 * sg; q < 2 * sg + 2; q++) stsm4(ad[q] + (un & 1) * SLOT + (un >> 1) * 8192, u[4 * q], u[4 * q + 1], u[4 * q + 2], u[4 * q + 3]);
          }
        };
        auto unit = [&](int un) { return kv + ((un >> 1) & 1) * 64 + (un & 1) * 16 + (un >> 2) * 32; };
        hedgehog_scale<1, 0>(kv, s0, nullptr, [] {});
#pragma unroll 1
        for (int it = 0;; it++) {
#pragma unroll
          for (int un = 0; un < 4; un++) {
            if (un == 1) {
              if (it) asm volatile("bar.sync 9, 256;" ::: "memory");
#pragma unroll
              for (int q = 0; q < 4; q++) ad[q] -= it * (OFF_S - OFF_B - 2 * SLOT);
            }
            norm((un + 3) & 3);
            dual_exp(unit(un), f[un & 1], x.goff);
            hedgehog_scale<1, KEEP>(unit(un + 1), ((un + 1) & 2) ? s1 : s0, f[(un + 1) & 1], [] {});
          }
          if (it) break;
#pragma unroll
          for (int q = 0; q < 32; q++) {
            asm volatile("mov.b32 %0, %1;" : "=f"(kv[q]) : "f"(kv[q + 32]));
            asm volatile("mov.b32 %0, %1;" : "=f"(kv[q + 64]) : "f"(kv[q + 96]));
            if (q < 16) kv[32 + q] = 0.f;
          }
        }
        norm(3);
        TSL_(3);
      } else {
        wg_bar(w);
#pragma unroll
        for (int hf = 0; hf < 2; hf++) {
          stsm4(tV[hf] + 512 + x.mhi * 512, uu[2 * hf], uu[2 * hf + 1], uu[2 * hf], uu[2 * hf + 1]);
          stsm4(tV[hf] + 1792 + x.mhi * 512, uu[2 * hf], uu[2 * hf + 1], uu[2 * hf], uu[2 * hf + 1]);
#pragma unroll
          for (int q = 0; q < 8; q++) {
            const float* u = kv + 64 * hf + 8 * q;
            stsm4(tV[hf] + (q >> 1) * 640 + (q & 1) * 256, pack2(u[0], u[1]), pack2(u[2], u[3]), pack2(u[4], u[5]), pack2(u[6], u[7]));
          }
        }
        TSL_(3);
      }
      {
        float d[2][20];
        uint4* dst = &g_kvpart[x.j()][w * 4 + x.warp][0][x.m() * 32 + x.lane];
        unsigned* dz = reinterpret_cast<unsigned*>(&g_kvpart[x.j()][w * 4 + x.warp][x.c & 1][512]) + x.m() * 8 + x.g;
        fence_async_smem();
        cta_bar();
        TSL_(11);
        uint32_t pk[9];
        auto prep = [&](float (&u)[20]) {
          fence_regs(u);
#pragma unroll
          for (int q = 0; q < 8; q++) pk[q] = pack2(u[((q >> 1) & 2) + 4 * (q & 3)], u[((q >> 1) & 2) + 4 * (q & 3) + 1]);
          pk[8] = __float_as_uint((x.c & 1) ? u[18] + u[19] : u[16] + u[17]);
#pragma unroll
          for (int q = 0; q < 9; q += 4) pk[q] = (pk[q] & ~1u) | (L == 1);
        };
        auto send = [&](int hp) {
          st_v4(dst + hp * 16 * 544, pk[0], pk[1], pk[2], pk[3]); st_v4(dst + (hp * 16 + 1) * 544, pk[4], pk[5], pk[6], pk[7]);
          st_flag(dz + hp * 16 * 544 * 4, pk[8]);
        };
        wgmma_fence();
#pragma unroll
        for (int q = 0; q < 17; q++) {
          if (q < 16) wgmma_ss_n40_tt(d[q >> 3], desc_lo(SB + (q < 8 ? OFF_S : OFF_B + 2 * SLOT), 1024) + w * (SLOT / 16) + 128 * (q & 7), desc_lo(SB + vreg(q & 7), 2560) + (w + (q >> 3) * 2) * 40, q & 7);
          else wgmma_r1_n128(acc, dm + w * 64, dcs, 0);
          if (q == 7 || q == KVS || q == 16) wgmma_commit();
          if (q == KVS) { mbar_wait2(x.fullA(x.ra.s), x.ra.ph, x.fullB(x.rb.s), x.rb.ph); wgmma_wait<1>(); prep(d[0]); send(0); bb_fence(x.goff); wgmma_fence(); }
        }
        gemm_issue<128, false>(acc, x, true); gemm_next<128>(x);
        wgmma_wait<1>();
        x.releaseA(h0); x.releaseA(h1); x.releaseB(2); x.releaseB(3);
        if (x.lane == 0) mbar_arrive(sb + BAR_SIGT);
        prep(d[1]);
        TSL_(4);
#pragma unroll 1
        for (int seg = 0; seg < 2; seg++) {
          const int n0 = w ? PS1 : PS0;
          gemm_run(acc, x, seg ? 15 - n0 : n0, seg, seg ? L : 0);
          if (seg == 0) send(1);
        }
      }
      gemm_end(acc, x);
      TSL_(5);
      {
        float dp[2][20], dn[2][20];
        uint32_t f[4][16];
        auto mma = [&](int h) {
          if (!(h & 1)) mbar_wait(sb + BAR_KV + h * 4, L >> 1);
          if (h == 0) TSL_(9);
          const uint32_t db = desc_lo(SB + OFF_S + h * 5120, 128);
          const uint32_t (&a)[16] = f[h];
          wgmma_fence();
          wgmma_rs_n40(dp[h & 1], a[0], a[1], a[2], a[3], db, 0);
          wgmma_rs_n40(dn[h & 1], a[8], a[9], a[10], a[11], db + 160, 0);
          wgmma_rs_n40(dp[h & 1], a[4], a[5], a[6], a[7], db + 80, 1);
          wgmma_rs_n40(dn[h & 1], a[12], a[13], a[14], a[15], db + 240, 1);
          wgmma_commit();
        };
        uint32_t xr[16];
        auto fin = [&](int h) {
          const uint32_t tile = x.aslot(x.held(h >> 1));
          if (!(h & 1)) img_load(xr, tile, x);
          float (&u)[20] = dp[h & 1];
          float (&v)[20] = dn[h & 1];
          fence_regs(u); fence_regs(v);
#pragma unroll
          for (int r = 0; r < 2; r++) {
            const float sp = u[16 + 2 * r], sn = v[16 + 2 * r];
            const float id = rcp(fmaf(fmaf(sp, L == 1 ? 0.065536f * 128 / 129 : 0.065536f, u[17 + 2 * r]), sn, v[17 + 2 * r] * sp)), aa = sn * id, cc = sp * id;
            uint32_t o[4];
#pragma unroll
            for (int t = 0; t < 4; t++) o[t] = pack2(fmaf(u[4 * t + 2 * r], aa, v[4 * t + 2 * r] * cc), fmaf(u[4 * t + 2 * r + 1], aa, v[4 * t + 2 * r + 1] * cc));
            o[2 * r + (h & 1)] = img_tag(o[2 * r + (h & 1)], false, 1, x);
            stg128(x.img(0, h >> 1) + r * 64 + (h & 1) * 32, make_uint4(o[0], o[1], o[2], o[3]));
            sts128(tile + r * 1024 + (h & 1) * 512 + x.so, o[0], o[1], o[2], o[3]);
          }
          if (h & 1) { if (h == 1) publish(0, x); img_unpack(acc + 16 * (h - 1), xr); }
        };
        auto ex = [&](int h) { dual_exp_rcp(acc + 16 * h, f[h]); };
        Stats sq = st;
#pragma unroll
        for (int h = 0; h < 4; h += 2) {
          hedgehog_scale<2, 0>(acc + 16 * h, sq, nullptr, [&] { ex(h); });
          mma(h);
          ex(h + 1); wgmma_wait<0>(); fin(h);
          if (h == 0) bb_fence(x.goff);
          mma(h + 1);
          wgmma_wait<0>(); fin(h + 1);
          if (h == 0) sq.rstd1 += bb_fence(x.goff);
        }
      }
    }
    if (PW & 2) { mbar_wait(x.fullB(x.rb.s), x.rb.ph); fence_regs(acc); }
    fence_async_smem();
    wg_bar(w);
    TSL_(6);
    rewind2<NA>(x.ra);
    gemm_issue<128, false>(acc, x, PW & 2); gemm_next<128>(x);
    uint4* out = solid(P.out + goff + (x.warp * 16 + (x.lane >> 3)) * 256 + (x.lane & 7));
#pragma unroll 1
    for (int seg = L >= TSL ? 0 : 1; seg < 2; seg++) {
      gemm_run(acc, x, L >= TSL ? (seg ? TSK : 15 - TSK) : 15, seg, 10 + L);
      if (L >= TSL) {
        if (seg == 0 && w == 1) asm volatile("bar.sync 6, 256;" ::: "memory");
        if (seg == 1 && w == 0) asm volatile("bar.arrive 6, 256;" ::: "memory");
      }
    }
    gemm_end(acc, x);
    TSL_(7);
    rewind2<NA>(x.ra);
    out_epilogue(acc, r1, ts, out, L, x);
    TSL_(13);
  }
}

typedef unsigned long long u64;
template <class T> __device__ __forceinline__ T* early(T* p) { return (T*)__shfl_xor_sync(0xffffffffu, (u64)p, 1); }
__device__ __forceinline__ void pause(uint32_t GAP) {
  if (GAP) { uint32_t t0, t; asm volatile("mov.u32 %0, %%clock;" : "=r"(t0)); do { asm volatile("mov.u32 %0, %%clock;" : "=r"(t)); } while (t - t0 < GAP); }
}
__device__ __forceinline__ u64 order_table(int kind, int j) {
  const int i = threadIdx.x & 15;
  const unsigned v = (unsigned)(kind == 2 ? q_order(i, j) : kv_order(i, j, kind)) << (4 * (i & 7));
  return (u64)__reduce_or_sync(0xffffffffu, i < 8 ? 0u : v) << 32 | __reduce_or_sync(0xffffffffu, i < 8 ? v : 0u);
}

__device__ __forceinline__ void b_producer(const Params& P, uint32_t sb, unsigned vb) {
  const int j = cta_j(vb);
  const u64 t0 = order_table(0, j), t1 = order_table(1, j), t2 = order_table(2, j);
  Ring r = {PRE_B % NB, PRE_B < NB};
#pragma unroll 1
  for (int sg = 0; sg < 20; sg++) {
    const int L = sg / 5, p = sg - 5 * L, wt = L & 1;
    int n = p >= 3 ? 16 : (wt ? (p ? 16 - NJ : 2 * NJ) : (p ? 0 : (L ? 32 : 32 - PRE_B)));
    u64 tab = p == 3 ? t2 : (sg == 0 ? t0 >> (2 * PRE_B) : (p == 1 || p == 2 ? t1 >> (4 * NJ) : t1));
    const CUtensorMap* tm = p == 4 ? &P.mwo[wt] : &P.mw[wt ? 1 : L];
    const uint4* img = &g_wf[p != 3][j][0][0];
    int col = (p >= 3 ? 0 : (p == 2 ? 2048 : 1024)) + 128 * j;
    const int flip = p == 0 ? 3072 : 0;
    const bool fold = wt && p != 4;
    if (sg == 5 || sg == 8) { mbar_wait(sb + (sg == 5 ? BAR_WPHI : BAR_CS + 8), sg == 5); fence_async_global(); }
    if (DEFER && p == 4 && ((DEFL >> wt) & 1)) {
      Ring q = r;
      for (int u = 0; u < DEFER; u++) adv<NB>(q);
      mbar_wait(sb + BAR_EMPTYB + q.s * 8, q.ph);
    }
#pragma unroll 1
    for (; n > 0; n--) {
      const int kb = (int)tab & 15;
      mbar_wait(sb + BAR_EMPTYB + r.s * 8, r.ph);
      if (elect()) {
        mbar_expect_tx(sb + BAR_FULLB + r.s * 8, SLOT);
        if (fold && col < 2048) bulk_load(sb + OFF_B + r.s * SLOT, img + kb * 1024, SLOT, sb + BAR_FULLB + r.s * 8);
        else tma_load_w(sb + OFF_B + r.s * SLOT, tm, sb + BAR_FULLB + r.s * 8, col, kb);
      }
      adv<NB>(r);
      if (p == 2 && (n | 4) == 5) r.s = 4;
      col ^= flip;
      if (!(col & flip & 2048)) tab >>= 4;
    }
  }
}

__device__ __forceinline__ void a_loader(const Params& P, uint32_t sb, unsigned vb) {
  const int j = cta_j(vb), m = cta_m(vb);
  const u64 t1 = order_table(1, j), t2 = order_table(2, j);
  Ring r = {PRE_A % NA, PRE_A < NA};
  {
    u64 tab = order_table(0, j) >> (4 * PRE_A);
#pragma unroll 1
    for (int i = PRE_A; i < 33; i++) {
      if (i == 17) tab = t2;
      mbar_wait(sb + BAR_EMPTYA + r.s * 8, r.ph);
      if (elect()) {
        mbar_expect_tx(sb + BAR_FULLA + r.s * 8, SLOT);
        if (i != 14) tma_load_3d(sb + OFF_A + r.s * SLOT, &P.mx, sb + BAR_FULLA + r.s * 8, ((int)tab & 15) * 64, m * 64, 0);
        else {
          tma_load_w(sb + OFF_A + r.s * SLOT, &P.mw[1], sb + BAR_FULLA + r.s * 8, 1024 + 128 * j, m);
          mbar_expect_tx(sb + BAR_WPHI, 8192); tma_load_2d(sb + OFF_S + 4096, &P.mwphi, sb + BAR_WPHI, 0, 128 * j);
        }
        if (i == PF1 || i == PF2) tma_prefetch_w(&P.mwo[i == PF2], 128 * j, m);
      }
      adv<NA>(r);
      if (i != 14) tab >>= 4;
    }
  }
  const unsigned tag = get_tag(sb);
  unsigned kph = 0;
#pragma unroll 1
  for (int sg = 0; sg < 13; sg++) {
    const int L = sg >> 2, p = sg & 3;
    if (p == 0 && (L & 1)) {
#pragma unroll 1
      for (int h = 0; h < 2; h++) {
        poll_flags(&g_kvfflag[L >> 1][j][h][0], 16, 0xFFFFu, tag);
        TS(4, h ? 14 + L : 26 + L);
        for (int it = 0;; it++) {
          if (elect()) { mbar_expect_tx(sb + BAR_STAT + 8, 10240); bulk_load(sb + OFF_S + h * 10240, &g_kvfin[j][8 * h][0], 10240, sb + BAR_STAT + 8); }
          mbar_wait(sb + BAR_STAT + 8, kph);
          kph ^= 1;
          uint32_t a = 1u, o = 0u;
#pragma unroll
          for (int u = 0; u < 20; u++) { const uint32_t v = __float_as_uint(lds32f(sb + OFF_S + h * 10240 + u * 512 + (threadIdx.x & 31) * 16)); a &= v; o |= v; }
          if (__all_sync(0xffffffffu, (L == 1 ? a : ~o) & 1u)) break;
          fence_async_smem();
          if (it > (1 << 16)) __trap();
        }
        if (elect()) mbar_arrive(sb + BAR_KV + h * 8);
        TS(4, h ? 30 + L : (L == 1 ? 20 : 25));
      }
    }
    int n = p < 2 ? 14 : (p == 2 ? ((L & 1) ? 0 : 16 - NJ) : 16);
    u64 tab = p == 3 ? t2 : t1 >> (p < 2 ? 8 : 4 * NJ);
    const uint4* img = &g_img[p ? XBUF(L + 1) : 0][m][0][0];
#pragma unroll 1
    for (; n > 0; n--) {
      const uint4* src = early(img + ((int)tab & 15) * 1024);
      const uint32_t bar = sb + (p < 2 ? BAR_LAND : BAR_FULLA) + r.s * 8;
      mbar_wait(sb + BAR_EMPTYA + r.s * 8, r.ph);
      if (elect()) mbar_expect_tx(bar, SLOT);
      if (p < 2 && n == 14) {
        const int lane = threadIdx.x & 31;
        const unsigned* f = &g_hint[(m & 14) + ((lane >> 3) & 1)][(~j & 4) + (lane & ND0)];
        mbar_wait(sb + BAR_SIGP + p * 8, L & 1);
        pause(PD);
        int it = 0;
        while (!__all_sync(0xffffffffu, (int)(ld_flag(f) - (tag * 8 + 2 * L + p)) >= 0)) { if (++it > (1 << 22)) __trap(); }
        TS(2, p == 0 ? 5 + L * 8 : 9 + L * 8);
        TSH((2 * L + p) * 8 + 2);
      }
      if (elect()) bulk_load(sb + OFF_A + r.s * SLOT, src, SLOT, bar);
      adv<NA>(r);
      tab >>= 4;
      pause(p < 2 && n > 10 ? G0 : 0);
    }
  }
}

template <int KB>
__device__ __forceinline__ uint2 sum_packets(float (&a)[8], uint32_t addr, int n) {
  uint2 ok = make_uint2(~0u, 0u);
#pragma unroll 1
  for (int b = 0; b < n; b += KB) {
    uint4 v[KB];
#pragma unroll
    for (int u = 0; u < KB; u++) lds128(addr + (b + u) * 512, v[u].x, v[u].y, v[u].z, v[u].w);
#pragma unroll
    for (int u = 0; u < KB; u++) {
      ok.x &= v[u].x; ok.y |= v[u].x;
      a[0] += lo16(v[u].x); a[1] += hi16(v[u].x); a[2] += lo16(v[u].y); a[3] += hi16(v[u].y);
      a[4] += lo16(v[u].z); a[5] += hi16(v[u].z); a[6] += lo16(v[u].w); a[7] += hi16(v[u].w);
    }
  }
  return ok;
}
__device__ __forceinline__ void helper_bar() { asm volatile("bar.sync 4, 64;" ::: "memory"); }
__device__ __forceinline__ void helper(const Params& P, uint32_t sb, int w, unsigned vb) {
  const int j = cta_j(vb), m = cta_m(vb);
  if (w == 0) {
    if (elect()) {
      const unsigned t = atomicAdd(&g_ctr, 1u) / NCTA + 1u;
      asm volatile("st.shared.u32 [%0], %1;" ::"r"(sb + OFF_EPOCH), "r"(t) : "memory");
      mbar_arrive(sb + BAR_EPOCH);
    }
  }
  const unsigned tag = get_tag(sb);
  mbar_wait(sb + BAR_FULLB + 24, 0);
  const uint32_t stg = sb + OFF_T + w * 12288, stb = sb + BAR_STG + w * 24;
  Ring rs = {0, 0};
  uint32_t vs = 33 % NA, vph = 0;
  auto cs_image = [&](int L) {
      const int lane = lane_id();
      poll_flags(&g_csflag[L][j][0], 16, L ? CSNEED : 0xFFFu, tag);
#pragma unroll
      for (int p = 0; p < 3; p++) {
        const uint4 u = ldcg4(&g_cs[L][0][p * 1024 + 128 * j + lane * 4]), v = ldcg4(&g_cs[L][1][p * 1024 + 128 * j + lane * 4]);
        const float c0 = __uint_as_float(u.x) + __uint_as_float(v.x), c1 = __uint_as_float(u.y) + __uint_as_float(v.y);
        const float c2 = __uint_as_float(u.z) + __uint_as_float(v.z), c3 = __uint_as_float(u.w) + __uint_as_float(v.w);
        const uint32_t h0 = pack2(c0, c1), h1 = pack2(c2, c3), dst = sb + OFF_CS + (p * 16 + (lane >> 1)) * 96 + L * 48 + (lane & 1) * 8;
        sts64(dst, h0, h1); sts64(dst + 16, pack2(c0 - lo16(h0), c1 - hi16(h0)), pack2(c2 - lo16(h1), c3 - hi16(h1))); sts64(dst + 32, h0, h1);
        if (L == 0) { sts64(dst + 48, 0u, 0u); sts64(dst + 64, 0u, 0u); sts64(dst + 80, 0u, 0u); }
      }
      if (L == 0 && lane < 4) sts64(sb + OFF_CS + 4608 + lane * 8, 0u, 0u);
      fence_async_smem();
      __syncwarp();
      if (elect()) mbar_arrive(sb + BAR_CS + L * 8);
      TS(4, 2 + L * 2);
  };
#pragma unroll 1
  for (int L = 0; L < 4; L++) {
    const int lane = lane_id();
    if (L == 0) {
      {
        const int wt = m >= 12, col = ((0x2021 >> (m & 12)) & 3) * 1024 + 128 * j + (m & 3) * 32;
        const CUtensorMap* tm = &P.mcs[wt];
        __nanosleep(wt ? D2 : CD);
        constexpr int nb = 8;
        float a[8] = {0.f, 0.f, 0.f, 0.f, 0.f, 0.f, 0.f, 0.f};
#pragma unroll 1
        for (int b = -3; b < nb; b++) {
          if (b >= 0) {
            mbar_wait(stb + rs.s * 8, rs.ph);
            sum_packets<KC>(a, stg + rs.s * 4096 + lane * 16, 8);
            fence_async_smem();
            __syncwarp();
          }
          const uint32_t sl = b < 0 ? (rs.s + b + 3) % 3 : rs.s;
          if (b + 3 < nb && elect()) { mbar_expect_tx(stb + sl * 8, 4096); tma_load_2d(stg + sl * 4096, tm, stb + sl * 8, col, (w * (16 - nb) + b + 3) * 64); }
          if (b >= 0) adv<3>(rs); else pause(CP);
        }
#pragma unroll 1
        for (int d = 4; d < 32; d *= 2)
#pragma unroll
          for (int u = 0; u < 8; u++) a[u] += __shfl_xor_sync(0xffffffffu, a[u], d);
        if (lane < 4) {
          float4* dst = reinterpret_cast<float4*>(&g_cs[wt][w][col + lane * 8]);
          dst[0] = make_float4(a[0], a[1], a[2], a[3]); dst[1] = make_float4(a[4], a[5], a[6], a[7]);
        }
        helper_bar();
        if (w == 0 && elect()) { fence_gpu(); st_flag(&g_csflag[wt][j][m], tag); }
      }
      if (w == 0) TS(4, 1 + L * 2);
    }
    if (L > 0 && w == 0) {
      mbar_wait(sb + BAR_SIGP + 16, (L - 1) & 1);
      fence_async_global();
      __nanosleep(CO && L == 1 ? SE : SD);
    }
    if (CO && L < 2 && w == 0) cs_image(L);
    if (w == (L == 0)) {
      if (L == 0) { mbar_wait(sb + BAR_WPHI, 0); __nanosleep(S0); }
#pragma unroll 1
      for (int p = 0; p < 2; p++) {
        uint4 v[8];
        for (int it = 0;; it++) {
          bool ok = true;
#pragma unroll
          for (int t = 0; t < 8; t++) v[t] = ld_pkt(&g_stats[m][p][t][lane]);
#pragma unroll
          for (int t = 0; t < 8; t++) ok = ok && (v[t].w & 15u) == seq4(tag, L);
          if (__all_sync(0xffffffffu, ok)) break;
          __nanosleep(200);
          if (it > (1 << 20)) __trap();
        }
        float s0 = 0.f, q0 = 0.f, s1 = 0.f, q1 = 0.f;
#pragma unroll
        for (int t = 0; t < 8; t++) { s0 += __uint_as_float(v[t].x); q0 += __uint_as_float(v[t].y); s1 += __uint_as_float(v[t].z); q1 += __uint_as_float(v[t].w & ~15u); }
        s0 *= (1.f / 1024); s1 *= (1.f / 1024);
        sts64(sb + OFF_MR + p * 256 + lane * 8, __float_as_uint(rsqrtf(fmaxf(q0 * (1.f / 1024) - s0 * s0, 0.f) + 1e-5f)),
              __float_as_uint(rsqrtf(fmaxf(q1 * (1.f / 1024) - s1 * s1, 0.f) + 1e-5f)));
#pragma unroll
        for (int r = 0; r < 2; r++) {
          const float v = -0.5f * (r ? s1 : s0);
          const uint32_t hh = pack2(v, v), hl = pack2(v, v - lo16(hh));
          const bool b = L & 1;
          sts128(sb + (b ? OFF_MB : OFF_MA) + p * 1024 + (lane >> 3) * 256 + r * 128 + (lane & 7) * 16, b ? 0u : hh, b ? hh << 16 : hl >> 16, b ? hl : 0u, 0u);
        }
      }
      fence_async_smem();
      __syncwarp();
      if (elect()) {
        mbar_arrive(sb + BAR_STAT);
      }
      TS(2, 0 + L * 8);
    }
    if (!CO && L < 2 && w == 0) cs_image(L);
    if (L & 1) {
      const uint32_t flip = L == 1 ? 0u : 1u;
      mbar_wait(sb + BAR_SIGT, 1);
      {
        int it = 0;
        if (PSL) __nanosleep(m < 8 ? PSL : PSL + 600);
        while (!__all_sync(0xffffffffu, (ld_flag(reinterpret_cast<const unsigned*>(&g_kvpart[j][m][w][512]) + (lane & 15) * 8) ^ flip) & 1u)) { if (PSL) __nanosleep(100); if (++it > (1 << 22)) __trap(); }
        fence_async_global();
      }
      if (w == 0) TS(4, 6 + L * 2);
      float a[8], z;
      for (int it = 0;; it++) {
        if (elect()) { mbar_expect_tx(stb + rs.s * 8, 8704); bulk_load(stg, &g_kvpart[j][m][w][0], 8704, stb + rs.s * 8); }
        mbar_wait(stb + rs.s * 8, rs.ph);
        if (w == 0) TS(4, 21 + L);
        adv<3>(rs);
#pragma unroll
        for (int u = 0; u < 8; u++) a[u] = 0.f;
        z = 0.f;
        uint32_t ok = 1u;
#pragma unroll
        for (int u = 0; u < 4; u++) { const float v = lds32f(stg + 8192 + u * 128 + (lane & 3) * 32 + (lane >> 2) * 4); z += v; ok &= __float_as_uint(v) ^ flip; }
        const uint2 tg = sum_packets<8>(a, stg + lane * 16, 16);
        ok &= flip ? ~tg.y : tg.x;
        if (__all_sync(0xffffffffu, ok & 1u)) break;
        fence_async_smem();
        if (it > (1 << 16)) __trap();
      }
      {
        uint4* img = &g_kvfin[j][m][w * 8 + (lane >> 2)];
        uint32_t a0 = __float_as_uint(a[0]) >> 16;
        a0 += ~(a0 ^ flip) & 1u;
        st_v4(img + (lane & 3) * 16, __byte_perm(a0, pack2(0.f, a[1]), 0x7610), pack2(a[2], a[3]), pack2(a[4], a[5]), pack2(a[6], a[7]));
        const uint32_t cz = pack2(0.f, qsum(z)) | (0x3781u ^ flip);
        if (!(lane & 3)) st_v4(img + 64, cz, cz, cz, cz);
        __syncwarp();
        if (elect()) st_flag(&g_kvfflag[L >> 1][j][m >> 3][(m & 7) * 2 + w], tag);
      }
      if (w == 0) TS(4, 7 + L * 2);
    } else {
      mbar_wait(sb + BAR_SIGT, 0);
      if (w == 0) {
        if (elect()) { fence_gpu(); st_flag(&g_hflag[L >> 1][m][j][0], tag); st_flag(&g_kflag[j][m], tag); }
        if (L == 0) {
          __nanosleep(KSL);
          poll_flags(&g_kflag[j][0], 16, 0xFFFFu, tag);
          if (elect()) mbar_arrive(sb + BAR_WPHI);
        }
      } else if (m > 0) {
        poll_flags(&g_hflag[L >> 1][m - 1][j][0], 1, 1u, tag);
        if (elect()) { mbar_expect_tx(sb + BAR_HALO, 8192); bulk_load(sb + OFF_S + 8192, &g_halo[m - 1][j][0][0], 8192, sb + BAR_HALO); }
        TS(2, 2 + L * 8);
      }
    }
    if (w == 0) {
#pragma unroll 1
      for (int e = 0; e < (L < 3 ? 2 : 1); e++) {
        unsigned* flag = early(&g_hint[m][j]);
        mbar_wait(sb + BAR_SIGP + e * 8, L & 1);
        TS(2, (e ? 6 : 3) + L * 8);
        TSH((2 * L + e) * 8);
        pause(XD);
        if (elect()) st_flag(flag, tag * 8 + 2 * L + e);
        TSH((2 * L + e) * 8 + 1);
      }
    } else {
#pragma unroll 1
      for (int i = 0; i < (L < 3 ? 28 : 14); i++) {
        const bool isx = i >= 14;
        const uint32_t a = sb + OFF_A + vs * SLOT + lane * 128 + ((lane >> 4) * 4 + (lane & 3)) * 16 + (lane & 12), code = img_code(isx, L + isx);
        for (int it = 0;; it++) {
          mbar_wait(sb + BAR_LAND + vs * 8, (vph >> vs) & 1);
          vph ^= 1u << vs;
          if (i - 14 * isx < 2) TSH((2 * L + isx) * 8 + 3 + 2 * (i - 14 * isx));
          uint32_t bad = 0;
#pragma unroll
          for (int u = 0; u < 4; u++) bad |= __float_as_uint(lds32f(a + u * 4096)) ^ code;
          if (__all_sync(0xffffffffu, !(bad & img_mask(isx)))) break;
          if (it > (1 << 16)) __trap();
          fence_async_smem();
          if (elect()) {
            mbar_expect_tx(sb + BAR_LAND + vs * 8, SLOT);
            bulk_load(sb + OFF_A + vs * SLOT, &g_img[isx ? XBUF(L + 1) : 0][m][o_order(i - 14 * isx + 2, j)][0], SLOT, sb + BAR_LAND + vs * 8);
          }
        }
        if (elect()) mbar_arrive(sb + BAR_FULLA + vs * 8);
        if (i - 14 * isx < 2) TSH((2 * L + isx) * 8 + 4 + 2 * (i - 14 * isx));
        if (++vs == NA) vs = 0;
      }
      vs = (vs + ((L & 1) ? 16 : 32 - NJ)) % NA;
    }
  }
}

__device__ __forceinline__ void spare(const Params& P, uint32_t sb, int id) {
  const int tid = threadIdx.x & 127, warp = __shfl_sync(0xffffffffu, threadIdx.x >> 5, 0), w = warp >> 2, lane = tid & 31, j = 2 * id + w;
  const uint32_t ring = w * 6 * SLOT, wp = 12 * SLOT + w * 8192, bar = sb + 13 * SLOT + w * 64;
  auto part = [&](int t) { return (t >> 4) ^ w; };
  auto load = [&](int t, uint32_t sl) {
    mbar_expect_tx(bar + sl * 8, t == 0 ? SLOT + 8192 : SLOT);
    tma_load_w(sb + ring + sl * SLOT, &P.mw[1], bar + sl * 8, part(t) * 1024 + 128 * j, t & 15);
  };
  if (!(warp & 3) && elect()) {
    if (w == 2) sts32(sb + OFF_EPOCH, atomicAdd(&g_ctr, 1u) / NCTA + 1u);
    else {
      __nanosleep(D3);
#pragma unroll 1
      for (int t = 0; t < 5; t++) {
        mbar_init(bar + t * 8, 1);
        asm volatile("fence.mbarrier_init.release.cluster;" ::: "memory");
        load(t, t);
      }
      tma_load_2d(sb + wp, &P.mwphi, bar, 0, 128 * j);
    }
  }
  __syncthreads();
  const unsigned tag = get_tag<false>(sb);
  if (w == 2) {
    int it = 0;
    while ((int)(ld_flag(&g_ctr) - tag * NCTA) < 0) { if (++it > (1 << 22)) __trap(); }
    return;
  }
  Ring r = {4, 1};
  float d[64] = {}, cs[32] = {};
  auto fold = [&]() {
    mbar_wait(bar + r.s * 8, r.ph);
    wgmma_fence();
#pragma unroll
    for (int q = 0; q < 8; q++)
      wgmma_ss_n32(reinterpret_cast<float (&)[16]>(d[16 * (q >> 1)]), desc_lo(SB + ring + r.s * SLOT, 16) + (q >> 2) * 512 + (q & 3) * 2, desc_lo(SB + wp, 512) + q * 64, q & 1);
    wgmma_commit();
  };
  const int row = (tid >> 5) * 16 + (lane >> 2);
#pragma unroll 1
  for (int t = -1; t < 32; t++) {
    uint32_t f[32];
#pragma unroll
    for (int i = 0; i < 32; i++) { f[i] = pack2(d[2 * i], d[2 * i + 1]); cs[i & 30] += d[2 * i]; cs[i | 1] += d[2 * i + 1]; }
    wg_bar(w);
    const uint32_t sl = r.s;
    if (t < 31) adv<5>(r);
    fold();
    if (!(warp & 3) && t >= 0 && t < 27 && elect()) load(t + 5, sl);
    if (part(t) == 0 && t >= 0) {
#pragma unroll
      for (int q = 0; q < 8; q++)
        g_wf[0][j][t & 15][(q >> 2) * 512 + (row + 8 * (q & 1)) * 8 + (((q & 2) * 2 + (lane & 3)) ^ (lane >> 2))] =
            make_uint4(f[4 * (q & 6) + (q & 1)], f[4 * (q & 6) + (q & 1) + 2], f[4 * (q & 6) + (q & 1) + 4], f[4 * (q & 6) + (q & 1) + 6]);
    }
    wgmma_wait<0>();
    fence_regs(d);
    if ((t & 15) == 15) {
      if (t >= 0) {
        const uint32_t red = sb + ring + 5 * SLOT;
#pragma unroll
        for (int i = 0; i < 8; i++) sts128(red + (tid >> 2) * 512 + (i >> 1) * 128 + (lane & 3) * 32 + (i & 1) * 16, __float_as_uint(cs[4 * i]), __float_as_uint(cs[4 * i + 1]), __float_as_uint(cs[4 * i + 2]), __float_as_uint(cs[4 * i + 3]));
        wg_bar(w);
        float a = 0.f;
#pragma unroll 4
        for (int i = 0; i < 32; i++) a += lds32f(red + i * 512 + tid * 4);
        g_cs[1][0][part(t) * 1024 + j * 128 + tid] = a;
        wg_bar(w);
        if (tid == 0) {
          fence_gpu();
          st_flag(&g_csflag[1][j][part(t)], tag);
        }
        __syncwarp();
      }
#pragma unroll
      for (int i = 0; i < 32; i++) cs[i] = 0.f;
    }
  }
}

__global__ void __launch_bounds__(NTHREADS, 1) fused_kernel(const __grid_constant__ Params P) {
  extern __shared__ __align__(1024) uint8_t smem_raw[];
  constexpr uint32_t sb = SB;
  const int tid = threadIdx.x;
  const unsigned vb = vblock();
  if (vb >= 128) { spare(P, sb, vb - 128); return; }
  const int warp = __shfl_sync(0xffffffffu, tid >> 5, 0);
  if (elect()) {
    if (warp == 11) { prefetch_map(&P.mx); prefetch_map(&P.mw[0]); if (smem_u32(smem_raw) != SB) __trap(); }
    if (warp < 8) {
#pragma unroll
      for (int i = 0; i < 8; i++) mbar_init(sb + OFF_BAR + (warp * 8 + i) * 8, warp == 2 || warp == 3 ? 2 : (warp == 4 ? 8 : 1));
    }
    asm volatile("fence.mbarrier_init.release.cluster;" ::: "memory");
    if (warp < 2) {
      const int j = cta_j(vb);
#pragma unroll 1
      for (int i = 0; i < (warp == 0 ? PRE_B : PRE_A); i++) {
        const uint32_t bar = sb + BAR_FULLB + warp * 64 + i * 8;
        mbar_expect_tx(bar, SLOT);
        if (warp == 0) tma_load_w(sb + OFF_B + i * SLOT, &P.mw[0], bar, 1024 + (i & 1) * 1024 + 128 * j, kv_order(i >> 1, j, 0));
        else tma_load_3d(sb + OFF_A + i * SLOT, &P.mx, bar, kv_order(i, j, 0) * 64, cta_m(vb) * 64, 0);
      }
    }
  }
  if (tid == 0) TS(6, 0);
  __syncthreads();
  if (tid == 0) TS(6, 2);
  if (warp < 4) {
    reg_dealloc<PREGS>();
    if (warp & 2) helper(P, sb, warp & 1, vb);
    else if (warp & 1) a_loader(P, sb, vb);
    else b_producer(P, sb, vb);
  } else {
    reg_alloc<CREGS>();
    consumer(P, sb, (warp >> 2) - 1, vb);
  }
}

typedef CUresult (*EncodeFn)(CUtensorMap*, CUtensorMapDataType, cuuint32_t, void*, const cuuint64_t*, const cuuint64_t*,
                             const cuuint32_t*, const cuuint32_t*, CUtensorMapInterleave, CUtensorMapSwizzle,
                             CUtensorMapL2promotion, CUtensorMapFloatOOBfill);

void encode(EncodeFn fn, CUtensorMap* m, const void* ptr, int rank, const cuuint64_t* dims, const cuuint64_t* strides,
            const cuuint32_t* box, CUtensorMapSwizzle swz) {
  const cuuint32_t es[5] = {1, 1, 1, 1, 1};
  fn(m, CU_TENSOR_MAP_DATA_TYPE_BFLOAT16, rank, const_cast<void*>(ptr), dims, strides, box, es, CU_TENSOR_MAP_INTERLEAVE_NONE,
     swz, CU_TENSOR_MAP_L2_PROMOTION_L2_256B, CU_TENSOR_MAP_FLOAT_OOB_FILL_NONE);
}
void encode_w(EncodeFn fn, CUtensorMap* m, const void* ptr, int ncols, bool perm) {
  const cuuint64_t p = (cuuint64_t)ncols * 2, d[5] = {(cuuint64_t)ncols, 2, 4, 4, 32}, s[4] = {p, (perm ? 8 : 2) * p, (perm ? 2 : 8) * p, 32 * p};
  const cuuint32_t box[5] = {64, 2, 4, 4, 2};
  encode(fn, m, ptr, 5, d, s, box, CU_TENSOR_MAP_SWIZZLE_128B);
}

void encode_cs(EncodeFn fn, CUtensorMap* m, const void* ptr, int ncols) {
  const cuuint64_t d[2] = {(cuuint64_t)ncols, 1024}, s[1] = {(cuuint64_t)ncols * 2};
  const cuuint32_t box[2] = {32, 64};
  encode(fn, m, ptr, 2, d, s, box, CU_TENSOR_MAP_SWIZZLE_NONE);
}

}

extern "C" void kernel_launch(void* const* d_in, const int* in_sizes, int n_in, void* d_out, int out_size) {
  (void)in_sizes; (void)n_in; (void)out_size;
  void* fnp = nullptr;
  cudaDriverEntryPointQueryResult q;
  cudaGetDriverEntryPoint("cuTensorMapEncodeTiled", &fnp, cudaEnableDefault, &q);
  EncodeFn fn = (EncodeFn)fnp;
  Params P;
  {
    const cuuint64_t dims[3] = {1024, 1024, 2}, strides[2] = {4096, 2048};
    const cuuint32_t box[3] = {64, 64, 2};
    encode(fn, &P.mx, d_in[0], 3, dims, strides, box, CU_TENSOR_MAP_SWIZZLE_128B);
  }
  P.out = (uint4*)d_out;
  encode_w(fn, &P.mw[0], d_in[1], 3072, false);
  encode_w(fn, &P.mw[1], d_in[4], 3072, true);
  encode_w(fn, &P.mw[2], d_in[1], 3072, true);
  encode_w(fn, &P.mwo[0], d_in[2], 1024, true);
  encode_w(fn, &P.mwo[1], d_in[6], 1024, false);
  encode_cs(fn, &P.mcs[0], d_in[1], 3072);
  encode_cs(fn, &P.mcs[1], d_in[4], 3072);
  {
    const cuuint64_t dims[2] = {32, 1024}, strides[1] = {64};
    const cuuint32_t box[2] = {32, 128};
    encode(fn, &P.mwphi, d_in[5], 2, dims, strides, box, CU_TENSOR_MAP_SWIZZLE_64B);
  }
  cudaFuncSetAttribute(fused_kernel, cudaFuncAttributeMaxDynamicSharedMemorySize, SMEM_BYTES);
  fused_kernel<<<NCTA, NTHREADS, SMEM_BYTES, cudaStreamPerThread>>>(P);
}
```

```cpp
#include <cuda_runtime.h>
#include <cuda_bf16.h>
#include <cuda.h>
#include <stdint.h>

namespace {

__device__ __forceinline__ void wgmma_ss_n256(float (&d)[128], uint32_t da, uint32_t ha, uint32_t db, int sd) {
  asm volatile("{\n.reg .pred p;\n.reg .b64 a, b;\nsetp.ne.b32 p, %130, 0;\nmov.b64 a, {%128, %131};\nmov.b64 b, {%129, 0x40000040};\n"
    "wgmma.mma_async.sync.aligned.m64n256k16.f32.bf16.bf16 {%0,%1,%2,%3,%4,%5,%6,%7,%8,%9,%10,%11,%12,%13,%14,%15,%16,%17,%18,%19,%20,%21,%22,%23,%24,%25,%26,%27,%28,%29,%30,%31,%32,%33,%34,%35,%36,%37,%38,%39,%40,%41,%42,%43,%44,%45,%46,%47,%48,%49,%50,%51,%52,%53,%54,%55,%56,%57,%58,%59,%60,%61,%62,%63,%64,%65,%66,%67,%68,%69,%70,%71,%72,%73,%74,%75,%76,%77,%78,%79,%80,%81,%82,%83,%84,%85,%86,%87,%88,%89,%90,%91,%92,%93,%94,%95,%96,%97,%98,%99,%100,%101,%102,%103,%104,%105,%106,%107,%108,%109,%110,%111,%112,%113,%114,%115,%116,%117,%118,%119,%120,%121,%122,%123,%124,%125,%126,%127}, a, b, p, 1, 1, 0, 1;\n}\n"
    : "+f"(d[0]),"+f"(d[1]),"+f"(d[2]),"+f"(d[3]),"+f"(d[4]),"+f"(d[5]),"+f"(d[6]),"+f"(d[7]),"+f"(d[8]),"+f"(d[9]),"+f"(d[10]),"+f"(d[11]),"+f"(d[12]),"+f"(d[13]),"+f"(d[14]),"+f"(d[15]),"+f"(d[16]),"+f"(d[17]),"+f"(d[18]),"+f"(d[19]),"+f"(d[20]),"+f"(d[21]),"+f"(d[22]),"+f"(d[23]),"+f"(d[24]),"+f"(d[25]),"+f"(d[26]),"+f"(d[27]),"+f"(d[28]),"+f"(d[29]),"+f"(d[30]),"+f"(d[31]),"+f"(d[32]),"+f"(d[33]),"+f"(d[34]),"+f"(d[35]),"+f"(d[36]),"+f"(d[37]),"+f"(d[38]),"+f"(d[39]),"+f"(d[40]),"+f"(d[41]),"+f"(d[42]),"+f"(d[43]),"+f"(d[44]),"+f"(d[45]),"+f"(d[46]),"+f"(d[47]),"+f"(d[48]),"+f"(d[49]),"+f"(d[50]),"+f"(d[51]),"+f"(d[52]),"+f"(d[53]),"+f"(d[54]),"+f"(d[55]),"+f"(d[56]),"+f"(d[57]),"+f"(d[58]),"+f"(d[59]),"+f"(d[60]),"+f"(d[61]),"+f"(d[62]),"+f"(d[63]),"+f"(d[64]),"+f"(d[65]),"+f"(d[66]),"+f"(d[67]),"+f"(d[68]),"+f"(d[69]),"+f"(d[70]),"+f"(d[71]),"+f"(d[72]),"+f"(d[73]),"+f"(d[74]),"+f"(d[75]),"+f"(d[76]),"+f"(d[77]),"+f"(d[78]),"+f"(d[79]),"+f"(d[80]),"+f"(d[81]),"+f"(d[82]),"+f"(d[83]),"+f"(d[84]),"+f"(d[85]),"+f"(d[86]),"+f"(d[87]),"+f"(d[88]),"+f"(d[89]),"+f"(d[90]),"+f"(d[91]),"+f"(d[92]),"+f"(d[93]),"+f"(d[94]),"+f"(d[95]),"+f"(d[96]),"+f"(d[97]),"+f"(d[98]),"+f"(d[99]),"+f"(d[100]),"+f"(d[101]),"+f"(d[102]),"+f"(d[103]),"+f"(d[104]),"+f"(d[105]),"+f"(d[106]),"+f"(d[107]),"+f"(d[108]),"+f"(d[109]),"+f"(d[110]),"+f"(d[111]),"+f"(d[112]),"+f"(d[113]),"+f"(d[114]),"+f"(d[115]),"+f"(d[116]),"+f"(d[117]),"+f"(d[118]),"+f"(d[119]),"+f"(d[120]),"+f"(d[121]),"+f"(d[122]),"+f"(d[123]),"+f"(d[124]),"+f"(d[125]),"+f"(d[126]),"+f"(d[127])
    : "r"(da), "r"(db), "r"(sd), "r"(ha));
}
__device__ __forceinline__ void wgmma_ss_n128(float (&d)[64], uint32_t da, uint32_t ha, uint32_t db, int sd) {
  asm volatile("{\n.reg .pred p;\n.reg .b64 a, b;\nsetp.ne.b32 p, %66, 0;\nmov.b64 a, {%64, %67};\nmov.b64 b, {%65, 0x40000040};\n"
    "wgmma.mma_async.sync.aligned.m64n128k16.f32.bf16.bf16 {%0,%1,%2,%3,%4,%5,%6,%7,%8,%9,%10,%11,%12,%13,%14,%15,%16,%17,%18,%19,%20,%21,%22,%23,%24,%25,%26,%27,%28,%29,%30,%31,%32,%33,%34,%35,%36,%37,%38,%39,%40,%41,%42,%43,%44,%45,%46,%47,%48,%49,%50,%51,%52,%53,%54,%55,%56,%57,%58,%59,%60,%61,%62,%63}, a, b, p, 1, 1, 0, 1;\n}\n"
    : "+f"(d[0]),"+f"(d[1]),"+f"(d[2]),"+f"(d[3]),"+f"(d[4]),"+f"(d[5]),"+f"(d[6]),"+f"(d[7]),"+f"(d[8]),"+f"(d[9]),"+f"(d[10]),"+f"(d[11]),"+f"(d[12]),"+f"(d[13]),"+f"(d[14]),"+f"(d[15]),"+f"(d[16]),"+f"(d[17]),"+f"(d[18]),"+f"(d[19]),"+f"(d[20]),"+f"(d[21]),"+f"(d[22]),"+f"(d[23]),"+f"(d[24]),"+f"(d[25]),"+f"(d[26]),"+f"(d[27]),"+f"(d[28]),"+f"(d[29]),"+f"(d[30]),"+f"(d[31]),"+f"(d[32]),"+f"(d[33]),"+f"(d[34]),"+f"(d[35]),"+f"(d[36]),"+f"(d[37]),"+f"(d[38]),"+f"(d[39]),"+f"(d[40]),"+f"(d[41]),"+f"(d[42]),"+f"(d[43]),"+f"(d[44]),"+f"(d[45]),"+f"(d[46]),"+f"(d[47]),"+f"(d[48]),"+f"(d[49]),"+f"(d[50]),"+f"(d[51]),"+f"(d[52]),"+f"(d[53]),"+f"(d[54]),"+f"(d[55]),"+f"(d[56]),"+f"(d[57]),"+f"(d[58]),"+f"(d[59]),"+f"(d[60]),"+f"(d[61]),"+f"(d[62]),"+f"(d[63])
    : "r"(da), "r"(db), "r"(sd), "r"(ha));
}
__device__ __forceinline__ void wgmma_ss_n40_tt(float (&d)[20], uint32_t da, uint32_t db, int sd) {
  asm volatile("{\n.reg .pred p;\n.reg .b64 a, b;\nsetp.ne.b32 p, %22, 0;\nmov.b64 a, {%20, 0x40000040};\nmov.b64 b, {%21, 0x8};\n"
    "wgmma.mma_async.sync.aligned.m64n40k16.f32.bf16.bf16 {%0,%1,%2,%3,%4,%5,%6,%7,%8,%9,%10,%11,%12,%13,%14,%15,%16,%17,%18,%19}, a, b, p, 1, 1, 1, 1;\n}\n"
    : "+f"(d[0]),"+f"(d[1]),"+f"(d[2]),"+f"(d[3]),"+f"(d[4]),"+f"(d[5]),"+f"(d[6]),"+f"(d[7]),"+f"(d[8]),"+f"(d[9]),"+f"(d[10]),"+f"(d[11]),"+f"(d[12]),"+f"(d[13]),"+f"(d[14]),"+f"(d[15]),"+f"(d[16]),"+f"(d[17]),"+f"(d[18]),"+f"(d[19])
    : "r"(da), "r"(db), "r"(sd));
}
__device__ __forceinline__ void wgmma_ss_n32(float (&d)[16], uint32_t da, uint32_t db, int sd) {
  asm volatile("{\n.reg .pred p;\n.reg .b64 a, b;\nsetp.ne.b32 p, %18, 0;\nmov.b64 a, {%16, 0x40000040};\nmov.b64 b, {%17, 0x80000020};\n"
    "wgmma.mma_async.sync.aligned.m64n32k16.f32.bf16.bf16 {%0,%1,%2,%3,%4,%5,%6,%7,%8,%9,%10,%11,%12,%13,%14,%15}, a, b, p, 1, 1, 0, 1;\n}\n"
    : "+f"(d[0]),"+f"(d[1]),"+f"(d[2]),"+f"(d[3]),"+f"(d[4]),"+f"(d[5]),"+f"(d[6]),"+f"(d[7]),"+f"(d[8]),"+f"(d[9]),"+f"(d[10]),"+f"(d[11]),"+f"(d[12]),"+f"(d[13]),"+f"(d[14]),"+f"(d[15])
    : "r"(da), "r"(db), "r"(sd));
}
__device__ __forceinline__ void wgmma_rs_n40(float (&d)[20], uint32_t a0, uint32_t a1, uint32_t a2, uint32_t a3, uint32_t db, int sd) {
  asm volatile("{\n.reg .pred p;\n.reg .b64 b;\nsetp.ne.b32 p, %25, 0;\nmov.b64 b, {%24, 0x10};\n"
    "wgmma.mma_async.sync.aligned.m64n40k16.f32.bf16.bf16 {%0,%1,%2,%3,%4,%5,%6,%7,%8,%9,%10,%11,%12,%13,%14,%15,%16,%17,%18,%19}, {%20,%21,%22,%23}, b, p, 1, 1, 1;\n}\n"
    : "+f"(d[0]),"+f"(d[1]),"+f"(d[2]),"+f"(d[3]),"+f"(d[4]),"+f"(d[5]),"+f"(d[6]),"+f"(d[7]),"+f"(d[8]),"+f"(d[9]),"+f"(d[10]),"+f"(d[11]),"+f"(d[12]),"+f"(d[13]),"+f"(d[14]),"+f"(d[15]),"+f"(d[16]),"+f"(d[17]),"+f"(d[18]),"+f"(d[19])
    : "r"(a0), "r"(a1), "r"(a2), "r"(a3), "r"(db), "r"(sd));
}
__device__ __forceinline__ void wgmma_r1_n256(float (&d)[128], uint32_t da, uint32_t db, int sd) {
  asm volatile("{\n.reg .pred p;\n.reg .b64 a, b;\nsetp.ne.b32 p, %130, 0;\nmov.b64 a, {%128, 0x8};\nmov.b64 b, {%129, 0x6};\n"
    "wgmma.mma_async.sync.aligned.m64n256k16.f32.bf16.bf16 {%0,%1,%2,%3,%4,%5,%6,%7,%8,%9,%10,%11,%12,%13,%14,%15,%16,%17,%18,%19,%20,%21,%22,%23,%24,%25,%26,%27,%28,%29,%30,%31,%32,%33,%34,%35,%36,%37,%38,%39,%40,%41,%42,%43,%44,%45,%46,%47,%48,%49,%50,%51,%52,%53,%54,%55,%56,%57,%58,%59,%60,%61,%62,%63,%64,%65,%66,%67,%68,%69,%70,%71,%72,%73,%74,%75,%76,%77,%78,%79,%80,%81,%82,%83,%84,%85,%86,%87,%88,%89,%90,%91,%92,%93,%94,%95,%96,%97,%98,%99,%100,%101,%102,%103,%104,%105,%106,%107,%108,%109,%110,%111,%112,%113,%114,%115,%116,%117,%118,%119,%120,%121,%122,%123,%124,%125,%126,%127}, a, b, p, 1, 1, 0, 1;\n}\n"
    : "+f"(d[0]),"+f"(d[1]),"+f"(d[2]),"+f"(d[3]),"+f"(d[4]),"+f"(d[5]),"+f"(d[6]),"+f"(d[7]),"+f"(d[8]),"+f"(d[9]),"+f"(d[10]),"+f"(d[11]),"+f"(d[12]),"+f"(d[13]),"+f"(d[14]),"+f"(d[15]),"+f"(d[16]),"+f"(d[17]),"+f"(d[18]),"+f"(d[19]),"+f"(d[20]),"+f"(d[21]),"+f"(d[22]),"+f"(d[23]),"+f"(d[24]),"+f"(d[25]),"+f"(d[26]),"+f"(d[27]),"+f"(d[28]),"+f"(d[29]),"+f"(d[30]),"+f"(d[31]),"+f"(d[32]),"+f"(d[33]),"+f"(d[34]),"+f"(d[35]),"+f"(d[36]),"+f"(d[37]),"+f"(d[38]),"+f"(d[39]),"+f"(d[40]),"+f"(d[41]),"+f"(d[42]),"+f"(d[43]),"+f"(d[44]),"+f"(d[45]),"+f"(d[46]),"+f"(d[47]),"+f"(d[48]),"+f"(d[49]),"+f"(d[50]),"+f"(d[51]),"+f"(d[52]),"+f"(d[53]),"+f"(d[54]),"+f"(d[55]),"+f"(d[56]),"+f"(d[57]),"+f"(d[58]),"+f"(d[59]),"+f"(d[60]),"+f"(d[61]),"+f"(d[62]),"+f"(d[63]),"+f"(d[64]),"+f"(d[65]),"+f"(d[66]),"+f"(d[67]),"+f"(d[68]),"+f"(d[69]),"+f"(d[70]),"+f"(d[71]),"+f"(d[72]),"+f"(d[73]),"+f"(d[74]),"+f"(d[75]),"+f"(d[76]),"+f"(d[77]),"+f"(d[78]),"+f"(d[79]),"+f"(d[80]),"+f"(d[81]),"+f"(d[82]),"+f"(d[83]),"+f"(d[84]),"+f"(d[85]),"+f"(d[86]),"+f"(d[87]),"+f"(d[88]),"+f"(d[89]),"+f"(d[90]),"+f"(d[91]),"+f"(d[92]),"+f"(d[93]),"+f"(d[94]),"+f"(d[95]),"+f"(d[96]),"+f"(d[97]),"+f"(d[98]),"+f"(d[99]),"+f"(d[100]),"+f"(d[101]),"+f"(d[102]),"+f"(d[103]),"+f"(d[104]),"+f"(d[105]),"+f"(d[106]),"+f"(d[107]),"+f"(d[108]),"+f"(d[109]),"+f"(d[110]),"+f"(d[111]),"+f"(d[112]),"+f"(d[113]),"+f"(d[114]),"+f"(d[115]),"+f"(d[116]),"+f"(d[117]),"+f"(d[118]),"+f"(d[119]),"+f"(d[120]),"+f"(d[121]),"+f"(d[122]),"+f"(d[123]),"+f"(d[124]),"+f"(d[125]),"+f"(d[126]),"+f"(d[127])
    : "r"(da), "r"(db), "r"(sd));
}
__device__ __forceinline__ void wgmma_r1_n128(float (&d)[64], uint32_t da, uint32_t db, int sd) {
  asm volatile("{\n.reg .pred p;\n.reg .b64 a, b;\nsetp.ne.b32 p, %66, 0;\nmov.b64 a, {%64, 0x8};\nmov.b64 b, {%65, 0x6};\n"
    "wgmma.mma_async.sync.aligned.m64n128k16.f32.bf16.bf16 {%0,%1,%2,%3,%4,%5,%6,%7,%8,%9,%10,%11,%12,%13,%14,%15,%16,%17,%18,%19,%20,%21,%22,%23,%24,%25,%26,%27,%28,%29,%30,%31,%32,%33,%34,%35,%36,%37,%38,%39,%40,%41,%42,%43,%44,%45,%46,%47,%48,%49,%50,%51,%52,%53,%54,%55,%56,%57,%58,%59,%60,%61,%62,%63}, a, b, p, 1, 1, 0, 1;\n}\n"
    : "+f"(d[0]),"+f"(d[1]),"+f"(d[2]),"+f"(d[3]),"+f"(d[4]),"+f"(d[5]),"+f"(d[6]),"+f"(d[7]),"+f"(d[8]),"+f"(d[9]),"+f"(d[10]),"+f"(d[11]),"+f"(d[12]),"+f"(d[13]),"+f"(d[14]),"+f"(d[15]),"+f"(d[16]),"+f"(d[17]),"+f"(d[18]),"+f"(d[19]),"+f"(d[20]),"+f"(d[21]),"+f"(d[22]),"+f"(d[23]),"+f"(d[24]),"+f"(d[25]),"+f"(d[26]),"+f"(d[27]),"+f"(d[28]),"+f"(d[29]),"+f"(d[30]),"+f"(d[31]),"+f"(d[32]),"+f"(d[33]),"+f"(d[34]),"+f"(d[35]),"+f"(d[36]),"+f"(d[37]),"+f"(d[38]),"+f"(d[39]),"+f"(d[40]),"+f"(d[41]),"+f"(d[42]),"+f"(d[43]),"+f"(d[44]),"+f"(d[45]),"+f"(d[46]),"+f"(d[47]),"+f"(d[48]),"+f"(d[49]),"+f"(d[50]),"+f"(d[51]),"+f"(d[52]),"+f"(d[53]),"+f"(d[54]),"+f"(d[55]),"+f"(d[56]),"+f"(d[57]),"+f"(d[58]),"+f"(d[59]),"+f"(d[60]),"+f"(d[61]),"+f"(d[62]),"+f"(d[63])
    : "r"(da), "r"(db), "r"(sd));
}

__device__ __forceinline__ uint32_t smem_u32(const void* p) { return (uint32_t)__cvta_generic_to_shared(p); }
__device__ __forceinline__ void mbar_init(uint32_t bar, uint32_t cnt) { asm volatile("mbarrier.init.shared::cta.b64 [%0], %1;" ::"r"(bar), "r"(cnt)); }
__device__ __forceinline__ void mbar_expect_tx(uint32_t bar, uint32_t bytes) { asm volatile("mbarrier.arrive.expect_tx.shared::cta.b64 _, [%0], %1;" ::"r"(bar), "r"(bytes) : "memory"); }
__device__ __forceinline__ void mbar_arrive(uint32_t bar) { asm volatile("mbarrier.arrive.shared::cta.b64 _, [%0];" ::"r"(bar) : "memory"); }
__device__ __forceinline__ void mbar_arrive_n(uint32_t bar, uint32_t n) { asm volatile("mbarrier.arrive.shared::cta.b64 _, [%0], %1;" ::"r"(bar), "r"(n) : "memory"); }
__device__ __forceinline__ void mbar_wait(uint32_t bar, uint32_t parity) {
  asm volatile("{\n.reg .pred p;\nLAB_WAIT:\nmbarrier.try_wait.parity.shared::cta.b64 p, [%0], %1;\n@p bra DONE;\nbra LAB_WAIT;\nDONE:\n}" ::"r"(bar), "r"(parity) : "memory");
}
__device__ __forceinline__ void mbar_wait2(uint32_t a, uint32_t pa, uint32_t b, uint32_t pb) {
  asm volatile("{\n.reg .pred p, q;\nLAB_WAIT:\nmbarrier.try_wait.parity.shared::cta.b64 p, [%0], %1;\nmbarrier.try_wait.parity.shared::cta.b64 q, [%2], %3;\n"
               "and.pred p, p, q;\n@p bra DONE;\nbra LAB_WAIT;\nDONE:\n}" ::"r"(a), "r"(pa), "r"(b), "r"(pb) : "memory");
}
__device__ __forceinline__ void mbar_wait3(uint32_t a, uint32_t pa, uint32_t b, uint32_t pb) {
  asm volatile("{\n.reg .pred p, q, r;\nLAB_WAIT:\nmbarrier.try_wait.parity.shared::cta.b64 p, [%0], %1;\nmbarrier.try_wait.parity.shared::cta.b64 q, [%2], %3;\n"
               "mbarrier.try_wait.parity.shared::cta.b64 r, [%2+8], %3;\nand.pred p, p, q;\nand.pred p, p, r;\n@p bra DONE;\nbra LAB_WAIT;\nDONE:\n}" ::"r"(a), "r"(pa), "r"(b), "r"(pb) : "memory");
}
__device__ __forceinline__ bool mbar_probe2(uint32_t a, uint32_t pa, uint32_t b, uint32_t pb) {
  uint32_t ok;
  asm volatile("{\n.reg .pred p, q;\nmbarrier.test_wait.parity.shared::cta.b64 p, [%1], %2;\nmbarrier.test_wait.parity.shared::cta.b64 q, [%3], %4;\n"
               "and.pred p, p, q;\nselp.u32 %0, 1, 0, p;\n}" : "=r"(ok) : "r"(a), "r"(pa), "r"(b), "r"(pb) : "memory");
  return ok != 0;
}
__device__ __forceinline__ void tma_load_3d(uint32_t dst, const CUtensorMap* tm, uint32_t bar, int c0, int c1, int c2) {
  asm volatile("cp.async.bulk.tensor.3d.shared::cluster.global.mbarrier::complete_tx::bytes [%0], [%1, {%3, %4, %5}], [%2];"
               ::"r"(dst), "l"(tm), "r"(bar), "r"(c0), "r"(c1), "r"(c2) : "memory");
}
__device__ __forceinline__ void tma_load_2d(uint32_t dst, const CUtensorMap* tm, uint32_t bar, int c0, int c1) {
  asm volatile("cp.async.bulk.tensor.2d.shared::cluster.global.mbarrier::complete_tx::bytes [%0], [%1, {%3, %4}], [%2];"
               ::"r"(dst), "l"(tm), "r"(bar), "r"(c0), "r"(c1) : "memory");
}
__device__ __forceinline__ void tma_load_w(uint32_t dst, const CUtensorMap* tm, uint32_t bar, int col, int kb) {
#pragma unroll
  for (int q = 0; q < 2; q++)
    asm volatile("cp.async.bulk.tensor.5d.shared::cluster.global.mbarrier::complete_tx::bytes [%0], [%1, {%3, %4, %4, %4, %5}], [%2];"
                 ::"r"(dst + q * 8192), "l"(tm), "r"(bar), "r"(col + q * 64), "r"(0), "r"(2 * kb) : "memory");
}
__device__ __forceinline__ void tma_prefetch_w(const CUtensorMap* tm, int col, int kb) {
#pragma unroll
  for (int q = 0; q < 2; q++)
    asm volatile("cp.async.bulk.prefetch.tensor.5d.L2.global [%0, {%1, %2, %2, %2, %3}];" ::"l"(tm), "r"(col + q * 64), "r"(0), "r"(2 * kb) : "memory");
}
__device__ __forceinline__ void bulk_load(uint32_t dst, const void* g, uint32_t bytes, uint32_t bar) {
  asm volatile("cp.async.bulk.shared::cluster.global.mbarrier::complete_tx::bytes [%0], [%1], %2, [%3];" ::"r"(dst), "l"(g), "r"(bytes), "r"(bar) : "memory");
}
__device__ __forceinline__ void prefetch_map(const CUtensorMap* tm) { asm volatile("prefetch.tensormap [%0];" ::"l"(tm) : "memory"); }
__device__ __forceinline__ void fence_async_smem() { asm volatile("fence.proxy.async.shared::cta;" ::: "memory"); }
__device__ __forceinline__ void fence_async_global() { asm volatile("fence.proxy.async.global;" ::: "memory"); }
__device__ __forceinline__ void fence_gpu() { asm volatile("fence.release.gpu;" ::: "memory"); }
__device__ __forceinline__ void st_flag(unsigned* p, unsigned v) { asm volatile("st.relaxed.gpu.global.u32 [%0], %1;" ::"l"(p), "r"(v) : "memory"); }
__device__ __forceinline__ unsigned ld_flag(const unsigned* p) { unsigned v; asm volatile("ld.relaxed.gpu.global.u32 %0, [%1];" : "=r"(v) : "l"(p) : "memory"); return v; }
__device__ __forceinline__ uint4 ldcg4(const void* p) { uint4 v; asm volatile("ld.global.cg.v4.u32 {%0,%1,%2,%3}, [%4];" : "=r"(v.x), "=r"(v.y), "=r"(v.z), "=r"(v.w) : "l"(p)); return v; }
__device__ __forceinline__ uint4 ld_pkt(const uint4* p) {
  uint4 v; asm volatile("{\n.reg .b128 t;\nld.relaxed.gpu.global.b128 t, [%4];\nmov.b128 {%0,%1,%2,%3}, t;\n}" : "=r"(v.x), "=r"(v.y), "=r"(v.z), "=r"(v.w) : "l"(p) : "memory"); return v;
}
__device__ __forceinline__ void st_pkt(uint4* p, uint32_t a, uint32_t b, uint32_t c, uint32_t tag) {
  asm volatile("{\n.reg .b128 t;\nmov.b128 t, {%1,%2,%3,%4};\nst.relaxed.gpu.global.b128 [%0], t;\n}" ::"l"(p), "r"(a), "r"(b), "r"(c), "r"(tag) : "memory");
}
__device__ __forceinline__ void st_v4(uint4* p, uint32_t a, uint32_t b, uint32_t c, uint32_t d) { asm volatile("st.relaxed.gpu.global.v4.u32 [%0], {%1,%2,%3,%4};" ::"l"(p), "r"(a), "r"(b), "r"(c), "r"(d) : "memory"); }
__device__ __forceinline__ void stg128(uint4* p, uint4 v) { asm volatile("st.global.v4.u32 [%0], {%1,%2,%3,%4};" ::"l"(p), "r"(v.x), "r"(v.y), "r"(v.z), "r"(v.w) : "memory"); }
__device__ __forceinline__ void sts32(uint32_t addr, uint32_t a) { asm volatile("st.shared.u32 [%0], %1;" ::"r"(addr), "r"(a) : "memory"); }
__device__ __forceinline__ void sts64(uint32_t addr, uint32_t a, uint32_t b) { asm volatile("st.shared.v2.u32 [%0], {%1,%2};" ::"r"(addr), "r"(a), "r"(b) : "memory"); }
__device__ __forceinline__ uint32_t mul2(uint32_t a, uint32_t b) { uint32_t r; asm("mul.rn.bf16x2 %0, %1, %2;" : "=r"(r) : "r"(a), "r"(b)); return r; }
__device__ __forceinline__ uint32_t add2(uint32_t a, uint32_t b) { uint32_t r; asm("add.rn.bf16x2 %0, %1, %2;" : "=r"(r) : "r"(a), "r"(b)); return r; }
__device__ __forceinline__ bool elect() {
  uint32_t p; asm volatile("{\n.reg .pred q;\nelect.sync _|q, 0xffffffff;\nselp.u32 %0, 1, 0, q;\n}" : "=r"(p)); return p != 0;
}
__device__ __forceinline__ void wgmma_fence() { asm volatile("wgmma.fence.sync.aligned;" ::: "memory"); }
__device__ __forceinline__ void wgmma_commit() { asm volatile("wgmma.commit_group.sync.aligned;" ::: "memory"); }
template <int N> __device__ __forceinline__ void wgmma_wait() { asm volatile("wgmma.wait_group.sync.aligned %0;" ::"n"(N) : "memory"); }
template <int N> __device__ __forceinline__ void fence_regs(float (&d)[N]) {
#pragma unroll
  for (int i = 0; i < N; i++) asm volatile("" : "+f"(d[i])::"memory");
}
template <int R> __device__ __forceinline__ void reg_alloc() { asm volatile("setmaxnreg.inc.sync.aligned.u32 %0;" ::"n"(R)); }
template <int R> __device__ __forceinline__ void reg_dealloc() { asm volatile("setmaxnreg.dec.sync.aligned.u32 %0;" ::"n"(R)); }
__device__ __forceinline__ void wg_bar(int w) { asm volatile("bar.sync %0, 128;" ::"r"(w + 1) : "memory"); }
__device__ __forceinline__ constexpr uint32_t desc_lo(uint32_t addr, uint32_t lbo) { return (addr >> 4) + ((lbo >> 4) << 16); }
__device__ __forceinline__ uint32_t pack2(float lo, float hi) { uint32_t r; asm("cvt.rn.bf16x2.f32 %0, %1, %2;" : "=r"(r) : "f"(hi), "f"(lo)); return r; }
__device__ __forceinline__ float lo16(uint32_t v) { return __uint_as_float(v << 16); }
__device__ __forceinline__ float hi16(uint32_t v) { return __uint_as_float(v & 0xFFFF0000u); }
__device__ __forceinline__ float ex2(float x) { float r; asm("ex2.approx.ftz.f32 %0, %1;" : "=f"(r) : "f"(x)); return r; }
__device__ __forceinline__ float rcp(float x) { float r; asm("rcp.approx.ftz.f32 %0, %1;" : "=f"(r) : "f"(x)); return r; }
__device__ __forceinline__ uint32_t movm(uint32_t a) { uint32_t d; asm volatile("movmatrix.sync.aligned.m8n8.trans.b16 %0, %1;" : "=r"(d) : "r"(a)); return d; }
__device__ __forceinline__ void stsm4(uint32_t addr, uint32_t a, uint32_t b, uint32_t c, uint32_t d) {
  asm volatile("stmatrix.sync.aligned.m8n8.x4.shared.b16 [%0], {%1,%2,%3,%4};" ::"r"(addr), "r"(a), "r"(b), "r"(c), "r"(d) : "memory");
}
__device__ __forceinline__ void ldsm4(uint32_t addr, uint32_t (&r)[4]) {
  asm volatile("ldmatrix.sync.aligned.m8n8.x4.shared.b16 {%0,%1,%2,%3}, [%4];" : "=r"(r[0]), "=r"(r[1]), "=r"(r[2]), "=r"(r[3]) : "r"(addr) : "memory");
}
__device__ __forceinline__ void sts128(uint32_t addr, uint32_t a, uint32_t b, uint32_t c, uint32_t d) {
  asm volatile("st.shared.v4.u32 [%0], {%1,%2,%3,%4};" ::"r"(addr), "r"(a), "r"(b), "r"(c), "r"(d) : "memory");
}
__device__ __forceinline__ void lds128(uint32_t addr, uint32_t& a, uint32_t& b, uint32_t& c, uint32_t& d) {
  asm volatile("ld.shared.v4.u32 {%0,%1,%2,%3}, [%4];" : "=r"(a), "=r"(b), "=r"(c), "=r"(d) : "r"(addr) : "memory");
}
__device__ __forceinline__ float lds32f(uint32_t addr) { float v; asm volatile("ld.shared.f32 %0, [%1];" : "=f"(v) : "r"(addr) : "memory"); return v; }
__device__ __forceinline__ float2 lds64f(uint32_t addr) { float2 v; asm volatile("ld.shared.v2.f32 {%0,%1}, [%2];" : "=f"(v.x), "=f"(v.y) : "r"(addr) : "memory"); return v; }
__device__ __forceinline__ void mma16816(float (&d)[4], uint32_t a0, uint32_t a1, uint32_t a2, uint32_t a3, uint32_t b0, uint32_t b1) {
  asm("mma.sync.aligned.m16n8k16.row.col.f32.bf16.bf16.f32 {%0,%1,%2,%3}, {%4,%5,%6,%7}, {%8,%9}, {%0,%1,%2,%3};"
      : "+f"(d[0]), "+f"(d[1]), "+f"(d[2]), "+f"(d[3]) : "r"(a0), "r"(a1), "r"(a2), "r"(a3), "r"(b0), "r"(b1));
}
__device__ __forceinline__ void mma1688(float (&d)[4], uint32_t a0, uint32_t a1, uint32_t b0) {
  asm("mma.sync.aligned.m16n8k8.row.col.f32.bf16.bf16.f32 {%0,%1,%2,%3}, {%4,%5}, {%6}, {%0,%1,%2,%3};"
      : "+f"(d[0]), "+f"(d[1]), "+f"(d[2]), "+f"(d[3]) : "r"(a0), "r"(a1), "r"(b0));
}

__device__ __forceinline__ float qsum(float v) { v += __shfl_xor_sync(0xffffffffu, v, 1); v += __shfl_xor_sync(0xffffffffu, v, 2); return v; }

constexpr int NCTA = 132;
#define NB_ 6
#define NA_ 5
constexpr int NB = NB_;
constexpr int NA = NA_;
constexpr uint32_t SLOT = 16384;
constexpr uint32_t SB = 1024;
constexpr uint32_t OFF_B = 0;
constexpr uint32_t OFF_A = NB * SLOT;
constexpr uint32_t OFF_S = OFF_A + NA * SLOT;
constexpr uint32_t OFF_T = OFF_S + 20480;
constexpr uint32_t OFF_CS = OFF_T + 24576;
constexpr uint32_t OFF_MR = OFF_CS + 4640;
constexpr uint32_t OFF_BAR = OFF_MR + 512;
constexpr uint32_t OFF_MA = OFF_S, OFF_MB = OFF_CS - 2048;
constexpr uint32_t BAR_FULLB = OFF_BAR;
constexpr uint32_t BAR_FULLA = BAR_FULLB + 64;
constexpr uint32_t BAR_EMPTYB = BAR_FULLA + 64;
constexpr uint32_t BAR_EMPTYA = BAR_EMPTYB + 64;
constexpr uint32_t BAR_SIGP = BAR_EMPTYA + 64;
constexpr uint32_t BAR_SIGT = BAR_SIGP + 24;
constexpr uint32_t BAR_STAT = BAR_SIGP + 64;
constexpr uint32_t BAR_HALO = BAR_STAT + 16;
constexpr uint32_t BAR_CS = BAR_HALO + 8;
constexpr uint32_t BAR_WPHI = BAR_CS + 16;
constexpr uint32_t BAR_KV = BAR_WPHI + 8;
constexpr uint32_t BAR_STG = BAR_KV + 16;
constexpr uint32_t BAR_EPOCH = BAR_STG + 48;
constexpr uint32_t BAR_LAND = OFF_BAR + 7 * 64;
constexpr uint32_t OFF_EPOCH = OFF_BAR + 8 * 64;
static_assert(BAR_EPOCH < BAR_LAND, "barriers");
constexpr uint32_t SMEM_BYTES = OFF_EPOCH + 8;
static_assert(SMEM_BYTES <= 232448 && NB % 2 == 0 && NB <= 8 && NA <= 6, "smem");

#define CREGS 224
#define PREGS 56
#define PF1 19
#define PF2 21
#define PRE_A 2
#define PRE_B 4
#define CSB 4
#define CSNEED 0xF001u
#define XR 1
#define PS0 1
#define PS1 3
#define PSW 0
#define SD 1000
#define KSPLIT 12
#define KEEP 16
#define NJ 3
#define KSL 1000
#define PSL 0
#define KVS 12
#define D2 2000
#define D3 1500
#define G0 50
#define MAP 3
#define PMAP 0x76321450u
#define ZO 0
#define XA 3
#define XS 1
#define CP 500
#define CD 0
#define S0 500
#define NS 2
#define XO 0
#define SW 2
#define SA 1
#define SB_ 4
#define XD 250
#define ND0 1
#define KC 8
#define CO 0
#define SE 500
#define PD 0
#define DEFER 3
#define DEFL 2
#define TSK 3
#define TSL 3
constexpr int NTHREADS = 384;

struct Params {
  CUtensorMap mx;
  CUtensorMap mw[3];
  CUtensorMap mwo[2];
  CUtensorMap mcs[2];
  CUtensorMap mwphi;
  uint4* out;
};

#define XBUF(L) 1
__device__ __align__(256) uint4 g_img[XBUF(3) + 1][16][16][1024];
__device__ __forceinline__ uint32_t img_code(bool isx, int L) { return isx ? (L & 1) | (L & 2) << 15 : ~L & 1; }
__device__ __forceinline__ uint32_t img_mask(bool isx) { return isx ? 0x10001u : 1u; }
__device__ __align__(256) uint4 g_wf[2][8][16][1024];
__device__ __align__(256) uint4 g_stats[16][2][8][32];
__device__ __align__(256) uint4 g_halo[16][8][2][256];
__device__ __align__(256) float g_cs[2][2][3072];
__device__ __align__(256) uint4 g_kvpart[8][16][2][544];
__device__ __align__(256) uint4 g_kvfin[8][16][80];
__device__ __align__(256) unsigned g_hint[16][32];
__device__ __align__(256) unsigned g_hflag[2][16][8][32];
__device__ __align__(256) unsigned g_kvfflag[2][8][2][32];
__device__ __align__(256) unsigned g_csflag[2][8][32];
__device__ __align__(256) unsigned g_kflag[8][32];
__device__ unsigned g_ctr;
__device__ __forceinline__ unsigned vblock() {
  unsigned s;
  asm volatile("mov.u32 %0, %%smid;" : "=r"(s));
  const unsigned r = s & 1;
  s >>= 1;
  const unsigned t = s - 32, q = (t * 37) >> 8;
  const unsigned hi = s < 60 ? 12 + (t - 7 * q) * 8 + q : (s < 62 ? s + 4 : s - 58);
  unsigned b = 2 * (s < 32 ? (s & 7) * 8 + (s >> 3) : hi) + r;
  if (b < 128) b = (b & 15) | ((PMAP >> ((b >> 4) * 4)) & 7) << 4;
  if (s >= 62) b = 8 + 4 * r + s - 62;
  unsigned n;
  asm volatile("mov.u32 %0, %%nsmid;" : "=r"(n));
  return __shfl_sync(0xffffffffu, n == NCTA ? b : blockIdx.x, 0);
}
#define TS(who, id) do {} while (0)
#define TSW(id) do {} while (0)

#define TSH(id) do {} while (0)
#define TSMASK 0xFFFF
#define TSL_(a) do { if ((TSMASK >> (a)) & 1) TSW((a) + L * 12); } while (0)
__device__ __forceinline__ int cta_m(unsigned b) { return ((b >> 2) & 12) | (b & 3); }
__device__ __forceinline__ int cta_j(unsigned b) { return ((b >> 2) & 3) | ((b >> 4) & 4); }
struct Ring { uint32_t s, ph; };
template <int N> __device__ __forceinline__ void adv(Ring& r) { if (++r.s == N) { r.s = 0; r.ph ^= 1; } }
template <int N> __device__ __forceinline__ void rewind2(Ring& r) { if (r.s < 2) { r.s += N - 2; r.ph ^= 1; } else r.s -= 2; }
__device__ __forceinline__ int other_tile(int t, int j) { return (t == (j | 4) ? 7 : t) ^ (~j & 4); }
__device__ __forceinline__ int o_order(int i, int j) {
  if (i < 2) return 2 * j + i;
  const int odd = i >= 9;
  return 2 * other_tile(i - 2 - 7 * odd, j) + odd;
}
__device__ __forceinline__ int kv_order(int i, int j, int L) { return L > 0 ? o_order(i, j) : (i + 14 + 2 * (j & 4)) & 15; }

__device__ __forceinline__ unsigned poll_flags(const unsigned* f, int n, unsigned need, unsigned tag) {
  const int lane = threadIdx.x & 31;
  unsigned mask; int it = 0;
  do {
    unsigned v = lane < n ? ld_flag(f + lane) : 0u;
    mask = __ballot_sync(0xffffffffu, lane < n && v == tag);
    if (++it > (1 << 22)) __trap();
  } while ((mask & need) != need);
  fence_async_global();
  return mask;
}
template <bool WAIT = true>
__device__ __forceinline__ unsigned get_tag(uint32_t sb) {
  if (WAIT) mbar_wait(sb + BAR_EPOCH, 0);
  unsigned t; asm volatile("ld.shared.u32 %0, [%1];" : "=r"(t) : "r"(sb + OFF_EPOCH) : "memory");
  return t;
}

__device__ __forceinline__ int lane_id() { int l; asm volatile("mov.u32 %0, %%laneid;" : "=r"(l)); return l; }
__device__ __forceinline__ unsigned seq4(unsigned tag, int L) { return 8u | ((tag & 1u) << 2) | (unsigned)L; }
constexpr float LOG2E = 1.4426950408889634f;

__device__ __forceinline__ float bb_fence(int never, const void* p = &g_ctr, uint32_t keep = 0) {
  while (never < 0) never = ld_flag((const unsigned*)p) + keep;
  return __int_as_float(never >> 30);
}
__device__ __forceinline__ uint32_t solid(uint32_t v) { return __shfl_sync(0xffffffffu, v, threadIdx.x & 31); }
template <class T> __device__ __forceinline__ T* solid(T* p) { return (T*)__shfl_sync(0xffffffffu, (unsigned long long)p, threadIdx.x & 31); }
constexpr uint32_t HA128 = 0x40000040u, HA64 = 0x80000040u;
struct Ctx {
  static constexpr uint32_t sb = SB;
  uint32_t ab, da0;
  int w, warp, lane, g, c;
  int goff;
  __device__ __forceinline__ int m() const { return goff >> 14; }
  __device__ __forceinline__ int j() const { return (goff >> 4) & 7; }
  bool elected;
  Ring ra, rb;
  uint32_t pa, pb;
  uint32_t ha, k2;
  uint32_t mrow, mxor, mhi;
  __device__ __forceinline__ uint32_t aslot(uint32_t s) const { return ab + s * SLOT; }
  __device__ __forceinline__ uint32_t fullA(uint32_t s) const { return sb + BAR_FULLA + s * 8; }
  __device__ __forceinline__ uint32_t fullB(uint32_t s) const { return sb + BAR_FULLB + s * 8; }
  __device__ __forceinline__ void releaseA(uint32_t s) const { if (elected) mbar_arrive(sb + BAR_EMPTYA + s * 8); }
  __device__ __forceinline__ void releaseB(uint32_t s) const { if (elected) mbar_arrive(sb + BAR_EMPTYB + s * 8); }
  __device__ __forceinline__ uint32_t maddr(uint32_t tile, uint32_t ch) const { return tile + mrow + (((ch + mhi) ^ mxor) << 4); }
  __device__ __forceinline__ uint32_t oo() const { return warp * 128 + g * 4 + (c ^ (g >> 1)); }
  __device__ __forceinline__ uint4* img(int b, int hp) const { return ip + (b * 256 + hp) * 1024; }
  uint4* ip;
  uint32_t so;
  __device__ __forceinline__ uint32_t held(int i) const { return ra.s + i < 2 ? ra.s + i + NA - 2 : ra.s + i - 2; }
};

template <int N, bool FIRST, bool O = true>
__device__ __forceinline__ void gemm_issue(float (&acc)[N / 2], Ctx& x, bool ready = false) {
  if (!ready) {
    if (N == 256) mbar_wait3(x.fullA(x.ra.s), x.ra.ph, x.fullB(x.rb.s), x.rb.ph);
    else mbar_wait2(x.fullA(x.ra.s), x.ra.ph, x.fullB(x.rb.s), x.rb.ph);
  }
  const uint32_t da = x.da0 + x.ra.s * (SLOT / 16), db = desc_lo(SB + OFF_B, 8192) + x.rb.s * (SLOT / 16);
  wgmma_fence();
#pragma unroll
  for (int k = 0; k < 4; k++) {
    const uint32_t a = da + (k >> 1) * (O ? 32 : x.k2) + (k & 1) * 2, ha = O ? HA64 : x.ha;
    if constexpr (N == 256) wgmma_ss_n256(acc, a, ha, db + 128 * k, !(FIRST && k == 0));
    else wgmma_ss_n128(acc, a, ha, db + 128 * k, !(FIRST && k == 0));
  }
  wgmma_commit();
}
template <int N>
__device__ __forceinline__ void gemm_next(Ctx& x) {
  x.pa = x.ra.s; x.pb = x.rb.s;
  if (N == 256) x.rb.s++;
  adv<NA>(x.ra); adv<NB>(x.rb);
}
template <int N>
__device__ __forceinline__ void gemm_release(Ctx& x, bool relA) {
  if (relA) x.releaseA(x.pa);
  x.releaseB(x.pb);
  if (N == 256) x.releaseB(x.pb + 1);
}
template <int N>
__device__ __forceinline__ void gemm_retire(Ctx& x, bool relA) { wgmma_wait<1>(); gemm_release<N>(x, relA); gemm_next<N>(x); }
template <bool O = true>
__device__ __forceinline__ void gemm_run(float (&acc)[64], Ctx& x, int n, int hold, int n4 = 0) {
  bool ready = false;
#pragma unroll 1
  for (; n > 0; n--) {
    gemm_issue<128, false, O>(acc, x, ready);
    const uint32_t pa = x.pa, pb = x.pb;
    gemm_next<128>(x);
    ready = mbar_probe2(x.fullA(x.ra.s), x.ra.ph, x.fullB(x.rb.s), x.rb.ph);
    wgmma_wait<1>();
    if (n > hold) x.releaseA(pa);
    x.releaseB(pb);
  }
}
__device__ __forceinline__ void gemm_end(float (&acc)[64], Ctx& x) { wgmma_wait<0>(); fence_regs(acc); gemm_release<128>(x, false); }

__device__ __forceinline__ void rows_load(uint4* r, uint32_t tile, const Ctx& x) {
#pragma unroll
  for (int q = 0; q < 4; q++) {
    const uint32_t row = x.warp * 16 + 4 * q + (x.lane >> 3);
    lds128(tile + row * 128 + (((x.lane & 7) ^ (row & 7)) << 4), r[q].x, r[q].y, r[q].z, r[q].w);
  }
}
__device__ __forceinline__ void rows_store(const uint4* r, uint4* g) {
#pragma unroll
  for (int q = 0; q < 4; q++) stg128(g + q * 1024, r[q]);
}
__device__ __forceinline__ void publish(int id, const Ctx& x) { __syncwarp(); if (x.lane == 0) mbar_arrive(x.sb + BAR_SIGP + id * 8); }
__device__ __forceinline__ uint32_t img_tag(uint32_t v, bool isx, int L, const Ctx& x) {
  const uint32_t mk = ((x.lane ^ (x.warp * 4)) & 7) ? 0u : img_mask(isx);
  return (v & ~mk) | (img_code(isx, L) & mk);
}
__device__ __forceinline__ void img_tag(uint4 (&r)[4], bool isx, int L, const Ctx& x) {
#pragma unroll
  for (int q = 0; q < 4; q++) { uint32_t& v = q == 0 ? r[q].x : (q == 1 ? r[q].y : (q == 2 ? r[q].z : r[q].w)); v = img_tag(v, isx, L, x); }
}
__device__ __forceinline__ void img_store(const uint4 (&r)[4], uint4* g) {
#pragma unroll
  for (int q = 0; q < 4; q++) stg128(g + q * 32, r[q]);
}
__device__ __forceinline__ void img_sts(const uint4 (&r)[4], uint32_t tile, const Ctx& x) {
#pragma unroll
  for (int q = 0; q < 4; q++) sts128(tile + x.so + q * 512, r[q].x, r[q].y, r[q].z, r[q].w);
}
__device__ __forceinline__ void img_load(uint32_t (&v)[16], uint32_t tile, const Ctx& x) {
#pragma unroll
  for (int q = 0; q < 4; q++) lds128(tile + x.so + q * 512, v[4 * q], v[4 * q + 1], v[4 * q + 2], v[4 * q + 3]);
}
__device__ __forceinline__ void img_unpack(float* a, const uint32_t (&v)[16]) {
#pragma unroll
  for (int q = 0; q < 16; q++) { a[4 * (q & 7) + 2 * (q >> 3)] = lo16(v[q]); a[4 * (q & 7) + 2 * (q >> 3) + 1] = hi16(v[q]); }
}

template <int N>
__device__ __forceinline__ void stats_acc(const float* a, float (&t)[4]) {
#pragma unroll
  for (int i = 0; i < N; i++) { t[i & 2] += a[i]; t[(i & 2) + 1] = fmaf(a[i], a[i], t[(i & 2) + 1]); }
}
__device__ __forceinline__ void stats_send(float (&t)[4], int L, const Ctx& x) {
  const unsigned seq = seq4(get_tag<false>(x.sb), L);
#pragma unroll
  for (int q = 0; q < 4; q++) t[q] = qsum(t[q]);
  if (x.c == 0) st_pkt(&g_stats[x.m()][x.w][x.j()][x.warp * 8 + x.g], __float_as_uint(t[0]), __float_as_uint(t[1]), __float_as_uint(t[2]), (__float_as_uint(t[3]) & ~15u) | seq);
}
__device__ __forceinline__ void out_epilogue(const float (&acc)[64], uint4 (&r1)[4], float (&t)[4], uint4* g, int L, Ctx& x) {
  const uint32_t t0 = x.aslot(x.ra.s), t1 = x.aslot(x.ra.s + 1 == NA ? 0 : x.ra.s + 1);
  if (L == 3) {
#pragma unroll
    for (int p = 0; p < 8; p++) {
      stsm4(x.maddr(p < 4 ? t0 : t1, (p & 3) * 2), pack2(acc[8 * p], acc[8 * p + 1]), pack2(acc[8 * p + 2], acc[8 * p + 3]),
            pack2(acc[8 * p + 4], acc[8 * p + 5]), pack2(acc[8 * p + 6], acc[8 * p + 7]));
      if ((p & 3) == 3) { uint4 r[4]; __syncwarp(); rows_load(r, p < 4 ? t0 : t1, x); rows_store(r, g + (p >> 2) * 8); }
    }
  } else {
    auto pack16 = [&](uint4 (&r)[4], const float* a) {
#pragma unroll
      for (int q = 0; q < 4; q++) { const float* u = a + 16 * (q & 1) + (q & 2); r[q] = make_uint4(pack2(u[0], u[1]), pack2(u[4], u[5]), pack2(u[8], u[9]), pack2(u[12], u[13])); }
    };
    uint4 r0[4];
    pack16(r0, acc);
    img_tag(r0, true, L + 1, x);
    img_store(r0, x.img(XBUF(L + 1), 0));
    publish(1, x);
    const float z = bb_fence(x.goff);
    img_sts(r0, t0, x);
    pack16(r1, acc + 32);
    img_tag(r1, true, L + 1, x);
    img_sts(r1, t1, x);
    float u[4] = {z, z, z, z}, v[4] = {z, z, z, z};
    stats_acc<32>(acc, v);
    stats_acc<32>(acc + 32, u);
#pragma unroll
    for (int q = 0; q < 4; q++) t[q] = u[q] + v[q];
    mbar_wait2(x.fullB(x.rb.s), x.rb.ph, x.fullB(x.rb.s + 1), x.rb.ph);
    fence_async_smem();
    asm volatile("bar.sync %0, %1;" ::"r"(L == 1 ? x.w + 1 : 3), "r"(L == 1 ? 128 : 256) : "memory");
  }
}

struct Stats { float rstd0, rstd1; };
__device__ __forceinline__ Stats load_stats(int half, const Ctx& x) {
  const float2 u = lds64f(x.sb + OFF_MR + half * 256 + (x.warp * 8 + x.g) * 8);
  return {u.x, u.y};
}

template <int NH, int NK, class F>
__device__ __forceinline__ void hedgehog_scale(float* t, const Stats& st, const uint32_t* keep, F use) {
#pragma unroll
  for (int q = 0; q < 16 * NH; q++) t[q] *= ((q & 2) ? st.rstd1 : st.rstd0) * LOG2E;
  use();
  float m[4];
#pragma unroll
  for (int q = 0; q < 4 * NH; q++) {
    const float v = fmaxf(fmaxf(fabsf(t[4 * q]), fabsf(t[4 * q + 1])), fmaxf(fabsf(t[4 * q + 2]), fabsf(t[4 * q + 3])));
    m[q & 3] = q < 4 ? v : fmaxf(m[q & 3], v);
  }
  if (__builtin_expect(__any_sync(0xffffffffu, fmaxf(fmaxf(m[0], m[1]), fmaxf(m[2], m[3])) > 58.f), 0)) {
    float z[16 * NH + NK];
#pragma unroll
    for (int q = 0; q < 16 * NH + NK; q++) z[q] = q < 16 * NH ? t[q % (16 * NH)] : __uint_as_float(keep[q & 15]);
#pragma unroll 1
    for (int r = 0; r < 2 * NH; r++) {
      float hi = -INFINITY, lo = INFINITY;
#pragma unroll 1
      for (int i = 0; i < 16; i++) {
        const int k = (i & 6) * 2 + (i & 1) + (r & 1) * 2 + (r & 2) * 8;
        const float v = z[k];
        if (i < 8) { hi = fmaxf(hi, v); lo = fminf(lo, v); }
        else z[k] = v - fminf(fmaxf(v, lo), hi);
        if (i == 7) {
#pragma unroll 1
          for (int d = 1; d <= 2; d++) { hi = fmaxf(hi, __shfl_xor_sync(0xffffffffu, hi, d)); lo = fminf(lo, __shfl_xor_sync(0xffffffffu, lo, d)); }
          const float mid = 0.5f * hi + 0.5f * lo;
          hi = fmaxf(hi - 58.f, mid); lo = fminf(lo + 58.f, mid);
        }
      }
    }
#pragma unroll
    for (int q = 0; q < 16 * NH; q++) t[q] = z[q];
    use();
  }
}
__device__ __forceinline__ void dual_exp(const float* t, uint32_t (&f)[18], int never) {
  float e[KSPLIT];
#pragma unroll
  for (int q = 0; q < KSPLIT; q++) e[q] = ex2(q < 16 ? t[q] : -t[q & 15]);
  while (never < 0) {
#pragma unroll
    for (int i = 0; i < KSPLIT; i += 4) asm volatile("ld.shared.v4.f32 {%0,%1,%2,%3}, [%4];" : "=f"(e[i]), "=f"(e[i + 1]), "=f"(e[i + 2]), "=f"(e[i + 3]) : "r"(never + i) : "memory");
    never += __float_as_int(e[0]);
  }
#pragma unroll
  for (int q = 0; q < KSPLIT; q += 2) f[q >> 1] = pack2(e[q], e[q + 1]);
#pragma unroll
  for (int q = KSPLIT; q < 32; q += 2) f[q >> 1] = q < 16 ? pack2(ex2(t[q]), ex2(t[q + 1])) : pack2(ex2(-t[q & 15]), ex2(-t[(q & 15) + 1]));
#pragma unroll
  for (int sg = 0; sg < 2; sg++) {
    const uint32_t* u = f + 8 * sg;
    const uint32_t a = add2(add2(u[0], u[2]), add2(u[4], u[6])), b = add2(add2(u[1], u[3]), add2(u[5], u[7]));
    f[16 + sg] = add2(__byte_perm(a, b, 0x5410), __byte_perm(a, b, 0x7632));
  }
}
__device__ __forceinline__ void dual_exp_rcp(const float* t, uint32_t* f) {
#pragma unroll
  for (int q = 0; q < 8; q++) {
    const float a = ex2(t[2 * q]), b = ex2(t[2 * q + 1]), r = rcp(a * b);
    f[q] = pack2(a, b); f[8 + q] = pack2(r * b, r * a);
  }
}
__device__ __forceinline__ void cta_bar() { asm volatile("bar.sync 3, 256;" ::: "memory"); }

template <int N> __device__ __forceinline__ void pin(const uint32_t* v, uint32_t addr) {
#pragma unroll
  for (int i = 0; i < N; i += 4)
    asm volatile("{\n.reg .pred p;\nsetp.eq.u32 p, %0, 0;\n@p st.shared.v4.u32 [%0], {%1,%2,%3,%4};\n}" ::"r"(addr), "r"(v[i]), "r"(v[i + 1]), "r"(v[i + 2]), "r"(v[i + 3]) : "memory");
}

__device__ __forceinline__ void consumer(const Params& P, uint32_t sb, int w, unsigned vb) {
  Ctx x;
  x.w = w;
  x.ab = sb + OFF_A + w * 8192; x.da0 = desc_lo(SB + OFF_A, 16) + w * 512;
  x.lane = threadIdx.x & 31; x.warp = __shfl_sync(0xffffffffu, (threadIdx.x >> 5) & 3, 0); x.g = x.lane >> 2; x.c = x.lane & 3;
  x.goff = (cta_m(vb) * 128 + w) * 128 + cta_j(vb) * 16;
  asm volatile("" : "+r"(x.goff));
  x.elected = (threadIdx.x & 127) == 0;
  x.ra = {0, 0}; x.rb = {0, 0}; x.pa = x.pb = 0;
  {
    const uint32_t row = x.warp * 16 + (x.lane & 15);
    x.mrow = row * 128; x.mxor = row & 7; x.mhi = x.lane >> 4;
  }
  const int goff = x.goff;
  x.ip = solid(&g_img[0][x.m()][2 * x.j()][w * 512 + x.oo()]);
  x.so = solid(16 * x.oo());
  uint4 r1[4];
  float ts[4] = {0.f, 0.f, 0.f, 0.f};
#pragma unroll
  for (int i = 0; i < 4; i++) r1[i] = make_uint4(0, 0, 0, 0);
  TSW(0);
  mbar_wait3(x.fullA(0), 0, x.fullB(0), 0);
#pragma unroll 1
  for (int L = 0; L < 4; L++) {
    float acc[64];
    constexpr uint32_t dcs = desc_lo(SB + OFF_CS, 0);
    if ((L & 1) == 0) {
    float kv[128];
    x.ha = L ? HA64 : HA128; x.k2 = L ? 32 : 4;
    gemm_issue<256, true, false>(kv, x, true); gemm_next<256>(x);
    {
      int i = 1;
#pragma unroll 1
      for (int seg = L ? NS - 1 : 0; seg <= NS; seg++) {
        const int end = seg < NS ? (L == 0 ? 3 + SA * ((x.j() + SW * w) & 3) + SB_ * seg : XA + 1) : 14 + L;
#pragma unroll 1
        do {
          gemm_issue<256, false, false>(kv, x);
          gemm_retire<256>(x, true);
          i++;
          if (i == 5) TSL_(8);
          if (i == 11) TSL_(10);
        } while (i != end);
        if (seg < NS && L == 0) {
          uint32_t v[16];
          float a[32];
#pragma unroll
          for (int q = 0; q < 4; q++) ldsm4(x.maddr(x.aslot(x.pa), 2 * q), reinterpret_cast<uint32_t (&)[4]>(v[4 * q]));
#pragma unroll
          for (int q = 0; q < 16; q++) { a[2 * q] = lo16(v[q]); a[2 * q + 1] = hi16(v[q]); }
          stats_acc<32>(a, ts);
          fence_regs(ts);
          wg_bar(w);
        }
        if (seg == NS - 1) {
          if (L > 0) { img_store(r1, x.img(XBUF(L), 1)); publish(2, x); }
          mbar_wait(sb + BAR_EPOCH, 0);
          stats_send(ts, L, x);
        }
      }
    }
      const Ring kt = x.ra;
      if (L == 0) adv<NA>(x.ra);
#pragma unroll 1
      for (int h = L; h < 2; h++) {
        float d[16];
        mbar_wait2(x.fullA(kt.s), kt.ph, sb + BAR_WPHI, 0);
        wgmma_fence();
#pragma unroll
        for (int q = 0; q < 2; q++) wgmma_ss_n32(d, x.da0 + kt.s * (SLOT / 16) + h * 4 + q * 2, desc_lo(SB + OFF_S + 4096, 512) + w * 256 + h * 128 + q * 64, q);
        wgmma_commit();
        gemm_issue<256, false, false>(kv, x);
        gemm_retire<256>(x, true);
        if (h) x.releaseA(kt.s);
        fence_regs(d);
        uint4* dst = &g_wf[1][x.j()][x.m()][w * 512 + (x.warp * 16 + x.g) * 8 + ((h * 4 + x.c) ^ x.g)];
        dst[0] = make_uint4(pack2(d[0], d[1]), pack2(d[4], d[5]), pack2(d[8], d[9]), pack2(d[12], d[13]));
        dst[64] = make_uint4(pack2(d[2], d[3]), pack2(d[6], d[7]), pack2(d[10], d[11]), pack2(d[14], d[15]));
      }
      const uint32_t dm = desc_lo(SB + OFF_MA, 0) + w * 64;
      mbar_wait2(sb + BAR_STAT, 0, sb + BAR_CS, 0);
      wgmma_fence();
      wgmma_r1_n256(kv, dm, dcs + 96, 1);
      wgmma_commit();
      const Stats st = load_stats(w, x);
      mbar_wait2(x.fullA(x.ra.s), x.ra.ph, x.fullB(x.rb.s), x.rb.ph);
      wgmma_wait<0>();
      fence_regs(kv);
      gemm_release<256>(x, true);
      TSL_(2);
      uint32_t P0[32], P1[32], PH[32];
#pragma unroll
      for (int t = 0; t < 16; t++) { P0[t] = pack2(kv[4 * t] * st.rstd0, kv[4 * t + 1] * st.rstd0); P1[t] = pack2(kv[4 * t + 2] * st.rstd1, kv[4 * t + 3] * st.rstd1); }
      pin<16>(P0, x.mrow + 16);
      {
#pragma unroll
        for (int q = 0; q < 4; q++) sts128((x.warp < 3 ? sb + OFF_T + w * 12288 + x.warp * 4096 : sb + OFF_S + 16384 + w * 2048) + x.lane * 16 + q * 512, P1[4 * q], P1[4 * q + 1], P1[4 * q + 2], P1[4 * q + 3]);
      }
      wgmma_fence();
      wgmma_r1_n128(acc, dm, dcs, 0);
      gemm_issue<128, false, false>(acc, x, true); gemm_next<128>(x);
      TSL_(3);
#pragma unroll
      for (int s = 0; s < 4; s++) {
#pragma unroll
        for (int t = 16 + 8 * (s & 1); t < 24 + 8 * (s & 1); t++) {
          if (s < 2) P1[t] = movm(pack2(kv[4 * t + 2] * st.rstd1, kv[4 * t + 3] * st.rstd1));
          else P0[t] = movm(pack2(kv[4 * t] * st.rstd0, kv[4 * t + 1] * st.rstd0));
        }
        if (s < 3) { gemm_issue<128, false, false>(acc, x); gemm_retire<128>(x, true); }
        if (s == 1) {
          if (x.warp < 3) {
#pragma unroll
            for (int q = 4; q < 8; q++) sts128(sb + OFF_T + w * 12288 + x.warp * 4096 + x.lane * 16 + q * 512, P1[4 * q], P1[4 * q + 1], P1[4 * q + 2], P1[4 * q + 3]);
          } else {
            uint4* dst = &g_halo[x.m()][x.j()][w][x.lane];
#pragma unroll
            for (int q = 0; q < 8; q++) dst[q * 32] = make_uint4(P1[4 * q], P1[4 * q + 1], P1[4 * q + 2], P1[4 * q + 3]);
          }
          publish(3, x);
          gemm_issue<128, false, false>(acc, x);
          gemm_retire<128>(x, true);
        }
      }
      TSL_(4);
      gemm_run<false>(acc, x, 10, 0);
      gemm_issue<128, false, false>(acc, x);
      {
        wg_bar(w);
        uint32_t tr = sb + OFF_T + w * 12288 + (x.warp - 1) * 4096;
        if (x.warp == 0) {
          tr = x.m() > 0 ? sb + OFF_S + 8192 + w * 4096 : tr + 4096;
          if (x.m() > 0) mbar_wait(sb + BAR_HALO, L >> 1);
        }
#pragma unroll
        for (int q = 0; q < 8; q++) lds128(tr + x.lane * 16 + q * 512, PH[4 * q], PH[4 * q + 1], PH[4 * q + 2], PH[4 * q + 3]);
      }
      gemm_retire<128>(x, false);
      gemm_end(acc, x);
      TSL_(5);
      const bool first = (x.m() == 0) && (x.warp == 0);
      const bool hi0 = 2 * x.c > x.g, hi1 = 2 * x.c + 1 > x.g;
      const uint32_t mhi = (hi0 ? 0xFFFFu : 0u) | (hi1 ? 0xFFFF0000u : 0u);
      const float sc0 = st.rstd0 * (0.17677669529663687f * LOG2E), sc1 = st.rstd1 * (0.17677669529663687f * LOG2E);
#pragma unroll
      for (int hp = 0; hp < 2; hp++) {
        const uint32_t tile = x.aslot(x.held(hp));
        uint32_t px[2], py[2];
        float s[2][3][4];
#pragma unroll
        for (int u = 0; u < 2; u++) {
#pragma unroll
          for (int q = 0; q < 12; q++) s[u][q >> 2][q & 3] = 0.f;
#pragma unroll
          for (int ks = 0; ks < 2; ks++) {
            const int t = 8 * hp + 4 * u + 2 * ks;
            const uint32_t a0 = pack2(acc[4 * t], acc[4 * t + 1]), a1 = pack2(acc[4 * t + 2], acc[4 * t + 3]);
            const uint32_t a2 = pack2(acc[4 * t + 4], acc[4 * t + 5]), a3 = pack2(acc[4 * t + 6], acc[4 * t + 7]);
            mma16816(s[u][0], a0, a1, a2, a3, PH[t], PH[t + 1]);
            mma16816(s[u][1], a0, a1, a2, a3, P0[t], P0[t + 1]);
            mma16816(s[u][2], a0, a1, a2, a3, P1[t], P1[t + 1]);
          }
        }
        float e[2][4], r[2][2];
#pragma unroll
        for (int u = 0; u < 2; u++) {
          e[u][0] = (hi0 ? s[u][0][0] : s[u][1][0]) * sc0; e[u][1] = (hi1 ? s[u][0][1] : s[u][1][1]) * sc0;
          e[u][2] = (hi0 ? s[u][1][2] : s[u][2][2]) * sc1; e[u][3] = (hi1 ? s[u][1][3] : s[u][2][3]) * sc1;
          if (first) { if (hi0) e[u][0] = -1e30f; if (hi1) e[u][1] = -1e30f; }
          r[u][0] = fmaxf(e[u][0], e[u][1]); r[u][1] = fmaxf(e[u][2], e[u][3]);
        }
#pragma unroll
        for (int d = 1; d <= 2; d++)
#pragma unroll
          for (int q = 0; q < 4; q++) r[q >> 1][q & 1] = fmaxf(r[q >> 1][q & 1], __shfl_xor_sync(0xffffffffu, r[q >> 1][q & 1], d));
#pragma unroll
        for (int u = 0; u < 2; u++) {
#pragma unroll
          for (int q = 0; q < 4; q++) e[u][q] = ex2(e[u][q] - r[u][q >> 1]);
          r[u][0] = e[u][0] + e[u][1]; r[u][1] = e[u][2] + e[u][3];
        }
#pragma unroll
        for (int d = 1; d <= 2; d++)
#pragma unroll
          for (int q = 0; q < 4; q++) r[q >> 1][q & 1] += __shfl_xor_sync(0xffffffffu, r[q >> 1][q & 1], d);
#pragma unroll
        for (int u = 0; u < 2; u++) {
          const float rx = rcp(r[u][0]), ry = rcp(r[u][1]);
          px[u] = pack2(e[u][0] * rx, e[u][1] * rx); py[u] = pack2(e[u][2] * ry, e[u][3] * ry);
        }
        uint32_t o[8][2];
        uint4 ro[4];
#pragma unroll
        for (int q = 0; q < 8; q++) {
          float d[4] = {0.f, 0.f, 0.f, 0.f};
          const int t = 16 + 8 * hp + q, u = q >> 2;
          mma16816(d, px[u] & mhi, 0u, px[u] & ~mhi, py[u] & mhi, PH[t], P0[t]);
          mma1688(d, 0u, py[u] & ~mhi, P1[t]);
          o[q][0] = pack2(d[0], d[1]); o[q][1] = pack2(d[2], d[3]);
        }
#pragma unroll
        for (int q = 0; q < 4; q++) ro[q] = make_uint4(o[4 * (q & 1)][q >> 1], o[4 * (q & 1) + 1][q >> 1], o[4 * (q & 1) + 2][q >> 1], o[4 * (q & 1) + 3][q >> 1]);
        img_tag(ro, false, 0, x);
        img_store(ro, x.img(0, hp));
        if (hp == 0) publish(0, x);
        uint32_t xs[16];
        if (L) img_load(xs, tile, x);
        else {
#pragma unroll
          for (int q = 0; q < 4; q++) {
            uint32_t v[4];
            ldsm4(x.maddr(tile, 2 * q), v);
            xs[2 * q] = v[0]; xs[8 + 2 * q] = v[1]; xs[2 * q + 1] = v[2]; xs[9 + 2 * q] = v[3];
          }
          __syncwarp();
        }
        img_sts(ro, tile, x);
        img_unpack(acc + 32 * hp, xs);
      }
    } else {
      float kv[128];
      float (&kv0)[64] = reinterpret_cast<float (&)[64]>(kv[0]);
      float (&kv1)[64] = reinterpret_cast<float (&)[64]>(kv[64]);
      auto mma8 = [&](uint32_t as, uint32_t bs, int i, bool fence) {
        const uint32_t da = desc_lo(SB + OFF_A, 16) + as * (SLOT / 16), db = desc_lo(SB + OFF_B, 8192) + bs * (SLOT / 16);
        if (fence) wgmma_fence();
#pragma unroll
        for (int k = 0; k < 4; k++) {
          wgmma_ss_n128(kv0, da + (k >> 1) * 32 + (k & 1) * 2, HA64, db + 128 * k, i + k);
          wgmma_ss_n128(kv1, da + 512 + (k >> 1) * 32 + (k & 1) * 2, HA64, db + 128 * k, i + k);
        }
        wgmma_commit();
      };
      constexpr uint32_t dm = desc_lo(SB + OFF_MB, 0);
      auto relB = [&](uint32_t s) { mbar_arrive_n(sb + BAR_EMPTYB + s * 8, 2); };
      auto skip = [&]() {
#pragma unroll
        for (int q = 0; q < 6 - NJ; q++) adv<NA>(x.ra);
        x.rb.s = w ? (2 + NJ) % 6 : 4;
        if (!w && NJ < 4) x.rb.ph ^= 1;
      };
      static_assert(NA == 5 && NB == 6, "ring arithmetic");
      mma8(x.ra.s, x.rb.s + w, 0, true);
      gemm_next<256>(x);
#pragma unroll 1
      for (int i = 1; i < NJ; i++) {
        mbar_wait2(x.fullA(x.ra.s), x.ra.ph, x.fullB(x.rb.s + w), x.rb.ph);
        mma8(x.ra.s, x.rb.s + w, 1, true);
        if (!XO && i == XR) { img_store(r1, x.img(XBUF(L), 1)); publish(2, x); }
        if (!XO && i == XS) stats_send(ts, L, x);
        wgmma_wait<1>();
        if (x.elected) { x.releaseA(x.pa); relB(x.pb + w); }
        gemm_next<256>(x);
        if (XO && i == XR) { img_store(r1, x.img(XBUF(L), 1)); publish(2, x); stats_send(ts, L, x); }
      }
      if (w) {
        wgmma_wait<0>();
        if (x.elected) { x.releaseA(x.pa); relB(x.pb + 1); }
        skip();
        asm volatile("bar.sync 7, 256;" ::: "memory");
      }
      TSL_(8);
      {
        const int t = lane_id() + 32 * x.warp;
        uint32_t mask = t < 2 ? ((w ? (t ? 0xFF3Fu : 0x3FFFu) : 0xFFFFu) >> (NJ - 1)) & (w ? ~1u : ~0u) : 0u, cnt = 1 + t;
        bool ready = false;
#pragma unroll 1
        for (int i = NJ; i < 16; i++) {
          if (!ready) mbar_wait2(x.fullA(x.ra.s), x.ra.ph, x.fullB(x.rb.s), x.rb.ph);
          mma8(x.ra.s, x.rb.s, 1, true);
          const uint32_t bar = sb + (t ? BAR_EMPTYB + x.pb * 8 : BAR_EMPTYA + x.pa * 8);
          gemm_next<128>(x);
          if (w && (i | 4) == 15) x.rb.s = 4;
          ready = mbar_probe2(x.fullA(x.ra.s), x.ra.ph, x.fullB(x.rb.s), x.rb.ph);
          wgmma_wait<1>();
          if (mask & 1) mbar_arrive_n(bar, cnt);
          mask >>= 1; cnt = 2;
          if (i == 8 && w) asm volatile("bar.arrive 9, 256;" ::: "memory");
          if (i == 9) TSL_(10);
        }
        mbar_wait2(sb + BAR_STAT, 1, sb + BAR_CS + 8, 0);
        wgmma_fence();
        wgmma_r1_n128(kv0, dm, dcs + 96 + 96 * w, 1);
        wgmma_r1_n128(kv1, dm + 64, dcs + 96 + 96 * w, 1);
        wgmma_commit();
        if (w == 0) asm volatile("bar.arrive 7, 256;" ::: "memory");
        wgmma_wait<1>();
        if (mask & 1) mbar_arrive_n(sb + (t ? BAR_EMPTYB + x.pb * 8 : BAR_EMPTYA + x.pa * 8), 2);
      }
      const Stats s0 = load_stats(0, x), s1 = load_stats(1, x), st = w ? s1 : s0;
      if (w == 0) skip();
      const uint32_t h0 = x.held(0), h1 = x.held(1);
      auto vreg = [&](int ks) { return ks < 6 ? OFF_A + (ks < 3 ? h0 * SLOT : h1 * SLOT - 15360) + ks * 5120 : OFF_S + 2048 + ks * 5120; };
      uint32_t tV[2], uu[4];
#pragma unroll
      for (int hf = 0; hf < 2; hf++) {
        tV[hf] = sb + vreg(4 * hf + x.warp) + ((x.lane >> 3) & 1) * 2560 + (x.lane & 7) * 16 + x.mhi * 128;
        const float i0 = rcp(hf ? s1.rstd0 : s0.rstd0), i1 = rcp(hf ? s1.rstd1 : s0.rstd1);
        const uint32_t h = pack2(i0, i1);
        uu[2 * hf] = pack2(lo16(h), i0 - lo16(h)); uu[2 * hf + 1] = pack2(hi16(h), i1 - hi16(h));
        asm volatile("" : "+r"(tV[hf]), "+r"(uu[2 * hf]), "+r"(uu[2 * hf + 1])::"memory");
      }
      wgmma_wait<0>();
      fence_regs(kv);
      TSL_(2);
      if (w == 0) {
        uint32_t f[2][18], ad[4];
#pragma unroll
        for (int q = 0; q < 18; q++) f[1][q] = 0u;
#pragma unroll
        for (int q = 0; q < 4; q++) ad[q] = x.maddr(sb + OFF_S, 2 * q);
        auto norm = [&](int un) {
          uint32_t* u = f[un & 1];
          const Stats& sn = (un & 2) ? s1 : s0;
#pragma unroll
          for (int sg = 0; sg < 2; sg++) {
            uint32_t v = u[16 + sg];
            v = add2(v, __shfl_xor_sync(0xffffffffu, v, 1)); v = add2(v, __shfl_xor_sync(0xffffffffu, v, 2));
            const float a = rcp(lo16(v)) * sn.rstd0, b = rcp(hi16(v)) * sn.rstd1;
            const uint32_t r0 = pack2(a, a), r1_ = pack2(b, b);
#pragma unroll
            for (int q = 8 * sg; q < 8 * sg + 8; q++) u[q] = mul2(u[q], (q & 1) ? r1_ : r0);
#pragma unroll
            for (int q = 2 * sg; q < 2 * sg + 2; q++) stsm4(ad[q] + (un & 1) * SLOT + (un >> 1) * 8192, u[4 * q], u[4 * q + 1], u[4 * q + 2], u[4 * q + 3]);
          }
        };
        auto unit = [&](int un) { return kv + ((un >> 1) & 1) * 64 + (un & 1) * 16 + (un >> 2) * 32; };
        hedgehog_scale<1, 0>(kv, s0, nullptr, [] {});
#pragma unroll 1
        for (int it = 0;; it++) {
#pragma unroll
          for (int un = 0; un < 4; un++) {
            if (un == 1) {
              if (it) asm volatile("bar.sync 9, 256;" ::: "memory");
#pragma unroll
              for (int q = 0; q < 4; q++) ad[q] -= it * (OFF_S - OFF_B - 2 * SLOT);
            }
            norm((un + 3) & 3);
            dual_exp(unit(un), f[un & 1], x.goff);
            hedgehog_scale<1, KEEP>(unit(un + 1), ((un + 1) & 2) ? s1 : s0, f[(un + 1) & 1], [] {});
          }
          if (it) break;
#pragma unroll
          for (int q = 0; q < 32; q++) {
            asm volatile("mov.b32 %0, %1;" : "=f"(kv[q]) : "f"(kv[q + 32]));
            asm volatile("mov.b32 %0, %1;" : "=f"(kv[q + 64]) : "f"(kv[q + 96]));
            if (q < 16) kv[32 + q] = 0.f;
          }
        }
        norm(3);
        TSL_(3);
      } else {
        wg_bar(w);
#pragma unroll
        for (int hf = 0; hf < 2; hf++) {
          stsm4(tV[hf] + 512 + x.mhi * 512, uu[2 * hf], uu[2 * hf + 1], uu[2 * hf], uu[2 * hf + 1]);
          stsm4(tV[hf] + 1792 + x.mhi * 512, uu[2 * hf], uu[2 * hf + 1], uu[2 * hf], uu[2 * hf + 1]);
#pragma unroll
          for (int q = 0; q < 8; q++) {
            const float* u = kv + 64 * hf + 8 * q;
            stsm4(tV[hf] + (q >> 1) * 640 + (q & 1) * 256, pack2(u[0], u[1]), pack2(u[2], u[3]), pack2(u[4], u[5]), pack2(u[6], u[7]));
          }
        }
        TSL_(3);
      }
      {
        float d[2][20];
        uint4* dst = &g_kvpart[x.j()][w * 4 + x.warp][0][x.m() * 32 + x.lane];
        unsigned* dz = reinterpret_cast<unsigned*>(&g_kvpart[x.j()][w * 4 + x.warp][x.c & 1][512]) + x.m() * 8 + x.g;
        fence_async_smem();
        cta_bar();
        TSL_(11);
        uint32_t pk[9];
        auto prep = [&](float (&u)[20]) {
          fence_regs(u);
#pragma unroll
          for (int q = 0; q < 8; q++) pk[q] = pack2(u[((q >> 1) & 2) + 4 * (q & 3)], u[((q >> 1) & 2) + 4 * (q & 3) + 1]);
          pk[8] = __float_as_uint((x.c & 1) ? u[18] + u[19] : u[16] + u[17]);
#pragma unroll
          for (int q = 0; q < 9; q += 4) pk[q] = (pk[q] & ~1u) | (L == 1);
        };
        auto send = [&](int hp) {
          st_v4(dst + hp * 16 * 544, pk[0], pk[1], pk[2], pk[3]); st_v4(dst + (hp * 16 + 1) * 544, pk[4], pk[5], pk[6], pk[7]);
          st_flag(dz + hp * 16 * 544 * 4, pk[8]);
        };
        wgmma_fence();
#pragma unroll
        for (int q = 0; q < 17; q++) {
          if (q < 16) wgmma_ss_n40_tt(d[q >> 3], desc_lo(SB + (q < 8 ? OFF_S : OFF_B + 2 * SLOT), 1024) + w * (SLOT / 16) + 128 * (q & 7), desc_lo(SB + vreg(q & 7), 2560) + (w + (q >> 3) * 2) * 40, q & 7);
          else wgmma_r1_n128(acc, dm + w * 64, dcs, 0);
          if (q == 7 || q == KVS || q == 16) wgmma_commit();
          if (q == KVS) { mbar_wait2(x.fullA(x.ra.s), x.ra.ph, x.fullB(x.rb.s), x.rb.ph); wgmma_wait<1>(); prep(d[0]); send(0); bb_fence(x.goff); wgmma_fence(); }
        }
        gemm_issue<128, false>(acc, x, true); gemm_next<128>(x);
        wgmma_wait<1>();
        x.releaseA(h0); x.releaseA(h1); x.releaseB(2); x.releaseB(3);
        if (x.lane == 0) mbar_arrive(sb + BAR_SIGT);
        prep(d[1]);
        TSL_(4);
#pragma unroll 1
        for (int seg = 0; seg < 2; seg++) {
          const int n0 = w ? PS1 : PS0;
          gemm_run(acc, x, seg ? 15 - n0 : n0, seg, seg ? L : 0);
          if (seg == 0) send(1);
        }
      }
      gemm_end(acc, x);
      TSL_(5);
      {
        float dp[2][20], dn[2][20];
        uint32_t f[4][16];
        auto mma = [&](int h) {
          if (!(h & 1)) mbar_wait(sb + BAR_KV + h * 4, L >> 1);
          if (h == 0) TSL_(9);
          const uint32_t db = desc_lo(SB + OFF_S + h * 5120, 128);
          const uint32_t (&a)[16] = f[h];
          wgmma_fence();
          wgmma_rs_n40(dp[h & 1], a[0], a[1], a[2], a[3], db, 0);
          wgmma_rs_n40(dn[h & 1], a[8], a[9], a[10], a[11], db + 160, 0);
          wgmma_rs_n40(dp[h & 1], a[4], a[5], a[6], a[7], db + 80, 1);
          wgmma_rs_n40(dn[h & 1], a[12], a[13], a[14], a[15], db + 240, 1);
          wgmma_commit();
        };
        uint32_t xr[16];
        auto fin = [&](int h) {
          const uint32_t tile = x.aslot(x.held(h >> 1));
          if (!(h & 1)) img_load(xr, tile, x);
          float (&u)[20] = dp[h & 1];
          float (&v)[20] = dn[h & 1];
          fence_regs(u); fence_regs(v);
#pragma unroll
          for (int r = 0; r < 2; r++) {
            const float sp = u[16 + 2 * r], sn = v[16 + 2 * r];
            const float id = rcp(fmaf(fmaf(sp, L == 1 ? 0.065536f * 128 / 129 : 0.065536f, u[17 + 2 * r]), sn, v[17 + 2 * r] * sp)), aa = sn * id, cc = sp * id;
            uint32_t o[4];
#pragma unroll
            for (int t = 0; t < 4; t++) o[t] = pack2(fmaf(u[4 * t + 2 * r], aa, v[4 * t + 2 * r] * cc), fmaf(u[4 * t + 2 * r + 1], aa, v[4 * t + 2 * r + 1] * cc));
            o[2 * r + (h & 1)] = img_tag(o[2 * r + (h & 1)], false, 1, x);
            if (ZO && h == 3) r1[r] = make_uint4(o[0], o[1], o[2], o[3]);
            else stg128(x.img(0, h >> 1) + r * 64 + (h & 1) * 32, make_uint4(o[0], o[1], o[2], o[3]));
            sts128(tile + r * 1024 + (h & 1) * 512 + x.so, o[0], o[1], o[2], o[3]);
          }
          if (h & 1) { if (h == 1) publish(0, x); img_unpack(acc + 16 * (h - 1), xr); }
        };
        auto ex = [&](int h) { dual_exp_rcp(acc + 16 * h, f[h]); };
        Stats sq = st;
#pragma unroll
        for (int h = 0; h < 4; h += 2) {
          hedgehog_scale<2, 0>(acc + 16 * h, sq, nullptr, [&] { ex(h); });
          mma(h);
          ex(h + 1); wgmma_wait<0>(); fin(h);
          if (h == 0) bb_fence(x.goff);
          mma(h + 1);
          wgmma_wait<0>(); fin(h + 1);
          if (h == 0) sq.rstd1 += bb_fence(x.goff);
        }
      }
    }
    mbar_wait(x.fullB(x.rb.s), x.rb.ph);
    fence_regs(acc);
    fence_async_smem();
    wg_bar(w);
    TSL_(6);
    rewind2<NA>(x.ra);
    if (ZO && (L & 1)) { stg128(x.img(0, 1) + 32, r1[0]); stg128(x.img(0, 1) + 96, r1[1]); }
    gemm_issue<128, false>(acc, x, true); gemm_next<128>(x);
    uint4* out = solid(P.out + goff + (x.warp * 16 + (x.lane >> 3)) * 256 + (x.lane & 7));
#pragma unroll 1
    for (int seg = L >= TSL ? 0 : 1; seg < 2; seg++) {
      gemm_run(acc, x, L >= TSL ? (seg ? TSK : 15 - TSK) : 15, seg, 10 + L);
      if (L >= TSL) {
        if (seg == 0 && w == 1) asm volatile("bar.sync 6, 256;" ::: "memory");
        if (seg == 1 && w == 0) asm volatile("bar.arrive 6, 256;" ::: "memory");
      }
    }
    gemm_end(acc, x);
    TSL_(7);
    rewind2<NA>(x.ra);
    out_epilogue(acc, r1, ts, out, L, x);
    TSL_(13);
  }
}

typedef unsigned long long u64;
template <class T> __device__ __forceinline__ T* early(T* p) { return (T*)__shfl_xor_sync(0xffffffffu, (u64)p, 1); }
__device__ __forceinline__ void pause(uint32_t GAP) {
  if (GAP) { uint32_t t0, t; asm volatile("mov.u32 %0, %%clock;" : "=r"(t0)); do { asm volatile("mov.u32 %0, %%clock;" : "=r"(t)); } while (t - t0 < GAP); }
}
__device__ __forceinline__ u64 order_table0(int j) { return (j & 4) ? 0x543210FEDCBA9876ull : 0xDCBA9876543210FEull; }
__device__ __forceinline__ void order_tables(u64& t1, u64& t2, int j) {
#pragma unroll 1
  for (int i = 6; i >= 0; i--) { const u64 o = 2 * other_tile(i, j); t1 = t1 << 4 | o | (o + 1) << 28; t2 = t2 << 8 | (o * 17 + 16); }
  const u64 own = 2 * j * 17 + 16;
  t1 = t1 << 8 | own; t2 |= own << 56;
}

__device__ __forceinline__ void b_producer(const Params& P, uint32_t sb, unsigned vb) {
  const int j = cta_j(vb);
  u64 t1 = 0, t2 = 0;
  Ring r = {PRE_B % NB, PRE_B < NB};
#pragma unroll 1
  for (int sg = 0; sg < 20; sg++) {
    const int L = sg / 5, p = sg - 5 * L, wt = L & 1;
    if (sg == 1) order_tables(t1, t2, j);
    int n = p >= 3 ? 16 : (wt ? (p ? 16 - NJ : 2 * NJ) : (p ? 0 : (L ? 32 : 32 - PRE_B)));
    u64 tab = p == 3 ? t2 : (sg == 0 ? order_table0(j) >> (2 * PRE_B) : (p == 1 || p == 2 ? t1 >> (4 * NJ) : t1));
    const CUtensorMap* tm = p == 4 ? &P.mwo[wt] : &P.mw[wt ? 1 : L];
    const uint4* img = &g_wf[p != 3][j][0][0];
    int col = (p >= 3 ? 0 : (p == 2 ? 2048 : 1024)) + 128 * j;
    const int flip = p == 0 ? 3072 : 0;
    const bool fold = wt && p != 4;
    if (sg == 5 || sg == 8) { mbar_wait(sb + (sg == 5 ? BAR_WPHI : BAR_CS + 8), sg == 5); fence_async_global(); }
    if (DEFER && p == 4 && ((DEFL >> wt) & 1)) {
      Ring q = r;
      for (int u = 0; u < DEFER; u++) adv<NB>(q);
      mbar_wait(sb + BAR_EMPTYB + q.s * 8, q.ph);
    }
#pragma unroll 1
    for (; n > 0; n--) {
      const int kb = (int)tab & 15;
      mbar_wait(sb + BAR_EMPTYB + r.s * 8, r.ph);
      if (elect()) {
        mbar_expect_tx(sb + BAR_FULLB + r.s * 8, SLOT);
        if (fold && col < 2048) bulk_load(sb + OFF_B + r.s * SLOT, img + kb * 1024, SLOT, sb + BAR_FULLB + r.s * 8);
        else tma_load_w(sb + OFF_B + r.s * SLOT, tm, sb + BAR_FULLB + r.s * 8, col, kb);
      }
      adv<NB>(r);
      if (p == 2 && (n | 4) == 5) r.s = 4;
      col ^= flip;
      if (!(col & flip & 2048)) tab >>= 4;
    }
  }
}

__device__ __forceinline__ void a_loader(const Params& P, uint32_t sb, unsigned vb) {
  const int j = cta_j(vb), m = cta_m(vb);
  u64 t1 = 0, t2 = 0;
  Ring r = {PRE_A % NA, PRE_A < NA};
  {
    u64 tab = order_table0(j) >> (4 * PRE_A);
#pragma unroll 1
    for (int i = PRE_A; i < 33; i++) {
      if (i == 17) { order_tables(t1, t2, j); tab = t2; }
      mbar_wait(sb + BAR_EMPTYA + r.s * 8, r.ph);
      if (elect()) {
        mbar_expect_tx(sb + BAR_FULLA + r.s * 8, SLOT);
        if (i != 14) tma_load_3d(sb + OFF_A + r.s * SLOT, &P.mx, sb + BAR_FULLA + r.s * 8, ((int)tab & 15) * 64, m * 64, 0);
        else {
          tma_load_w(sb + OFF_A + r.s * SLOT, &P.mw[1], sb + BAR_FULLA + r.s * 8, 1024 + 128 * j, m);
          mbar_expect_tx(sb + BAR_WPHI, 8192); tma_load_2d(sb + OFF_S + 4096, &P.mwphi, sb + BAR_WPHI, 0, 128 * j);
        }
        if (i == PF1 || i == PF2) tma_prefetch_w(&P.mwo[i == PF2], 128 * j, m);
      }
      adv<NA>(r);
      if (i != 14) tab >>= 4;
    }
  }
  const unsigned tag = get_tag(sb);
  unsigned kph = 0;
#pragma unroll 1
  for (int sg = 0; sg < 13; sg++) {
    const int L = sg >> 2, p = sg & 3;
    if (p == 0 && (L & 1)) {
#pragma unroll 1
      for (int h = 0; h < 2; h++) {
        poll_flags(&g_kvfflag[L >> 1][j][h][0], 16, 0xFFFFu, tag);
        TS(4, h ? 14 + L : 26 + L);
        for (int it = 0;; it++) {
          if (elect()) { mbar_expect_tx(sb + BAR_STAT + 8, 10240); bulk_load(sb + OFF_S + h * 10240, &g_kvfin[j][8 * h][0], 10240, sb + BAR_STAT + 8); }
          mbar_wait(sb + BAR_STAT + 8, kph);
          kph ^= 1;
          uint32_t a = 1u, o = 0u;
#pragma unroll
          for (int u = 0; u < 20; u++) { const uint32_t v = __float_as_uint(lds32f(sb + OFF_S + h * 10240 + u * 512 + (threadIdx.x & 31) * 16)); a &= v; o |= v; }
          if (__all_sync(0xffffffffu, (L == 1 ? a : ~o) & 1u)) break;
          fence_async_smem();
          if (it > (1 << 16)) __trap();
        }
        if (elect()) mbar_arrive(sb + BAR_KV + h * 8);
        TS(4, h ? 30 + L : (L == 1 ? 20 : 25));
      }
    }
    int n = p < 2 ? 14 : (p == 2 ? ((L & 1) ? 0 : 16 - NJ) : 16);
    u64 tab = p == 3 ? t2 : t1 >> (p < 2 ? 8 : 4 * NJ);
    const uint4* img = &g_img[p ? XBUF(L + 1) : 0][m][0][0];
#pragma unroll 1
    for (; n > 0; n--) {
      const uint4* src = early(img + ((int)tab & 15) * 1024);
      const uint32_t bar = sb + (p < 2 ? BAR_LAND : BAR_FULLA) + r.s * 8;
      mbar_wait(sb + BAR_EMPTYA + r.s * 8, r.ph);
      if (elect()) mbar_expect_tx(bar, SLOT);
      if (p < 2 && n == 14) {
        const int lane = threadIdx.x & 31;
        const unsigned* f = &g_hint[(m & 14) + ((lane >> 3) & 1)][(~j & 4) + (lane & ND0)];
        mbar_wait(sb + BAR_SIGP + p * 8, L & 1);
        pause(PD);
        int it = 0;
        while (!__all_sync(0xffffffffu, (int)(ld_flag(f) - (tag * 8 + 2 * L + p)) >= 0)) { if (++it > (1 << 22)) __trap(); }
        TS(2, p == 0 ? 5 + L * 8 : 9 + L * 8);
        TSH((2 * L + p) * 8 + 2);
      }
      if (elect()) bulk_load(sb + OFF_A + r.s * SLOT, src, SLOT, bar);
      adv<NA>(r);
      tab >>= 4;
      pause(p < 2 && n > 10 ? G0 : 0);
    }
  }
}

template <int KB>
__device__ __forceinline__ uint2 sum_packets(float (&a)[8], uint32_t addr, int n) {
  uint2 ok = make_uint2(~0u, 0u);
#pragma unroll 1
  for (int b = 0; b < n; b += KB) {
    uint4 v[KB];
#pragma unroll
    for (int u = 0; u < KB; u++) lds128(addr + (b + u) * 512, v[u].x, v[u].y, v[u].z, v[u].w);
#pragma unroll
    for (int u = 0; u < KB; u++) {
      ok.x &= v[u].x; ok.y |= v[u].x;
      a[0] += lo16(v[u].x); a[1] += hi16(v[u].x); a[2] += lo16(v[u].y); a[3] += hi16(v[u].y);
      a[4] += lo16(v[u].z); a[5] += hi16(v[u].z); a[6] += lo16(v[u].w); a[7] += hi16(v[u].w);
    }
  }
  return ok;
}
__device__ __forceinline__ void helper_bar() { asm volatile("bar.sync 4, 64;" ::: "memory"); }
__device__ __forceinline__ void helper(const Params& P, uint32_t sb, int w, unsigned vb) {
  const int j = cta_j(vb), m = cta_m(vb);
  if (w == 0) {
    if (elect()) {
      const unsigned t = atomicAdd(&g_ctr, 1u) / NCTA + 1u;
      asm volatile("st.shared.u32 [%0], %1;" ::"r"(sb + OFF_EPOCH), "r"(t) : "memory");
      mbar_arrive(sb + BAR_EPOCH);
    }
  }
  const unsigned tag = get_tag(sb);
  mbar_wait(sb + BAR_FULLB + 24, 0);
  const uint32_t stg = sb + OFF_T + w * 12288, stb = sb + BAR_STG + w * 24;
  Ring rs = {0, 0};
  uint32_t vs = 33 % NA, vph = 0;
  auto cs_image = [&](int L) {
      const int lane = lane_id();
      poll_flags(&g_csflag[L][j][0], 16, L ? CSNEED : 0xFFFu, tag);
#pragma unroll
      for (int p = 0; p < 3; p++) {
        const uint4 u = ldcg4(&g_cs[L][0][p * 1024 + 128 * j + lane * 4]), v = ldcg4(&g_cs[L][1][p * 1024 + 128 * j + lane * 4]);
        const float c0 = __uint_as_float(u.x) + __uint_as_float(v.x), c1 = __uint_as_float(u.y) + __uint_as_float(v.y);
        const float c2 = __uint_as_float(u.z) + __uint_as_float(v.z), c3 = __uint_as_float(u.w) + __uint_as_float(v.w);
        const uint32_t h0 = pack2(c0, c1), h1 = pack2(c2, c3), dst = sb + OFF_CS + (p * 16 + (lane >> 1)) * 96 + L * 48 + (lane & 1) * 8;
        sts64(dst, h0, h1); sts64(dst + 16, pack2(c0 - lo16(h0), c1 - hi16(h0)), pack2(c2 - lo16(h1), c3 - hi16(h1))); sts64(dst + 32, h0, h1);
        if (L == 0) { sts64(dst + 48, 0u, 0u); sts64(dst + 64, 0u, 0u); sts64(dst + 80, 0u, 0u); }
      }
      if (L == 0 && lane < 4) sts64(sb + OFF_CS + 4608 + lane * 8, 0u, 0u);
      fence_async_smem();
      __syncwarp();
      if (elect()) mbar_arrive(sb + BAR_CS + L * 8);
      TS(4, 2 + L * 2);
  };
#pragma unroll 1
  for (int L = 0; L < 4; L++) {
    const int lane = lane_id();
    if (L == 0) {
      {
        const int wt = m >= 12, col = ((0x2021 >> (m & 12)) & 3) * 1024 + 128 * j + (m & 3) * 32;
        const CUtensorMap* tm = &P.mcs[wt];
        __nanosleep(wt ? D2 : CD);
        constexpr int nb = 8;
        float a[8] = {0.f, 0.f, 0.f, 0.f, 0.f, 0.f, 0.f, 0.f};
#pragma unroll 1
        for (int b = -3; b < nb; b++) {
          if (b >= 0) {
            mbar_wait(stb + rs.s * 8, rs.ph);
            sum_packets<KC>(a, stg + rs.s * 4096 + lane * 16, 8);
            fence_async_smem();
            __syncwarp();
          }
          const uint32_t sl = b < 0 ? (rs.s + b + 3) % 3 : rs.s;
          if (b + 3 < nb && elect()) { mbar_expect_tx(stb + sl * 8, 4096); tma_load_2d(stg + sl * 4096, tm, stb + sl * 8, col, (w * (16 - nb) + b + 3) * 64); }
          if (b >= 0) adv<3>(rs); else pause(CP);
        }
#pragma unroll 1
        for (int d = 4; d < 32; d *= 2)
#pragma unroll
          for (int u = 0; u < 8; u++) a[u] += __shfl_xor_sync(0xffffffffu, a[u], d);
        if (lane < 4) {
          float4* dst = reinterpret_cast<float4*>(&g_cs[wt][w][col + lane * 8]);
          dst[0] = make_float4(a[0], a[1], a[2], a[3]); dst[1] = make_float4(a[4], a[5], a[6], a[7]);
        }
        helper_bar();
        if (w == 0 && elect()) { fence_gpu(); st_flag(&g_csflag[wt][j][m], tag); }
      }
      if (w == 0) TS(4, 1 + L * 2);
    }
    if (L > 0 && w == 0) {
      mbar_wait(sb + BAR_SIGP + 16, (L - 1) & 1);
      fence_async_global();
      __nanosleep(CO && L == 1 ? SE : SD);
    }
    if (CO && L < 2 && w == 0) cs_image(L);
    if (w == (L == 0)) {
      if (L == 0) { mbar_wait(sb + BAR_WPHI, 0); __nanosleep(S0); }
#pragma unroll 1
      for (int p = 0; p < 2; p++) {
        uint4 v[8];
        for (int it = 0;; it++) {
          bool ok = true;
#pragma unroll
          for (int t = 0; t < 8; t++) v[t] = ld_pkt(&g_stats[m][p][t][lane]);
#pragma unroll
          for (int t = 0; t < 8; t++) ok = ok && (v[t].w & 15u) == seq4(tag, L);
          if (__all_sync(0xffffffffu, ok)) break;
          __nanosleep(200);
          if (it > (1 << 20)) __trap();
        }
        float s0 = 0.f, q0 = 0.f, s1 = 0.f, q1 = 0.f;
#pragma unroll
        for (int t = 0; t < 8; t++) { s0 += __uint_as_float(v[t].x); q0 += __uint_as_float(v[t].y); s1 += __uint_as_float(v[t].z); q1 += __uint_as_float(v[t].w & ~15u); }
        s0 *= (1.f / 1024); s1 *= (1.f / 1024);
        sts64(sb + OFF_MR + p * 256 + lane * 8, __float_as_uint(rsqrtf(fmaxf(q0 * (1.f / 1024) - s0 * s0, 0.f) + 1e-5f)),
              __float_as_uint(rsqrtf(fmaxf(q1 * (1.f / 1024) - s1 * s1, 0.f) + 1e-5f)));
#pragma unroll
        for (int r = 0; r < 2; r++) {
          const float v = -0.5f * (r ? s1 : s0);
          const uint32_t hh = pack2(v, v), hl = pack2(v, v - lo16(hh));
          const bool b = L & 1;
          sts128(sb + (b ? OFF_MB : OFF_MA) + p * 1024 + (lane >> 3) * 256 + r * 128 + (lane & 7) * 16, b ? 0u : hh, b ? hh << 16 : hl >> 16, b ? hl : 0u, 0u);
        }
      }
      fence_async_smem();
      __syncwarp();
      if (elect()) {
        mbar_arrive(sb + BAR_STAT);
      }
      TS(2, 0 + L * 8);
    }
    if (!CO && L < 2 && w == 0) cs_image(L);
    if (L & 1) {
      const uint32_t flip = L == 1 ? 0u : 1u;
      mbar_wait(sb + BAR_SIGT, 1);
      {
        int it = 0;
        if (PSL) __nanosleep(m < 8 ? PSL : PSL + 600);
        while (!__all_sync(0xffffffffu, (ld_flag(reinterpret_cast<const unsigned*>(&g_kvpart[j][m][w][512]) + (lane & 15) * 8) ^ flip) & 1u)) { if (PSL) __nanosleep(100); if (++it > (1 << 22)) __trap(); }
        fence_async_global();
      }
      if (w == 0) TS(4, 6 + L * 2);
      float a[8], z;
      for (int it = 0;; it++) {
        if (elect()) { mbar_expect_tx(stb + rs.s * 8, 8704); bulk_load(stg, &g_kvpart[j][m][w][0], 8704, stb + rs.s * 8); }
        mbar_wait(stb + rs.s * 8, rs.ph);
        if (w == 0) TS(4, 21 + L);
        adv<3>(rs);
#pragma unroll
        for (int u = 0; u < 8; u++) a[u] = 0.f;
        z = 0.f;
        uint32_t ok = 1u;
#pragma unroll
        for (int u = 0; u < 4; u++) { const float v = lds32f(stg + 8192 + u * 128 + (lane & 3) * 32 + (lane >> 2) * 4); z += v; ok &= __float_as_uint(v) ^ flip; }
        const uint2 tg = sum_packets<8>(a, stg + lane * 16, 16);
        ok &= flip ? ~tg.y : tg.x;
        if (__all_sync(0xffffffffu, ok & 1u)) break;
        fence_async_smem();
        if (it > (1 << 16)) __trap();
      }
      {
        uint4* img = &g_kvfin[j][m][w * 8 + (lane >> 2)];
        uint32_t a0 = __float_as_uint(a[0]) >> 16;
        a0 += ~(a0 ^ flip) & 1u;
        st_v4(img + (lane & 3) * 16, __byte_perm(a0, pack2(0.f, a[1]), 0x7610), pack2(a[2], a[3]), pack2(a[4], a[5]), pack2(a[6], a[7]));
        const uint32_t cz = pack2(0.f, qsum(z)) | (0x3781u ^ flip);
        if (!(lane & 3)) st_v4(img + 64, cz, cz, cz, cz);
        __syncwarp();
        if (elect()) st_flag(&g_kvfflag[L >> 1][j][m >> 3][(m & 7) * 2 + w], tag);
      }
      if (w == 0) TS(4, 7 + L * 2);
    } else {
      mbar_wait(sb + BAR_SIGT, 0);
      if (w == 0) {
        if (elect()) { fence_gpu(); st_flag(&g_hflag[L >> 1][m][j][0], tag); st_flag(&g_kflag[j][m], tag); }
        if (L == 0) {
          __nanosleep(KSL);
          poll_flags(&g_kflag[j][0], 16, 0xFFFFu, tag);
          if (elect()) mbar_arrive(sb + BAR_WPHI);
        }
      } else if (m > 0) {
        poll_flags(&g_hflag[L >> 1][m - 1][j][0], 1, 1u, tag);
        if (elect()) { mbar_expect_tx(sb + BAR_HALO, 8192); bulk_load(sb + OFF_S + 8192, &g_halo[m - 1][j][0][0], 8192, sb + BAR_HALO); }
        TS(2, 2 + L * 8);
      }
    }
    if (w == 0) {
#pragma unroll 1
      for (int e = 0; e < (L < 3 ? 2 : 1); e++) {
        unsigned* flag = early(&g_hint[m][j]);
        mbar_wait(sb + BAR_SIGP + e * 8, L & 1);
        TS(2, (e ? 6 : 3) + L * 8);
        TSH((2 * L + e) * 8);
        pause(XD);
        if (elect()) st_flag(flag, tag * 8 + 2 * L + e);
        TSH((2 * L + e) * 8 + 1);
      }
    } else {
#pragma unroll 1
      for (int i = 0; i < (L < 3 ? 28 : 14); i++) {
        const bool isx = i >= 14;
        const uint32_t a = sb + OFF_A + vs * SLOT + lane * 128 + ((lane >> 4) * 4 + (lane & 3)) * 16 + (lane & 12), code = img_code(isx, L + isx);
        for (int it = 0;; it++) {
          mbar_wait(sb + BAR_LAND + vs * 8, (vph >> vs) & 1);
          vph ^= 1u << vs;
          if (i - 14 * isx < 2) TSH((2 * L + isx) * 8 + 3 + 2 * (i - 14 * isx));
          uint32_t bad = 0;
#pragma unroll
          for (int u = 0; u < 4; u++) bad |= __float_as_uint(lds32f(a + u * 4096)) ^ code;
          if (__all_sync(0xffffffffu, !(bad & img_mask(isx)))) break;
          if (it > (1 << 16)) __trap();
          fence_async_smem();
          if (elect()) {
            mbar_expect_tx(sb + BAR_LAND + vs * 8, SLOT);
            bulk_load(sb + OFF_A + vs * SLOT, &g_img[isx ? XBUF(L + 1) : 0][m][o_order(i - 14 * isx + 2, j)][0], SLOT, sb + BAR_LAND + vs * 8);
          }
        }
        if (elect()) mbar_arrive(sb + BAR_FULLA + vs * 8);
        if (i - 14 * isx < 2) TSH((2 * L + isx) * 8 + 4 + 2 * (i - 14 * isx));
        if (++vs == NA) vs = 0;
      }
      vs = (vs + ((L & 1) ? 16 : 32 - NJ)) % NA;
    }
  }
}

__device__ __forceinline__ void spare(const Params& P, uint32_t sb, int id) {
  const int tid = threadIdx.x & 127, warp = __shfl_sync(0xffffffffu, threadIdx.x >> 5, 0), w = warp >> 2, lane = tid & 31, j = 2 * id + w;
  const uint32_t ring = w * 6 * SLOT, wp = 12 * SLOT + w * 8192, bar = sb + 13 * SLOT + w * 64;
  auto part = [&](int t) { return (t >> 4) ^ w; };
  auto load = [&](int t, uint32_t sl) {
    mbar_expect_tx(bar + sl * 8, t == 0 ? SLOT + 8192 : SLOT);
    tma_load_w(sb + ring + sl * SLOT, &P.mw[1], bar + sl * 8, part(t) * 1024 + 128 * j, t & 15);
  };
  if (!(warp & 3) && elect()) {
    if (w == 2) sts32(sb + OFF_EPOCH, atomicAdd(&g_ctr, 1u) / NCTA + 1u);
    else {
      __nanosleep(D3);
#pragma unroll 1
      for (int t = 0; t < 5; t++) {
        mbar_init(bar + t * 8, 1);
        asm volatile("fence.mbarrier_init.release.cluster;" ::: "memory");
        load(t, t);
      }
      tma_load_2d(sb + wp, &P.mwphi, bar, 0, 128 * j);
    }
  }
  __syncthreads();
  const unsigned tag = get_tag<false>(sb);
  if (w == 2) {
    int it = 0;
    while ((int)(ld_flag(&g_ctr) - tag * NCTA) < 0) { if (++it > (1 << 22)) __trap(); }
    return;
  }
  Ring r = {4, 1};
  float d[64];
  auto fold = [&]() {
    mbar_wait(bar + r.s * 8, r.ph);
    wgmma_fence();
#pragma unroll
    for (int q = 0; q < 8; q++)
      wgmma_ss_n32(reinterpret_cast<float (&)[16]>(d[16 * (q >> 1)]), desc_lo(SB + ring + r.s * SLOT, 16) + (q >> 2) * 512 + (q & 3) * 2, desc_lo(SB + wp, 512) + q * 64, q & 1);
    wgmma_commit();
  };
#pragma unroll
  for (int i = 0; i < 64; i++) d[i] = 0.f;
  int t = -1;
#pragma unroll 1
  for (int g = 0; g < 2; g++) {
    float cs[32] = {};
#pragma unroll 1
    do {
      uint32_t f[32];
#pragma unroll
      for (int i = 0; i < 32; i++) { f[i] = pack2(d[2 * i], d[2 * i + 1]); cs[i & 30] += d[2 * i]; cs[i | 1] += d[2 * i + 1]; }
      wg_bar(w);
      const uint32_t sl = r.s;
      if (t < 31) adv<5>(r);
      fold();
      if (!(warp & 3) && t >= 0 && t < 27 && elect()) load(t + 5, sl);
      if (g == w && t >= 0) {
        uint4* dst = &g_wf[0][j][t & 15][((tid >> 5) * 16 + (lane >> 2)) * 8];
#pragma unroll
        for (int q = 0; q < 8; q++)
          dst[(q >> 2) * 512 + (q & 1) * 64 + (((q & 2) * 2 + (lane & 3)) ^ (lane >> 2))] =
              make_uint4(f[4 * (q & 6) + (q & 1)], f[4 * (q & 6) + (q & 1) + 2], f[4 * (q & 6) + (q & 1) + 4], f[4 * (q & 6) + (q & 1) + 6]);
      }
      wgmma_wait<0>();
      fence_regs(d);
    } while (++t != 16 * g + 16);
    const uint32_t red = sb + ring + 5 * SLOT;
#pragma unroll
    for (int i = 0; i < 8; i++) sts128(red + (tid >> 2) * 512 + (i >> 1) * 128 + (lane & 3) * 32 + (i & 1) * 16, __float_as_uint(cs[4 * i]), __float_as_uint(cs[4 * i + 1]), __float_as_uint(cs[4 * i + 2]), __float_as_uint(cs[4 * i + 3]));
    wg_bar(w);
    float a = 0.f;
#pragma unroll 4
    for (int i = 0; i < 32; i++) a += lds32f(red + i * 512 + tid * 4);
    g_cs[1][0][(g ^ w) * 1024 + j * 128 + tid] = a;
  }
  wg_bar(w);
  if (tid == 0) { fence_gpu(); st_flag(&g_csflag[1][j][0], tag); }
}

__global__ void __launch_bounds__(NTHREADS, 1) fused_kernel(const __grid_constant__ Params P) {
  extern __shared__ __align__(1024) uint8_t smem_raw[];
  constexpr uint32_t sb = SB;
  const int tid = threadIdx.x;
  const unsigned vb = vblock();
  if (vb >= 128) { spare(P, sb, vb - 128); return; }
  const int warp = __shfl_sync(0xffffffffu, tid >> 5, 0);
  if (elect()) {
    if (warp == 11) { prefetch_map(&P.mx); prefetch_map(&P.mw[0]); if (smem_u32(smem_raw) != SB) __trap(); }
    if (warp < 8) {
#pragma unroll
      for (int i = 0; i < 8; i++) mbar_init(sb + OFF_BAR + (warp * 8 + i) * 8, warp == 2 || warp == 3 ? 2 : (warp == 4 ? 8 : 1));
    }
    asm volatile("fence.mbarrier_init.release.cluster;" ::: "memory");
    if (warp < 2) {
      const int j = cta_j(vb);
#pragma unroll 1
      for (int i = 0; i < (warp == 0 ? PRE_B : PRE_A); i++) {
        const uint32_t bar = sb + BAR_FULLB + warp * 64 + i * 8;
        mbar_expect_tx(bar, SLOT);
        if (warp == 0) tma_load_w(sb + OFF_B + i * SLOT, &P.mw[0], bar, 1024 + (i & 1) * 1024 + 128 * j, kv_order(i >> 1, j, 0));
        else tma_load_3d(sb + OFF_A + i * SLOT, &P.mx, bar, kv_order(i, j, 0) * 64, cta_m(vb) * 64, 0);
      }
    }
  }
  if (tid == 0) TS(6, 0);
  __syncthreads();
  if (tid == 0) TS(6, 2);
  if (warp < 4) {
    reg_dealloc<PREGS>();
    if (warp & 2) helper(P, sb, warp & 1, vb);
    else if (warp & 1) a_loader(P, sb, vb);
    else b_producer(P, sb, vb);
  } else {
    reg_alloc<CREGS>();
    consumer(P, sb, (warp >> 2) - 1, vb);
  }
}

typedef CUresult (*EncodeFn)(CUtensorMap*, CUtensorMapDataType, cuuint32_t, void*, const cuuint64_t*, const cuuint64_t*,
                             const cuuint32_t*, const cuuint32_t*, CUtensorMapInterleave, CUtensorMapSwizzle,
                             CUtensorMapL2promotion, CUtensorMapFloatOOBfill);

void encode(EncodeFn fn, CUtensorMap* m, const void* ptr, int rank, const cuuint64_t* dims, const cuuint64_t* strides,
            const cuuint32_t* box, CUtensorMapSwizzle swz) {
  const cuuint32_t es[5] = {1, 1, 1, 1, 1};
  fn(m, CU_TENSOR_MAP_DATA_TYPE_BFLOAT16, rank, const_cast<void*>(ptr), dims, strides, box, es, CU_TENSOR_MAP_INTERLEAVE_NONE,
     swz, CU_TENSOR_MAP_L2_PROMOTION_L2_256B, CU_TENSOR_MAP_FLOAT_OOB_FILL_NONE);
}
void encode_w(EncodeFn fn, CUtensorMap* m, const void* ptr, int ncols, bool perm) {
  const cuuint64_t p = (cuuint64_t)ncols * 2, d[5] = {(cuuint64_t)ncols, 2, 4, 4, 32}, s[4] = {p, (perm ? 8 : 2) * p, (perm ? 2 : 8) * p, 32 * p};
  const cuuint32_t box[5] = {64, 2, 4, 4, 2};
  encode(fn, m, ptr, 5, d, s, box, CU_TENSOR_MAP_SWIZZLE_128B);
}

void encode_cs(EncodeFn fn, CUtensorMap* m, const void* ptr, int ncols) {
  const cuuint64_t d[2] = {(cuuint64_t)ncols, 1024}, s[1] = {(cuuint64_t)ncols * 2};
  const cuuint32_t box[2] = {32, 64};
  encode(fn, m, ptr, 2, d, s, box, CU_TENSOR_MAP_SWIZZLE_NONE);
}

}

extern "C" void kernel_launch(void* const* d_in, const int* in_sizes, int n_in, void* d_out, int out_size) {
  (void)in_sizes; (void)n_in; (void)out_size;
  void* fnp = nullptr;
  cudaDriverEntryPointQueryResult q;
  cudaGetDriverEntryPoint("cuTensorMapEncodeTiled", &fnp, cudaEnableDefault, &q);
  EncodeFn fn = (EncodeFn)fnp;
  Params P;
  {
    const cuuint64_t dims[3] = {1024, 1024, 2}, strides[2] = {4096, 2048};
    const cuuint32_t box[3] = {64, 64, 2};
    encode(fn, &P.mx, d_in[0], 3, dims, strides, box, CU_TENSOR_MAP_SWIZZLE_128B);
  }
  P.out = (uint4*)d_out;
  encode_w(fn, &P.mw[0], d_in[1], 3072, false);
  encode_w(fn, &P.mw[1], d_in[4], 3072, true);
  encode_w(fn, &P.mw[2], d_in[1], 3072, true);
  encode_w(fn, &P.mwo[0], d_in[2], 1024, true);
  encode_w(fn, &P.mwo[1], d_in[6], 1024, false);
  encode_cs(fn, &P.mcs[0], d_in[1], 3072);
  encode_cs(fn, &P.mcs[1], d_in[4], 3072);
  {
    const cuuint64_t dims[2] = {32, 1024}, strides[1] = {64};
    const cuuint32_t box[2] = {32, 128};
    encode(fn, &P.mwphi, d_in[5], 2, dims, strides, box, CU_TENSOR_MAP_SWIZZLE_64B);
  }
  cudaFuncSetAttribute(fused_kernel, cudaFuncAttributeMaxDynamicSharedMemorySize, SMEM_BYTES);
  fused_kernel<<<NCTA, NTHREADS, SMEM_BYTES, cudaStreamPerThread>>>(P);
}
```

```cpp
#include <cuda_runtime.h>
#include <cuda_bf16.h>
#include <cuda.h>
#include <stdint.h>

namespace {

__device__ __forceinline__ void wgmma_ss_n256(float (&d)[128], uint32_t da, uint32_t ha, uint32_t db, int sd) {
  asm volatile("{\n.reg .pred p;\n.reg .b64 a, b;\nsetp.ne.b32 p, %130, 0;\nmov.b64 a, {%128, %131};\nmov.b64 b, {%129, 0x40000040};\n"
    "wgmma.mma_async.sync.aligned.m64n256k16.f32.bf16.bf16 {%0,%1,%2,%3,%4,%5,%6,%7,%8,%9,%10,%11,%12,%13,%14,%15,%16,%17,%18,%19,%20,%21,%22,%23,%24,%25,%26,%27,%28,%29,%30,%31,%32,%33,%34,%35,%36,%37,%38,%39,%40,%41,%42,%43,%44,%45,%46,%47,%48,%49,%50,%51,%52,%53,%54,%55,%56,%57,%58,%59,%60,%61,%62,%63,%64,%65,%66,%67,%68,%69,%70,%71,%72,%73,%74,%75,%76,%77,%78,%79,%80,%81,%82,%83,%84,%85,%86,%87,%88,%89,%90,%91,%92,%93,%94,%95,%96,%97,%98,%99,%100,%101,%102,%103,%104,%105,%106,%107,%108,%109,%110,%111,%112,%113,%114,%115,%116,%117,%118,%119,%120,%121,%122,%123,%124,%125,%126,%127}, a, b, p, 1, 1, 0, 1;\n}\n"
    : "+f"(d[0]),"+f"(d[1]),"+f"(d[2]),"+f"(d[3]),"+f"(d[4]),"+f"(d[5]),"+f"(d[6]),"+f"(d[7]),"+f"(d[8]),"+f"(d[9]),"+f"(d[10]),"+f"(d[11]),"+f"(d[12]),"+f"(d[13]),"+f"(d[14]),"+f"(d[15]),"+f"(d[16]),"+f"(d[17]),"+f"(d[18]),"+f"(d[19]),"+f"(d[20]),"+f"(d[21]),"+f"(d[22]),"+f"(d[23]),"+f"(d[24]),"+f"(d[25]),"+f"(d[26]),"+f"(d[27]),"+f"(d[28]),"+f"(d[29]),"+f"(d[30]),"+f"(d[31]),"+f"(d[32]),"+f"(d[33]),"+f"(d[34]),"+f"(d[35]),"+f"(d[36]),"+f"(d[37]),"+f"(d[38]),"+f"(d[39]),"+f"(d[40]),"+f"(d[41]),"+f"(d[42]),"+f"(d[43]),"+f"(d[44]),"+f"(d[45]),"+f"(d[46]),"+f"(d[47]),"+f"(d[48]),"+f"(d[49]),"+f"(d[50]),"+f"(d[51]),"+f"(d[52]),"+f"(d[53]),"+f"(d[54]),"+f"(d[55]),"+f"(d[56]),"+f"(d[57]),"+f"(d[58]),"+f"(d[59]),"+f"(d[60]),"+f"(d[61]),"+f"(d[62]),"+f"(d[63]),"+f"(d[64]),"+f"(d[65]),"+f"(d[66]),"+f"(d[67]),"+f"(d[68]),"+f"(d[69]),"+f"(d[70]),"+f"(d[71]),"+f"(d[72]),"+f"(d[73]),"+f"(d[74]),"+f"(d[75]),"+f"(d[76]),"+f"(d[77]),"+f"(d[78]),"+f"(d[79]),"+f"(d[80]),"+f"(d[81]),"+f"(d[82]),"+f"(d[83]),"+f"(d[84]),"+f"(d[85]),"+f"(d[86]),"+f"(d[87]),"+f"(d[88]),"+f"(d[89]),"+f"(d[90]),"+f"(d[91]),"+f"(d[92]),"+f"(d[93]),"+f"(d[94]),"+f"(d[95]),"+f"(d[96]),"+f"(d[97]),"+f"(d[98]),"+f"(d[99]),"+f"(d[100]),"+f"(d[101]),"+f"(d[102]),"+f"(d[103]),"+f"(d[104]),"+f"(d[105]),"+f"(d[106]),"+f"(d[107]),"+f"(d[108]),"+f"(d[109]),"+f"(d[110]),"+f"(d[111]),"+f"(d[112]),"+f"(d[113]),"+f"(d[114]),"+f"(d[115]),"+f"(d[116]),"+f"(d[117]),"+f"(d[118]),"+f"(d[119]),"+f"(d[120]),"+f"(d[121]),"+f"(d[122]),"+f"(d[123]),"+f"(d[124]),"+f"(d[125]),"+f"(d[126]),"+f"(d[127])
    : "r"(da), "r"(db), "r"(sd), "r"(ha));
}
__device__ __forceinline__ void wgmma_ss_n128(float (&d)[64], uint32_t da, uint32_t ha, uint32_t db, int sd) {
  asm volatile("{\n.reg .pred p;\n.reg .b64 a, b;\nsetp.ne.b32 p, %66, 0;\nmov.b64 a, {%64, %67};\nmov.b64 b, {%65, 0x40000040};\n"
    "wgmma.mma_async.sync.aligned.m64n128k16.f32.bf16.bf16 {%0,%1,%2,%3,%4,%5,%6,%7,%8,%9,%10,%11,%12,%13,%14,%15,%16,%17,%18,%19,%20,%21,%22,%23,%24,%25,%26,%27,%28,%29,%30,%31,%32,%33,%34,%35,%36,%37,%38,%39,%40,%41,%42,%43,%44,%45,%46,%47,%48,%49,%50,%51,%52,%53,%54,%55,%56,%57,%58,%59,%60,%61,%62,%63}, a, b, p, 1, 1, 0, 1;\n}\n"
    : "+f"(d[0]),"+f"(d[1]),"+f"(d[2]),"+f"(d[3]),"+f"(d[4]),"+f"(d[5]),"+f"(d[6]),"+f"(d[7]),"+f"(d[8]),"+f"(d[9]),"+f"(d[10]),"+f"(d[11]),"+f"(d[12]),"+f"(d[13]),"+f"(d[14]),"+f"(d[15]),"+f"(d[16]),"+f"(d[17]),"+f"(d[18]),"+f"(d[19]),"+f"(d[20]),"+f"(d[21]),"+f"(d[22]),"+f"(d[23]),"+f"(d[24]),"+f"(d[25]),"+f"(d[26]),"+f"(d[27]),"+f"(d[28]),"+f"(d[29]),"+f"(d[30]),"+f"(d[31]),"+f"(d[32]),"+f"(d[33]),"+f"(d[34]),"+f"(d[35]),"+f"(d[36]),"+f"(d[37]),"+f"(d[38]),"+f"(d[39]),"+f"(d[40]),"+f"(d[41]),"+f"(d[42]),"+f"(d[43]),"+f"(d[44]),"+f"(d[45]),"+f"(d[46]),"+f"(d[47]),"+f"(d[48]),"+f"(d[49]),"+f"(d[50]),"+f"(d[51]),"+f"(d[52]),"+f"(d[53]),"+f"(d[54]),"+f"(d[55]),"+f"(d[56]),"+f"(d[57]),"+f"(d[58]),"+f"(d[59]),"+f"(d[60]),"+f"(d[61]),"+f"(d[62]),"+f"(d[63])
    : "r"(da), "r"(db), "r"(sd), "r"(ha));
}
__device__ __forceinline__ void wgmma_ss_n40_tt(float (&d)[20], uint32_t da, uint32_t db, int sd) {
  asm volatile("{\n.reg .pred p;\n.reg .b64 a, b;\nsetp.ne.b32 p, %22, 0;\nmov.b64 a, {%20, 0x40000040};\nmov.b64 b, {%21, 0x8};\n"
    "wgmma.mma_async.sync.aligned.m64n40k16.f32.bf16.bf16 {%0,%1,%2,%3,%4,%5,%6,%7,%8,%9,%10,%11,%12,%13,%14,%15,%16,%17,%18,%19}, a, b, p, 1, 1, 1, 1;\n}\n"
    : "+f"(d[0]),"+f"(d[1]),"+f"(d[2]),"+f"(d[3]),"+f"(d[4]),"+f"(d[5]),"+f"(d[6]),"+f"(d[7]),"+f"(d[8]),"+f"(d[9]),"+f"(d[10]),"+f"(d[11]),"+f"(d[12]),"+f"(d[13]),"+f"(d[14]),"+f"(d[15]),"+f"(d[16]),"+f"(d[17]),"+f"(d[18]),"+f"(d[19])
    : "r"(da), "r"(db), "r"(sd));
}
__device__ __forceinline__ void wgmma_ss_n32(float (&d)[16], uint32_t da, uint32_t db, int sd) {
  asm volatile("{\n.reg .pred p;\n.reg .b64 a, b;\nsetp.ne.b32 p, %18, 0;\nmov.b64 a, {%16, 0x40000040};\nmov.b64 b, {%17, 0x80000020};\n"
    "wgmma.mma_async.sync.aligned.m64n32k16.f32.bf16.bf16 {%0,%1,%2,%3,%4,%5,%6,%7,%8,%9,%10,%11,%12,%13,%14,%15}, a, b, p, 1, 1, 0, 1;\n}\n"
    : "+f"(d[0]),"+f"(d[1]),"+f"(d[2]),"+f"(d[3]),"+f"(d[4]),"+f"(d[5]),"+f"(d[6]),"+f"(d[7]),"+f"(d[8]),"+f"(d[9]),"+f"(d[10]),"+f"(d[11]),"+f"(d[12]),"+f"(d[13]),"+f"(d[14]),"+f"(d[15])
    : "r"(da), "r"(db), "r"(sd));
}
__device__ __forceinline__ void wgmma_rs_n40(float (&d)[20], uint32_t a0, uint32_t a1, uint32_t a2, uint32_t a3, uint32_t db, int sd) {
  asm volatile("{\n.reg .pred p;\n.reg .b64 b;\nsetp.ne.b32 p, %25, 0;\nmov.b64 b, {%24, 0x10};\n"
    "wgmma.mma_async.sync.aligned.m64n40k16.f32.bf16.bf16 {%0,%1,%2,%3,%4,%5,%6,%7,%8,%9,%10,%11,%12,%13,%14,%15,%16,%17,%18,%19}, {%20,%21,%22,%23}, b, p, 1, 1, 1;\n}\n"
    : "+f"(d[0]),"+f"(d[1]),"+f"(d[2]),"+f"(d[3]),"+f"(d[4]),"+f"(d[5]),"+f"(d[6]),"+f"(d[7]),"+f"(d[8]),"+f"(d[9]),"+f"(d[10]),"+f"(d[11]),"+f"(d[12]),"+f"(d[13]),"+f"(d[14]),"+f"(d[15]),"+f"(d[16]),"+f"(d[17]),"+f"(d[18]),"+f"(d[19])
    : "r"(a0), "r"(a1), "r"(a2), "r"(a3), "r"(db), "r"(sd));
}
__device__ __forceinline__ void wgmma_r1_n256(float (&d)[128], uint32_t da, uint32_t db, int sd) {
  asm volatile("{\n.reg .pred p;\n.reg .b64 a, b;\nsetp.ne.b32 p, %130, 0;\nmov.b64 a, {%128, 0x8};\nmov.b64 b, {%129, 0x6};\n"
    "wgmma.mma_async.sync.aligned.m64n256k16.f32.bf16.bf16 {%0,%1,%2,%3,%4,%5,%6,%7,%8,%9,%10,%11,%12,%13,%14,%15,%16,%17,%18,%19,%20,%21,%22,%23,%24,%25,%26,%27,%28,%29,%30,%31,%32,%33,%34,%35,%36,%37,%38,%39,%40,%41,%42,%43,%44,%45,%46,%47,%48,%49,%50,%51,%52,%53,%54,%55,%56,%57,%58,%59,%60,%61,%62,%63,%64,%65,%66,%67,%68,%69,%70,%71,%72,%73,%74,%75,%76,%77,%78,%79,%80,%81,%82,%83,%84,%85,%86,%87,%88,%89,%90,%91,%92,%93,%94,%95,%96,%97,%98,%99,%100,%101,%102,%103,%104,%105,%106,%107,%108,%109,%110,%111,%112,%113,%114,%115,%116,%117,%118,%119,%120,%121,%122,%123,%124,%125,%126,%127}, a, b, p, 1, 1, 0, 1;\n}\n"
    : "+f"(d[0]),"+f"(d[1]),"+f"(d[2]),"+f"(d[3]),"+f"(d[4]),"+f"(d[5]),"+f"(d[6]),"+f"(d[7]),"+f"(d[8]),"+f"(d[9]),"+f"(d[10]),"+f"(d[11]),"+f"(d[12]),"+f"(d[13]),"+f"(d[14]),"+f"(d[15]),"+f"(d[16]),"+f"(d[17]),"+f"(d[18]),"+f"(d[19]),"+f"(d[20]),"+f"(d[21]),"+f"(d[22]),"+f"(d[23]),"+f"(d[24]),"+f"(d[25]),"+f"(d[26]),"+f"(d[27]),"+f"(d[28]),"+f"(d[29]),"+f"(d[30]),"+f"(d[31]),"+f"(d[32]),"+f"(d[33]),"+f"(d[34]),"+f"(d[35]),"+f"(d[36]),"+f"(d[37]),"+f"(d[38]),"+f"(d[39]),"+f"(d[40]),"+f"(d[41]),"+f"(d[42]),"+f"(d[43]),"+f"(d[44]),"+f"(d[45]),"+f"(d[46]),"+f"(d[47]),"+f"(d[48]),"+f"(d[49]),"+f"(d[50]),"+f"(d[51]),"+f"(d[52]),"+f"(d[53]),"+f"(d[54]),"+f"(d[55]),"+f"(d[56]),"+f"(d[57]),"+f"(d[58]),"+f"(d[59]),"+f"(d[60]),"+f"(d[61]),"+f"(d[62]),"+f"(d[63]),"+f"(d[64]),"+f"(d[65]),"+f"(d[66]),"+f"(d[67]),"+f"(d[68]),"+f"(d[69]),"+f"(d[70]),"+f"(d[71]),"+f"(d[72]),"+f"(d[73]),"+f"(d[74]),"+f"(d[75]),"+f"(d[76]),"+f"(d[77]),"+f"(d[78]),"+f"(d[79]),"+f"(d[80]),"+f"(d[81]),"+f"(d[82]),"+f"(d[83]),"+f"(d[84]),"+f"(d[85]),"+f"(d[86]),"+f"(d[87]),"+f"(d[88]),"+f"(d[89]),"+f"(d[90]),"+f"(d[91]),"+f"(d[92]),"+f"(d[93]),"+f"(d[94]),"+f"(d[95]),"+f"(d[96]),"+f"(d[97]),"+f"(d[98]),"+f"(d[99]),"+f"(d[100]),"+f"(d[101]),"+f"(d[102]),"+f"(d[103]),"+f"(d[104]),"+f"(d[105]),"+f"(d[106]),"+f"(d[107]),"+f"(d[108]),"+f"(d[109]),"+f"(d[110]),"+f"(d[111]),"+f"(d[112]),"+f"(d[113]),"+f"(d[114]),"+f"(d[115]),"+f"(d[116]),"+f"(d[117]),"+f"(d[118]),"+f"(d[119]),"+f"(d[120]),"+f"(d[121]),"+f"(d[122]),"+f"(d[123]),"+f"(d[124]),"+f"(d[125]),"+f"(d[126]),"+f"(d[127])
    : "r"(da), "r"(db), "r"(sd));
}
__device__ __forceinline__ void wgmma_r1_n128(float (&d)[64], uint32_t da, uint32_t db, int sd) {
  asm volatile("{\n.reg .pred p;\n.reg .b64 a, b;\nsetp.ne.b32 p, %66, 0;\nmov.b64 a, {%64, 0x8};\nmov.b64 b, {%65, 0x6};\n"
    "wgmma.mma_async.sync.aligned.m64n128k16.f32.bf16.bf16 {%0,%1,%2,%3,%4,%5,%6,%7,%8,%9,%10,%11,%12,%13,%14,%15,%16,%17,%18,%19,%20,%21,%22,%23,%24,%25,%26,%27,%28,%29,%30,%31,%32,%33,%34,%35,%36,%37,%38,%39,%40,%41,%42,%43,%44,%45,%46,%47,%48,%49,%50,%51,%52,%53,%54,%55,%56,%57,%58,%59,%60,%61,%62,%63}, a, b, p, 1, 1, 0, 1;\n}\n"
    : "+f"(d[0]),"+f"(d[1]),"+f"(d[2]),"+f"(d[3]),"+f"(d[4]),"+f"(d[5]),"+f"(d[6]),"+f"(d[7]),"+f"(d[8]),"+f"(d[9]),"+f"(d[10]),"+f"(d[11]),"+f"(d[12]),"+f"(d[13]),"+f"(d[14]),"+f"(d[15]),"+f"(d[16]),"+f"(d[17]),"+f"(d[18]),"+f"(d[19]),"+f"(d[20]),"+f"(d[21]),"+f"(d[22]),"+f"(d[23]),"+f"(d[24]),"+f"(d[25]),"+f"(d[26]),"+f"(d[27]),"+f"(d[28]),"+f"(d[29]),"+f"(d[30]),"+f"(d[31]),"+f"(d[32]),"+f"(d[33]),"+f"(d[34]),"+f"(d[35]),"+f"(d[36]),"+f"(d[37]),"+f"(d[38]),"+f"(d[39]),"+f"(d[40]),"+f"(d[41]),"+f"(d[42]),"+f"(d[43]),"+f"(d[44]),"+f"(d[45]),"+f"(d[46]),"+f"(d[47]),"+f"(d[48]),"+f"(d[49]),"+f"(d[50]),"+f"(d[51]),"+f"(d[52]),"+f"(d[53]),"+f"(d[54]),"+f"(d[55]),"+f"(d[56]),"+f"(d[57]),"+f"(d[58]),"+f"(d[59]),"+f"(d[60]),"+f"(d[61]),"+f"(d[62]),"+f"(d[63])
    : "r"(da), "r"(db), "r"(sd));
}

__device__ __forceinline__ uint32_t smem_u32(const void* p) { return (uint32_t)__cvta_generic_to_shared(p); }
__device__ __forceinline__ void mbar_init(uint32_t bar, uint32_t cnt) { asm volatile("mbarrier.init.shared::cta.b64 [%0], %1;" ::"r"(bar), "r"(cnt)); }
__device__ __forceinline__ void mbar_expect_tx(uint32_t bar, uint32_t bytes) { asm volatile("mbarrier.arrive.expect_tx.shared::cta.b64 _, [%0], %1;" ::"r"(bar), "r"(bytes) : "memory"); }
__device__ __forceinline__ void mbar_arrive(uint32_t bar) { asm volatile("mbarrier.arrive.shared::cta.b64 _, [%0];" ::"r"(bar) : "memory"); }
__device__ __forceinline__ void mbar_arrive_n(uint32_t bar, uint32_t n) { asm volatile("mbarrier.arrive.shared::cta.b64 _, [%0], %1;" ::"r"(bar), "r"(n) : "memory"); }
__device__ __forceinline__ void mbar_wait(uint32_t bar, uint32_t parity) {
  asm volatile("{\n.reg .pred p;\nLAB_WAIT:\nmbarrier.try_wait.parity.shared::cta.b64 p, [%0], %1;\n@p bra DONE;\nbra LAB_WAIT;\nDONE:\n}" ::"r"(bar), "r"(parity) : "memory");
}
__device__ __forceinline__ void mbar_wait2(uint32_t a, uint32_t pa, uint32_t b, uint32_t pb) {
  asm volatile("{\n.reg .pred p, q;\nLAB_WAIT:\nmbarrier.try_wait.parity.shared::cta.b64 p, [%0], %1;\nmbarrier.try_wait.parity.shared::cta.b64 q, [%2], %3;\n"
               "and.pred p, p, q;\n@p bra DONE;\nbra LAB_WAIT;\nDONE:\n}" ::"r"(a), "r"(pa), "r"(b), "r"(pb) : "memory");
}
__device__ __forceinline__ void mbar_wait3(uint32_t a, uint32_t pa, uint32_t b, uint32_t pb) {
  asm volatile("{\n.reg .pred p, q, r;\nLAB_WAIT:\nmbarrier.try_wait.parity.shared::cta.b64 p, [%0], %1;\nmbarrier.try_wait.parity.shared::cta.b64 q, [%2], %3;\n"
               "mbarrier.try_wait.parity.shared::cta.b64 r, [%2+8], %3;\nand.pred p, p, q;\nand.pred p, p, r;\n@p bra DONE;\nbra LAB_WAIT;\nDONE:\n}" ::"r"(a), "r"(pa), "r"(b), "r"(pb) : "memory");
}
__device__ __forceinline__ bool mbar_probe2(uint32_t a, uint32_t pa, uint32_t b, uint32_t pb) {
  uint32_t ok;
  asm volatile("{\n.reg .pred p, q;\nmbarrier.test_wait.parity.shared::cta.b64 p, [%1], %2;\nmbarrier.test_wait.parity.shared::cta.b64 q, [%3], %4;\n"
               "and.pred p, p, q;\nselp.u32 %0, 1, 0, p;\n}" : "=r"(ok) : "r"(a), "r"(pa), "r"(b), "r"(pb) : "memory");
  return ok != 0;
}
__device__ __forceinline__ void tma_load_3d(uint32_t dst, const CUtensorMap* tm, uint32_t bar, int c0, int c1, int c2) {
  asm volatile("cp.async.bulk.tensor.3d.shared::cluster.global.mbarrier::complete_tx::bytes [%0], [%1, {%3, %4, %5}], [%2];"
               ::"r"(dst), "l"(tm), "r"(bar), "r"(c0), "r"(c1), "r"(c2) : "memory");
}
__device__ __forceinline__ void tma_load_2d(uint32_t dst, const CUtensorMap* tm, uint32_t bar, int c0, int c1) {
  asm volatile("cp.async.bulk.tensor.2d.shared::cluster.global.mbarrier::complete_tx::bytes [%0], [%1, {%3, %4}], [%2];"
               ::"r"(dst), "l"(tm), "r"(bar), "r"(c0), "r"(c1) : "memory");
}
__device__ __forceinline__ void tma_load_w(uint32_t dst, const CUtensorMap* tm, uint32_t bar, int col, int kb) {
#pragma unroll
  for (int q = 0; q < 2; q++)
    asm volatile("cp.async.bulk.tensor.5d.shared::cluster.global.mbarrier::complete_tx::bytes [%0], [%1, {%3, %4, %4, %4, %5}], [%2];"
                 ::"r"(dst + q * 8192), "l"(tm), "r"(bar), "r"(col + q * 64), "r"(0), "r"(2 * kb) : "memory");
}
__device__ __forceinline__ void tma_prefetch_w(const CUtensorMap* tm, int col, int kb) {
#pragma unroll
  for (int q = 0; q < 2; q++)
    asm volatile("cp.async.bulk.prefetch.tensor.5d.L2.global [%0, {%1, %2, %2, %2, %3}];" ::"l"(tm), "r"(col + q * 64), "r"(0), "r"(2 * kb) : "memory");
}
__device__ __forceinline__ void bulk_load(uint32_t dst, const void* g, uint32_t bytes, uint32_t bar) {
  asm volatile("cp.async.bulk.shared::cluster.global.mbarrier::complete_tx::bytes [%0], [%1], %2, [%3];" ::"r"(dst), "l"(g), "r"(bytes), "r"(bar) : "memory");
}
__device__ __forceinline__ void prefetch_map(const CUtensorMap* tm) { asm volatile("prefetch.tensormap [%0];" ::"l"(tm) : "memory"); }
__device__ __forceinline__ void fence_async_smem() { asm volatile("fence.proxy.async.shared::cta;" ::: "memory"); }
__device__ __forceinline__ void fence_async_global() { asm volatile("fence.proxy.async.global;" ::: "memory"); }
__device__ __forceinline__ void fence_gpu() { asm volatile("fence.release.gpu;" ::: "memory"); }
__device__ __forceinline__ void st_flag(unsigned* p, unsigned v) { asm volatile("st.relaxed.gpu.global.u32 [%0], %1;" ::"l"(p), "r"(v) : "memory"); }
__device__ __forceinline__ unsigned ld_flag(const unsigned* p) { unsigned v; asm volatile("ld.relaxed.gpu.global.u32 %0, [%1];" : "=r"(v) : "l"(p) : "memory"); return v; }
__device__ __forceinline__ uint4 ldcg4(const void* p) { uint4 v; asm volatile("ld.global.cg.v4.u32 {%0,%1,%2,%3}, [%4];" : "=r"(v.x), "=r"(v.y), "=r"(v.z), "=r"(v.w) : "l"(p)); return v; }
__device__ __forceinline__ uint4 ld_pkt(const uint4* p) {
  uint4 v; asm volatile("{\n.reg .b128 t;\nld.relaxed.gpu.global.b128 t, [%4];\nmov.b128 {%0,%1,%2,%3}, t;\n}" : "=r"(v.x), "=r"(v.y), "=r"(v.z), "=r"(v.w) : "l"(p) : "memory"); return v;
}
__device__ __forceinline__ void st_pkt(uint4* p, uint32_t a, uint32_t b, uint32_t c, uint32_t tag) {
  asm volatile("{\n.reg .b128 t;\nmov.b128 t, {%1,%2,%3,%4};\nst.relaxed.gpu.global.b128 [%0], t;\n}" ::"l"(p), "r"(a), "r"(b), "r"(c), "r"(tag) : "memory");
}
__device__ __forceinline__ void st_v4(uint4* p, uint32_t a, uint32_t b, uint32_t c, uint32_t d) { asm volatile("st.relaxed.gpu.global.v4.u32 [%0], {%1,%2,%3,%4};" ::"l"(p), "r"(a), "r"(b), "r"(c), "r"(d) : "memory"); }
__device__ __forceinline__ void stg128(uint4* p, uint4 v) { asm volatile("st.global.v4.u32 [%0], {%1,%2,%3,%4};" ::"l"(p), "r"(v.x), "r"(v.y), "r"(v.z), "r"(v.w) : "memory"); }
__device__ __forceinline__ void sts32(uint32_t addr, uint32_t a) { asm volatile("st.shared.u32 [%0], %1;" ::"r"(addr), "r"(a) : "memory"); }
__device__ __forceinline__ void sts64(uint32_t addr, uint32_t a, uint32_t b) { asm volatile("st.shared.v2.u32 [%0], {%1,%2};" ::"r"(addr), "r"(a), "r"(b) : "memory"); }
__device__ __forceinline__ uint32_t mul2(uint32_t a, uint32_t b) { uint32_t r; asm("mul.rn.bf16x2 %0, %1, %2;" : "=r"(r) : "r"(a), "r"(b)); return r; }
__device__ __forceinline__ uint32_t add2(uint32_t a, uint32_t b) { uint32_t r; asm("add.rn.bf16x2 %0, %1, %2;" : "=r"(r) : "r"(a), "r"(b)); return r; }
__device__ __forceinline__ bool elect() {
  uint32_t p; asm volatile("{\n.reg .pred q;\nelect.sync _|q, 0xffffffff;\nselp.u32 %0, 1, 0, q;\n}" : "=r"(p)); return p != 0;
}
__device__ __forceinline__ void wgmma_fence() { asm volatile("wgmma.fence.sync.aligned;" ::: "memory"); }
__device__ __forceinline__ void wgmma_commit() { asm volatile("wgmma.commit_group.sync.aligned;" ::: "memory"); }
template <int N> __device__ __forceinline__ void wgmma_wait() { asm volatile("wgmma.wait_group.sync.aligned %0;" ::"n"(N) : "memory"); }
template <int N> __device__ __forceinline__ void fence_regs(float (&d)[N]) {
#pragma unroll
  for (int i = 0; i < N; i++) asm volatile("" : "+f"(d[i])::"memory");
}
template <int R> __device__ __forceinline__ void reg_alloc() { asm volatile("setmaxnreg.inc.sync.aligned.u32 %0;" ::"n"(R)); }
template <int R> __device__ __forceinline__ void reg_dealloc() { asm volatile("setmaxnreg.dec.sync.aligned.u32 %0;" ::"n"(R)); }
__device__ __forceinline__ void wg_bar(int w) { asm volatile("bar.sync %0, 128;" ::"r"(w + 1) : "memory"); }
__device__ __forceinline__ constexpr uint32_t desc_lo(uint32_t addr, uint32_t lbo) { return (addr >> 4) + ((lbo >> 4) << 16); }
__device__ __forceinline__ uint32_t pack2(float lo, float hi) { uint32_t r; asm("cvt.rn.bf16x2.f32 %0, %1, %2;" : "=r"(r) : "f"(hi), "f"(lo)); return r; }
__device__ __forceinline__ float lo16(uint32_t v) { return __uint_as_float(v << 16); }
__device__ __forceinline__ float hi16(uint32_t v) { return __uint_as_float(v & 0xFFFF0000u); }
__device__ __forceinline__ float ex2(float x) { float r; asm("ex2.approx.ftz.f32 %0, %1;" : "=f"(r) : "f"(x)); return r; }
__device__ __forceinline__ float rcp(float x) { float r; asm("rcp.approx.ftz.f32 %0, %1;" : "=f"(r) : "f"(x)); return r; }
__device__ __forceinline__ uint32_t movm(uint32_t a) { uint32_t d; asm volatile("movmatrix.sync.aligned.m8n8.trans.b16 %0, %1;" : "=r"(d) : "r"(a)); return d; }
__device__ __forceinline__ void stsm4(uint32_t addr, uint32_t a, uint32_t b, uint32_t c, uint32_t d) {
  asm volatile("stmatrix.sync.aligned.m8n8.x4.shared.b16 [%0], {%1,%2,%3,%4};" ::"r"(addr), "r"(a), "r"(b), "r"(c), "r"(d) : "memory");
}
__device__ __forceinline__ void ldsm4(uint32_t addr, uint32_t (&r)[4]) {
  asm volatile("ldmatrix.sync.aligned.m8n8.x4.shared.b16 {%0,%1,%2,%3}, [%4];" : "=r"(r[0]), "=r"(r[1]), "=r"(r[2]), "=r"(r[3]) : "r"(addr) : "memory");
}
__device__ __forceinline__ void sts128(uint32_t addr, uint32_t a, uint32_t b, uint32_t c, uint32_t d) {
  asm volatile("st.shared.v4.u32 [%0], {%1,%2,%3,%4};" ::"r"(addr), "r"(a), "r"(b), "r"(c), "r"(d) : "memory");
}
__device__ __forceinline__ void lds128(uint32_t addr, uint32_t& a, uint32_t& b, uint32_t& c, uint32_t& d) {
  asm volatile("ld.shared.v4.u32 {%0,%1,%2,%3}, [%4];" : "=r"(a), "=r"(b), "=r"(c), "=r"(d) : "r"(addr) : "memory");
}
__device__ __forceinline__ float lds32f(uint32_t addr) { float v; asm volatile("ld.shared.f32 %0, [%1];" : "=f"(v) : "r"(addr) : "memory"); return v; }
__device__ __forceinline__ float2 lds64f(uint32_t addr) { float2 v; asm volatile("ld.shared.v2.f32 {%0,%1}, [%2];" : "=f"(v.x), "=f"(v.y) : "r"(addr) : "memory"); return v; }
__device__ __forceinline__ void mma16816(float (&d)[4], uint32_t a0, uint32_t a1, uint32_t a2, uint32_t a3, uint32_t b0, uint32_t b1) {
  asm("mma.sync.aligned.m16n8k16.row.col.f32.bf16.bf16.f32 {%0,%1,%2,%3}, {%4,%5,%6,%7}, {%8,%9}, {%0,%1,%2,%3};"
      : "+f"(d[0]), "+f"(d[1]), "+f"(d[2]), "+f"(d[3]) : "r"(a0), "r"(a1), "r"(a2), "r"(a3), "r"(b0), "r"(b1));
}
__device__ __forceinline__ void mma1688(float (&d)[4], uint32_t a0, uint32_t a1, uint32_t b0) {
  asm("mma.sync.aligned.m16n8k8.row.col.f32.bf16.bf16.f32 {%0,%1,%2,%3}, {%4,%5}, {%6}, {%0,%1,%2,%3};"
      : "+f"(d[0]), "+f"(d[1]), "+f"(d[2]), "+f"(d[3]) : "r"(a0), "r"(a1), "r"(b0));
}

__device__ __forceinline__ float qsum(float v) { v += __shfl_xor_sync(0xffffffffu, v, 1); v += __shfl_xor_sync(0xffffffffu, v, 2); return v; }

constexpr int NCTA = 132;
#define NB_ 6
#define NA_ 5
constexpr int NB = NB_;
constexpr int NA = NA_;
constexpr uint32_t SLOT = 16384;
constexpr uint32_t SB = 1024;
constexpr uint32_t OFF_B = 0;
constexpr uint32_t OFF_A = NB * SLOT;
constexpr uint32_t OFF_S = OFF_A + NA * SLOT;
constexpr uint32_t OFF_T = OFF_S + 20480;
constexpr uint32_t OFF_CS = OFF_T + 24576;
constexpr uint32_t OFF_MR = OFF_CS + 4640;
constexpr uint32_t OFF_BAR = OFF_MR + 512;
constexpr uint32_t OFF_MA = OFF_S, OFF_MB = OFF_CS - 2048;
constexpr uint32_t BAR_FULLB = OFF_BAR;
constexpr uint32_t BAR_FULLA = BAR_FULLB + 64;
constexpr uint32_t BAR_EMPTYB = BAR_FULLA + 64;
constexpr uint32_t BAR_EMPTYA = BAR_EMPTYB + 64;
constexpr uint32_t BAR_SIGP = BAR_EMPTYA + 64;
constexpr uint32_t BAR_SIGT = BAR_SIGP + 24;
constexpr uint32_t BAR_STAT = BAR_SIGP + 64;
constexpr uint32_t BAR_HALO = BAR_STAT + 16;
constexpr uint32_t BAR_CS = BAR_HALO + 8;
constexpr uint32_t BAR_WPHI = BAR_CS + 16;
constexpr uint32_t BAR_KV = BAR_WPHI + 8;
constexpr uint32_t BAR_STG = BAR_KV + 16;
constexpr uint32_t BAR_EPOCH = BAR_STG + 48;
constexpr uint32_t BAR_LAND = OFF_BAR + 7 * 64;
constexpr uint32_t OFF_EPOCH = OFF_BAR + 8 * 64;
static_assert(BAR_EPOCH < BAR_LAND, "barriers");
constexpr uint32_t SMEM_BYTES = OFF_EPOCH + 8;
static_assert(SMEM_BYTES <= 232448 && NB % 2 == 0 && NB <= 8 && NA <= 6, "smem");

#define CREGS 224
#define PREGS 56
#define PF1 19
#define PF2 21
#define PRE_A 2
#define PRE_B 4
#define CSB 4
#define CSNEED 0xF001u
#define XR 1
#define PS0 1
#define PS1 3
#define PSW 0
#define SD 1000
#define KSPLIT 12
#define KEEP 16
#define NJ 3
#define KSL 1000
#define PSL 0
#define KVS 12
#define D2 2000
#define D3 1500
#define G0 50
#define MAP 3
#define PMAP 0x76321450u
#define ZO 0
#define XA 3
#define XS 1
#define CP 500
#define CD 0
#define S0 500
#define NS 2
#define XO 0
#define SW 2
#define SA 1
#define SB_ 4
#define XD 250
#define ND0 1
#define KC 8
#define CO 0
#define SE 500
#define PD 0
#define DEFER 3
#define DEFL 2
#define TSK 3
#define TSL 3
constexpr int NTHREADS = 384;

struct Params {
  CUtensorMap mx;
  CUtensorMap mw[3];
  CUtensorMap mwo[2];
  CUtensorMap mcs[2];
  CUtensorMap mwphi;
  uint4* out;
};

#define XBUF(L) 1
__device__ __align__(256) uint4 g_img[XBUF(3) + 1][16][16][1024];
__device__ __forceinline__ uint32_t img_code(bool isx, int L) { return isx ? (L & 1) | (L & 2) << 15 : ~L & 1; }
__device__ __forceinline__ uint32_t img_mask(bool isx) { return isx ? 0x10001u : 1u; }
__device__ __align__(256) uint4 g_wf[2][8][16][1024];
__device__ __align__(256) uint4 g_stats[16][2][8][32];
__device__ __align__(256) uint4 g_halo[16][8][2][256];
__device__ __align__(256) float g_cs[2][2][3072];
__device__ __align__(256) uint4 g_kvpart[8][16][2][544];
__device__ __align__(256) uint4 g_kvfin[8][16][80];
__device__ __align__(256) unsigned g_hint[16][32];
__device__ __align__(256) unsigned g_jflag[3][8][32];
__device__ unsigned g_ctr;
__device__ __forceinline__ unsigned vblock() {
  unsigned s;
  asm volatile("mov.u32 %0, %%smid;" : "=r"(s));
  const unsigned r = s & 1;
  s >>= 1;
  const unsigned t = s - 32, q = (t * 37) >> 8;
  const unsigned hi = s < 60 ? 12 + (t - 7 * q) * 8 + q : (s < 62 ? s + 4 : s - 58);
  unsigned b = 2 * (s < 32 ? (s & 7) * 8 + (s >> 3) : hi) + r;
  if (b < 128) b = (b & 15) | ((PMAP >> ((b >> 4) * 4)) & 7) << 4;
  if (s >= 62) b = 8 + 4 * r + s - 62;
  unsigned n;
  asm volatile("mov.u32 %0, %%nsmid;" : "=r"(n));
  return __shfl_sync(0xffffffffu, n == NCTA ? b : blockIdx.x, 0);
}
#define TS(who, id) do {} while (0)
#define TSW(id) do {} while (0)

#define TSH(id) do {} while (0)
#define TSMASK 0xFFFF
#define TSL_(a) do { if ((TSMASK >> (a)) & 1) TSW((a) + L * 12); } while (0)
__device__ __forceinline__ int cta_m(unsigned b) { return ((b >> 2) & 12) | (b & 3); }
__device__ __forceinline__ int cta_j(unsigned b) { return ((b >> 2) & 3) | ((b >> 4) & 4); }
struct Ring { uint32_t s, ph; };
template <int N> __device__ __forceinline__ void adv(Ring& r) { if (++r.s == N) { r.s = 0; r.ph ^= 1; } }
template <int N> __device__ __forceinline__ void rewind2(Ring& r) { if (r.s < 2) { r.s += N - 2; r.ph ^= 1; } else r.s -= 2; }
__device__ __forceinline__ int other_tile(int t, int j) { return (t == (j | 4) ? 7 : t) ^ (~j & 4); }
__device__ __forceinline__ int o_order(int i, int j) {
  if (i < 2) return 2 * j + i;
  const int odd = i >= 9;
  return 2 * other_tile(i - 2 - 7 * odd, j) + odd;
}
__device__ __forceinline__ int kv_order(int i, int j, int L) { return L > 0 ? o_order(i, j) : (i + 14 + 2 * (j & 4)) & 15; }

__device__ __forceinline__ unsigned poll_flags(const unsigned* f, int n, unsigned need, unsigned tag) {
  const int lane = threadIdx.x & 31;
  unsigned mask; int it = 0;
  do {
    unsigned v = lane < n ? ld_flag(f + lane) : 0u;
    mask = __ballot_sync(0xffffffffu, lane < n && (int)(v - tag) >= 0);
    if (++it > (1 << 22)) __trap();
  } while ((mask & need) != need);
  fence_async_global();
  return mask;
}
template <bool WAIT = true>
__device__ __forceinline__ unsigned get_tag(uint32_t sb) {
  if (WAIT) mbar_wait(sb + BAR_EPOCH, 0);
  unsigned t; asm volatile("ld.shared.u32 %0, [%1];" : "=r"(t) : "r"(sb + OFF_EPOCH) : "memory");
  return t;
}

__device__ __forceinline__ int lane_id() { int l; asm volatile("mov.u32 %0, %%laneid;" : "=r"(l)); return l; }
__device__ __forceinline__ unsigned seq4(unsigned tag, int L) { return 8u | ((tag & 1u) << 2) | (unsigned)L; }
constexpr float LOG2E = 1.4426950408889634f;

__device__ __forceinline__ float bb_fence(int never, const void* p = &g_ctr, uint32_t keep = 0) {
  while (never < 0) never = ld_flag((const unsigned*)p) + keep;
  return __int_as_float(never >> 30);
}
__device__ __forceinline__ uint32_t solid(uint32_t v) { return __shfl_sync(0xffffffffu, v, threadIdx.x & 31); }
template <class T> __device__ __forceinline__ T* solid(T* p) { return (T*)__shfl_sync(0xffffffffu, (unsigned long long)p, threadIdx.x & 31); }
constexpr uint32_t HA128 = 0x40000040u, HA64 = 0x80000040u;
struct Ctx {
  static constexpr uint32_t sb = SB;
  uint32_t ab, da0;
  int w, warp, lane, g, c;
  int goff;
  __device__ __forceinline__ int m() const { return goff >> 14; }
  __device__ __forceinline__ int j() const { return (goff >> 4) & 7; }
  bool elected;
  Ring ra, rb;
  uint32_t pa, pb;
  uint32_t ha, k2;
  uint32_t mrow, mxor, mhi;
  __device__ __forceinline__ uint32_t aslot(uint32_t s) const { return ab + s * SLOT; }
  __device__ __forceinline__ uint32_t fullA(uint32_t s) const { return sb + BAR_FULLA + s * 8; }
  __device__ __forceinline__ uint32_t fullB(uint32_t s) const { return sb + BAR_FULLB + s * 8; }
  __device__ __forceinline__ void releaseA(uint32_t s) const { if (elected) mbar_arrive(sb + BAR_EMPTYA + s * 8); }
  __device__ __forceinline__ void releaseB(uint32_t s) const { if (elected) mbar_arrive(sb + BAR_EMPTYB + s * 8); }
  __device__ __forceinline__ uint32_t maddr(uint32_t tile, uint32_t ch) const { return tile + mrow + (((ch + mhi) ^ mxor) << 4); }
  __device__ __forceinline__ uint32_t oo() const { return warp * 128 + g * 4 + (c ^ (g >> 1)); }
  __device__ __forceinline__ uint4* img(int b, int hp) const { return ip + (b * 256 + hp) * 1024; }
  uint4* ip;
  uint32_t so;
  __device__ __forceinline__ uint32_t held(int i) const { return ra.s + i < 2 ? ra.s + i + NA - 2 : ra.s + i - 2; }
};

template <int N, bool FIRST, bool O = true>
__device__ __forceinline__ void gemm_issue(float (&acc)[N / 2], Ctx& x, bool ready = false) {
  if (!ready) {
    if (N == 256) mbar_wait3(x.fullA(x.ra.s), x.ra.ph, x.fullB(x.rb.s), x.rb.ph);
    else mbar_wait2(x.fullA(x.ra.s), x.ra.ph, x.fullB(x.rb.s), x.rb.ph);
  }
  const uint32_t da = x.da0 + x.ra.s * (SLOT / 16), db = desc_lo(SB + OFF_B, 8192) + x.rb.s * (SLOT / 16);
  wgmma_fence();
#pragma unroll
  for (int k = 0; k < 4; k++) {
    const uint32_t a = da + (k >> 1) * (O ? 32 : x.k2) + (k & 1) * 2, ha = O ? HA64 : x.ha;
    if constexpr (N == 256) wgmma_ss_n256(acc, a, ha, db + 128 * k, !(FIRST && k == 0));
    else wgmma_ss_n128(acc, a, ha, db + 128 * k, !(FIRST && k == 0));
  }
  wgmma_commit();
}
template <int N>
__device__ __forceinline__ void gemm_next(Ctx& x) {
  x.pa = x.ra.s; x.pb = x.rb.s;
  if (N == 256) x.rb.s++;
  adv<NA>(x.ra); adv<NB>(x.rb);
}
template <int N>
__device__ __forceinline__ void gemm_release(Ctx& x, bool relA) {
  if (relA) x.releaseA(x.pa);
  x.releaseB(x.pb);
  if (N == 256) x.releaseB(x.pb + 1);
}
template <int N>
__device__ __forceinline__ void gemm_retire(Ctx& x, bool relA) { wgmma_wait<1>(); gemm_release<N>(x, relA); gemm_next<N>(x); }
template <bool O = true>
__device__ __forceinline__ void gemm_run(float (&acc)[64], Ctx& x, int n, int hold, int n4 = 0) {
  bool ready = false;
#pragma unroll 1
  for (; n > 0; n--) {
    gemm_issue<128, false, O>(acc, x, ready);
    const uint32_t pa = x.pa, pb = x.pb;
    gemm_next<128>(x);
    ready = mbar_probe2(x.fullA(x.ra.s), x.ra.ph, x.fullB(x.rb.s), x.rb.ph);
    wgmma_wait<1>();
    if (n > hold) x.releaseA(pa);
    x.releaseB(pb);
  }
}
__device__ __forceinline__ void gemm_end(float (&acc)[64], Ctx& x) { wgmma_wait<0>(); fence_regs(acc); gemm_release<128>(x, false); }

__device__ __forceinline__ void rows_load(uint4* r, uint32_t tile, const Ctx& x) {
#pragma unroll
  for (int q = 0; q < 4; q++) {
    const uint32_t row = x.warp * 16 + 4 * q + (x.lane >> 3);
    lds128(tile + row * 128 + (((x.lane & 7) ^ (row & 7)) << 4), r[q].x, r[q].y, r[q].z, r[q].w);
  }
}
__device__ __forceinline__ void rows_store(const uint4* r, uint4* g) {
#pragma unroll
  for (int q = 0; q < 4; q++) stg128(g + q * 1024, r[q]);
}
__device__ __forceinline__ void publish(int id, const Ctx& x) { __syncwarp(); if (x.lane == 0) mbar_arrive(x.sb + BAR_SIGP + id * 8); }
__device__ __forceinline__ uint32_t img_tag(uint32_t v, bool isx, int L, const Ctx& x) {
  const uint32_t mk = ((x.lane ^ (x.warp * 4)) & 7) ? 0u : img_mask(isx);
  return (v & ~mk) | (img_code(isx, L) & mk);
}
__device__ __forceinline__ void img_tag(uint4 (&r)[4], bool isx, int L, const Ctx& x) {
#pragma unroll
  for (int q = 0; q < 4; q++) { uint32_t& v = q == 0 ? r[q].x : (q == 1 ? r[q].y : (q == 2 ? r[q].z : r[q].w)); v = img_tag(v, isx, L, x); }
}
__device__ __forceinline__ void img_store(const uint4 (&r)[4], uint4* g) {
#pragma unroll
  for (int q = 0; q < 4; q++) stg128(g + q * 32, r[q]);
}
__device__ __forceinline__ void img_sts(const uint4 (&r)[4], uint32_t tile, const Ctx& x) {
#pragma unroll
  for (int q = 0; q < 4; q++) sts128(tile + x.so + q * 512, r[q].x, r[q].y, r[q].z, r[q].w);
}
__device__ __forceinline__ void img_load(uint32_t (&v)[16], uint32_t tile, const Ctx& x) {
#pragma unroll
  for (int q = 0; q < 4; q++) lds128(tile + x.so + q * 512, v[4 * q], v[4 * q + 1], v[4 * q + 2], v[4 * q + 3]);
}
__device__ __forceinline__ void img_unpack(float* a, const uint32_t (&v)[16]) {
#pragma unroll
  for (int q = 0; q < 16; q++) { a[4 * (q & 7) + 2 * (q >> 3)] = lo16(v[q]); a[4 * (q & 7) + 2 * (q >> 3) + 1] = hi16(v[q]); }
}

template <int N>
__device__ __forceinline__ void stats_acc(const float* a, float (&t)[4]) {
#pragma unroll
  for (int i = 0; i < N; i++) { t[i & 2] += a[i]; t[(i & 2) + 1] = fmaf(a[i], a[i], t[(i & 2) + 1]); }
}
__device__ __forceinline__ void stats_send(float (&t)[4], int L, const Ctx& x) {
  const unsigned seq = seq4(get_tag<false>(x.sb), L);
#pragma unroll
  for (int q = 0; q < 4; q++) t[q] = qsum(t[q]);
  if (x.c == 0) st_pkt(&g_stats[x.m()][x.w][x.j()][x.warp * 8 + x.g], __float_as_uint(t[0]), __float_as_uint(t[1]), __float_as_uint(t[2]), (__float_as_uint(t[3]) & ~15u) | seq);
}
__device__ __forceinline__ void out_epilogue(const float (&acc)[64], uint4 (&r1)[4], float (&t)[4], uint4* g, int L, Ctx& x) {
  const uint32_t t0 = x.aslot(x.ra.s), t1 = x.aslot(x.ra.s + 1 == NA ? 0 : x.ra.s + 1);
  if (L == 3) {
#pragma unroll
    for (int p = 0; p < 8; p++) {
      stsm4(x.maddr(p < 4 ? t0 : t1, (p & 3) * 2), pack2(acc[8 * p], acc[8 * p + 1]), pack2(acc[8 * p + 2], acc[8 * p + 3]),
            pack2(acc[8 * p + 4], acc[8 * p + 5]), pack2(acc[8 * p + 6], acc[8 * p + 7]));
      if ((p & 3) == 3) { uint4 r[4]; __syncwarp(); rows_load(r, p < 4 ? t0 : t1, x); rows_store(r, g + (p >> 2) * 8); }
    }
  } else {
    auto pack16 = [&](uint4 (&r)[4], const float* a) {
#pragma unroll
      for (int q = 0; q < 4; q++) { const float* u = a + 16 * (q & 1) + (q & 2); r[q] = make_uint4(pack2(u[0], u[1]), pack2(u[4], u[5]), pack2(u[8], u[9]), pack2(u[12], u[13])); }
    };
    uint4 r0[4];
    pack16(r0, acc);
    img_tag(r0, true, L + 1, x);
    img_store(r0, x.img(XBUF(L + 1), 0));
    publish(1, x);
    const float z = bb_fence(x.goff);
    img_sts(r0, t0, x);
    pack16(r1, acc + 32);
    img_tag(r1, true, L + 1, x);
    img_sts(r1, t1, x);
    float u[4] = {z, z, z, z}, v[4] = {z, z, z, z};
    stats_acc<32>(acc, v);
    stats_acc<32>(acc + 32, u);
#pragma unroll
    for (int q = 0; q < 4; q++) t[q] = u[q] + v[q];
    mbar_wait2(x.fullB(x.rb.s), x.rb.ph, x.fullB(x.rb.s + 1), x.rb.ph);
    fence_async_smem();
    asm volatile("bar.sync %0, %1;" ::"r"(L == 1 ? x.w + 1 : 3), "r"(L == 1 ? 128 : 256) : "memory");
  }
}

struct Stats { float rstd0, rstd1; };
__device__ __forceinline__ Stats load_stats(int half, const Ctx& x) {
  const float2 u = lds64f(x.sb + OFF_MR + half * 256 + (x.warp * 8 + x.g) * 8);
  return {u.x, u.y};
}

template <int NH, int NK, class F>
__device__ __forceinline__ void hedgehog_scale(float* t, const Stats& st, const uint32_t* keep, F use) {
#pragma unroll
  for (int q = 0; q < 16 * NH; q++) t[q] *= ((q & 2) ? st.rstd1 : st.rstd0) * LOG2E;
  use();
  float m[4];
#pragma unroll
  for (int q = 0; q < 4 * NH; q++) {
    const float v = fmaxf(fmaxf(fabsf(t[4 * q]), fabsf(t[4 * q + 1])), fmaxf(fabsf(t[4 * q + 2]), fabsf(t[4 * q + 3])));
    m[q & 3] = q < 4 ? v : fmaxf(m[q & 3], v);
  }
  if (__builtin_expect(__any_sync(0xffffffffu, fmaxf(fmaxf(m[0], m[1]), fmaxf(m[2], m[3])) > 58.f), 0)) {
    float z[16 * NH + NK];
#pragma unroll
    for (int q = 0; q < 16 * NH + NK; q++) z[q] = q < 16 * NH ? t[q % (16 * NH)] : __uint_as_float(keep[q & 15]);
#pragma unroll 1
    for (int r = 0; r < 2 * NH; r++) {
      float hi = -INFINITY, lo = INFINITY;
#pragma unroll 1
      for (int i = 0; i < 16; i++) {
        const int k = (i & 6) * 2 + (i & 1) + (r & 1) * 2 + (r & 2) * 8;
        const float v = z[k];
        if (i < 8) { hi = fmaxf(hi, v); lo = fminf(lo, v); }
        else z[k] = v - fminf(fmaxf(v, lo), hi);
        if (i == 7) {
#pragma unroll 1
          for (int d = 1; d <= 2; d++) { hi = fmaxf(hi, __shfl_xor_sync(0xffffffffu, hi, d)); lo = fminf(lo, __shfl_xor_sync(0xffffffffu, lo, d)); }
          const float mid = 0.5f * hi + 0.5f * lo;
          hi = fmaxf(hi - 58.f, mid); lo = fminf(lo + 58.f, mid);
        }
      }
    }
#pragma unroll
    for (int q = 0; q < 16 * NH; q++) t[q] = z[q];
    use();
  }
}
__device__ __forceinline__ void dual_exp(const float* t, uint32_t (&f)[18], int never) {
  float e[KSPLIT];
#pragma unroll
  for (int q = 0; q < KSPLIT; q++) e[q] = ex2(q < 16 ? t[q] : -t[q & 15]);
  while (never < 0) {
#pragma unroll
    for (int i = 0; i < KSPLIT; i += 4) asm volatile("ld.shared.v4.f32 {%0,%1,%2,%3}, [%4];" : "=f"(e[i]), "=f"(e[i + 1]), "=f"(e[i + 2]), "=f"(e[i + 3]) : "r"(never + i) : "memory");
    never += __float_as_int(e[0]);
  }
#pragma unroll
  for (int q = 0; q < KSPLIT; q += 2) f[q >> 1] = pack2(e[q], e[q + 1]);
#pragma unroll
  for (int q = KSPLIT; q < 32; q += 2) f[q >> 1] = q < 16 ? pack2(ex2(t[q]), ex2(t[q + 1])) : pack2(ex2(-t[q & 15]), ex2(-t[(q & 15) + 1]));
#pragma unroll
  for (int sg = 0; sg < 2; sg++) {
    const uint32_t* u = f + 8 * sg;
    const uint32_t a = add2(add2(u[0], u[2]), add2(u[4], u[6])), b = add2(add2(u[1], u[3]), add2(u[5], u[7]));
    f[16 + sg] = add2(__byte_perm(a, b, 0x5410), __byte_perm(a, b, 0x7632));
  }
}
__device__ __forceinline__ void dual_exp_rcp(const float* t, uint32_t* f) {
#pragma unroll
  for (int q = 0; q < 8; q++) {
    const float a = ex2(t[2 * q]), b = ex2(t[2 * q + 1]), r = rcp(a * b);
    f[q] = pack2(a, b); f[8 + q] = pack2(r * b, r * a);
  }
}
__device__ __forceinline__ void cta_bar() { asm volatile("bar.sync 3, 256;" ::: "memory"); }

template <int N> __device__ __forceinline__ void pin(const uint32_t* v, uint32_t addr) {
#pragma unroll
  for (int i = 0; i < N; i += 4)
    asm volatile("{\n.reg .pred p;\nsetp.eq.u32 p, %0, 0;\n@p st.shared.v4.u32 [%0], {%1,%2,%3,%4};\n}" ::"r"(addr), "r"(v[i]), "r"(v[i + 1]), "r"(v[i + 2]), "r"(v[i + 3]) : "memory");
}

__device__ __forceinline__ void consumer(const Params& P, uint32_t sb, int w, unsigned vb) {
  Ctx x;
  x.w = w;
  x.ab = sb + OFF_A + w * 8192; x.da0 = desc_lo(SB + OFF_A, 16) + w * 512;
  x.lane = threadIdx.x & 31; x.warp = __shfl_sync(0xffffffffu, (threadIdx.x >> 5) & 3, 0); x.g = x.lane >> 2; x.c = x.lane & 3;
  x.goff = (cta_m(vb) * 128 + w) * 128 + cta_j(vb) * 16;
  asm volatile("" : "+r"(x.goff));
  x.elected = (threadIdx.x & 127) == 0;
  x.ra = {0, 0}; x.rb = {0, 0}; x.pa = x.pb = 0;
  {
    const uint32_t row = x.warp * 16 + (x.lane & 15);
    x.mrow = row * 128; x.mxor = row & 7; x.mhi = x.lane >> 4;
  }
  const int goff = x.goff;
  x.ip = solid(&g_img[0][x.m()][2 * x.j()][w * 512 + x.oo()]);
  x.so = solid(16 * x.oo());
  uint4 r1[4];
  float ts[4] = {0.f, 0.f, 0.f, 0.f};
#pragma unroll
  for (int i = 0; i < 4; i++) r1[i] = make_uint4(0, 0, 0, 0);
  TSW(0);
  mbar_wait3(x.fullA(0), 0, x.fullB(0), 0);
#pragma unroll 1
  for (int L = 0; L < 4; L++) {
    float acc[64];
    constexpr uint32_t dcs = desc_lo(SB + OFF_CS, 0);
    if ((L & 1) == 0) {
    float kv[128];
    x.ha = L ? HA64 : HA128; x.k2 = L ? 32 : 4;
    gemm_issue<256, true, false>(kv, x, true); gemm_next<256>(x);
    {
      int i = 1;
#pragma unroll 1
      for (int seg = L ? NS - 1 : 0; seg <= NS; seg++) {
        const int end = seg < NS ? (L == 0 ? 3 + SA * ((x.j() + SW * w) & 3) + SB_ * seg : XA + 1) : 14 + L;
#pragma unroll 1
        do {
          gemm_issue<256, false, false>(kv, x);
          gemm_retire<256>(x, true);
          i++;
          if (i == 5) TSL_(8);
          if (i == 11) TSL_(10);
        } while (i != end);
        if (seg < NS && L == 0) {
          uint32_t v[16];
          float a[32];
#pragma unroll
          for (int q = 0; q < 4; q++) ldsm4(x.maddr(x.aslot(x.pa), 2 * q), reinterpret_cast<uint32_t (&)[4]>(v[4 * q]));
#pragma unroll
          for (int q = 0; q < 16; q++) { a[2 * q] = lo16(v[q]); a[2 * q + 1] = hi16(v[q]); }
          stats_acc<32>(a, ts);
          fence_regs(ts);
          wg_bar(w);
        }
        if (seg == NS - 1) {
          if (L > 0) { img_store(r1, x.img(XBUF(L), 1)); publish(2, x); }
          mbar_wait(sb + BAR_EPOCH, 0);
          stats_send(ts, L, x);
        }
      }
    }
      const Ring kt = x.ra;
      if (L == 0) adv<NA>(x.ra);
#pragma unroll 1
      for (int h = L; h < 2; h++) {
        float d[16];
        mbar_wait2(x.fullA(kt.s), kt.ph, sb + BAR_WPHI, 0);
        wgmma_fence();
#pragma unroll
        for (int q = 0; q < 2; q++) wgmma_ss_n32(d, x.da0 + kt.s * (SLOT / 16) + h * 4 + q * 2, desc_lo(SB + OFF_S + 4096, 512) + w * 256 + h * 128 + q * 64, q);
        wgmma_commit();
        gemm_issue<256, false, false>(kv, x);
        gemm_retire<256>(x, true);
        if (h) x.releaseA(kt.s);
        fence_regs(d);
        uint4* dst = &g_wf[1][x.j()][x.m()][w * 512 + (x.warp * 16 + x.g) * 8 + ((h * 4 + x.c) ^ x.g)];
        dst[0] = make_uint4(pack2(d[0], d[1]), pack2(d[4], d[5]), pack2(d[8], d[9]), pack2(d[12], d[13]));
        dst[64] = make_uint4(pack2(d[2], d[3]), pack2(d[6], d[7]), pack2(d[10], d[11]), pack2(d[14], d[15]));
      }
      const uint32_t dm = desc_lo(SB + OFF_MA, 0) + w * 64;
      mbar_wait2(sb + BAR_STAT, 0, sb + BAR_CS, 0);
      wgmma_fence();
      wgmma_r1_n256(kv, dm, dcs + 96, 1);
      wgmma_commit();
      const Stats st = load_stats(w, x);
      mbar_wait2(x.fullA(x.ra.s), x.ra.ph, x.fullB(x.rb.s), x.rb.ph);
      wgmma_wait<0>();
      fence_regs(kv);
      gemm_release<256>(x, true);
      TSL_(2);
      uint32_t P0[32], P1[32], PH[32];
#pragma unroll
      for (int t = 0; t < 16; t++) { P0[t] = pack2(kv[4 * t] * st.rstd0, kv[4 * t + 1] * st.rstd0); P1[t] = pack2(kv[4 * t + 2] * st.rstd1, kv[4 * t + 3] * st.rstd1); }
      pin<16>(P0, x.mrow + 16);
      {
#pragma unroll
        for (int q = 0; q < 4; q++) sts128((x.warp < 3 ? sb + OFF_T + w * 12288 + x.warp * 4096 : sb + OFF_S + 16384 + w * 2048) + x.lane * 16 + q * 512, P1[4 * q], P1[4 * q + 1], P1[4 * q + 2], P1[4 * q + 3]);
      }
      wgmma_fence();
      wgmma_r1_n128(acc, dm, dcs, 0);
      gemm_issue<128, false, false>(acc, x, true); gemm_next<128>(x);
      TSL_(3);
#pragma unroll
      for (int s = 0; s < 4; s++) {
#pragma unroll
        for (int t = 16 + 8 * (s & 1); t < 24 + 8 * (s & 1); t++) {
          if (s < 2) P1[t] = movm(pack2(kv[4 * t + 2] * st.rstd1, kv[4 * t + 3] * st.rstd1));
          else P0[t] = movm(pack2(kv[4 * t] * st.rstd0, kv[4 * t + 1] * st.rstd0));
        }
        if (s < 3) { gemm_issue<128, false, false>(acc, x); gemm_retire<128>(x, true); }
        if (s == 1) {
          if (x.warp < 3) {
#pragma unroll
            for (int q = 4; q < 8; q++) sts128(sb + OFF_T + w * 12288 + x.warp * 4096 + x.lane * 16 + q * 512, P1[4 * q], P1[4 * q + 1], P1[4 * q + 2], P1[4 * q + 3]);
          } else {
            uint4* dst = &g_halo[x.m()][x.j()][w][x.lane];
#pragma unroll
            for (int q = 0; q < 8; q++) dst[q * 32] = make_uint4(P1[4 * q], P1[4 * q + 1], P1[4 * q + 2], P1[4 * q + 3]);
          }
          publish(3, x);
          gemm_issue<128, false, false>(acc, x);
          gemm_retire<128>(x, true);
        }
      }
      TSL_(4);
      gemm_run<false>(acc, x, 10, 0);
      gemm_issue<128, false, false>(acc, x);
      {
        wg_bar(w);
        uint32_t tr = sb + OFF_T + w * 12288 + (x.warp - 1) * 4096;
        if (x.warp == 0) {
          tr = x.m() > 0 ? sb + OFF_S + 8192 + w * 4096 : tr + 4096;
          if (x.m() > 0) mbar_wait(sb + BAR_HALO, L >> 1);
        }
#pragma unroll
        for (int q = 0; q < 8; q++) lds128(tr + x.lane * 16 + q * 512, PH[4 * q], PH[4 * q + 1], PH[4 * q + 2], PH[4 * q + 3]);
      }
      gemm_retire<128>(x, false);
      gemm_end(acc, x);
      TSL_(5);
      const bool first = (x.m() == 0) && (x.warp == 0);
      const bool hi0 = 2 * x.c > x.g, hi1 = 2 * x.c + 1 > x.g;
      const uint32_t mhi = (hi0 ? 0xFFFFu : 0u) | (hi1 ? 0xFFFF0000u : 0u);
      const float sc0 = st.rstd0 * (0.17677669529663687f * LOG2E), sc1 = st.rstd1 * (0.17677669529663687f * LOG2E);
#pragma unroll
      for (int hp = 0; hp < 2; hp++) {
        const uint32_t tile = x.aslot(x.held(hp));
        uint32_t px[2], py[2];
        float s[2][3][4];
#pragma unroll
        for (int u = 0; u < 2; u++) {
#pragma unroll
          for (int q = 0; q < 12; q++) s[u][q >> 2][q & 3] = 0.f;
#pragma unroll
          for (int ks = 0; ks < 2; ks++) {
            const int t = 8 * hp + 4 * u + 2 * ks;
            const uint32_t a0 = pack2(acc[4 * t], acc[4 * t + 1]), a1 = pack2(acc[4 * t + 2], acc[4 * t + 3]);
            const uint32_t a2 = pack2(acc[4 * t + 4], acc[4 * t + 5]), a3 = pack2(acc[4 * t + 6], acc[4 * t + 7]);
            mma16816(s[u][0], a0, a1, a2, a3, PH[t], PH[t + 1]);
            mma16816(s[u][1], a0, a1, a2, a3, P0[t], P0[t + 1]);
            mma16816(s[u][2], a0, a1, a2, a3, P1[t], P1[t + 1]);
          }
        }
        float e[2][4], r[2][2];
#pragma unroll
        for (int u = 0; u < 2; u++) {
          e[u][0] = (hi0 ? s[u][0][0] : s[u][1][0]) * sc0; e[u][1] = (hi1 ? s[u][0][1] : s[u][1][1]) * sc0;
          e[u][2] = (hi0 ? s[u][1][2] : s[u][2][2]) * sc1; e[u][3] = (hi1 ? s[u][1][3] : s[u][2][3]) * sc1;
          if (first) { if (hi0) e[u][0] = -1e30f; if (hi1) e[u][1] = -1e30f; }
          r[u][0] = fmaxf(e[u][0], e[u][1]); r[u][1] = fmaxf(e[u][2], e[u][3]);
        }
#pragma unroll
        for (int d = 1; d <= 2; d++)
#pragma unroll
          for (int q = 0; q < 4; q++) r[q >> 1][q & 1] = fmaxf(r[q >> 1][q & 1], __shfl_xor_sync(0xffffffffu, r[q >> 1][q & 1], d));
#pragma unroll
        for (int u = 0; u < 2; u++) {
#pragma unroll
          for (int q = 0; q < 4; q++) e[u][q] = ex2(e[u][q] - r[u][q >> 1]);
          r[u][0] = e[u][0] + e[u][1]; r[u][1] = e[u][2] + e[u][3];
        }
#pragma unroll
        for (int d = 1; d <= 2; d++)
#pragma unroll
          for (int q = 0; q < 4; q++) r[q >> 1][q & 1] += __shfl_xor_sync(0xffffffffu, r[q >> 1][q & 1], d);
#pragma unroll
        for (int u = 0; u < 2; u++) {
          const float rx = rcp(r[u][0]), ry = rcp(r[u][1]);
          px[u] = pack2(e[u][0] * rx, e[u][1] * rx); py[u] = pack2(e[u][2] * ry, e[u][3] * ry);
        }
        uint32_t o[8][2];
        uint4 ro[4];
#pragma unroll
        for (int q = 0; q < 8; q++) {
          float d[4] = {0.f, 0.f, 0.f, 0.f};
          const int t = 16 + 8 * hp + q, u = q >> 2;
          mma16816(d, px[u] & mhi, 0u, px[u] & ~mhi, py[u] & mhi, PH[t], P0[t]);
          mma1688(d, 0u, py[u] & ~mhi, P1[t]);
          o[q][0] = pack2(d[0], d[1]); o[q][1] = pack2(d[2], d[3]);
        }
#pragma unroll
        for (int q = 0; q < 4; q++) ro[q] = make_uint4(o[4 * (q & 1)][q >> 1], o[4 * (q & 1) + 1][q >> 1], o[4 * (q & 1) + 2][q >> 1], o[4 * (q & 1) + 3][q >> 1]);
        img_tag(ro, false, 0, x);
        img_store(ro, x.img(0, hp));
        if (hp == 0) publish(0, x);
        uint32_t xs[16];
        if (L) img_load(xs, tile, x);
        else {
#pragma unroll
          for (int q = 0; q < 4; q++) {
            uint32_t v[4];
            ldsm4(x.maddr(tile, 2 * q), v);
            xs[2 * q] = v[0]; xs[8 + 2 * q] = v[1]; xs[2 * q + 1] = v[2]; xs[9 + 2 * q] = v[3];
          }
          __syncwarp();
        }
        img_sts(ro, tile, x);
        img_unpack(acc + 32 * hp, xs);
      }
    } else {
      float kv[128];
      float (&kv0)[64] = reinterpret_cast<float (&)[64]>(kv[0]);
      float (&kv1)[64] = reinterpret_cast<float (&)[64]>(kv[64]);
      auto mma8 = [&](uint32_t as, uint32_t bs, int i, bool fence) {
        const uint32_t da = desc_lo(SB + OFF_A, 16) + as * (SLOT / 16), db = desc_lo(SB + OFF_B, 8192) + bs * (SLOT / 16);
        if (fence) wgmma_fence();
#pragma unroll
        for (int k = 0; k < 4; k++) {
          wgmma_ss_n128(kv0, da + (k >> 1) * 32 + (k & 1) * 2, HA64, db + 128 * k, i + k);
          wgmma_ss_n128(kv1, da + 512 + (k >> 1) * 32 + (k & 1) * 2, HA64, db + 128 * k, i + k);
        }
        wgmma_commit();
      };
      constexpr uint32_t dm = desc_lo(SB + OFF_MB, 0);
      auto relB = [&](uint32_t s) { mbar_arrive_n(sb + BAR_EMPTYB + s * 8, 2); };
      auto skip = [&]() {
#pragma unroll
        for (int q = 0; q < 6 - NJ; q++) adv<NA>(x.ra);
        x.rb.s = w ? (2 + NJ) % 6 : 4;
        if (!w && NJ < 4) x.rb.ph ^= 1;
      };
      static_assert(NA == 5 && NB == 6, "ring arithmetic");
      mma8(x.ra.s, x.rb.s + w, 0, true);
      gemm_next<256>(x);
#pragma unroll 1
      for (int i = 1; i < NJ; i++) {
        mbar_wait2(x.fullA(x.ra.s), x.ra.ph, x.fullB(x.rb.s + w), x.rb.ph);
        mma8(x.ra.s, x.rb.s + w, 1, true);
        if (!XO && i == XR) { img_store(r1, x.img(XBUF(L), 1)); publish(2, x); }
        if (!XO && i == XS) stats_send(ts, L, x);
        wgmma_wait<1>();
        if (x.elected) { x.releaseA(x.pa); relB(x.pb + w); }
        gemm_next<256>(x);
        if (XO && i == XR) { img_store(r1, x.img(XBUF(L), 1)); publish(2, x); stats_send(ts, L, x); }
      }
      if (w) {
        wgmma_wait<0>();
        if (x.elected) { x.releaseA(x.pa); relB(x.pb + 1); }
        skip();
        asm volatile("bar.sync 7, 256;" ::: "memory");
      }
      TSL_(8);
      {
        const int t = lane_id() + 32 * x.warp;
        uint32_t mask = t < 2 ? ((w ? (t ? 0xFF3Fu : 0x3FFFu) : 0xFFFFu) >> (NJ - 1)) & (w ? ~1u : ~0u) : 0u, cnt = 1 + t;
        bool ready = false;
#pragma unroll 1
        for (int i = NJ; i < 16; i++) {
          if (!ready) mbar_wait2(x.fullA(x.ra.s), x.ra.ph, x.fullB(x.rb.s), x.rb.ph);
          mma8(x.ra.s, x.rb.s, 1, true);
          const uint32_t bar = sb + (t ? BAR_EMPTYB + x.pb * 8 : BAR_EMPTYA + x.pa * 8);
          gemm_next<128>(x);
          if (w && (i | 4) == 15) x.rb.s = 4;
          ready = mbar_probe2(x.fullA(x.ra.s), x.ra.ph, x.fullB(x.rb.s), x.rb.ph);
          wgmma_wait<1>();
          if (mask & 1) mbar_arrive_n(bar, cnt);
          mask >>= 1; cnt = 2;
          if (i == 8 && w) asm volatile("bar.arrive 9, 256;" ::: "memory");
          if (i == 9) TSL_(10);
        }
        mbar_wait2(sb + BAR_STAT, 1, sb + BAR_CS + 8, 0);
        wgmma_fence();
        wgmma_r1_n128(kv0, dm, dcs + 96 + 96 * w, 1);
        wgmma_r1_n128(kv1, dm + 64, dcs + 96 + 96 * w, 1);
        wgmma_commit();
        if (w == 0) asm volatile("bar.arrive 7, 256;" ::: "memory");
        wgmma_wait<1>();
        if (mask & 1) mbar_arrive_n(sb + (t ? BAR_EMPTYB + x.pb * 8 : BAR_EMPTYA + x.pa * 8), 2);
      }
      const Stats s0 = load_stats(0, x), s1 = load_stats(1, x), st = w ? s1 : s0;
      if (w == 0) skip();
      const uint32_t h0 = x.held(0), h1 = x.held(1);
      auto vreg = [&](int ks) { return ks < 6 ? OFF_A + (ks < 3 ? h0 * SLOT : h1 * SLOT - 15360) + ks * 5120 : OFF_S + 2048 + ks * 5120; };
      uint32_t tV[2], uu[4];
#pragma unroll
      for (int hf = 0; hf < 2; hf++) {
        tV[hf] = sb + vreg(4 * hf + x.warp) + ((x.lane >> 3) & 1) * 2560 + (x.lane & 7) * 16 + x.mhi * 128;
        const float i0 = rcp(hf ? s1.rstd0 : s0.rstd0), i1 = rcp(hf ? s1.rstd1 : s0.rstd1);
        const uint32_t h = pack2(i0, i1);
        uu[2 * hf] = pack2(lo16(h), i0 - lo16(h)); uu[2 * hf + 1] = pack2(hi16(h), i1 - hi16(h));
        asm volatile("" : "+r"(tV[hf]), "+r"(uu[2 * hf]), "+r"(uu[2 * hf + 1])::"memory");
      }
      wgmma_wait<0>();
      fence_regs(kv);
      TSL_(2);
      if (w == 0) {
        uint32_t f[2][18], ad[4];
#pragma unroll
        for (int q = 0; q < 18; q++) f[1][q] = 0u;
#pragma unroll
        for (int q = 0; q < 4; q++) ad[q] = x.maddr(sb + OFF_S, 2 * q);
        auto norm = [&](int un) {
          uint32_t* u = f[un & 1];
          const Stats& sn = (un & 2) ? s1 : s0;
#pragma unroll
          for (int sg = 0; sg < 2; sg++) {
            uint32_t v = u[16 + sg];
            v = add2(v, __shfl_xor_sync(0xffffffffu, v, 1)); v = add2(v, __shfl_xor_sync(0xffffffffu, v, 2));
            const float a = rcp(lo16(v)) * sn.rstd0, b = rcp(hi16(v)) * sn.rstd1;
            const uint32_t r0 = pack2(a, a), r1_ = pack2(b, b);
#pragma unroll
            for (int q = 8 * sg; q < 8 * sg + 8; q++) u[q] = mul2(u[q], (q & 1) ? r1_ : r0);
#pragma unroll
            for (int q = 2 * sg; q < 2 * sg + 2; q++) stsm4(ad[q] + (un & 1) * SLOT + (un >> 1) * 8192, u[4 * q], u[4 * q + 1], u[4 * q + 2], u[4 * q + 3]);
          }
        };
        auto unit = [&](int un) { return kv + ((un >> 1) & 1) * 64 + (un & 1) * 16 + (un >> 2) * 32; };
        hedgehog_scale<1, 0>(kv, s0, nullptr, [] {});
#pragma unroll 1
        for (int it = 0;; it++) {
#pragma unroll
          for (int un = 0; un < 4; un++) {
            if (un == 1) {
              if (it) asm volatile("bar.sync 9, 256;" ::: "memory");
#pragma unroll
              for (int q = 0; q < 4; q++) ad[q] -= it * (OFF_S - OFF_B - 2 * SLOT);
            }
            norm((un + 3) & 3);
            dual_exp(unit(un), f[un & 1], x.goff);
            hedgehog_scale<1, KEEP>(unit(un + 1), ((un + 1) & 2) ? s1 : s0, f[(un + 1) & 1], [] {});
          }
          if (it) break;
#pragma unroll
          for (int q = 0; q < 32; q++) {
            asm volatile("mov.b32 %0, %1;" : "=f"(kv[q]) : "f"(kv[q + 32]));
            asm volatile("mov.b32 %0, %1;" : "=f"(kv[q + 64]) : "f"(kv[q + 96]));
            if (q < 16) kv[32 + q] = 0.f;
          }
        }
        norm(3);
        TSL_(3);
      } else {
        wg_bar(w);
#pragma unroll
        for (int hf = 0; hf < 2; hf++) {
          stsm4(tV[hf] + 512 + x.mhi * 512, uu[2 * hf], uu[2 * hf + 1], uu[2 * hf], uu[2 * hf + 1]);
          stsm4(tV[hf] + 1792 + x.mhi * 512, uu[2 * hf], uu[2 * hf + 1], uu[2 * hf], uu[2 * hf + 1]);
#pragma unroll
          for (int q = 0; q < 8; q++) {
            const float* u = kv + 64 * hf + 8 * q;
            stsm4(tV[hf] + (q >> 1) * 640 + (q & 1) * 256, pack2(u[0], u[1]), pack2(u[2], u[3]), pack2(u[4], u[5]), pack2(u[6], u[7]));
          }
        }
        TSL_(3);
      }
      {
        float d[2][20];
        uint4* dst = &g_kvpart[x.j()][w * 4 + x.warp][0][x.m() * 32 + x.lane];
        unsigned* dz = reinterpret_cast<unsigned*>(&g_kvpart[x.j()][w * 4 + x.warp][x.c & 1][512]) + x.m() * 8 + x.g;
        fence_async_smem();
        cta_bar();
        TSL_(11);
        uint32_t pk[9];
        auto prep = [&](float (&u)[20]) {
          fence_regs(u);
#pragma unroll
          for (int q = 0; q < 8; q++) pk[q] = pack2(u[((q >> 1) & 2) + 4 * (q & 3)], u[((q >> 1) & 2) + 4 * (q & 3) + 1]);
          pk[8] = __float_as_uint((x.c & 1) ? u[18] + u[19] : u[16] + u[17]);
#pragma unroll
          for (int q = 0; q < 9; q += 4) pk[q] = (pk[q] & ~1u) | (L == 1);
        };
        auto send = [&](int hp) {
          st_v4(dst + hp * 16 * 544, pk[0], pk[1], pk[2], pk[3]); st_v4(dst + (hp * 16 + 1) * 544, pk[4], pk[5], pk[6], pk[7]);
          st_flag(dz + hp * 16 * 544 * 4, pk[8]);
        };
        wgmma_fence();
#pragma unroll
        for (int q = 0; q < 17; q++) {
          if (q < 16) wgmma_ss_n40_tt(d[q >> 3], desc_lo(SB + (q < 8 ? OFF_S : OFF_B + 2 * SLOT), 1024) + w * (SLOT / 16) + 128 * (q & 7), desc_lo(SB + vreg(q & 7), 2560) + (w + (q >> 3) * 2) * 40, q & 7);
          else wgmma_r1_n128(acc, dm + w * 64, dcs, 0);
          if (q == 7 || q == KVS || q == 16) wgmma_commit();
          if (q == KVS) { mbar_wait2(x.fullA(x.ra.s), x.ra.ph, x.fullB(x.rb.s), x.rb.ph); wgmma_wait<1>(); prep(d[0]); send(0); bb_fence(x.goff); wgmma_fence(); }
        }
        gemm_issue<128, false>(acc, x, true); gemm_next<128>(x);
        wgmma_wait<1>();
        x.releaseA(h0); x.releaseA(h1); x.releaseB(2); x.releaseB(3);
        if (x.lane == 0) mbar_arrive(sb + BAR_SIGT);
        prep(d[1]);
        TSL_(4);
#pragma unroll 1
        for (int seg = 0; seg < 2; seg++) {
          const int n0 = w ? PS1 : PS0;
          gemm_run(acc, x, seg ? 15 - n0 : n0, seg, seg ? L : 0);
          if (seg == 0) send(1);
        }
      }
      gemm_end(acc, x);
      TSL_(5);
      {
        float dp[2][20], dn[2][20];
        uint32_t f[4][16];
        auto mma = [&](int h) {
          if (!(h & 1)) mbar_wait(sb + BAR_KV + h * 4, L >> 1);
          if (h == 0) TSL_(9);
          const uint32_t db = desc_lo(SB + OFF_S + h * 5120, 128);
          const uint32_t (&a)[16] = f[h];
          wgmma_fence();
          wgmma_rs_n40(dp[h & 1], a[0], a[1], a[2], a[3], db, 0);
          wgmma_rs_n40(dn[h & 1], a[8], a[9], a[10], a[11], db + 160, 0);
          wgmma_rs_n40(dp[h & 1], a[4], a[5], a[6], a[7], db + 80, 1);
          wgmma_rs_n40(dn[h & 1], a[12], a[13], a[14], a[15], db + 240, 1);
          wgmma_commit();
        };
        uint32_t xr[16];
        auto fin = [&](int h) {
          const uint32_t tile = x.aslot(x.held(h >> 1));
          if (!(h & 1)) img_load(xr, tile, x);
          float (&u)[20] = dp[h & 1];
          float (&v)[20] = dn[h & 1];
          fence_regs(u); fence_regs(v);
#pragma unroll
          for (int r = 0; r < 2; r++) {
            const float sp = u[16 + 2 * r], sn = v[16 + 2 * r];
            const float id = rcp(fmaf(fmaf(sp, L == 1 ? 0.065536f * 128 / 129 : 0.065536f, u[17 + 2 * r]), sn, v[17 + 2 * r] * sp)), aa = sn * id, cc = sp * id;
            uint32_t o[4];
#pragma unroll
            for (int t = 0; t < 4; t++) o[t] = pack2(fmaf(u[4 * t + 2 * r], aa, v[4 * t + 2 * r] * cc), fmaf(u[4 * t + 2 * r + 1], aa, v[4 * t + 2 * r + 1] * cc));
            o[2 * r + (h & 1)] = img_tag(o[2 * r + (h & 1)], false, 1, x);
            if (ZO && h == 3) r1[r] = make_uint4(o[0], o[1], o[2], o[3]);
            else stg128(x.img(0, h >> 1) + r * 64 + (h & 1) * 32, make_uint4(o[0], o[1], o[2], o[3]));
            sts128(tile + r * 1024 + (h & 1) * 512 + x.so, o[0], o[1], o[2], o[3]);
          }
          if (h & 1) { if (h == 1) publish(0, x); img_unpack(acc + 16 * (h - 1), xr); }
        };
        auto ex = [&](int h) { dual_exp_rcp(acc + 16 * h, f[h]); };
        Stats sq = st;
#pragma unroll
        for (int h = 0; h < 4; h += 2) {
          hedgehog_scale<2, 0>(acc + 16 * h, sq, nullptr, [&] { ex(h); });
          mma(h);
          ex(h + 1); wgmma_wait<0>(); fin(h);
          if (h == 0) bb_fence(x.goff);
          mma(h + 1);
          wgmma_wait<0>(); fin(h + 1);
          if (h == 0) sq.rstd1 += bb_fence(x.goff);
        }
      }
    }
    mbar_wait(x.fullB(x.rb.s), x.rb.ph);
    fence_regs(acc);
    fence_async_smem();
    wg_bar(w);
    TSL_(6);
    rewind2<NA>(x.ra);
    if (ZO && (L & 1)) { stg128(x.img(0, 1) + 32, r1[0]); stg128(x.img(0, 1) + 96, r1[1]); }
    gemm_issue<128, false>(acc, x, true); gemm_next<128>(x);
    uint4* out = solid(P.out + goff + (x.warp * 16 + (x.lane >> 3)) * 256 + (x.lane & 7));
#pragma unroll 1
    for (int seg = L >= TSL ? 0 : 1; seg < 2; seg++) {
      gemm_run(acc, x, L >= TSL ? (seg ? TSK : 15 - TSK) : 15, seg, 10 + L);
      if (L >= TSL) {
        if (seg == 0 && w == 1) asm volatile("bar.sync 6, 256;" ::: "memory");
        if (seg == 1 && w == 0) asm volatile("bar.arrive 6, 256;" ::: "memory");
      }
    }
    gemm_end(acc, x);
    TSL_(7);
    rewind2<NA>(x.ra);
    out_epilogue(acc, r1, ts, out, L, x);
    TSL_(13);
  }
}

typedef unsigned long long u64;
template <class T> __device__ __forceinline__ T* early(T* p) { return (T*)__shfl_xor_sync(0xffffffffu, (u64)p, 1); }
__device__ __forceinline__ void pause(uint32_t GAP) {
  if (GAP) { uint32_t t0, t; asm volatile("mov.u32 %0, %%clock;" : "=r"(t0)); do { asm volatile("mov.u32 %0, %%clock;" : "=r"(t)); } while (t - t0 < GAP); }
}
__device__ __forceinline__ u64 order_table0(int j) { return (j & 4) ? 0x543210FEDCBA9876ull : 0xDCBA9876543210FEull; }
__device__ __forceinline__ void order_tables(u64& t1, u64& t2, int j) {
#pragma unroll 1
  for (int i = 6; i >= 0; i--) { const u64 o = 2 * other_tile(i, j); t1 = t1 << 4 | o | (o + 1) << 28; t2 = t2 << 8 | (o * 17 + 16); }
  const u64 own = 2 * j * 17 + 16;
  t1 = t1 << 8 | own; t2 |= own << 56;
}

__device__ __forceinline__ void b_producer(const Params& P, uint32_t sb, unsigned vb) {
  const int j = cta_j(vb);
  u64 t1 = 0, t2 = 0;
  Ring r = {PRE_B % NB, PRE_B < NB};
#pragma unroll 1
  for (int sg = 0; sg < 20; sg++) {
    const int L = sg / 5, p = sg - 5 * L, wt = L & 1;
    if (sg == 1) order_tables(t1, t2, j);
    int n = p >= 3 ? 16 : (wt ? (p ? 16 - NJ : 2 * NJ) : (p ? 0 : (L ? 32 : 32 - PRE_B)));
    u64 tab = p == 3 ? t2 : (sg == 0 ? order_table0(j) >> (2 * PRE_B) : (p == 1 || p == 2 ? t1 >> (4 * NJ) : t1));
    const CUtensorMap* tm = p == 4 ? &P.mwo[wt] : &P.mw[wt ? 1 : L];
    const uint4* img = &g_wf[p != 3][j][0][0];
    int col = (p >= 3 ? 0 : (p == 2 ? 2048 : 1024)) + 128 * j;
    const int flip = p == 0 ? 3072 : 0;
    const bool fold = wt && p != 4;
    if (sg == 5 || sg == 8) { mbar_wait(sb + (sg == 5 ? BAR_WPHI : BAR_CS + 8), sg == 5); fence_async_global(); }
    if (DEFER && p == 4 && ((DEFL >> wt) & 1)) {
      Ring q = r;
      for (int u = 0; u < DEFER; u++) adv<NB>(q);
      mbar_wait(sb + BAR_EMPTYB + q.s * 8, q.ph);
    }
#pragma unroll 1
    for (; n > 0; n--) {
      const int kb = (int)tab & 15;
      mbar_wait(sb + BAR_EMPTYB + r.s * 8, r.ph);
      if (elect()) {
        mbar_expect_tx(sb + BAR_FULLB + r.s * 8, SLOT);
        if (fold && col < 2048) bulk_load(sb + OFF_B + r.s * SLOT, img + kb * 1024, SLOT, sb + BAR_FULLB + r.s * 8);
        else tma_load_w(sb + OFF_B + r.s * SLOT, tm, sb + BAR_FULLB + r.s * 8, col, kb);
      }
      adv<NB>(r);
      if (p == 2 && (n | 4) == 5) r.s = 4;
      col ^= flip;
      if (!(col & flip & 2048)) tab >>= 4;
    }
  }
}

__device__ __forceinline__ void a_loader(const Params& P, uint32_t sb, unsigned vb) {
  const int j = cta_j(vb), m = cta_m(vb);
  u64 t1 = 0, t2 = 0;
  Ring r = {PRE_A % NA, PRE_A < NA};
  {
    u64 tab = order_table0(j) >> (4 * PRE_A);
#pragma unroll 1
    for (int i = PRE_A; i < 33; i++) {
      if (i == 17) { order_tables(t1, t2, j); tab = t2; }
      mbar_wait(sb + BAR_EMPTYA + r.s * 8, r.ph);
      if (elect()) {
        mbar_expect_tx(sb + BAR_FULLA + r.s * 8, SLOT);
        if (i != 14) tma_load_3d(sb + OFF_A + r.s * SLOT, &P.mx, sb + BAR_FULLA + r.s * 8, ((int)tab & 15) * 64, m * 64, 0);
        else {
          tma_load_w(sb + OFF_A + r.s * SLOT, &P.mw[1], sb + BAR_FULLA + r.s * 8, 1024 + 128 * j, m);
          mbar_expect_tx(sb + BAR_WPHI, 8192); tma_load_2d(sb + OFF_S + 4096, &P.mwphi, sb + BAR_WPHI, 0, 128 * j);
        }
        if (i == PF1 || i == PF2) tma_prefetch_w(&P.mwo[i == PF2], 128 * j, m);
      }
      adv<NA>(r);
      if (i != 14) tab >>= 4;
    }
  }
  const unsigned tag = get_tag(sb);
  unsigned kph = 0;
#pragma unroll 1
  for (int sg = 0; sg < 13; sg++) {
    const int L = sg >> 2, p = sg & 3;
    if (p == 0 && (L & 1)) {
#pragma unroll 1
      for (int h = 0; h < 2; h++) {
        poll_flags(&g_jflag[h][j][0], 16, 0xFFFFu, tag * 4 + L);
        TS(4, h ? 14 + L : 26 + L);
        for (int it = 0;; it++) {
          if (elect()) { mbar_expect_tx(sb + BAR_STAT + 8, 10240); bulk_load(sb + OFF_S + h * 10240, &g_kvfin[j][8 * h][0], 10240, sb + BAR_STAT + 8); }
          mbar_wait(sb + BAR_STAT + 8, kph);
          kph ^= 1;
          uint32_t a = 1u, o = 0u;
#pragma unroll
          for (int u = 0; u < 20; u++) { const uint32_t v = __float_as_uint(lds32f(sb + OFF_S + h * 10240 + u * 512 + (threadIdx.x & 31) * 16)); a &= v; o |= v; }
          if (__all_sync(0xffffffffu, (L == 1 ? a : ~o) & 1u)) break;
          fence_async_smem();
          if (it > (1 << 16)) __trap();
        }
        if (elect()) mbar_arrive(sb + BAR_KV + h * 8);
        TS(4, h ? 30 + L : (L == 1 ? 20 : 25));
      }
    }
    int n = p < 2 ? 14 : (p == 2 ? ((L & 1) ? 0 : 16 - NJ) : 16);
    u64 tab = p == 3 ? t2 : t1 >> (p < 2 ? 8 : 4 * NJ);
    const uint4* img = &g_img[p ? XBUF(L + 1) : 0][m][0][0];
#pragma unroll 1
    for (; n > 0; n--) {
      const uint4* src = early(img + ((int)tab & 15) * 1024);
      const uint32_t bar = sb + (p < 2 ? BAR_LAND : BAR_FULLA) + r.s * 8;
      mbar_wait(sb + BAR_EMPTYA + r.s * 8, r.ph);
      if (elect()) mbar_expect_tx(bar, SLOT);
      if (p < 2 && n == 14) {
        const int lane = threadIdx.x & 31;
        const unsigned* f = &g_hint[(m & 14) + ((lane >> 3) & 1)][(~j & 4) + (lane & ND0)];
        mbar_wait(sb + BAR_SIGP + p * 8, L & 1);
        pause(PD);
        int it = 0;
        while (!__all_sync(0xffffffffu, (int)(ld_flag(f) - (tag * 16 + 4 * L + 1 + p)) >= 0)) { if (++it > (1 << 22)) __trap(); }
        TS(2, p == 0 ? 5 + L * 8 : 9 + L * 8);
        TSH((2 * L + p) * 8 + 2);
      }
      if (elect()) bulk_load(sb + OFF_A + r.s * SLOT, src, SLOT, bar);
      adv<NA>(r);
      tab >>= 4;
      pause(p < 2 && n > 10 ? G0 : 0);
    }
  }
}

template <int KB>
__device__ __forceinline__ uint2 sum_packets(float (&a)[8], uint32_t addr, int n) {
  uint2 ok = make_uint2(~0u, 0u);
#pragma unroll 1
  for (int b = 0; b < n; b += KB) {
    uint4 v[KB];
#pragma unroll
    for (int u = 0; u < KB; u++) lds128(addr + (b + u) * 512, v[u].x, v[u].y, v[u].z, v[u].w);
#pragma unroll
    for (int u = 0; u < KB; u++) {
      ok.x &= v[u].x; ok.y |= v[u].x;
      a[0] += lo16(v[u].x); a[1] += hi16(v[u].x); a[2] += lo16(v[u].y); a[3] += hi16(v[u].y);
      a[4] += lo16(v[u].z); a[5] += hi16(v[u].z); a[6] += lo16(v[u].w); a[7] += hi16(v[u].w);
    }
  }
  return ok;
}
__device__ __forceinline__ void helper_bar() { asm volatile("bar.sync 4, 64;" ::: "memory"); }
__device__ __forceinline__ void helper(const Params& P, uint32_t sb, int w, unsigned vb) {
  const int j = cta_j(vb), m = cta_m(vb);
  if (w == 0) {
    if (elect()) {
      const unsigned t = atomicAdd(&g_ctr, 1u) / NCTA + 1u;
      asm volatile("st.shared.u32 [%0], %1;" ::"r"(sb + OFF_EPOCH), "r"(t) : "memory");
      mbar_arrive(sb + BAR_EPOCH);
    }
  }
  const unsigned tag = get_tag(sb);
  mbar_wait(sb + BAR_FULLB + 24, 0);
  const uint32_t stg = sb + OFF_T + w * 12288, stb = sb + BAR_STG + w * 24;
  Ring rs = {0, 0};
  uint32_t vs = 33 % NA, vph = 0;
  auto cs_image = [&](int L) {
      const int lane = lane_id();
      poll_flags(&g_jflag[2 * L][j][0], 16, L ? CSNEED : 0xFFFu, tag * 4);
#pragma unroll
      for (int p = 0; p < 3; p++) {
        const uint4 u = ldcg4(&g_cs[L][0][p * 1024 + 128 * j + lane * 4]), v = ldcg4(&g_cs[L][1][p * 1024 + 128 * j + lane * 4]);
        const float c0 = __uint_as_float(u.x) + __uint_as_float(v.x), c1 = __uint_as_float(u.y) + __uint_as_float(v.y);
        const float c2 = __uint_as_float(u.z) + __uint_as_float(v.z), c3 = __uint_as_float(u.w) + __uint_as_float(v.w);
        const uint32_t h0 = pack2(c0, c1), h1 = pack2(c2, c3), dst = sb + OFF_CS + (p * 16 + (lane >> 1)) * 96 + L * 48 + (lane & 1) * 8;
        sts64(dst, h0, h1); sts64(dst + 16, pack2(c0 - lo16(h0), c1 - hi16(h0)), pack2(c2 - lo16(h1), c3 - hi16(h1))); sts64(dst + 32, h0, h1);
        if (L == 0) { sts64(dst + 48, 0u, 0u); sts64(dst + 64, 0u, 0u); sts64(dst + 80, 0u, 0u); }
      }
      if (L == 0 && lane < 4) sts64(sb + OFF_CS + 4608 + lane * 8, 0u, 0u);
      fence_async_smem();
      __syncwarp();
      if (elect()) mbar_arrive(sb + BAR_CS + L * 8);
      TS(4, 2 + L * 2);
  };
#pragma unroll 1
  for (int L = 0; L < 4; L++) {
    const int lane = lane_id();
    if (L == 0) {
      {
        const int wt = m >= 12, col = ((0x2021 >> (m & 12)) & 3) * 1024 + 128 * j + (m & 3) * 32;
        const CUtensorMap* tm = &P.mcs[wt];
        __nanosleep(wt ? D2 : CD);
        constexpr int nb = 8;
        float a[8] = {0.f, 0.f, 0.f, 0.f, 0.f, 0.f, 0.f, 0.f};
#pragma unroll 1
        for (int b = -3; b < nb; b++) {
          if (b >= 0) {
            mbar_wait(stb + rs.s * 8, rs.ph);
            sum_packets<KC>(a, stg + rs.s * 4096 + lane * 16, 8);
            fence_async_smem();
            __syncwarp();
          }
          const uint32_t sl = b < 0 ? (rs.s + b + 3) % 3 : rs.s;
          if (b + 3 < nb && elect()) { mbar_expect_tx(stb + sl * 8, 4096); tma_load_2d(stg + sl * 4096, tm, stb + sl * 8, col, (w * (16 - nb) + b + 3) * 64); }
          if (b >= 0) adv<3>(rs); else pause(CP);
        }
#pragma unroll 1
        for (int d = 4; d < 32; d *= 2)
#pragma unroll
          for (int u = 0; u < 8; u++) a[u] += __shfl_xor_sync(0xffffffffu, a[u], d);
        if (lane < 4) {
          float4* dst = reinterpret_cast<float4*>(&g_cs[wt][w][col + lane * 8]);
          dst[0] = make_float4(a[0], a[1], a[2], a[3]); dst[1] = make_float4(a[4], a[5], a[6], a[7]);
        }
        helper_bar();
        if (w == 0 && elect()) { fence_gpu(); st_flag(&g_jflag[2 * wt][j][m], tag * 4); }
      }
      if (w == 0) TS(4, 1 + L * 2);
    }
    if (L > 0 && w == 0) {
      mbar_wait(sb + BAR_SIGP + 16, (L - 1) & 1);
      fence_async_global();
      __nanosleep(CO && L == 1 ? SE : SD);
    }
    if (CO && L < 2 && w == 0) cs_image(L);
    if (w == (L == 0)) {
      if (L == 0) { mbar_wait(sb + BAR_WPHI, 0); __nanosleep(S0); }
#pragma unroll 1
      for (int p = 0; p < 2; p++) {
        uint4 v[8];
        for (int it = 0;; it++) {
          bool ok = true;
#pragma unroll
          for (int t = 0; t < 8; t++) v[t] = ld_pkt(&g_stats[m][p][t][lane]);
#pragma unroll
          for (int t = 0; t < 8; t++) ok = ok && (v[t].w & 15u) == seq4(tag, L);
          if (__all_sync(0xffffffffu, ok)) break;
          __nanosleep(200);
          if (it > (1 << 20)) __trap();
        }
        float s0 = 0.f, q0 = 0.f, s1 = 0.f, q1 = 0.f;
#pragma unroll
        for (int t = 0; t < 8; t++) { s0 += __uint_as_float(v[t].x); q0 += __uint_as_float(v[t].y); s1 += __uint_as_float(v[t].z); q1 += __uint_as_float(v[t].w & ~15u); }
        s0 *= (1.f / 1024); s1 *= (1.f / 1024);
        sts64(sb + OFF_MR + p * 256 + lane * 8, __float_as_uint(rsqrtf(fmaxf(q0 * (1.f / 1024) - s0 * s0, 0.f) + 1e-5f)),
              __float_as_uint(rsqrtf(fmaxf(q1 * (1.f / 1024) - s1 * s1, 0.f) + 1e-5f)));
#pragma unroll
        for (int r = 0; r < 2; r++) {
          const float v = -0.5f * (r ? s1 : s0);
          const uint32_t hh = pack2(v, v), hl = pack2(v, v - lo16(hh));
          const bool b = L & 1;
          sts128(sb + (b ? OFF_MB : OFF_MA) + p * 1024 + (lane >> 3) * 256 + r * 128 + (lane & 7) * 16, b ? 0u : hh, b ? hh << 16 : hl >> 16, b ? hl : 0u, 0u);
        }
      }
      fence_async_smem();
      __syncwarp();
      if (elect()) {
        mbar_arrive(sb + BAR_STAT);
      }
      TS(2, 0 + L * 8);
    }
    if (!CO && L < 2 && w == 0) cs_image(L);
    if (L & 1) {
      const uint32_t flip = L == 1 ? 0u : 1u;
      mbar_wait(sb + BAR_SIGT, 1);
      {
        int it = 0;
        if (PSL) __nanosleep(m < 8 ? PSL : PSL + 600);
        while (!__all_sync(0xffffffffu, (ld_flag(reinterpret_cast<const unsigned*>(&g_kvpart[j][m][w][512]) + (lane & 15) * 8) ^ flip) & 1u)) { if (PSL) __nanosleep(100); if (++it > (1 << 22)) __trap(); }
        fence_async_global();
      }
      if (w == 0) TS(4, 6 + L * 2);
      float a[8], z;
      for (int it = 0;; it++) {
        if (elect()) { mbar_expect_tx(stb + rs.s * 8, 8704); bulk_load(stg, &g_kvpart[j][m][w][0], 8704, stb + rs.s * 8); }
        mbar_wait(stb + rs.s * 8, rs.ph);
        if (w == 0) TS(4, 21 + L);
        adv<3>(rs);
#pragma unroll
        for (int u = 0; u < 8; u++) a[u] = 0.f;
        z = 0.f;
        uint32_t ok = 1u;
#pragma unroll
        for (int u = 0; u < 4; u++) { const float v = lds32f(stg + 8192 + u * 128 + (lane & 3) * 32 + (lane >> 2) * 4); z += v; ok &= __float_as_uint(v) ^ flip; }
        const uint2 tg = sum_packets<8>(a, stg + lane * 16, 16);
        ok &= flip ? ~tg.y : tg.x;
        if (__all_sync(0xffffffffu, ok & 1u)) break;
        fence_async_smem();
        if (it > (1 << 16)) __trap();
      }
      {
        uint4* img = &g_kvfin[j][m][w * 8 + (lane >> 2)];
        uint32_t a0 = __float_as_uint(a[0]) >> 16;
        a0 += ~(a0 ^ flip) & 1u;
        st_v4(img + (lane & 3) * 16, __byte_perm(a0, pack2(0.f, a[1]), 0x7610), pack2(a[2], a[3]), pack2(a[4], a[5]), pack2(a[6], a[7]));
        const uint32_t cz = pack2(0.f, qsum(z)) | (0x3781u ^ flip);
        if (!(lane & 3)) st_v4(img + 64, cz, cz, cz, cz);
        __syncwarp();
        if (elect()) st_flag(&g_jflag[m >> 3][j][(m & 7) * 2 + w], tag * 4 + L);
      }
      if (w == 0) TS(4, 7 + L * 2);
    } else {
      mbar_wait(sb + BAR_SIGT, 0);
      if (w == 0) {
        if (elect()) { fence_gpu(); st_flag(&g_hint[m][j], tag * 16 + 4 * L); st_flag(&g_jflag[1][j][m], tag * 4 + L); }
        if (L == 0) {
          __nanosleep(KSL);
          poll_flags(&g_jflag[1][j][0], 16, 0xFFFFu, tag * 4);
          if (elect()) mbar_arrive(sb + BAR_WPHI);
        }
      } else if (m > 0) {
        poll_flags(&g_hint[m - 1][j], 1, 1u, tag * 16 + 4 * L);
        if (elect()) { mbar_expect_tx(sb + BAR_HALO, 8192); bulk_load(sb + OFF_S + 8192, &g_halo[m - 1][j][0][0], 8192, sb + BAR_HALO); }
        TS(2, 2 + L * 8);
      }
    }
    if (w == 0) {
#pragma unroll 1
      for (int e = 0; e < (L < 3 ? 2 : 1); e++) {
        unsigned* flag = early(&g_hint[m][j]);
        mbar_wait(sb + BAR_SIGP + e * 8, L & 1);
        TS(2, (e ? 6 : 3) + L * 8);
        TSH((2 * L + e) * 8);
        pause(XD);
        if (elect()) st_flag(flag, tag * 16 + 4 * L + 1 + e);
        TSH((2 * L + e) * 8 + 1);
      }
    } else {
#pragma unroll 1
      for (int i = 0; i < (L < 3 ? 28 : 14); i++) {
        const bool isx = i >= 14;
        const uint32_t a = sb + OFF_A + vs * SLOT + lane * 128 + ((lane >> 4) * 4 + (lane & 3)) * 16 + (lane & 12), code = img_code(isx, L + isx);
        for (int it = 0;; it++) {
          mbar_wait(sb + BAR_LAND + vs * 8, (vph >> vs) & 1);
          vph ^= 1u << vs;
          if (i - 14 * isx < 2) TSH((2 * L + isx) * 8 + 3 + 2 * (i - 14 * isx));
          uint32_t bad = 0;
#pragma unroll
          for (int u = 0; u < 4; u++) bad |= __float_as_uint(lds32f(a + u * 4096)) ^ code;
          if (__all_sync(0xffffffffu, !(bad & img_mask(isx)))) break;
          if (it > (1 << 16)) __trap();
          fence_async_smem();
          if (elect()) {
            mbar_expect_tx(sb + BAR_LAND + vs * 8, SLOT);
            bulk_load(sb + OFF_A + vs * SLOT, &g_img[isx ? XBUF(L + 1) : 0][m][o_order(i - 14 * isx + 2, j)][0], SLOT, sb + BAR_LAND + vs * 8);
          }
        }
        if (elect()) mbar_arrive(sb + BAR_FULLA + vs * 8);
        if (i - 14 * isx < 2) TSH((2 * L + isx) * 8 + 4 + 2 * (i - 14 * isx));
        if (++vs == NA) vs = 0;
      }
      vs = (vs + ((L & 1) ? 16 : 32 - NJ)) % NA;
    }
  }
}

__device__ __forceinline__ void spare(const Params& P, uint32_t sb, int id) {
  const int tid = threadIdx.x & 127, warp = __shfl_sync(0xffffffffu, threadIdx.x >> 5, 0), w = warp >> 2, lane = tid & 31, j = 2 * id + w;
  const uint32_t ring = w * 6 * SLOT, wp = 12 * SLOT + w * 8192, bar = sb + 13 * SLOT + w * 64;
  auto part = [&](int t) { return (t >> 4) ^ w; };
  auto load = [&](int t, uint32_t sl) {
    mbar_expect_tx(bar + sl * 8, t == 0 ? SLOT + 8192 : SLOT);
    tma_load_w(sb + ring + sl * SLOT, &P.mw[1], bar + sl * 8, part(t) * 1024 + 128 * j, t & 15);
  };
  if (!(warp & 3) && elect()) {
    if (w == 2) sts32(sb + OFF_EPOCH, atomicAdd(&g_ctr, 1u) / NCTA + 1u);
    else {
      __nanosleep(D3);
#pragma unroll 1
      for (int t = 0; t < 5; t++) {
        mbar_init(bar + t * 8, 1);
        asm volatile("fence.mbarrier_init.release.cluster;" ::: "memory");
        load(t, t);
      }
      tma_load_2d(sb + wp, &P.mwphi, bar, 0, 128 * j);
    }
  }
  __syncthreads();
  const unsigned tag = get_tag<false>(sb);
  if (w == 2) {
    int it = 0;
    while ((int)(ld_flag(&g_ctr) - tag * NCTA) < 0) { if (++it > (1 << 22)) __trap(); }
    return;
  }
  Ring r = {4, 1};
  float d[64];
  auto fold = [&]() {
    mbar_wait(bar + r.s * 8, r.ph);
    wgmma_fence();
#pragma unroll
    for (int q = 0; q < 8; q++)
      wgmma_ss_n32(reinterpret_cast<float (&)[16]>(d[16 * (q >> 1)]), desc_lo(SB + ring + r.s * SLOT, 16) + (q >> 2) * 512 + (q & 3) * 2, desc_lo(SB + wp, 512) + q * 64, q & 1);
    wgmma_commit();
  };
#pragma unroll
  for (int i = 0; i < 64; i++) d[i] = 0.f;
  int t = -1;
#pragma unroll 1
  for (int g = 0; g < 2; g++) {
    float cs[32] = {};
#pragma unroll 1
    do {
      uint32_t f[32];
#pragma unroll
      for (int i = 0; i < 32; i++) { f[i] = pack2(d[2 * i], d[2 * i + 1]); cs[i & 30] += d[2 * i]; cs[i | 1] += d[2 * i + 1]; }
      wg_bar(w);
      const uint32_t sl = r.s;
      if (t < 31) adv<5>(r);
      fold();
      if (!(warp & 3) && t >= 0 && t < 27 && elect()) load(t + 5, sl);
      if (g == w && t >= 0) {
        uint4* dst = &g_wf[0][j][t & 15][((tid >> 5) * 16 + (lane >> 2)) * 8];
#pragma unroll
        for (int q = 0; q < 8; q++)
          dst[(q >> 2) * 512 + (q & 1) * 64 + (((q & 2) * 2 + (lane & 3)) ^ (lane >> 2))] =
              make_uint4(f[4 * (q & 6) + (q & 1)], f[4 * (q & 6) + (q & 1) + 2], f[4 * (q & 6) + (q & 1) + 4], f[4 * (q & 6) + (q & 1) + 6]);
      }
      wgmma_wait<0>();
      fence_regs(d);
    } while (++t != 16 * g + 16);
    const uint32_t red = sb + ring + 5 * SLOT;
#pragma unroll
    for (int i = 0; i < 8; i++) sts128(red + (tid >> 2) * 512 + (i >> 1) * 128 + (lane & 3) * 32 + (i & 1) * 16, __float_as_uint(cs[4 * i]), __float_as_uint(cs[4 * i + 1]), __float_as_uint(cs[4 * i + 2]), __float_as_uint(cs[4 * i + 3]));
    wg_bar(w);
    float a = 0.f;
#pragma unroll 4
    for (int i = 0; i < 32; i++) a += lds32f(red + i * 512 + tid * 4);
    g_cs[1][0][(g ^ w) * 1024 + j * 128 + tid] = a;
  }
  wg_bar(w);
  if (tid == 0) { fence_gpu(); st_flag(&g_jflag[2][j][0], tag * 4); }
}

__global__ void __launch_bounds__(NTHREADS, 1) fused_kernel(const __grid_constant__ Params P) {
  extern __shared__ __align__(1024) uint8_t smem_raw[];
  constexpr uint32_t sb = SB;
  const int tid = threadIdx.x;
  const unsigned vb = vblock();
  if (vb >= 128) { spare(P, sb, vb - 128); return; }
  const int warp = __shfl_sync(0xffffffffu, tid >> 5, 0);
  if (elect()) {
    if (warp == 11) { prefetch_map(&P.mx); prefetch_map(&P.mw[0]); if (smem_u32(smem_raw) != SB) __trap(); }
    if (warp < 8) {
#pragma unroll
      for (int i = 0; i < 8; i++) mbar_init(sb + OFF_BAR + (warp * 8 + i) * 8, warp == 2 || warp == 3 ? 2 : (warp == 4 ? 8 : 1));
    }
    asm volatile("fence.mbarrier_init.release.cluster;" ::: "memory");
    if (warp < 2) {
      const int j = cta_j(vb);
#pragma unroll 1
      for (int i = 0; i < (warp == 0 ? PRE_B : PRE_A); i++) {
        const uint32_t bar = sb + BAR_FULLB + warp * 64 + i * 8;
        mbar_expect_tx(bar, SLOT);
        if (warp == 0) tma_load_w(sb + OFF_B + i * SLOT, &P.mw[0], bar, 1024 + (i & 1) * 1024 + 128 * j, kv_order(i >> 1, j, 0));
        else tma_load_3d(sb + OFF_A + i * SLOT, &P.mx, bar, kv_order(i, j, 0) * 64, cta_m(vb) * 64, 0);
      }
    }
  }
  if (tid == 0) TS(6, 0);
  __syncthreads();
  if (tid == 0) TS(6, 2);
  if (warp < 4) {
    reg_dealloc<PREGS>();
    if (warp & 2) helper(P, sb, warp & 1, vb);
    else if (warp & 1) a_loader(P, sb, vb);
    else b_producer(P, sb, vb);
  } else {
    reg_alloc<CREGS>();
    consumer(P, sb, (warp >> 2) - 1, vb);
  }
}

typedef CUresult (*EncodeFn)(CUtensorMap*, CUtensorMapDataType, cuuint32_t, void*, const cuuint64_t*, const cuuint64_t*,
                             const cuuint32_t*, const cuuint32_t*, CUtensorMapInterleave, CUtensorMapSwizzle,
                             CUtensorMapL2promotion, CUtensorMapFloatOOBfill);

void encode(EncodeFn fn, CUtensorMap* m, const void* ptr, int rank, const cuuint64_t* dims, const cuuint64_t* strides,
            const cuuint32_t* box, CUtensorMapSwizzle swz) {
  const cuuint32_t es[5] = {1, 1, 1, 1, 1};
  fn(m, CU_TENSOR_MAP_DATA_TYPE_BFLOAT16, rank, const_cast<void*>(ptr), dims, strides, box, es, CU_TENSOR_MAP_INTERLEAVE_NONE,
     swz, CU_TENSOR_MAP_L2_PROMOTION_L2_256B, CU_TENSOR_MAP_FLOAT_OOB_FILL_NONE);
}
void encode_w(EncodeFn fn, CUtensorMap* m, const void* ptr, int ncols, bool perm) {
  const cuuint64_t p = (cuuint64_t)ncols * 2, d[5] = {(cuuint64_t)ncols, 2, 4, 4, 32}, s[4] = {p, (perm ? 8 : 2) * p, (perm ? 2 : 8) * p, 32 * p};
  const cuuint32_t box[5] = {64, 2, 4, 4, 2};
  encode(fn, m, ptr, 5, d, s, box, CU_TENSOR_MAP_SWIZZLE_128B);
}

void encode_cs(EncodeFn fn, CUtensorMap* m, const void* ptr, int ncols) {
  const cuuint64_t d[2] = {(cuuint64_t)ncols, 1024}, s[1] = {(cuuint64_t)ncols * 2};
  const cuuint32_t box[2] = {32, 64};
  encode(fn, m, ptr, 2, d, s, box, CU_TENSOR_MAP_SWIZZLE_NONE);
}

}

extern "C" void kernel_launch(void* const* d_in, const int* in_sizes, int n_in, void* d_out, int out_size) {
  (void)in_sizes; (void)n_in; (void)out_size;
  void* fnp = nullptr;
  cudaDriverEntryPointQueryResult q;
  cudaGetDriverEntryPoint("cuTensorMapEncodeTiled", &fnp, cudaEnableDefault, &q);
  EncodeFn fn = (EncodeFn)fnp;
  Params P;
  {
    const cuuint64_t dims[3] = {1024, 1024, 2}, strides[2] = {4096, 2048};
    const cuuint32_t box[3] = {64, 64, 2};
    encode(fn, &P.mx, d_in[0], 3, dims, strides, box, CU_TENSOR_MAP_SWIZZLE_128B);
  }
  P.out = (uint4*)d_out;
  encode_w(fn, &P.mw[0], d_in[1], 3072, false);
  encode_w(fn, &P.mw[1], d_in[4], 3072, true);
  encode_w(fn, &P.mw[2], d_in[1], 3072, true);
  encode_w(fn, &P.mwo[0], d_in[2], 1024, true);
  encode_w(fn, &P.mwo[1], d_in[6], 1024, false);
  encode_cs(fn, &P.mcs[0], d_in[1], 3072);
  encode_cs(fn, &P.mcs[1], d_in[4], 3072);
  {
    const cuuint64_t dims[2] = {32, 1024}, strides[1] = {64};
    const cuuint32_t box[2] = {32, 128};
    encode(fn, &P.mwphi, d_in[5], 2, dims, strides, box, CU_TENSOR_MAP_SWIZZLE_64B);
  }
  cudaFuncSetAttribute(fused_kernel, cudaFuncAttributeMaxDynamicSharedMemorySize, SMEM_BYTES);
  fused_kernel<<<NCTA, NTHREADS, SMEM_BYTES, cudaStreamPerThread>>>(P);
}
```

```cpp
#include <cuda_runtime.h>
#include <cuda_bf16.h>
#include <cuda.h>
#include <stdint.h>

namespace {

__device__ __forceinline__ void wgmma_ss_n256(float (&d)[128], uint32_t da, uint32_t ha, uint32_t db, int sd) {
  asm volatile("{\n.reg .pred p;\n.reg .b64 a, b;\nsetp.ne.b32 p, %130, 0;\nmov.b64 a, {%128, %131};\nmov.b64 b, {%129, 0x40000040};\n"
    "wgmma.mma_async.sync.aligned.m64n256k16.f32.bf16.bf16 {%0,%1,%2,%3,%4,%5,%6,%7,%8,%9,%10,%11,%12,%13,%14,%15,%16,%17,%18,%19,%20,%21,%22,%23,%24,%25,%26,%27,%28,%29,%30,%31,%32,%33,%34,%35,%36,%37,%38,%39,%40,%41,%42,%43,%44,%45,%46,%47,%48,%49,%50,%51,%52,%53,%54,%55,%56,%57,%58,%59,%60,%61,%62,%63,%64,%65,%66,%67,%68,%69,%70,%71,%72,%73,%74,%75,%76,%77,%78,%79,%80,%81,%82,%83,%84,%85,%86,%87,%88,%89,%90,%91,%92,%93,%94,%95,%96,%97,%98,%99,%100,%101,%102,%103,%104,%105,%106,%107,%108,%109,%110,%111,%112,%113,%114,%115,%116,%117,%118,%119,%120,%121,%122,%123,%124,%125,%126,%127}, a, b, p, 1, 1, 0, 1;\n}\n"
    : "+f"(d[0]),"+f"(d[1]),"+f"(d[2]),"+f"(d[3]),"+f"(d[4]),"+f"(d[5]),"+f"(d[6]),"+f"(d[7]),"+f"(d[8]),"+f"(d[9]),"+f"(d[10]),"+f"(d[11]),"+f"(d[12]),"+f"(d[13]),"+f"(d[14]),"+f"(d[15]),"+f"(d[16]),"+f"(d[17]),"+f"(d[18]),"+f"(d[19]),"+f"(d[20]),"+f"(d[21]),"+f"(d[22]),"+f"(d[23]),"+f"(d[24]),"+f"(d[25]),"+f"(d[26]),"+f"(d[27]),"+f"(d[28]),"+f"(d[29]),"+f"(d[30]),"+f"(d[31]),"+f"(d[32]),"+f"(d[33]),"+f"(d[34]),"+f"(d[35]),"+f"(d[36]),"+f"(d[37]),"+f"(d[38]),"+f"(d[39]),"+f"(d[40]),"+f"(d[41]),"+f"(d[42]),"+f"(d[43]),"+f"(d[44]),"+f"(d[45]),"+f"(d[46]),"+f"(d[47]),"+f"(d[48]),"+f"(d[49]),"+f"(d[50]),"+f"(d[51]),"+f"(d[52]),"+f"(d[53]),"+f"(d[54]),"+f"(d[55]),"+f"(d[56]),"+f"(d[57]),"+f"(d[58]),"+f"(d[59]),"+f"(d[60]),"+f"(d[61]),"+f"(d[62]),"+f"(d[63]),"+f"(d[64]),"+f"(d[65]),"+f"(d[66]),"+f"(d[67]),"+f"(d[68]),"+f"(d[69]),"+f"(d[70]),"+f"(d[71]),"+f"(d[72]),"+f"(d[73]),"+f"(d[74]),"+f"(d[75]),"+f"(d[76]),"+f"(d[77]),"+f"(d[78]),"+f"(d[79]),"+f"(d[80]),"+f"(d[81]),"+f"(d[82]),"+f"(d[83]),"+f"(d[84]),"+f"(d[85]),"+f"(d[86]),"+f"(d[87]),"+f"(d[88]),"+f"(d[89]),"+f"(d[90]),"+f"(d[91]),"+f"(d[92]),"+f"(d[93]),"+f"(d[94]),"+f"(d[95]),"+f"(d[96]),"+f"(d[97]),"+f"(d[98]),"+f"(d[99]),"+f"(d[100]),"+f"(d[101]),"+f"(d[102]),"+f"(d[103]),"+f"(d[104]),"+f"(d[105]),"+f"(d[106]),"+f"(d[107]),"+f"(d[108]),"+f"(d[109]),"+f"(d[110]),"+f"(d[111]),"+f"(d[112]),"+f"(d[113]),"+f"(d[114]),"+f"(d[115]),"+f"(d[116]),"+f"(d[117]),"+f"(d[118]),"+f"(d[119]),"+f"(d[120]),"+f"(d[121]),"+f"(d[122]),"+f"(d[123]),"+f"(d[124]),"+f"(d[125]),"+f"(d[126]),"+f"(d[127])
    : "r"(da), "r"(db), "r"(sd), "r"(ha));
}
__device__ __forceinline__ void wgmma_ss_n128(float (&d)[64], uint32_t da, uint32_t ha, uint32_t db, int sd) {
  asm volatile("{\n.reg .pred p;\n.reg .b64 a, b;\nsetp.ne.b32 p, %66, 0;\nmov.b64 a, {%64, %67};\nmov.b64 b, {%65, 0x40000040};\n"
    "wgmma.mma_async.sync.aligned.m64n128k16.f32.bf16.bf16 {%0,%1,%2,%3,%4,%5,%6,%7,%8,%9,%10,%11,%12,%13,%14,%15,%16,%17,%18,%19,%20,%21,%22,%23,%24,%25,%26,%27,%28,%29,%30,%31,%32,%33,%34,%35,%36,%37,%38,%39,%40,%41,%42,%43,%44,%45,%46,%47,%48,%49,%50,%51,%52,%53,%54,%55,%56,%57,%58,%59,%60,%61,%62,%63}, a, b, p, 1, 1, 0, 1;\n}\n"
    : "+f"(d[0]),"+f"(d[1]),"+f"(d[2]),"+f"(d[3]),"+f"(d[4]),"+f"(d[5]),"+f"(d[6]),"+f"(d[7]),"+f"(d[8]),"+f"(d[9]),"+f"(d[10]),"+f"(d[11]),"+f"(d[12]),"+f"(d[13]),"+f"(d[14]),"+f"(d[15]),"+f"(d[16]),"+f"(d[17]),"+f"(d[18]),"+f"(d[19]),"+f"(d[20]),"+f"(d[21]),"+f"(d[22]),"+f"(d[23]),"+f"(d[24]),"+f"(d[25]),"+f"(d[26]),"+f"(d[27]),"+f"(d[28]),"+f"(d[29]),"+f"(d[30]),"+f"(d[31]),"+f"(d[32]),"+f"(d[33]),"+f"(d[34]),"+f"(d[35]),"+f"(d[36]),"+f"(d[37]),"+f"(d[38]),"+f"(d[39]),"+f"(d[40]),"+f"(d[41]),"+f"(d[42]),"+f"(d[43]),"+f"(d[44]),"+f"(d[45]),"+f"(d[46]),"+f"(d[47]),"+f"(d[48]),"+f"(d[49]),"+f"(d[50]),"+f"(d[51]),"+f"(d[52]),"+f"(d[53]),"+f"(d[54]),"+f"(d[55]),"+f"(d[56]),"+f"(d[57]),"+f"(d[58]),"+f"(d[59]),"+f"(d[60]),"+f"(d[61]),"+f"(d[62]),"+f"(d[63])
    : "r"(da), "r"(db), "r"(sd), "r"(ha));
}
__device__ __forceinline__ void wgmma_ss_n40_tt(float (&d)[20], uint32_t da, uint32_t db, int sd) {
  asm volatile("{\n.reg .pred p;\n.reg .b64 a, b;\nsetp.ne.b32 p, %22, 0;\nmov.b64 a, {%20, 0x40000040};\nmov.b64 b, {%21, 0x8};\n"
    "wgmma.mma_async.sync.aligned.m64n40k16.f32.bf16.bf16 {%0,%1,%2,%3,%4,%5,%6,%7,%8,%9,%10,%11,%12,%13,%14,%15,%16,%17,%18,%19}, a, b, p, 1, 1, 1, 1;\n}\n"
    : "+f"(d[0]),"+f"(d[1]),"+f"(d[2]),"+f"(d[3]),"+f"(d[4]),"+f"(d[5]),"+f"(d[6]),"+f"(d[7]),"+f"(d[8]),"+f"(d[9]),"+f"(d[10]),"+f"(d[11]),"+f"(d[12]),"+f"(d[13]),"+f"(d[14]),"+f"(d[15]),"+f"(d[16]),"+f"(d[17]),"+f"(d[18]),"+f"(d[19])
    : "r"(da), "r"(db), "r"(sd));
}
__device__ __forceinline__ void wgmma_ss_n32(float (&d)[16], uint32_t da, uint32_t db, int sd) {
  asm volatile("{\n.reg .pred p;\n.reg .b64 a, b;\nsetp.ne.b32 p, %18, 0;\nmov.b64 a, {%16, 0x40000040};\nmov.b64 b, {%17, 0x80000020};\n"
    "wgmma.mma_async.sync.aligned.m64n32k16.f32.bf16.bf16 {%0,%1,%2,%3,%4,%5,%6,%7,%8,%9,%10,%11,%12,%13,%14,%15}, a, b, p, 1, 1, 0, 1;\n}\n"
    : "+f"(d[0]),"+f"(d[1]),"+f"(d[2]),"+f"(d[3]),"+f"(d[4]),"+f"(d[5]),"+f"(d[6]),"+f"(d[7]),"+f"(d[8]),"+f"(d[9]),"+f"(d[10]),"+f"(d[11]),"+f"(d[12]),"+f"(d[13]),"+f"(d[14]),"+f"(d[15])
    : "r"(da), "r"(db), "r"(sd));
}
__device__ __forceinline__ void wgmma_rs_n40(float (&d)[20], uint32_t a0, uint32_t a1, uint32_t a2, uint32_t a3, uint32_t db, int sd) {
  asm volatile("{\n.reg .pred p;\n.reg .b64 b;\nsetp.ne.b32 p, %25, 0;\nmov.b64 b, {%24, 0x10};\n"
    "wgmma.mma_async.sync.aligned.m64n40k16.f32.bf16.bf16 {%0,%1,%2,%3,%4,%5,%6,%7,%8,%9,%10,%11,%12,%13,%14,%15,%16,%17,%18,%19}, {%20,%21,%22,%23}, b, p, 1, 1, 1;\n}\n"
    : "+f"(d[0]),"+f"(d[1]),"+f"(d[2]),"+f"(d[3]),"+f"(d[4]),"+f"(d[5]),"+f"(d[6]),"+f"(d[7]),"+f"(d[8]),"+f"(d[9]),"+f"(d[10]),"+f"(d[11]),"+f"(d[12]),"+f"(d[13]),"+f"(d[14]),"+f"(d[15]),"+f"(d[16]),"+f"(d[17]),"+f"(d[18]),"+f"(d[19])
    : "r"(a0), "r"(a1), "r"(a2), "r"(a3), "r"(db), "r"(sd));
}
__device__ __forceinline__ void wgmma_r1_n256(float (&d)[128], uint32_t da, uint32_t db, int sd) {
  asm volatile("{\n.reg .pred p;\n.reg .b64 a, b;\nsetp.ne.b32 p, %130, 0;\nmov.b64 a, {%128, 0x8};\nmov.b64 b, {%129, 0x6};\n"
    "wgmma.mma_async.sync.aligned.m64n256k16.f32.bf16.bf16 {%0,%1,%2,%3,%4,%5,%6,%7,%8,%9,%10,%11,%12,%13,%14,%15,%16,%17,%18,%19,%20,%21,%22,%23,%24,%25,%26,%27,%28,%29,%30,%31,%32,%33,%34,%35,%36,%37,%38,%39,%40,%41,%42,%43,%44,%45,%46,%47,%48,%49,%50,%51,%52,%53,%54,%55,%56,%57,%58,%59,%60,%61,%62,%63,%64,%65,%66,%67,%68,%69,%70,%71,%72,%73,%74,%75,%76,%77,%78,%79,%80,%81,%82,%83,%84,%85,%86,%87,%88,%89,%90,%91,%92,%93,%94,%95,%96,%97,%98,%99,%100,%101,%102,%103,%104,%105,%106,%107,%108,%109,%110,%111,%112,%113,%114,%115,%116,%117,%118,%119,%120,%121,%122,%123,%124,%125,%126,%127}, a, b, p, 1, 1, 0, 1;\n}\n"
    : "+f"(d[0]),"+f"(d[1]),"+f"(d[2]),"+f"(d[3]),"+f"(d[4]),"+f"(d[5]),"+f"(d[6]),"+f"(d[7]),"+f"(d[8]),"+f"(d[9]),"+f"(d[10]),"+f"(d[11]),"+f"(d[12]),"+f"(d[13]),"+f"(d[14]),"+f"(d[15]),"+f"(d[16]),"+f"(d[17]),"+f"(d[18]),"+f"(d[19]),"+f"(d[20]),"+f"(d[21]),"+f"(d[22]),"+f"(d[23]),"+f"(d[24]),"+f"(d[25]),"+f"(d[26]),"+f"(d[27]),"+f"(d[28]),"+f"(d[29]),"+f"(d[30]),"+f"(d[31]),"+f"(d[32]),"+f"(d[33]),"+f"(d[34]),"+f"(d[35]),"+f"(d[36]),"+f"(d[37]),"+f"(d[38]),"+f"(d[39]),"+f"(d[40]),"+f"(d[41]),"+f"(d[42]),"+f"(d[43]),"+f"(d[44]),"+f"(d[45]),"+f"(d[46]),"+f"(d[47]),"+f"(d[48]),"+f"(d[49]),"+f"(d[50]),"+f"(d[51]),"+f"(d[52]),"+f"(d[53]),"+f"(d[54]),"+f"(d[55]),"+f"(d[56]),"+f"(d[57]),"+f"(d[58]),"+f"(d[59]),"+f"(d[60]),"+f"(d[61]),"+f"(d[62]),"+f"(d[63]),"+f"(d[64]),"+f"(d[65]),"+f"(d[66]),"+f"(d[67]),"+f"(d[68]),"+f"(d[69]),"+f"(d[70]),"+f"(d[71]),"+f"(d[72]),"+f"(d[73]),"+f"(d[74]),"+f"(d[75]),"+f"(d[76]),"+f"(d[77]),"+f"(d[78]),"+f"(d[79]),"+f"(d[80]),"+f"(d[81]),"+f"(d[82]),"+f"(d[83]),"+f"(d[84]),"+f"(d[85]),"+f"(d[86]),"+f"(d[87]),"+f"(d[88]),"+f"(d[89]),"+f"(d[90]),"+f"(d[91]),"+f"(d[92]),"+f"(d[93]),"+f"(d[94]),"+f"(d[95]),"+f"(d[96]),"+f"(d[97]),"+f"(d[98]),"+f"(d[99]),"+f"(d[100]),"+f"(d[101]),"+f"(d[102]),"+f"(d[103]),"+f"(d[104]),"+f"(d[105]),"+f"(d[106]),"+f"(d[107]),"+f"(d[108]),"+f"(d[109]),"+f"(d[110]),"+f"(d[111]),"+f"(d[112]),"+f"(d[113]),"+f"(d[114]),"+f"(d[115]),"+f"(d[116]),"+f"(d[117]),"+f"(d[118]),"+f"(d[119]),"+f"(d[120]),"+f"(d[121]),"+f"(d[122]),"+f"(d[123]),"+f"(d[124]),"+f"(d[125]),"+f"(d[126]),"+f"(d[127])
    : "r"(da), "r"(db), "r"(sd));
}
__device__ __forceinline__ void wgmma_r1_n128(float (&d)[64], uint32_t da, uint32_t db, int sd) {
  asm volatile("{\n.reg .pred p;\n.reg .b64 a, b;\nsetp.ne.b32 p, %66, 0;\nmov.b64 a, {%64, 0x8};\nmov.b64 b, {%65, 0x6};\n"
    "wgmma.mma_async.sync.aligned.m64n128k16.f32.bf16.bf16 {%0,%1,%2,%3,%4,%5,%6,%7,%8,%9,%10,%11,%12,%13,%14,%15,%16,%17,%18,%19,%20,%21,%22,%23,%24,%25,%26,%27,%28,%29,%30,%31,%32,%33,%34,%35,%36,%37,%38,%39,%40,%41,%42,%43,%44,%45,%46,%47,%48,%49,%50,%51,%52,%53,%54,%55,%56,%57,%58,%59,%60,%61,%62,%63}, a, b, p, 1, 1, 0, 1;\n}\n"
    : "+f"(d[0]),"+f"(d[1]),"+f"(d[2]),"+f"(d[3]),"+f"(d[4]),"+f"(d[5]),"+f"(d[6]),"+f"(d[7]),"+f"(d[8]),"+f"(d[9]),"+f"(d[10]),"+f"(d[11]),"+f"(d[12]),"+f"(d[13]),"+f"(d[14]),"+f"(d[15]),"+f"(d[16]),"+f"(d[17]),"+f"(d[18]),"+f"(d[19]),"+f"(d[20]),"+f"(d[21]),"+f"(d[22]),"+f"(d[23]),"+f"(d[24]),"+f"(d[25]),"+f"(d[26]),"+f"(d[27]),"+f"(d[28]),"+f"(d[29]),"+f"(d[30]),"+f"(d[31]),"+f"(d[32]),"+f"(d[33]),"+f"(d[34]),"+f"(d[35]),"+f"(d[36]),"+f"(d[37]),"+f"(d[38]),"+f"(d[39]),"+f"(d[40]),"+f"(d[41]),"+f"(d[42]),"+f"(d[43]),"+f"(d[44]),"+f"(d[45]),"+f"(d[46]),"+f"(d[47]),"+f"(d[48]),"+f"(d[49]),"+f"(d[50]),"+f"(d[51]),"+f"(d[52]),"+f"(d[53]),"+f"(d[54]),"+f"(d[55]),"+f"(d[56]),"+f"(d[57]),"+f"(d[58]),"+f"(d[59]),"+f"(d[60]),"+f"(d[61]),"+f"(d[62]),"+f"(d[63])
    : "r"(da), "r"(db), "r"(sd));
}

__device__ __forceinline__ uint32_t smem_u32(const void* p) { return (uint32_t)__cvta_generic_to_shared(p); }
__device__ __forceinline__ void mbar_init(uint32_t bar, uint32_t cnt) { asm volatile("mbarrier.init.shared::cta.b64 [%0], %1;" ::"r"(bar), "r"(cnt)); }
__device__ __forceinline__ void mbar_expect_tx(uint32_t bar, uint32_t bytes) { asm volatile("mbarrier.arrive.expect_tx.shared::cta.b64 _, [%0], %1;" ::"r"(bar), "r"(bytes) : "memory"); }
__device__ __forceinline__ void mbar_arrive(uint32_t bar) { asm volatile("mbarrier.arrive.shared::cta.b64 _, [%0];" ::"r"(bar) : "memory"); }
__device__ __forceinline__ void mbar_arrive_n(uint32_t bar, uint32_t n) { asm volatile("mbarrier.arrive.shared::cta.b64 _, [%0], %1;" ::"r"(bar), "r"(n) : "memory"); }
__device__ __forceinline__ void mbar_wait(uint32_t bar, uint32_t parity) {
  asm volatile("{\n.reg .pred p;\nLAB_WAIT:\nmbarrier.try_wait.parity.shared::cta.b64 p, [%0], %1;\n@p bra DONE;\nbra LAB_WAIT;\nDONE:\n}" ::"r"(bar), "r"(parity) : "memory");
}
__device__ __forceinline__ void mbar_wait2(uint32_t a, uint32_t pa, uint32_t b, uint32_t pb) {
  asm volatile("{\n.reg .pred p, q;\nLAB_WAIT:\nmbarrier.try_wait.parity.shared::cta.b64 p, [%0], %1;\nmbarrier.try_wait.parity.shared::cta.b64 q, [%2], %3;\n"
               "and.pred p, p, q;\n@p bra DONE;\nbra LAB_WAIT;\nDONE:\n}" ::"r"(a), "r"(pa), "r"(b), "r"(pb) : "memory");
}
__device__ __forceinline__ void mbar_wait3(uint32_t a, uint32_t pa, uint32_t b, uint32_t pb) {
  asm volatile("{\n.reg .pred p, q, r;\nLAB_WAIT:\nmbarrier.try_wait.parity.shared::cta.b64 p, [%0], %1;\nmbarrier.try_wait.parity.shared::cta.b64 q, [%2], %3;\n"
               "mbarrier.try_wait.parity.shared::cta.b64 r, [%2+8], %3;\nand.pred p, p, q;\nand.pred p, p, r;\n@p bra DONE;\nbra LAB_WAIT;\nDONE:\n}" ::"r"(a), "r"(pa), "r"(b), "r"(pb) : "memory");
}
__device__ __forceinline__ bool mbar_probe2(uint32_t a, uint32_t pa, uint32_t b, uint32_t pb) {
  uint32_t ok;
  asm volatile("{\n.reg .pred p, q;\nmbarrier.test_wait.parity.shared::cta.b64 p, [%1], %2;\nmbarrier.test_wait.parity.shared::cta.b64 q, [%3], %4;\n"
               "and.pred p, p, q;\nselp.u32 %0, 1, 0, p;\n}" : "=r"(ok) : "r"(a), "r"(pa), "r"(b), "r"(pb) : "memory");
  return ok != 0;
}
__device__ __forceinline__ void tma_load_3d(uint32_t dst, const CUtensorMap* tm, uint32_t bar, int c0, int c1, int c2) {
  asm volatile("cp.async.bulk.tensor.3d.shared::cluster.global.mbarrier::complete_tx::bytes [%0], [%1, {%3, %4, %5}], [%2];"
               ::"r"(dst), "l"(tm), "r"(bar), "r"(c0), "r"(c1), "r"(c2) : "memory");
}
__device__ __forceinline__ void tma_load_2d(uint32_t dst, const CUtensorMap* tm, uint32_t bar, int c0, int c1) {
  asm volatile("cp.async.bulk.tensor.2d.shared::cluster.global.mbarrier::complete_tx::bytes [%0], [%1, {%3, %4}], [%2];"
               ::"r"(dst), "l"(tm), "r"(bar), "r"(c0), "r"(c1) : "memory");
}
__device__ __forceinline__ void tma_load_w(uint32_t dst, const CUtensorMap* tm, uint32_t bar, int col, int kb) {
#pragma unroll
  for (int q = 0; q < 2; q++)
    asm volatile("cp.async.bulk.tensor.5d.shared::cluster.global.mbarrier::complete_tx::bytes [%0], [%1, {%3, %4, %4, %4, %5}], [%2];"
                 ::"r"(dst + q * 8192), "l"(tm), "r"(bar), "r"(col + q * 64), "r"(0), "r"(2 * kb) : "memory");
}
__device__ __forceinline__ void tma_prefetch_w(const CUtensorMap* tm, int col, int kb) {
#pragma unroll
  for (int q = 0; q < 2; q++)
    asm volatile("cp.async.bulk.prefetch.tensor.5d.L2.global [%0, {%1, %2, %2, %2, %3}];" ::"l"(tm), "r"(col + q * 64), "r"(0), "r"(2 * kb) : "memory");
}
__device__ __forceinline__ void bulk_load(uint32_t dst, const void* g, uint32_t bytes, uint32_t bar) {
  asm volatile("cp.async.bulk.shared::cluster.global.mbarrier::complete_tx::bytes [%0], [%1], %2, [%3];" ::"r"(dst), "l"(g), "r"(bytes), "r"(bar) : "memory");
}
__device__ __forceinline__ void prefetch_map(const CUtensorMap* tm) { asm volatile("prefetch.tensormap [%0];" ::"l"(tm) : "memory"); }
__device__ __forceinline__ void fence_async_smem() { asm volatile("fence.proxy.async.shared::cta;" ::: "memory"); }
__device__ __forceinline__ void fence_async_global() { asm volatile("fence.proxy.async.global;" ::: "memory"); }
__device__ __forceinline__ void fence_gpu() { asm volatile("fence.release.gpu;" ::: "memory"); }
__device__ __forceinline__ void st_flag(unsigned* p, unsigned v) { asm volatile("st.relaxed.gpu.global.u32 [%0], %1;" ::"l"(p), "r"(v) : "memory"); }
__device__ __forceinline__ unsigned ld_flag(const unsigned* p) { unsigned v; asm volatile("ld.relaxed.gpu.global.u32 %0, [%1];" : "=r"(v) : "l"(p) : "memory"); return v; }
__device__ __forceinline__ uint4 ldcg4(const void* p) { uint4 v; asm volatile("ld.global.cg.v4.u32 {%0,%1,%2,%3}, [%4];" : "=r"(v.x), "=r"(v.y), "=r"(v.z), "=r"(v.w) : "l"(p)); return v; }
__device__ __forceinline__ uint4 ld_pkt(const uint4* p) {
  uint4 v; asm volatile("{\n.reg .b128 t;\nld.relaxed.gpu.global.b128 t, [%4];\nmov.b128 {%0,%1,%2,%3}, t;\n}" : "=r"(v.x), "=r"(v.y), "=r"(v.z), "=r"(v.w) : "l"(p) : "memory"); return v;
}
__device__ __forceinline__ void st_pkt(uint4* p, uint32_t a, uint32_t b, uint32_t c, uint32_t tag) {
  asm volatile("{\n.reg .b128 t;\nmov.b128 t, {%1,%2,%3,%4};\nst.relaxed.gpu.global.b128 [%0], t;\n}" ::"l"(p), "r"(a), "r"(b), "r"(c), "r"(tag) : "memory");
}
__device__ __forceinline__ void st_v4(uint4* p, uint32_t a, uint32_t b, uint32_t c, uint32_t d) { asm volatile("st.relaxed.gpu.global.v4.u32 [%0], {%1,%2,%3,%4};" ::"l"(p), "r"(a), "r"(b), "r"(c), "r"(d) : "memory"); }
__device__ __forceinline__ void stg128(uint4* p, uint4 v) { asm volatile("st.global.v4.u32 [%0], {%1,%2,%3,%4};" ::"l"(p), "r"(v.x), "r"(v.y), "r"(v.z), "r"(v.w) : "memory"); }
__device__ __forceinline__ void sts32(uint32_t addr, uint32_t a) { asm volatile("st.shared.u32 [%0], %1;" ::"r"(addr), "r"(a) : "memory"); }
__device__ __forceinline__ void sts64(uint32_t addr, uint32_t a, uint32_t b) { asm volatile("st.shared.v2.u32 [%0], {%1,%2};" ::"r"(addr), "r"(a), "r"(b) : "memory"); }
__device__ __forceinline__ uint32_t mul2(uint32_t a, uint32_t b) { uint32_t r; asm("mul.rn.bf16x2 %0, %1, %2;" : "=r"(r) : "r"(a), "r"(b)); return r; }
__device__ __forceinline__ uint32_t add2(uint32_t a, uint32_t b) { uint32_t r; asm("add.rn.bf16x2 %0, %1, %2;" : "=r"(r) : "r"(a), "r"(b)); return r; }
__device__ __forceinline__ bool elect() {
  uint32_t p; asm volatile("{\n.reg .pred q;\nelect.sync _|q, 0xffffffff;\nselp.u32 %0, 1, 0, q;\n}" : "=r"(p)); return p != 0;
}
__device__ __forceinline__ void wgmma_fence() { asm volatile("wgmma.fence.sync.aligned;" ::: "memory"); }
__device__ __forceinline__ void wgmma_commit() { asm volatile("wgmma.commit_group.sync.aligned;" ::: "memory"); }
template <int N> __device__ __forceinline__ void wgmma_wait() { asm volatile("wgmma.wait_group.sync.aligned %0;" ::"n"(N) : "memory"); }
template <int N> __device__ __forceinline__ void fence_regs(float (&d)[N]) {
#pragma unroll
  for (int i = 0; i < N; i++) asm volatile("" : "+f"(d[i])::"memory");
}
template <int R> __device__ __forceinline__ void reg_alloc() { asm volatile("setmaxnreg.inc.sync.aligned.u32 %0;" ::"n"(R)); }
template <int R> __device__ __forceinline__ void reg_dealloc() { asm volatile("setmaxnreg.dec.sync.aligned.u32 %0;" ::"n"(R)); }
__device__ __forceinline__ void wg_bar(int w) { asm volatile("bar.sync %0, 128;" ::"r"(w + 1) : "memory"); }
__device__ __forceinline__ constexpr uint32_t desc_lo(uint32_t addr, uint32_t lbo) { return (addr >> 4) + ((lbo >> 4) << 16); }
__device__ __forceinline__ uint32_t pack2(float lo, float hi) { uint32_t r; asm("cvt.rn.bf16x2.f32 %0, %1, %2;" : "=r"(r) : "f"(hi), "f"(lo)); return r; }
__device__ __forceinline__ float lo16(uint32_t v) { return __uint_as_float(v << 16); }
__device__ __forceinline__ float hi16(uint32_t v) { return __uint_as_float(v & 0xFFFF0000u); }
__device__ __forceinline__ float ex2(float x) { float r; asm("ex2.approx.ftz.f32 %0, %1;" : "=f"(r) : "f"(x)); return r; }
__device__ __forceinline__ float rcp(float x) { float r; asm("rcp.approx.ftz.f32 %0, %1;" : "=f"(r) : "f"(x)); return r; }
__device__ __forceinline__ uint32_t movm(uint32_t a) { uint32_t d; asm volatile("movmatrix.sync.aligned.m8n8.trans.b16 %0, %1;" : "=r"(d) : "r"(a)); return d; }
__device__ __forceinline__ void stsm4(uint32_t addr, uint32_t a, uint32_t b, uint32_t c, uint32_t d) {
  asm volatile("stmatrix.sync.aligned.m8n8.x4.shared.b16 [%0], {%1,%2,%3,%4};" ::"r"(addr), "r"(a), "r"(b), "r"(c), "r"(d) : "memory");
}
__device__ __forceinline__ void ldsm4(uint32_t addr, uint32_t (&r)[4]) {
  asm volatile("ldmatrix.sync.aligned.m8n8.x4.shared.b16 {%0,%1,%2,%3}, [%4];" : "=r"(r[0]), "=r"(r[1]), "=r"(r[2]), "=r"(r[3]) : "r"(addr) : "memory");
}
__device__ __forceinline__ void sts128(uint32_t addr, uint32_t a, uint32_t b, uint32_t c, uint32_t d) {
  asm volatile("st.shared.v4.u32 [%0], {%1,%2,%3,%4};" ::"r"(addr), "r"(a), "r"(b), "r"(c), "r"(d) : "memory");
}
__device__ __forceinline__ void lds128(uint32_t addr, uint32_t& a, uint32_t& b, uint32_t& c, uint32_t& d) {
  asm volatile("ld.shared.v4.u32 {%0,%1,%2,%3}, [%4];" : "=r"(a), "=r"(b), "=r"(c), "=r"(d) : "r"(addr) : "memory");
}
__device__ __forceinline__ float lds32f(uint32_t addr) { float v; asm volatile("ld.shared.f32 %0, [%1];" : "=f"(v) : "r"(addr) : "memory"); return v; }
__device__ __forceinline__ float2 lds64f(uint32_t addr) { float2 v; asm volatile("ld.shared.v2.f32 {%0,%1}, [%2];" : "=f"(v.x), "=f"(v.y) : "r"(addr) : "memory"); return v; }
__device__ __forceinline__ void mma16816(float (&d)[4], uint32_t a0, uint32_t a1, uint32_t a2, uint32_t a3, uint32_t b0, uint32_t b1) {
  asm("mma.sync.aligned.m16n8k16.row.col.f32.bf16.bf16.f32 {%0,%1,%2,%3}, {%4,%5,%6,%7}, {%8,%9}, {%0,%1,%2,%3};"
      : "+f"(d[0]), "+f"(d[1]), "+f"(d[2]), "+f"(d[3]) : "r"(a0), "r"(a1), "r"(a2), "r"(a3), "r"(b0), "r"(b1));
}
__device__ __forceinline__ void mma1688(float (&d)[4], uint32_t a0, uint32_t a1, uint32_t b0) {
  asm("mma.sync.aligned.m16n8k8.row.col.f32.bf16.bf16.f32 {%0,%1,%2,%3}, {%4,%5}, {%6}, {%0,%1,%2,%3};"
      : "+f"(d[0]), "+f"(d[1]), "+f"(d[2]), "+f"(d[3]) : "r"(a0), "r"(a1), "r"(b0));
}

__device__ __forceinline__ float qsum(float v) { v += __shfl_xor_sync(0xffffffffu, v, 1); v += __shfl_xor_sync(0xffffffffu, v, 2); return v; }

constexpr int NCTA = 132;
#define NB_ 6
#define NA_ 5
constexpr int NB = NB_;
constexpr int NA = NA_;
constexpr uint32_t SLOT = 16384;
constexpr uint32_t SB = 1024;
constexpr uint32_t OFF_B = 0;
constexpr uint32_t OFF_A = NB * SLOT;
constexpr uint32_t OFF_S = OFF_A + NA * SLOT;
constexpr uint32_t OFF_T = OFF_S + 20480;
constexpr uint32_t OFF_CS = OFF_T + 24576;
constexpr uint32_t OFF_MR = OFF_CS + 4640;
constexpr uint32_t OFF_BAR = OFF_MR + 512;
constexpr uint32_t OFF_MA = OFF_S, OFF_MB = OFF_CS - 2048;
constexpr uint32_t BAR_FULLB = OFF_BAR;
constexpr uint32_t BAR_FULLA = BAR_FULLB + 64;
constexpr uint32_t BAR_EMPTYB = BAR_FULLA + 64;
constexpr uint32_t BAR_EMPTYA = BAR_EMPTYB + 64;
constexpr uint32_t BAR_SIGP = BAR_EMPTYA + 64;
constexpr uint32_t BAR_SIGT = BAR_SIGP + 24;
constexpr uint32_t BAR_STAT = BAR_SIGP + 64;
constexpr uint32_t BAR_HALO = BAR_STAT + 16;
constexpr uint32_t BAR_CS = BAR_HALO + 8;
constexpr uint32_t BAR_WPHI = BAR_CS + 16;
constexpr uint32_t BAR_KV = BAR_WPHI + 8;
constexpr uint32_t BAR_STG = BAR_KV + 16;
constexpr uint32_t BAR_EPOCH = BAR_STG + 48;
constexpr uint32_t BAR_LAND = OFF_BAR + 7 * 64;
constexpr uint32_t OFF_EPOCH = OFF_BAR + 8 * 64;
static_assert(BAR_EPOCH < BAR_LAND, "barriers");
constexpr uint32_t SMEM_BYTES = OFF_EPOCH + 8;
static_assert(SMEM_BYTES <= 232448 && NB % 2 == 0 && NB <= 8 && NA <= 6, "smem");

#define CREGS 224
#define PREGS 56
#define PF1 19
#define PF2 21
#define PRE_A 2
#define PRE_B 4
#define CSB 4
#define CSNEED 0xF001u
#define XR 1
#define PS0 1
#define PS1 3
#define PSW 0
#define SD 1000
#define KSPLIT 12
#define KEEP 16
#define NJ 3
#define KSL 1000
#define PSL 0
#define KVS 12
#define D2 2000
#define D3 1500
#define G0 50
#define MAP 3
#define PMAP 0x76321450u
#define ZO 0
#define XA 3
#define XS 1
#define CP 500
#define CD 0
#define S0 500
#define NS 2
#define XO 0
#define SW 2
#define SA 1
#define SB_ 4
#define XD 250
#define ND0 1
#define KC 8
#define CO 0
#define SE 500
#define PD 0
#define AS 1
#define IPF 1
#define IP0 65536
#define IP1 123904
#define DEFER 3
#define DEFL 2
#define TSK 3
#define TSL 3
constexpr int NTHREADS = 384;

struct Params {
  CUtensorMap mx;
  CUtensorMap mw[3];
  CUtensorMap mwo[2];
  CUtensorMap mcs[2];
  CUtensorMap mwphi;
  uint4* out;
};

#define XBUF(L) 1
__device__ __align__(256) uint4 g_img[XBUF(3) + 1][16][16][1024];
__device__ __forceinline__ uint32_t img_code(bool isx, int L) { return isx ? (L & 1) | (L & 2) << 15 : ~L & 1; }
__device__ __forceinline__ uint32_t img_mask(bool isx) { return isx ? 0x10001u : 1u; }
__device__ __align__(256) uint4 g_wf[2][8][16][1024];
__device__ __align__(256) uint4 g_stats[16][2][8][32];
__device__ __align__(256) uint4 g_halo[16][8][2][256];
__device__ __align__(256) float g_cs[2][2][3072];
__device__ __align__(256) uint4 g_kvpart[8][16][2][544];
__device__ __align__(256) uint4 g_kvfin[8][16][80];
__device__ __align__(256) unsigned g_hint[16][32];
__device__ __align__(256) unsigned g_jflag[3][8][32];
__device__ unsigned g_ctr;
__device__ __forceinline__ unsigned vblock() {
  unsigned s;
  asm volatile("mov.u32 %0, %%smid;" : "=r"(s));
  const unsigned r = s & 1;
  s >>= 1;
  const unsigned t = s - 32, q = (t * 37) >> 8;
  const unsigned hi = s < 60 ? 12 + (t - 7 * q) * 8 + q : (s < 62 ? s + 4 : s - 58);
  unsigned b = 2 * (s < 32 ? (s & 7) * 8 + (s >> 3) : hi) + r;
  if (b < 128) b = (b & 15) | ((PMAP >> ((b >> 4) * 4)) & 7) << 4;
  if (s >= 62) b = 8 + 4 * r + s - 62;
  unsigned n;
  asm volatile("mov.u32 %0, %%nsmid;" : "=r"(n));
  return __shfl_sync(0xffffffffu, n == NCTA ? b : blockIdx.x, 0);
}
#define TS(who, id) do {} while (0)
#define TSW(id) do {} while (0)

#define TSH(id) do {} while (0)
#define TSMASK 0xFFFF
#define TSL_(a) do { if ((TSMASK >> (a)) & 1) TSW((a) + L * 12); } while (0)
__device__ __forceinline__ int cta_m(unsigned b) { return ((b >> 2) & 12) | (b & 3); }
__device__ __forceinline__ int cta_j(unsigned b) { return ((b >> 2) & 3) | ((b >> 4) & 4); }
struct Ring { uint32_t s, ph; };
template <int N> __device__ __forceinline__ void adv(Ring& r) { if (++r.s == N) { r.s = 0; r.ph ^= 1; } }
template <int N> __device__ __forceinline__ void rewind2(Ring& r) { if (r.s < 2) { r.s += N - 2; r.ph ^= 1; } else r.s -= 2; }
__device__ __forceinline__ int other_tile(int t, int j) { return (t == (j | 4) ? 7 : t) ^ (~j & 4); }
__device__ __forceinline__ int o_order(int i, int j) {
  if (i < 2) return 2 * j + i;
  const int odd = i >= 9;
  return 2 * other_tile(i - 2 - 7 * odd, j) + odd;
}
__device__ __forceinline__ int kv_order(int i, int j, int L) { return L > 0 ? o_order(i, j) : (i + 14 + 2 * (j & 4)) & 15; }

__device__ __forceinline__ unsigned poll_flags(const unsigned* f, int n, unsigned need, unsigned tag) {
  const int lane = threadIdx.x & 31;
  unsigned mask; int it = 0;
  do {
    unsigned v = lane < n ? ld_flag(f + lane) : 0u;
    mask = __ballot_sync(0xffffffffu, lane < n && (int)(v - tag) >= 0);
    if (++it > (1 << 22)) __trap();
  } while ((mask & need) != need);
  fence_async_global();
  return mask;
}
template <bool WAIT = true>
__device__ __forceinline__ unsigned get_tag(uint32_t sb) {
  if (WAIT) mbar_wait(sb + BAR_EPOCH, 0);
  unsigned t; asm volatile("ld.shared.u32 %0, [%1];" : "=r"(t) : "r"(sb + OFF_EPOCH) : "memory");
  return t;
}

__device__ __forceinline__ int lane_id() { int l; asm volatile("mov.u32 %0, %%laneid;" : "=r"(l)); return l; }
__device__ __forceinline__ unsigned seq4(unsigned tag, int L) { return 8u | ((tag & 1u) << 2) | (unsigned)L; }
constexpr float LOG2E = 1.4426950408889634f;

__device__ __forceinline__ float bb_fence(int never, const void* p = &g_ctr, uint32_t keep = 0) {
  while (never < 0) never = ld_flag((const unsigned*)p) + keep;
  return __int_as_float(never >> 30);
}
__device__ __forceinline__ uint32_t solid(uint32_t v) { return __shfl_sync(0xffffffffu, v, threadIdx.x & 31); }
template <class T> __device__ __forceinline__ T* solid(T* p) { return (T*)__shfl_sync(0xffffffffu, (unsigned long long)p, threadIdx.x & 31); }
constexpr uint32_t HA128 = 0x40000040u, HA64 = 0x80000040u;
struct Ctx {
  static constexpr uint32_t sb = SB;
  uint32_t ab, da0;
  int w, warp, lane, g, c;
  int goff;
  __device__ __forceinline__ int m() const { return goff >> 14; }
  __device__ __forceinline__ int j() const { return (goff >> 4) & 7; }
  bool elected;
  Ring ra, rb;
  uint32_t pa, pb;
  uint32_t ha, k2;
  uint32_t mrow, mxor, mhi;
  __device__ __forceinline__ uint32_t aslot(uint32_t s) const { return ab + s * SLOT; }
  __device__ __forceinline__ uint32_t fullA(uint32_t s) const { return sb + BAR_FULLA + s * 8; }
  __device__ __forceinline__ uint32_t fullB(uint32_t s) const { return sb + BAR_FULLB + s * 8; }
  __device__ __forceinline__ void releaseA(uint32_t s) const { if (elected) mbar_arrive(sb + BAR_EMPTYA + s * 8); }
  __device__ __forceinline__ void releaseB(uint32_t s) const { if (elected) mbar_arrive(sb + BAR_EMPTYB + s * 8); }
  __device__ __forceinline__ uint32_t maddr(uint32_t tile, uint32_t ch) const { return tile + mrow + (((ch + mhi) ^ mxor) << 4); }
  __device__ __forceinline__ uint32_t oo() const { return warp * 128 + g * 4 + (c ^ (g >> 1)); }
  __device__ __forceinline__ uint4* img(int b, int hp) const { return ip + (b * 256 + hp) * 1024; }
  uint4* ip;
  uint32_t so;
  __device__ __forceinline__ uint32_t held(int i) const { return ra.s + i < 2 ? ra.s + i + NA - 2 : ra.s + i - 2; }
};

template <int N, bool FIRST, bool O = true>
__device__ __forceinline__ void gemm_issue(float (&acc)[N / 2], Ctx& x, bool ready = false) {
  if (!ready) {
    if (N == 256) mbar_wait3(x.fullA(x.ra.s), x.ra.ph, x.fullB(x.rb.s), x.rb.ph);
    else mbar_wait2(x.fullA(x.ra.s), x.ra.ph, x.fullB(x.rb.s), x.rb.ph);
  }
  const uint32_t da = x.da0 + x.ra.s * (SLOT / 16), db = desc_lo(SB + OFF_B, 8192) + x.rb.s * (SLOT / 16);
  wgmma_fence();
#pragma unroll
  for (int k = 0; k < 4; k++) {
    const uint32_t a = da + (k >> 1) * (O ? 32 : x.k2) + (k & 1) * 2, ha = O ? HA64 : x.ha;
    if constexpr (N == 256) wgmma_ss_n256(acc, a, ha, db + 128 * k, !(FIRST && k == 0));
    else wgmma_ss_n128(acc, a, ha, db + 128 * k, !(FIRST && k == 0));
  }
  wgmma_commit();
}
template <int N>
__device__ __forceinline__ void gemm_next(Ctx& x) {
  x.pa = x.ra.s; x.pb = x.rb.s;
  if (N == 256) x.rb.s++;
  adv<NA>(x.ra); adv<NB>(x.rb);
}
template <int N>
__device__ __forceinline__ void gemm_release(Ctx& x, bool relA) {
  if (relA) x.releaseA(x.pa);
  x.releaseB(x.pb);
  if (N == 256) x.releaseB(x.pb + 1);
}
template <int N>
__device__ __forceinline__ void gemm_retire(Ctx& x, bool relA) { wgmma_wait<1>(); gemm_release<N>(x, relA); gemm_next<N>(x); }
template <bool O = true>
__device__ __forceinline__ void gemm_run(float (&acc)[64], Ctx& x, int n, int hold, int n4 = 0) {
  bool ready = false;
#pragma unroll 1
  for (; n > 0; n--) {
    gemm_issue<128, false, O>(acc, x, ready);
    const uint32_t pa = x.pa, pb = x.pb;
    gemm_next<128>(x);
    ready = mbar_probe2(x.fullA(x.ra.s), x.ra.ph, x.fullB(x.rb.s), x.rb.ph);
    wgmma_wait<1>();
    if (n > hold) x.releaseA(pa);
    x.releaseB(pb);
  }
}
__device__ __forceinline__ void gemm_end(float (&acc)[64], Ctx& x) { wgmma_wait<0>(); fence_regs(acc); gemm_release<128>(x, false); }

__device__ __forceinline__ void rows_load(uint4* r, uint32_t tile, const Ctx& x) {
#pragma unroll
  for (int q = 0; q < 4; q++) {
    const uint32_t row = x.warp * 16 + 4 * q + (x.lane >> 3);
    lds128(tile + row * 128 + (((x.lane & 7) ^ (row & 7)) << 4), r[q].x, r[q].y, r[q].z, r[q].w);
  }
}
__device__ __forceinline__ void rows_store(const uint4* r, uint4* g) {
#pragma unroll
  for (int q = 0; q < 4; q++) stg128(g + q * 1024, r[q]);
}
__device__ __forceinline__ void publish(int id, const Ctx& x) { __syncwarp(); if (x.lane == 0) mbar_arrive(x.sb + BAR_SIGP + id * 8); }
__device__ __forceinline__ uint32_t img_tag(uint32_t v, bool isx, int L, const Ctx& x) {
  const uint32_t mk = ((x.lane ^ (x.warp * 4)) & 7) ? 0u : img_mask(isx);
  return (v & ~mk) | (img_code(isx, L) & mk);
}
__device__ __forceinline__ void img_tag(uint4 (&r)[4], bool isx, int L, const Ctx& x) {
#pragma unroll
  for (int q = 0; q < 4; q++) { uint32_t& v = q == 0 ? r[q].x : (q == 1 ? r[q].y : (q == 2 ? r[q].z : r[q].w)); v = img_tag(v, isx, L, x); }
}
__device__ __forceinline__ void img_store(const uint4 (&r)[4], uint4* g) {
#pragma unroll
  for (int q = 0; q < 4; q++) stg128(g + q * 32, r[q]);
}
__device__ __forceinline__ void img_sts(const uint4 (&r)[4], uint32_t tile, const Ctx& x) {
#pragma unroll
  for (int q = 0; q < 4; q++) sts128(tile + x.so + q * 512, r[q].x, r[q].y, r[q].z, r[q].w);
}
__device__ __forceinline__ void img_load(uint32_t (&v)[16], uint32_t tile, const Ctx& x) {
#pragma unroll
  for (int q = 0; q < 4; q++) lds128(tile + x.so + q * 512, v[4 * q], v[4 * q + 1], v[4 * q + 2], v[4 * q + 3]);
}
__device__ __forceinline__ void img_unpack(float* a, const uint32_t (&v)[16]) {
#pragma unroll
  for (int q = 0; q < 16; q++) { a[4 * (q & 7) + 2 * (q >> 3)] = lo16(v[q]); a[4 * (q & 7) + 2 * (q >> 3) + 1] = hi16(v[q]); }
}

template <int N>
__device__ __forceinline__ void stats_acc(const float* a, float (&t)[4]) {
#pragma unroll
  for (int i = 0; i < N; i++) { t[i & 2] += a[i]; t[(i & 2) + 1] = fmaf(a[i], a[i], t[(i & 2) + 1]); }
}
__device__ __forceinline__ void stats_send(float (&t)[4], int L, const Ctx& x) {
  const unsigned seq = seq4(get_tag<false>(x.sb), L);
#pragma unroll
  for (int q = 0; q < 4; q++) t[q] = qsum(t[q]);
  if (x.c == 0) st_pkt(&g_stats[x.m()][x.w][x.j()][x.warp * 8 + x.g], __float_as_uint(t[0]), __float_as_uint(t[1]), __float_as_uint(t[2]), (__float_as_uint(t[3]) & ~15u) | seq);
}
__device__ __forceinline__ void out_epilogue(const float (&acc)[64], uint4 (&r1)[4], float (&t)[4], uint4* g, int L, Ctx& x) {
  const uint32_t t0 = x.aslot(x.ra.s), t1 = x.aslot(x.ra.s + 1 == NA ? 0 : x.ra.s + 1);
  if (L == 3) {
#pragma unroll
    for (int p = 0; p < 8; p++) {
      stsm4(x.maddr(p < 4 ? t0 : t1, (p & 3) * 2), pack2(acc[8 * p], acc[8 * p + 1]), pack2(acc[8 * p + 2], acc[8 * p + 3]),
            pack2(acc[8 * p + 4], acc[8 * p + 5]), pack2(acc[8 * p + 6], acc[8 * p + 7]));
      if ((p & 3) == 3) { uint4 r[4]; __syncwarp(); rows_load(r, p < 4 ? t0 : t1, x); rows_store(r, g + (p >> 2) * 8); }
    }
  } else {
    auto pack16 = [&](uint4 (&r)[4], const float* a) {
#pragma unroll
      for (int q = 0; q < 4; q++) { const float* u = a + 16 * (q & 1) + (q & 2); r[q] = make_uint4(pack2(u[0], u[1]), pack2(u[4], u[5]), pack2(u[8], u[9]), pack2(u[12], u[13])); }
    };
    uint4 r0[4];
    pack16(r0, acc);
    img_tag(r0, true, L + 1, x);
    img_store(r0, x.img(XBUF(L + 1), 0));
    publish(1, x);
    const float z = bb_fence(x.goff);
    img_sts(r0, t0, x);
    pack16(r1, acc + 32);
    img_tag(r1, true, L + 1, x);
    img_sts(r1, t1, x);
    float u[4] = {z, z, z, z}, v[4] = {z, z, z, z};
    stats_acc<32>(acc, v);
    stats_acc<32>(acc + 32, u);
#pragma unroll
    for (int q = 0; q < 4; q++) t[q] = u[q] + v[q];
    mbar_wait2(x.fullB(x.rb.s), x.rb.ph, x.fullB(x.rb.s + 1), x.rb.ph);
    fence_async_smem();
    asm volatile("bar.sync %0, %1;" ::"r"(L == 1 ? x.w + 1 : 3), "r"(L == 1 ? 128 : 256) : "memory");
  }
}

struct Stats { float rstd0, rstd1; };
__device__ __forceinline__ Stats load_stats(int half, const Ctx& x) {
  const float2 u = lds64f(x.sb + OFF_MR + half * 256 + (x.warp * 8 + x.g) * 8);
  return {u.x, u.y};
}

template <int NH, int NK, class F>
__device__ __forceinline__ void hedgehog_scale(float* t, const Stats& st, const uint32_t* keep, F use) {
#pragma unroll
  for (int q = 0; q < 16 * NH; q++) t[q] *= ((q & 2) ? st.rstd1 : st.rstd0) * LOG2E;
  use();
  float m[4];
#pragma unroll
  for (int q = 0; q < 4 * NH; q++) {
    const float v = fmaxf(fmaxf(fabsf(t[4 * q]), fabsf(t[4 * q + 1])), fmaxf(fabsf(t[4 * q + 2]), fabsf(t[4 * q + 3])));
    m[q & 3] = q < 4 ? v : fmaxf(m[q & 3], v);
  }
  if (__builtin_expect(__any_sync(0xffffffffu, fmaxf(fmaxf(m[0], m[1]), fmaxf(m[2], m[3])) > 58.f), 0)) {
    float z[16 * NH + NK];
#pragma unroll
    for (int q = 0; q < 16 * NH + NK; q++) z[q] = q < 16 * NH ? t[q % (16 * NH)] : __uint_as_float(keep[q & 15]);
#pragma unroll 1
    for (int r = 0; r < 2 * NH; r++) {
      float hi = -INFINITY, lo = INFINITY;
#pragma unroll 1
      for (int i = 0; i < 16; i++) {
        const int k = (i & 6) * 2 + (i & 1) + (r & 1) * 2 + (r & 2) * 8;
        const float v = z[k];
        if (i < 8) { hi = fmaxf(hi, v); lo = fminf(lo, v); }
        else z[k] = v - fminf(fmaxf(v, lo), hi);
        if (i == 7) {
#pragma unroll 1
          for (int d = 1; d <= 2; d++) { hi = fmaxf(hi, __shfl_xor_sync(0xffffffffu, hi, d)); lo = fminf(lo, __shfl_xor_sync(0xffffffffu, lo, d)); }
          const float mid = 0.5f * hi + 0.5f * lo;
          hi = fmaxf(hi - 58.f, mid); lo = fminf(lo + 58.f, mid);
        }
      }
    }
#pragma unroll
    for (int q = 0; q < 16 * NH; q++) t[q] = z[q];
    use();
  }
}
__device__ __forceinline__ void dual_exp(const float* t, uint32_t (&f)[18], int never) {
  float e[KSPLIT];
#pragma unroll
  for (int q = 0; q < KSPLIT; q++) e[q] = ex2(q < 16 ? t[q] : -t[q & 15]);
  while (never < 0) {
#pragma unroll
    for (int i = 0; i < KSPLIT; i += 4) asm volatile("ld.shared.v4.f32 {%0,%1,%2,%3}, [%4];" : "=f"(e[i]), "=f"(e[i + 1]), "=f"(e[i + 2]), "=f"(e[i + 3]) : "r"(never + i) : "memory");
    never += __float_as_int(e[0]);
  }
#pragma unroll
  for (int q = 0; q < KSPLIT; q += 2) f[q >> 1] = pack2(e[q], e[q + 1]);
#pragma unroll
  for (int q = KSPLIT; q < 32; q += 2) f[q >> 1] = q < 16 ? pack2(ex2(t[q]), ex2(t[q + 1])) : pack2(ex2(-t[q & 15]), ex2(-t[(q & 15) + 1]));
#pragma unroll
  for (int sg = 0; sg < 2; sg++) {
    const uint32_t* u = f + 8 * sg;
    const uint32_t a = add2(add2(u[0], u[2]), add2(u[4], u[6])), b = add2(add2(u[1], u[3]), add2(u[5], u[7]));
    f[16 + sg] = add2(__byte_perm(a, b, 0x5410), __byte_perm(a, b, 0x7632));
  }
}
__device__ __forceinline__ void dual_exp_rcp(const float* t, uint32_t* f) {
#pragma unroll
  for (int q = 0; q < 8; q++) {
    const float a = ex2(t[2 * q]), b = ex2(t[2 * q + 1]), r = rcp(a * b);
    f[q] = pack2(a, b); f[8 + q] = pack2(r * b, r * a);
  }
}
__device__ __forceinline__ void cta_bar() { asm volatile("bar.sync 3, 256;" ::: "memory"); }

template <int N> __device__ __forceinline__ void pin(const uint32_t* v, uint32_t addr) {
#pragma unroll
  for (int i = 0; i < N; i += 4)
    asm volatile("{\n.reg .pred p;\nsetp.eq.u32 p, %0, 0;\n@p st.shared.v4.u32 [%0], {%1,%2,%3,%4};\n}" ::"r"(addr), "r"(v[i]), "r"(v[i + 1]), "r"(v[i + 2]), "r"(v[i + 3]) : "memory");
}

__device__ __forceinline__ void consumer(const Params& P, uint32_t sb, int w, unsigned vb) {
  Ctx x;
  x.w = w;
  x.ab = sb + OFF_A + w * 8192; x.da0 = desc_lo(SB + OFF_A, 16) + w * 512;
  x.lane = threadIdx.x & 31; x.warp = __shfl_sync(0xffffffffu, (threadIdx.x >> 5) & 3, 0); x.g = x.lane >> 2; x.c = x.lane & 3;
  x.goff = (cta_m(vb) * 128 + w) * 128 + cta_j(vb) * 16;
  asm volatile("" : "+r"(x.goff));
  x.elected = (threadIdx.x & 127) == 0;
  x.ra = {0, 0}; x.rb = {0, 0}; x.pa = x.pb = 0;
  {
    const uint32_t row = x.warp * 16 + (x.lane & 15);
    x.mrow = row * 128; x.mxor = row & 7; x.mhi = x.lane >> 4;
  }
  const int goff = x.goff;
  x.ip = solid(&g_img[0][x.m()][2 * x.j()][w * 512 + x.oo()]);
  x.so = solid(16 * x.oo());
  uint4 r1[4];
  float ts[4] = {0.f, 0.f, 0.f, 0.f};
#pragma unroll
  for (int i = 0; i < 4; i++) r1[i] = make_uint4(0, 0, 0, 0);
  TSW(0);
  mbar_wait3(x.fullA(0), 0, x.fullB(0), 0);
#pragma unroll 1
  for (int L = 0; L < 4; L++) {
    float acc[64];
    constexpr uint32_t dcs = desc_lo(SB + OFF_CS, 0);
    if ((L & 1) == 0) {
    float kv[128];
    x.ha = L ? HA64 : HA128; x.k2 = L ? 32 : 4;
    gemm_issue<256, true, false>(kv, x, true); gemm_next<256>(x);
    {
      int i = 1;
#pragma unroll 1
      for (int seg = L ? NS - 1 : 0; seg <= NS; seg++) {
        const int end = seg < NS ? (L == 0 ? 3 + SA * ((x.j() + SW * w) & 3) + SB_ * seg : XA + 1) : 14 + L;
#pragma unroll 1
        do {
          gemm_issue<256, false, false>(kv, x);
          gemm_retire<256>(x, true);
          i++;
          if (i == 5) TSL_(8);
          if (i == 11) TSL_(10);
        } while (i != end);
        if (seg < NS && L == 0) {
          uint32_t v[16];
          float a[32];
#pragma unroll
          for (int q = 0; q < 4; q++) ldsm4(x.maddr(x.aslot(x.pa), 2 * q), reinterpret_cast<uint32_t (&)[4]>(v[4 * q]));
#pragma unroll
          for (int q = 0; q < 16; q++) { a[2 * q] = lo16(v[q]); a[2 * q + 1] = hi16(v[q]); }
          stats_acc<32>(a, ts);
          fence_regs(ts);
          wg_bar(w);
        }
        if (seg == NS - 1) {
          if (L > 0) { img_store(r1, x.img(XBUF(L), 1)); publish(2, x); }
          mbar_wait(sb + BAR_EPOCH, 0);
          stats_send(ts, L, x);
        }
      }
    }
      const Ring kt = x.ra;
      if (L == 0) adv<NA>(x.ra);
#pragma unroll 1
      for (int h = L; h < 2; h++) {
        float d[16];
        mbar_wait2(x.fullA(kt.s), kt.ph, sb + BAR_WPHI, 0);
        wgmma_fence();
#pragma unroll
        for (int q = 0; q < 2; q++) wgmma_ss_n32(d, x.da0 + kt.s * (SLOT / 16) + h * 4 + q * 2, desc_lo(SB + OFF_S + 4096, 512) + w * 256 + h * 128 + q * 64, q);
        wgmma_commit();
        gemm_issue<256, false, false>(kv, x);
        gemm_retire<256>(x, true);
        if (h) x.releaseA(kt.s);
        fence_regs(d);
        uint4* dst = &g_wf[1][x.j()][x.m()][w * 512 + (x.warp * 16 + x.g) * 8 + ((h * 4 + x.c) ^ x.g)];
        dst[0] = make_uint4(pack2(d[0], d[1]), pack2(d[4], d[5]), pack2(d[8], d[9]), pack2(d[12], d[13]));
        dst[64] = make_uint4(pack2(d[2], d[3]), pack2(d[6], d[7]), pack2(d[10], d[11]), pack2(d[14], d[15]));
      }
      const uint32_t dm = desc_lo(SB + OFF_MA, 0) + w * 64;
      mbar_wait2(sb + BAR_STAT, 0, sb + BAR_CS, 0);
      wgmma_fence();
      wgmma_r1_n256(kv, dm, dcs + 96, 1);
      wgmma_commit();
      const Stats st = load_stats(w, x);
      mbar_wait2(x.fullA(x.ra.s), x.ra.ph, x.fullB(x.rb.s), x.rb.ph);
      wgmma_wait<0>();
      fence_regs(kv);
      gemm_release<256>(x, true);
      TSL_(2);
      uint32_t P0[32], P1[32], PH[32];
#pragma unroll
      for (int t = 0; t < 16; t++) { P0[t] = pack2(kv[4 * t] * st.rstd0, kv[4 * t + 1] * st.rstd0); P1[t] = pack2(kv[4 * t + 2] * st.rstd1, kv[4 * t + 3] * st.rstd1); }
      pin<16>(P0, x.mrow + 16);
      {
#pragma unroll
        for (int q = 0; q < 4; q++) sts128((x.warp < 3 ? sb + OFF_T + w * 12288 + x.warp * 4096 : sb + OFF_S + 16384 + w * 2048) + x.lane * 16 + q * 512, P1[4 * q], P1[4 * q + 1], P1[4 * q + 2], P1[4 * q + 3]);
      }
      wgmma_fence();
      wgmma_r1_n128(acc, dm, dcs, 0);
      gemm_issue<128, false, false>(acc, x, true); gemm_next<128>(x);
      TSL_(3);
#pragma unroll
      for (int s = 0; s < 4; s++) {
#pragma unroll
        for (int t = 16 + 8 * (s & 1); t < 24 + 8 * (s & 1); t++) {
          if (s < 2) P1[t] = movm(pack2(kv[4 * t + 2] * st.rstd1, kv[4 * t + 3] * st.rstd1));
          else P0[t] = movm(pack2(kv[4 * t] * st.rstd0, kv[4 * t + 1] * st.rstd0));
        }
        if (s < 3) { gemm_issue<128, false, false>(acc, x); gemm_retire<128>(x, true); }
        if (s == 1) {
          if (x.warp < 3) {
#pragma unroll
            for (int q = 4; q < 8; q++) sts128(sb + OFF_T + w * 12288 + x.warp * 4096 + x.lane * 16 + q * 512, P1[4 * q], P1[4 * q + 1], P1[4 * q + 2], P1[4 * q + 3]);
          } else {
            uint4* dst = &g_halo[x.m()][x.j()][w][x.lane];
#pragma unroll
            for (int q = 0; q < 8; q++) dst[q * 32] = make_uint4(P1[4 * q], P1[4 * q + 1], P1[4 * q + 2], P1[4 * q + 3]);
          }
          publish(3, x);
          gemm_issue<128, false, false>(acc, x);
          gemm_retire<128>(x, true);
        }
      }
      TSL_(4);
      gemm_run<false>(acc, x, 10, 0);
      gemm_issue<128, false, false>(acc, x);
      {
        wg_bar(w);
        uint32_t tr = sb + OFF_T + w * 12288 + (x.warp - 1) * 4096;
        if (x.warp == 0) {
          tr = x.m() > 0 ? sb + OFF_S + 8192 + w * 4096 : tr + 4096;
          if (x.m() > 0) mbar_wait(sb + BAR_HALO, L >> 1);
        }
#pragma unroll
        for (int q = 0; q < 8; q++) lds128(tr + x.lane * 16 + q * 512, PH[4 * q], PH[4 * q + 1], PH[4 * q + 2], PH[4 * q + 3]);
      }
      gemm_retire<128>(x, false);
      gemm_end(acc, x);
      TSL_(5);
      const bool first = (x.m() == 0) && (x.warp == 0);
      const bool hi0 = 2 * x.c > x.g, hi1 = 2 * x.c + 1 > x.g;
      const uint32_t mhi = (hi0 ? 0xFFFFu : 0u) | (hi1 ? 0xFFFF0000u : 0u);
      const uint32_t valid = first ? ~mhi : ~0u;
      const float sc0 = st.rstd0 * (0.17677669529663687f * LOG2E), sc1 = st.rstd1 * (0.17677669529663687f * LOG2E);
#pragma unroll
      for (int hp = 0; hp < 2; hp++) {
        const uint32_t tile = x.aslot(x.held(hp));
        uint32_t px[2], py[2];
        float s[2][3][4];
#pragma unroll
        for (int u = 0; u < 2; u++) {
#pragma unroll
          for (int q = 0; q < 12; q++) s[u][q >> 2][q & 3] = 0.f;
#pragma unroll
          for (int ks = 0; ks < 2; ks++) {
            const int t = 8 * hp + 4 * u + 2 * ks;
            const uint32_t a0 = pack2(acc[4 * t], acc[4 * t + 1]), a1 = pack2(acc[4 * t + 2], acc[4 * t + 3]);
            const uint32_t a2 = pack2(acc[4 * t + 4], acc[4 * t + 5]), a3 = pack2(acc[4 * t + 6], acc[4 * t + 7]);
            mma16816(s[u][0], a0, a1, a2, a3, PH[t], PH[t + 1]);
            mma16816(s[u][1], a0, a1, a2, a3, P0[t], P0[t + 1]);
            mma16816(s[u][2], a0, a1, a2, a3, P1[t], P1[t + 1]);
          }
        }
        float e[2][4], big = 0.f;
#pragma unroll
        for (int u = 0; u < 2; u++) {
          e[u][0] = (hi0 ? s[u][0][0] : s[u][1][0]) * sc0; e[u][1] = (hi1 ? s[u][0][1] : s[u][1][1]) * sc0;
          e[u][2] = (hi0 ? s[u][1][2] : s[u][2][2]) * sc1; e[u][3] = (hi1 ? s[u][1][3] : s[u][2][3]) * sc1;
          big = fmaxf(big, fmaxf(fmaxf(fabsf(e[u][0]), fabsf(e[u][1])), fmaxf(fabsf(e[u][2]), fabsf(e[u][3]))));
          px[u] = pack2(ex2(e[u][0]), ex2(e[u][1])) & valid; py[u] = pack2(ex2(e[u][2]), ex2(e[u][3]));
        }
        if (__builtin_expect(__any_sync(0xffffffffu, big > 58.f), 0)) {
#pragma unroll
          for (int q = 0; q < 4; q++) {
            float v0 = e[q >> 1][2 * (q & 1)], v1 = e[q >> 1][2 * (q & 1) + 1];
            if (first && !(q & 1)) { if (hi0) v0 = -INFINITY; if (hi1) v1 = -INFINITY; }
            float r = fmaxf(v0, v1);
            r = fmaxf(r, __shfl_xor_sync(0xffffffffu, r, 1)); r = fmaxf(r, __shfl_xor_sync(0xffffffffu, r, 2));
            ((q & 1) ? py : px)[q >> 1] = pack2(ex2(v0 - r), ex2(v1 - r));
          }
        }
        float r[2][2];
#pragma unroll
        for (int u = 0; u < 2; u++) {
          float d[4] = {0.f, 0.f, 0.f, 0.f};
          mma1688(d, px[u], py[u], 0x3F803F80u);
          r[u][0] = rcp(d[0]); r[u][1] = rcp(d[2]);
        }
        uint32_t o[8][2];
        uint4 ro[4];
#pragma unroll
        for (int q = 0; q < 8; q++) {
          float d[4] = {0.f, 0.f, 0.f, 0.f};
          const int t = 16 + 8 * hp + q, u = q >> 2;
          if (AS == 2) { mma1688(d, px[u] & ~mhi, py[u] & mhi, P0[t]); mma1688(d, px[u] & mhi, 0u, PH[t]); mma1688(d, 0u, py[u] & ~mhi, P1[t]); }
          else if (AS == 3) { mma16816(d, px[u] & ~mhi, py[u] & mhi, 0u, py[u] & ~mhi, P0[t], P1[t]); mma1688(d, px[u] & mhi, 0u, PH[t]); }
          else { mma16816(d, px[u] & mhi, 0u, px[u] & ~mhi, py[u] & mhi, PH[t], P0[t]); mma1688(d, 0u, py[u] & ~mhi, P1[t]); }
          o[q][0] = pack2(d[0] * r[u][0], d[1] * r[u][0]); o[q][1] = pack2(d[2] * r[u][1], d[3] * r[u][1]);
        }
#pragma unroll
        for (int q = 0; q < 4; q++) ro[q] = make_uint4(o[4 * (q & 1)][q >> 1], o[4 * (q & 1) + 1][q >> 1], o[4 * (q & 1) + 2][q >> 1], o[4 * (q & 1) + 3][q >> 1]);
        img_tag(ro, false, 0, x);
        img_store(ro, x.img(0, hp));
        if (hp == 0) publish(0, x);
        uint32_t xs[16];
        if (L) img_load(xs, tile, x);
        else {
#pragma unroll
          for (int q = 0; q < 4; q++) {
            uint32_t v[4];
            ldsm4(x.maddr(tile, 2 * q), v);
            xs[2 * q] = v[0]; xs[8 + 2 * q] = v[1]; xs[2 * q + 1] = v[2]; xs[9 + 2 * q] = v[3];
          }
          __syncwarp();
        }
        img_sts(ro, tile, x);
        img_unpack(acc + 32 * hp, xs);
      }
    } else {
      float kv[128];
      float (&kv0)[64] = reinterpret_cast<float (&)[64]>(kv[0]);
      float (&kv1)[64] = reinterpret_cast<float (&)[64]>(kv[64]);
      auto mma8 = [&](uint32_t as, uint32_t bs, int i, bool fence) {
        const uint32_t da = desc_lo(SB + OFF_A, 16) + as * (SLOT / 16), db = desc_lo(SB + OFF_B, 8192) + bs * (SLOT / 16);
        if (fence) wgmma_fence();
#pragma unroll
        for (int k = 0; k < 4; k++) {
          wgmma_ss_n128(kv0, da + (k >> 1) * 32 + (k & 1) * 2, HA64, db + 128 * k, i + k);
          wgmma_ss_n128(kv1, da + 512 + (k >> 1) * 32 + (k & 1) * 2, HA64, db + 128 * k, i + k);
        }
        wgmma_commit();
      };
      constexpr uint32_t dm = desc_lo(SB + OFF_MB, 0);
      auto relB = [&](uint32_t s) { mbar_arrive_n(sb + BAR_EMPTYB + s * 8, 2); };
      auto skip = [&]() {
#pragma unroll
        for (int q = 0; q < 6 - NJ; q++) adv<NA>(x.ra);
        x.rb.s = w ? (2 + NJ) % 6 : 4;
        if (!w && NJ < 4) x.rb.ph ^= 1;
      };
      static_assert(NA == 5 && NB == 6, "ring arithmetic");
      mma8(x.ra.s, x.rb.s + w, 0, true);
      gemm_next<256>(x);
#pragma unroll 1
      for (int i = 1; i < NJ; i++) {
        mbar_wait2(x.fullA(x.ra.s), x.ra.ph, x.fullB(x.rb.s + w), x.rb.ph);
        mma8(x.ra.s, x.rb.s + w, 1, true);
        if (!XO && i == XR) { img_store(r1, x.img(XBUF(L), 1)); publish(2, x); }
        if (!XO && i == XS) stats_send(ts, L, x);
        wgmma_wait<1>();
        if (x.elected) { x.releaseA(x.pa); relB(x.pb + w); }
        gemm_next<256>(x);
        if (XO && i == XR) { img_store(r1, x.img(XBUF(L), 1)); publish(2, x); stats_send(ts, L, x); }
      }
      if (w) {
        wgmma_wait<0>();
        if (x.elected) { x.releaseA(x.pa); relB(x.pb + 1); }
        skip();
        asm volatile("bar.sync 7, 256;" ::: "memory");
      }
      TSL_(8);
      {
        const int t = lane_id() + 32 * x.warp;
        uint32_t mask = t < 2 ? ((w ? (t ? 0xFF3Fu : 0x3FFFu) : 0xFFFFu) >> (NJ - 1)) & (w ? ~1u : ~0u) : 0u, cnt = 1 + t;
        bool ready = false;
#pragma unroll 1
        for (int i = NJ; i < 16; i++) {
          if (!ready) mbar_wait2(x.fullA(x.ra.s), x.ra.ph, x.fullB(x.rb.s), x.rb.ph);
          mma8(x.ra.s, x.rb.s, 1, true);
          const uint32_t bar = sb + (t ? BAR_EMPTYB + x.pb * 8 : BAR_EMPTYA + x.pa * 8);
          gemm_next<128>(x);
          if (w && (i | 4) == 15) x.rb.s = 4;
          ready = mbar_probe2(x.fullA(x.ra.s), x.ra.ph, x.fullB(x.rb.s), x.rb.ph);
          wgmma_wait<1>();
          if (mask & 1) mbar_arrive_n(bar, cnt);
          mask >>= 1; cnt = 2;
          if (i == 8 && w) asm volatile("bar.arrive 9, 256;" ::: "memory");
          if (i == 9) TSL_(10);
        }
        mbar_wait2(sb + BAR_STAT, 1, sb + BAR_CS + 8, 0);
        wgmma_fence();
        wgmma_r1_n128(kv0, dm, dcs + 96 + 96 * w, 1);
        wgmma_r1_n128(kv1, dm + 64, dcs + 96 + 96 * w, 1);
        wgmma_commit();
        if (w == 0) asm volatile("bar.arrive 7, 256;" ::: "memory");
        wgmma_wait<1>();
        if (mask & 1) mbar_arrive_n(sb + (t ? BAR_EMPTYB + x.pb * 8 : BAR_EMPTYA + x.pa * 8), 2);
      }
      const Stats s0 = load_stats(0, x), s1 = load_stats(1, x), st = w ? s1 : s0;
      if (w == 0) skip();
      const uint32_t h0 = x.held(0), h1 = x.held(1);
      auto vreg = [&](int ks) { return ks < 6 ? OFF_A + (ks < 3 ? h0 * SLOT : h1 * SLOT - 15360) + ks * 5120 : OFF_S + 2048 + ks * 5120; };
      uint32_t tV[2], uu[4];
#pragma unroll
      for (int hf = 0; hf < 2; hf++) {
        tV[hf] = sb + vreg(4 * hf + x.warp) + ((x.lane >> 3) & 1) * 2560 + (x.lane & 7) * 16 + x.mhi * 128;
        const float i0 = rcp(hf ? s1.rstd0 : s0.rstd0), i1 = rcp(hf ? s1.rstd1 : s0.rstd1);
        const uint32_t h = pack2(i0, i1);
        uu[2 * hf] = pack2(lo16(h), i0 - lo16(h)); uu[2 * hf + 1] = pack2(hi16(h), i1 - hi16(h));
        asm volatile("" : "+r"(tV[hf]), "+r"(uu[2 * hf]), "+r"(uu[2 * hf + 1])::"memory");
      }
      wgmma_wait<0>();
      fence_regs(kv);
      TSL_(2);
      if (w == 0) {
        uint32_t f[2][18], ad[4];
#pragma unroll
        for (int q = 0; q < 18; q++) f[1][q] = 0u;
#pragma unroll
        for (int q = 0; q < 4; q++) ad[q] = x.maddr(sb + OFF_S, 2 * q);
        auto norm = [&](int un) {
          uint32_t* u = f[un & 1];
          const Stats& sn = (un & 2) ? s1 : s0;
#pragma unroll
          for (int sg = 0; sg < 2; sg++) {
            uint32_t v = u[16 + sg];
            v = add2(v, __shfl_xor_sync(0xffffffffu, v, 1)); v = add2(v, __shfl_xor_sync(0xffffffffu, v, 2));
            const float a = rcp(lo16(v)) * sn.rstd0, b = rcp(hi16(v)) * sn.rstd1;
            const uint32_t r0 = pack2(a, a), r1_ = pack2(b, b);
#pragma unroll
            for (int q = 8 * sg; q < 8 * sg + 8; q++) u[q] = mul2(u[q], (q & 1) ? r1_ : r0);
#pragma unroll
            for (int q = 2 * sg; q < 2 * sg + 2; q++) stsm4(ad[q] + (un & 1) * SLOT + (un >> 1) * 8192, u[4 * q], u[4 * q + 1], u[4 * q + 2], u[4 * q + 3]);
          }
        };
        auto unit = [&](int un) { return kv + ((un >> 1) & 1) * 64 + (un & 1) * 16 + (un >> 2) * 32; };
        hedgehog_scale<1, 0>(kv, s0, nullptr, [] {});
#pragma unroll 1
        for (int it = 0;; it++) {
#pragma unroll
          for (int un = 0; un < 4; un++) {
            if (un == 1) {
              if (it) asm volatile("bar.sync 9, 256;" ::: "memory");
#pragma unroll
              for (int q = 0; q < 4; q++) ad[q] -= it * (OFF_S - OFF_B - 2 * SLOT);
            }
            norm((un + 3) & 3);
            dual_exp(unit(un), f[un & 1], x.goff);
            hedgehog_scale<1, KEEP>(unit(un + 1), ((un + 1) & 2) ? s1 : s0, f[(un + 1) & 1], [] {});
          }
          if (it) break;
#pragma unroll
          for (int q = 0; q < 32; q++) {
            asm volatile("mov.b32 %0, %1;" : "=f"(kv[q]) : "f"(kv[q + 32]));
            asm volatile("mov.b32 %0, %1;" : "=f"(kv[q + 64]) : "f"(kv[q + 96]));
            if (q < 16) kv[32 + q] = 0.f;
          }
        }
        norm(3);
        TSL_(3);
      } else {
        wg_bar(w);
#pragma unroll
        for (int hf = 0; hf < 2; hf++) {
          stsm4(tV[hf] + 512 + x.mhi * 512, uu[2 * hf], uu[2 * hf + 1], uu[2 * hf], uu[2 * hf + 1]);
          stsm4(tV[hf] + 1792 + x.mhi * 512, uu[2 * hf], uu[2 * hf + 1], uu[2 * hf], uu[2 * hf + 1]);
#pragma unroll
          for (int q = 0; q < 8; q++) {
            const float* u = kv + 64 * hf + 8 * q;
            stsm4(tV[hf] + (q >> 1) * 640 + (q & 1) * 256, pack2(u[0], u[1]), pack2(u[2], u[3]), pack2(u[4], u[5]), pack2(u[6], u[7]));
          }
        }
        TSL_(3);
      }
      {
        float d[2][20];
        uint4* dst = &g_kvpart[x.j()][w * 4 + x.warp][0][x.m() * 32 + x.lane];
        unsigned* dz = reinterpret_cast<unsigned*>(&g_kvpart[x.j()][w * 4 + x.warp][x.c & 1][512]) + x.m() * 8 + x.g;
        fence_async_smem();
        cta_bar();
        TSL_(11);
        uint32_t pk[9];
        auto prep = [&](float (&u)[20]) {
          fence_regs(u);
#pragma unroll
          for (int q = 0; q < 8; q++) pk[q] = pack2(u[((q >> 1) & 2) + 4 * (q & 3)], u[((q >> 1) & 2) + 4 * (q & 3) + 1]);
          pk[8] = __float_as_uint((x.c & 1) ? u[18] + u[19] : u[16] + u[17]);
#pragma unroll
          for (int q = 0; q < 9; q += 4) pk[q] = (pk[q] & ~1u) | (L == 1);
        };
        auto send = [&](int hp) {
          st_v4(dst + hp * 16 * 544, pk[0], pk[1], pk[2], pk[3]); st_v4(dst + (hp * 16 + 1) * 544, pk[4], pk[5], pk[6], pk[7]);
          st_flag(dz + hp * 16 * 544 * 4, pk[8]);
        };
        wgmma_fence();
#pragma unroll
        for (int q = 0; q < 17; q++) {
          if (q < 16) wgmma_ss_n40_tt(d[q >> 3], desc_lo(SB + (q < 8 ? OFF_S : OFF_B + 2 * SLOT), 1024) + w * (SLOT / 16) + 128 * (q & 7), desc_lo(SB + vreg(q & 7), 2560) + (w + (q >> 3) * 2) * 40, q & 7);
          else wgmma_r1_n128(acc, dm + w * 64, dcs, 0);
          if (q == 7 || q == KVS || q == 16) wgmma_commit();
          if (q == KVS) { mbar_wait2(x.fullA(x.ra.s), x.ra.ph, x.fullB(x.rb.s), x.rb.ph); wgmma_wait<1>(); prep(d[0]); send(0); bb_fence(x.goff); wgmma_fence(); }
        }
        gemm_issue<128, false>(acc, x, true); gemm_next<128>(x);
        wgmma_wait<1>();
        x.releaseA(h0); x.releaseA(h1); x.releaseB(2); x.releaseB(3);
        if (x.lane == 0) mbar_arrive(sb + BAR_SIGT);
        prep(d[1]);
        TSL_(4);
#pragma unroll 1
        for (int seg = 0; seg < 2; seg++) {
          const int n0 = w ? PS1 : PS0;
          gemm_run(acc, x, seg ? 15 - n0 : n0, seg, seg ? L : 0);
          if (seg == 0) send(1);
        }
      }
      gemm_end(acc, x);
      TSL_(5);
      {
        float dp[2][20], dn[2][20];
        uint32_t f[4][16];
        auto mma = [&](int h) {
          if (!(h & 1)) mbar_wait(sb + BAR_KV + h * 4, L >> 1);
          if (h == 0) TSL_(9);
          const uint32_t db = desc_lo(SB + OFF_S + h * 5120, 128);
          const uint32_t (&a)[16] = f[h];
          wgmma_fence();
          wgmma_rs_n40(dp[h & 1], a[0], a[1], a[2], a[3], db, 0);
          wgmma_rs_n40(dn[h & 1], a[8], a[9], a[10], a[11], db + 160, 0);
          wgmma_rs_n40(dp[h & 1], a[4], a[5], a[6], a[7], db + 80, 1);
          wgmma_rs_n40(dn[h & 1], a[12], a[13], a[14], a[15], db + 240, 1);
          wgmma_commit();
        };
        uint32_t xr[16];
        auto fin = [&](int h) {
          const uint32_t tile = x.aslot(x.held(h >> 1));
          if (!(h & 1)) img_load(xr, tile, x);
          float (&u)[20] = dp[h & 1];
          float (&v)[20] = dn[h & 1];
          fence_regs(u); fence_regs(v);
#pragma unroll
          for (int r = 0; r < 2; r++) {
            const float sp = u[16 + 2 * r], sn = v[16 + 2 * r];
            const float id = rcp(fmaf(fmaf(sp, L == 1 ? 0.065536f * 128 / 129 : 0.065536f, u[17 + 2 * r]), sn, v[17 + 2 * r] * sp)), aa = sn * id, cc = sp * id;
            uint32_t o[4];
#pragma unroll
            for (int t = 0; t < 4; t++) o[t] = pack2(fmaf(u[4 * t + 2 * r], aa, v[4 * t + 2 * r] * cc), fmaf(u[4 * t + 2 * r + 1], aa, v[4 * t + 2 * r + 1] * cc));
            o[2 * r + (h & 1)] = img_tag(o[2 * r + (h & 1)], false, 1, x);
            if (ZO && h == 3) r1[r] = make_uint4(o[0], o[1], o[2], o[3]);
            else stg128(x.img(0, h >> 1) + r * 64 + (h & 1) * 32, make_uint4(o[0], o[1], o[2], o[3]));
            sts128(tile + r * 1024 + (h & 1) * 512 + x.so, o[0], o[1], o[2], o[3]);
          }
          if (h & 1) { if (h == 1) publish(0, x); img_unpack(acc + 16 * (h - 1), xr); }
        };
        auto ex = [&](int h) { dual_exp_rcp(acc + 16 * h, f[h]); };
        Stats sq = st;
#pragma unroll
        for (int h = 0; h < 4; h += 2) {
          hedgehog_scale<2, 0>(acc + 16 * h, sq, nullptr, [&] { ex(h); });
          mma(h);
          ex(h + 1); wgmma_wait<0>(); fin(h);
          if (h == 0) bb_fence(x.goff);
          mma(h + 1);
          wgmma_wait<0>(); fin(h + 1);
          if (h == 0) sq.rstd1 += bb_fence(x.goff);
        }
      }
    }
    mbar_wait(x.fullB(x.rb.s), x.rb.ph);
    fence_regs(acc);
    fence_async_smem();
    wg_bar(w);
    TSL_(6);
    rewind2<NA>(x.ra);
    if (ZO && (L & 1)) { stg128(x.img(0, 1) + 32, r1[0]); stg128(x.img(0, 1) + 96, r1[1]); }
    gemm_issue<128, false>(acc, x, true); gemm_next<128>(x);
    uint4* out = solid(P.out + goff + (x.warp * 16 + (x.lane >> 3)) * 256 + (x.lane & 7));
#pragma unroll 1
    for (int seg = L >= TSL ? 0 : 1; seg < 2; seg++) {
      gemm_run(acc, x, L >= TSL ? (seg ? TSK : 15 - TSK) : 15, seg, 10 + L);
      if (L >= TSL) {
        if (seg == 0 && w == 1) asm volatile("bar.sync 6, 256;" ::: "memory");
        if (seg == 1 && w == 0) asm volatile("bar.arrive 6, 256;" ::: "memory");
      }
    }
    gemm_end(acc, x);
    TSL_(7);
    rewind2<NA>(x.ra);
    out_epilogue(acc, r1, ts, out, L, x);
    TSL_(13);
  }
}

typedef unsigned long long u64;
template <class T> __device__ __forceinline__ T* early(T* p) { return (T*)__shfl_xor_sync(0xffffffffu, (u64)p, 1); }
__device__ __forceinline__ void pause(uint32_t GAP) {
  if (GAP) { uint32_t t0, t; asm volatile("mov.u32 %0, %%clock;" : "=r"(t0)); do { asm volatile("mov.u32 %0, %%clock;" : "=r"(t)); } while (t - t0 < GAP); }
}
__device__ __forceinline__ u64 order_table0(int j) { return (j & 4) ? 0x543210FEDCBA9876ull : 0xDCBA9876543210FEull; }
__device__ __forceinline__ void order_tables(u64& t1, u64& t2, int j) {
#pragma unroll 1
  for (int i = 6; i >= 0; i--) { const u64 o = 2 * other_tile(i, j); t1 = t1 << 4 | o | (o + 1) << 28; t2 = t2 << 8 | (o * 17 + 16); }
  const u64 own = 2 * j * 17 + 16;
  t1 = t1 << 8 | own; t2 |= own << 56;
}

__device__ __forceinline__ void b_producer(const Params& P, uint32_t sb, unsigned vb) {
  const int j = cta_j(vb);
  u64 t1 = 0, t2 = 0;
  Ring r = {PRE_B % NB, PRE_B < NB};
#pragma unroll 1
  for (int sg = 0; sg < 20; sg++) {
    const int L = sg / 5, p = sg - 5 * L, wt = L & 1;
    if (sg == 1) order_tables(t1, t2, j);
    int n = p >= 3 ? 16 : (wt ? (p ? 16 - NJ : 2 * NJ) : (p ? 0 : (L ? 32 : 32 - PRE_B)));
    u64 tab = p == 3 ? t2 : (sg == 0 ? order_table0(j) >> (2 * PRE_B) : (p == 1 || p == 2 ? t1 >> (4 * NJ) : t1));
    const CUtensorMap* tm = p == 4 ? &P.mwo[wt] : &P.mw[wt ? 1 : L];
    const uint4* img = &g_wf[p != 3][j][0][0];
    int col = (p >= 3 ? 0 : (p == 2 ? 2048 : 1024)) + 128 * j;
    const int flip = p == 0 ? 3072 : 0;
    const bool fold = wt && p != 4;
    if (sg == 5 || sg == 8) { mbar_wait(sb + (sg == 5 ? BAR_WPHI : BAR_CS + 8), sg == 5); fence_async_global(); }
    if (DEFER && p == 4 && ((DEFL >> wt) & 1)) {
      Ring q = r;
      for (int u = 0; u < DEFER; u++) adv<NB>(q);
      mbar_wait(sb + BAR_EMPTYB + q.s * 8, q.ph);
    }
#pragma unroll 1
    for (; n > 0; n--) {
      const int kb = (int)tab & 15;
      mbar_wait(sb + BAR_EMPTYB + r.s * 8, r.ph);
      if (elect()) {
        mbar_expect_tx(sb + BAR_FULLB + r.s * 8, SLOT);
        if (fold && col < 2048) bulk_load(sb + OFF_B + r.s * SLOT, img + kb * 1024, SLOT, sb + BAR_FULLB + r.s * 8);
        else tma_load_w(sb + OFF_B + r.s * SLOT, tm, sb + BAR_FULLB + r.s * 8, col, kb);
      }
      adv<NB>(r);
      if (p == 2 && (n | 4) == 5) r.s = 4;
      col ^= flip;
      if (!(col & flip & 2048)) tab >>= 4;
    }
  }
}

__device__ __forceinline__ void a_loader(const Params& P, uint32_t sb, unsigned vb) {
  const int j = cta_j(vb), m = cta_m(vb);
  u64 t1 = 0, t2 = 0;
  Ring r = {PRE_A % NA, PRE_A < NA};
  {
    u64 tab = order_table0(j) >> (4 * PRE_A);
#pragma unroll 1
    for (int i = PRE_A; i < 33; i++) {
      if (i == 17) { order_tables(t1, t2, j); tab = t2; }
      mbar_wait(sb + BAR_EMPTYA + r.s * 8, r.ph);
      if (elect()) {
        mbar_expect_tx(sb + BAR_FULLA + r.s * 8, SLOT);
        if (i != 14) tma_load_3d(sb + OFF_A + r.s * SLOT, &P.mx, sb + BAR_FULLA + r.s * 8, ((int)tab & 15) * 64, m * 64, 0);
        else {
          tma_load_w(sb + OFF_A + r.s * SLOT, &P.mw[1], sb + BAR_FULLA + r.s * 8, 1024 + 128 * j, m);
          mbar_expect_tx(sb + BAR_WPHI, 8192); tma_load_2d(sb + OFF_S + 4096, &P.mwphi, sb + BAR_WPHI, 0, 128 * j);
        }
        if (i == PF1 || i == PF2) tma_prefetch_w(&P.mwo[i == PF2], 128 * j, m);
      }
      adv<NA>(r);
      if (i != 14) tab >>= 4;
    }
  }
  const unsigned tag = get_tag(sb);
  unsigned kph = 0;
#pragma unroll 1
  for (int sg = 0; sg < 13; sg++) {
    const int L = sg >> 2, p = sg & 3;
    if (p == 0 && (L & 1)) {
#pragma unroll 1
      for (int h = 0; h < 2; h++) {
        poll_flags(&g_jflag[h][j][0], 16, 0xFFFFu, tag * 4 + L);
        TS(4, h ? 14 + L : 26 + L);
        for (int it = 0;; it++) {
          if (elect()) { mbar_expect_tx(sb + BAR_STAT + 8, 10240); bulk_load(sb + OFF_S + h * 10240, &g_kvfin[j][8 * h][0], 10240, sb + BAR_STAT + 8); }
          mbar_wait(sb + BAR_STAT + 8, kph);
          kph ^= 1;
          uint32_t a = 1u, o = 0u;
#pragma unroll
          for (int u = 0; u < 20; u++) { const uint32_t v = __float_as_uint(lds32f(sb + OFF_S + h * 10240 + u * 512 + (threadIdx.x & 31) * 16)); a &= v; o |= v; }
          if (__all_sync(0xffffffffu, (L == 1 ? a : ~o) & 1u)) break;
          fence_async_smem();
          if (it > (1 << 16)) __trap();
        }
        if (elect()) mbar_arrive(sb + BAR_KV + h * 8);
        TS(4, h ? 30 + L : (L == 1 ? 20 : 25));
      }
    }
    int n = p < 2 ? 14 : (p == 2 ? ((L & 1) ? 0 : 16 - NJ) : 16);
    u64 tab = p == 3 ? t2 : t1 >> (p < 2 ? 8 : 4 * NJ);
    const uint4* img = &g_img[p ? XBUF(L + 1) : 0][m][0][0];
#pragma unroll 1
    for (; n > 0; n--) {
      const uint4* src = early(img + ((int)tab & 15) * 1024);
      const uint32_t bar = sb + (p < 2 ? BAR_LAND : BAR_FULLA) + r.s * 8;
      mbar_wait(sb + BAR_EMPTYA + r.s * 8, r.ph);
      if (elect()) mbar_expect_tx(bar, SLOT);
      if (p < 2 && n == 14) {
        const int lane = threadIdx.x & 31;
        const unsigned* f = &g_hint[(m & 14) + ((lane >> 3) & 1)][(~j & 4) + (lane & ND0)];
        mbar_wait(sb + BAR_SIGP + p * 8, L & 1);
        pause(PD);
        int it = 0;
        while (!__all_sync(0xffffffffu, (int)(ld_flag(f) - (tag * 16 + 4 * L + 1 + p)) >= 0)) { if (++it > (1 << 22)) __trap(); }
        TS(2, p == 0 ? 5 + L * 8 : 9 + L * 8);
        TSH((2 * L + p) * 8 + 2);
      }
      if (elect()) bulk_load(sb + OFF_A + r.s * SLOT, src, SLOT, bar);
      adv<NA>(r);
      tab >>= 4;
      pause(p < 2 && n > 10 ? G0 : 0);
    }
  }
}

template <int KB>
__device__ __forceinline__ uint2 sum_packets(float (&a)[8], uint32_t addr, int n) {
  uint2 ok = make_uint2(~0u, 0u);
#pragma unroll 1
  for (int b = 0; b < n; b += KB) {
    uint4 v[KB];
#pragma unroll
    for (int u = 0; u < KB; u++) lds128(addr + (b + u) * 512, v[u].x, v[u].y, v[u].z, v[u].w);
#pragma unroll
    for (int u = 0; u < KB; u++) {
      ok.x &= v[u].x; ok.y |= v[u].x;
      a[0] += lo16(v[u].x); a[1] += hi16(v[u].x); a[2] += lo16(v[u].y); a[3] += hi16(v[u].y);
      a[4] += lo16(v[u].z); a[5] += hi16(v[u].z); a[6] += lo16(v[u].w); a[7] += hi16(v[u].w);
    }
  }
  return ok;
}
__device__ __forceinline__ void helper_bar() { asm volatile("bar.sync 4, 64;" ::: "memory"); }
__device__ __forceinline__ void helper(const Params& P, uint32_t sb, int w, unsigned vb) {
  const int j = cta_j(vb), m = cta_m(vb);
  if (w == 0) {
    if (elect()) {
      const unsigned t = atomicAdd(&g_ctr, 1u) / NCTA + 1u;
      asm volatile("st.shared.u32 [%0], %1;" ::"r"(sb + OFF_EPOCH), "r"(t) : "memory");
      mbar_arrive(sb + BAR_EPOCH);
    }
  }
  const unsigned tag = get_tag(sb);
  mbar_wait(sb + BAR_FULLB + 24, 0);
  const uint32_t stg = sb + OFF_T + w * 12288, stb = sb + BAR_STG + w * 24;
  Ring rs = {0, 0};
  uint32_t vs = 33 % NA, vph = 0;
  auto cs_image = [&](int L) {
      const int lane = lane_id();
      poll_flags(&g_jflag[2 * L][j][0], 16, L ? CSNEED : 0xFFFu, tag * 4);
#pragma unroll
      for (int p = 0; p < 3; p++) {
        const uint4 u = ldcg4(&g_cs[L][0][p * 1024 + 128 * j + lane * 4]), v = ldcg4(&g_cs[L][1][p * 1024 + 128 * j + lane * 4]);
        const float c0 = __uint_as_float(u.x) + __uint_as_float(v.x), c1 = __uint_as_float(u.y) + __uint_as_float(v.y);
        const float c2 = __uint_as_float(u.z) + __uint_as_float(v.z), c3 = __uint_as_float(u.w) + __uint_as_float(v.w);
        const uint32_t h0 = pack2(c0, c1), h1 = pack2(c2, c3), dst = sb + OFF_CS + (p * 16 + (lane >> 1)) * 96 + L * 48 + (lane & 1) * 8;
        sts64(dst, h0, h1); sts64(dst + 16, pack2(c0 - lo16(h0), c1 - hi16(h0)), pack2(c2 - lo16(h1), c3 - hi16(h1))); sts64(dst + 32, h0, h1);
        if (L == 0) { sts64(dst + 48, 0u, 0u); sts64(dst + 64, 0u, 0u); sts64(dst + 80, 0u, 0u); }
      }
      if (L == 0 && lane < 4) sts64(sb + OFF_CS + 4608 + lane * 8, 0u, 0u);
      fence_async_smem();
      __syncwarp();
      if (elect()) mbar_arrive(sb + BAR_CS + L * 8);
      TS(4, 2 + L * 2);
  };
#pragma unroll 1
  for (int L = 0; L < 4; L++) {
    const int lane = lane_id();
    if (L == 0) {
      {
        const int wt = m >= 12, col = ((0x2021 >> (m & 12)) & 3) * 1024 + 128 * j + (m & 3) * 32;
        const CUtensorMap* tm = &P.mcs[wt];
        __nanosleep(wt ? D2 : CD);
        constexpr int nb = 8;
        float a[8] = {0.f, 0.f, 0.f, 0.f, 0.f, 0.f, 0.f, 0.f};
#pragma unroll 1
        for (int b = -3; b < nb; b++) {
          if (b >= 0) {
            mbar_wait(stb + rs.s * 8, rs.ph);
            sum_packets<KC>(a, stg + rs.s * 4096 + lane * 16, 8);
            fence_async_smem();
            __syncwarp();
          }
          const uint32_t sl = b < 0 ? (rs.s + b + 3) % 3 : rs.s;
          if (b + 3 < nb && elect()) { mbar_expect_tx(stb + sl * 8, 4096); tma_load_2d(stg + sl * 4096, tm, stb + sl * 8, col, (w * (16 - nb) + b + 3) * 64); }
          if (b >= 0) adv<3>(rs); else pause(CP);
        }
#pragma unroll 1
        for (int d = 4; d < 32; d *= 2)
#pragma unroll
          for (int u = 0; u < 8; u++) a[u] += __shfl_xor_sync(0xffffffffu, a[u], d);
        if (lane < 4) {
          float4* dst = reinterpret_cast<float4*>(&g_cs[wt][w][col + lane * 8]);
          dst[0] = make_float4(a[0], a[1], a[2], a[3]); dst[1] = make_float4(a[4], a[5], a[6], a[7]);
        }
        helper_bar();
        if (w == 0 && elect()) { fence_gpu(); st_flag(&g_jflag[2 * wt][j][m], tag * 4); }
      }
      if (w == 0) TS(4, 1 + L * 2);
    }
    if (L > 0 && w == 0) {
      mbar_wait(sb + BAR_SIGP + 16, (L - 1) & 1);
      fence_async_global();
      __nanosleep(CO && L == 1 ? SE : SD);
    }
    if (CO && L < 2 && w == 0) cs_image(L);
    if (w == (L == 0)) {
      if (L == 0) { mbar_wait(sb + BAR_WPHI, 0); __nanosleep(S0); }
#pragma unroll 1
      for (int p = 0; p < 2; p++) {
        uint4 v[8];
        for (int it = 0;; it++) {
          bool ok = true;
#pragma unroll
          for (int t = 0; t < 8; t++) v[t] = ld_pkt(&g_stats[m][p][t][lane]);
#pragma unroll
          for (int t = 0; t < 8; t++) ok = ok && (v[t].w & 15u) == seq4(tag, L);
          if (__all_sync(0xffffffffu, ok)) break;
          __nanosleep(200);
          if (it > (1 << 20)) __trap();
        }
        float s0 = 0.f, q0 = 0.f, s1 = 0.f, q1 = 0.f;
#pragma unroll
        for (int t = 0; t < 8; t++) { s0 += __uint_as_float(v[t].x); q0 += __uint_as_float(v[t].y); s1 += __uint_as_float(v[t].z); q1 += __uint_as_float(v[t].w & ~15u); }
        s0 *= (1.f / 1024); s1 *= (1.f / 1024);
        sts64(sb + OFF_MR + p * 256 + lane * 8, __float_as_uint(rsqrtf(fmaxf(q0 * (1.f / 1024) - s0 * s0, 0.f) + 1e-5f)),
              __float_as_uint(rsqrtf(fmaxf(q1 * (1.f / 1024) - s1 * s1, 0.f) + 1e-5f)));
#pragma unroll
        for (int r = 0; r < 2; r++) {
          const float v = -0.5f * (r ? s1 : s0);
          const uint32_t hh = pack2(v, v), hl = pack2(v, v - lo16(hh));
          const bool b = L & 1;
          sts128(sb + (b ? OFF_MB : OFF_MA) + p * 1024 + (lane >> 3) * 256 + r * 128 + (lane & 7) * 16, b ? 0u : hh, b ? hh << 16 : hl >> 16, b ? hl : 0u, 0u);
        }
      }
      fence_async_smem();
      __syncwarp();
      if (elect()) {
        mbar_arrive(sb + BAR_STAT);
      }
      TS(2, 0 + L * 8);
    }
    if (!CO && L < 2 && w == 0) cs_image(L);
    if (L & 1) {
      const uint32_t flip = L == 1 ? 0u : 1u;
      mbar_wait(sb + BAR_SIGT, 1);
      {
        int it = 0;
        if (PSL) __nanosleep(m < 8 ? PSL : PSL + 600);
        while (!__all_sync(0xffffffffu, (ld_flag(reinterpret_cast<const unsigned*>(&g_kvpart[j][m][w][512]) + (lane & 15) * 8) ^ flip) & 1u)) { if (PSL) __nanosleep(100); if (++it > (1 << 22)) __trap(); }
        fence_async_global();
      }
      if (w == 0) TS(4, 6 + L * 2);
      float a[8], z;
      for (int it = 0;; it++) {
        if (elect()) { mbar_expect_tx(stb + rs.s * 8, 8704); bulk_load(stg, &g_kvpart[j][m][w][0], 8704, stb + rs.s * 8); }
        mbar_wait(stb + rs.s * 8, rs.ph);
        if (w == 0) TS(4, 21 + L);
        adv<3>(rs);
#pragma unroll
        for (int u = 0; u < 8; u++) a[u] = 0.f;
        z = 0.f;
        uint32_t ok = 1u;
#pragma unroll
        for (int u = 0; u < 4; u++) { const float v = lds32f(stg + 8192 + u * 128 + (lane & 3) * 32 + (lane >> 2) * 4); z += v; ok &= __float_as_uint(v) ^ flip; }
        const uint2 tg = sum_packets<8>(a, stg + lane * 16, 16);
        ok &= flip ? ~tg.y : tg.x;
        if (__all_sync(0xffffffffu, ok & 1u)) break;
        fence_async_smem();
        if (it > (1 << 16)) __trap();
      }
      {
        uint4* img = &g_kvfin[j][m][w * 8 + (lane >> 2)];
        uint32_t a0 = __float_as_uint(a[0]) >> 16;
        a0 += ~(a0 ^ flip) & 1u;
        st_v4(img + (lane & 3) * 16, __byte_perm(a0, pack2(0.f, a[1]), 0x7610), pack2(a[2], a[3]), pack2(a[4], a[5]), pack2(a[6], a[7]));
        const uint32_t cz = pack2(0.f, qsum(z)) | (0x3781u ^ flip);
        if (!(lane & 3)) st_v4(img + 64, cz, cz, cz, cz);
        __syncwarp();
        if (elect()) st_flag(&g_jflag[m >> 3][j][(m & 7) * 2 + w], tag * 4 + L);
      }
      if (w == 0) TS(4, 7 + L * 2);
    } else {
      mbar_wait(sb + BAR_SIGT, 0);
      if (w == 0) {
        if (elect()) { fence_gpu(); st_flag(&g_hint[m][j], tag * 16 + 4 * L); st_flag(&g_jflag[1][j][m], tag * 4 + L); }
        if (L == 0) {
          __nanosleep(KSL);
          poll_flags(&g_jflag[1][j][0], 16, 0xFFFFu, tag * 4);
          if (elect()) mbar_arrive(sb + BAR_WPHI);
        }
      } else if (m > 0) {
        poll_flags(&g_hint[m - 1][j], 1, 1u, tag * 16 + 4 * L);
        if (elect()) { mbar_expect_tx(sb + BAR_HALO, 8192); bulk_load(sb + OFF_S + 8192, &g_halo[m - 1][j][0][0], 8192, sb + BAR_HALO); }
        TS(2, 2 + L * 8);
      }
    }
    if (w == 0) {
#pragma unroll 1
      for (int e = 0; e < (L < 3 ? 2 : 1); e++) {
        unsigned* flag = early(&g_hint[m][j]);
        mbar_wait(sb + BAR_SIGP + e * 8, L & 1);
        TS(2, (e ? 6 : 3) + L * 8);
        TSH((2 * L + e) * 8);
        pause(XD);
        if (elect()) st_flag(flag, tag * 16 + 4 * L + 1 + e);
        TSH((2 * L + e) * 8 + 1);
      }
    } else {
#pragma unroll 1
      for (int i = 0; i < (L < 3 ? 28 : 14); i++) {
        const bool isx = i >= 14;
        const uint32_t a = sb + OFF_A + vs * SLOT + lane * 128 + ((lane >> 4) * 4 + (lane & 3)) * 16 + (lane & 12), code = img_code(isx, L + isx);
        for (int it = 0;; it++) {
          mbar_wait(sb + BAR_LAND + vs * 8, (vph >> vs) & 1);
          vph ^= 1u << vs;
          if (i - 14 * isx < 2) TSH((2 * L + isx) * 8 + 3 + 2 * (i - 14 * isx));
          uint32_t bad = 0;
#pragma unroll
          for (int u = 0; u < 4; u++) bad |= __float_as_uint(lds32f(a + u * 4096)) ^ code;
          if (__all_sync(0xffffffffu, !(bad & img_mask(isx)))) break;
          if (it > (1 << 16)) __trap();
          fence_async_smem();
          if (elect()) {
            mbar_expect_tx(sb + BAR_LAND + vs * 8, SLOT);
            bulk_load(sb + OFF_A + vs * SLOT, &g_img[isx ? XBUF(L + 1) : 0][m][o_order(i - 14 * isx + 2, j)][0], SLOT, sb + BAR_LAND + vs * 8);
          }
        }
        if (elect()) mbar_arrive(sb + BAR_FULLA + vs * 8);
        if (i - 14 * isx < 2) TSH((2 * L + isx) * 8 + 4 + 2 * (i - 14 * isx));
        if (++vs == NA) vs = 0;
      }
      vs = (vs + ((L & 1) ? 16 : 32 - NJ)) % NA;
    }
  }
}

__device__ __forceinline__ void spare(const Params& P, uint32_t sb, int id) {
  const int tid = threadIdx.x & 127, warp = __shfl_sync(0xffffffffu, threadIdx.x >> 5, 0), w = warp >> 2, lane = tid & 31, j = 2 * id + w;
  const uint32_t ring = w * 6 * SLOT, wp = 12 * SLOT + w * 8192, bar = sb + 13 * SLOT + w * 64;
  auto part = [&](int t) { return (t >> 4) ^ w; };
  auto load = [&](int t, uint32_t sl) {
    mbar_expect_tx(bar + sl * 8, t == 0 ? SLOT + 8192 : SLOT);
    tma_load_w(sb + ring + sl * SLOT, &P.mw[1], bar + sl * 8, part(t) * 1024 + 128 * j, t & 15);
  };
  if (!(warp & 3) && elect()) {
    if (w == 2) sts32(sb + OFF_EPOCH, atomicAdd(&g_ctr, 1u) / NCTA + 1u);
    else {
      __nanosleep(D3);
#pragma unroll 1
      for (int t = 0; t < 5; t++) {
        mbar_init(bar + t * 8, 1);
        asm volatile("fence.mbarrier_init.release.cluster;" ::: "memory");
        load(t, t);
      }
      tma_load_2d(sb + wp, &P.mwphi, bar, 0, 128 * j);
    }
  }
  if (w == 2) {
    u64 a = (u64)&P;
    asm volatile("" : "+l"(a));
    const u64 pc = *reinterpret_cast<const u64*>(a - 0x240 + 0x118);
    const unsigned off = IP0 + (id * 128 + tid) * 128;
    if ((pc >> 40) == (a >> 40) && off < IP1) asm volatile("prefetch.global.L2 [%0];" ::"l"(pc + off));
    if (IPF == 2 && (pc >> 40) == (a >> 40)) asm volatile("prefetch.global.L2 [%0];" ::"l"(pc + off - IP0));
  }
  __syncthreads();
  const unsigned tag = get_tag<false>(sb);
  if (w == 2) {
    int it = 0;
    while ((int)(ld_flag(&g_ctr) - tag * NCTA) < 0) { if (++it > (1 << 22)) __trap(); }
    return;
  }
  Ring r = {4, 1};
  float d[64];
  auto fold = [&]() {
    mbar_wait(bar + r.s * 8, r.ph);
    wgmma_fence();
#pragma unroll
    for (int q = 0; q < 8; q++)
      wgmma_ss_n32(reinterpret_cast<float (&)[16]>(d[16 * (q >> 1)]), desc_lo(SB + ring + r.s * SLOT, 16) + (q >> 2) * 512 + (q & 3) * 2, desc_lo(SB + wp, 512) + q * 64, q & 1);
    wgmma_commit();
  };
#pragma unroll
  for (int i = 0; i < 64; i++) d[i] = 0.f;
  int t = -1;
#pragma unroll 1
  for (int g = 0; g < 2; g++) {
    float cs[32] = {};
#pragma unroll 1
    do {
      uint32_t f[32];
#pragma unroll
      for (int i = 0; i < 32; i++) { f[i] = pack2(d[2 * i], d[2 * i + 1]); cs[i & 30] += d[2 * i]; cs[i | 1] += d[2 * i + 1]; }
      wg_bar(w);
      const uint32_t sl = r.s;
      if (t < 31) adv<5>(r);
      fold();
      if (!(warp & 3) && t >= 0 && t < 27 && elect()) load(t + 5, sl);
      if (g == w && t >= 0) {
        uint4* dst = &g_wf[0][j][t & 15][((tid >> 5) * 16 + (lane >> 2)) * 8];
#pragma unroll
        for (int q = 0; q < 8; q++)
          dst[(q >> 2) * 512 + (q & 1) * 64 + (((q & 2) * 2 + (lane & 3)) ^ (lane >> 2))] =
              make_uint4(f[4 * (q & 6) + (q & 1)], f[4 * (q & 6) + (q & 1) + 2], f[4 * (q & 6) + (q & 1) + 4], f[4 * (q & 6) + (q & 1) + 6]);
      }
      wgmma_wait<0>();
      fence_regs(d);
    } while (++t != 16 * g + 16);
    const uint32_t red = sb + ring + 5 * SLOT;
#pragma unroll
    for (int i = 0; i < 8; i++) sts128(red + (tid >> 2) * 512 + (i >> 1) * 128 + (lane & 3) * 32 + (i & 1) * 16, __float_as_uint(cs[4 * i]), __float_as_uint(cs[4 * i + 1]), __float_as_uint(cs[4 * i + 2]), __float_as_uint(cs[4 * i + 3]));
    wg_bar(w);
    float a = 0.f;
#pragma unroll 4
    for (int i = 0; i < 32; i++) a += lds32f(red + i * 512 + tid * 4);
    g_cs[1][0][(g ^ w) * 1024 + j * 128 + tid] = a;
  }
  wg_bar(w);
  if (tid == 0) { fence_gpu(); st_flag(&g_jflag[2][j][0], tag * 4); }
}

__global__ void __launch_bounds__(NTHREADS, 1) fused_kernel(const __grid_constant__ Params P) {
  extern __shared__ __align__(1024) uint8_t smem_raw[];
  constexpr uint32_t sb = SB;
  const int tid = threadIdx.x;
  const unsigned vb = vblock();
  if (vb >= 128) { spare(P, sb, vb - 128); return; }
  const int warp = __shfl_sync(0xffffffffu, tid >> 5, 0);
  if (elect()) {
    if (warp == 11) { prefetch_map(&P.mx); prefetch_map(&P.mw[0]); if (smem_u32(smem_raw) != SB) __trap(); }
    if (warp < 8) {
#pragma unroll
      for (int i = 0; i < 8; i++) mbar_init(sb + OFF_BAR + (warp * 8 + i) * 8, warp == 2 || warp == 3 ? 2 : (warp == 4 ? 8 : 1));
    }
    asm volatile("fence.mbarrier_init.release.cluster;" ::: "memory");
    if (warp < 2) {
      const int j = cta_j(vb);
#pragma unroll 1
      for (int i = 0; i < (warp == 0 ? PRE_B : PRE_A); i++) {
        const uint32_t bar = sb + BAR_FULLB + warp * 64 + i * 8;
        mbar_expect_tx(bar, SLOT);
        if (warp == 0) tma_load_w(sb + OFF_B + i * SLOT, &P.mw[0], bar, 1024 + (i & 1) * 1024 + 128 * j, kv_order(i >> 1, j, 0));
        else tma_load_3d(sb + OFF_A + i * SLOT, &P.mx, bar, kv_order(i, j, 0) * 64, cta_m(vb) * 64, 0);
      }
    }
  }
  if (tid == 0) TS(6, 0);
  __syncthreads();
  if (tid == 0) TS(6, 2);
  if (warp < 4) {
    reg_dealloc<PREGS>();
    if (warp & 2) helper(P, sb, warp & 1, vb);
    else if (warp & 1) a_loader(P, sb, vb);
    else b_producer(P, sb, vb);
  } else {
    reg_alloc<CREGS>();
    consumer(P, sb, (warp >> 2) - 1, vb);
  }
}

typedef CUresult (*EncodeFn)(CUtensorMap*, CUtensorMapDataType, cuuint32_t, void*, const cuuint64_t*, const cuuint64_t*,
                             const cuuint32_t*, const cuuint32_t*, CUtensorMapInterleave, CUtensorMapSwizzle,
                             CUtensorMapL2promotion, CUtensorMapFloatOOBfill);

void encode(EncodeFn fn, CUtensorMap* m, const void* ptr, int rank, const cuuint64_t* dims, const cuuint64_t* strides,
            const cuuint32_t* box, CUtensorMapSwizzle swz) {
  const cuuint32_t es[5] = {1, 1, 1, 1, 1};
  fn(m, CU_TENSOR_MAP_DATA_TYPE_BFLOAT16, rank, const_cast<void*>(ptr), dims, strides, box, es, CU_TENSOR_MAP_INTERLEAVE_NONE,
     swz, CU_TENSOR_MAP_L2_PROMOTION_L2_256B, CU_TENSOR_MAP_FLOAT_OOB_FILL_NONE);
}
void encode_w(EncodeFn fn, CUtensorMap* m, const void* ptr, int ncols, bool perm) {
  const cuuint64_t p = (cuuint64_t)ncols * 2, d[5] = {(cuuint64_t)ncols, 2, 4, 4, 32}, s[4] = {p, (perm ? 8 : 2) * p, (perm ? 2 : 8) * p, 32 * p};
  const cuuint32_t box[5] = {64, 2, 4, 4, 2};
  encode(fn, m, ptr, 5, d, s, box, CU_TENSOR_MAP_SWIZZLE_128B);
}

void encode_cs(EncodeFn fn, CUtensorMap* m, const void* ptr, int ncols) {
  const cuuint64_t d[2] = {(cuuint64_t)ncols, 1024}, s[1] = {(cuuint64_t)ncols * 2};
  const cuuint32_t box[2] = {32, 64};
  encode(fn, m, ptr, 2, d, s, box, CU_TENSOR_MAP_SWIZZLE_NONE);
}

}

extern "C" void kernel_launch(void* const* d_in, const int* in_sizes, int n_in, void* d_out, int out_size) {
  (void)in_sizes; (void)n_in; (void)out_size;
  void* fnp = nullptr;
  cudaDriverEntryPointQueryResult q;
  cudaGetDriverEntryPoint("cuTensorMapEncodeTiled", &fnp, cudaEnableDefault, &q);
  EncodeFn fn = (EncodeFn)fnp;
  Params P;
  {
    const cuuint64_t dims[3] = {1024, 1024, 2}, strides[2] = {4096, 2048};
    const cuuint32_t box[3] = {64, 64, 2};
    encode(fn, &P.mx, d_in[0], 3, dims, strides, box, CU_TENSOR_MAP_SWIZZLE_128B);
  }
  P.out = (uint4*)d_out;
  encode_w(fn, &P.mw[0], d_in[1], 3072, false);
  encode_w(fn, &P.mw[1], d_in[4], 3072, true);
  encode_w(fn, &P.mw[2], d_in[1], 3072, true);
  encode_w(fn, &P.mwo[0], d_in[2], 1024, true);
  encode_w(fn, &P.mwo[1], d_in[6], 1024, false);
  encode_cs(fn, &P.mcs[0], d_in[1], 3072);
  encode_cs(fn, &P.mcs[1], d_in[4], 3072);
  {
    const cuuint64_t dims[2] = {32, 1024}, strides[1] = {64};
    const cuuint32_t box[2] = {32, 128};
    encode(fn, &P.mwphi, d_in[5], 2, dims, strides, box, CU_TENSOR_MAP_SWIZZLE_64B);
  }
  cudaFuncSetAttribute(fused_kernel, cudaFuncAttributeMaxDynamicSharedMemorySize, SMEM_BYTES);
  fused_kernel<<<NCTA, NTHREADS, SMEM_BYTES, cudaStreamPerThread>>>(P);
}
```

```cpp
#include <cuda_runtime.h>
#include <cuda_bf16.h>
#include <cuda.h>
#include <stdint.h>

namespace {

__device__ __forceinline__ void wgmma_ss_n256(float (&d)[128], uint32_t da, uint32_t ha, uint32_t db, int sd) {
  asm volatile("{\n.reg .pred p;\n.reg .b64 a, b;\nsetp.ne.b32 p, %130, 0;\nmov.b64 a, {%128, %131};\nmov.b64 b, {%129, 0x40000040};\n"
    "wgmma.mma_async.sync.aligned.m64n256k16.f32.bf16.bf16 {%0,%1,%2,%3,%4,%5,%6,%7,%8,%9,%10,%11,%12,%13,%14,%15,%16,%17,%18,%19,%20,%21,%22,%23,%24,%25,%26,%27,%28,%29,%30,%31,%32,%33,%34,%35,%36,%37,%38,%39,%40,%41,%42,%43,%44,%45,%46,%47,%48,%49,%50,%51,%52,%53,%54,%55,%56,%57,%58,%59,%60,%61,%62,%63,%64,%65,%66,%67,%68,%69,%70,%71,%72,%73,%74,%75,%76,%77,%78,%79,%80,%81,%82,%83,%84,%85,%86,%87,%88,%89,%90,%91,%92,%93,%94,%95,%96,%97,%98,%99,%100,%101,%102,%103,%104,%105,%106,%107,%108,%109,%110,%111,%112,%113,%114,%115,%116,%117,%118,%119,%120,%121,%122,%123,%124,%125,%126,%127}, a, b, p, 1, 1, 0, 1;\n}\n"
    : "+f"(d[0]),"+f"(d[1]),"+f"(d[2]),"+f"(d[3]),"+f"(d[4]),"+f"(d[5]),"+f"(d[6]),"+f"(d[7]),"+f"(d[8]),"+f"(d[9]),"+f"(d[10]),"+f"(d[11]),"+f"(d[12]),"+f"(d[13]),"+f"(d[14]),"+f"(d[15]),"+f"(d[16]),"+f"(d[17]),"+f"(d[18]),"+f"(d[19]),"+f"(d[20]),"+f"(d[21]),"+f"(d[22]),"+f"(d[23]),"+f"(d[24]),"+f"(d[25]),"+f"(d[26]),"+f"(d[27]),"+f"(d[28]),"+f"(d[29]),"+f"(d[30]),"+f"(d[31]),"+f"(d[32]),"+f"(d[33]),"+f"(d[34]),"+f"(d[35]),"+f"(d[36]),"+f"(d[37]),"+f"(d[38]),"+f"(d[39]),"+f"(d[40]),"+f"(d[41]),"+f"(d[42]),"+f"(d[43]),"+f"(d[44]),"+f"(d[45]),"+f"(d[46]),"+f"(d[47]),"+f"(d[48]),"+f"(d[49]),"+f"(d[50]),"+f"(d[51]),"+f"(d[52]),"+f"(d[53]),"+f"(d[54]),"+f"(d[55]),"+f"(d[56]),"+f"(d[57]),"+f"(d[58]),"+f"(d[59]),"+f"(d[60]),"+f"(d[61]),"+f"(d[62]),"+f"(d[63]),"+f"(d[64]),"+f"(d[65]),"+f"(d[66]),"+f"(d[67]),"+f"(d[68]),"+f"(d[69]),"+f"(d[70]),"+f"(d[71]),"+f"(d[72]),"+f"(d[73]),"+f"(d[74]),"+f"(d[75]),"+f"(d[76]),"+f"(d[77]),"+f"(d[78]),"+f"(d[79]),"+f"(d[80]),"+f"(d[81]),"+f"(d[82]),"+f"(d[83]),"+f"(d[84]),"+f"(d[85]),"+f"(d[86]),"+f"(d[87]),"+f"(d[88]),"+f"(d[89]),"+f"(d[90]),"+f"(d[91]),"+f"(d[92]),"+f"(d[93]),"+f"(d[94]),"+f"(d[95]),"+f"(d[96]),"+f"(d[97]),"+f"(d[98]),"+f"(d[99]),"+f"(d[100]),"+f"(d[101]),"+f"(d[102]),"+f"(d[103]),"+f"(d[104]),"+f"(d[105]),"+f"(d[106]),"+f"(d[107]),"+f"(d[108]),"+f"(d[109]),"+f"(d[110]),"+f"(d[111]),"+f"(d[112]),"+f"(d[113]),"+f"(d[114]),"+f"(d[115]),"+f"(d[116]),"+f"(d[117]),"+f"(d[118]),"+f"(d[119]),"+f"(d[120]),"+f"(d[121]),"+f"(d[122]),"+f"(d[123]),"+f"(d[124]),"+f"(d[125]),"+f"(d[126]),"+f"(d[127])
    : "r"(da), "r"(db), "r"(sd), "r"(ha));
}
__device__ __forceinline__ void wgmma_ss_n128(float (&d)[64], uint32_t da, uint32_t ha, uint32_t db, int sd) {
  asm volatile("{\n.reg .pred p;\n.reg .b64 a, b;\nsetp.ne.b32 p, %66, 0;\nmov.b64 a, {%64, %67};\nmov.b64 b, {%65, 0x40000040};\n"
    "wgmma.mma_async.sync.aligned.m64n128k16.f32.bf16.bf16 {%0,%1,%2,%3,%4,%5,%6,%7,%8,%9,%10,%11,%12,%13,%14,%15,%16,%17,%18,%19,%20,%21,%22,%23,%24,%25,%26,%27,%28,%29,%30,%31,%32,%33,%34,%35,%36,%37,%38,%39,%40,%41,%42,%43,%44,%45,%46,%47,%48,%49,%50,%51,%52,%53,%54,%55,%56,%57,%58,%59,%60,%61,%62,%63}, a, b, p, 1, 1, 0, 1;\n}\n"
    : "+f"(d[0]),"+f"(d[1]),"+f"(d[2]),"+f"(d[3]),"+f"(d[4]),"+f"(d[5]),"+f"(d[6]),"+f"(d[7]),"+f"(d[8]),"+f"(d[9]),"+f"(d[10]),"+f"(d[11]),"+f"(d[12]),"+f"(d[13]),"+f"(d[14]),"+f"(d[15]),"+f"(d[16]),"+f"(d[17]),"+f"(d[18]),"+f"(d[19]),"+f"(d[20]),"+f"(d[21]),"+f"(d[22]),"+f"(d[23]),"+f"(d[24]),"+f"(d[25]),"+f"(d[26]),"+f"(d[27]),"+f"(d[28]),"+f"(d[29]),"+f"(d[30]),"+f"(d[31]),"+f"(d[32]),"+f"(d[33]),"+f"(d[34]),"+f"(d[35]),"+f"(d[36]),"+f"(d[37]),"+f"(d[38]),"+f"(d[39]),"+f"(d[40]),"+f"(d[41]),"+f"(d[42]),"+f"(d[43]),"+f"(d[44]),"+f"(d[45]),"+f"(d[46]),"+f"(d[47]),"+f"(d[48]),"+f"(d[49]),"+f"(d[50]),"+f"(d[51]),"+f"(d[52]),"+f"(d[53]),"+f"(d[54]),"+f"(d[55]),"+f"(d[56]),"+f"(d[57]),"+f"(d[58]),"+f"(d[59]),"+f"(d[60]),"+f"(d[61]),"+f"(d[62]),"+f"(d[63])
    : "r"(da), "r"(db), "r"(sd), "r"(ha));
}
__device__ __forceinline__ void wgmma_ss_n40_tt(float (&d)[20], uint32_t da, uint32_t db, int sd) {
  asm volatile("{\n.reg .pred p;\n.reg .b64 a, b;\nsetp.ne.b32 p, %22, 0;\nmov.b64 a, {%20, 0x40000040};\nmov.b64 b, {%21, 0x8};\n"
    "wgmma.mma_async.sync.aligned.m64n40k16.f32.bf16.bf16 {%0,%1,%2,%3,%4,%5,%6,%7,%8,%9,%10,%11,%12,%13,%14,%15,%16,%17,%18,%19}, a, b, p, 1, 1, 1, 1;\n}\n"
    : "+f"(d[0]),"+f"(d[1]),"+f"(d[2]),"+f"(d[3]),"+f"(d[4]),"+f"(d[5]),"+f"(d[6]),"+f"(d[7]),"+f"(d[8]),"+f"(d[9]),"+f"(d[10]),"+f"(d[11]),"+f"(d[12]),"+f"(d[13]),"+f"(d[14]),"+f"(d[15]),"+f"(d[16]),"+f"(d[17]),"+f"(d[18]),"+f"(d[19])
    : "r"(da), "r"(db), "r"(sd));
}
__device__ __forceinline__ void wgmma_ss_n32(float (&d)[16], uint32_t da, uint32_t db, int sd) {
  asm volatile("{\n.reg .pred p;\n.reg .b64 a, b;\nsetp.ne.b32 p, %18, 0;\nmov.b64 a, {%16, 0x40000040};\nmov.b64 b, {%17, 0x80000020};\n"
    "wgmma.mma_async.sync.aligned.m64n32k16.f32.bf16.bf16 {%0,%1,%2,%3,%4,%5,%6,%7,%8,%9,%10,%11,%12,%13,%14,%15}, a, b, p, 1, 1, 0, 1;\n}\n"
    : "+f"(d[0]),"+f"(d[1]),"+f"(d[2]),"+f"(d[3]),"+f"(d[4]),"+f"(d[5]),"+f"(d[6]),"+f"(d[7]),"+f"(d[8]),"+f"(d[9]),"+f"(d[10]),"+f"(d[11]),"+f"(d[12]),"+f"(d[13]),"+f"(d[14]),"+f"(d[15])
    : "r"(da), "r"(db), "r"(sd));
}
__device__ __forceinline__ void wgmma_rs_n40(float (&d)[20], uint32_t a0, uint32_t a1, uint32_t a2, uint32_t a3, uint32_t db, int sd) {
  asm volatile("{\n.reg .pred p;\n.reg .b64 b;\nsetp.ne.b32 p, %25, 0;\nmov.b64 b, {%24, 0x10};\n"
    "wgmma.mma_async.sync.aligned.m64n40k16.f32.bf16.bf16 {%0,%1,%2,%3,%4,%5,%6,%7,%8,%9,%10,%11,%12,%13,%14,%15,%16,%17,%18,%19}, {%20,%21,%22,%23}, b, p, 1, 1, 1;\n}\n"
    : "+f"(d[0]),"+f"(d[1]),"+f"(d[2]),"+f"(d[3]),"+f"(d[4]),"+f"(d[5]),"+f"(d[6]),"+f"(d[7]),"+f"(d[8]),"+f"(d[9]),"+f"(d[10]),"+f"(d[11]),"+f"(d[12]),"+f"(d[13]),"+f"(d[14]),"+f"(d[15]),"+f"(d[16]),"+f"(d[17]),"+f"(d[18]),"+f"(d[19])
    : "r"(a0), "r"(a1), "r"(a2), "r"(a3), "r"(db), "r"(sd));
}
__device__ __forceinline__ void wgmma_r1_n256(float (&d)[128], uint32_t da, uint32_t db, int sd) {
  asm volatile("{\n.reg .pred p;\n.reg .b64 a, b;\nsetp.ne.b32 p, %130, 0;\nmov.b64 a, {%128, 0x8};\nmov.b64 b, {%129, 0x6};\n"
    "wgmma.mma_async.sync.aligned.m64n256k16.f32.bf16.bf16 {%0,%1,%2,%3,%4,%5,%6,%7,%8,%9,%10,%11,%12,%13,%14,%15,%16,%17,%18,%19,%20,%21,%22,%23,%24,%25,%26,%27,%28,%29,%30,%31,%32,%33,%34,%35,%36,%37,%38,%39,%40,%41,%42,%43,%44,%45,%46,%47,%48,%49,%50,%51,%52,%53,%54,%55,%56,%57,%58,%59,%60,%61,%62,%63,%64,%65,%66,%67,%68,%69,%70,%71,%72,%73,%74,%75,%76,%77,%78,%79,%80,%81,%82,%83,%84,%85,%86,%87,%88,%89,%90,%91,%92,%93,%94,%95,%96,%97,%98,%99,%100,%101,%102,%103,%104,%105,%106,%107,%108,%109,%110,%111,%112,%113,%114,%115,%116,%117,%118,%119,%120,%121,%122,%123,%124,%125,%126,%127}, a, b, p, 1, 1, 0, 1;\n}\n"
    : "+f"(d[0]),"+f"(d[1]),"+f"(d[2]),"+f"(d[3]),"+f"(d[4]),"+f"(d[5]),"+f"(d[6]),"+f"(d[7]),"+f"(d[8]),"+f"(d[9]),"+f"(d[10]),"+f"(d[11]),"+f"(d[12]),"+f"(d[13]),"+f"(d[14]),"+f"(d[15]),"+f"(d[16]),"+f"(d[17]),"+f"(d[18]),"+f"(d[19]),"+f"(d[20]),"+f"(d[21]),"+f"(d[22]),"+f"(d[23]),"+f"(d[24]),"+f"(d[25]),"+f"(d[26]),"+f"(d[27]),"+f"(d[28]),"+f"(d[29]),"+f"(d[30]),"+f"(d[31]),"+f"(d[32]),"+f"(d[33]),"+f"(d[34]),"+f"(d[35]),"+f"(d[36]),"+f"(d[37]),"+f"(d[38]),"+f"(d[39]),"+f"(d[40]),"+f"(d[41]),"+f"(d[42]),"+f"(d[43]),"+f"(d[44]),"+f"(d[45]),"+f"(d[46]),"+f"(d[47]),"+f"(d[48]),"+f"(d[49]),"+f"(d[50]),"+f"(d[51]),"+f"(d[52]),"+f"(d[53]),"+f"(d[54]),"+f"(d[55]),"+f"(d[56]),"+f"(d[57]),"+f"(d[58]),"+f"(d[59]),"+f"(d[60]),"+f"(d[61]),"+f"(d[62]),"+f"(d[63]),"+f"(d[64]),"+f"(d[65]),"+f"(d[66]),"+f"(d[67]),"+f"(d[68]),"+f"(d[69]),"+f"(d[70]),"+f"(d[71]),"+f"(d[72]),"+f"(d[73]),"+f"(d[74]),"+f"(d[75]),"+f"(d[76]),"+f"(d[77]),"+f"(d[78]),"+f"(d[79]),"+f"(d[80]),"+f"(d[81]),"+f"(d[82]),"+f"(d[83]),"+f"(d[84]),"+f"(d[85]),"+f"(d[86]),"+f"(d[87]),"+f"(d[88]),"+f"(d[89]),"+f"(d[90]),"+f"(d[91]),"+f"(d[92]),"+f"(d[93]),"+f"(d[94]),"+f"(d[95]),"+f"(d[96]),"+f"(d[97]),"+f"(d[98]),"+f"(d[99]),"+f"(d[100]),"+f"(d[101]),"+f"(d[102]),"+f"(d[103]),"+f"(d[104]),"+f"(d[105]),"+f"(d[106]),"+f"(d[107]),"+f"(d[108]),"+f"(d[109]),"+f"(d[110]),"+f"(d[111]),"+f"(d[112]),"+f"(d[113]),"+f"(d[114]),"+f"(d[115]),"+f"(d[116]),"+f"(d[117]),"+f"(d[118]),"+f"(d[119]),"+f"(d[120]),"+f"(d[121]),"+f"(d[122]),"+f"(d[123]),"+f"(d[124]),"+f"(d[125]),"+f"(d[126]),"+f"(d[127])
    : "r"(da), "r"(db), "r"(sd));
}
__device__ __forceinline__ void wgmma_r1_n128(float (&d)[64], uint32_t da, uint32_t db, int sd) {
  asm volatile("{\n.reg .pred p;\n.reg .b64 a, b;\nsetp.ne.b32 p, %66, 0;\nmov.b64 a, {%64, 0x8};\nmov.b64 b, {%65, 0x6};\n"
    "wgmma.mma_async.sync.aligned.m64n128k16.f32.bf16.bf16 {%0,%1,%2,%3,%4,%5,%6,%7,%8,%9,%10,%11,%12,%13,%14,%15,%16,%17,%18,%19,%20,%21,%22,%23,%24,%25,%26,%27,%28,%29,%30,%31,%32,%33,%34,%35,%36,%37,%38,%39,%40,%41,%42,%43,%44,%45,%46,%47,%48,%49,%50,%51,%52,%53,%54,%55,%56,%57,%58,%59,%60,%61,%62,%63}, a, b, p, 1, 1, 0, 1;\n}\n"
    : "+f"(d[0]),"+f"(d[1]),"+f"(d[2]),"+f"(d[3]),"+f"(d[4]),"+f"(d[5]),"+f"(d[6]),"+f"(d[7]),"+f"(d[8]),"+f"(d[9]),"+f"(d[10]),"+f"(d[11]),"+f"(d[12]),"+f"(d[13]),"+f"(d[14]),"+f"(d[15]),"+f"(d[16]),"+f"(d[17]),"+f"(d[18]),"+f"(d[19]),"+f"(d[20]),"+f"(d[21]),"+f"(d[22]),"+f"(d[23]),"+f"(d[24]),"+f"(d[25]),"+f"(d[26]),"+f"(d[27]),"+f"(d[28]),"+f"(d[29]),"+f"(d[30]),"+f"(d[31]),"+f"(d[32]),"+f"(d[33]),"+f"(d[34]),"+f"(d[35]),"+f"(d[36]),"+f"(d[37]),"+f"(d[38]),"+f"(d[39]),"+f"(d[40]),"+f"(d[41]),"+f"(d[42]),"+f"(d[43]),"+f"(d[44]),"+f"(d[45]),"+f"(d[46]),"+f"(d[47]),"+f"(d[48]),"+f"(d[49]),"+f"(d[50]),"+f"(d[51]),"+f"(d[52]),"+f"(d[53]),"+f"(d[54]),"+f"(d[55]),"+f"(d[56]),"+f"(d[57]),"+f"(d[58]),"+f"(d[59]),"+f"(d[60]),"+f"(d[61]),"+f"(d[62]),"+f"(d[63])
    : "r"(da), "r"(db), "r"(sd));
}

__device__ __forceinline__ uint32_t smem_u32(const void* p) { return (uint32_t)__cvta_generic_to_shared(p); }
__device__ __forceinline__ void mbar_init(uint32_t bar, uint32_t cnt) { asm volatile("mbarrier.init.shared::cta.b64 [%0], %1;" ::"r"(bar), "r"(cnt)); }
__device__ __forceinline__ void mbar_expect_tx(uint32_t bar, uint32_t bytes) { asm volatile("mbarrier.arrive.expect_tx.shared::cta.b64 _, [%0], %1;" ::"r"(bar), "r"(bytes) : "memory"); }
__device__ __forceinline__ void mbar_arrive(uint32_t bar) { asm volatile("mbarrier.arrive.shared::cta.b64 _, [%0];" ::"r"(bar) : "memory"); }
__device__ __forceinline__ void mbar_arrive_n(uint32_t bar, uint32_t n) { asm volatile("mbarrier.arrive.shared::cta.b64 _, [%0], %1;" ::"r"(bar), "r"(n) : "memory"); }
__device__ __forceinline__ void mbar_wait(uint32_t bar, uint32_t parity) {
  asm volatile("{\n.reg .pred p;\nLAB_WAIT:\nmbarrier.try_wait.parity.shared::cta.b64 p, [%0], %1;\n@p bra DONE;\nbra LAB_WAIT;\nDONE:\n}" ::"r"(bar), "r"(parity) : "memory");
}
__device__ __forceinline__ void mbar_wait2(uint32_t a, uint32_t pa, uint32_t b, uint32_t pb) {
  asm volatile("{\n.reg .pred p, q;\nLAB_WAIT:\nmbarrier.try_wait.parity.shared::cta.b64 p, [%0], %1;\nmbarrier.try_wait.parity.shared::cta.b64 q, [%2], %3;\n"
               "and.pred p, p, q;\n@p bra DONE;\nbra LAB_WAIT;\nDONE:\n}" ::"r"(a), "r"(pa), "r"(b), "r"(pb) : "memory");
}
__device__ __forceinline__ void mbar_wait3(uint32_t a, uint32_t pa, uint32_t b, uint32_t pb) {
  asm volatile("{\n.reg .pred p, q, r;\nLAB_WAIT:\nmbarrier.try_wait.parity.shared::cta.b64 p, [%0], %1;\nmbarrier.try_wait.parity.shared::cta.b64 q, [%2], %3;\n"
               "mbarrier.try_wait.parity.shared::cta.b64 r, [%2+8], %3;\nand.pred p, p, q;\nand.pred p, p, r;\n@p bra DONE;\nbra LAB_WAIT;\nDONE:\n}" ::"r"(a), "r"(pa), "r"(b), "r"(pb) : "memory");
}
__device__ __forceinline__ bool mbar_probe2(uint32_t a, uint32_t pa, uint32_t b, uint32_t pb) {
  uint32_t ok;
  asm volatile("{\n.reg .pred p, q;\nmbarrier.test_wait.parity.shared::cta.b64 p, [%1], %2;\nmbarrier.test_wait.parity.shared::cta.b64 q, [%3], %4;\n"
               "and.pred p, p, q;\nselp.u32 %0, 1, 0, p;\n}" : "=r"(ok) : "r"(a), "r"(pa), "r"(b), "r"(pb) : "memory");
  return ok != 0;
}
__device__ __forceinline__ void tma_load_3d(uint32_t dst, const CUtensorMap* tm, uint32_t bar, int c0, int c1, int c2) {
  asm volatile("cp.async.bulk.tensor.3d.shared::cluster.global.mbarrier::complete_tx::bytes [%0], [%1, {%3, %4, %5}], [%2];"
               ::"r"(dst), "l"(tm), "r"(bar), "r"(c0), "r"(c1), "r"(c2) : "memory");
}
__device__ __forceinline__ void tma_load_2d(uint32_t dst, const CUtensorMap* tm, uint32_t bar, int c0, int c1) {
  asm volatile("cp.async.bulk.tensor.2d.shared::cluster.global.mbarrier::complete_tx::bytes [%0], [%1, {%3, %4}], [%2];"
               ::"r"(dst), "l"(tm), "r"(bar), "r"(c0), "r"(c1) : "memory");
}
__device__ __forceinline__ void tma_load_w(uint32_t dst, const CUtensorMap* tm, uint32_t bar, int col, int kb) {
#pragma unroll
  for (int q = 0; q < 2; q++)
    asm volatile("cp.async.bulk.tensor.5d.shared::cluster.global.mbarrier::complete_tx::bytes [%0], [%1, {%3, %4, %4, %4, %5}], [%2];"
                 ::"r"(dst + q * 8192), "l"(tm), "r"(bar), "r"(col + q * 64), "r"(0), "r"(2 * kb) : "memory");
}
__device__ __forceinline__ void tma_prefetch_w(const CUtensorMap* tm, int col, int kb) {
#pragma unroll
  for (int q = 0; q < 2; q++)
    asm volatile("cp.async.bulk.prefetch.tensor.5d.L2.global [%0, {%1, %2, %2, %2, %3}];" ::"l"(tm), "r"(col + q * 64), "r"(0), "r"(2 * kb) : "memory");
}
__device__ __forceinline__ void bulk_load(uint32_t dst, const void* g, uint32_t bytes, uint32_t bar) {
  asm volatile("cp.async.bulk.shared::cluster.global.mbarrier::complete_tx::bytes [%0], [%1], %2, [%3];" ::"r"(dst), "l"(g), "r"(bytes), "r"(bar) : "memory");
}
__device__ __forceinline__ void prefetch_map(const CUtensorMap* tm) { asm volatile("prefetch.tensormap [%0];" ::"l"(tm) : "memory"); }
__device__ __forceinline__ void fence_async_smem() { asm volatile("fence.proxy.async.shared::cta;" ::: "memory"); }
__device__ __forceinline__ void fence_async_global() { asm volatile("fence.proxy.async.global;" ::: "memory"); }
__device__ __forceinline__ void fence_gpu() { asm volatile("fence.release.gpu;" ::: "memory"); }
__device__ __forceinline__ void st_flag(unsigned* p, unsigned v) { asm volatile("st.relaxed.gpu.global.u32 [%0], %1;" ::"l"(p), "r"(v) : "memory"); }
__device__ __forceinline__ unsigned ld_flag(const unsigned* p) { unsigned v; asm volatile("ld.relaxed.gpu.global.u32 %0, [%1];" : "=r"(v) : "l"(p) : "memory"); return v; }
__device__ __forceinline__ uint4 ldcg4(const void* p) { uint4 v; asm volatile("ld.global.cg.v4.u32 {%0,%1,%2,%3}, [%4];" : "=r"(v.x), "=r"(v.y), "=r"(v.z), "=r"(v.w) : "l"(p)); return v; }
__device__ __forceinline__ uint4 ld_pkt(const uint4* p) {
  uint4 v; asm volatile("{\n.reg .b128 t;\nld.relaxed.gpu.global.b128 t, [%4];\nmov.b128 {%0,%1,%2,%3}, t;\n}" : "=r"(v.x), "=r"(v.y), "=r"(v.z), "=r"(v.w) : "l"(p) : "memory"); return v;
}
__device__ __forceinline__ void st_pkt(uint4* p, uint32_t a, uint32_t b, uint32_t c, uint32_t tag) {
  asm volatile("{\n.reg .b128 t;\nmov.b128 t, {%1,%2,%3,%4};\nst.relaxed.gpu.global.b128 [%0], t;\n}" ::"l"(p), "r"(a), "r"(b), "r"(c), "r"(tag) : "memory");
}
__device__ __forceinline__ void st_v4(uint4* p, uint32_t a, uint32_t b, uint32_t c, uint32_t d) { asm volatile("st.relaxed.gpu.global.v4.u32 [%0], {%1,%2,%3,%4};" ::"l"(p), "r"(a), "r"(b), "r"(c), "r"(d) : "memory"); }
__device__ __forceinline__ void stg128(uint4* p, uint4 v) { asm volatile("st.global.v4.u32 [%0], {%1,%2,%3,%4};" ::"l"(p), "r"(v.x), "r"(v.y), "r"(v.z), "r"(v.w) : "memory"); }
__device__ __forceinline__ void sts32(uint32_t addr, uint32_t a) { asm volatile("st.shared.u32 [%0], %1;" ::"r"(addr), "r"(a) : "memory"); }
__device__ __forceinline__ void sts64(uint32_t addr, uint32_t a, uint32_t b) { asm volatile("st.shared.v2.u32 [%0], {%1,%2};" ::"r"(addr), "r"(a), "r"(b) : "memory"); }
__device__ __forceinline__ uint32_t mul2(uint32_t a, uint32_t b) { uint32_t r; asm("mul.rn.bf16x2 %0, %1, %2;" : "=r"(r) : "r"(a), "r"(b)); return r; }
__device__ __forceinline__ uint32_t add2(uint32_t a, uint32_t b) { uint32_t r; asm("add.rn.bf16x2 %0, %1, %2;" : "=r"(r) : "r"(a), "r"(b)); return r; }
__device__ __forceinline__ bool elect() {
  uint32_t p; asm volatile("{\n.reg .pred q;\nelect.sync _|q, 0xffffffff;\nselp.u32 %0, 1, 0, q;\n}" : "=r"(p)); return p != 0;
}
__device__ __forceinline__ void wgmma_fence() { asm volatile("wgmma.fence.sync.aligned;" ::: "memory"); }
__device__ __forceinline__ void wgmma_commit() { asm volatile("wgmma.commit_group.sync.aligned;" ::: "memory"); }
template <int N> __device__ __forceinline__ void wgmma_wait() { asm volatile("wgmma.wait_group.sync.aligned %0;" ::"n"(N) : "memory"); }
template <int N> __device__ __forceinline__ void fence_regs(float (&d)[N]) {
#pragma unroll
  for (int i = 0; i < N; i++) asm volatile("" : "+f"(d[i])::"memory");
}
template <int R> __device__ __forceinline__ void reg_alloc() { asm volatile("setmaxnreg.inc.sync.aligned.u32 %0;" ::"n"(R)); }
template <int R> __device__ __forceinline__ void reg_dealloc() { asm volatile("setmaxnreg.dec.sync.aligned.u32 %0;" ::"n"(R)); }
__device__ __forceinline__ void wg_bar(int w) { asm volatile("bar.sync %0, 128;" ::"r"(w + 1) : "memory"); }
__device__ __forceinline__ constexpr uint32_t desc_lo(uint32_t addr, uint32_t lbo) { return (addr >> 4) + ((lbo >> 4) << 16); }
__device__ __forceinline__ uint32_t pack2(float lo, float hi) { uint32_t r; asm("cvt.rn.bf16x2.f32 %0, %1, %2;" : "=r"(r) : "f"(hi), "f"(lo)); return r; }
__device__ __forceinline__ float lo16(uint32_t v) { return __uint_as_float(v << 16); }
__device__ __forceinline__ float hi16(uint32_t v) { return __uint_as_float(v & 0xFFFF0000u); }
__device__ __forceinline__ float ex2(float x) { float r; asm("ex2.approx.ftz.f32 %0, %1;" : "=f"(r) : "f"(x)); return r; }
__device__ __forceinline__ float rcp(float x) { float r; asm("rcp.approx.ftz.f32 %0, %1;" : "=f"(r) : "f"(x)); return r; }
__device__ __forceinline__ uint32_t movm(uint32_t a) { uint32_t d; asm volatile("movmatrix.sync.aligned.m8n8.trans.b16 %0, %1;" : "=r"(d) : "r"(a)); return d; }
__device__ __forceinline__ void stsm4(uint32_t addr, uint32_t a, uint32_t b, uint32_t c, uint32_t d) {
  asm volatile("stmatrix.sync.aligned.m8n8.x4.shared.b16 [%0], {%1,%2,%3,%4};" ::"r"(addr), "r"(a), "r"(b), "r"(c), "r"(d) : "memory");
}
__device__ __forceinline__ void ldsm4(uint32_t addr, uint32_t (&r)[4]) {
  asm volatile("ldmatrix.sync.aligned.m8n8.x4.shared.b16 {%0,%1,%2,%3}, [%4];" : "=r"(r[0]), "=r"(r[1]), "=r"(r[2]), "=r"(r[3]) : "r"(addr) : "memory");
}
__device__ __forceinline__ void sts128(uint32_t addr, uint32_t a, uint32_t b, uint32_t c, uint32_t d) {
  asm volatile("st.shared.v4.u32 [%0], {%1,%2,%3,%4};" ::"r"(addr), "r"(a), "r"(b), "r"(c), "r"(d) : "memory");
}
__device__ __forceinline__ void lds128(uint32_t addr, uint32_t& a, uint32_t& b, uint32_t& c, uint32_t& d) {
  asm volatile("ld.shared.v4.u32 {%0,%1,%2,%3}, [%4];" : "=r"(a), "=r"(b), "=r"(c), "=r"(d) : "r"(addr) : "memory");
}
__device__ __forceinline__ float lds32f(uint32_t addr) { float v; asm volatile("ld.shared.f32 %0, [%1];" : "=f"(v) : "r"(addr) : "memory"); return v; }
__device__ __forceinline__ float2 lds64f(uint32_t addr) { float2 v; asm volatile("ld.shared.v2.f32 {%0,%1}, [%2];" : "=f"(v.x), "=f"(v.y) : "r"(addr) : "memory"); return v; }
__device__ __forceinline__ void mma16816(float (&d)[4], uint32_t a0, uint32_t a1, uint32_t a2, uint32_t a3, uint32_t b0, uint32_t b1) {
  asm("mma.sync.aligned.m16n8k16.row.col.f32.bf16.bf16.f32 {%0,%1,%2,%3}, {%4,%5,%6,%7}, {%8,%9}, {%0,%1,%2,%3};"
      : "+f"(d[0]), "+f"(d[1]), "+f"(d[2]), "+f"(d[3]) : "r"(a0), "r"(a1), "r"(a2), "r"(a3), "r"(b0), "r"(b1));
}
__device__ __forceinline__ void mma1688(float (&d)[4], uint32_t a0, uint32_t a1, uint32_t b0) {
  asm("mma.sync.aligned.m16n8k8.row.col.f32.bf16.bf16.f32 {%0,%1,%2,%3}, {%4,%5}, {%6}, {%0,%1,%2,%3};"
      : "+f"(d[0]), "+f"(d[1]), "+f"(d[2]), "+f"(d[3]) : "r"(a0), "r"(a1), "r"(b0));
}

__device__ __forceinline__ float qsum(float v) { v += __shfl_xor_sync(0xffffffffu, v, 1); v += __shfl_xor_sync(0xffffffffu, v, 2); return v; }

constexpr int NCTA = 132;
#define NB_ 6
#define NA_ 5
constexpr int NB = NB_;
constexpr int NA = NA_;
constexpr uint32_t SLOT = 16384;
constexpr uint32_t SB = 1024;
constexpr uint32_t OFF_B = 0;
constexpr uint32_t OFF_A = NB * SLOT;
constexpr uint32_t OFF_S = OFF_A + NA * SLOT;
constexpr uint32_t OFF_T = OFF_S + 20480;
constexpr uint32_t OFF_CS = OFF_T + 24576;
constexpr uint32_t OFF_MR = OFF_CS + 4640;
constexpr uint32_t OFF_BAR = OFF_MR + 512;
constexpr uint32_t OFF_MA = OFF_S, OFF_MB = OFF_CS - 2048;
constexpr uint32_t BAR_FULLB = OFF_BAR;
constexpr uint32_t BAR_FULLA = BAR_FULLB + 64;
constexpr uint32_t BAR_EMPTYB = BAR_FULLA + 64;
constexpr uint32_t BAR_EMPTYA = BAR_EMPTYB + 64;
constexpr uint32_t BAR_SIGP = BAR_EMPTYA + 64;
constexpr uint32_t BAR_SIGT = BAR_SIGP + 24;
constexpr uint32_t BAR_STAT = BAR_SIGP + 64;
constexpr uint32_t BAR_HALO = BAR_STAT + 16;
constexpr uint32_t BAR_CS = BAR_HALO + 8;
constexpr uint32_t BAR_WPHI = BAR_CS + 16;
constexpr uint32_t BAR_KV = BAR_WPHI + 8;
constexpr uint32_t BAR_STG = BAR_KV + 16;
constexpr uint32_t BAR_EPOCH = BAR_STG + 48;
constexpr uint32_t BAR_LAND = OFF_BAR + 7 * 64;
constexpr uint32_t OFF_EPOCH = OFF_BAR + 8 * 64;
static_assert(BAR_EPOCH < BAR_LAND, "barriers");
constexpr uint32_t SMEM_BYTES = OFF_EPOCH + 8;
static_assert(SMEM_BYTES <= 232448 && NB % 2 == 0 && NB <= 8 && NA <= 6, "smem");

#define CREGS 224
#define PREGS 56
#define PF1 19
#define PF2 21
#define PRE_A 2
#define PRE_B 4
#define CSB 4
#define CSNEED 0xF001u
#define XR 1
#define PS0 1
#define PS1 3
#define PSW 0
#define SD 1000
#define KSPLIT 12
#define KEEP 16
#define NJ 3
#define KSL 1000
#define PSL 0
#define KVS 12
#define D2 2000
#define D3 1500
#define G0 50
#define MAP 3
#define PMAP 0x76321450u
#define ZO 0
#define XA 3
#define XS 1
#define CP 500
#define CD 0
#define S0 500
#define NS 2
#define XO 0
#define SW 2
#define SA 1
#define SB_ 4
#define XD 250
#define ND0 1
#define KC 8
#define CO 0
#define SE 500
#define PD 0
#define AS 1
#define IPF 1
#define IP0 65536
#define IP1 123904
#define DEFER 3
#define DEFL 2
#define TSK 3
#define TSL 3
constexpr int NTHREADS = 384;

struct Params {
  CUtensorMap mx;
  CUtensorMap mw[3];
  CUtensorMap mwo[2];
  CUtensorMap mcs[2];
  CUtensorMap mwphi;
  uint4* out;
};

#define XBUF(L) 1
__device__ __align__(256) uint4 g_img[XBUF(3) + 1][16][16][1024];
__device__ __forceinline__ uint32_t img_code(bool isx, int L) { return isx ? (L & 1) | (L & 2) << 15 : ~L & 1; }
__device__ __forceinline__ uint32_t img_mask(bool isx) { return isx ? 0x10001u : 1u; }
__device__ __align__(256) uint4 g_wf[2][8][16][1024];
__device__ __align__(256) uint4 g_stats[16][2][8][32];
__device__ __align__(256) uint4 g_halo[16][8][2][256];
__device__ __align__(256) float g_cs[2][2][3072];
__device__ __align__(256) uint4 g_kvpart[8][16][2][544];
__device__ __align__(256) uint4 g_kvfin[8][16][80];
__device__ __align__(256) unsigned g_hint[16][32];
__device__ __align__(256) unsigned g_jflag[3][8][32];
__device__ unsigned g_ctr;
__device__ __forceinline__ unsigned vblock() {
  unsigned s;
  asm volatile("mov.u32 %0, %%smid;" : "=r"(s));
  const unsigned r = s & 1;
  s >>= 1;
  const unsigned t = s - 32, q = (t * 37) >> 8;
  const unsigned hi = s < 60 ? 12 + (t - 7 * q) * 8 + q : (s < 62 ? s + 4 : s - 58);
  unsigned b = 2 * (s < 32 ? (s & 7) * 8 + (s >> 3) : hi) + r;
  if (b < 128) b = (b & 15) | ((PMAP >> ((b >> 4) * 4)) & 7) << 4;
  if (s >= 62) b = 8 + 4 * r + s - 62;
  unsigned n;
  asm volatile("mov.u32 %0, %%nsmid;" : "=r"(n));
  return __shfl_sync(0xffffffffu, n == NCTA ? b : blockIdx.x, 0);
}
#define TS(who, id) do {} while (0)
#define TSW(id) do {} while (0)

#define TSH(id) do {} while (0)
#define TSMASK 0xFFFF
#define TSL_(a) do { if ((TSMASK >> (a)) & 1) TSW((a) + L * 12); } while (0)
__device__ __forceinline__ int cta_m(unsigned b) { return ((b >> 2) & 12) | (b & 3); }
__device__ __forceinline__ int cta_j(unsigned b) { return ((b >> 2) & 3) | ((b >> 4) & 4); }
struct Ring { uint32_t s, ph; };
template <int N> __device__ __forceinline__ void adv(Ring& r) { if (++r.s == N) { r.s = 0; r.ph ^= 1; } }
template <int N> __device__ __forceinline__ void rewind2(Ring& r) { if (r.s < 2) { r.s += N - 2; r.ph ^= 1; } else r.s -= 2; }
__device__ __forceinline__ int other_tile(int t, int j) { return (t == (j | 4) ? 7 : t) ^ (~j & 4); }
__device__ __forceinline__ int o_order(int i, int j) {
  if (i < 2) return 2 * j + i;
  const int odd = i >= 9;
  return 2 * other_tile(i - 2 - 7 * odd, j) + odd;
}
__device__ __forceinline__ int kv_order(int i, int j, int L) { return L > 0 ? o_order(i, j) : (i + 14 + 2 * (j & 4)) & 15; }

__device__ __forceinline__ unsigned poll_flags(const unsigned* f, int n, unsigned need, unsigned tag) {
  const int lane = threadIdx.x & 31;
  unsigned mask; int it = 0;
  do {
    unsigned v = lane < n ? ld_flag(f + lane) : 0u;
    mask = __ballot_sync(0xffffffffu, lane < n && (int)(v - tag) >= 0);
    if (++it > (1 << 22)) __trap();
  } while ((mask & need) != need);
  fence_async_global();
  return mask;
}
template <bool WAIT = true>
__device__ __forceinline__ unsigned get_tag(uint32_t sb) {
  if (WAIT) mbar_wait(sb + BAR_EPOCH, 0);
  unsigned t; asm volatile("ld.shared.u32 %0, [%1];" : "=r"(t) : "r"(sb + OFF_EPOCH) : "memory");
  return t;
}

__device__ __forceinline__ int lane_id() { int l; asm volatile("mov.u32 %0, %%laneid;" : "=r"(l)); return l; }
__device__ __forceinline__ unsigned seq4(unsigned tag, int L) { return 8u | ((tag & 1u) << 2) | (unsigned)L; }
constexpr float LOG2E = 1.4426950408889634f;

__device__ __forceinline__ float bb_fence(int never, const void* p = &g_ctr, uint32_t keep = 0) {
  while (never < 0) never = ld_flag((const unsigned*)p) + keep;
  return __int_as_float(never >> 30);
}
__device__ __forceinline__ uint32_t solid(uint32_t v) { return __shfl_sync(0xffffffffu, v, threadIdx.x & 31); }
template <class T> __device__ __forceinline__ T* solid(T* p) { return (T*)__shfl_sync(0xffffffffu, (unsigned long long)p, threadIdx.x & 31); }
constexpr uint32_t HA128 = 0x40000040u, HA64 = 0x80000040u;
struct Ctx {
  static constexpr uint32_t sb = SB;
  uint32_t ab, da0;
  int w, warp, lane, g, c;
  int goff;
  __device__ __forceinline__ int m() const { return goff >> 14; }
  __device__ __forceinline__ int j() const { return (goff >> 4) & 7; }
  bool elected;
  Ring ra, rb;
  uint32_t pa, pb;
  uint32_t ha, k2;
  uint32_t mrow, mxor, mhi;
  __device__ __forceinline__ uint32_t aslot(uint32_t s) const { return ab + s * SLOT; }
  __device__ __forceinline__ uint32_t fullA(uint32_t s) const { return sb + BAR_FULLA + s * 8; }
  __device__ __forceinline__ uint32_t fullB(uint32_t s) const { return sb + BAR_FULLB + s * 8; }
  __device__ __forceinline__ void releaseA(uint32_t s) const { if (elected) mbar_arrive(sb + BAR_EMPTYA + s * 8); }
  __device__ __forceinline__ void releaseB(uint32_t s) const { if (elected) mbar_arrive(sb + BAR_EMPTYB + s * 8); }
  __device__ __forceinline__ uint32_t maddr(uint32_t tile, uint32_t ch) const { return tile + mrow + (((ch + mhi) ^ mxor) << 4); }
  __device__ __forceinline__ uint32_t oo() const { return warp * 128 + g * 4 + (c ^ (g >> 1)); }
  __device__ __forceinline__ uint4* img(int b, int hp) const { return ip + (b * 256 + hp) * 1024; }
  uint4* ip;
  uint32_t so;
  __device__ __forceinline__ uint32_t held(int i) const { return ra.s + i < 2 ? ra.s + i + NA - 2 : ra.s + i - 2; }
};

template <int N, bool FIRST, bool O = true>
__device__ __forceinline__ void gemm_issue(float (&acc)[N / 2], Ctx& x, bool ready = false) {
  if (!ready) {
    if (N == 256) mbar_wait3(x.fullA(x.ra.s), x.ra.ph, x.fullB(x.rb.s), x.rb.ph);
    else mbar_wait2(x.fullA(x.ra.s), x.ra.ph, x.fullB(x.rb.s), x.rb.ph);
  }
  const uint32_t da = x.da0 + x.ra.s * (SLOT / 16), db = desc_lo(SB + OFF_B, 8192) + x.rb.s * (SLOT / 16);
  wgmma_fence();
#pragma unroll
  for (int k = 0; k < 4; k++) {
    const uint32_t a = da + (k >> 1) * (O ? 32 : x.k2) + (k & 1) * 2, ha = O ? HA64 : x.ha;
    if constexpr (N == 256) wgmma_ss_n256(acc, a, ha, db + 128 * k, !(FIRST && k == 0));
    else wgmma_ss_n128(acc, a, ha, db + 128 * k, !(FIRST && k == 0));
  }
  wgmma_commit();
}
template <int N>
__device__ __forceinline__ void gemm_next(Ctx& x) {
  x.pa = x.ra.s; x.pb = x.rb.s;
  if (N == 256) x.rb.s++;
  adv<NA>(x.ra); adv<NB>(x.rb);
}
template <int N>
__device__ __forceinline__ void gemm_release(Ctx& x, bool relA) {
  if (relA) x.releaseA(x.pa);
  x.releaseB(x.pb);
  if (N == 256) x.releaseB(x.pb + 1);
}
template <int N>
__device__ __forceinline__ void gemm_retire(Ctx& x, bool relA) { wgmma_wait<1>(); gemm_release<N>(x, relA); gemm_next<N>(x); }
template <bool O = true>
__device__ __forceinline__ void gemm_run(float (&acc)[64], Ctx& x, int n, int hold, int n4 = 0) {
  bool ready = false;
#pragma unroll 1
  for (; n > 0; n--) {
    gemm_issue<128, false, O>(acc, x, ready);
    const uint32_t pa = x.pa, pb = x.pb;
    gemm_next<128>(x);
    ready = mbar_probe2(x.fullA(x.ra.s), x.ra.ph, x.fullB(x.rb.s), x.rb.ph);
    wgmma_wait<1>();
    if (n > hold) x.releaseA(pa);
    x.releaseB(pb);
  }
}
__device__ __forceinline__ void gemm_end(float (&acc)[64], Ctx& x) { wgmma_wait<0>(); fence_regs(acc); gemm_release<128>(x, false); }

__device__ __forceinline__ void rows_load(uint4* r, uint32_t tile, const Ctx& x) {
#pragma unroll
  for (int q = 0; q < 4; q++) {
    const uint32_t row = x.warp * 16 + 4 * q + (x.lane >> 3);
    lds128(tile + row * 128 + (((x.lane & 7) ^ (row & 7)) << 4), r[q].x, r[q].y, r[q].z, r[q].w);
  }
}
__device__ __forceinline__ void rows_store(const uint4* r, uint4* g) {
#pragma unroll
  for (int q = 0; q < 4; q++) stg128(g + q * 1024, r[q]);
}
__device__ __forceinline__ void publish(int id, const Ctx& x) { __syncwarp(); if (x.lane == 0) mbar_arrive(x.sb + BAR_SIGP + id * 8); }
__device__ __forceinline__ uint32_t img_tag(uint32_t v, bool isx, int L, const Ctx& x) {
  const uint32_t mk = ((x.lane ^ (x.warp * 4)) & 7) ? 0u : img_mask(isx);
  return (v & ~mk) | (img_code(isx, L) & mk);
}
__device__ __forceinline__ void img_tag(uint4 (&r)[4], bool isx, int L, const Ctx& x) {
#pragma unroll
  for (int q = 0; q < 4; q++) { uint32_t& v = q == 0 ? r[q].x : (q == 1 ? r[q].y : (q == 2 ? r[q].z : r[q].w)); v = img_tag(v, isx, L, x); }
}
__device__ __forceinline__ void img_store(const uint4 (&r)[4], uint4* g) {
#pragma unroll
  for (int q = 0; q < 4; q++) stg128(g + q * 32, r[q]);
}
__device__ __forceinline__ void img_sts(const uint4 (&r)[4], uint32_t tile, const Ctx& x) {
#pragma unroll
  for (int q = 0; q < 4; q++) sts128(tile + x.so + q * 512, r[q].x, r[q].y, r[q].z, r[q].w);
}
__device__ __forceinline__ void img_load(uint32_t (&v)[16], uint32_t tile, const Ctx& x) {
#pragma unroll
  for (int q = 0; q < 4; q++) lds128(tile + x.so + q * 512, v[4 * q], v[4 * q + 1], v[4 * q + 2], v[4 * q + 3]);
}
__device__ __forceinline__ void img_unpack(float* a, const uint32_t (&v)[16]) {
#pragma unroll
  for (int q = 0; q < 16; q++) { a[4 * (q & 7) + 2 * (q >> 3)] = lo16(v[q]); a[4 * (q & 7) + 2 * (q >> 3) + 1] = hi16(v[q]); }
}

template <int N>
__device__ __forceinline__ void stats_acc(const float* a, float (&t)[4]) {
#pragma unroll
  for (int i = 0; i < N; i++) { t[i & 2] += a[i]; t[(i & 2) + 1] = fmaf(a[i], a[i], t[(i & 2) + 1]); }
}
__device__ __forceinline__ void stats_send(float (&t)[4], int L, const Ctx& x) {
  const unsigned seq = seq4(get_tag<false>(x.sb), L);
#pragma unroll
  for (int q = 0; q < 4; q++) t[q] = qsum(t[q]);
  if (x.c == 0) st_pkt(&g_stats[x.m()][x.w][x.j()][x.warp * 8 + x.g], __float_as_uint(t[0]), __float_as_uint(t[1]), __float_as_uint(t[2]), (__float_as_uint(t[3]) & ~15u) | seq);
}
__device__ __forceinline__ void out_epilogue(const float (&acc)[64], uint4 (&r1)[4], float (&t)[4], uint4* g, int L, Ctx& x) {
  const uint32_t t0 = x.aslot(x.ra.s), t1 = x.aslot(x.ra.s + 1 == NA ? 0 : x.ra.s + 1);
  if (L == 3) {
#pragma unroll
    for (int p = 0; p < 8; p++) {
      stsm4(x.maddr(p < 4 ? t0 : t1, (p & 3) * 2), pack2(acc[8 * p], acc[8 * p + 1]), pack2(acc[8 * p + 2], acc[8 * p + 3]),
            pack2(acc[8 * p + 4], acc[8 * p + 5]), pack2(acc[8 * p + 6], acc[8 * p + 7]));
      if ((p & 3) == 3) { uint4 r[4]; __syncwarp(); rows_load(r, p < 4 ? t0 : t1, x); rows_store(r, g + (p >> 2) * 8); }
    }
  } else {
    auto pack16 = [&](uint4 (&r)[4], const float* a) {
#pragma unroll
      for (int q = 0; q < 4; q++) { const float* u = a + 16 * (q & 1) + (q & 2); r[q] = make_uint4(pack2(u[0], u[1]), pack2(u[4], u[5]), pack2(u[8], u[9]), pack2(u[12], u[13])); }
    };
    uint4 r0[4];
    pack16(r0, acc);
    img_tag(r0, true, L + 1, x);
    img_store(r0, x.img(XBUF(L + 1), 0));
    publish(1, x);
    const float z = bb_fence(x.goff);
    img_sts(r0, t0, x);
    pack16(r1, acc + 32);
    img_tag(r1, true, L + 1, x);
    img_sts(r1, t1, x);
    float u[4] = {z, z, z, z}, v[4] = {z, z, z, z};
    stats_acc<32>(acc, v);
    stats_acc<32>(acc + 32, u);
#pragma unroll
    for (int q = 0; q < 4; q++) t[q] = u[q] + v[q];
    mbar_wait2(x.fullB(x.rb.s), x.rb.ph, x.fullB(x.rb.s + 1), x.rb.ph);
    fence_async_smem();
    asm volatile("bar.sync %0, %1;" ::"r"(L == 1 ? x.w + 1 : 3), "r"(L == 1 ? 128 : 256) : "memory");
  }
}

struct Stats { float rstd0, rstd1; };
__device__ __forceinline__ Stats load_stats(int half, const Ctx& x) {
  const float2 u = lds64f(x.sb + OFF_MR + half * 256 + (x.warp * 8 + x.g) * 8);
  return {u.x, u.y};
}

template <int NH, int NK, class F>
__device__ __forceinline__ void hedgehog_scale(float* t, const Stats& st, const uint32_t* keep, F use) {
#pragma unroll
  for (int q = 0; q < 16 * NH; q++) t[q] *= ((q & 2) ? st.rstd1 : st.rstd0) * LOG2E;
  use();
  float m[4];
#pragma unroll
  for (int q = 0; q < 4 * NH; q++) {
    const float v = fmaxf(fmaxf(fabsf(t[4 * q]), fabsf(t[4 * q + 1])), fmaxf(fabsf(t[4 * q + 2]), fabsf(t[4 * q + 3])));
    m[q & 3] = q < 4 ? v : fmaxf(m[q & 3], v);
  }
  if (__builtin_expect(__any_sync(0xffffffffu, fmaxf(fmaxf(m[0], m[1]), fmaxf(m[2], m[3])) > 58.f), 0)) {
    float z[16 * NH + NK];
#pragma unroll
    for (int q = 0; q < 16 * NH + NK; q++) z[q] = q < 16 * NH ? t[q % (16 * NH)] : __uint_as_float(keep[q & 15]);
#pragma unroll 1
    for (int r = 0; r < 2 * NH; r++) {
      float hi = -INFINITY, lo = INFINITY;
#pragma unroll 1
      for (int i = 0; i < 16; i++) {
        const int k = (i & 6) * 2 + (i & 1) + (r & 1) * 2 + (r & 2) * 8;
        const float v = z[k];
        if (i < 8) { hi = fmaxf(hi, v); lo = fminf(lo, v); }
        else z[k] = v - fminf(fmaxf(v, lo), hi);
        if (i == 7) {
#pragma unroll 1
          for (int d = 1; d <= 2; d++) { hi = fmaxf(hi, __shfl_xor_sync(0xffffffffu, hi, d)); lo = fminf(lo, __shfl_xor_sync(0xffffffffu, lo, d)); }
          const float mid = 0.5f * hi + 0.5f * lo;
          hi = fmaxf(hi - 58.f, mid); lo = fminf(lo + 58.f, mid);
        }
      }
    }
#pragma unroll
    for (int q = 0; q < 16 * NH; q++) t[q] = z[q];
    use();
  }
}
__device__ __forceinline__ void dual_exp(const float* t, uint32_t (&f)[18], int never) {
  float e[KSPLIT];
#pragma unroll
  for (int q = 0; q < KSPLIT; q++) e[q] = ex2(q < 16 ? t[q] : -t[q & 15]);
  while (never < 0) {
#pragma unroll
    for (int i = 0; i < KSPLIT; i += 4) asm volatile("ld.shared.v4.f32 {%0,%1,%2,%3}, [%4];" : "=f"(e[i]), "=f"(e[i + 1]), "=f"(e[i + 2]), "=f"(e[i + 3]) : "r"(never + i) : "memory");
    never += __float_as_int(e[0]);
  }
#pragma unroll
  for (int q = 0; q < KSPLIT; q += 2) f[q >> 1] = pack2(e[q], e[q + 1]);
#pragma unroll
  for (int q = KSPLIT; q < 32; q += 2) f[q >> 1] = q < 16 ? pack2(ex2(t[q]), ex2(t[q + 1])) : pack2(ex2(-t[q & 15]), ex2(-t[(q & 15) + 1]));
#pragma unroll
  for (int sg = 0; sg < 2; sg++) {
    const uint32_t* u = f + 8 * sg;
    const uint32_t a = add2(add2(u[0], u[2]), add2(u[4], u[6])), b = add2(add2(u[1], u[3]), add2(u[5], u[7]));
    f[16 + sg] = add2(__byte_perm(a, b, 0x5410), __byte_perm(a, b, 0x7632));
  }
}
__device__ __forceinline__ void dual_exp_rcp(const float* t, uint32_t* f) {
#pragma unroll
  for (int q = 0; q < 8; q++) {
    const float a = ex2(t[2 * q]), b = ex2(t[2 * q + 1]), r = rcp(a * b);
    f[q] = pack2(a, b); f[8 + q] = pack2(r * b, r * a);
  }
}
__device__ __forceinline__ void cta_bar() { asm volatile("bar.sync 3, 256;" ::: "memory"); }

template <int N> __device__ __forceinline__ void pin(const uint32_t* v, uint32_t addr) {
#pragma unroll
  for (int i = 0; i < N; i += 4)
    asm volatile("{\n.reg .pred p;\nsetp.eq.u32 p, %0, 0;\n@p st.shared.v4.u32 [%0], {%1,%2,%3,%4};\n}" ::"r"(addr), "r"(v[i]), "r"(v[i + 1]), "r"(v[i + 2]), "r"(v[i + 3]) : "memory");
}

__device__ __forceinline__ void consumer(const Params& P, uint32_t sb, int w, unsigned vb) {
  Ctx x;
  x.w = w;
  x.ab = sb + OFF_A + w * 8192; x.da0 = desc_lo(SB + OFF_A, 16) + w * 512;
  x.lane = threadIdx.x & 31; x.warp = __shfl_sync(0xffffffffu, (threadIdx.x >> 5) & 3, 0); x.g = x.lane >> 2; x.c = x.lane & 3;
  x.goff = (cta_m(vb) * 128 + w) * 128 + cta_j(vb) * 16;
  asm volatile("" : "+r"(x.goff));
  x.elected = (threadIdx.x & 127) == 0;
  x.ra = {0, 0}; x.rb = {0, 0}; x.pa = x.pb = 0;
  {
    const uint32_t row = x.warp * 16 + (x.lane & 15);
    x.mrow = row * 128; x.mxor = row & 7; x.mhi = x.lane >> 4;
  }
  const int goff = x.goff;
  x.ip = solid(&g_img[0][x.m()][2 * x.j()][w * 512 + x.oo()]);
  x.so = solid(16 * x.oo());
  uint4 r1[4];
  float ts[4] = {0.f, 0.f, 0.f, 0.f};
#pragma unroll
  for (int i = 0; i < 4; i++) r1[i] = make_uint4(0, 0, 0, 0);
  TSW(0);
  mbar_wait3(x.fullA(0), 0, x.fullB(0), 0);
#pragma unroll 1
  for (int L = 0; L < 4; L++) {
    float acc[64];
    constexpr uint32_t dcs = desc_lo(SB + OFF_CS, 0);
    if ((L & 1) == 0) {
    float kv[128];
    x.ha = L ? HA64 : HA128; x.k2 = L ? 32 : 4;
    gemm_issue<256, true, false>(kv, x, true); gemm_next<256>(x);
    {
      int i = 1;
#pragma unroll 1
      for (int seg = L ? NS - 1 : 0; seg <= NS; seg++) {
        const int end = seg < NS ? (L == 0 ? 3 + SA * ((x.j() + SW * w) & 3) + SB_ * seg : XA + 1) : 14 + L;
#pragma unroll 1
        do {
          gemm_issue<256, false, false>(kv, x);
          gemm_retire<256>(x, true);
          i++;
          if (i == 5) TSL_(8);
          if (i == 11) TSL_(10);
        } while (i != end);
        if (seg < NS && L == 0) {
          uint32_t v[16];
          float a[32];
#pragma unroll
          for (int q = 0; q < 4; q++) ldsm4(x.maddr(x.aslot(x.pa), 2 * q), reinterpret_cast<uint32_t (&)[4]>(v[4 * q]));
#pragma unroll
          for (int q = 0; q < 16; q++) { a[2 * q] = lo16(v[q]); a[2 * q + 1] = hi16(v[q]); }
          stats_acc<32>(a, ts);
          fence_regs(ts);
          wg_bar(w);
        }
        if (seg == NS - 1) {
          if (L > 0) { img_store(r1, x.img(XBUF(L), 1)); publish(2, x); }
          mbar_wait(sb + BAR_EPOCH, 0);
          stats_send(ts, L, x);
        }
      }
    }
      const Ring kt = x.ra;
      if (L == 0) adv<NA>(x.ra);
#pragma unroll 1
      for (int h = L; h < 2; h++) {
        float d[16];
        mbar_wait2(x.fullA(kt.s), kt.ph, sb + BAR_WPHI, 0);
        wgmma_fence();
#pragma unroll
        for (int q = 0; q < 2; q++) wgmma_ss_n32(d, x.da0 + kt.s * (SLOT / 16) + h * 4 + q * 2, desc_lo(SB + OFF_S + 4096, 512) + w * 256 + h * 128 + q * 64, q);
        wgmma_commit();
        gemm_issue<256, false, false>(kv, x);
        gemm_retire<256>(x, true);
        if (h) x.releaseA(kt.s);
        fence_regs(d);
        uint4* dst = &g_wf[1][x.j()][x.m()][w * 512 + (x.warp * 16 + x.g) * 8 + ((h * 4 + x.c) ^ x.g)];
        dst[0] = make_uint4(pack2(d[0], d[1]), pack2(d[4], d[5]), pack2(d[8], d[9]), pack2(d[12], d[13]));
        dst[64] = make_uint4(pack2(d[2], d[3]), pack2(d[6], d[7]), pack2(d[10], d[11]), pack2(d[14], d[15]));
      }
      const uint32_t dm = desc_lo(SB + OFF_MA, 0) + w * 64;
      mbar_wait2(sb + BAR_STAT, 0, sb + BAR_CS, 0);
      wgmma_fence();
      wgmma_r1_n256(kv, dm, dcs + 96, 1);
      wgmma_commit();
      const Stats st = load_stats(w, x);
      mbar_wait2(x.fullA(x.ra.s), x.ra.ph, x.fullB(x.rb.s), x.rb.ph);
      wgmma_wait<0>();
      fence_regs(kv);
      gemm_release<256>(x, true);
      TSL_(2);
      uint32_t P0[32], P1[32], PH[32];
#pragma unroll
      for (int t = 0; t < 16; t++) { P0[t] = pack2(kv[4 * t] * st.rstd0, kv[4 * t + 1] * st.rstd0); P1[t] = pack2(kv[4 * t + 2] * st.rstd1, kv[4 * t + 3] * st.rstd1); }
      pin<16>(P0, x.mrow + 16);
      {
#pragma unroll
        for (int q = 0; q < 4; q++) sts128((x.warp < 3 ? sb + OFF_T + w * 12288 + x.warp * 4096 : sb + OFF_S + 16384 + w * 2048) + x.lane * 16 + q * 512, P1[4 * q], P1[4 * q + 1], P1[4 * q + 2], P1[4 * q + 3]);
      }
      wgmma_fence();
      wgmma_r1_n128(acc, dm, dcs, 0);
      gemm_issue<128, false, false>(acc, x, true); gemm_next<128>(x);
      TSL_(3);
#pragma unroll
      for (int s = 0; s < 4; s++) {
#pragma unroll
        for (int t = 16 + 8 * (s & 1); t < 24 + 8 * (s & 1); t++) {
          if (s < 2) P1[t] = movm(pack2(kv[4 * t + 2] * st.rstd1, kv[4 * t + 3] * st.rstd1));
          else P0[t] = movm(pack2(kv[4 * t] * st.rstd0, kv[4 * t + 1] * st.rstd0));
        }
        if (s < 3) { gemm_issue<128, false, false>(acc, x); gemm_retire<128>(x, true); }
        if (s == 1) {
          if (x.warp < 3) {
#pragma unroll
            for (int q = 4; q < 8; q++) sts128(sb + OFF_T + w * 12288 + x.warp * 4096 + x.lane * 16 + q * 512, P1[4 * q], P1[4 * q + 1], P1[4 * q + 2], P1[4 * q + 3]);
          } else {
            uint4* dst = &g_halo[x.m()][x.j()][w][x.lane];
#pragma unroll
            for (int q = 0; q < 8; q++) dst[q * 32] = make_uint4(P1[4 * q], P1[4 * q + 1], P1[4 * q + 2], P1[4 * q + 3]);
          }
          publish(3, x);
          gemm_issue<128, false, false>(acc, x);
          gemm_retire<128>(x, true);
        }
      }
      TSL_(4);
      gemm_run<false>(acc, x, 10, 0);
      gemm_issue<128, false, false>(acc, x);
      {
        wg_bar(w);
        uint32_t tr = sb + OFF_T + w * 12288 + (x.warp - 1) * 4096;
        if (x.warp == 0) {
          tr = x.m() > 0 ? sb + OFF_S + 8192 + w * 4096 : tr + 4096;
          if (x.m() > 0) mbar_wait(sb + BAR_HALO, L >> 1);
        }
#pragma unroll
        for (int q = 0; q < 8; q++) lds128(tr + x.lane * 16 + q * 512, PH[4 * q], PH[4 * q + 1], PH[4 * q + 2], PH[4 * q + 3]);
      }
      gemm_retire<128>(x, false);
      gemm_end(acc, x);
      TSL_(5);
      const bool first = (x.m() == 0) && (x.warp == 0);
      const bool hi0 = 2 * x.c > x.g, hi1 = 2 * x.c + 1 > x.g;
      const uint32_t mhi = (hi0 ? 0xFFFFu : 0u) | (hi1 ? 0xFFFF0000u : 0u);
      const uint32_t valid = first ? ~mhi : ~0u;
      const float sc0 = st.rstd0 * (0.17677669529663687f * LOG2E), sc1 = st.rstd1 * (0.17677669529663687f * LOG2E);
#pragma unroll
      for (int hp = 0; hp < 2; hp++) {
        const uint32_t tile = x.aslot(x.held(hp));
        uint32_t px[2], py[2];
        float s[2][3][4];
#pragma unroll
        for (int u = 0; u < 2; u++) {
#pragma unroll
          for (int q = 0; q < 12; q++) s[u][q >> 2][q & 3] = 0.f;
#pragma unroll
          for (int ks = 0; ks < 2; ks++) {
            const int t = 8 * hp + 4 * u + 2 * ks;
            const uint32_t a0 = pack2(acc[4 * t], acc[4 * t + 1]), a1 = pack2(acc[4 * t + 2], acc[4 * t + 3]);
            const uint32_t a2 = pack2(acc[4 * t + 4], acc[4 * t + 5]), a3 = pack2(acc[4 * t + 6], acc[4 * t + 7]);
            mma16816(s[u][0], a0, a1, a2, a3, PH[t], PH[t + 1]);
            mma16816(s[u][1], a0, a1, a2, a3, P0[t], P0[t + 1]);
            mma16816(s[u][2], a0, a1, a2, a3, P1[t], P1[t + 1]);
          }
        }
        float e[2][4], big = 0.f;
#pragma unroll
        for (int u = 0; u < 2; u++) {
          e[u][0] = (hi0 ? s[u][0][0] : s[u][1][0]) * sc0; e[u][1] = (hi1 ? s[u][0][1] : s[u][1][1]) * sc0;
          e[u][2] = (hi0 ? s[u][1][2] : s[u][2][2]) * sc1; e[u][3] = (hi1 ? s[u][1][3] : s[u][2][3]) * sc1;
          big = fmaxf(big, fmaxf(fmaxf(fabsf(e[u][0]), fabsf(e[u][1])), fmaxf(fabsf(e[u][2]), fabsf(e[u][3]))));
          px[u] = pack2(ex2(e[u][0]), ex2(e[u][1])) & valid; py[u] = pack2(ex2(e[u][2]), ex2(e[u][3]));
        }
        if (__builtin_expect(__any_sync(0xffffffffu, big > 58.f), 0)) {
#pragma unroll
          for (int q = 0; q < 4; q++) {
            float v0 = e[q >> 1][2 * (q & 1)], v1 = e[q >> 1][2 * (q & 1) + 1];
            if (first && !(q & 1)) { if (hi0) v0 = -INFINITY; if (hi1) v1 = -INFINITY; }
            float r = fmaxf(v0, v1);
            r = fmaxf(r, __shfl_xor_sync(0xffffffffu, r, 1)); r = fmaxf(r, __shfl_xor_sync(0xffffffffu, r, 2));
            ((q & 1) ? py : px)[q >> 1] = pack2(ex2(v0 - r), ex2(v1 - r));
          }
        }
        float r[2][2];
#pragma unroll
        for (int u = 0; u < 2; u++) {
          float d[4] = {0.f, 0.f, 0.f, 0.f};
          mma1688(d, px[u], py[u], 0x3F803F80u);
          r[u][0] = rcp(d[0]); r[u][1] = rcp(d[2]);
        }
        uint32_t o[8][2];
        uint4 ro[4];
#pragma unroll
        for (int q = 0; q < 8; q++) {
          float d[4] = {0.f, 0.f, 0.f, 0.f};
          const int t = 16 + 8 * hp + q, u = q >> 2;
          if (AS == 2) { mma1688(d, px[u] & ~mhi, py[u] & mhi, P0[t]); mma1688(d, px[u] & mhi, 0u, PH[t]); mma1688(d, 0u, py[u] & ~mhi, P1[t]); }
          else if (AS == 3) { mma16816(d, px[u] & ~mhi, py[u] & mhi, 0u, py[u] & ~mhi, P0[t], P1[t]); mma1688(d, px[u] & mhi, 0u, PH[t]); }
          else { mma16816(d, px[u] & mhi, 0u, px[u] & ~mhi, py[u] & mhi, PH[t], P0[t]); mma1688(d, 0u, py[u] & ~mhi, P1[t]); }
          o[q][0] = pack2(d[0] * r[u][0], d[1] * r[u][0]); o[q][1] = pack2(d[2] * r[u][1], d[3] * r[u][1]);
        }
#pragma unroll
        for (int q = 0; q < 4; q++) ro[q] = make_uint4(o[4 * (q & 1)][q >> 1], o[4 * (q & 1) + 1][q >> 1], o[4 * (q & 1) + 2][q >> 1], o[4 * (q & 1) + 3][q >> 1]);
        img_tag(ro, false, 0, x);
        img_store(ro, x.img(0, hp));
        if (hp == 0) publish(0, x);
        uint32_t xs[16];
        if (L) img_load(xs, tile, x);
        else {
#pragma unroll
          for (int q = 0; q < 4; q++) {
            uint32_t v[4];
            ldsm4(x.maddr(tile, 2 * q), v);
            xs[2 * q] = v[0]; xs[8 + 2 * q] = v[1]; xs[2 * q + 1] = v[2]; xs[9 + 2 * q] = v[3];
          }
          __syncwarp();
        }
        img_sts(ro, tile, x);
        img_unpack(acc + 32 * hp, xs);
      }
    } else {
      float kv[128];
      float (&kv0)[64] = reinterpret_cast<float (&)[64]>(kv[0]);
      float (&kv1)[64] = reinterpret_cast<float (&)[64]>(kv[64]);
      auto mma8 = [&](uint32_t as, uint32_t bs, int i, bool fence) {
        const uint32_t da = desc_lo(SB + OFF_A, 16) + as * (SLOT / 16), db = desc_lo(SB + OFF_B, 8192) + bs * (SLOT / 16);
        if (fence) wgmma_fence();
#pragma unroll
        for (int k = 0; k < 4; k++) {
          wgmma_ss_n128(kv0, da + (k >> 1) * 32 + (k & 1) * 2, HA64, db + 128 * k, i + k);
          wgmma_ss_n128(kv1, da + 512 + (k >> 1) * 32 + (k & 1) * 2, HA64, db + 128 * k, i + k);
        }
        wgmma_commit();
      };
      constexpr uint32_t dm = desc_lo(SB + OFF_MB, 0);
      auto relB = [&](uint32_t s) { mbar_arrive_n(sb + BAR_EMPTYB + s * 8, 2); };
      auto skip = [&]() {
#pragma unroll
        for (int q = 0; q < 6 - NJ; q++) adv<NA>(x.ra);
        x.rb.s = w ? (2 + NJ) % 6 : 4;
        if (!w && NJ < 4) x.rb.ph ^= 1;
      };
      static_assert(NA == 5 && NB == 6, "ring arithmetic");
      mma8(x.ra.s, x.rb.s + w, 0, true);
      gemm_next<256>(x);
#pragma unroll 1
      for (int i = 1; i < NJ; i++) {
        mbar_wait2(x.fullA(x.ra.s), x.ra.ph, x.fullB(x.rb.s + w), x.rb.ph);
        mma8(x.ra.s, x.rb.s + w, 1, true);
        if (!XO && i == XR) { img_store(r1, x.img(XBUF(L), 1)); publish(2, x); }
        if (!XO && i == XS) stats_send(ts, L, x);
        wgmma_wait<1>();
        if (x.elected) { x.releaseA(x.pa); relB(x.pb + w); }
        gemm_next<256>(x);
        if (XO && i == XR) { img_store(r1, x.img(XBUF(L), 1)); publish(2, x); stats_send(ts, L, x); }
      }
      if (w) {
        wgmma_wait<0>();
        if (x.elected) { x.releaseA(x.pa); relB(x.pb + 1); }
        skip();
        asm volatile("bar.sync 7, 256;" ::: "memory");
      }
      TSL_(8);
      {
        const int t = lane_id() + 32 * x.warp;
        uint32_t mask = t < 2 ? ((w ? (t ? 0xFF3Fu : 0x3FFFu) : 0xFFFFu) >> (NJ - 1)) & (w ? ~1u : ~0u) : 0u, cnt = 1 + t;
        bool ready = false;
#pragma unroll 1
        for (int i = NJ; i < 16; i++) {
          if (!ready) mbar_wait2(x.fullA(x.ra.s), x.ra.ph, x.fullB(x.rb.s), x.rb.ph);
          mma8(x.ra.s, x.rb.s, 1, true);
          const uint32_t bar = sb + (t ? BAR_EMPTYB + x.pb * 8 : BAR_EMPTYA + x.pa * 8);
          gemm_next<128>(x);
          if (w && (i | 4) == 15) x.rb.s = 4;
          ready = mbar_probe2(x.fullA(x.ra.s), x.ra.ph, x.fullB(x.rb.s), x.rb.ph);
          wgmma_wait<1>();
          if (mask & 1) mbar_arrive_n(bar, cnt);
          mask >>= 1; cnt = 2;
          if (i == 8 && w) asm volatile("bar.arrive 9, 256;" ::: "memory");
          if (i == 9) TSL_(10);
        }
        mbar_wait2(sb + BAR_STAT, 1, sb + BAR_CS + 8, 0);
        wgmma_fence();
        wgmma_r1_n128(kv0, dm, dcs + 96 + 96 * w, 1);
        wgmma_r1_n128(kv1, dm + 64, dcs + 96 + 96 * w, 1);
        wgmma_commit();
        if (w == 0) asm volatile("bar.arrive 7, 256;" ::: "memory");
        wgmma_wait<1>();
        if (mask & 1) mbar_arrive_n(sb + (t ? BAR_EMPTYB + x.pb * 8 : BAR_EMPTYA + x.pa * 8), 2);
      }
      const Stats s0 = load_stats(0, x), s1 = load_stats(1, x), st = w ? s1 : s0;
      if (w == 0) skip();
      const uint32_t h0 = x.held(0), h1 = x.held(1);
      auto vreg = [&](int ks) { return ks < 6 ? OFF_A + (ks < 3 ? h0 * SLOT : h1 * SLOT - 15360) + ks * 5120 : OFF_S + 2048 + ks * 5120; };
      uint32_t tV[2], uu[4];
#pragma unroll
      for (int hf = 0; hf < 2; hf++) {
        tV[hf] = sb + vreg(4 * hf + x.warp) + ((x.lane >> 3) & 1) * 2560 + (x.lane & 7) * 16 + x.mhi * 128;
        const float i0 = rcp(hf ? s1.rstd0 : s0.rstd0), i1 = rcp(hf ? s1.rstd1 : s0.rstd1);
        const uint32_t h = pack2(i0, i1);
        uu[2 * hf] = pack2(lo16(h), i0 - lo16(h)); uu[2 * hf + 1] = pack2(hi16(h), i1 - hi16(h));
        asm volatile("" : "+r"(tV[hf]), "+r"(uu[2 * hf]), "+r"(uu[2 * hf + 1])::"memory");
      }
      wgmma_wait<0>();
      fence_regs(kv);
      TSL_(2);
      if (w == 0) {
        uint32_t f[2][18], ad[4];
#pragma unroll
        for (int q = 0; q < 18; q++) f[1][q] = 0u;
#pragma unroll
        for (int q = 0; q < 4; q++) ad[q] = x.maddr(sb + OFF_S, 2 * q);
        auto norm = [&](int un) {
          uint32_t* u = f[un & 1];
          const Stats& sn = un ? s1 : s0;
#pragma unroll
          for (int sg = 0; sg < 2; sg++) {
            uint32_t v = u[16 + sg];
            v = add2(v, __shfl_xor_sync(0xffffffffu, v, 1)); v = add2(v, __shfl_xor_sync(0xffffffffu, v, 2));
            const float a = rcp(lo16(v)) * sn.rstd0, b = rcp(hi16(v)) * sn.rstd1;
            const uint32_t r0 = pack2(a, a), r1_ = pack2(b, b);
#pragma unroll
            for (int q = 8 * sg; q < 8 * sg + 8; q++) u[q] = mul2(u[q], (q & 1) ? r1_ : r0);
#pragma unroll
            for (int q = 2 * sg; q < 2 * sg + 2; q++) stsm4(ad[q] + un * 8192, u[4 * q], u[4 * q + 1], u[4 * q + 2], u[4 * q + 3]);
          }
        };
        auto move = [&](int dst, int src) {
#pragma unroll
          for (int q = 0; q < 16; q++) asm volatile("mov.b32 %0, %1;" : "=f"(kv[dst + q]) : "f"(src ? kv[src + q] : 0.f));
        };
        hedgehog_scale<1, 0>(kv, s0, nullptr, [] {});
        uint32_t step = 0;
#pragma unroll 1
        for (int h = 0;; h++) {
          norm(1);
          dual_exp(kv, f[0], x.goff);
          hedgehog_scale<1, KEEP>(kv + 64, s1, f[1], [] {});
          if (h == 2) asm volatile("bar.sync 9, 256;" ::: "memory");
#pragma unroll
          for (int q = 0; q < 4; q++) ad[q] += step;
          norm(0);
          dual_exp(kv + 64, f[1], x.goff);
#pragma unroll
          for (int q = 0; q < 16; q++) kv[q] = kv[16 + q];
          hedgehog_scale<1, KEEP>(kv, s0, f[0], [] {});
          step = SLOT;
          if (h == 0) { move(64, 80); move(16, 32); }
          else if (h == 1) { move(64, 96); move(16, 48); step = OFF_B + SLOT - OFF_S; }
          else if (h == 2) { move(64, 112); move(16, 0); }
          else break;
        }
        norm(1);
        TSL_(3);
      } else {
        wg_bar(w);
#pragma unroll
        for (int hf = 0; hf < 2; hf++) {
          stsm4(tV[hf] + 512 + x.mhi * 512, uu[2 * hf], uu[2 * hf + 1], uu[2 * hf], uu[2 * hf + 1]);
          stsm4(tV[hf] + 1792 + x.mhi * 512, uu[2 * hf], uu[2 * hf + 1], uu[2 * hf], uu[2 * hf + 1]);
#pragma unroll
          for (int q = 0; q < 8; q++) {
            const float* u = kv + 64 * hf + 8 * q;
            stsm4(tV[hf] + (q >> 1) * 640 + (q & 1) * 256, pack2(u[0], u[1]), pack2(u[2], u[3]), pack2(u[4], u[5]), pack2(u[6], u[7]));
          }
        }
        TSL_(3);
      }
      {
        float d[2][20];
        uint4* dst = &g_kvpart[x.j()][w * 4 + x.warp][0][x.m() * 32 + x.lane];
        unsigned* dz = reinterpret_cast<unsigned*>(&g_kvpart[x.j()][w * 4 + x.warp][x.c & 1][512]) + x.m() * 8 + x.g;
        fence_async_smem();
        cta_bar();
        TSL_(11);
        uint32_t pk[9];
        auto prep = [&](float (&u)[20]) {
          fence_regs(u);
#pragma unroll
          for (int q = 0; q < 8; q++) pk[q] = pack2(u[((q >> 1) & 2) + 4 * (q & 3)], u[((q >> 1) & 2) + 4 * (q & 3) + 1]);
          pk[8] = __float_as_uint((x.c & 1) ? u[18] + u[19] : u[16] + u[17]);
#pragma unroll
          for (int q = 0; q < 9; q += 4) pk[q] = (pk[q] & ~1u) | (L == 1);
        };
        auto send = [&](int hp) {
          st_v4(dst + hp * 16 * 544, pk[0], pk[1], pk[2], pk[3]); st_v4(dst + (hp * 16 + 1) * 544, pk[4], pk[5], pk[6], pk[7]);
          st_flag(dz + hp * 16 * 544 * 4, pk[8]);
        };
        wgmma_fence();
#pragma unroll
        for (int q = 0; q < 17; q++) {
          if (q < 16) wgmma_ss_n40_tt(d[q >> 3], desc_lo(SB + (q < 8 ? OFF_S : OFF_B + 2 * SLOT), 1024) + w * (SLOT / 16) + 128 * (q & 7), desc_lo(SB + vreg(q & 7), 2560) + (w + (q >> 3) * 2) * 40, q & 7);
          else wgmma_r1_n128(acc, dm + w * 64, dcs, 0);
          if (q == 7 || q == KVS || q == 16) wgmma_commit();
          if (q == KVS) { mbar_wait2(x.fullA(x.ra.s), x.ra.ph, x.fullB(x.rb.s), x.rb.ph); wgmma_wait<1>(); prep(d[0]); send(0); bb_fence(x.goff); wgmma_fence(); }
        }
        gemm_issue<128, false>(acc, x, true); gemm_next<128>(x);
        wgmma_wait<1>();
        x.releaseA(h0); x.releaseA(h1); x.releaseB(2); x.releaseB(3);
        if (x.lane == 0) mbar_arrive(sb + BAR_SIGT);
        prep(d[1]);
        TSL_(4);
#pragma unroll 1
        for (int seg = 0; seg < 2; seg++) {
          const int n0 = w ? PS1 : PS0;
          gemm_run(acc, x, seg ? 15 - n0 : n0, seg, seg ? L : 0);
          if (seg == 0) send(1);
        }
      }
      gemm_end(acc, x);
      TSL_(5);
      {
        float dp[2][20], dn[2][20];
        uint32_t f[4][16];
        auto mma = [&](int h) {
          if (!(h & 1)) mbar_wait(sb + BAR_KV + h * 4, L >> 1);
          if (h == 0) TSL_(9);
          const uint32_t db = desc_lo(SB + OFF_S + h * 5120, 128);
          const uint32_t (&a)[16] = f[h];
          wgmma_fence();
          wgmma_rs_n40(dp[h & 1], a[0], a[1], a[2], a[3], db, 0);
          wgmma_rs_n40(dn[h & 1], a[8], a[9], a[10], a[11], db + 160, 0);
          wgmma_rs_n40(dp[h & 1], a[4], a[5], a[6], a[7], db + 80, 1);
          wgmma_rs_n40(dn[h & 1], a[12], a[13], a[14], a[15], db + 240, 1);
          wgmma_commit();
        };
        uint32_t xr[16];
        auto fin = [&](int h) {
          const uint32_t tile = x.aslot(x.held(h >> 1));
          if (!(h & 1)) img_load(xr, tile, x);
          float (&u)[20] = dp[h & 1];
          float (&v)[20] = dn[h & 1];
          fence_regs(u); fence_regs(v);
#pragma unroll
          for (int r = 0; r < 2; r++) {
            const float sp = u[16 + 2 * r], sn = v[16 + 2 * r];
            const float id = rcp(fmaf(fmaf(sp, L == 1 ? 0.065536f * 128 / 129 : 0.065536f, u[17 + 2 * r]), sn, v[17 + 2 * r] * sp)), aa = sn * id, cc = sp * id;
            uint32_t o[4];
#pragma unroll
            for (int t = 0; t < 4; t++) o[t] = pack2(fmaf(u[4 * t + 2 * r], aa, v[4 * t + 2 * r] * cc), fmaf(u[4 * t + 2 * r + 1], aa, v[4 * t + 2 * r + 1] * cc));
            o[2 * r + (h & 1)] = img_tag(o[2 * r + (h & 1)], false, 1, x);
            if (ZO && h == 3) r1[r] = make_uint4(o[0], o[1], o[2], o[3]);
            else stg128(x.img(0, h >> 1) + r * 64 + (h & 1) * 32, make_uint4(o[0], o[1], o[2], o[3]));
            sts128(tile + r * 1024 + (h & 1) * 512 + x.so, o[0], o[1], o[2], o[3]);
          }
          if (h & 1) { if (h == 1) publish(0, x); img_unpack(acc + 16 * (h - 1), xr); }
        };
        auto ex = [&](int h) { dual_exp_rcp(acc + 16 * h, f[h]); };
        Stats sq = st;
#pragma unroll
        for (int h = 0; h < 4; h += 2) {
          hedgehog_scale<2, 0>(acc + 16 * h, sq, nullptr, [&] { ex(h); });
          mma(h);
          ex(h + 1); wgmma_wait<0>(); fin(h);
          if (h == 0) bb_fence(x.goff);
          mma(h + 1);
          wgmma_wait<0>(); fin(h + 1);
          if (h == 0) sq.rstd1 += bb_fence(x.goff);
        }
      }
    }
    mbar_wait(x.fullB(x.rb.s), x.rb.ph);
    fence_regs(acc);
    fence_async_smem();
    wg_bar(w);
    TSL_(6);
    rewind2<NA>(x.ra);
    if (ZO && (L & 1)) { stg128(x.img(0, 1) + 32, r1[0]); stg128(x.img(0, 1) + 96, r1[1]); }
    gemm_issue<128, false>(acc, x, true); gemm_next<128>(x);
    uint4* out = solid(P.out + goff + (x.warp * 16 + (x.lane >> 3)) * 256 + (x.lane & 7));
#pragma unroll 1
    for (int seg = L >= TSL ? 0 : 1; seg < 2; seg++) {
      gemm_run(acc, x, L >= TSL ? (seg ? TSK : 15 - TSK) : 15, seg, 10 + L);
      if (L >= TSL) {
        if (seg == 0 && w == 1) asm volatile("bar.sync 6, 256;" ::: "memory");
        if (seg == 1 && w == 0) asm volatile("bar.arrive 6, 256;" ::: "memory");
      }
    }
    gemm_end(acc, x);
    TSL_(7);
    rewind2<NA>(x.ra);
    out_epilogue(acc, r1, ts, out, L, x);
    TSL_(13);
  }
}

typedef unsigned long long u64;
template <class T> __device__ __forceinline__ T* early(T* p) { return (T*)__shfl_xor_sync(0xffffffffu, (u64)p, 1); }
__device__ __forceinline__ void pause(uint32_t GAP) {
  if (GAP) { uint32_t t0, t; asm volatile("mov.u32 %0, %%clock;" : "=r"(t0)); do { asm volatile("mov.u32 %0, %%clock;" : "=r"(t)); } while (t - t0 < GAP); }
}
__device__ __forceinline__ u64 order_table0(int j) { return (j & 4) ? 0x543210FEDCBA9876ull : 0xDCBA9876543210FEull; }
__device__ __forceinline__ void order_tables(u64& t1, u64& t2, int j) {
#pragma unroll 1
  for (int i = 6; i >= 0; i--) { const u64 o = 2 * other_tile(i, j); t1 = t1 << 4 | o | (o + 1) << 28; t2 = t2 << 8 | (o * 17 + 16); }
  const u64 own = 2 * j * 17 + 16;
  t1 = t1 << 8 | own; t2 |= own << 56;
}

__device__ __forceinline__ void b_producer(const Params& P, uint32_t sb, unsigned vb) {
  const int j = cta_j(vb);
  u64 t1 = 0, t2 = 0;
  Ring r = {PRE_B % NB, PRE_B < NB};
#pragma unroll 1
  for (int sg = 0; sg < 20; sg++) {
    const int L = sg / 5, p = sg - 5 * L, wt = L & 1;
    if (sg == 1) order_tables(t1, t2, j);
    int n = p >= 3 ? 16 : (wt ? (p ? 16 - NJ : 2 * NJ) : (p ? 0 : (L ? 32 : 32 - PRE_B)));
    u64 tab = p == 3 ? t2 : (sg == 0 ? order_table0(j) >> (2 * PRE_B) : (p == 1 || p == 2 ? t1 >> (4 * NJ) : t1));
    const CUtensorMap* tm = p == 4 ? &P.mwo[wt] : &P.mw[wt ? 1 : L];
    const uint4* img = &g_wf[p != 3][j][0][0];
    int col = (p >= 3 ? 0 : (p == 2 ? 2048 : 1024)) + 128 * j;
    const int flip = p == 0 ? 3072 : 0;
    const bool fold = wt && p != 4;
    if (sg == 5 || sg == 8) { mbar_wait(sb + (sg == 5 ? BAR_WPHI : BAR_CS + 8), sg == 5); fence_async_global(); }
    if (DEFER && p == 4 && ((DEFL >> wt) & 1)) {
      Ring q = r;
      for (int u = 0; u < DEFER; u++) adv<NB>(q);
      mbar_wait(sb + BAR_EMPTYB + q.s * 8, q.ph);
    }
#pragma unroll 1
    for (; n > 0; n--) {
      const int kb = (int)tab & 15;
      mbar_wait(sb + BAR_EMPTYB + r.s * 8, r.ph);
      if (elect()) {
        mbar_expect_tx(sb + BAR_FULLB + r.s * 8, SLOT);
        if (fold && col < 2048) bulk_load(sb + OFF_B + r.s * SLOT, img + kb * 1024, SLOT, sb + BAR_FULLB + r.s * 8);
        else tma_load_w(sb + OFF_B + r.s * SLOT, tm, sb + BAR_FULLB + r.s * 8, col, kb);
      }
      adv<NB>(r);
      if (p == 2 && (n | 4) == 5) r.s = 4;
      col ^= flip;
      if (!(col & flip & 2048)) tab >>= 4;
    }
  }
}

__device__ __forceinline__ void a_loader(const Params& P, uint32_t sb, unsigned vb) {
  const int j = cta_j(vb), m = cta_m(vb);
  u64 t1 = 0, t2 = 0;
  Ring r = {PRE_A % NA, PRE_A < NA};
  {
    u64 tab = order_table0(j) >> (4 * PRE_A);
#pragma unroll 1
    for (int i = PRE_A; i < 33; i++) {
      if (i == 17) { order_tables(t1, t2, j); tab = t2; }
      mbar_wait(sb + BAR_EMPTYA + r.s * 8, r.ph);
      if (elect()) {
        mbar_expect_tx(sb + BAR_FULLA + r.s * 8, SLOT);
        if (i != 14) tma_load_3d(sb + OFF_A + r.s * SLOT, &P.mx, sb + BAR_FULLA + r.s * 8, ((int)tab & 15) * 64, m * 64, 0);
        else {
          tma_load_w(sb + OFF_A + r.s * SLOT, &P.mw[1], sb + BAR_FULLA + r.s * 8, 1024 + 128 * j, m);
          mbar_expect_tx(sb + BAR_WPHI, 8192); tma_load_2d(sb + OFF_S + 4096, &P.mwphi, sb + BAR_WPHI, 0, 128 * j);
        }
        if (i == PF1 || i == PF2) tma_prefetch_w(&P.mwo[i == PF2], 128 * j, m);
      }
      adv<NA>(r);
      if (i != 14) tab >>= 4;
    }
  }
  const unsigned tag = get_tag(sb);
  unsigned kph = 0;
#pragma unroll 1
  for (int sg = 0; sg < 13; sg++) {
    const int L = sg >> 2, p = sg & 3;
    if (p == 0 && (L & 1)) {
#pragma unroll 1
      for (int h = 0; h < 2; h++) {
        poll_flags(&g_jflag[h][j][0], 16, 0xFFFFu, tag * 4 + L);
        TS(4, h ? 14 + L : 26 + L);
        for (int it = 0;; it++) {
          if (elect()) { mbar_expect_tx(sb + BAR_STAT + 8, 10240); bulk_load(sb + OFF_S + h * 10240, &g_kvfin[j][8 * h][0], 10240, sb + BAR_STAT + 8); }
          mbar_wait(sb + BAR_STAT + 8, kph);
          kph ^= 1;
          uint32_t a = 1u, o = 0u;
#pragma unroll
          for (int u = 0; u < 20; u++) { const uint32_t v = __float_as_uint(lds32f(sb + OFF_S + h * 10240 + u * 512 + (threadIdx.x & 31) * 16)); a &= v; o |= v; }
          if (__all_sync(0xffffffffu, (L == 1 ? a : ~o) & 1u)) break;
          fence_async_smem();
          if (it > (1 << 16)) __trap();
        }
        if (elect()) mbar_arrive(sb + BAR_KV + h * 8);
        TS(4, h ? 30 + L : (L == 1 ? 20 : 25));
      }
    }
    int n = p < 2 ? 14 : (p == 2 ? ((L & 1) ? 0 : 16 - NJ) : 16);
    u64 tab = p == 3 ? t2 : t1 >> (p < 2 ? 8 : 4 * NJ);
    const uint4* img = &g_img[p ? XBUF(L + 1) : 0][m][0][0];
#pragma unroll 1
    for (; n > 0; n--) {
      const uint4* src = early(img + ((int)tab & 15) * 1024);
      const uint32_t bar = sb + (p < 2 ? BAR_LAND : BAR_FULLA) + r.s * 8;
      mbar_wait(sb + BAR_EMPTYA + r.s * 8, r.ph);
      if (elect()) mbar_expect_tx(bar, SLOT);
      if (p < 2 && n == 14) {
        const int lane = threadIdx.x & 31;
        const unsigned* f = &g_hint[(m & 14) + ((lane >> 3) & 1)][(~j & 4) + (lane & ND0)];
        mbar_wait(sb + BAR_SIGP + p * 8, L & 1);
        pause(PD);
        int it = 0;
        while (!__all_sync(0xffffffffu, (int)(ld_flag(f) - (tag * 16 + 4 * L + 1 + p)) >= 0)) { if (++it > (1 << 22)) __trap(); }
        TS(2, p == 0 ? 5 + L * 8 : 9 + L * 8);
        TSH((2 * L + p) * 8 + 2);
      }
      if (elect()) bulk_load(sb + OFF_A + r.s * SLOT, src, SLOT, bar);
      adv<NA>(r);
      tab >>= 4;
      pause(p < 2 && n > 10 ? G0 : 0);
    }
  }
}

template <int KB>
__device__ __forceinline__ uint2 sum_packets(float (&a)[8], uint32_t addr, int n) {
  uint2 ok = make_uint2(~0u, 0u);
#pragma unroll 1
  for (int b = 0; b < n; b += KB) {
    uint4 v[KB];
#pragma unroll
    for (int u = 0; u < KB; u++) lds128(addr + (b + u) * 512, v[u].x, v[u].y, v[u].z, v[u].w);
#pragma unroll
    for (int u = 0; u < KB; u++) {
      ok.x &= v[u].x; ok.y |= v[u].x;
      a[0] += lo16(v[u].x); a[1] += hi16(v[u].x); a[2] += lo16(v[u].y); a[3] += hi16(v[u].y);
      a[4] += lo16(v[u].z); a[5] += hi16(v[u].z); a[6] += lo16(v[u].w); a[7] += hi16(v[u].w);
    }
  }
  return ok;
}
__device__ __forceinline__ void helper_bar() { asm volatile("bar.sync 4, 64;" ::: "memory"); }
__device__ __forceinline__ void helper(const Params& P, uint32_t sb, int w, unsigned vb) {
  const int j = cta_j(vb), m = cta_m(vb);
  if (w == 0) {
    if (elect()) {
      const unsigned t = atomicAdd(&g_ctr, 1u) / NCTA + 1u;
      asm volatile("st.shared.u32 [%0], %1;" ::"r"(sb + OFF_EPOCH), "r"(t) : "memory");
      mbar_arrive(sb + BAR_EPOCH);
    }
  }
  const unsigned tag = get_tag(sb);
  mbar_wait(sb + BAR_FULLB + 24, 0);
  const uint32_t stg = sb + OFF_T + w * 12288, stb = sb + BAR_STG + w * 24;
  Ring rs = {0, 0};
  uint32_t vs = 33 % NA, vph = 0;
  auto cs_image = [&](int L) {
      const int lane = lane_id();
      poll_flags(&g_jflag[2 * L][j][0], 16, L ? CSNEED : 0xFFFu, tag * 4);
#pragma unroll
      for (int p = 0; p < 3; p++) {
        const uint4 u = ldcg4(&g_cs[L][0][p * 1024 + 128 * j + lane * 4]), v = ldcg4(&g_cs[L][1][p * 1024 + 128 * j + lane * 4]);
        const float c0 = __uint_as_float(u.x) + __uint_as_float(v.x), c1 = __uint_as_float(u.y) + __uint_as_float(v.y);
        const float c2 = __uint_as_float(u.z) + __uint_as_float(v.z), c3 = __uint_as_float(u.w) + __uint_as_float(v.w);
        const uint32_t h0 = pack2(c0, c1), h1 = pack2(c2, c3), dst = sb + OFF_CS + (p * 16 + (lane >> 1)) * 96 + L * 48 + (lane & 1) * 8;
        sts64(dst, h0, h1); sts64(dst + 16, pack2(c0 - lo16(h0), c1 - hi16(h0)), pack2(c2 - lo16(h1), c3 - hi16(h1))); sts64(dst + 32, h0, h1);
        if (L == 0) { sts64(dst + 48, 0u, 0u); sts64(dst + 64, 0u, 0u); sts64(dst + 80, 0u, 0u); }
      }
      if (L == 0 && lane < 4) sts64(sb + OFF_CS + 4608 + lane * 8, 0u, 0u);
      fence_async_smem();
      __syncwarp();
      if (elect()) mbar_arrive(sb + BAR_CS + L * 8);
      TS(4, 2 + L * 2);
  };
#pragma unroll 1
  for (int L = 0; L < 4; L++) {
    const int lane = lane_id();
    if (L == 0) {
      {
        const int wt = m >= 12, col = ((0x2021 >> (m & 12)) & 3) * 1024 + 128 * j + (m & 3) * 32;
        const CUtensorMap* tm = &P.mcs[wt];
        __nanosleep(wt ? D2 : CD);
        constexpr int nb = 8;
        float a[8] = {0.f, 0.f, 0.f, 0.f, 0.f, 0.f, 0.f, 0.f};
#pragma unroll 1
        for (int b = -3; b < nb; b++) {
          if (b >= 0) {
            mbar_wait(stb + rs.s * 8, rs.ph);
            sum_packets<KC>(a, stg + rs.s * 4096 + lane * 16, 8);
            fence_async_smem();
            __syncwarp();
          }
          const uint32_t sl = b < 0 ? (rs.s + b + 3) % 3 : rs.s;
          if (b + 3 < nb && elect()) { mbar_expect_tx(stb + sl * 8, 4096); tma_load_2d(stg + sl * 4096, tm, stb + sl * 8, col, (w * (16 - nb) + b + 3) * 64); }
          if (b >= 0) adv<3>(rs); else pause(CP);
        }
#pragma unroll 1
        for (int d = 4; d < 32; d *= 2)
#pragma unroll
          for (int u = 0; u < 8; u++) a[u] += __shfl_xor_sync(0xffffffffu, a[u], d);
        if (lane < 4) {
          float4* dst = reinterpret_cast<float4*>(&g_cs[wt][w][col + lane * 8]);
          dst[0] = make_float4(a[0], a[1], a[2], a[3]); dst[1] = make_float4(a[4], a[5], a[6], a[7]);
        }
        helper_bar();
        if (w == 0 && elect()) { fence_gpu(); st_flag(&g_jflag[2 * wt][j][m], tag * 4); }
      }
      if (w == 0) TS(4, 1 + L * 2);
    }
    if (L > 0 && w == 0) {
      mbar_wait(sb + BAR_SIGP + 16, (L - 1) & 1);
      fence_async_global();
      __nanosleep(CO && L == 1 ? SE : SD);
    }
    if (CO && L < 2 && w == 0) cs_image(L);
    if (w == (L == 0)) {
      if (L == 0) { mbar_wait(sb + BAR_WPHI, 0); __nanosleep(S0); }
#pragma unroll 1
      for (int p = 0; p < 2; p++) {
        uint4 v[8];
        for (int it = 0;; it++) {
          bool ok = true;
#pragma unroll
          for (int t = 0; t < 8; t++) v[t] = ld_pkt(&g_stats[m][p][t][lane]);
#pragma unroll
          for (int t = 0; t < 8; t++) ok = ok && (v[t].w & 15u) == seq4(tag, L);
          if (__all_sync(0xffffffffu, ok)) break;
          __nanosleep(200);
          if (it > (1 << 20)) __trap();
        }
        float s0 = 0.f, q0 = 0.f, s1 = 0.f, q1 = 0.f;
#pragma unroll
        for (int t = 0; t < 8; t++) { s0 += __uint_as_float(v[t].x); q0 += __uint_as_float(v[t].y); s1 += __uint_as_float(v[t].z); q1 += __uint_as_float(v[t].w & ~15u); }
        s0 *= (1.f / 1024); s1 *= (1.f / 1024);
        sts64(sb + OFF_MR + p * 256 + lane * 8, __float_as_uint(rsqrtf(fmaxf(q0 * (1.f / 1024) - s0 * s0, 0.f) + 1e-5f)),
              __float_as_uint(rsqrtf(fmaxf(q1 * (1.f / 1024) - s1 * s1, 0.f) + 1e-5f)));
#pragma unroll
        for (int r = 0; r < 2; r++) {
          const float v = -0.5f * (r ? s1 : s0);
          const uint32_t hh = pack2(v, v), hl = pack2(v, v - lo16(hh));
          const bool b = L & 1;
          sts128(sb + (b ? OFF_MB : OFF_MA) + p * 1024 + (lane >> 3) * 256 + r * 128 + (lane & 7) * 16, b ? 0u : hh, b ? hh << 16 : hl >> 16, b ? hl : 0u, 0u);
        }
      }
      fence_async_smem();
      __syncwarp();
      if (elect()) {
        mbar_arrive(sb + BAR_STAT);
      }
      TS(2, 0 + L * 8);
    }
    if (!CO && L < 2 && w == 0) cs_image(L);
    if (L & 1) {
      const uint32_t flip = L == 1 ? 0u : 1u;
      mbar_wait(sb + BAR_SIGT, 1);
      {
        int it = 0;
        if (PSL) __nanosleep(m < 8 ? PSL : PSL + 600);
        while (!__all_sync(0xffffffffu, (ld_flag(reinterpret_cast<const unsigned*>(&g_kvpart[j][m][w][512]) + (lane & 15) * 8) ^ flip) & 1u)) { if (PSL) __nanosleep(100); if (++it > (1 << 22)) __trap(); }
        fence_async_global();
      }
      if (w == 0) TS(4, 6 + L * 2);
      float a[8], z;
      for (int it = 0;; it++) {
        if (elect()) { mbar_expect_tx(stb + rs.s * 8, 8704); bulk_load(stg, &g_kvpart[j][m][w][0], 8704, stb + rs.s * 8); }
        mbar_wait(stb + rs.s * 8, rs.ph);
        if (w == 0) TS(4, 21 + L);
        adv<3>(rs);
#pragma unroll
        for (int u = 0; u < 8; u++) a[u] = 0.f;
        z = 0.f;
        uint32_t ok = 1u;
#pragma unroll
        for (int u = 0; u < 4; u++) { const float v = lds32f(stg + 8192 + u * 128 + (lane & 3) * 32 + (lane >> 2) * 4); z += v; ok &= __float_as_uint(v) ^ flip; }
        const uint2 tg = sum_packets<8>(a, stg + lane * 16, 16);
        ok &= flip ? ~tg.y : tg.x;
        if (__all_sync(0xffffffffu, ok & 1u)) break;
        fence_async_smem();
        if (it > (1 << 16)) __trap();
      }
      {
        uint4* img = &g_kvfin[j][m][w * 8 + (lane >> 2)];
        uint32_t a0 = __float_as_uint(a[0]) >> 16;
        a0 += ~(a0 ^ flip) & 1u;
        st_v4(img + (lane & 3) * 16, __byte_perm(a0, pack2(0.f, a[1]), 0x7610), pack2(a[2], a[3]), pack2(a[4], a[5]), pack2(a[6], a[7]));
        const uint32_t cz = pack2(0.f, qsum(z)) | (0x3781u ^ flip);
        if (!(lane & 3)) st_v4(img + 64, cz, cz, cz, cz);
        __syncwarp();
        if (elect()) st_flag(&g_jflag[m >> 3][j][(m & 7) * 2 + w], tag * 4 + L);
      }
      if (w == 0) TS(4, 7 + L * 2);
    } else {
      mbar_wait(sb + BAR_SIGT, 0);
      if (w == 0) {
        if (elect()) { fence_gpu(); st_flag(&g_hint[m][j], tag * 16 + 4 * L); st_flag(&g_jflag[1][j][m], tag * 4 + L); }
        if (L == 0) {
          __nanosleep(KSL);
          poll_flags(&g_jflag[1][j][0], 16, 0xFFFFu, tag * 4);
          if (elect()) mbar_arrive(sb + BAR_WPHI);
        }
      } else if (m > 0) {
        poll_flags(&g_hint[m - 1][j], 1, 1u, tag * 16 + 4 * L);
        if (elect()) { mbar_expect_tx(sb + BAR_HALO, 8192); bulk_load(sb + OFF_S + 8192, &g_halo[m - 1][j][0][0], 8192, sb + BAR_HALO); }
        TS(2, 2 + L * 8);
      }
    }
    if (w == 0) {
#pragma unroll 1
      for (int e = 0; e < (L < 3 ? 2 : 1); e++) {
        unsigned* flag = early(&g_hint[m][j]);
        mbar_wait(sb + BAR_SIGP + e * 8, L & 1);
        TS(2, (e ? 6 : 3) + L * 8);
        TSH((2 * L + e) * 8);
        pause(XD);
        if (elect()) st_flag(flag, tag * 16 + 4 * L + 1 + e);
        TSH((2 * L + e) * 8 + 1);
      }
    } else {
#pragma unroll 1
      for (int i = 0; i < (L < 3 ? 28 : 14); i++) {
        const bool isx = i >= 14;
        const uint32_t a = sb + OFF_A + vs * SLOT + lane * 128 + ((lane >> 4) * 4 + (lane & 3)) * 16 + (lane & 12), code = img_code(isx, L + isx);
        for (int it = 0;; it++) {
          mbar_wait(sb + BAR_LAND + vs * 8, (vph >> vs) & 1);
          vph ^= 1u << vs;
          if (i - 14 * isx < 2) TSH((2 * L + isx) * 8 + 3 + 2 * (i - 14 * isx));
          uint32_t bad = 0;
#pragma unroll
          for (int u = 0; u < 4; u++) bad |= __float_as_uint(lds32f(a + u * 4096)) ^ code;
          if (__all_sync(0xffffffffu, !(bad & img_mask(isx)))) break;
          if (it > (1 << 16)) __trap();
          fence_async_smem();
          if (elect()) {
            mbar_expect_tx(sb + BAR_LAND + vs * 8, SLOT);
            bulk_load(sb + OFF_A + vs * SLOT, &g_img[isx ? XBUF(L + 1) : 0][m][o_order(i - 14 * isx + 2, j)][0], SLOT, sb + BAR_LAND + vs * 8);
          }
        }
        if (elect()) mbar_arrive(sb + BAR_FULLA + vs * 8);
        if (i - 14 * isx < 2) TSH((2 * L + isx) * 8 + 4 + 2 * (i - 14 * isx));
        if (++vs == NA) vs = 0;
      }
      vs = (vs + ((L & 1) ? 16 : 32 - NJ)) % NA;
    }
  }
}

__device__ __forceinline__ void spare(const Params& P, uint32_t sb, int id) {
  const int tid = threadIdx.x & 127, warp = __shfl_sync(0xffffffffu, threadIdx.x >> 5, 0), w = warp >> 2, lane = tid & 31, j = 2 * id + w;
  const uint32_t ring = w * 6 * SLOT, wp = 12 * SLOT + w * 8192, bar = sb + 13 * SLOT + w * 64;
  auto part = [&](int t) { return (t >> 4) ^ w; };
  auto load = [&](int t, uint32_t sl) {
    mbar_expect_tx(bar + sl * 8, t == 0 ? SLOT + 8192 : SLOT);
    tma_load_w(sb + ring + sl * SLOT, &P.mw[1], bar + sl * 8, part(t) * 1024 + 128 * j, t & 15);
  };
  if (!(warp & 3) && elect()) {
    if (w == 2) sts32(sb + OFF_EPOCH, atomicAdd(&g_ctr, 1u) / NCTA + 1u);
    else {
      __nanosleep(D3);
#pragma unroll 1
      for (int t = 0; t < 5; t++) {
        mbar_init(bar + t * 8, 1);
        asm volatile("fence.mbarrier_init.release.cluster;" ::: "memory");
        load(t, t);
      }
      tma_load_2d(sb + wp, &P.mwphi, bar, 0, 128 * j);
    }
  }
  if (w == 2) {
    u64 a = (u64)&P;
    asm volatile("" : "+l"(a));
    const u64 pc = *reinterpret_cast<const u64*>(a - 0x240 + 0x118);
    const unsigned off = IP0 + (id * 128 + tid) * 128;
    if ((pc >> 40) == (a >> 40) && off < IP1) asm volatile("prefetch.global.L2 [%0];" ::"l"(pc + off));
    if (IPF == 2 && (pc >> 40) == (a >> 40)) asm volatile("prefetch.global.L2 [%0];" ::"l"(pc + off - IP0));
  }
  __syncthreads();
  const unsigned tag = get_tag<false>(sb);
  if (w == 2) {
    int it = 0;
    while ((int)(ld_flag(&g_ctr) - tag * NCTA) < 0) { if (++it > (1 << 22)) __trap(); }
    return;
  }
  Ring r = {4, 1};
  float d[64];
  auto fold = [&]() {
    mbar_wait(bar + r.s * 8, r.ph);
    wgmma_fence();
#pragma unroll
    for (int q = 0; q < 8; q++)
      wgmma_ss_n32(reinterpret_cast<float (&)[16]>(d[16 * (q >> 1)]), desc_lo(SB + ring + r.s * SLOT, 16) + (q >> 2) * 512 + (q & 3) * 2, desc_lo(SB + wp, 512) + q * 64, q & 1);
    wgmma_commit();
  };
#pragma unroll
  for (int i = 0; i < 64; i++) d[i] = 0.f;
  int t = -1;
#pragma unroll 1
  for (int g = 0; g < 2; g++) {
    float cs[32] = {};
#pragma unroll 1
    do {
      uint32_t f[32];
#pragma unroll
      for (int i = 0; i < 32; i++) { f[i] = pack2(d[2 * i], d[2 * i + 1]); cs[i & 30] += d[2 * i]; cs[i | 1] += d[2 * i + 1]; }
      wg_bar(w);
      const uint32_t sl = r.s;
      if (t < 31) adv<5>(r);
      fold();
      if (!(warp & 3) && t >= 0 && t < 27 && elect()) load(t + 5, sl);
      if (g == w && t >= 0) {
        uint4* dst = &g_wf[0][j][t & 15][((tid >> 5) * 16 + (lane >> 2)) * 8];
#pragma unroll
        for (int q = 0; q < 8; q++)
          dst[(q >> 2) * 512 + (q & 1) * 64 + (((q & 2) * 2 + (lane & 3)) ^ (lane >> 2))] =
              make_uint4(f[4 * (q & 6) + (q & 1)], f[4 * (q & 6) + (q & 1) + 2], f[4 * (q & 6) + (q & 1) + 4], f[4 * (q & 6) + (q & 1) + 6]);
      }
      wgmma_wait<0>();
      fence_regs(d);
    } while (++t != 16 * g + 16);
    const uint32_t red = sb + ring + 5 * SLOT;
#pragma unroll
    for (int i = 0; i < 8; i++) sts128(red + (tid >> 2) * 512 + (i >> 1) * 128 + (lane & 3) * 32 + (i & 1) * 16, __float_as_uint(cs[4 * i]), __float_as_uint(cs[4 * i + 1]), __float_as_uint(cs[4 * i + 2]), __float_as_uint(cs[4 * i + 3]));
    wg_bar(w);
    float a = 0.f;
#pragma unroll 4
    for (int i = 0; i < 32; i++) a += lds32f(red + i * 512 + tid * 4);
    g_cs[1][0][(g ^ w) * 1024 + j * 128 + tid] = a;
  }
  wg_bar(w);
  if (tid == 0) { fence_gpu(); st_flag(&g_jflag[2][j][0], tag * 4); }
}

__global__ void __launch_bounds__(NTHREADS, 1) fused_kernel(const __grid_constant__ Params P) {
  extern __shared__ __align__(1024) uint8_t smem_raw[];
  constexpr uint32_t sb = SB;
  const int tid = threadIdx.x;
  const unsigned vb = vblock();
  if (vb >= 128) { spare(P, sb, vb - 128); return; }
  const int warp = __shfl_sync(0xffffffffu, tid >> 5, 0);
  if (elect()) {
    if (warp == 11) { prefetch_map(&P.mx); prefetch_map(&P.mw[0]); if (smem_u32(smem_raw) != SB) __trap(); }
    if (warp < 8) {
#pragma unroll
      for (int i = 0; i < 8; i++) mbar_init(sb + OFF_BAR + (warp * 8 + i) * 8, warp == 2 || warp == 3 ? 2 : (warp == 4 ? 8 : 1));
    }
    asm volatile("fence.mbarrier_init.release.cluster;" ::: "memory");
    if (warp < 2) {
      const int j = cta_j(vb);
#pragma unroll 1
      for (int i = 0; i < (warp == 0 ? PRE_B : PRE_A); i++) {
        const uint32_t bar = sb + BAR_FULLB + warp * 64 + i * 8;
        mbar_expect_tx(bar, SLOT);
        if (warp == 0) tma_load_w(sb + OFF_B + i * SLOT, &P.mw[0], bar, 1024 + (i & 1) * 1024 + 128 * j, kv_order(i >> 1, j, 0));
        else tma_load_3d(sb + OFF_A + i * SLOT, &P.mx, bar, kv_order(i, j, 0) * 64, cta_m(vb) * 64, 0);
      }
    }
  }
  if (tid == 0) TS(6, 0);
  __syncthreads();
  if (tid == 0) TS(6, 2);
  if (warp < 4) {
    reg_dealloc<PREGS>();
    if (warp & 2) helper(P, sb, warp & 1, vb);
    else if (warp & 1) a_loader(P, sb, vb);
    else b_producer(P, sb, vb);
  } else {
    reg_alloc<CREGS>();
    consumer(P, sb, (warp >> 2) - 1, vb);
  }
}

typedef CUresult (*EncodeFn)(CUtensorMap*, CUtensorMapDataType, cuuint32_t, void*, const cuuint64_t*, const cuuint64_t*,
                             const cuuint32_t*, const cuuint32_t*, CUtensorMapInterleave, CUtensorMapSwizzle,
                             CUtensorMapL2promotion, CUtensorMapFloatOOBfill);

void encode(EncodeFn fn, CUtensorMap* m, const void* ptr, int rank, const cuuint64_t* dims, const cuuint64_t* strides,
            const cuuint32_t* box, CUtensorMapSwizzle swz) {
  const cuuint32_t es[5] = {1, 1, 1, 1, 1};
  fn(m, CU_TENSOR_MAP_DATA_TYPE_BFLOAT16, rank, const_cast<void*>(ptr), dims, strides, box, es, CU_TENSOR_MAP_INTERLEAVE_NONE,
     swz, CU_TENSOR_MAP_L2_PROMOTION_L2_256B, CU_TENSOR_MAP_FLOAT_OOB_FILL_NONE);
}
void encode_w(EncodeFn fn, CUtensorMap* m, const void* ptr, int ncols, bool perm) {
  const cuuint64_t p = (cuuint64_t)ncols * 2, d[5] = {(cuuint64_t)ncols, 2, 4, 4, 32}, s[4] = {p, (perm ? 8 : 2) * p, (perm ? 2 : 8) * p, 32 * p};
  const cuuint32_t box[5] = {64, 2, 4, 4, 2};
  encode(fn, m, ptr, 5, d, s, box, CU_TENSOR_MAP_SWIZZLE_128B);
}

void encode_cs(EncodeFn fn, CUtensorMap* m, const void* ptr, int ncols) {
  const cuuint64_t d[2] = {(cuuint64_t)ncols, 1024}, s[1] = {(cuuint64_t)ncols * 2};
  const cuuint32_t box[2] = {32, 64};
  encode(fn, m, ptr, 2, d, s, box, CU_TENSOR_MAP_SWIZZLE_NONE);
}

}

extern "C" void kernel_launch(void* const* d_in, const int* in_sizes, int n_in, void* d_out, int out_size) {
  (void)in_sizes; (void)n_in; (void)out_size;
  void* fnp = nullptr;
  cudaDriverEntryPointQueryResult q;
  cudaGetDriverEntryPoint("cuTensorMapEncodeTiled", &fnp, cudaEnableDefault, &q);
  EncodeFn fn = (EncodeFn)fnp;
  Params P;
  {
    const cuuint64_t dims[3] = {1024, 1024, 2}, strides[2] = {4096, 2048};
    const cuuint32_t box[3] = {64, 64, 2};
    encode(fn, &P.mx, d_in[0], 3, dims, strides, box, CU_TENSOR_MAP_SWIZZLE_128B);
  }
  P.out = (uint4*)d_out;
  encode_w(fn, &P.mw[0], d_in[1], 3072, false);
  encode_w(fn, &P.mw[1], d_in[4], 3072, true);
  encode_w(fn, &P.mw[2], d_in[1], 3072, true);
  encode_w(fn, &P.mwo[0], d_in[2], 1024, true);
  encode_w(fn, &P.mwo[1], d_in[6], 1024, false);
  encode_cs(fn, &P.mcs[0], d_in[1], 3072);
  encode_cs(fn, &P.mcs[1], d_in[4], 3072);
  {
    const cuuint64_t dims[2] = {32, 1024}, strides[1] = {64};
    const cuuint32_t box[2] = {32, 128};
    encode(fn, &P.mwphi, d_in[5], 2, dims, strides, box, CU_TENSOR_MAP_SWIZZLE_64B);
  }
  cudaFuncSetAttribute(fused_kernel, cudaFuncAttributeMaxDynamicSharedMemorySize, SMEM_BYTES);
  fused_kernel<<<NCTA, NTHREADS, SMEM_BYTES, cudaStreamPerThread>>>(P);
}
```

```cpp
#include <cuda_runtime.h>
#include <cuda_bf16.h>
#include <cuda.h>
#include <stdint.h>

namespace {

__device__ __forceinline__ void wgmma_ss_n256(float (&d)[128], uint32_t da, uint32_t ha, uint32_t db, int sd) {
  asm volatile("{\n.reg .pred p;\n.reg .b64 a, b;\nsetp.ne.b32 p, %130, 0;\nmov.b64 a, {%128, %131};\nmov.b64 b, {%129, 0x40000040};\n"
    "wgmma.mma_async.sync.aligned.m64n256k16.f32.bf16.bf16 {%0,%1,%2,%3,%4,%5,%6,%7,%8,%9,%10,%11,%12,%13,%14,%15,%16,%17,%18,%19,%20,%21,%22,%23,%24,%25,%26,%27,%28,%29,%30,%31,%32,%33,%34,%35,%36,%37,%38,%39,%40,%41,%42,%43,%44,%45,%46,%47,%48,%49,%50,%51,%52,%53,%54,%55,%56,%57,%58,%59,%60,%61,%62,%63,%64,%65,%66,%67,%68,%69,%70,%71,%72,%73,%74,%75,%76,%77,%78,%79,%80,%81,%82,%83,%84,%85,%86,%87,%88,%89,%90,%91,%92,%93,%94,%95,%96,%97,%98,%99,%100,%101,%102,%103,%104,%105,%106,%107,%108,%109,%110,%111,%112,%113,%114,%115,%116,%117,%118,%119,%120,%121,%122,%123,%124,%125,%126,%127}, a, b, p, 1, 1, 0, 1;\n}\n"
    : "+f"(d[0]),"+f"(d[1]),"+f"(d[2]),"+f"(d[3]),"+f"(d[4]),"+f"(d[5]),"+f"(d[6]),"+f"(d[7]),"+f"(d[8]),"+f"(d[9]),"+f"(d[10]),"+f"(d[11]),"+f"(d[12]),"+f"(d[13]),"+f"(d[14]),"+f"(d[15]),"+f"(d[16]),"+f"(d[17]),"+f"(d[18]),"+f"(d[19]),"+f"(d[20]),"+f"(d[21]),"+f"(d[22]),"+f"(d[23]),"+f"(d[24]),"+f"(d[25]),"+f"(d[26]),"+f"(d[27]),"+f"(d[28]),"+f"(d[29]),"+f"(d[30]),"+f"(d[31]),"+f"(d[32]),"+f"(d[33]),"+f"(d[34]),"+f"(d[35]),"+f"(d[36]),"+f"(d[37]),"+f"(d[38]),"+f"(d[39]),"+f"(d[40]),"+f"(d[41]),"+f"(d[42]),"+f"(d[43]),"+f"(d[44]),"+f"(d[45]),"+f"(d[46]),"+f"(d[47]),"+f"(d[48]),"+f"(d[49]),"+f"(d[50]),"+f"(d[51]),"+f"(d[52]),"+f"(d[53]),"+f"(d[54]),"+f"(d[55]),"+f"(d[56]),"+f"(d[57]),"+f"(d[58]),"+f"(d[59]),"+f"(d[60]),"+f"(d[61]),"+f"(d[62]),"+f"(d[63]),"+f"(d[64]),"+f"(d[65]),"+f"(d[66]),"+f"(d[67]),"+f"(d[68]),"+f"(d[69]),"+f"(d[70]),"+f"(d[71]),"+f"(d[72]),"+f"(d[73]),"+f"(d[74]),"+f"(d[75]),"+f"(d[76]),"+f"(d[77]),"+f"(d[78]),"+f"(d[79]),"+f"(d[80]),"+f"(d[81]),"+f"(d[82]),"+f"(d[83]),"+f"(d[84]),"+f"(d[85]),"+f"(d[86]),"+f"(d[87]),"+f"(d[88]),"+f"(d[89]),"+f"(d[90]),"+f"(d[91]),"+f"(d[92]),"+f"(d[93]),"+f"(d[94]),"+f"(d[95]),"+f"(d[96]),"+f"(d[97]),"+f"(d[98]),"+f"(d[99]),"+f"(d[100]),"+f"(d[101]),"+f"(d[102]),"+f"(d[103]),"+f"(d[104]),"+f"(d[105]),"+f"(d[106]),"+f"(d[107]),"+f"(d[108]),"+f"(d[109]),"+f"(d[110]),"+f"(d[111]),"+f"(d[112]),"+f"(d[113]),"+f"(d[114]),"+f"(d[115]),"+f"(d[116]),"+f"(d[117]),"+f"(d[118]),"+f"(d[119]),"+f"(d[120]),"+f"(d[121]),"+f"(d[122]),"+f"(d[123]),"+f"(d[124]),"+f"(d[125]),"+f"(d[126]),"+f"(d[127])
    : "r"(da), "r"(db), "r"(sd), "r"(ha));
}
__device__ __forceinline__ void wgmma_ss_n128(float (&d)[64], uint32_t da, uint32_t ha, uint32_t db, int sd) {
  asm volatile("{\n.reg .pred p;\n.reg .b64 a, b;\nsetp.ne.b32 p, %66, 0;\nmov.b64 a, {%64, %67};\nmov.b64 b, {%65, 0x40000040};\n"
    "wgmma.mma_async.sync.aligned.m64n128k16.f32.bf16.bf16 {%0,%1,%2,%3,%4,%5,%6,%7,%8,%9,%10,%11,%12,%13,%14,%15,%16,%17,%18,%19,%20,%21,%22,%23,%24,%25,%26,%27,%28,%29,%30,%31,%32,%33,%34,%35,%36,%37,%38,%39,%40,%41,%42,%43,%44,%45,%46,%47,%48,%49,%50,%51,%52,%53,%54,%55,%56,%57,%58,%59,%60,%61,%62,%63}, a, b, p, 1, 1, 0, 1;\n}\n"
    : "+f"(d[0]),"+f"(d[1]),"+f"(d[2]),"+f"(d[3]),"+f"(d[4]),"+f"(d[5]),"+f"(d[6]),"+f"(d[7]),"+f"(d[8]),"+f"(d[9]),"+f"(d[10]),"+f"(d[11]),"+f"(d[12]),"+f"(d[13]),"+f"(d[14]),"+f"(d[15]),"+f"(d[16]),"+f"(d[17]),"+f"(d[18]),"+f"(d[19]),"+f"(d[20]),"+f"(d[21]),"+f"(d[22]),"+f"(d[23]),"+f"(d[24]),"+f"(d[25]),"+f"(d[26]),"+f"(d[27]),"+f"(d[28]),"+f"(d[29]),"+f"(d[30]),"+f"(d[31]),"+f"(d[32]),"+f"(d[33]),"+f"(d[34]),"+f"(d[35]),"+f"(d[36]),"+f"(d[37]),"+f"(d[38]),"+f"(d[39]),"+f"(d[40]),"+f"(d[41]),"+f"(d[42]),"+f"(d[43]),"+f"(d[44]),"+f"(d[45]),"+f"(d[46]),"+f"(d[47]),"+f"(d[48]),"+f"(d[49]),"+f"(d[50]),"+f"(d[51]),"+f"(d[52]),"+f"(d[53]),"+f"(d[54]),"+f"(d[55]),"+f"(d[56]),"+f"(d[57]),"+f"(d[58]),"+f"(d[59]),"+f"(d[60]),"+f"(d[61]),"+f"(d[62]),"+f"(d[63])
    : "r"(da), "r"(db), "r"(sd), "r"(ha));
}
__device__ __forceinline__ void wgmma_ss_n40_tt(float (&d)[20], uint32_t da, uint32_t db, int sd) {
  asm volatile("{\n.reg .pred p;\n.reg .b64 a, b;\nsetp.ne.b32 p, %22, 0;\nmov.b64 a, {%20, 0x40000040};\nmov.b64 b, {%21, 0x8};\n"
    "wgmma.mma_async.sync.aligned.m64n40k16.f32.bf16.bf16 {%0,%1,%2,%3,%4,%5,%6,%7,%8,%9,%10,%11,%12,%13,%14,%15,%16,%17,%18,%19}, a, b, p, 1, 1, 1, 1;\n}\n"
    : "+f"(d[0]),"+f"(d[1]),"+f"(d[2]),"+f"(d[3]),"+f"(d[4]),"+f"(d[5]),"+f"(d[6]),"+f"(d[7]),"+f"(d[8]),"+f"(d[9]),"+f"(d[10]),"+f"(d[11]),"+f"(d[12]),"+f"(d[13]),"+f"(d[14]),"+f"(d[15]),"+f"(d[16]),"+f"(d[17]),"+f"(d[18]),"+f"(d[19])
    : "r"(da), "r"(db), "r"(sd));
}
__device__ __forceinline__ void wgmma_ss_n32(float (&d)[16], uint32_t da, uint32_t db, int sd) {
  asm volatile("{\n.reg .pred p;\n.reg .b64 a, b;\nsetp.ne.b32 p, %18, 0;\nmov.b64 a, {%16, 0x40000040};\nmov.b64 b, {%17, 0x80000020};\n"
    "wgmma.mma_async.sync.aligned.m64n32k16.f32.bf16.bf16 {%0,%1,%2,%3,%4,%5,%6,%7,%8,%9,%10,%11,%12,%13,%14,%15}, a, b, p, 1, 1, 0, 1;\n}\n"
    : "+f"(d[0]),"+f"(d[1]),"+f"(d[2]),"+f"(d[3]),"+f"(d[4]),"+f"(d[5]),"+f"(d[6]),"+f"(d[7]),"+f"(d[8]),"+f"(d[9]),"+f"(d[10]),"+f"(d[11]),"+f"(d[12]),"+f"(d[13]),"+f"(d[14]),"+f"(d[15])
    : "r"(da), "r"(db), "r"(sd));
}
__device__ __forceinline__ void wgmma_rs_n40(float (&d)[20], uint32_t a0, uint32_t a1, uint32_t a2, uint32_t a3, uint32_t db, int sd) {
  asm volatile("{\n.reg .pred p;\n.reg .b64 b;\nsetp.ne.b32 p, %25, 0;\nmov.b64 b, {%24, 0x10};\n"
    "wgmma.mma_async.sync.aligned.m64n40k16.f32.bf16.bf16 {%0,%1,%2,%3,%4,%5,%6,%7,%8,%9,%10,%11,%12,%13,%14,%15,%16,%17,%18,%19}, {%20,%21,%22,%23}, b, p, 1, 1, 1;\n}\n"
    : "+f"(d[0]),"+f"(d[1]),"+f"(d[2]),"+f"(d[3]),"+f"(d[4]),"+f"(d[5]),"+f"(d[6]),"+f"(d[7]),"+f"(d[8]),"+f"(d[9]),"+f"(d[10]),"+f"(d[11]),"+f"(d[12]),"+f"(d[13]),"+f"(d[14]),"+f"(d[15]),"+f"(d[16]),"+f"(d[17]),"+f"(d[18]),"+f"(d[19])
    : "r"(a0), "r"(a1), "r"(a2), "r"(a3), "r"(db), "r"(sd));
}
__device__ __forceinline__ void wgmma_r1_n256(float (&d)[128], uint32_t da, uint32_t db, int sd) {
  asm volatile("{\n.reg .pred p;\n.reg .b64 a, b;\nsetp.ne.b32 p, %130, 0;\nmov.b64 a, {%128, 0x8};\nmov.b64 b, {%129, 0x6};\n"
    "wgmma.mma_async.sync.aligned.m64n256k16.f32.bf16.bf16 {%0,%1,%2,%3,%4,%5,%6,%7,%8,%9,%10,%11,%12,%13,%14,%15,%16,%17,%18,%19,%20,%21,%22,%23,%24,%25,%26,%27,%28,%29,%30,%31,%32,%33,%34,%35,%36,%37,%38,%39,%40,%41,%42,%43,%44,%45,%46,%47,%48,%49,%50,%51,%52,%53,%54,%55,%56,%57,%58,%59,%60,%61,%62,%63,%64,%65,%66,%67,%68,%69,%70,%71,%72,%73,%74,%75,%76,%77,%78,%79,%80,%81,%82,%83,%84,%85,%86,%87,%88,%89,%90,%91,%92,%93,%94,%95,%96,%97,%98,%99,%100,%101,%102,%103,%104,%105,%106,%107,%108,%109,%110,%111,%112,%113,%114,%115,%116,%117,%118,%119,%120,%121,%122,%123,%124,%125,%126,%127}, a, b, p, 1, 1, 0, 1;\n}\n"
    : "+f"(d[0]),"+f"(d[1]),"+f"(d[2]),"+f"(d[3]),"+f"(d[4]),"+f"(d[5]),"+f"(d[6]),"+f"(d[7]),"+f"(d[8]),"+f"(d[9]),"+f"(d[10]),"+f"(d[11]),"+f"(d[12]),"+f"(d[13]),"+f"(d[14]),"+f"(d[15]),"+f"(d[16]),"+f"(d[17]),"+f"(d[18]),"+f"(d[19]),"+f"(d[20]),"+f"(d[21]),"+f"(d[22]),"+f"(d[23]),"+f"(d[24]),"+f"(d[25]),"+f"(d[26]),"+f"(d[27]),"+f"(d[28]),"+f"(d[29]),"+f"(d[30]),"+f"(d[31]),"+f"(d[32]),"+f"(d[33]),"+f"(d[34]),"+f"(d[35]),"+f"(d[36]),"+f"(d[37]),"+f"(d[38]),"+f"(d[39]),"+f"(d[40]),"+f"(d[41]),"+f"(d[42]),"+f"(d[43]),"+f"(d[44]),"+f"(d[45]),"+f"(d[46]),"+f"(d[47]),"+f"(d[48]),"+f"(d[49]),"+f"(d[50]),"+f"(d[51]),"+f"(d[52]),"+f"(d[53]),"+f"(d[54]),"+f"(d[55]),"+f"(d[56]),"+f"(d[57]),"+f"(d[58]),"+f"(d[59]),"+f"(d[60]),"+f"(d[61]),"+f"(d[62]),"+f"(d[63]),"+f"(d[64]),"+f"(d[65]),"+f"(d[66]),"+f"(d[67]),"+f"(d[68]),"+f"(d[69]),"+f"(d[70]),"+f"(d[71]),"+f"(d[72]),"+f"(d[73]),"+f"(d[74]),"+f"(d[75]),"+f"(d[76]),"+f"(d[77]),"+f"(d[78]),"+f"(d[79]),"+f"(d[80]),"+f"(d[81]),"+f"(d[82]),"+f"(d[83]),"+f"(d[84]),"+f"(d[85]),"+f"(d[86]),"+f"(d[87]),"+f"(d[88]),"+f"(d[89]),"+f"(d[90]),"+f"(d[91]),"+f"(d[92]),"+f"(d[93]),"+f"(d[94]),"+f"(d[95]),"+f"(d[96]),"+f"(d[97]),"+f"(d[98]),"+f"(d[99]),"+f"(d[100]),"+f"(d[101]),"+f"(d[102]),"+f"(d[103]),"+f"(d[104]),"+f"(d[105]),"+f"(d[106]),"+f"(d[107]),"+f"(d[108]),"+f"(d[109]),"+f"(d[110]),"+f"(d[111]),"+f"(d[112]),"+f"(d[113]),"+f"(d[114]),"+f"(d[115]),"+f"(d[116]),"+f"(d[117]),"+f"(d[118]),"+f"(d[119]),"+f"(d[120]),"+f"(d[121]),"+f"(d[122]),"+f"(d[123]),"+f"(d[124]),"+f"(d[125]),"+f"(d[126]),"+f"(d[127])
    : "r"(da), "r"(db), "r"(sd));
}
__device__ __forceinline__ void wgmma_r1_n128(float (&d)[64], uint32_t da, uint32_t db, int sd) {
  asm volatile("{\n.reg .pred p;\n.reg .b64 a, b;\nsetp.ne.b32 p, %66, 0;\nmov.b64 a, {%64, 0x8};\nmov.b64 b, {%65, 0x6};\n"
    "wgmma.mma_async.sync.aligned.m64n128k16.f32.bf16.bf16 {%0,%1,%2,%3,%4,%5,%6,%7,%8,%9,%10,%11,%12,%13,%14,%15,%16,%17,%18,%19,%20,%21,%22,%23,%24,%25,%26,%27,%28,%29,%30,%31,%32,%33,%34,%35,%36,%37,%38,%39,%40,%41,%42,%43,%44,%45,%46,%47,%48,%49,%50,%51,%52,%53,%54,%55,%56,%57,%58,%59,%60,%61,%62,%63}, a, b, p, 1, 1, 0, 1;\n}\n"
    : "+f"(d[0]),"+f"(d[1]),"+f"(d[2]),"+f"(d[3]),"+f"(d[4]),"+f"(d[5]),"+f"(d[6]),"+f"(d[7]),"+f"(d[8]),"+f"(d[9]),"+f"(d[10]),"+f"(d[11]),"+f"(d[12]),"+f"(d[13]),"+f"(d[14]),"+f"(d[15]),"+f"(d[16]),"+f"(d[17]),"+f"(d[18]),"+f"(d[19]),"+f"(d[20]),"+f"(d[21]),"+f"(d[22]),"+f"(d[23]),"+f"(d[24]),"+f"(d[25]),"+f"(d[26]),"+f"(d[27]),"+f"(d[28]),"+f"(d[29]),"+f"(d[30]),"+f"(d[31]),"+f"(d[32]),"+f"(d[33]),"+f"(d[34]),"+f"(d[35]),"+f"(d[36]),"+f"(d[37]),"+f"(d[38]),"+f"(d[39]),"+f"(d[40]),"+f"(d[41]),"+f"(d[42]),"+f"(d[43]),"+f"(d[44]),"+f"(d[45]),"+f"(d[46]),"+f"(d[47]),"+f"(d[48]),"+f"(d[49]),"+f"(d[50]),"+f"(d[51]),"+f"(d[52]),"+f"(d[53]),"+f"(d[54]),"+f"(d[55]),"+f"(d[56]),"+f"(d[57]),"+f"(d[58]),"+f"(d[59]),"+f"(d[60]),"+f"(d[61]),"+f"(d[62]),"+f"(d[63])
    : "r"(da), "r"(db), "r"(sd));
}

__device__ __forceinline__ uint32_t smem_u32(const void* p) { return (uint32_t)__cvta_generic_to_shared(p); }
__device__ __forceinline__ void mbar_init(uint32_t bar, uint32_t cnt) { asm volatile("mbarrier.init.shared::cta.b64 [%0], %1;" ::"r"(bar), "r"(cnt)); }
__device__ __forceinline__ void mbar_expect_tx(uint32_t bar, uint32_t bytes) { asm volatile("mbarrier.arrive.expect_tx.shared::cta.b64 _, [%0], %1;" ::"r"(bar), "r"(bytes) : "memory"); }
__device__ __forceinline__ void mbar_arrive(uint32_t bar) { asm volatile("mbarrier.arrive.shared::cta.b64 _, [%0];" ::"r"(bar) : "memory"); }
__device__ __forceinline__ void mbar_arrive_n(uint32_t bar, uint32_t n) { asm volatile("mbarrier.arrive.shared::cta.b64 _, [%0], %1;" ::"r"(bar), "r"(n) : "memory"); }
__device__ __forceinline__ void mbar_wait(uint32_t bar, uint32_t parity) {
  asm volatile("{\n.reg .pred p;\nLAB_WAIT:\nmbarrier.try_wait.parity.shared::cta.b64 p, [%0], %1;\n@p bra DONE;\nbra LAB_WAIT;\nDONE:\n}" ::"r"(bar), "r"(parity) : "memory");
}
__device__ __forceinline__ void mbar_wait2(uint32_t a, uint32_t pa, uint32_t b, uint32_t pb) {
  asm volatile("{\n.reg .pred p, q;\nLAB_WAIT:\nmbarrier.try_wait.parity.shared::cta.b64 p, [%0], %1;\nmbarrier.try_wait.parity.shared::cta.b64 q, [%2], %3;\n"
               "and.pred p, p, q;\n@p bra DONE;\nbra LAB_WAIT;\nDONE:\n}" ::"r"(a), "r"(pa), "r"(b), "r"(pb) : "memory");
}
__device__ __forceinline__ void mbar_wait3(uint32_t a, uint32_t pa, uint32_t b, uint32_t pb) {
  asm volatile("{\n.reg .pred p, q, r;\nLAB_WAIT:\nmbarrier.try_wait.parity.shared::cta.b64 p, [%0], %1;\nmbarrier.try_wait.parity.shared::cta.b64 q, [%2], %3;\n"
               "mbarrier.try_wait.parity.shared::cta.b64 r, [%2+8], %3;\nand.pred p, p, q;\nand.pred p, p, r;\n@p bra DONE;\nbra LAB_WAIT;\nDONE:\n}" ::"r"(a), "r"(pa), "r"(b), "r"(pb) : "memory");
}
__device__ __forceinline__ bool mbar_probe2(uint32_t a, uint32_t pa, uint32_t b, uint32_t pb) {
  uint32_t ok;
  asm volatile("{\n.reg .pred p, q;\nmbarrier.test_wait.parity.shared::cta.b64 p, [%1], %2;\nmbarrier.test_wait.parity.shared::cta.b64 q, [%3], %4;\n"
               "and.pred p, p, q;\nselp.u32 %0, 1, 0, p;\n}" : "=r"(ok) : "r"(a), "r"(pa), "r"(b), "r"(pb) : "memory");
  return ok != 0;
}
__device__ __forceinline__ void tma_load_3d(uint32_t dst, const CUtensorMap* tm, uint32_t bar, int c0, int c1, int c2) {
  asm volatile("cp.async.bulk.tensor.3d.shared::cluster.global.mbarrier::complete_tx::bytes [%0], [%1, {%3, %4, %5}], [%2];"
               ::"r"(dst), "l"(tm), "r"(bar), "r"(c0), "r"(c1), "r"(c2) : "memory");
}
__device__ __forceinline__ void tma_load_2d(uint32_t dst, const CUtensorMap* tm, uint32_t bar, int c0, int c1) {
  asm volatile("cp.async.bulk.tensor.2d.shared::cluster.global.mbarrier::complete_tx::bytes [%0], [%1, {%3, %4}], [%2];"
               ::"r"(dst), "l"(tm), "r"(bar), "r"(c0), "r"(c1) : "memory");
}
__device__ __forceinline__ void tma_load_w(uint32_t dst, const CUtensorMap* tm, uint32_t bar, int col, int kb) {
#pragma unroll
  for (int q = 0; q < 2; q++)
    asm volatile("cp.async.bulk.tensor.5d.shared::cluster.global.mbarrier::complete_tx::bytes [%0], [%1, {%3, %4, %4, %4, %5}], [%2];"
                 ::"r"(dst + q * 8192), "l"(tm), "r"(bar), "r"(col + q * 64), "r"(0), "r"(2 * kb) : "memory");
}
__device__ __forceinline__ void tma_prefetch_w(const CUtensorMap* tm, int col, int kb) {
#pragma unroll
  for (int q = 0; q < 2; q++)
    asm volatile("cp.async.bulk.prefetch.tensor.5d.L2.global [%0, {%1, %2, %2, %2, %3}];" ::"l"(tm), "r"(col + q * 64), "r"(0), "r"(2 * kb) : "memory");
}
__device__ __forceinline__ void bulk_load(uint32_t dst, const void* g, uint32_t bytes, uint32_t bar) {
  asm volatile("cp.async.bulk.shared::cluster.global.mbarrier::complete_tx::bytes [%0], [%1], %2, [%3];" ::"r"(dst), "l"(g), "r"(bytes), "r"(bar) : "memory");
}
__device__ __forceinline__ void prefetch_map(const CUtensorMap* tm) { asm volatile("prefetch.tensormap [%0];" ::"l"(tm) : "memory"); }
__device__ __forceinline__ void fence_async_smem() { asm volatile("fence.proxy.async.shared::cta;" ::: "memory"); }
__device__ __forceinline__ void fence_async_global() { asm volatile("fence.proxy.async.global;" ::: "memory"); }
__device__ __forceinline__ void fence_gpu() { asm volatile("fence.release.gpu;" ::: "memory"); }
__device__ __forceinline__ void st_flag(unsigned* p, unsigned v) { asm volatile("st.relaxed.gpu.global.u32 [%0], %1;" ::"l"(p), "r"(v) : "memory"); }
__device__ __forceinline__ unsigned ld_flag(const unsigned* p) { unsigned v; asm volatile("ld.relaxed.gpu.global.u32 %0, [%1];" : "=r"(v) : "l"(p) : "memory"); return v; }
__device__ __forceinline__ uint4 ldcg4(const void* p) { uint4 v; asm volatile("ld.global.cg.v4.u32 {%0,%1,%2,%3}, [%4];" : "=r"(v.x), "=r"(v.y), "=r"(v.z), "=r"(v.w) : "l"(p)); return v; }
__device__ __forceinline__ uint4 ld_pkt(const uint4* p) {
  uint4 v; asm volatile("{\n.reg .b128 t;\nld.relaxed.gpu.global.b128 t, [%4];\nmov.b128 {%0,%1,%2,%3}, t;\n}" : "=r"(v.x), "=r"(v.y), "=r"(v.z), "=r"(v.w) : "l"(p) : "memory"); return v;
}
__device__ __forceinline__ void st_pkt(uint4* p, uint32_t a, uint32_t b, uint32_t c, uint32_t tag) {
  asm volatile("{\n.reg .b128 t;\nmov.b128 t, {%1,%2,%3,%4};\nst.relaxed.gpu.global.b128 [%0], t;\n}" ::"l"(p), "r"(a), "r"(b), "r"(c), "r"(tag) : "memory");
}
__device__ __forceinline__ void st_v4(uint4* p, uint32_t a, uint32_t b, uint32_t c, uint32_t d) { asm volatile("st.relaxed.gpu.global.v4.u32 [%0], {%1,%2,%3,%4};" ::"l"(p), "r"(a), "r"(b), "r"(c), "r"(d) : "memory"); }
__device__ __forceinline__ void stg128(uint4* p, uint4 v) { asm volatile("st.global.v4.u32 [%0], {%1,%2,%3,%4};" ::"l"(p), "r"(v.x), "r"(v.y), "r"(v.z), "r"(v.w) : "memory"); }
__device__ __forceinline__ void sts32(uint32_t addr, uint32_t a) { asm volatile("st.shared.u32 [%0], %1;" ::"r"(addr), "r"(a) : "memory"); }
__device__ __forceinline__ void sts64(uint32_t addr, uint32_t a, uint32_t b) { asm volatile("st.shared.v2.u32 [%0], {%1,%2};" ::"r"(addr), "r"(a), "r"(b) : "memory"); }
__device__ __forceinline__ uint32_t mul2(uint32_t a, uint32_t b) { uint32_t r; asm("mul.rn.bf16x2 %0, %1, %2;" : "=r"(r) : "r"(a), "r"(b)); return r; }
__device__ __forceinline__ uint32_t add2(uint32_t a, uint32_t b) { uint32_t r; asm("add.rn.bf16x2 %0, %1, %2;" : "=r"(r) : "r"(a), "r"(b)); return r; }
__device__ __forceinline__ bool elect() {
  uint32_t p; asm volatile("{\n.reg .pred q;\nelect.sync _|q, 0xffffffff;\nselp.u32 %0, 1, 0, q;\n}" : "=r"(p)); return p != 0;
}
__device__ __forceinline__ void wgmma_fence() { asm volatile("wgmma.fence.sync.aligned;" ::: "memory"); }
__device__ __forceinline__ void wgmma_commit() { asm volatile("wgmma.commit_group.sync.aligned;" ::: "memory"); }
template <int N> __device__ __forceinline__ void wgmma_wait() { asm volatile("wgmma.wait_group.sync.aligned %0;" ::"n"(N) : "memory"); }
template <int N> __device__ __forceinline__ void fence_regs(float (&d)[N]) {
#pragma unroll
  for (int i = 0; i < N; i++) asm volatile("" : "+f"(d[i])::"memory");
}
template <int R> __device__ __forceinline__ void reg_alloc() { asm volatile("setmaxnreg.inc.sync.aligned.u32 %0;" ::"n"(R)); }
template <int R> __device__ __forceinline__ void reg_dealloc() { asm volatile("setmaxnreg.dec.sync.aligned.u32 %0;" ::"n"(R)); }
__device__ __forceinline__ void wg_bar(int w) { asm volatile("bar.sync %0, 128;" ::"r"(w + 1) : "memory"); }
__device__ __forceinline__ constexpr uint32_t desc_lo(uint32_t addr, uint32_t lbo) { return (addr >> 4) + ((lbo >> 4) << 16); }
__device__ __forceinline__ uint32_t pack2(float lo, float hi) { uint32_t r; asm("cvt.rn.bf16x2.f32 %0, %1, %2;" : "=r"(r) : "f"(hi), "f"(lo)); return r; }
__device__ __forceinline__ float lo16(uint32_t v) { return __uint_as_float(v << 16); }
__device__ __forceinline__ float hi16(uint32_t v) { return __uint_as_float(v & 0xFFFF0000u); }
__device__ __forceinline__ float ex2(float x) { float r; asm("ex2.approx.ftz.f32 %0, %1;" : "=f"(r) : "f"(x)); return r; }
__device__ __forceinline__ float rcp(float x) { float r; asm("rcp.approx.ftz.f32 %0, %1;" : "=f"(r) : "f"(x)); return r; }
__device__ __forceinline__ uint32_t movm(uint32_t a) { uint32_t d; asm volatile("movmatrix.sync.aligned.m8n8.trans.b16 %0, %1;" : "=r"(d) : "r"(a)); return d; }
__device__ __forceinline__ void stsm4(uint32_t addr, uint32_t a, uint32_t b, uint32_t c, uint32_t d) {
  asm volatile("stmatrix.sync.aligned.m8n8.x4.shared.b16 [%0], {%1,%2,%3,%4};" ::"r"(addr), "r"(a), "r"(b), "r"(c), "r"(d) : "memory");
}
__device__ __forceinline__ void ldsm4(uint32_t addr, uint32_t (&r)[4]) {
  asm volatile("ldmatrix.sync.aligned.m8n8.x4.shared.b16 {%0,%1,%2,%3}, [%4];" : "=r"(r[0]), "=r"(r[1]), "=r"(r[2]), "=r"(r[3]) : "r"(addr) : "memory");
}
__device__ __forceinline__ void sts128(uint32_t addr, uint32_t a, uint32_t b, uint32_t c, uint32_t d) {
  asm volatile("st.shared.v4.u32 [%0], {%1,%2,%3,%4};" ::"r"(addr), "r"(a), "r"(b), "r"(c), "r"(d) : "memory");
}
__device__ __forceinline__ void lds128(uint32_t addr, uint32_t& a, uint32_t& b, uint32_t& c, uint32_t& d) {
  asm volatile("ld.shared.v4.u32 {%0,%1,%2,%3}, [%4];" : "=r"(a), "=r"(b), "=r"(c), "=r"(d) : "r"(addr) : "memory");
}
__device__ __forceinline__ float lds32f(uint32_t addr) { float v; asm volatile("ld.shared.f32 %0, [%1];" : "=f"(v) : "r"(addr) : "memory"); return v; }
__device__ __forceinline__ float2 lds64f(uint32_t addr) { float2 v; asm volatile("ld.shared.v2.f32 {%0,%1}, [%2];" : "=f"(v.x), "=f"(v.y) : "r"(addr) : "memory"); return v; }
__device__ __forceinline__ void mma16816(float (&d)[4], uint32_t a0, uint32_t a1, uint32_t a2, uint32_t a3, uint32_t b0, uint32_t b1) {
  asm("mma.sync.aligned.m16n8k16.row.col.f32.bf16.bf16.f32 {%0,%1,%2,%3}, {%4,%5,%6,%7}, {%8,%9}, {%0,%1,%2,%3};"
      : "+f"(d[0]), "+f"(d[1]), "+f"(d[2]), "+f"(d[3]) : "r"(a0), "r"(a1), "r"(a2), "r"(a3), "r"(b0), "r"(b1));
}
__device__ __forceinline__ void mma1688(float (&d)[4], uint32_t a0, uint32_t a1, uint32_t b0) {
  asm("mma.sync.aligned.m16n8k8.row.col.f32.bf16.bf16.f32 {%0,%1,%2,%3}, {%4,%5}, {%6}, {%0,%1,%2,%3};"
      : "+f"(d[0]), "+f"(d[1]), "+f"(d[2]), "+f"(d[3]) : "r"(a0), "r"(a1), "r"(b0));
}

__device__ __forceinline__ float qsum(float v) { v += __shfl_xor_sync(0xffffffffu, v, 1); v += __shfl_xor_sync(0xffffffffu, v, 2); return v; }

constexpr int NCTA = 132;
#define NB_ 6
#define NA_ 5
constexpr int NB = NB_;
constexpr int NA = NA_;
constexpr uint32_t SLOT = 16384;
constexpr uint32_t SB = 1024;
constexpr uint32_t OFF_B = 0;
constexpr uint32_t OFF_A = NB * SLOT;
constexpr uint32_t OFF_S = OFF_A + NA * SLOT;
constexpr uint32_t OFF_T = OFF_S + 20480;
constexpr uint32_t OFF_CS = OFF_T + 24576;
constexpr uint32_t OFF_MR = OFF_CS + 4640;
constexpr uint32_t OFF_BAR = OFF_MR + 512;
constexpr uint32_t OFF_MA = OFF_S, OFF_MB = OFF_CS - 2048;
constexpr uint32_t BAR_FULLB = OFF_BAR;
constexpr uint32_t BAR_FULLA = BAR_FULLB + 64;
constexpr uint32_t BAR_EMPTYB = BAR_FULLA + 64;
constexpr uint32_t BAR_EMPTYA = BAR_EMPTYB + 64;
constexpr uint32_t BAR_SIGP = BAR_EMPTYA + 64;
constexpr uint32_t BAR_SIGT = BAR_SIGP + 24;
constexpr uint32_t BAR_STAT = BAR_SIGP + 64;
constexpr uint32_t BAR_HALO = BAR_STAT + 16;
constexpr uint32_t BAR_CS = BAR_HALO + 8;
constexpr uint32_t BAR_WPHI = BAR_CS + 16;
constexpr uint32_t BAR_KV = BAR_WPHI + 8;
constexpr uint32_t BAR_STG = BAR_KV + 16;
constexpr uint32_t BAR_EPOCH = BAR_STG + 48;
constexpr uint32_t BAR_LAND = OFF_BAR + 7 * 64;
constexpr uint32_t OFF_EPOCH = OFF_BAR + 8 * 64;
static_assert(BAR_EPOCH < BAR_LAND, "barriers");
constexpr uint32_t SMEM_BYTES = OFF_EPOCH + 8;
static_assert(SMEM_BYTES <= 232448 && NB % 2 == 0 && NB <= 8 && NA <= 6, "smem");

#define CREGS 224
#define PREGS 56
#define PF1 19
#define PF2 21
#define PRE_A 2
#define PRE_B 4
#define CSB 4
#define CSNEED 0xF001u
#define XR 1
#define PS0 1
#define PS1 3
#define PSW 0
#define SD 1000
#define KSPLIT 12
#define KEEP 16
#define NJ 3
#define KSL 1000
#define PSL 0
#define KVS 12
#define D2 2000
#define D3 1500
#define G0 50
#define MAP 3
#define PMAP 0x76321450u
#define ZO 0
#define XA 3
#define XS 1
#define CP 500
#define CD 0
#define S0 500
#define NS 2
#define XO 0
#define SW 2
#define SA 1
#define SB_ 4
#define XD 250
#define ND0 1
#define KC 8
#define CO 0
#define SE 500
#define PD 0
#define XD0 XD
#define XDA XD
#define XDB XD
#define DEFER 3
#define DEFL 2
#define TSK 3
#define TSL 3
constexpr int NTHREADS = 384;

struct Params {
  CUtensorMap mx;
  CUtensorMap mw[3];
  CUtensorMap mwo[2];
  CUtensorMap mcs[2];
  CUtensorMap mwphi;
  uint4* out;
};

#define XBUF(L) 1
__device__ __align__(256) uint4 g_img[XBUF(3) + 1][16][16][1024];
__device__ __forceinline__ uint32_t img_code(bool isx, int L) { return isx ? (L & 1) | (L & 2) << 15 : ~L & 1; }
__device__ __forceinline__ uint32_t img_mask(bool isx) { return isx ? 0x10001u : 1u; }
__device__ __align__(256) uint4 g_wf[2][8][16][1024];
__device__ __align__(256) uint4 g_stats[16][2][8][32];
__device__ __align__(256) uint4 g_halo[16][8][2][256];
__device__ __align__(256) float g_cs[2][2][3072];
__device__ __align__(256) uint4 g_kvpart[8][16][2][544];
__device__ __align__(256) uint4 g_kvfin[8][16][80];
__device__ __align__(256) unsigned g_hint[16][32];
__device__ __align__(256) unsigned g_jflag[3][8][32];
__device__ unsigned g_ctr;
__device__ __forceinline__ unsigned vblock() {
  unsigned s;
  asm volatile("mov.u32 %0, %%smid;" : "=r"(s));
  const unsigned r = s & 1;
  s >>= 1;
  const unsigned t = s - 32, q = (t * 37) >> 8;
  const unsigned hi = s < 60 ? 12 + (t - 7 * q) * 8 + q : (s < 62 ? s + 4 : s - 58);
  unsigned b = 2 * (s < 32 ? (s & 7) * 8 + (s >> 3) : hi) + r;
  if (b < 128) b = (b & 15) | ((PMAP >> ((b >> 4) * 4)) & 7) << 4;
  if (s >= 62) b = 8 + 4 * r + s - 62;
  unsigned n;
  asm volatile("mov.u32 %0, %%nsmid;" : "=r"(n));
  return __shfl_sync(0xffffffffu, n == NCTA ? b : blockIdx.x, 0);
}
#define TS(who, id) do {} while (0)
#define TSW(id) do {} while (0)

#define TSH(id) do {} while (0)
#define TSMASK 0xFFFF
#define TSL_(a) do { if ((TSMASK >> (a)) & 1) TSW((a) + L * 12); } while (0)
__device__ __forceinline__ int cta_m(unsigned b) { return ((b >> 2) & 12) | (b & 3); }
__device__ __forceinline__ int cta_j(unsigned b) { return ((b >> 2) & 3) | ((b >> 4) & 4); }
struct Ring { uint32_t s, ph; };
template <int N> __device__ __forceinline__ void adv(Ring& r) { if (++r.s == N) { r.s = 0; r.ph ^= 1; } }
template <int N> __device__ __forceinline__ void rewind2(Ring& r) { if (r.s < 2) { r.s += N - 2; r.ph ^= 1; } else r.s -= 2; }
__device__ __forceinline__ int other_tile(int t, int j) { return (t == (j | 4) ? 7 : t) ^ (~j & 4); }
__device__ __forceinline__ int o_order(int i, int j) {
  if (i < 2) return 2 * j + i;
  const int odd = i >= 9;
  return 2 * other_tile(i - 2 - 7 * odd, j) + odd;
}
__device__ __forceinline__ int kv_order(int i, int j, int L) { return L > 0 ? o_order(i, j) : (i + 14 + 2 * (j & 4)) & 15; }

__device__ __forceinline__ unsigned poll_flags(const unsigned* f, int n, unsigned need, unsigned tag) {
  const int lane = threadIdx.x & 31;
  unsigned mask; int it = 0;
  do {
    unsigned v = lane < n ? ld_flag(f + lane) : 0u;
    mask = __ballot_sync(0xffffffffu, lane < n && (int)(v - tag) >= 0);
    if (++it > (1 << 22)) __trap();
  } while ((mask & need) != need);
  fence_async_global();
  return mask;
}
template <bool WAIT = true>
__device__ __forceinline__ unsigned get_tag(uint32_t sb) {
  if (WAIT) mbar_wait(sb + BAR_EPOCH, 0);
  unsigned t; asm volatile("ld.shared.u32 %0, [%1];" : "=r"(t) : "r"(sb + OFF_EPOCH) : "memory");
  return t;
}

__device__ __forceinline__ int lane_id() { int l; asm volatile("mov.u32 %0, %%laneid;" : "=r"(l)); return l; }
__device__ __forceinline__ unsigned seq4(unsigned tag, int L) { return 8u | ((tag & 1u) << 2) | (unsigned)L; }
constexpr float LOG2E = 1.4426950408889634f;

__device__ __forceinline__ float bb_fence(int never, const void* p = &g_ctr, uint32_t keep = 0) {
  while (never < 0) never = ld_flag((const unsigned*)p) + keep;
  return __int_as_float(never >> 30);
}
__device__ __forceinline__ uint32_t solid(uint32_t v) { return __shfl_sync(0xffffffffu, v, threadIdx.x & 31); }
template <class T> __device__ __forceinline__ T* solid(T* p) { return (T*)__shfl_sync(0xffffffffu, (unsigned long long)p, threadIdx.x & 31); }
constexpr uint32_t HA128 = 0x40000040u, HA64 = 0x80000040u;
struct Ctx {
  static constexpr uint32_t sb = SB;
  uint32_t ab, da0;
  int w, warp, lane, g, c;
  int goff;
  __device__ __forceinline__ int m() const { return goff >> 14; }
  __device__ __forceinline__ int j() const { return (goff >> 4) & 7; }
  bool elected;
  Ring ra, rb;
  uint32_t pa, pb;
  uint32_t ha, k2;
  uint32_t mrow, mxor, mhi;
  __device__ __forceinline__ uint32_t aslot(uint32_t s) const { return ab + s * SLOT; }
  __device__ __forceinline__ uint32_t fullA(uint32_t s) const { return sb + BAR_FULLA + s * 8; }
  __device__ __forceinline__ uint32_t fullB(uint32_t s) const { return sb + BAR_FULLB + s * 8; }
  __device__ __forceinline__ void releaseA(uint32_t s) const { if (elected) mbar_arrive(sb + BAR_EMPTYA + s * 8); }
  __device__ __forceinline__ void releaseB(uint32_t s) const { if (elected) mbar_arrive(sb + BAR_EMPTYB + s * 8); }
  __device__ __forceinline__ uint32_t maddr(uint32_t tile, uint32_t ch) const { return tile + mrow + (((ch + mhi) ^ mxor) << 4); }
  __device__ __forceinline__ uint32_t oo() const { return warp * 128 + g * 4 + (c ^ (g >> 1)); }
  __device__ __forceinline__ uint4* img(int b, int hp) const { return ip + (b * 256 + hp) * 1024; }
  uint4* ip;
  uint32_t so;
  __device__ __forceinline__ uint32_t held(int i) const { return ra.s + i < 2 ? ra.s + i + NA - 2 : ra.s + i - 2; }
};

template <int N, bool FIRST, bool O = true>
__device__ __forceinline__ void gemm_issue(float (&acc)[N / 2], Ctx& x, bool ready = false) {
  if (!ready) {
    if (N == 256) mbar_wait3(x.fullA(x.ra.s), x.ra.ph, x.fullB(x.rb.s), x.rb.ph);
    else mbar_wait2(x.fullA(x.ra.s), x.ra.ph, x.fullB(x.rb.s), x.rb.ph);
  }
  const uint32_t da = x.da0 + x.ra.s * (SLOT / 16), db = desc_lo(SB + OFF_B, 8192) + x.rb.s * (SLOT / 16);
  wgmma_fence();
#pragma unroll
  for (int k = 0; k < 4; k++) {
    const uint32_t a = da + (k >> 1) * (O ? 32 : x.k2) + (k & 1) * 2, ha = O ? HA64 : x.ha;
    if constexpr (N == 256) wgmma_ss_n256(acc, a, ha, db + 128 * k, !(FIRST && k == 0));
    else wgmma_ss_n128(acc, a, ha, db + 128 * k, !(FIRST && k == 0));
  }
  wgmma_commit();
}
template <int N>
__device__ __forceinline__ void gemm_next(Ctx& x) {
  x.pa = x.ra.s; x.pb = x.rb.s;
  if (N == 256) x.rb.s++;
  adv<NA>(x.ra); adv<NB>(x.rb);
}
template <int N>
__device__ __forceinline__ void gemm_release(Ctx& x, bool relA) {
  if (relA) x.releaseA(x.pa);
  x.releaseB(x.pb);
  if (N == 256) x.releaseB(x.pb + 1);
}
template <int N>
__device__ __forceinline__ void gemm_retire(Ctx& x, bool relA) { wgmma_wait<1>(); gemm_release<N>(x, relA); gemm_next<N>(x); }
template <bool O = true>
__device__ __forceinline__ void gemm_run(float (&acc)[64], Ctx& x, int n, int hold, int n4 = 0) {
  bool ready = false;
#pragma unroll 1
  for (; n > 0; n--) {
    gemm_issue<128, false, O>(acc, x, ready);
    const uint32_t pa = x.pa, pb = x.pb;
    gemm_next<128>(x);
    ready = mbar_probe2(x.fullA(x.ra.s), x.ra.ph, x.fullB(x.rb.s), x.rb.ph);
    wgmma_wait<1>();
    if (n > hold) x.releaseA(pa);
    x.releaseB(pb);
  }
}
__device__ __forceinline__ void gemm_end(float (&acc)[64], Ctx& x) { wgmma_wait<0>(); fence_regs(acc); gemm_release<128>(x, false); }

__device__ __forceinline__ void rows_load(uint4* r, uint32_t tile, const Ctx& x) {
#pragma unroll
  for (int q = 0; q < 4; q++) {
    const uint32_t row = x.warp * 16 + 4 * q + (x.lane >> 3);
    lds128(tile + row * 128 + (((x.lane & 7) ^ (row & 7)) << 4), r[q].x, r[q].y, r[q].z, r[q].w);
  }
}
__device__ __forceinline__ void rows_store(const uint4* r, uint4* g) {
#pragma unroll
  for (int q = 0; q < 4; q++) stg128(g + q * 1024, r[q]);
}
__device__ __forceinline__ void publish(int id, const Ctx& x) { __syncwarp(); if (x.lane == 0) mbar_arrive(x.sb + BAR_SIGP + id * 8); }
__device__ __forceinline__ uint32_t img_tag(uint32_t v, bool isx, int L, const Ctx& x) {
  const uint32_t mk = ((x.lane ^ (x.warp * 4)) & 7) ? 0u : img_mask(isx);
  return (v & ~mk) | (img_code(isx, L) & mk);
}
__device__ __forceinline__ void img_tag(uint4 (&r)[4], bool isx, int L, const Ctx& x) {
#pragma unroll
  for (int q = 0; q < 4; q++) { uint32_t& v = q == 0 ? r[q].x : (q == 1 ? r[q].y : (q == 2 ? r[q].z : r[q].w)); v = img_tag(v, isx, L, x); }
}
__device__ __forceinline__ void img_store(const uint4 (&r)[4], uint4* g) {
#pragma unroll
  for (int q = 0; q < 4; q++) stg128(g + q * 32, r[q]);
}
__device__ __forceinline__ void img_sts(const uint4 (&r)[4], uint32_t tile, const Ctx& x) {
#pragma unroll
  for (int q = 0; q < 4; q++) sts128(tile + x.so + q * 512, r[q].x, r[q].y, r[q].z, r[q].w);
}
__device__ __forceinline__ void img_load(uint32_t (&v)[16], uint32_t tile, const Ctx& x) {
#pragma unroll
  for (int q = 0; q < 4; q++) lds128(tile + x.so + q * 512, v[4 * q], v[4 * q + 1], v[4 * q + 2], v[4 * q + 3]);
}
__device__ __forceinline__ void img_unpack(float* a, const uint32_t (&v)[16]) {
#pragma unroll
  for (int q = 0; q < 16; q++) { a[4 * (q & 7) + 2 * (q >> 3)] = lo16(v[q]); a[4 * (q & 7) + 2 * (q >> 3) + 1] = hi16(v[q]); }
}

template <int N>
__device__ __forceinline__ void stats_acc(const float* a, float (&t)[4]) {
#pragma unroll
  for (int i = 0; i < N; i++) { t[i & 2] += a[i]; t[(i & 2) + 1] = fmaf(a[i], a[i], t[(i & 2) + 1]); }
}
__device__ __forceinline__ void stats_send(float (&t)[4], int L, const Ctx& x) {
  const unsigned seq = seq4(get_tag<false>(x.sb), L);
#pragma unroll
  for (int q = 0; q < 4; q++) t[q] = qsum(t[q]);
  if (x.c == 0) st_pkt(&g_stats[x.m()][x.w][x.j()][x.warp * 8 + x.g], __float_as_uint(t[0]), __float_as_uint(t[1]), __float_as_uint(t[2]), (__float_as_uint(t[3]) & ~15u) | seq);
}
__device__ __forceinline__ void out_epilogue(const float (&acc)[64], uint4 (&r1)[4], float (&t)[4], uint4* g, int L, Ctx& x) {
  const uint32_t t0 = x.aslot(x.ra.s), t1 = x.aslot(x.ra.s + 1 == NA ? 0 : x.ra.s + 1);
  if (L == 3) {
#pragma unroll
    for (int p = 0; p < 8; p++) {
      stsm4(x.maddr(p < 4 ? t0 : t1, (p & 3) * 2), pack2(acc[8 * p], acc[8 * p + 1]), pack2(acc[8 * p + 2], acc[8 * p + 3]),
            pack2(acc[8 * p + 4], acc[8 * p + 5]), pack2(acc[8 * p + 6], acc[8 * p + 7]));
      if ((p & 3) == 3) { uint4 r[4]; __syncwarp(); rows_load(r, p < 4 ? t0 : t1, x); rows_store(r, g + (p >> 2) * 8); }
    }
  } else {
    auto pack16 = [&](uint4 (&r)[4], const float* a) {
#pragma unroll
      for (int q = 0; q < 4; q++) { const float* u = a + 16 * (q & 1) + (q & 2); r[q] = make_uint4(pack2(u[0], u[1]), pack2(u[4], u[5]), pack2(u[8], u[9]), pack2(u[12], u[13])); }
    };
    uint4 r0[4];
    pack16(r0, acc);
    img_tag(r0, true, L + 1, x);
    img_store(r0, x.img(XBUF(L + 1), 0));
    publish(1, x);
    const float z = bb_fence(x.goff);
    img_sts(r0, t0, x);
    pack16(r1, acc + 32);
    img_tag(r1, true, L + 1, x);
    img_sts(r1, t1, x);
    float u[4] = {z, z, z, z}, v[4] = {z, z, z, z};
    stats_acc<32>(acc, v);
    stats_acc<32>(acc + 32, u);
#pragma unroll
    for (int q = 0; q < 4; q++) t[q] = u[q] + v[q];
    mbar_wait2(x.fullB(x.rb.s), x.rb.ph, x.fullB(x.rb.s + 1), x.rb.ph);
    fence_async_smem();
    asm volatile("bar.sync %0, %1;" ::"r"(L == 1 ? x.w + 1 : 3), "r"(L == 1 ? 128 : 256) : "memory");
  }
}

struct Stats { float rstd0, rstd1; };
__device__ __forceinline__ Stats load_stats(int half, const Ctx& x) {
  const float2 u = lds64f(x.sb + OFF_MR + half * 256 + (x.warp * 8 + x.g) * 8);
  return {u.x, u.y};
}

template <int NH, int NK, class F>
__device__ __forceinline__ void hedgehog_scale(float* t, const Stats& st, const uint32_t* keep, F use) {
#pragma unroll
  for (int q = 0; q < 16 * NH; q++) t[q] *= ((q & 2) ? st.rstd1 : st.rstd0) * LOG2E;
  use();
  float m[4];
#pragma unroll
  for (int q = 0; q < 4 * NH; q++) {
    const float v = fmaxf(fmaxf(fabsf(t[4 * q]), fabsf(t[4 * q + 1])), fmaxf(fabsf(t[4 * q + 2]), fabsf(t[4 * q + 3])));
    m[q & 3] = q < 4 ? v : fmaxf(m[q & 3], v);
  }
  if (__builtin_expect(__any_sync(0xffffffffu, fmaxf(fmaxf(m[0], m[1]), fmaxf(m[2], m[3])) > 58.f), 0)) {
    float z[16 * NH + NK];
#pragma unroll
    for (int q = 0; q < 16 * NH + NK; q++) z[q] = q < 16 * NH ? t[q % (16 * NH)] : __uint_as_float(keep[q & 15]);
#pragma unroll 1
    for (int r = 0; r < 2 * NH; r++) {
      float hi = -INFINITY, lo = INFINITY;
#pragma unroll 1
      for (int i = 0; i < 16; i++) {
        const int k = (i & 6) * 2 + (i & 1) + (r & 1) * 2 + (r & 2) * 8;
        const float v = z[k];
        if (i < 8) { hi = fmaxf(hi, v); lo = fminf(lo, v); }
        else z[k] = v - fminf(fmaxf(v, lo), hi);
        if (i == 7) {
#pragma unroll 1
          for (int d = 1; d <= 2; d++) { hi = fmaxf(hi, __shfl_xor_sync(0xffffffffu, hi, d)); lo = fminf(lo, __shfl_xor_sync(0xffffffffu, lo, d)); }
          const float mid = 0.5f * hi + 0.5f * lo;
          hi = fmaxf(hi - 58.f, mid); lo = fminf(lo + 58.f, mid);
        }
      }
    }
#pragma unroll
    for (int q = 0; q < 16 * NH; q++) t[q] = z[q];
    use();
  }
}
__device__ __forceinline__ void dual_exp(const float* t, uint32_t (&f)[18], int never) {
  float e[KSPLIT];
#pragma unroll
  for (int q = 0; q < KSPLIT; q++) e[q] = ex2(q < 16 ? t[q] : -t[q & 15]);
  while (never < 0) {
#pragma unroll
    for (int i = 0; i < KSPLIT; i += 4) asm volatile("ld.shared.v4.f32 {%0,%1,%2,%3}, [%4];" : "=f"(e[i]), "=f"(e[i + 1]), "=f"(e[i + 2]), "=f"(e[i + 3]) : "r"(never + i) : "memory");
    never += __float_as_int(e[0]);
  }
#pragma unroll
  for (int q = 0; q < KSPLIT; q += 2) f[q >> 1] = pack2(e[q], e[q + 1]);
#pragma unroll
  for (int q = KSPLIT; q < 32; q += 2) f[q >> 1] = q < 16 ? pack2(ex2(t[q]), ex2(t[q + 1])) : pack2(ex2(-t[q & 15]), ex2(-t[(q & 15) + 1]));
#pragma unroll
  for (int sg = 0; sg < 2; sg++) {
    const uint32_t* u = f + 8 * sg;
    const uint32_t a = add2(add2(u[0], u[2]), add2(u[4], u[6])), b = add2(add2(u[1], u[3]), add2(u[5], u[7]));
    f[16 + sg] = add2(__byte_perm(a, b, 0x5410), __byte_perm(a, b, 0x7632));
  }
}
__device__ __forceinline__ void dual_exp_rcp(const float* t, uint32_t* f) {
#pragma unroll
  for (int q = 0; q < 8; q++) {
    const float a = ex2(t[2 * q]), b = ex2(t[2 * q + 1]), r = rcp(a * b);
    f[q] = pack2(a, b); f[8 + q] = pack2(r * b, r * a);
  }
}
__device__ __forceinline__ void cta_bar() { asm volatile("bar.sync 3, 256;" ::: "memory"); }

template <int N> __device__ __forceinline__ void pin(const uint32_t* v, uint32_t addr) {
#pragma unroll
  for (int i = 0; i < N; i += 4)
    asm volatile("{\n.reg .pred p;\nsetp.eq.u32 p, %0, 0;\n@p st.shared.v4.u32 [%0], {%1,%2,%3,%4};\n}" ::"r"(addr), "r"(v[i]), "r"(v[i + 1]), "r"(v[i + 2]), "r"(v[i + 3]) : "memory");
}

__device__ __forceinline__ void consumer(const Params& P, uint32_t sb, int w, unsigned vb) {
  Ctx x;
  x.w = w;
  x.ab = sb + OFF_A + w * 8192; x.da0 = desc_lo(SB + OFF_A, 16) + w * 512;
  x.lane = threadIdx.x & 31; x.warp = __shfl_sync(0xffffffffu, (threadIdx.x >> 5) & 3, 0); x.g = x.lane >> 2; x.c = x.lane & 3;
  x.goff = (cta_m(vb) * 128 + w) * 128 + cta_j(vb) * 16;
  asm volatile("" : "+r"(x.goff));
  x.elected = (threadIdx.x & 127) == 0;
  x.ra = {0, 0}; x.rb = {0, 0}; x.pa = x.pb = 0;
  {
    const uint32_t row = x.warp * 16 + (x.lane & 15);
    x.mrow = row * 128; x.mxor = row & 7; x.mhi = x.lane >> 4;
  }
  const int goff = x.goff;
  x.ip = solid(&g_img[0][x.m()][2 * x.j()][w * 512 + x.oo()]);
  x.so = solid(16 * x.oo());
  uint4 r1[4];
  float ts[4] = {0.f, 0.f, 0.f, 0.f};
#pragma unroll
  for (int i = 0; i < 4; i++) r1[i] = make_uint4(0, 0, 0, 0);
  TSW(0);
  mbar_wait3(x.fullA(0), 0, x.fullB(0), 0);
#pragma unroll 1
  for (int L = 0; L < 4; L++) {
    float acc[64];
    constexpr uint32_t dcs = desc_lo(SB + OFF_CS, 0);
    if ((L & 1) == 0) {
    float kv[128];
    x.ha = L ? HA64 : HA128; x.k2 = L ? 32 : 4;
    gemm_issue<256, true, false>(kv, x, true); gemm_next<256>(x);
    {
      int i = 1;
#pragma unroll 1
      for (int seg = L ? NS - 1 : 0; seg <= NS; seg++) {
        const int end = seg < NS ? (L == 0 ? 3 + SA * ((x.j() + SW * w) & 3) + SB_ * seg : XA + 1) : 14 + L;
#pragma unroll 1
        do {
          gemm_issue<256, false, false>(kv, x);
          gemm_retire<256>(x, true);
          i++;
          if (i == 5) TSL_(8);
          if (i == 11) TSL_(10);
        } while (i != end);
        if (seg < NS && L == 0) {
          uint32_t v[16];
          float a[32];
#pragma unroll
          for (int q = 0; q < 4; q++) ldsm4(x.maddr(x.aslot(x.pa), 2 * q), reinterpret_cast<uint32_t (&)[4]>(v[4 * q]));
#pragma unroll
          for (int q = 0; q < 16; q++) { a[2 * q] = lo16(v[q]); a[2 * q + 1] = hi16(v[q]); }
          stats_acc<32>(a, ts);
          fence_regs(ts);
          wg_bar(w);
        }
        if (seg == NS - 1) {
          if (L > 0) { img_store(r1, x.img(XBUF(L), 1)); publish(2, x); }
          mbar_wait(sb + BAR_EPOCH, 0);
          stats_send(ts, L, x);
        }
      }
    }
      const Ring kt = x.ra;
      if (L == 0) adv<NA>(x.ra);
#pragma unroll 1
      for (int h = L; h < 2; h++) {
        float d[16];
        mbar_wait2(x.fullA(kt.s), kt.ph, sb + BAR_WPHI, 0);
        wgmma_fence();
#pragma unroll
        for (int q = 0; q < 2; q++) wgmma_ss_n32(d, x.da0 + kt.s * (SLOT / 16) + h * 4 + q * 2, desc_lo(SB + OFF_S + 4096, 512) + w * 256 + h * 128 + q * 64, q);
        wgmma_commit();
        gemm_issue<256, false, false>(kv, x);
        gemm_retire<256>(x, true);
        if (h) x.releaseA(kt.s);
        fence_regs(d);
        uint4* dst = &g_wf[1][x.j()][x.m()][w * 512 + (x.warp * 16 + x.g) * 8 + ((h * 4 + x.c) ^ x.g)];
        dst[0] = make_uint4(pack2(d[0], d[1]), pack2(d[4], d[5]), pack2(d[8], d[9]), pack2(d[12], d[13]));
        dst[64] = make_uint4(pack2(d[2], d[3]), pack2(d[6], d[7]), pack2(d[10], d[11]), pack2(d[14], d[15]));
      }
      const uint32_t dm = desc_lo(SB + OFF_MA, 0) + w * 64;
      mbar_wait2(sb + BAR_STAT, 0, sb + BAR_CS, 0);
      wgmma_fence();
      wgmma_r1_n256(kv, dm, dcs + 96, 1);
      wgmma_commit();
      const Stats st = load_stats(w, x);
      mbar_wait2(x.fullA(x.ra.s), x.ra.ph, x.fullB(x.rb.s), x.rb.ph);
      wgmma_wait<0>();
      fence_regs(kv);
      gemm_release<256>(x, true);
      TSL_(2);
      uint32_t P0[32], P1[32], PH[32];
#pragma unroll
      for (int t = 0; t < 16; t++) { P0[t] = pack2(kv[4 * t] * st.rstd0, kv[4 * t + 1] * st.rstd0); P1[t] = pack2(kv[4 * t + 2] * st.rstd1, kv[4 * t + 3] * st.rstd1); }
      pin<16>(P0, x.mrow + 16);
      {
#pragma unroll
        for (int q = 0; q < 4; q++) sts128((x.warp < 3 ? sb + OFF_T + w * 12288 + x.warp * 4096 : sb + OFF_S + 16384 + w * 2048) + x.lane * 16 + q * 512, P1[4 * q], P1[4 * q + 1], P1[4 * q + 2], P1[4 * q + 3]);
      }
      wgmma_fence();
      wgmma_r1_n128(acc, dm, dcs, 0);
      gemm_issue<128, false, false>(acc, x, true); gemm_next<128>(x);
      TSL_(3);
#pragma unroll
      for (int s = 0; s < 4; s++) {
#pragma unroll
        for (int t = 16 + 8 * (s & 1); t < 24 + 8 * (s & 1); t++) {
          if (s < 2) P1[t] = movm(pack2(kv[4 * t + 2] * st.rstd1, kv[4 * t + 3] * st.rstd1));
          else P0[t] = movm(pack2(kv[4 * t] * st.rstd0, kv[4 * t + 1] * st.rstd0));
        }
        if (s < 3) { gemm_issue<128, false, false>(acc, x); gemm_retire<128>(x, true); }
        if (s == 1) {
          if (x.warp < 3) {
#pragma unroll
            for (int q = 4; q < 8; q++) sts128(sb + OFF_T + w * 12288 + x.warp * 4096 + x.lane * 16 + q * 512, P1[4 * q], P1[4 * q + 1], P1[4 * q + 2], P1[4 * q + 3]);
          } else {
            uint4* dst = &g_halo[x.m()][x.j()][w][x.lane];
#pragma unroll
            for (int q = 0; q < 8; q++) dst[q * 32] = make_uint4(P1[4 * q], P1[4 * q + 1], P1[4 * q + 2], P1[4 * q + 3]);
          }
          publish(3, x);
          gemm_issue<128, false, false>(acc, x);
          gemm_retire<128>(x, true);
        }
      }
      TSL_(4);
      gemm_run<false>(acc, x, 10, 0);
      gemm_issue<128, false, false>(acc, x);
      {
        wg_bar(w);
        uint32_t tr = sb + OFF_T + w * 12288 + (x.warp - 1) * 4096;
        if (x.warp == 0) {
          tr = x.m() > 0 ? sb + OFF_S + 8192 + w * 4096 : tr + 4096;
          if (x.m() > 0) mbar_wait(sb + BAR_HALO, L >> 1);
        }
#pragma unroll
        for (int q = 0; q < 8; q++) lds128(tr + x.lane * 16 + q * 512, PH[4 * q], PH[4 * q + 1], PH[4 * q + 2], PH[4 * q + 3]);
      }
      gemm_retire<128>(x, false);
      gemm_end(acc, x);
      TSL_(5);
      const bool first = (x.m() == 0) && (x.warp == 0);
      const bool hi0 = 2 * x.c > x.g, hi1 = 2 * x.c + 1 > x.g;
      const uint32_t mhi = (hi0 ? 0xFFFFu : 0u) | (hi1 ? 0xFFFF0000u : 0u);
      const uint32_t valid = first ? ~mhi : ~0u;
      const float sc0 = st.rstd0 * (0.17677669529663687f * LOG2E), sc1 = st.rstd1 * (0.17677669529663687f * LOG2E);
      uint32_t xr[2][16];
#pragma unroll
      for (int hp = 0; hp < 2; hp++) {
        const uint32_t tile = x.aslot(x.held(hp));
        uint32_t px[2], py[2];
        float s[2][3][4];
#pragma unroll
        for (int u = 0; u < 2; u++) {
#pragma unroll
          for (int q = 0; q < 12; q++) s[u][q >> 2][q & 3] = 0.f;
#pragma unroll
          for (int ks = 0; ks < 2; ks++) {
            const int t = 8 * hp + 4 * u + 2 * ks;
            const uint32_t a0 = pack2(acc[4 * t], acc[4 * t + 1]), a1 = pack2(acc[4 * t + 2], acc[4 * t + 3]);
            const uint32_t a2 = pack2(acc[4 * t + 4], acc[4 * t + 5]), a3 = pack2(acc[4 * t + 6], acc[4 * t + 7]);
            mma16816(s[u][0], a0, a1, a2, a3, PH[t], PH[t + 1]);
            mma16816(s[u][1], a0, a1, a2, a3, P0[t], P0[t + 1]);
            mma16816(s[u][2], a0, a1, a2, a3, P1[t], P1[t + 1]);
          }
        }
        float e[2][4], big = 0.f;
#pragma unroll
        for (int u = 0; u < 2; u++) {
          e[u][0] = (hi0 ? s[u][0][0] : s[u][1][0]) * sc0; e[u][1] = (hi1 ? s[u][0][1] : s[u][1][1]) * sc0;
          e[u][2] = (hi0 ? s[u][1][2] : s[u][2][2]) * sc1; e[u][3] = (hi1 ? s[u][1][3] : s[u][2][3]) * sc1;
          big = fmaxf(big, fmaxf(fmaxf(fabsf(e[u][0]), fabsf(e[u][1])), fmaxf(fabsf(e[u][2]), fabsf(e[u][3]))));
          px[u] = pack2(ex2(e[u][0]), ex2(e[u][1])) & valid; py[u] = pack2(ex2(e[u][2]), ex2(e[u][3]));
        }
        if (__builtin_expect(__any_sync(0xffffffffu, big > 58.f), 0)) {
#pragma unroll
          for (int q = 0; q < 4; q++) {
            float v0 = e[q >> 1][2 * (q & 1)], v1 = e[q >> 1][2 * (q & 1) + 1];
            if (first && !(q & 1)) { if (hi0) v0 = -INFINITY; if (hi1) v1 = -INFINITY; }
            float r = fmaxf(v0, v1);
            r = fmaxf(r, __shfl_xor_sync(0xffffffffu, r, 1)); r = fmaxf(r, __shfl_xor_sync(0xffffffffu, r, 2));
            ((q & 1) ? py : px)[q >> 1] = pack2(ex2(v0 - r), ex2(v1 - r));
          }
        }
        float r[2][2];
#pragma unroll
        for (int u = 0; u < 2; u++) {
          float d[4] = {0.f, 0.f, 0.f, 0.f};
          mma1688(d, px[u], py[u], 0x3F803F80u);
          r[u][0] = rcp(d[0]); r[u][1] = rcp(d[2]);
        }
        uint32_t o[8][2];
        uint4 ro[4];
#pragma unroll
        for (int q = 0; q < 8; q++) {
          float d[4] = {0.f, 0.f, 0.f, 0.f};
          const int t = 16 + 8 * hp + q, u = q >> 2;
          mma16816(d, px[u] & mhi, 0u, px[u] & ~mhi, py[u] & mhi, PH[t], P0[t]);
          mma1688(d, 0u, py[u] & ~mhi, P1[t]);
          o[q][0] = pack2(d[0] * r[u][0], d[1] * r[u][0]); o[q][1] = pack2(d[2] * r[u][1], d[3] * r[u][1]);
        }
#pragma unroll
        for (int q = 0; q < 4; q++) ro[q] = make_uint4(o[4 * (q & 1)][q >> 1], o[4 * (q & 1) + 1][q >> 1], o[4 * (q & 1) + 2][q >> 1], o[4 * (q & 1) + 3][q >> 1]);
        img_tag(ro, false, 0, x);
        img_store(ro, x.img(0, hp));
        if (hp == 0) publish(0, x);
        if (hp == 0) {
#pragma unroll
          for (int i = 0; i < 2; i++) {
            const uint32_t ti = x.aslot(x.held(i));
            if (L) img_load(xr[i], ti, x);
            else {
#pragma unroll
              for (int q = 0; q < 4; q++) ldsm4(x.maddr(ti, 2 * q), reinterpret_cast<uint32_t (&)[4]>(xr[i][4 * q]));
            }
          }
          __syncwarp();
        }
        img_sts(ro, tile, x);
      }
      if (L == 0) {
#pragma unroll
        for (int hp = 0; hp < 2; hp++) {
          uint32_t v[16];
#pragma unroll
          for (int q = 0; q < 16; q++) asm volatile("mov.b32 %0, %1;" : "=r"(v[(q & 1) * 8 + (q >> 1)]) : "r"(xr[hp][q]));
#pragma unroll
          for (int q = 0; q < 16; q++) xr[hp][q] = v[q];
        }
      }
      img_unpack(acc, xr[0]); img_unpack(acc + 32, xr[1]);
    } else {
      float kv[128];
      float (&kv0)[64] = reinterpret_cast<float (&)[64]>(kv[0]);
      float (&kv1)[64] = reinterpret_cast<float (&)[64]>(kv[64]);
      auto mma8 = [&](uint32_t as, uint32_t bs, int i, bool fence) {
        const uint32_t da = desc_lo(SB + OFF_A, 16) + as * (SLOT / 16), db = desc_lo(SB + OFF_B, 8192) + bs * (SLOT / 16);
        if (fence) wgmma_fence();
#pragma unroll
        for (int k = 0; k < 4; k++) {
          wgmma_ss_n128(kv0, da + (k >> 1) * 32 + (k & 1) * 2, HA64, db + 128 * k, i + k);
          wgmma_ss_n128(kv1, da + 512 + (k >> 1) * 32 + (k & 1) * 2, HA64, db + 128 * k, i + k);
        }
        wgmma_commit();
      };
      constexpr uint32_t dm = desc_lo(SB + OFF_MB, 0);
      auto relB = [&](uint32_t s) { mbar_arrive_n(sb + BAR_EMPTYB + s * 8, 2); };
      auto skip = [&]() {
#pragma unroll
        for (int q = 0; q < 6 - NJ; q++) adv<NA>(x.ra);
        x.rb.s = w ? (2 + NJ) % 6 : 4;
        if (!w && NJ < 4) x.rb.ph ^= 1;
      };
      static_assert(NA == 5 && NB == 6, "ring arithmetic");
      mma8(x.ra.s, x.rb.s + w, 0, true);
      gemm_next<256>(x);
#pragma unroll 1
      for (int i = 1; i < NJ; i++) {
        mbar_wait2(x.fullA(x.ra.s), x.ra.ph, x.fullB(x.rb.s + w), x.rb.ph);
        mma8(x.ra.s, x.rb.s + w, 1, true);
        if (!XO && i == XR) { img_store(r1, x.img(XBUF(L), 1)); publish(2, x); }
        if (!XO && i == XS) stats_send(ts, L, x);
        wgmma_wait<1>();
        if (x.elected) { x.releaseA(x.pa); relB(x.pb + w); }
        gemm_next<256>(x);
        if (XO && i == XR) { img_store(r1, x.img(XBUF(L), 1)); publish(2, x); stats_send(ts, L, x); }
      }
      if (w) {
        wgmma_wait<0>();
        if (x.elected) { x.releaseA(x.pa); relB(x.pb + 1); }
        skip();
        asm volatile("bar.sync 7, 256;" ::: "memory");
      }
      TSL_(8);
      {
        const int t = lane_id() + 32 * x.warp;
        uint32_t mask = t < 2 ? ((w ? (t ? 0xFF3Fu : 0x3FFFu) : 0xFFFFu) >> (NJ - 1)) & (w ? ~1u : ~0u) : 0u, cnt = 1 + t;
        bool ready = false;
#pragma unroll 1
        for (int i = NJ; i < 16; i++) {
          if (!ready) mbar_wait2(x.fullA(x.ra.s), x.ra.ph, x.fullB(x.rb.s), x.rb.ph);
          mma8(x.ra.s, x.rb.s, 1, true);
          const uint32_t bar = sb + (t ? BAR_EMPTYB + x.pb * 8 : BAR_EMPTYA + x.pa * 8);
          gemm_next<128>(x);
          if (w && (i | 4) == 15) x.rb.s = 4;
          ready = mbar_probe2(x.fullA(x.ra.s), x.ra.ph, x.fullB(x.rb.s), x.rb.ph);
          wgmma_wait<1>();
          if (mask & 1) mbar_arrive_n(bar, cnt);
          mask >>= 1; cnt = 2;
          if (i == 8 && w) asm volatile("bar.arrive 9, 256;" ::: "memory");
          if (i == 9) TSL_(10);
        }
        mbar_wait2(sb + BAR_STAT, 1, sb + BAR_CS + 8, 0);
        wgmma_fence();
        wgmma_r1_n128(kv0, dm, dcs + 96 + 96 * w, 1);
        wgmma_r1_n128(kv1, dm + 64, dcs + 96 + 96 * w, 1);
        wgmma_commit();
        if (w == 0) asm volatile("bar.arrive 7, 256;" ::: "memory");
        wgmma_wait<1>();
        if (mask & 1) mbar_arrive_n(sb + (t ? BAR_EMPTYB + x.pb * 8 : BAR_EMPTYA + x.pa * 8), 2);
      }
      const Stats s0 = load_stats(0, x), s1 = load_stats(1, x), st = w ? s1 : s0;
      if (w == 0) skip();
      const uint32_t h0 = x.held(0), h1 = x.held(1);
      auto vreg = [&](int ks) { return ks < 6 ? OFF_A + (ks < 3 ? h0 * SLOT : h1 * SLOT - 15360) + ks * 5120 : OFF_S + 2048 + ks * 5120; };
      uint32_t tV[2], uu[4];
#pragma unroll
      for (int hf = 0; hf < 2; hf++) {
        tV[hf] = sb + vreg(4 * hf + x.warp) + ((x.lane >> 3) & 1) * 2560 + (x.lane & 7) * 16 + x.mhi * 128;
        const float i0 = rcp(hf ? s1.rstd0 : s0.rstd0), i1 = rcp(hf ? s1.rstd1 : s0.rstd1);
        const uint32_t h = pack2(i0, i1);
        uu[2 * hf] = pack2(lo16(h), i0 - lo16(h)); uu[2 * hf + 1] = pack2(hi16(h), i1 - hi16(h));
        asm volatile("" : "+r"(tV[hf]), "+r"(uu[2 * hf]), "+r"(uu[2 * hf + 1])::"memory");
      }
      wgmma_wait<0>();
      fence_regs(kv);
      TSL_(2);
      if (w == 0) {
        uint32_t f[2][18], ad[4];
#pragma unroll
        for (int q = 0; q < 18; q++) f[1][q] = 0u;
#pragma unroll
        for (int q = 0; q < 4; q++) ad[q] = x.maddr(sb + OFF_S, 2 * q);
        auto norm = [&](int un) {
          uint32_t* u = f[un & 1];
          const Stats& sn = un ? s1 : s0;
#pragma unroll
          for (int sg = 0; sg < 2; sg++) {
            uint32_t v = u[16 + sg];
            v = add2(v, __shfl_xor_sync(0xffffffffu, v, 1)); v = add2(v, __shfl_xor_sync(0xffffffffu, v, 2));
            const float a = rcp(lo16(v)) * sn.rstd0, b = rcp(hi16(v)) * sn.rstd1;
            const uint32_t r0 = pack2(a, a), r1_ = pack2(b, b);
#pragma unroll
            for (int q = 8 * sg; q < 8 * sg + 8; q++) u[q] = mul2(u[q], (q & 1) ? r1_ : r0);
#pragma unroll
            for (int q = 2 * sg; q < 2 * sg + 2; q++) stsm4(ad[q] + un * 8192, u[4 * q], u[4 * q + 1], u[4 * q + 2], u[4 * q + 3]);
          }
        };
        auto move = [&](int dst, int src) {
#pragma unroll
          for (int q = 0; q < 16; q++) asm volatile("mov.b32 %0, %1;" : "=f"(kv[dst + q]) : "f"(src ? kv[src + q] : 0.f));
        };
        hedgehog_scale<1, 0>(kv, s0, nullptr, [] {});
        uint32_t step = 0;
#pragma unroll 1
        for (int h = 0;; h++) {
          norm(1);
          dual_exp(kv, f[0], x.goff);
          hedgehog_scale<1, KEEP>(kv + 64, s1, f[1], [] {});
          if (h == 2) asm volatile("bar.sync 9, 256;" ::: "memory");
#pragma unroll
          for (int q = 0; q < 4; q++) ad[q] += step;
          norm(0);
          dual_exp(kv + 64, f[1], x.goff);
#pragma unroll
          for (int q = 0; q < 16; q++) kv[q] = kv[16 + q];
          hedgehog_scale<1, KEEP>(kv, s0, f[0], [] {});
          step = SLOT;
          if (h == 0) { move(64, 80); move(16, 32); }
          else if (h == 1) { move(64, 96); move(16, 48); step = OFF_B + SLOT - OFF_S; }
          else if (h == 2) { move(64, 112); move(16, 0); }
          else break;
        }
        norm(1);
        TSL_(3);
      } else {
        wg_bar(w);
#pragma unroll
        for (int hf = 0; hf < 2; hf++) {
          stsm4(tV[hf] + 512 + x.mhi * 512, uu[2 * hf], uu[2 * hf + 1], uu[2 * hf], uu[2 * hf + 1]);
          stsm4(tV[hf] + 1792 + x.mhi * 512, uu[2 * hf], uu[2 * hf + 1], uu[2 * hf], uu[2 * hf + 1]);
#pragma unroll
          for (int q = 0; q < 8; q++) {
            const float* u = kv + 64 * hf + 8 * q;
            stsm4(tV[hf] + (q >> 1) * 640 + (q & 1) * 256, pack2(u[0], u[1]), pack2(u[2], u[3]), pack2(u[4], u[5]), pack2(u[6], u[7]));
          }
        }
        TSL_(3);
      }
      {
        float d[2][20];
        uint4* dst = &g_kvpart[x.j()][w * 4 + x.warp][0][x.m() * 32 + x.lane];
        unsigned* dz = reinterpret_cast<unsigned*>(&g_kvpart[x.j()][w * 4 + x.warp][x.c & 1][512]) + x.m() * 8 + x.g;
        fence_async_smem();
        cta_bar();
        TSL_(11);
        uint32_t pk[9];
        auto prep = [&](float (&u)[20]) {
          fence_regs(u);
#pragma unroll
          for (int q = 0; q < 8; q++) pk[q] = pack2(u[((q >> 1) & 2) + 4 * (q & 3)], u[((q >> 1) & 2) + 4 * (q & 3) + 1]);
          pk[8] = __float_as_uint((x.c & 1) ? u[18] + u[19] : u[16] + u[17]);
#pragma unroll
          for (int q = 0; q < 9; q += 4) pk[q] = (pk[q] & ~1u) | (L == 1);
        };
        auto send = [&](int hp) {
          st_v4(dst + hp * 16 * 544, pk[0], pk[1], pk[2], pk[3]); st_v4(dst + (hp * 16 + 1) * 544, pk[4], pk[5], pk[6], pk[7]);
          st_flag(dz + hp * 16 * 544 * 4, pk[8]);
        };
        wgmma_fence();
#pragma unroll
        for (int q = 0; q < 17; q++) {
          if (q < 16) wgmma_ss_n40_tt(d[q >> 3], desc_lo(SB + (q < 8 ? OFF_S : OFF_B + 2 * SLOT), 1024) + w * (SLOT / 16) + 128 * (q & 7), desc_lo(SB + vreg(q & 7), 2560) + (w + (q >> 3) * 2) * 40, q & 7);
          else wgmma_r1_n128(acc, dm + w * 64, dcs, 0);
          if (q == 7 || q == KVS || q == 16) wgmma_commit();
          if (q == KVS) { mbar_wait2(x.fullA(x.ra.s), x.ra.ph, x.fullB(x.rb.s), x.rb.ph); wgmma_wait<1>(); prep(d[0]); send(0); bb_fence(x.goff); wgmma_fence(); }
        }
        gemm_issue<128, false>(acc, x, true); gemm_next<128>(x);
        wgmma_wait<1>();
        x.releaseA(h0); x.releaseA(h1); x.releaseB(2); x.releaseB(3);
        if (x.lane == 0) mbar_arrive(sb + BAR_SIGT);
        prep(d[1]);
        TSL_(4);
#pragma unroll 1
        for (int seg = 0; seg < 2; seg++) {
          const int n0 = w ? PS1 : PS0;
          gemm_run(acc, x, seg ? 15 - n0 : n0, seg, seg ? L : 0);
          if (seg == 0) send(1);
        }
      }
      gemm_end(acc, x);
      TSL_(5);
      {
        float dp[2][20], dn[2][20];
        uint32_t f[4][16];
        auto mma = [&](int h) {
          if (!(h & 1)) mbar_wait(sb + BAR_KV + h * 4, L >> 1);
          if (h == 0) TSL_(9);
          const uint32_t db = desc_lo(SB + OFF_S + h * 5120, 128);
          const uint32_t (&a)[16] = f[h];
          wgmma_fence();
          wgmma_rs_n40(dp[h & 1], a[0], a[1], a[2], a[3], db, 0);
          wgmma_rs_n40(dn[h & 1], a[8], a[9], a[10], a[11], db + 160, 0);
          wgmma_rs_n40(dp[h & 1], a[4], a[5], a[6], a[7], db + 80, 1);
          wgmma_rs_n40(dn[h & 1], a[12], a[13], a[14], a[15], db + 240, 1);
          wgmma_commit();
        };
        uint32_t xr[16];
        auto fin = [&](int h) {
          const uint32_t tile = x.aslot(x.held(h >> 1));
          if (!(h & 1)) img_load(xr, tile, x);
          float (&u)[20] = dp[h & 1];
          float (&v)[20] = dn[h & 1];
          fence_regs(u); fence_regs(v);
#pragma unroll
          for (int r = 0; r < 2; r++) {
            const float sp = u[16 + 2 * r], sn = v[16 + 2 * r];
            const float id = rcp(fmaf(fmaf(sp, L == 1 ? 0.065536f * 128 / 129 : 0.065536f, u[17 + 2 * r]), sn, v[17 + 2 * r] * sp)), aa = sn * id, cc = sp * id;
            uint32_t o[4];
#pragma unroll
            for (int t = 0; t < 4; t++) o[t] = pack2(fmaf(u[4 * t + 2 * r], aa, v[4 * t + 2 * r] * cc), fmaf(u[4 * t + 2 * r + 1], aa, v[4 * t + 2 * r + 1] * cc));
            o[2 * r + (h & 1)] = img_tag(o[2 * r + (h & 1)], false, 1, x);
            if (ZO && h == 3) r1[r] = make_uint4(o[0], o[1], o[2], o[3]);
            else stg128(x.img(0, h >> 1) + r * 64 + (h & 1) * 32, make_uint4(o[0], o[1], o[2], o[3]));
            sts128(tile + r * 1024 + (h & 1) * 512 + x.so, o[0], o[1], o[2], o[3]);
          }
          if (h & 1) { if (h == 1) publish(0, x); img_unpack(acc + 16 * (h - 1), xr); }
        };
        auto ex = [&](int h) { dual_exp_rcp(acc + 16 * h, f[h]); };
        Stats sq = st;
#pragma unroll
        for (int h = 0; h < 4; h += 2) {
          hedgehog_scale<2, 0>(acc + 16 * h, sq, nullptr, [&] { ex(h); });
          mma(h);
          ex(h + 1); wgmma_wait<0>(); fin(h);
          if (h == 0) bb_fence(x.goff);
          mma(h + 1);
          wgmma_wait<0>(); fin(h + 1);
          if (h == 0) sq.rstd1 += bb_fence(x.goff);
        }
      }
    }
    mbar_wait(x.fullB(x.rb.s), x.rb.ph);
    fence_regs(acc);
    fence_async_smem();
    wg_bar(w);
    TSL_(6);
    rewind2<NA>(x.ra);
    if (ZO && (L & 1)) { stg128(x.img(0, 1) + 32, r1[0]); stg128(x.img(0, 1) + 96, r1[1]); }
    gemm_issue<128, false>(acc, x, true); gemm_next<128>(x);
    uint4* out = solid(P.out + goff + (x.warp * 16 + (x.lane >> 3)) * 256 + (x.lane & 7));
#pragma unroll 1
    for (int seg = L >= TSL ? 0 : 1; seg < 2; seg++) {
      gemm_run(acc, x, L >= TSL ? (seg ? TSK : 15 - TSK) : 15, seg, 10 + L);
      if (L >= TSL) {
        if (seg == 0 && w == 1) asm volatile("bar.sync 6, 256;" ::: "memory");
        if (seg == 1 && w == 0) asm volatile("bar.arrive 6, 256;" ::: "memory");
      }
    }
    gemm_end(acc, x);
    TSL_(7);
    rewind2<NA>(x.ra);
    out_epilogue(acc, r1, ts, out, L, x);
    TSL_(13);
  }
}

typedef unsigned long long u64;
template <class T> __device__ __forceinline__ T* early(T* p) { return (T*)__shfl_xor_sync(0xffffffffu, (u64)p, 1); }
__device__ __forceinline__ void pause(uint32_t GAP) {
  if (GAP) { uint32_t t0, t; asm volatile("mov.u32 %0, %%clock;" : "=r"(t0)); do { asm volatile("mov.u32 %0, %%clock;" : "=r"(t)); } while (t - t0 < GAP); }
}
__device__ __forceinline__ u64 order_table0(int j) { return (j & 4) ? 0x543210FEDCBA9876ull : 0xDCBA9876543210FEull; }
__device__ __forceinline__ void order_tables(u64& t1, u64& t2, int j) {
#pragma unroll 1
  for (int i = 6; i >= 0; i--) { const u64 o = 2 * other_tile(i, j); t1 = t1 << 4 | o | (o + 1) << 28; t2 = t2 << 8 | (o * 17 + 16); }
  const u64 own = 2 * j * 17 + 16;
  t1 = t1 << 8 | own; t2 |= own << 56;
}

__device__ __forceinline__ void b_producer(const Params& P, uint32_t sb, unsigned vb) {
  const int j = cta_j(vb);
  u64 t1 = 0, t2 = 0;
  Ring r = {PRE_B % NB, PRE_B < NB};
#pragma unroll 1
  for (int sg = 0; sg < 20; sg++) {
    const int L = sg / 5, p = sg - 5 * L, wt = L & 1;
    if (sg == 1) order_tables(t1, t2, j);
    int n = p >= 3 ? 16 : (wt ? (p ? 16 - NJ : 2 * NJ) : (p ? 0 : (L ? 32 : 32 - PRE_B)));
    u64 tab = p == 3 ? t2 : (sg == 0 ? order_table0(j) >> (2 * PRE_B) : (p == 1 || p == 2 ? t1 >> (4 * NJ) : t1));
    const CUtensorMap* tm = p == 4 ? &P.mwo[wt] : &P.mw[wt ? 1 : L];
    const uint4* img = &g_wf[p != 3][j][0][0];
    int col = (p >= 3 ? 0 : (p == 2 ? 2048 : 1024)) + 128 * j;
    const int flip = p == 0 ? 3072 : 0;
    const bool fold = wt && p != 4;
    if (sg == 5 || sg == 8) { mbar_wait(sb + (sg == 5 ? BAR_WPHI : BAR_CS + 8), sg == 5); fence_async_global(); }
    if (DEFER && p == 4 && ((DEFL >> wt) & 1)) {
      Ring q = r;
      for (int u = 0; u < DEFER; u++) adv<NB>(q);
      mbar_wait(sb + BAR_EMPTYB + q.s * 8, q.ph);
    }
#pragma unroll 1
    for (; n > 0; n--) {
      const int kb = (int)tab & 15;
      mbar_wait(sb + BAR_EMPTYB + r.s * 8, r.ph);
      if (elect()) {
        mbar_expect_tx(sb + BAR_FULLB + r.s * 8, SLOT);
        if (fold && col < 2048) bulk_load(sb + OFF_B + r.s * SLOT, img + kb * 1024, SLOT, sb + BAR_FULLB + r.s * 8);
        else tma_load_w(sb + OFF_B + r.s * SLOT, tm, sb + BAR_FULLB + r.s * 8, col, kb);
      }
      adv<NB>(r);
      if (p == 2 && (n | 4) == 5) r.s = 4;
      col ^= flip;
      if (!(col & flip & 2048)) tab >>= 4;
    }
  }
}

__device__ __forceinline__ void a_loader(const Params& P, uint32_t sb, unsigned vb) {
  const int j = cta_j(vb), m = cta_m(vb);
  u64 t1 = 0, t2 = 0;
  Ring r = {PRE_A % NA, PRE_A < NA};
  {
    u64 tab = order_table0(j) >> (4 * PRE_A);
#pragma unroll 1
    for (int i = PRE_A; i < 33; i++) {
      if (i == 17) { order_tables(t1, t2, j); tab = t2; }
      mbar_wait(sb + BAR_EMPTYA + r.s * 8, r.ph);
      if (elect()) {
        mbar_expect_tx(sb + BAR_FULLA + r.s * 8, SLOT);
        if (i != 14) tma_load_3d(sb + OFF_A + r.s * SLOT, &P.mx, sb + BAR_FULLA + r.s * 8, ((int)tab & 15) * 64, m * 64, 0);
        else {
          tma_load_w(sb + OFF_A + r.s * SLOT, &P.mw[1], sb + BAR_FULLA + r.s * 8, 1024 + 128 * j, m);
          mbar_expect_tx(sb + BAR_WPHI, 8192); tma_load_2d(sb + OFF_S + 4096, &P.mwphi, sb + BAR_WPHI, 0, 128 * j);
        }
        if (i == PF1 || i == PF2) tma_prefetch_w(&P.mwo[i == PF2], 128 * j, m);
      }
      adv<NA>(r);
      if (i != 14) tab >>= 4;
    }
  }
  const unsigned tag = get_tag(sb);
  unsigned kph = 0;
#pragma unroll 1
  for (int sg = 0; sg < 13; sg++) {
    const int L = sg >> 2, p = sg & 3;
    if (p == 0 && (L & 1)) {
#pragma unroll 1
      for (int h = 0; h < 2; h++) {
        poll_flags(&g_jflag[h][j][0], 16, 0xFFFFu, tag * 4 + L);
        TS(4, h ? 14 + L : 26 + L);
        for (int it = 0;; it++) {
          if (elect()) { mbar_expect_tx(sb + BAR_STAT + 8, 10240); bulk_load(sb + OFF_S + h * 10240, &g_kvfin[j][8 * h][0], 10240, sb + BAR_STAT + 8); }
          mbar_wait(sb + BAR_STAT + 8, kph);
          kph ^= 1;
          uint32_t a = 1u, o = 0u;
#pragma unroll
          for (int u = 0; u < 20; u++) { const uint32_t v = __float_as_uint(lds32f(sb + OFF_S + h * 10240 + u * 512 + (threadIdx.x & 31) * 16)); a &= v; o |= v; }
          if (__all_sync(0xffffffffu, (L == 1 ? a : ~o) & 1u)) break;
          fence_async_smem();
          if (it > (1 << 16)) __trap();
        }
        if (elect()) mbar_arrive(sb + BAR_KV + h * 8);
        TS(4, h ? 30 + L : (L == 1 ? 20 : 25));
      }
    }
    int n = p < 2 ? 14 : (p == 2 ? ((L & 1) ? 0 : 16 - NJ) : 16);
    u64 tab = p == 3 ? t2 : t1 >> (p < 2 ? 8 : 4 * NJ);
    const uint4* img = &g_img[p ? XBUF(L + 1) : 0][m][0][0];
#pragma unroll 1
    for (; n > 0; n--) {
      const uint4* src = early(img + ((int)tab & 15) * 1024);
      const uint32_t bar = sb + (p < 2 ? BAR_LAND : BAR_FULLA) + r.s * 8;
      mbar_wait(sb + BAR_EMPTYA + r.s * 8, r.ph);
      if (elect()) mbar_expect_tx(bar, SLOT);
      if (p < 2 && n == 14) {
        const int lane = threadIdx.x & 31;
        const unsigned* f = &g_hint[(m & 14) + ((lane >> 3) & 1)][(~j & 4) + (lane & ND0)];
        mbar_wait(sb + BAR_SIGP + p * 8, L & 1);
        pause(PD);
        int it = 0;
        while (!__all_sync(0xffffffffu, (int)(ld_flag(f) - (tag * 16 + 4 * L + 1 + p)) >= 0)) { if (++it > (1 << 22)) __trap(); }
        TS(2, p == 0 ? 5 + L * 8 : 9 + L * 8);
        TSH((2 * L + p) * 8 + 2);
      }
      if (elect()) bulk_load(sb + OFF_A + r.s * SLOT, src, SLOT, bar);
      adv<NA>(r);
      tab >>= 4;
      pause(p < 2 && n > 10 ? G0 : 0);
    }
  }
}

template <int KB>
__device__ __forceinline__ uint2 sum_packets(float (&a)[8], uint32_t addr, int n) {
  uint2 ok = make_uint2(~0u, 0u);
#pragma unroll 1
  for (int b = 0; b < n; b += KB) {
    uint4 v[KB];
#pragma unroll
    for (int u = 0; u < KB; u++) lds128(addr + (b + u) * 512, v[u].x, v[u].y, v[u].z, v[u].w);
#pragma unroll
    for (int u = 0; u < KB; u++) {
      ok.x &= v[u].x; ok.y |= v[u].x;
      a[0] += lo16(v[u].x); a[1] += hi16(v[u].x); a[2] += lo16(v[u].y); a[3] += hi16(v[u].y);
      a[4] += lo16(v[u].z); a[5] += hi16(v[u].z); a[6] += lo16(v[u].w); a[7] += hi16(v[u].w);
    }
  }
  return ok;
}
__device__ __forceinline__ void helper_bar() { asm volatile("bar.sync 4, 64;" ::: "memory"); }
__device__ __forceinline__ void helper(const Params& P, uint32_t sb, int w, unsigned vb) {
  const int j = cta_j(vb), m = cta_m(vb);
  if (w == 0) {
    if (elect()) {
      const unsigned t = atomicAdd(&g_ctr, 1u) / NCTA + 1u;
      asm volatile("st.shared.u32 [%0], %1;" ::"r"(sb + OFF_EPOCH), "r"(t) : "memory");
      mbar_arrive(sb + BAR_EPOCH);
    }
  }
  const unsigned tag = get_tag(sb);
  mbar_wait(sb + BAR_FULLB + 24, 0);
  const uint32_t stg = sb + OFF_T + w * 12288, stb = sb + BAR_STG + w * 24;
  Ring rs = {0, 0};
  uint32_t vs = 33 % NA, vph = 0;
  auto cs_image = [&](int L) {
      const int lane = lane_id();
      poll_flags(&g_jflag[2 * L][j][0], 16, L ? CSNEED : 0xFFFu, tag * 4);
#pragma unroll
      for (int p = 0; p < 3; p++) {
        const uint4 u = ldcg4(&g_cs[L][0][p * 1024 + 128 * j + lane * 4]), v = ldcg4(&g_cs[L][1][p * 1024 + 128 * j + lane * 4]);
        const float c0 = __uint_as_float(u.x) + __uint_as_float(v.x), c1 = __uint_as_float(u.y) + __uint_as_float(v.y);
        const float c2 = __uint_as_float(u.z) + __uint_as_float(v.z), c3 = __uint_as_float(u.w) + __uint_as_float(v.w);
        const uint32_t h0 = pack2(c0, c1), h1 = pack2(c2, c3), dst = sb + OFF_CS + (p * 16 + (lane >> 1)) * 96 + L * 48 + (lane & 1) * 8;
        sts64(dst, h0, h1); sts64(dst + 16, pack2(c0 - lo16(h0), c1 - hi16(h0)), pack2(c2 - lo16(h1), c3 - hi16(h1))); sts64(dst + 32, h0, h1);
        if (L == 0) { sts64(dst + 48, 0u, 0u); sts64(dst + 64, 0u, 0u); sts64(dst + 80, 0u, 0u); }
      }
      if (L == 0 && lane < 4) sts64(sb + OFF_CS + 4608 + lane * 8, 0u, 0u);
      fence_async_smem();
      __syncwarp();
      if (elect()) mbar_arrive(sb + BAR_CS + L * 8);
      TS(4, 2 + L * 2);
  };
#pragma unroll 1
  for (int L = 0; L < 4; L++) {
    const int lane = lane_id();
    if (L == 0) {
      {
        const int wt = m >= 12, col = ((0x2021 >> (m & 12)) & 3) * 1024 + 128 * j + (m & 3) * 32;
        const CUtensorMap* tm = &P.mcs[wt];
        __nanosleep(wt ? D2 : CD);
        constexpr int nb = 8;
        float a[8] = {0.f, 0.f, 0.f, 0.f, 0.f, 0.f, 0.f, 0.f};
#pragma unroll 1
        for (int b = -3; b < nb; b++) {
          if (b >= 0) {
            mbar_wait(stb + rs.s * 8, rs.ph);
            sum_packets<KC>(a, stg + rs.s * 4096 + lane * 16, 8);
            fence_async_smem();
            __syncwarp();
          }
          const uint32_t sl = b < 0 ? (rs.s + b + 3) % 3 : rs.s;
          if (b + 3 < nb && elect()) { mbar_expect_tx(stb + sl * 8, 4096); tma_load_2d(stg + sl * 4096, tm, stb + sl * 8, col, (w * (16 - nb) + b + 3) * 64); }
          if (b >= 0) adv<3>(rs); else pause(CP);
        }
#pragma unroll 1
        for (int d = 4; d < 32; d *= 2)
#pragma unroll
          for (int u = 0; u < 8; u++) a[u] += __shfl_xor_sync(0xffffffffu, a[u], d);
        if (lane < 4) {
          float4* dst = reinterpret_cast<float4*>(&g_cs[wt][w][col + lane * 8]);
          dst[0] = make_float4(a[0], a[1], a[2], a[3]); dst[1] = make_float4(a[4], a[5], a[6], a[7]);
        }
        helper_bar();
        if (w == 0 && elect()) { fence_gpu(); st_flag(&g_jflag[2 * wt][j][m], tag * 4); }
      }
      if (w == 0) TS(4, 1 + L * 2);
    }
    if (L > 0 && w == 0) {
      mbar_wait(sb + BAR_SIGP + 16, (L - 1) & 1);
      fence_async_global();
      __nanosleep(CO && L == 1 ? SE : SD);
    }
    if (CO && L < 2 && w == 0) cs_image(L);
    if (w == (L == 0)) {
      if (L == 0) { mbar_wait(sb + BAR_WPHI, 0); __nanosleep(S0); }
#pragma unroll 1
      for (int p = 0; p < 2; p++) {
        uint4 v[8];
        for (int it = 0;; it++) {
          bool ok = true;
#pragma unroll
          for (int t = 0; t < 8; t++) v[t] = ld_pkt(&g_stats[m][p][t][lane]);
#pragma unroll
          for (int t = 0; t < 8; t++) ok = ok && (v[t].w & 15u) == seq4(tag, L);
          if (__all_sync(0xffffffffu, ok)) break;
          __nanosleep(200);
          if (it > (1 << 20)) __trap();
        }
        float s0 = 0.f, q0 = 0.f, s1 = 0.f, q1 = 0.f;
#pragma unroll
        for (int t = 0; t < 8; t++) { s0 += __uint_as_float(v[t].x); q0 += __uint_as_float(v[t].y); s1 += __uint_as_float(v[t].z); q1 += __uint_as_float(v[t].w & ~15u); }
        s0 *= (1.f / 1024); s1 *= (1.f / 1024);
        sts64(sb + OFF_MR + p * 256 + lane * 8, __float_as_uint(rsqrtf(fmaxf(q0 * (1.f / 1024) - s0 * s0, 0.f) + 1e-5f)),
              __float_as_uint(rsqrtf(fmaxf(q1 * (1.f / 1024) - s1 * s1, 0.f) + 1e-5f)));
#pragma unroll
        for (int r = 0; r < 2; r++) {
          const float v = -0.5f * (r ? s1 : s0);
          const uint32_t hh = pack2(v, v), hl = pack2(v, v - lo16(hh));
          const bool b = L & 1;
          sts128(sb + (b ? OFF_MB : OFF_MA) + p * 1024 + (lane >> 3) * 256 + r * 128 + (lane & 7) * 16, b ? 0u : hh, b ? hh << 16 : hl >> 16, b ? hl : 0u, 0u);
        }
      }
      fence_async_smem();
      __syncwarp();
      if (elect()) {
        mbar_arrive(sb + BAR_STAT);
      }
      TS(2, 0 + L * 8);
    }
    if (!CO && L < 2 && w == 0) cs_image(L);
    if (L & 1) {
      const uint32_t flip = L == 1 ? 0u : 1u;
      mbar_wait(sb + BAR_SIGT, 1);
      {
        int it = 0;
        if (PSL) __nanosleep(m < 8 ? PSL : PSL + 600);
        while (!__all_sync(0xffffffffu, (ld_flag(reinterpret_cast<const unsigned*>(&g_kvpart[j][m][w][512]) + (lane & 15) * 8) ^ flip) & 1u)) { if (PSL) __nanosleep(100); if (++it > (1 << 22)) __trap(); }
        fence_async_global();
      }
      if (w == 0) TS(4, 6 + L * 2);
      float a[8], z;
      for (int it = 0;; it++) {
        if (elect()) { mbar_expect_tx(stb + rs.s * 8, 8704); bulk_load(stg, &g_kvpart[j][m][w][0], 8704, stb + rs.s * 8); }
        mbar_wait(stb + rs.s * 8, rs.ph);
        if (w == 0) TS(4, 21 + L);
        adv<3>(rs);
#pragma unroll
        for (int u = 0; u < 8; u++) a[u] = 0.f;
        z = 0.f;
        uint32_t ok = 1u;
#pragma unroll
        for (int u = 0; u < 4; u++) { const float v = lds32f(stg + 8192 + u * 128 + (lane & 3) * 32 + (lane >> 2) * 4); z += v; ok &= __float_as_uint(v) ^ flip; }
        const uint2 tg = sum_packets<8>(a, stg + lane * 16, 16);
        ok &= flip ? ~tg.y : tg.x;
        if (__all_sync(0xffffffffu, ok & 1u)) break;
        fence_async_smem();
        if (it > (1 << 16)) __trap();
      }
      {
        uint4* img = &g_kvfin[j][m][w * 8 + (lane >> 2)];
        uint32_t a0 = __float_as_uint(a[0]) >> 16;
        a0 += ~(a0 ^ flip) & 1u;
        st_v4(img + (lane & 3) * 16, __byte_perm(a0, pack2(0.f, a[1]), 0x7610), pack2(a[2], a[3]), pack2(a[4], a[5]), pack2(a[6], a[7]));
        const uint32_t cz = pack2(0.f, qsum(z)) | (0x3781u ^ flip);
        if (!(lane & 3)) st_v4(img + 64, cz, cz, cz, cz);
        __syncwarp();
        if (elect()) st_flag(&g_jflag[m >> 3][j][(m & 7) * 2 + w], tag * 4 + L);
      }
      if (w == 0) TS(4, 7 + L * 2);
    } else {
      if (L == 0 && w == 0) {
        st_v4(&g_kvpart[j][m][0][512 + lane], 0u, 0u, 0u, 0u); st_v4(&g_kvpart[j][m][1][512 + lane], 0u, 0u, 0u, 0u);
        __syncwarp();
      }
      mbar_wait(sb + BAR_SIGT, 0);
      if (w == 0) {
        if (elect()) { fence_gpu(); st_flag(&g_hint[m][j], tag * 16 + 4 * L); st_flag(&g_jflag[1][j][m], tag * 4 + L); }
        if (L == 0) {
          __nanosleep(KSL);
          poll_flags(&g_jflag[1][j][0], 16, 0xFFFFu, tag * 4);
          if (elect()) mbar_arrive(sb + BAR_WPHI);
        }
      } else if (m > 0) {
        poll_flags(&g_hint[m - 1][j], 1, 1u, tag * 16 + 4 * L);
        if (elect()) { mbar_expect_tx(sb + BAR_HALO, 8192); bulk_load(sb + OFF_S + 8192, &g_halo[m - 1][j][0][0], 8192, sb + BAR_HALO); }
        TS(2, 2 + L * 8);
      }
    }
    if (w == 0) {
#pragma unroll 1
      for (int e = 0; e < (L < 3 ? 2 : 1); e++) {
        unsigned* flag = early(&g_hint[m][j]);
        mbar_wait(sb + BAR_SIGP + e * 8, L & 1);
        TS(2, (e ? 6 : 3) + L * 8);
        TSH((2 * L + e) * 8);
        pause(e ? XD : (L == 0 ? XD0 : (L == 2 ? XDA : XDB)));
        if (elect()) st_flag(flag, tag * 16 + 4 * L + 1 + e);
        TSH((2 * L + e) * 8 + 1);
      }
    } else {
#pragma unroll 1
      for (int i = 0; i < (L < 3 ? 28 : 14); i++) {
        const bool isx = i >= 14;
        const uint32_t a = sb + OFF_A + vs * SLOT + lane * 128 + ((lane >> 4) * 4 + (lane & 3)) * 16 + (lane & 12), code = img_code(isx, L + isx);
        for (int it = 0;; it++) {
          mbar_wait(sb + BAR_LAND + vs * 8, (vph >> vs) & 1);
          vph ^= 1u << vs;
          if (i - 14 * isx < 2) TSH((2 * L + isx) * 8 + 3 + 2 * (i - 14 * isx));
          uint32_t bad = 0;
#pragma unroll
          for (int u = 0; u < 4; u++) bad |= __float_as_uint(lds32f(a + u * 4096)) ^ code;
          if (__all_sync(0xffffffffu, !(bad & img_mask(isx)))) break;
          if (it > (1 << 16)) __trap();
          fence_async_smem();
          if (elect()) {
            mbar_expect_tx(sb + BAR_LAND + vs * 8, SLOT);
            bulk_load(sb + OFF_A + vs * SLOT, &g_img[isx ? XBUF(L + 1) : 0][m][o_order(i - 14 * isx + 2, j)][0], SLOT, sb + BAR_LAND + vs * 8);
          }
        }
        if (elect()) mbar_arrive(sb + BAR_FULLA + vs * 8);
        if (i - 14 * isx < 2) TSH((2 * L + isx) * 8 + 4 + 2 * (i - 14 * isx));
        if (++vs == NA) vs = 0;
      }
      vs = (vs + ((L & 1) ? 16 : 32 - NJ)) % NA;
    }
  }
}

__device__ __forceinline__ void spare(const Params& P, uint32_t sb, int id) {
  const int tid = threadIdx.x & 127, warp = __shfl_sync(0xffffffffu, threadIdx.x >> 5, 0), w = warp >> 2, lane = tid & 31, j = 2 * id + w;
  const uint32_t ring = w * 6 * SLOT, wp = 12 * SLOT + w * 8192, bar = sb + 13 * SLOT + w * 64;
  auto part = [&](int t) { return (t >> 4) ^ w; };
  auto load = [&](int t, uint32_t sl) {
    mbar_expect_tx(bar + sl * 8, t == 0 ? SLOT + 8192 : SLOT);
    tma_load_w(sb + ring + sl * SLOT, &P.mw[1], bar + sl * 8, part(t) * 1024 + 128 * j, t & 15);
  };
  if (!(warp & 3) && elect()) {
    if (w == 2) sts32(sb + OFF_EPOCH, atomicAdd(&g_ctr, 1u) / NCTA + 1u);
    else {
      __nanosleep(D3);
#pragma unroll 1
      for (int t = 0; t < 5; t++) {
        mbar_init(bar + t * 8, 1);
        asm volatile("fence.mbarrier_init.release.cluster;" ::: "memory");
        load(t, t);
      }
      tma_load_2d(sb + wp, &P.mwphi, bar, 0, 128 * j);
    }
  }
  __syncthreads();
  const unsigned tag = get_tag<false>(sb);
  if (w == 2) {
    int it = 0;
    while ((int)(ld_flag(&g_ctr) - tag * NCTA) < 0) { if (++it > (1 << 22)) __trap(); }
    return;
  }
  Ring r = {4, 1};
  float d[64];
  auto fold = [&]() {
    mbar_wait(bar + r.s * 8, r.ph);
    wgmma_fence();
#pragma unroll
    for (int q = 0; q < 8; q++)
      wgmma_ss_n32(reinterpret_cast<float (&)[16]>(d[16 * (q >> 1)]), desc_lo(SB + ring + r.s * SLOT, 16) + (q >> 2) * 512 + (q & 3) * 2, desc_lo(SB + wp, 512) + q * 64, q & 1);
    wgmma_commit();
  };
#pragma unroll
  for (int i = 0; i < 64; i++) d[i] = 0.f;
  int t = -1;
#pragma unroll 1
  for (int g = 0; g < 2; g++) {
    float cs[32] = {};
#pragma unroll 1
    do {
      uint32_t f[32];
#pragma unroll
      for (int i = 0; i < 32; i++) { f[i] = pack2(d[2 * i], d[2 * i + 1]); cs[i & 30] += d[2 * i]; cs[i | 1] += d[2 * i + 1]; }
      wg_bar(w);
      const uint32_t sl = r.s;
      if (t < 31) adv<5>(r);
      fold();
      if (!(warp & 3) && t >= 0 && t < 27 && elect()) load(t + 5, sl);
      if (g == w && t >= 0) {
        uint4* dst = &g_wf[0][j][t & 15][((tid >> 5) * 16 + (lane >> 2)) * 8];
#pragma unroll
        for (int q = 0; q < 8; q++)
          dst[(q >> 2) * 512 + (q & 1) * 64 + (((q & 2) * 2 + (lane & 3)) ^ (lane >> 2))] =
              make_uint4(f[4 * (q & 6) + (q & 1)], f[4 * (q & 6) + (q & 1) + 2], f[4 * (q & 6) + (q & 1) + 4], f[4 * (q & 6) + (q & 1) + 6]);
      }
      wgmma_wait<0>();
      fence_regs(d);
    } while (++t != 16 * g + 16);
    const uint32_t red = sb + ring + 5 * SLOT;
#pragma unroll
    for (int i = 0; i < 8; i++) sts128(red + (tid >> 2) * 512 + (i >> 1) * 128 + (lane & 3) * 32 + (i & 1) * 16, __float_as_uint(cs[4 * i]), __float_as_uint(cs[4 * i + 1]), __float_as_uint(cs[4 * i + 2]), __float_as_uint(cs[4 * i + 3]));
    wg_bar(w);
    float a = 0.f;
#pragma unroll 4
    for (int i = 0; i < 32; i++) a += lds32f(red + i * 512 + tid * 4);
    g_cs[1][0][(g ^ w) * 1024 + j * 128 + tid] = a;
  }
  wg_bar(w);
  if (tid == 0) { fence_gpu(); st_flag(&g_jflag[2][j][0], tag * 4); }
}

__global__ void __launch_bounds__(NTHREADS, 1) fused_kernel(const __grid_constant__ Params P) {
  extern __shared__ __align__(1024) uint8_t smem_raw[];
  constexpr uint32_t sb = SB;
  const int tid = threadIdx.x;
  const unsigned vb = vblock();
  if (vb >= 128) { spare(P, sb, vb - 128); return; }
  const int warp = __shfl_sync(0xffffffffu, tid >> 5, 0);
  if (elect()) {
    if (warp == 11) { prefetch_map(&P.mx); prefetch_map(&P.mw[0]); if (smem_u32(smem_raw) != SB) __trap(); }
    if (warp < 8) {
#pragma unroll
      for (int i = 0; i < 8; i++) mbar_init(sb + OFF_BAR + (warp * 8 + i) * 8, warp == 2 || warp == 3 ? 2 : (warp == 4 ? 8 : 1));
    }
    asm volatile("fence.mbarrier_init.release.cluster;" ::: "memory");
    if (warp < 2) {
      const int j = cta_j(vb);
#pragma unroll 1
      for (int i = 0; i < (warp == 0 ? PRE_B : PRE_A); i++) {
        const uint32_t bar = sb + BAR_FULLB + warp * 64 + i * 8;
        mbar_expect_tx(bar, SLOT);
        if (warp == 0) tma_load_w(sb + OFF_B + i * SLOT, &P.mw[0], bar, 1024 + (i & 1) * 1024 + 128 * j, kv_order(i >> 1, j, 0));
        else tma_load_3d(sb + OFF_A + i * SLOT, &P.mx, bar, kv_order(i, j, 0) * 64, cta_m(vb) * 64, 0);
      }
    }
  }
  if (tid == 0) TS(6, 0);
  __syncthreads();
  if (tid == 0) TS(6, 2);
  if (warp < 4) {
    reg_dealloc<PREGS>();
    if (warp & 2) helper(P, sb, warp & 1, vb);
    else if (warp & 1) a_loader(P, sb, vb);
    else b_producer(P, sb, vb);
  } else {
    reg_alloc<CREGS>();
    consumer(P, sb, (warp >> 2) - 1, vb);
  }
}

typedef CUresult (*EncodeFn)(CUtensorMap*, CUtensorMapDataType, cuuint32_t, void*, const cuuint64_t*, const cuuint64_t*,
                             const cuuint32_t*, const cuuint32_t*, CUtensorMapInterleave, CUtensorMapSwizzle,
                             CUtensorMapL2promotion, CUtensorMapFloatOOBfill);

void encode(EncodeFn fn, CUtensorMap* m, const void* ptr, int rank, const cuuint64_t* dims, const cuuint64_t* strides,
            const cuuint32_t* box, CUtensorMapSwizzle swz) {
  const cuuint32_t es[5] = {1, 1, 1, 1, 1};
  fn(m, CU_TENSOR_MAP_DATA_TYPE_BFLOAT16, rank, const_cast<void*>(ptr), dims, strides, box, es, CU_TENSOR_MAP_INTERLEAVE_NONE,
     swz, CU_TENSOR_MAP_L2_PROMOTION_L2_256B, CU_TENSOR_MAP_FLOAT_OOB_FILL_NONE);
}
void encode_w(EncodeFn fn, CUtensorMap* m, const void* ptr, int ncols, bool perm) {
  const cuuint64_t p = (cuuint64_t)ncols * 2, d[5] = {(cuuint64_t)ncols, 2, 4, 4, 32}, s[4] = {p, (perm ? 8 : 2) * p, (perm ? 2 : 8) * p, 32 * p};
  const cuuint32_t box[5] = {64, 2, 4, 4, 2};
  encode(fn, m, ptr, 5, d, s, box, CU_TENSOR_MAP_SWIZZLE_128B);
}

void encode_cs(EncodeFn fn, CUtensorMap* m, const void* ptr, int ncols) {
  const cuuint64_t d[2] = {(cuuint64_t)ncols, 1024}, s[1] = {(cuuint64_t)ncols * 2};
  const cuuint32_t box[2] = {32, 64};
  encode(fn, m, ptr, 2, d, s, box, CU_TENSOR_MAP_SWIZZLE_NONE);
}

}

extern "C" void kernel_launch(void* const* d_in, const int* in_sizes, int n_in, void* d_out, int out_size) {
  (void)in_sizes; (void)n_in; (void)out_size;
  void* fnp = nullptr;
  cudaDriverEntryPointQueryResult q;
  cudaGetDriverEntryPoint("cuTensorMapEncodeTiled", &fnp, cudaEnableDefault, &q);
  EncodeFn fn = (EncodeFn)fnp;
  Params P;
  {
    const cuuint64_t dims[3] = {1024, 1024, 2}, strides[2] = {4096, 2048};
    const cuuint32_t box[3] = {64, 64, 2};
    encode(fn, &P.mx, d_in[0], 3, dims, strides, box, CU_TENSOR_MAP_SWIZZLE_128B);
  }
  P.out = (uint4*)d_out;
  encode_w(fn, &P.mw[0], d_in[1], 3072, false);
  encode_w(fn, &P.mw[1], d_in[4], 3072, true);
  encode_w(fn, &P.mw[2], d_in[1], 3072, true);
  encode_w(fn, &P.mwo[0], d_in[2], 1024, true);
  encode_w(fn, &P.mwo[1], d_in[6], 1024, false);
  encode_cs(fn, &P.mcs[0], d_in[1], 3072);
  encode_cs(fn, &P.mcs[1], d_in[4], 3072);
  {
    const cuuint64_t dims[2] = {32, 1024}, strides[1] = {64};
    const cuuint32_t box[2] = {32, 128};
    encode(fn, &P.mwphi, d_in[5], 2, dims, strides, box, CU_TENSOR_MAP_SWIZZLE_64B);
  }
  cudaFuncSetAttribute(fused_kernel, cudaFuncAttributeMaxDynamicSharedMemorySize, SMEM_BYTES);
  fused_kernel<<<NCTA, NTHREADS, SMEM_BYTES, cudaStreamPerThread>>>(P);
}
```

```cpp
#include <cuda_runtime.h>
#include <cuda_bf16.h>
#include <cuda.h>
#include <stdint.h>

namespace {

__device__ __forceinline__ void wgmma_ss_n256(float (&d)[128], uint32_t da, uint32_t ha, uint32_t db, int sd) {
  asm volatile("{\n.reg .pred p;\n.reg .b64 a, b;\nsetp.ne.b32 p, %130, 0;\nmov.b64 a, {%128, %131};\nmov.b64 b, {%129, 0x40000040};\n"
    "wgmma.mma_async.sync.aligned.m64n256k16.f32.bf16.bf16 {%0,%1,%2,%3,%4,%5,%6,%7,%8,%9,%10,%11,%12,%13,%14,%15,%16,%17,%18,%19,%20,%21,%22,%23,%24,%25,%26,%27,%28,%29,%30,%31,%32,%33,%34,%35,%36,%37,%38,%39,%40,%41,%42,%43,%44,%45,%46,%47,%48,%49,%50,%51,%52,%53,%54,%55,%56,%57,%58,%59,%60,%61,%62,%63,%64,%65,%66,%67,%68,%69,%70,%71,%72,%73,%74,%75,%76,%77,%78,%79,%80,%81,%82,%83,%84,%85,%86,%87,%88,%89,%90,%91,%92,%93,%94,%95,%96,%97,%98,%99,%100,%101,%102,%103,%104,%105,%106,%107,%108,%109,%110,%111,%112,%113,%114,%115,%116,%117,%118,%119,%120,%121,%122,%123,%124,%125,%126,%127}, a, b, p, 1, 1, 0, 1;\n}\n"
    : "+f"(d[0]),"+f"(d[1]),"+f"(d[2]),"+f"(d[3]),"+f"(d[4]),"+f"(d[5]),"+f"(d[6]),"+f"(d[7]),"+f"(d[8]),"+f"(d[9]),"+f"(d[10]),"+f"(d[11]),"+f"(d[12]),"+f"(d[13]),"+f"(d[14]),"+f"(d[15]),"+f"(d[16]),"+f"(d[17]),"+f"(d[18]),"+f"(d[19]),"+f"(d[20]),"+f"(d[21]),"+f"(d[22]),"+f"(d[23]),"+f"(d[24]),"+f"(d[25]),"+f"(d[26]),"+f"(d[27]),"+f"(d[28]),"+f"(d[29]),"+f"(d[30]),"+f"(d[31]),"+f"(d[32]),"+f"(d[33]),"+f"(d[34]),"+f"(d[35]),"+f"(d[36]),"+f"(d[37]),"+f"(d[38]),"+f"(d[39]),"+f"(d[40]),"+f"(d[41]),"+f"(d[42]),"+f"(d[43]),"+f"(d[44]),"+f"(d[45]),"+f"(d[46]),"+f"(d[47]),"+f"(d[48]),"+f"(d[49]),"+f"(d[50]),"+f"(d[51]),"+f"(d[52]),"+f"(d[53]),"+f"(d[54]),"+f"(d[55]),"+f"(d[56]),"+f"(d[57]),"+f"(d[58]),"+f"(d[59]),"+f"(d[60]),"+f"(d[61]),"+f"(d[62]),"+f"(d[63]),"+f"(d[64]),"+f"(d[65]),"+f"(d[66]),"+f"(d[67]),"+f"(d[68]),"+f"(d[69]),"+f"(d[70]),"+f"(d[71]),"+f"(d[72]),"+f"(d[73]),"+f"(d[74]),"+f"(d[75]),"+f"(d[76]),"+f"(d[77]),"+f"(d[78]),"+f"(d[79]),"+f"(d[80]),"+f"(d[81]),"+f"(d[82]),"+f"(d[83]),"+f"(d[84]),"+f"(d[85]),"+f"(d[86]),"+f"(d[87]),"+f"(d[88]),"+f"(d[89]),"+f"(d[90]),"+f"(d[91]),"+f"(d[92]),"+f"(d[93]),"+f"(d[94]),"+f"(d[95]),"+f"(d[96]),"+f"(d[97]),"+f"(d[98]),"+f"(d[99]),"+f"(d[100]),"+f"(d[101]),"+f"(d[102]),"+f"(d[103]),"+f"(d[104]),"+f"(d[105]),"+f"(d[106]),"+f"(d[107]),"+f"(d[108]),"+f"(d[109]),"+f"(d[110]),"+f"(d[111]),"+f"(d[112]),"+f"(d[113]),"+f"(d[114]),"+f"(d[115]),"+f"(d[116]),"+f"(d[117]),"+f"(d[118]),"+f"(d[119]),"+f"(d[120]),"+f"(d[121]),"+f"(d[122]),"+f"(d[123]),"+f"(d[124]),"+f"(d[125]),"+f"(d[126]),"+f"(d[127])
    : "r"(da), "r"(db), "r"(sd), "r"(ha));
}
__device__ __forceinline__ void wgmma_ss_n128(float (&d)[64], uint32_t da, uint32_t ha, uint32_t db, int sd) {
  asm volatile("{\n.reg .pred p;\n.reg .b64 a, b;\nsetp.ne.b32 p, %66, 0;\nmov.b64 a, {%64, %67};\nmov.b64 b, {%65, 0x40000040};\n"
    "wgmma.mma_async.sync.aligned.m64n128k16.f32.bf16.bf16 {%0,%1,%2,%3,%4,%5,%6,%7,%8,%9,%10,%11,%12,%13,%14,%15,%16,%17,%18,%19,%20,%21,%22,%23,%24,%25,%26,%27,%28,%29,%30,%31,%32,%33,%34,%35,%36,%37,%38,%39,%40,%41,%42,%43,%44,%45,%46,%47,%48,%49,%50,%51,%52,%53,%54,%55,%56,%57,%58,%59,%60,%61,%62,%63}, a, b, p, 1, 1, 0, 1;\n}\n"
    : "+f"(d[0]),"+f"(d[1]),"+f"(d[2]),"+f"(d[3]),"+f"(d[4]),"+f"(d[5]),"+f"(d[6]),"+f"(d[7]),"+f"(d[8]),"+f"(d[9]),"+f"(d[10]),"+f"(d[11]),"+f"(d[12]),"+f"(d[13]),"+f"(d[14]),"+f"(d[15]),"+f"(d[16]),"+f"(d[17]),"+f"(d[18]),"+f"(d[19]),"+f"(d[20]),"+f"(d[21]),"+f"(d[22]),"+f"(d[23]),"+f"(d[24]),"+f"(d[25]),"+f"(d[26]),"+f"(d[27]),"+f"(d[28]),"+f"(d[29]),"+f"(d[30]),"+f"(d[31]),"+f"(d[32]),"+f"(d[33]),"+f"(d[34]),"+f"(d[35]),"+f"(d[36]),"+f"(d[37]),"+f"(d[38]),"+f"(d[39]),"+f"(d[40]),"+f"(d[41]),"+f"(d[42]),"+f"(d[43]),"+f"(d[44]),"+f"(d[45]),"+f"(d[46]),"+f"(d[47]),"+f"(d[48]),"+f"(d[49]),"+f"(d[50]),"+f"(d[51]),"+f"(d[52]),"+f"(d[53]),"+f"(d[54]),"+f"(d[55]),"+f"(d[56]),"+f"(d[57]),"+f"(d[58]),"+f"(d[59]),"+f"(d[60]),"+f"(d[61]),"+f"(d[62]),"+f"(d[63])
    : "r"(da), "r"(db), "r"(sd), "r"(ha));
}
__device__ __forceinline__ void wgmma_ss_n40_tt(float (&d)[20], uint32_t da, uint32_t db, int sd) {
  asm volatile("{\n.reg .pred p;\n.reg .b64 a, b;\nsetp.ne.b32 p, %22, 0;\nmov.b64 a, {%20, 0x40000040};\nmov.b64 b, {%21, 0x8};\n"
    "wgmma.mma_async.sync.aligned.m64n40k16.f32.bf16.bf16 {%0,%1,%2,%3,%4,%5,%6,%7,%8,%9,%10,%11,%12,%13,%14,%15,%16,%17,%18,%19}, a, b, p, 1, 1, 1, 1;\n}\n"
    : "+f"(d[0]),"+f"(d[1]),"+f"(d[2]),"+f"(d[3]),"+f"(d[4]),"+f"(d[5]),"+f"(d[6]),"+f"(d[7]),"+f"(d[8]),"+f"(d[9]),"+f"(d[10]),"+f"(d[11]),"+f"(d[12]),"+f"(d[13]),"+f"(d[14]),"+f"(d[15]),"+f"(d[16]),"+f"(d[17]),"+f"(d[18]),"+f"(d[19])
    : "r"(da), "r"(db), "r"(sd));
}
__device__ __forceinline__ void wgmma_ss_n32(float (&d)[16], uint32_t da, uint32_t db, int sd) {
  asm volatile("{\n.reg .pred p;\n.reg .b64 a, b;\nsetp.ne.b32 p, %18, 0;\nmov.b64 a, {%16, 0x40000040};\nmov.b64 b, {%17, 0x80000020};\n"
    "wgmma.mma_async.sync.aligned.m64n32k16.f32.bf16.bf16 {%0,%1,%2,%3,%4,%5,%6,%7,%8,%9,%10,%11,%12,%13,%14,%15}, a, b, p, 1, 1, 0, 1;\n}\n"
    : "+f"(d[0]),"+f"(d[1]),"+f"(d[2]),"+f"(d[3]),"+f"(d[4]),"+f"(d[5]),"+f"(d[6]),"+f"(d[7]),"+f"(d[8]),"+f"(d[9]),"+f"(d[10]),"+f"(d[11]),"+f"(d[12]),"+f"(d[13]),"+f"(d[14]),"+f"(d[15])
    : "r"(da), "r"(db), "r"(sd));
}
__device__ __forceinline__ void wgmma_rs_n40(float (&d)[20], uint32_t a0, uint32_t a1, uint32_t a2, uint32_t a3, uint32_t db, int sd) {
  asm volatile("{\n.reg .pred p;\n.reg .b64 b;\nsetp.ne.b32 p, %25, 0;\nmov.b64 b, {%24, 0x10};\n"
    "wgmma.mma_async.sync.aligned.m64n40k16.f32.bf16.bf16 {%0,%1,%2,%3,%4,%5,%6,%7,%8,%9,%10,%11,%12,%13,%14,%15,%16,%17,%18,%19}, {%20,%21,%22,%23}, b, p, 1, 1, 1;\n}\n"
    : "+f"(d[0]),"+f"(d[1]),"+f"(d[2]),"+f"(d[3]),"+f"(d[4]),"+f"(d[5]),"+f"(d[6]),"+f"(d[7]),"+f"(d[8]),"+f"(d[9]),"+f"(d[10]),"+f"(d[11]),"+f"(d[12]),"+f"(d[13]),"+f"(d[14]),"+f"(d[15]),"+f"(d[16]),"+f"(d[17]),"+f"(d[18]),"+f"(d[19])
    : "r"(a0), "r"(a1), "r"(a2), "r"(a3), "r"(db), "r"(sd));
}
__device__ __forceinline__ void wgmma_r1_n256(float (&d)[128], uint32_t da, uint32_t db, int sd) {
  asm volatile("{\n.reg .pred p;\n.reg .b64 a, b;\nsetp.ne.b32 p, %130, 0;\nmov.b64 a, {%128, 0x8};\nmov.b64 b, {%129, 0x6};\n"
    "wgmma.mma_async.sync.aligned.m64n256k16.f32.bf16.bf16 {%0,%1,%2,%3,%4,%5,%6,%7,%8,%9,%10,%11,%12,%13,%14,%15,%16,%17,%18,%19,%20,%21,%22,%23,%24,%25,%26,%27,%28,%29,%30,%31,%32,%33,%34,%35,%36,%37,%38,%39,%40,%41,%42,%43,%44,%45,%46,%47,%48,%49,%50,%51,%52,%53,%54,%55,%56,%57,%58,%59,%60,%61,%62,%63,%64,%65,%66,%67,%68,%69,%70,%71,%72,%73,%74,%75,%76,%77,%78,%79,%80,%81,%82,%83,%84,%85,%86,%87,%88,%89,%90,%91,%92,%93,%94,%95,%96,%97,%98,%99,%100,%101,%102,%103,%104,%105,%106,%107,%108,%109,%110,%111,%112,%113,%114,%115,%116,%117,%118,%119,%120,%121,%122,%123,%124,%125,%126,%127}, a, b, p, 1, 1, 0, 1;\n}\n"
    : "+f"(d[0]),"+f"(d[1]),"+f"(d[2]),"+f"(d[3]),"+f"(d[4]),"+f"(d[5]),"+f"(d[6]),"+f"(d[7]),"+f"(d[8]),"+f"(d[9]),"+f"(d[10]),"+f"(d[11]),"+f"(d[12]),"+f"(d[13]),"+f"(d[14]),"+f"(d[15]),"+f"(d[16]),"+f"(d[17]),"+f"(d[18]),"+f"(d[19]),"+f"(d[20]),"+f"(d[21]),"+f"(d[22]),"+f"(d[23]),"+f"(d[24]),"+f"(d[25]),"+f"(d[26]),"+f"(d[27]),"+f"(d[28]),"+f"(d[29]),"+f"(d[30]),"+f"(d[31]),"+f"(d[32]),"+f"(d[33]),"+f"(d[34]),"+f"(d[35]),"+f"(d[36]),"+f"(d[37]),"+f"(d[38]),"+f"(d[39]),"+f"(d[40]),"+f"(d[41]),"+f"(d[42]),"+f"(d[43]),"+f"(d[44]),"+f"(d[45]),"+f"(d[46]),"+f"(d[47]),"+f"(d[48]),"+f"(d[49]),"+f"(d[50]),"+f"(d[51]),"+f"(d[52]),"+f"(d[53]),"+f"(d[54]),"+f"(d[55]),"+f"(d[56]),"+f"(d[57]),"+f"(d[58]),"+f"(d[59]),"+f"(d[60]),"+f"(d[61]),"+f"(d[62]),"+f"(d[63]),"+f"(d[64]),"+f"(d[65]),"+f"(d[66]),"+f"(d[67]),"+f"(d[68]),"+f"(d[69]),"+f"(d[70]),"+f"(d[71]),"+f"(d[72]),"+f"(d[73]),"+f"(d[74]),"+f"(d[75]),"+f"(d[76]),"+f"(d[77]),"+f"(d[78]),"+f"(d[79]),"+f"(d[80]),"+f"(d[81]),"+f"(d[82]),"+f"(d[83]),"+f"(d[84]),"+f"(d[85]),"+f"(d[86]),"+f"(d[87]),"+f"(d[88]),"+f"(d[89]),"+f"(d[90]),"+f"(d[91]),"+f"(d[92]),"+f"(d[93]),"+f"(d[94]),"+f"(d[95]),"+f"(d[96]),"+f"(d[97]),"+f"(d[98]),"+f"(d[99]),"+f"(d[100]),"+f"(d[101]),"+f"(d[102]),"+f"(d[103]),"+f"(d[104]),"+f"(d[105]),"+f"(d[106]),"+f"(d[107]),"+f"(d[108]),"+f"(d[109]),"+f"(d[110]),"+f"(d[111]),"+f"(d[112]),"+f"(d[113]),"+f"(d[114]),"+f"(d[115]),"+f"(d[116]),"+f"(d[117]),"+f"(d[118]),"+f"(d[119]),"+f"(d[120]),"+f"(d[121]),"+f"(d[122]),"+f"(d[123]),"+f"(d[124]),"+f"(d[125]),"+f"(d[126]),"+f"(d[127])
    : "r"(da), "r"(db), "r"(sd));
}
__device__ __forceinline__ void wgmma_r1_n128(float (&d)[64], uint32_t da, uint32_t db, int sd) {
  asm volatile("{\n.reg .pred p;\n.reg .b64 a, b;\nsetp.ne.b32 p, %66, 0;\nmov.b64 a, {%64, 0x8};\nmov.b64 b, {%65, 0x6};\n"
    "wgmma.mma_async.sync.aligned.m64n128k16.f32.bf16.bf16 {%0,%1,%2,%3,%4,%5,%6,%7,%8,%9,%10,%11,%12,%13,%14,%15,%16,%17,%18,%19,%20,%21,%22,%23,%24,%25,%26,%27,%28,%29,%30,%31,%32,%33,%34,%35,%36,%37,%38,%39,%40,%41,%42,%43,%44,%45,%46,%47,%48,%49,%50,%51,%52,%53,%54,%55,%56,%57,%58,%59,%60,%61,%62,%63}, a, b, p, 1, 1, 0, 1;\n}\n"
    : "+f"(d[0]),"+f"(d[1]),"+f"(d[2]),"+f"(d[3]),"+f"(d[4]),"+f"(d[5]),"+f"(d[6]),"+f"(d[7]),"+f"(d[8]),"+f"(d[9]),"+f"(d[10]),"+f"(d[11]),"+f"(d[12]),"+f"(d[13]),"+f"(d[14]),"+f"(d[15]),"+f"(d[16]),"+f"(d[17]),"+f"(d[18]),"+f"(d[19]),"+f"(d[20]),"+f"(d[21]),"+f"(d[22]),"+f"(d[23]),"+f"(d[24]),"+f"(d[25]),"+f"(d[26]),"+f"(d[27]),"+f"(d[28]),"+f"(d[29]),"+f"(d[30]),"+f"(d[31]),"+f"(d[32]),"+f"(d[33]),"+f"(d[34]),"+f"(d[35]),"+f"(d[36]),"+f"(d[37]),"+f"(d[38]),"+f"(d[39]),"+f"(d[40]),"+f"(d[41]),"+f"(d[42]),"+f"(d[43]),"+f"(d[44]),"+f"(d[45]),"+f"(d[46]),"+f"(d[47]),"+f"(d[48]),"+f"(d[49]),"+f"(d[50]),"+f"(d[51]),"+f"(d[52]),"+f"(d[53]),"+f"(d[54]),"+f"(d[55]),"+f"(d[56]),"+f"(d[57]),"+f"(d[58]),"+f"(d[59]),"+f"(d[60]),"+f"(d[61]),"+f"(d[62]),"+f"(d[63])
    : "r"(da), "r"(db), "r"(sd));
}

__device__ __forceinline__ uint32_t smem_u32(const void* p) { return (uint32_t)__cvta_generic_to_shared(p); }
__device__ __forceinline__ void mbar_init(uint32_t bar, uint32_t cnt) { asm volatile("mbarrier.init.shared::cta.b64 [%0], %1;" ::"r"(bar), "r"(cnt)); }
__device__ __forceinline__ void mbar_expect_tx(uint32_t bar, uint32_t bytes) { asm volatile("mbarrier.arrive.expect_tx.shared::cta.b64 _, [%0], %1;" ::"r"(bar), "r"(bytes) : "memory"); }
__device__ __forceinline__ void mbar_arrive(uint32_t bar) { asm volatile("mbarrier.arrive.shared::cta.b64 _, [%0];" ::"r"(bar) : "memory"); }
__device__ __forceinline__ void mbar_arrive_n(uint32_t bar, uint32_t n) { asm volatile("mbarrier.arrive.shared::cta.b64 _, [%0], %1;" ::"r"(bar), "r"(n) : "memory"); }
__device__ __forceinline__ void mbar_wait(uint32_t bar, uint32_t parity) {
  asm volatile("{\n.reg .pred p;\nLAB_WAIT:\nmbarrier.try_wait.parity.shared::cta.b64 p, [%0], %1;\n@p bra DONE;\nbra LAB_WAIT;\nDONE:\n}" ::"r"(bar), "r"(parity) : "memory");
}
__device__ __forceinline__ void mbar_wait2(uint32_t a, uint32_t pa, uint32_t b, uint32_t pb) {
  asm volatile("{\n.reg .pred p, q;\nLAB_WAIT:\nmbarrier.try_wait.parity.shared::cta.b64 p, [%0], %1;\nmbarrier.try_wait.parity.shared::cta.b64 q, [%2], %3;\n"
               "and.pred p, p, q;\n@p bra DONE;\nbra LAB_WAIT;\nDONE:\n}" ::"r"(a), "r"(pa), "r"(b), "r"(pb) : "memory");
}
__device__ __forceinline__ void mbar_wait3(uint32_t a, uint32_t pa, uint32_t b, uint32_t pb) {
  asm volatile("{\n.reg .pred p, q, r;\nLAB_WAIT:\nmbarrier.try_wait.parity.shared::cta.b64 p, [%0], %1;\nmbarrier.try_wait.parity.shared::cta.b64 q, [%2], %3;\n"
               "mbarrier.try_wait.parity.shared::cta.b64 r, [%2+8], %3;\nand.pred p, p, q;\nand.pred p, p, r;\n@p bra DONE;\nbra LAB_WAIT;\nDONE:\n}" ::"r"(a), "r"(pa), "r"(b), "r"(pb) : "memory");
}
__device__ __forceinline__ bool mbar_probe2(uint32_t a, uint32_t pa, uint32_t b, uint32_t pb) {
  uint32_t ok;
  asm volatile("{\n.reg .pred p, q;\nmbarrier.test_wait.parity.shared::cta.b64 p, [%1], %2;\nmbarrier.test_wait.parity.shared::cta.b64 q, [%3], %4;\n"
               "and.pred p, p, q;\nselp.u32 %0, 1, 0, p;\n}" : "=r"(ok) : "r"(a), "r"(pa), "r"(b), "r"(pb) : "memory");
  return ok != 0;
}
__device__ __forceinline__ void tma_load_3d(uint32_t dst, const CUtensorMap* tm, uint32_t bar, int c0, int c1, int c2) {
  asm volatile("cp.async.bulk.tensor.3d.shared::cluster.global.mbarrier::complete_tx::bytes [%0], [%1, {%3, %4, %5}], [%2];"
               ::"r"(dst), "l"(tm), "r"(bar), "r"(c0), "r"(c1), "r"(c2) : "memory");
}
__device__ __forceinline__ void tma_load_2d(uint32_t dst, const CUtensorMap* tm, uint32_t bar, int c0, int c1) {
  asm volatile("cp.async.bulk.tensor.2d.shared::cluster.global.mbarrier::complete_tx::bytes [%0], [%1, {%3, %4}], [%2];"
               ::"r"(dst), "l"(tm), "r"(bar), "r"(c0), "r"(c1) : "memory");
}
__device__ __forceinline__ void tma_load_w(uint32_t dst, const CUtensorMap* tm, uint32_t bar, int col, int kb) {
#pragma unroll
  for (int q = 0; q < 2; q++)
    asm volatile("cp.async.bulk.tensor.5d.shared::cluster.global.mbarrier::complete_tx::bytes [%0], [%1, {%3, %4, %4, %4, %5}], [%2];"
                 ::"r"(dst + q * 8192), "l"(tm), "r"(bar), "r"(col + q * 64), "r"(0), "r"(2 * kb) : "memory");
}
__device__ __forceinline__ void tma_prefetch_w(const CUtensorMap* tm, int col, int kb) {
#pragma unroll
  for (int q = 0; q < 2; q++)
    asm volatile("cp.async.bulk.prefetch.tensor.5d.L2.global [%0, {%1, %2, %2, %2, %3}];" ::"l"(tm), "r"(col + q * 64), "r"(0), "r"(2 * kb) : "memory");
}
__device__ __forceinline__ void bulk_load(uint32_t dst, const void* g, uint32_t bytes, uint32_t bar) {
  asm volatile("cp.async.bulk.shared::cluster.global.mbarrier::complete_tx::bytes [%0], [%1], %2, [%3];" ::"r"(dst), "l"(g), "r"(bytes), "r"(bar) : "memory");
}
__device__ __forceinline__ void prefetch_map(const CUtensorMap* tm) { asm volatile("prefetch.tensormap [%0];" ::"l"(tm) : "memory"); }
__device__ __forceinline__ void fence_async_smem() { asm volatile("fence.proxy.async.shared::cta;" ::: "memory"); }
__device__ __forceinline__ void fence_async_global() { asm volatile("fence.proxy.async.global;" ::: "memory"); }
__device__ __forceinline__ void fence_gpu() { asm volatile("fence.release.gpu;" ::: "memory"); }
__device__ __forceinline__ void st_flag(unsigned* p, unsigned v) { asm volatile("st.relaxed.gpu.global.u32 [%0], %1;" ::"l"(p), "r"(v) : "memory"); }
__device__ __forceinline__ unsigned ld_flag(const unsigned* p) { unsigned v; asm volatile("ld.relaxed.gpu.global.u32 %0, [%1];" : "=r"(v) : "l"(p) : "memory"); return v; }
__device__ __forceinline__ uint4 ldcg4(const void* p) { uint4 v; asm volatile("ld.global.cg.v4.u32 {%0,%1,%2,%3}, [%4];" : "=r"(v.x), "=r"(v.y), "=r"(v.z), "=r"(v.w) : "l"(p)); return v; }
__device__ __forceinline__ uint4 ld_pkt(const uint4* p) {
  uint4 v; asm volatile("{\n.reg .b128 t;\nld.relaxed.gpu.global.b128 t, [%4];\nmov.b128 {%0,%1,%2,%3}, t;\n}" : "=r"(v.x), "=r"(v.y), "=r"(v.z), "=r"(v.w) : "l"(p) : "memory"); return v;
}
__device__ __forceinline__ void st_pkt(uint4* p, uint32_t a, uint32_t b, uint32_t c, uint32_t tag) {
  asm volatile("{\n.reg .b128 t;\nmov.b128 t, {%1,%2,%3,%4};\nst.relaxed.gpu.global.b128 [%0], t;\n}" ::"l"(p), "r"(a), "r"(b), "r"(c), "r"(tag) : "memory");
}
__device__ __forceinline__ void st_v4(uint4* p, uint32_t a, uint32_t b, uint32_t c, uint32_t d) { asm volatile("st.relaxed.gpu.global.v4.u32 [%0], {%1,%2,%3,%4};" ::"l"(p), "r"(a), "r"(b), "r"(c), "r"(d) : "memory"); }
__device__ __forceinline__ void stg128(uint4* p, uint4 v) { asm volatile("st.global.v4.u32 [%0], {%1,%2,%3,%4};" ::"l"(p), "r"(v.x), "r"(v.y), "r"(v.z), "r"(v.w) : "memory"); }
__device__ __forceinline__ void sts32(uint32_t addr, uint32_t a) { asm volatile("st.shared.u32 [%0], %1;" ::"r"(addr), "r"(a) : "memory"); }
__device__ __forceinline__ void sts64(uint32_t addr, uint32_t a, uint32_t b) { asm volatile("st.shared.v2.u32 [%0], {%1,%2};" ::"r"(addr), "r"(a), "r"(b) : "memory"); }
__device__ __forceinline__ uint32_t mul2(uint32_t a, uint32_t b) { uint32_t r; asm("mul.rn.bf16x2 %0, %1, %2;" : "=r"(r) : "r"(a), "r"(b)); return r; }
__device__ __forceinline__ uint32_t add2(uint32_t a, uint32_t b) { uint32_t r; asm("add.rn.bf16x2 %0, %1, %2;" : "=r"(r) : "r"(a), "r"(b)); return r; }
__device__ __forceinline__ bool elect() {
  uint32_t p; asm volatile("{\n.reg .pred q;\nelect.sync _|q, 0xffffffff;\nselp.u32 %0, 1, 0, q;\n}" : "=r"(p)); return p != 0;
}
__device__ __forceinline__ void wgmma_fence() { asm volatile("wgmma.fence.sync.aligned;" ::: "memory"); }
__device__ __forceinline__ void wgmma_commit() { asm volatile("wgmma.commit_group.sync.aligned;" ::: "memory"); }
template <int N> __device__ __forceinline__ void wgmma_wait() { asm volatile("wgmma.wait_group.sync.aligned %0;" ::"n"(N) : "memory"); }
template <int N> __device__ __forceinline__ void fence_regs(float (&d)[N]) {
#pragma unroll
  for (int i = 0; i < N; i++) asm volatile("" : "+f"(d[i])::"memory");
}
template <int R> __device__ __forceinline__ void reg_alloc() { asm volatile("setmaxnreg.inc.sync.aligned.u32 %0;" ::"n"(R)); }
template <int R> __device__ __forceinline__ void reg_dealloc() { asm volatile("setmaxnreg.dec.sync.aligned.u32 %0;" ::"n"(R)); }
__device__ __forceinline__ void wg_bar(int w) { asm volatile("bar.sync %0, 128;" ::"r"(w + 1) : "memory"); }
__device__ __forceinline__ constexpr uint32_t desc_lo(uint32_t addr, uint32_t lbo) { return (addr >> 4) + ((lbo >> 4) << 16); }
__device__ __forceinline__ uint32_t pack2(float lo, float hi) { uint32_t r; asm("cvt.rn.bf16x2.f32 %0, %1, %2;" : "=r"(r) : "f"(hi), "f"(lo)); return r; }
__device__ __forceinline__ float lo16(uint32_t v) { return __uint_as_float(v << 16); }
__device__ __forceinline__ float hi16(uint32_t v) { return __uint_as_float(v & 0xFFFF0000u); }
__device__ __forceinline__ float ex2(float x) { float r; asm("ex2.approx.ftz.f32 %0, %1;" : "=f"(r) : "f"(x)); return r; }
__device__ __forceinline__ float rcp(float x) { float r; asm("rcp.approx.ftz.f32 %0, %1;" : "=f"(r) : "f"(x)); return r; }
__device__ __forceinline__ uint32_t movm(uint32_t a) { uint32_t d; asm volatile("movmatrix.sync.aligned.m8n8.trans.b16 %0, %1;" : "=r"(d) : "r"(a)); return d; }
__device__ __forceinline__ void stsm4(uint32_t addr, uint32_t a, uint32_t b, uint32_t c, uint32_t d) {
  asm volatile("stmatrix.sync.aligned.m8n8.x4.shared.b16 [%0], {%1,%2,%3,%4};" ::"r"(addr), "r"(a), "r"(b), "r"(c), "r"(d) : "memory");
}
__device__ __forceinline__ void ldsm4(uint32_t addr, uint32_t (&r)[4]) {
  asm volatile("ldmatrix.sync.aligned.m8n8.x4.shared.b16 {%0,%1,%2,%3}, [%4];" : "=r"(r[0]), "=r"(r[1]), "=r"(r[2]), "=r"(r[3]) : "r"(addr) : "memory");
}
__device__ __forceinline__ void sts128(uint32_t addr, uint32_t a, uint32_t b, uint32_t c, uint32_t d) {
  asm volatile("st.shared.v4.u32 [%0], {%1,%2,%3,%4};" ::"r"(addr), "r"(a), "r"(b), "r"(c), "r"(d) : "memory");
}
__device__ __forceinline__ void lds128(uint32_t addr, uint32_t& a, uint32_t& b, uint32_t& c, uint32_t& d) {
  asm volatile("ld.shared.v4.u32 {%0,%1,%2,%3}, [%4];" : "=r"(a), "=r"(b), "=r"(c), "=r"(d) : "r"(addr) : "memory");
}
__device__ __forceinline__ float lds32f(uint32_t addr) { float v; asm volatile("ld.shared.f32 %0, [%1];" : "=f"(v) : "r"(addr) : "memory"); return v; }
__device__ __forceinline__ float2 lds64f(uint32_t addr) { float2 v; asm volatile("ld.shared.v2.f32 {%0,%1}, [%2];" : "=f"(v.x), "=f"(v.y) : "r"(addr) : "memory"); return v; }
__device__ __forceinline__ void mma16816(float (&d)[4], uint32_t a0, uint32_t a1, uint32_t a2, uint32_t a3, uint32_t b0, uint32_t b1) {
  asm("mma.sync.aligned.m16n8k16.row.col.f32.bf16.bf16.f32 {%0,%1,%2,%3}, {%4,%5,%6,%7}, {%8,%9}, {%0,%1,%2,%3};"
      : "+f"(d[0]), "+f"(d[1]), "+f"(d[2]), "+f"(d[3]) : "r"(a0), "r"(a1), "r"(a2), "r"(a3), "r"(b0), "r"(b1));
}
__device__ __forceinline__ void mma1688(float (&d)[4], uint32_t a0, uint32_t a1, uint32_t b0) {
  asm("mma.sync.aligned.m16n8k8.row.col.f32.bf16.bf16.f32 {%0,%1,%2,%3}, {%4,%5}, {%6}, {%0,%1,%2,%3};"
      : "+f"(d[0]), "+f"(d[1]), "+f"(d[2]), "+f"(d[3]) : "r"(a0), "r"(a1), "r"(b0));
}

__device__ __forceinline__ float qsum(float v) { v += __shfl_xor_sync(0xffffffffu, v, 1); v += __shfl_xor_sync(0xffffffffu, v, 2); return v; }

constexpr int NCTA = 132;
#define NB_ 6
#define NA_ 5
constexpr int NB = NB_;
constexpr int NA = NA_;
constexpr uint32_t SLOT = 16384;
constexpr uint32_t SB = 1024;
constexpr uint32_t OFF_B = 0;
constexpr uint32_t OFF_A = NB * SLOT;
constexpr uint32_t OFF_S = OFF_A + NA * SLOT;
constexpr uint32_t OFF_T = OFF_S + 20480;
constexpr uint32_t OFF_CS = OFF_T + 24576;
constexpr uint32_t OFF_MR = OFF_CS + 4640;
constexpr uint32_t OFF_BAR = OFF_MR + 512;
constexpr uint32_t OFF_MA = OFF_S, OFF_MB = OFF_CS - 2048;
constexpr uint32_t BAR_FULLB = OFF_BAR;
constexpr uint32_t BAR_FULLA = BAR_FULLB + 64;
constexpr uint32_t BAR_EMPTYB = BAR_FULLA + 64;
constexpr uint32_t BAR_EMPTYA = BAR_EMPTYB + 64;
constexpr uint32_t BAR_SIGP = BAR_EMPTYA + 64;
constexpr uint32_t BAR_SIGT = BAR_SIGP + 24;
constexpr uint32_t BAR_STAT = BAR_SIGP + 64;
constexpr uint32_t BAR_HALO = BAR_STAT + 16;
constexpr uint32_t BAR_CS = BAR_HALO + 8;
constexpr uint32_t BAR_WPHI = BAR_CS + 16;
constexpr uint32_t BAR_KV = BAR_WPHI + 8;
constexpr uint32_t BAR_STG = BAR_KV + 16;
constexpr uint32_t BAR_EPOCH = BAR_STG + 48;
constexpr uint32_t BAR_LAND = OFF_BAR + 7 * 64;
constexpr uint32_t OFF_EPOCH = OFF_BAR + 8 * 64;
static_assert(BAR_EPOCH < BAR_LAND, "barriers");
constexpr uint32_t SMEM_BYTES = OFF_EPOCH + 8;
static_assert(SMEM_BYTES <= 232448 && NB % 2 == 0 && NB <= 8 && NA <= 6, "smem");

#define CREGS 224
#define PREGS 56
#define PF1 19
#define PF2 21
#define PRE_A 2
#define PRE_B 4
#define CSB 4
#define CSNEED 0xF001u
#define XR 1
#define PS0 1
#define PS1 3
#define PSW 0
#define SD 1000
#define KSPLIT 12
#define KEEP 16
#define NJ 3
#define KSL 1000
#define PSL 0
#define KVS 12
#define D2 2000
#define D3 1500
#define G0 50
#define MAP 3
#define PMAP 0x76321450u
#define ZO 0
#define XA 3
#define XS 1
#define CP 500
#define CD 0
#define S0 500
#define NS 2
#define XO 0
#define SW 2
#define SA 1
#define SB_ 4
#define XD 100
#define ND0 1
#define KC 8
#define CO 0
#define SE 500
#define PD 0
#define XD0 600
#define XD1 250
#define NDC 1
#define PD0 0
#define DEFER 3
#define DEFL 2
#define TSK 3
#define TSL 3
constexpr int NTHREADS = 384;

struct Params {
  CUtensorMap mx;
  CUtensorMap mw[3];
  CUtensorMap mwo[2];
  CUtensorMap mcs[2];
  CUtensorMap mwphi;
  uint4* out;
};

#define XBUF(L) 1
__device__ __align__(256) uint4 g_img[XBUF(3) + 1][16][16][1024];
__device__ __forceinline__ uint32_t img_code(bool isx, int L) { return isx ? (L & 1) | (L & 2) << 15 : ~L & 1; }
__device__ __forceinline__ uint32_t img_mask(bool isx) { return isx ? 0x10001u : 1u; }
__device__ __align__(256) uint4 g_wf[2][8][16][1024];
__device__ __align__(256) uint4 g_stats[16][2][8][32];
__device__ __align__(256) uint4 g_halo[16][8][2][256];
__device__ __align__(256) float g_cs[2][2][3072];
__device__ __align__(256) uint4 g_kvpart[8][16][2][544];
__device__ __align__(256) uint4 g_kvfin[8][16][80];
__device__ __align__(256) unsigned g_hint[16][32];
__device__ __align__(256) unsigned g_jflag[3][8][32];
__device__ unsigned g_ctr;
__device__ __forceinline__ unsigned vblock() {
  unsigned s;
  asm volatile("mov.u32 %0, %%smid;" : "=r"(s));
  const unsigned r = s & 1;
  s >>= 1;
  const unsigned t = s - 32, q = (t * 37) >> 8;
  const unsigned hi = s < 60 ? 12 + (t - 7 * q) * 8 + q : (s < 62 ? s + 4 : s - 58);
  unsigned b = 2 * (s < 32 ? (s & 7) * 8 + (s >> 3) : hi) + r;
  if (b < 128) b = (b & 15) | ((PMAP >> ((b >> 4) * 4)) & 7) << 4;
  if (s >= 62) b = 8 + 4 * r + s - 62;
  unsigned n;
  asm volatile("mov.u32 %0, %%nsmid;" : "=r"(n));
  return __shfl_sync(0xffffffffu, n == NCTA ? b : blockIdx.x, 0);
}
#define TS(who, id) do {} while (0)
#define TSW(id) do {} while (0)

#define TSH(id) do {} while (0)
#define TSMASK 0xFFFF
#define TSL_(a) do { if ((TSMASK >> (a)) & 1) TSW((a) + L * 12); } while (0)
__device__ __forceinline__ int cta_m(unsigned b) { return ((b >> 2) & 12) | (b & 3); }
__device__ __forceinline__ int cta_j(unsigned b) { return ((b >> 2) & 3) | ((b >> 4) & 4); }
struct Ring { uint32_t s, ph; };
template <int N> __device__ __forceinline__ void adv(Ring& r) { if (++r.s == N) { r.s = 0; r.ph ^= 1; } }
template <int N> __device__ __forceinline__ void rewind2(Ring& r) { if (r.s < 2) { r.s += N - 2; r.ph ^= 1; } else r.s -= 2; }
__device__ __forceinline__ int other_tile(int t, int j) { return (t == (j | 4) ? 7 : t) ^ (~j & 4); }
__device__ __forceinline__ int o_order(int i, int j) {
  if (i < 2) return 2 * j + i;
  const int odd = i >= 9;
  return 2 * other_tile(i - 2 - 7 * odd, j) + odd;
}
__device__ __forceinline__ int kv_order(int i, int j, int L) { return L > 0 ? o_order(i, j) : (i + 14 + 2 * (j & 4)) & 15; }

__device__ __forceinline__ unsigned poll_flags(const unsigned* f, int n, unsigned need, unsigned tag) {
  const int lane = threadIdx.x & 31;
  unsigned mask; int it = 0;
  do {
    unsigned v = lane < n ? ld_flag(f + lane) : 0u;
    mask = __ballot_sync(0xffffffffu, lane < n && (int)(v - tag) >= 0);
    if (++it > (1 << 22)) __trap();
  } while ((mask & need) != need);
  fence_async_global();
  return mask;
}
template <bool WAIT = true>
__device__ __forceinline__ unsigned get_tag(uint32_t sb) {
  if (WAIT) mbar_wait(sb + BAR_EPOCH, 0);
  unsigned t; asm volatile("ld.shared.u32 %0, [%1];" : "=r"(t) : "r"(sb + OFF_EPOCH) : "memory");
  return t;
}

__device__ __forceinline__ int lane_id() { int l; asm volatile("mov.u32 %0, %%laneid;" : "=r"(l)); return l; }
__device__ __forceinline__ unsigned seq4(unsigned tag, int L) { return 8u | ((tag & 1u) << 2) | (unsigned)L; }
constexpr float LOG2E = 1.4426950408889634f;

__device__ __forceinline__ float bb_fence(int never, const void* p = &g_ctr, uint32_t keep = 0) {
  while (never < 0) never = ld_flag((const unsigned*)p) + keep;
  return __int_as_float(never >> 30);
}
__device__ __forceinline__ uint32_t solid(uint32_t v) { return __shfl_sync(0xffffffffu, v, threadIdx.x & 31); }
template <class T> __device__ __forceinline__ T* solid(T* p) { return (T*)__shfl_sync(0xffffffffu, (unsigned long long)p, threadIdx.x & 31); }
constexpr uint32_t HA128 = 0x40000040u, HA64 = 0x80000040u;
struct Ctx {
  static constexpr uint32_t sb = SB;
  uint32_t ab, da0;
  int w, warp, lane, g, c;
  int goff;
  __device__ __forceinline__ int m() const { return goff >> 14; }
  __device__ __forceinline__ int j() const { return (goff >> 4) & 7; }
  bool elected;
  Ring ra, rb;
  uint32_t pa, pb;
  uint32_t ha, k2;
  uint32_t mrow, mxor, mhi;
  __device__ __forceinline__ uint32_t aslot(uint32_t s) const { return ab + s * SLOT; }
  __device__ __forceinline__ uint32_t fullA(uint32_t s) const { return sb + BAR_FULLA + s * 8; }
  __device__ __forceinline__ uint32_t fullB(uint32_t s) const { return sb + BAR_FULLB + s * 8; }
  __device__ __forceinline__ void releaseA(uint32_t s) const { if (elected) mbar_arrive(sb + BAR_EMPTYA + s * 8); }
  __device__ __forceinline__ void releaseB(uint32_t s) const { if (elected) mbar_arrive(sb + BAR_EMPTYB + s * 8); }
  __device__ __forceinline__ uint32_t maddr(uint32_t tile, uint32_t ch) const { return tile + mrow + (((ch + mhi) ^ mxor) << 4); }
  __device__ __forceinline__ uint32_t oo() const { return warp * 128 + g * 4 + (c ^ (g >> 1)); }
  __device__ __forceinline__ uint4* img(int b, int hp) const { return ip + (b * 256 + hp) * 1024; }
  uint4* ip;
  uint32_t so;
  __device__ __forceinline__ uint32_t held(int i) const { return ra.s + i < 2 ? ra.s + i + NA - 2 : ra.s + i - 2; }
};

template <int N, bool FIRST, bool O = true>
__device__ __forceinline__ void gemm_issue(float (&acc)[N / 2], Ctx& x, bool ready = false) {
  if (!ready) {
    if (N == 256) mbar_wait3(x.fullA(x.ra.s), x.ra.ph, x.fullB(x.rb.s), x.rb.ph);
    else mbar_wait2(x.fullA(x.ra.s), x.ra.ph, x.fullB(x.rb.s), x.rb.ph);
  }
  const uint32_t da = x.da0 + x.ra.s * (SLOT / 16), db = desc_lo(SB + OFF_B, 8192) + x.rb.s * (SLOT / 16);
  wgmma_fence();
#pragma unroll
  for (int k = 0; k < 4; k++) {
    const uint32_t a = da + (k >> 1) * (O ? 32 : x.k2) + (k & 1) * 2, ha = O ? HA64 : x.ha;
    if constexpr (N == 256) wgmma_ss_n256(acc, a, ha, db + 128 * k, !(FIRST && k == 0));
    else wgmma_ss_n128(acc, a, ha, db + 128 * k, !(FIRST && k == 0));
  }
  wgmma_commit();
}
template <int N>
__device__ __forceinline__ void gemm_next(Ctx& x) {
  x.pa = x.ra.s; x.pb = x.rb.s;
  if (N == 256) x.rb.s++;
  adv<NA>(x.ra); adv<NB>(x.rb);
}
template <int N>
__device__ __forceinline__ void gemm_release(Ctx& x, bool relA) {
  if (relA) x.releaseA(x.pa);
  x.releaseB(x.pb);
  if (N == 256) x.releaseB(x.pb + 1);
}
template <int N>
__device__ __forceinline__ void gemm_retire(Ctx& x, bool relA) { wgmma_wait<1>(); gemm_release<N>(x, relA); gemm_next<N>(x); }
template <bool O = true>
__device__ __forceinline__ void gemm_run(float (&acc)[64], Ctx& x, int n, int hold, int n4 = 0) {
  bool ready = false;
#pragma unroll 1
  for (; n > 0; n--) {
    gemm_issue<128, false, O>(acc, x, ready);
    const uint32_t pa = x.pa, pb = x.pb;
    gemm_next<128>(x);
    ready = mbar_probe2(x.fullA(x.ra.s), x.ra.ph, x.fullB(x.rb.s), x.rb.ph);
    wgmma_wait<1>();
    if (n > hold) x.releaseA(pa);
    x.releaseB(pb);
  }
}
__device__ __forceinline__ void gemm_end(float (&acc)[64], Ctx& x) { wgmma_wait<0>(); fence_regs(acc); gemm_release<128>(x, false); }

__device__ __forceinline__ void rows_load(uint4* r, uint32_t tile, const Ctx& x) {
#pragma unroll
  for (int q = 0; q < 4; q++) {
    const uint32_t row = x.warp * 16 + 4 * q + (x.lane >> 3);
    lds128(tile + row * 128 + (((x.lane & 7) ^ (row & 7)) << 4), r[q].x, r[q].y, r[q].z, r[q].w);
  }
}
__device__ __forceinline__ void rows_store(const uint4* r, uint4* g) {
#pragma unroll
  for (int q = 0; q < 4; q++) stg128(g + q * 1024, r[q]);
}
__device__ __forceinline__ void publish(int id, const Ctx& x) { __syncwarp(); if (x.lane == 0) mbar_arrive(x.sb + BAR_SIGP + id * 8); }
__device__ __forceinline__ uint32_t img_tag(uint32_t v, bool isx, int L, const Ctx& x) {
  const uint32_t mk = ((x.lane ^ (x.warp * 4)) & 7) ? 0u : img_mask(isx);
  return (v & ~mk) | (img_code(isx, L) & mk);
}
__device__ __forceinline__ void img_tag(uint4 (&r)[4], bool isx, int L, const Ctx& x) {
#pragma unroll
  for (int q = 0; q < 4; q++) { uint32_t& v = q == 0 ? r[q].x : (q == 1 ? r[q].y : (q == 2 ? r[q].z : r[q].w)); v = img_tag(v, isx, L, x); }
}
__device__ __forceinline__ void img_store(const uint4 (&r)[4], uint4* g) {
#pragma unroll
  for (int q = 0; q < 4; q++) stg128(g + q * 32, r[q]);
}
__device__ __forceinline__ void img_sts(const uint4 (&r)[4], uint32_t tile, const Ctx& x) {
#pragma unroll
  for (int q = 0; q < 4; q++) sts128(tile + x.so + q * 512, r[q].x, r[q].y, r[q].z, r[q].w);
}
__device__ __forceinline__ void img_load(uint32_t (&v)[16], uint32_t tile, const Ctx& x) {
#pragma unroll
  for (int q = 0; q < 4; q++) lds128(tile + x.so + q * 512, v[4 * q], v[4 * q + 1], v[4 * q + 2], v[4 * q + 3]);
}
__device__ __forceinline__ void img_unpack(float* a, const uint32_t (&v)[16]) {
#pragma unroll
  for (int q = 0; q < 16; q++) { a[4 * (q & 7) + 2 * (q >> 3)] = lo16(v[q]); a[4 * (q & 7) + 2 * (q >> 3) + 1] = hi16(v[q]); }
}

template <int N>
__device__ __forceinline__ void stats_acc(const float* a, float (&t)[4]) {
#pragma unroll
  for (int i = 0; i < N; i++) { t[i & 2] += a[i]; t[(i & 2) + 1] = fmaf(a[i], a[i], t[(i & 2) + 1]); }
}
__device__ __forceinline__ void stats_send(float (&t)[4], int L, const Ctx& x) {
  const unsigned seq = seq4(get_tag<false>(x.sb), L);
#pragma unroll
  for (int q = 0; q < 4; q++) t[q] = qsum(t[q]);
  if (x.c == 0) st_pkt(&g_stats[x.m()][x.w][x.j()][x.warp * 8 + x.g], __float_as_uint(t[0]), __float_as_uint(t[1]), __float_as_uint(t[2]), (__float_as_uint(t[3]) & ~15u) | seq);
}
__device__ __forceinline__ void out_epilogue(const float (&acc)[64], uint4 (&r1)[4], float (&t)[4], uint4* g, int L, Ctx& x) {
  const uint32_t t0 = x.aslot(x.ra.s), t1 = x.aslot(x.ra.s + 1 == NA ? 0 : x.ra.s + 1);
  if (L == 3) {
#pragma unroll
    for (int p = 0; p < 8; p++) {
      stsm4(x.maddr(p < 4 ? t0 : t1, (p & 3) * 2), pack2(acc[8 * p], acc[8 * p + 1]), pack2(acc[8 * p + 2], acc[8 * p + 3]),
            pack2(acc[8 * p + 4], acc[8 * p + 5]), pack2(acc[8 * p + 6], acc[8 * p + 7]));
      if ((p & 3) == 3) { uint4 r[4]; __syncwarp(); rows_load(r, p < 4 ? t0 : t1, x); rows_store(r, g + (p >> 2) * 8); }
    }
  } else {
    auto pack16 = [&](uint4 (&r)[4], const float* a) {
#pragma unroll
      for (int q = 0; q < 4; q++) { const float* u = a + 16 * (q & 1) + (q & 2); r[q] = make_uint4(pack2(u[0], u[1]), pack2(u[4], u[5]), pack2(u[8], u[9]), pack2(u[12], u[13])); }
    };
    uint4 r0[4];
    pack16(r0, acc);
    img_tag(r0, true, L + 1, x);
    img_store(r0, x.img(XBUF(L + 1), 0));
    publish(1, x);
    const float z = bb_fence(x.goff);
    img_sts(r0, t0, x);
    pack16(r1, acc + 32);
    img_tag(r1, true, L + 1, x);
    img_sts(r1, t1, x);
    float u[4] = {z, z, z, z}, v[4] = {z, z, z, z};
    stats_acc<32>(acc, v);
    stats_acc<32>(acc + 32, u);
#pragma unroll
    for (int q = 0; q < 4; q++) t[q] = u[q] + v[q];
    mbar_wait2(x.fullB(x.rb.s), x.rb.ph, x.fullB(x.rb.s + 1), x.rb.ph);
    fence_async_smem();
    asm volatile("bar.sync %0, %1;" ::"r"(L == 1 ? x.w + 1 : 3), "r"(L == 1 ? 128 : 256) : "memory");
  }
}

struct Stats { float rstd0, rstd1; };
__device__ __forceinline__ Stats load_stats(int half, const Ctx& x) {
  const float2 u = lds64f(x.sb + OFF_MR + half * 256 + (x.warp * 8 + x.g) * 8);
  return {u.x, u.y};
}

template <int NH, int NK, class F>
__device__ __forceinline__ void hedgehog_scale(float* t, const Stats& st, const uint32_t* keep, F use) {
#pragma unroll
  for (int q = 0; q < 16 * NH; q++) t[q] *= ((q & 2) ? st.rstd1 : st.rstd0) * LOG2E;
  use();
  float m[4];
#pragma unroll
  for (int q = 0; q < 4 * NH; q++) {
    const float v = fmaxf(fmaxf(fabsf(t[4 * q]), fabsf(t[4 * q + 1])), fmaxf(fabsf(t[4 * q + 2]), fabsf(t[4 * q + 3])));
    m[q & 3] = q < 4 ? v : fmaxf(m[q & 3], v);
  }
  if (__builtin_expect(__any_sync(0xffffffffu, fmaxf(fmaxf(m[0], m[1]), fmaxf(m[2], m[3])) > 58.f), 0)) {
    float z[16 * NH + NK];
#pragma unroll
    for (int q = 0; q < 16 * NH + NK; q++) z[q] = q < 16 * NH ? t[q % (16 * NH)] : __uint_as_float(keep[q & 15]);
#pragma unroll 1
    for (int r = 0; r < 2 * NH; r++) {
      float hi = -INFINITY, lo = INFINITY;
#pragma unroll 1
      for (int i = 0; i < 16; i++) {
        const int k = (i & 6) * 2 + (i & 1) + (r & 1) * 2 + (r & 2) * 8;
        const float v = z[k];
        if (i < 8) { hi = fmaxf(hi, v); lo = fminf(lo, v); }
        else z[k] = v - fminf(fmaxf(v, lo), hi);
        if (i == 7) {
#pragma unroll 1
          for (int d = 1; d <= 2; d++) { hi = fmaxf(hi, __shfl_xor_sync(0xffffffffu, hi, d)); lo = fminf(lo, __shfl_xor_sync(0xffffffffu, lo, d)); }
          const float mid = 0.5f * hi + 0.5f * lo;
          hi = fmaxf(hi - 58.f, mid); lo = fminf(lo + 58.f, mid);
        }
      }
    }
#pragma unroll
    for (int q = 0; q < 16 * NH; q++) t[q] = z[q];
    use();
  }
}
__device__ __forceinline__ void dual_exp(const float* t, uint32_t (&f)[18], int never) {
  float e[KSPLIT];
#pragma unroll
  for (int q = 0; q < KSPLIT; q++) e[q] = ex2(q < 16 ? t[q] : -t[q & 15]);
  while (never < 0) {
#pragma unroll
    for (int i = 0; i < KSPLIT; i += 4) asm volatile("ld.shared.v4.f32 {%0,%1,%2,%3}, [%4];" : "=f"(e[i]), "=f"(e[i + 1]), "=f"(e[i + 2]), "=f"(e[i + 3]) : "r"(never + i) : "memory");
    never += __float_as_int(e[0]);
  }
#pragma unroll
  for (int q = 0; q < KSPLIT; q += 2) f[q >> 1] = pack2(e[q], e[q + 1]);
#pragma unroll
  for (int q = KSPLIT; q < 32; q += 2) f[q >> 1] = q < 16 ? pack2(ex2(t[q]), ex2(t[q + 1])) : pack2(ex2(-t[q & 15]), ex2(-t[(q & 15) + 1]));
#pragma unroll
  for (int sg = 0; sg < 2; sg++) {
    const uint32_t* u = f + 8 * sg;
    const uint32_t a = add2(add2(u[0], u[2]), add2(u[4], u[6])), b = add2(add2(u[1], u[3]), add2(u[5], u[7]));
    f[16 + sg] = add2(__byte_perm(a, b, 0x5410), __byte_perm(a, b, 0x7632));
  }
}
__device__ __forceinline__ void dual_exp_rcp(const float* t, uint32_t* f) {
#pragma unroll
  for (int q = 0; q < 8; q++) {
    const float a = ex2(t[2 * q]), b = ex2(t[2 * q + 1]), r = rcp(a * b);
    f[q] = pack2(a, b); f[8 + q] = pack2(r * b, r * a);
  }
}
__device__ __forceinline__ void cta_bar() { asm volatile("bar.sync 3, 256;" ::: "memory"); }

template <int N> __device__ __forceinline__ void pin(const uint32_t* v, uint32_t addr) {
#pragma unroll
  for (int i = 0; i < N; i += 4)
    asm volatile("{\n.reg .pred p;\nsetp.eq.u32 p, %0, 0;\n@p st.shared.v4.u32 [%0], {%1,%2,%3,%4};\n}" ::"r"(addr), "r"(v[i]), "r"(v[i + 1]), "r"(v[i + 2]), "r"(v[i + 3]) : "memory");
}

__device__ __forceinline__ void consumer(const Params& P, uint32_t sb, int w, unsigned vb) {
  Ctx x;
  x.w = w;
  x.ab = sb + OFF_A + w * 8192; x.da0 = desc_lo(SB + OFF_A, 16) + w * 512;
  x.lane = threadIdx.x & 31; x.warp = __shfl_sync(0xffffffffu, (threadIdx.x >> 5) & 3, 0); x.g = x.lane >> 2; x.c = x.lane & 3;
  x.goff = (cta_m(vb) * 128 + w) * 128 + cta_j(vb) * 16;
  asm volatile("" : "+r"(x.goff));
  x.elected = (threadIdx.x & 127) == 0;
  x.ra = {0, 0}; x.rb = {0, 0}; x.pa = x.pb = 0;
  {
    const uint32_t row = x.warp * 16 + (x.lane & 15);
    x.mrow = row * 128; x.mxor = row & 7; x.mhi = x.lane >> 4;
  }
  const int goff = x.goff;
  x.ip = solid(&g_img[0][x.m()][2 * x.j()][w * 512 + x.oo()]);
  x.so = solid(16 * x.oo());
  uint4 r1[4];
  float ts[4] = {0.f, 0.f, 0.f, 0.f};
#pragma unroll
  for (int i = 0; i < 4; i++) r1[i] = make_uint4(0, 0, 0, 0);
  TSW(0);
  mbar_wait3(x.fullA(0), 0, x.fullB(0), 0);
#pragma unroll 1
  for (int L = 0; L < 4; L++) {
    float acc[64];
    constexpr uint32_t dcs = desc_lo(SB + OFF_CS, 0);
    if ((L & 1) == 0) {
    float kv[128];
    x.ha = L ? HA64 : HA128; x.k2 = L ? 32 : 4;
    gemm_issue<256, true, false>(kv, x, true); gemm_next<256>(x);
    {
      int i = 1;
#pragma unroll 1
      for (int seg = L ? NS - 1 : 0; seg <= NS; seg++) {
        const int end = seg < NS ? (L == 0 ? 3 + SA * ((x.j() + SW * w) & 3) + SB_ * seg : XA + 1) : 14 + L;
#pragma unroll 1
        do {
          gemm_issue<256, false, false>(kv, x);
          gemm_retire<256>(x, true);
          i++;
          if (i == 5) TSL_(8);
          if (i == 11) TSL_(10);
        } while (i != end);
        if (seg < NS && L == 0) {
          uint32_t v[16];
          float a[32];
#pragma unroll
          for (int q = 0; q < 4; q++) ldsm4(x.maddr(x.aslot(x.pa), 2 * q), reinterpret_cast<uint32_t (&)[4]>(v[4 * q]));
#pragma unroll
          for (int q = 0; q < 16; q++) { a[2 * q] = lo16(v[q]); a[2 * q + 1] = hi16(v[q]); }
          stats_acc<32>(a, ts);
          fence_regs(ts);
          wg_bar(w);
        }
        if (seg == NS - 1) {
          if (L > 0) { img_store(r1, x.img(XBUF(L), 1)); publish(2, x); }
          mbar_wait(sb + BAR_EPOCH, 0);
          stats_send(ts, L, x);
        }
      }
    }
      const Ring kt = x.ra;
      if (L == 0) adv<NA>(x.ra);
#pragma unroll 1
      for (int h = L; h < 2; h++) {
        float d[16];
        mbar_wait2(x.fullA(kt.s), kt.ph, sb + BAR_WPHI, 0);
        wgmma_fence();
#pragma unroll
        for (int q = 0; q < 2; q++) wgmma_ss_n32(d, x.da0 + kt.s * (SLOT / 16) + h * 4 + q * 2, desc_lo(SB + OFF_S + 4096, 512) + w * 256 + h * 128 + q * 64, q);
        wgmma_commit();
        gemm_issue<256, false, false>(kv, x);
        gemm_retire<256>(x, true);
        if (h) x.releaseA(kt.s);
        fence_regs(d);
        uint4* dst = &g_wf[1][x.j()][x.m()][w * 512 + (x.warp * 16 + x.g) * 8 + ((h * 4 + x.c) ^ x.g)];
        dst[0] = make_uint4(pack2(d[0], d[1]), pack2(d[4], d[5]), pack2(d[8], d[9]), pack2(d[12], d[13]));
        dst[64] = make_uint4(pack2(d[2], d[3]), pack2(d[6], d[7]), pack2(d[10], d[11]), pack2(d[14], d[15]));
      }
      const uint32_t dm = desc_lo(SB + OFF_MA, 0) + w * 64;
      mbar_wait2(sb + BAR_STAT, 0, sb + BAR_CS, 0);
      wgmma_fence();
      wgmma_r1_n256(kv, dm, dcs + 96, 1);
      wgmma_commit();
      const Stats st = load_stats(w, x);
      mbar_wait2(x.fullA(x.ra.s), x.ra.ph, x.fullB(x.rb.s), x.rb.ph);
      wgmma_wait<0>();
      fence_regs(kv);
      gemm_release<256>(x, true);
      TSL_(2);
      uint32_t P0[32], P1[32], PH[32];
#pragma unroll
      for (int t = 0; t < 16; t++) { P0[t] = pack2(kv[4 * t] * st.rstd0, kv[4 * t + 1] * st.rstd0); P1[t] = pack2(kv[4 * t + 2] * st.rstd1, kv[4 * t + 3] * st.rstd1); }
      pin<16>(P0, x.mrow + 16);
      {
#pragma unroll
        for (int q = 0; q < 4; q++) sts128((x.warp < 3 ? sb + OFF_T + w * 12288 + x.warp * 4096 : sb + OFF_S + 16384 + w * 2048) + x.lane * 16 + q * 512, P1[4 * q], P1[4 * q + 1], P1[4 * q + 2], P1[4 * q + 3]);
      }
      wgmma_fence();
      wgmma_r1_n128(acc, dm, dcs, 0);
      gemm_issue<128, false, false>(acc, x, true); gemm_next<128>(x);
      TSL_(3);
#pragma unroll
      for (int s = 0; s < 4; s++) {
#pragma unroll
        for (int t = 16 + 8 * (s & 1); t < 24 + 8 * (s & 1); t++) {
          if (s < 2) P1[t] = movm(pack2(kv[4 * t + 2] * st.rstd1, kv[4 * t + 3] * st.rstd1));
          else P0[t] = movm(pack2(kv[4 * t] * st.rstd0, kv[4 * t + 1] * st.rstd0));
        }
        if (s < 3) { gemm_issue<128, false, false>(acc, x); gemm_retire<128>(x, true); }
        if (s == 1) {
          if (x.warp < 3) {
#pragma unroll
            for (int q = 4; q < 8; q++) sts128(sb + OFF_T + w * 12288 + x.warp * 4096 + x.lane * 16 + q * 512, P1[4 * q], P1[4 * q + 1], P1[4 * q + 2], P1[4 * q + 3]);
          } else {
            uint4* dst = &g_halo[x.m()][x.j()][w][x.lane];
#pragma unroll
            for (int q = 0; q < 8; q++) dst[q * 32] = make_uint4(P1[4 * q], P1[4 * q + 1], P1[4 * q + 2], P1[4 * q + 3]);
          }
          publish(3, x);
          gemm_issue<128, false, false>(acc, x);
          gemm_retire<128>(x, true);
        }
      }
      TSL_(4);
      gemm_run<false>(acc, x, 10, 0);
      gemm_issue<128, false, false>(acc, x);
      {
        wg_bar(w);
        uint32_t tr = sb + OFF_T + w * 12288 + (x.warp - 1) * 4096;
        if (x.warp == 0) {
          tr = x.m() > 0 ? sb + OFF_S + 8192 + w * 4096 : tr + 4096;
          if (x.m() > 0) mbar_wait(sb + BAR_HALO, L >> 1);
        }
#pragma unroll
        for (int q = 0; q < 8; q++) lds128(tr + x.lane * 16 + q * 512, PH[4 * q], PH[4 * q + 1], PH[4 * q + 2], PH[4 * q + 3]);
      }
      gemm_retire<128>(x, false);
      gemm_end(acc, x);
      TSL_(5);
      const bool first = (x.m() == 0) && (x.warp == 0);
      const bool hi0 = 2 * x.c > x.g, hi1 = 2 * x.c + 1 > x.g;
      const uint32_t mhi = (hi0 ? 0xFFFFu : 0u) | (hi1 ? 0xFFFF0000u : 0u);
      const uint32_t valid = first ? ~mhi : ~0u;
      const float sc0 = st.rstd0 * (0.17677669529663687f * LOG2E), sc1 = st.rstd1 * (0.17677669529663687f * LOG2E);
      uint32_t xr[2][16];
#pragma unroll
      for (int hp = 0; hp < 2; hp++) {
        const uint32_t tile = x.aslot(x.held(hp));
        uint32_t px[2], py[2];
        float s[2][3][4];
#pragma unroll
        for (int u = 0; u < 2; u++) {
#pragma unroll
          for (int q = 0; q < 12; q++) s[u][q >> 2][q & 3] = 0.f;
#pragma unroll
          for (int ks = 0; ks < 2; ks++) {
            const int t = 8 * hp + 4 * u + 2 * ks;
            const uint32_t a0 = pack2(acc[4 * t], acc[4 * t + 1]), a1 = pack2(acc[4 * t + 2], acc[4 * t + 3]);
            const uint32_t a2 = pack2(acc[4 * t + 4], acc[4 * t + 5]), a3 = pack2(acc[4 * t + 6], acc[4 * t + 7]);
            mma16816(s[u][0], a0, a1, a2, a3, PH[t], PH[t + 1]);
            mma16816(s[u][1], a0, a1, a2, a3, P0[t], P0[t + 1]);
            mma16816(s[u][2], a0, a1, a2, a3, P1[t], P1[t + 1]);
          }
        }
        float e[2][4], big = 0.f;
#pragma unroll
        for (int u = 0; u < 2; u++) {
          e[u][0] = (hi0 ? s[u][0][0] : s[u][1][0]) * sc0; e[u][1] = (hi1 ? s[u][0][1] : s[u][1][1]) * sc0;
          e[u][2] = (hi0 ? s[u][1][2] : s[u][2][2]) * sc1; e[u][3] = (hi1 ? s[u][1][3] : s[u][2][3]) * sc1;
          big = fmaxf(big, fmaxf(fmaxf(fabsf(e[u][0]), fabsf(e[u][1])), fmaxf(fabsf(e[u][2]), fabsf(e[u][3]))));
          px[u] = pack2(ex2(e[u][0]), ex2(e[u][1])) & valid; py[u] = pack2(ex2(e[u][2]), ex2(e[u][3]));
        }
        if (__builtin_expect(__any_sync(0xffffffffu, big > 58.f), 0)) {
#pragma unroll
          for (int q = 0; q < 4; q++) {
            float v0 = e[q >> 1][2 * (q & 1)], v1 = e[q >> 1][2 * (q & 1) + 1];
            if (first && !(q & 1)) { if (hi0) v0 = -INFINITY; if (hi1) v1 = -INFINITY; }
            float r = fmaxf(v0, v1);
            r = fmaxf(r, __shfl_xor_sync(0xffffffffu, r, 1)); r = fmaxf(r, __shfl_xor_sync(0xffffffffu, r, 2));
            ((q & 1) ? py : px)[q >> 1] = pack2(ex2(v0 - r), ex2(v1 - r));
          }
        }
        float r[2][2];
#pragma unroll
        for (int u = 0; u < 2; u++) {
          float d[4] = {0.f, 0.f, 0.f, 0.f};
          mma1688(d, px[u], py[u], 0x3F803F80u);
          r[u][0] = rcp(d[0]); r[u][1] = rcp(d[2]);
        }
        uint32_t o[8][2];
        uint4 ro[4];
#pragma unroll
        for (int q = 0; q < 8; q++) {
          float d[4] = {0.f, 0.f, 0.f, 0.f};
          const int t = 16 + 8 * hp + q, u = q >> 2;
          mma16816(d, px[u] & mhi, 0u, px[u] & ~mhi, py[u] & mhi, PH[t], P0[t]);
          mma1688(d, 0u, py[u] & ~mhi, P1[t]);
          o[q][0] = pack2(d[0] * r[u][0], d[1] * r[u][0]); o[q][1] = pack2(d[2] * r[u][1], d[3] * r[u][1]);
        }
#pragma unroll
        for (int q = 0; q < 4; q++) ro[q] = make_uint4(o[4 * (q & 1)][q >> 1], o[4 * (q & 1) + 1][q >> 1], o[4 * (q & 1) + 2][q >> 1], o[4 * (q & 1) + 3][q >> 1]);
        img_tag(ro, false, 0, x);
        img_store(ro, x.img(0, hp));
        if (hp == 0) publish(0, x);
        if (hp == 0) {
#pragma unroll
          for (int i = 0; i < 2; i++) {
            const uint32_t ti = x.aslot(x.held(i));
            if (L) img_load(xr[i], ti, x);
            else {
#pragma unroll
              for (int q = 0; q < 4; q++) ldsm4(x.maddr(ti, 2 * q), reinterpret_cast<uint32_t (&)[4]>(xr[i][4 * q]));
            }
          }
          __syncwarp();
        }
        img_sts(ro, tile, x);
      }
      if (L == 0) {
#pragma unroll
        for (int hp = 0; hp < 2; hp++) {
          uint32_t v[16];
#pragma unroll
          for (int q = 0; q < 16; q++) asm volatile("mov.b32 %0, %1;" : "=r"(v[(q & 1) * 8 + (q >> 1)]) : "r"(xr[hp][q]));
#pragma unroll
          for (int q = 0; q < 16; q++) xr[hp][q] = v[q];
        }
      }
      img_unpack(acc, xr[0]); img_unpack(acc + 32, xr[1]);
    } else {
      float kv[128];
      float (&kv0)[64] = reinterpret_cast<float (&)[64]>(kv[0]);
      float (&kv1)[64] = reinterpret_cast<float (&)[64]>(kv[64]);
      auto mma8 = [&](uint32_t as, uint32_t bs, int i, bool fence) {
        const uint32_t da = desc_lo(SB + OFF_A, 16) + as * (SLOT / 16), db = desc_lo(SB + OFF_B, 8192) + bs * (SLOT / 16);
        if (fence) wgmma_fence();
#pragma unroll
        for (int k = 0; k < 4; k++) {
          wgmma_ss_n128(kv0, da + (k >> 1) * 32 + (k & 1) * 2, HA64, db + 128 * k, i + k);
          wgmma_ss_n128(kv1, da + 512 + (k >> 1) * 32 + (k & 1) * 2, HA64, db + 128 * k, i + k);
        }
        wgmma_commit();
      };
      constexpr uint32_t dm = desc_lo(SB + OFF_MB, 0);
      auto relB = [&](uint32_t s) { mbar_arrive_n(sb + BAR_EMPTYB + s * 8, 2); };
      auto skip = [&]() {
#pragma unroll
        for (int q = 0; q < 6 - NJ; q++) adv<NA>(x.ra);
        x.rb.s = w ? (2 + NJ) % 6 : 4;
        if (!w && NJ < 4) x.rb.ph ^= 1;
      };
      static_assert(NA == 5 && NB == 6, "ring arithmetic");
      mma8(x.ra.s, x.rb.s + w, 0, true);
      gemm_next<256>(x);
#pragma unroll 1
      for (int i = 1; i < NJ; i++) {
        mbar_wait2(x.fullA(x.ra.s), x.ra.ph, x.fullB(x.rb.s + w), x.rb.ph);
        mma8(x.ra.s, x.rb.s + w, 1, true);
        if (!XO && i == XR) { img_store(r1, x.img(XBUF(L), 1)); publish(2, x); }
        if (!XO && i == XS) stats_send(ts, L, x);
        wgmma_wait<1>();
        if (x.elected) { x.releaseA(x.pa); relB(x.pb + w); }
        gemm_next<256>(x);
        if (XO && i == XR) { img_store(r1, x.img(XBUF(L), 1)); publish(2, x); stats_send(ts, L, x); }
      }
      if (w) {
        wgmma_wait<0>();
        if (x.elected) { x.releaseA(x.pa); relB(x.pb + 1); }
        skip();
        asm volatile("bar.sync 7, 256;" ::: "memory");
      }
      TSL_(8);
      {
        const int t = lane_id() + 32 * x.warp;
        uint32_t mask = t < 2 ? ((w ? (t ? 0xFF3Fu : 0x3FFFu) : 0xFFFFu) >> (NJ - 1)) & (w ? ~1u : ~0u) : 0u, cnt = 1 + t;
        bool ready = false;
#pragma unroll 1
        for (int i = NJ; i < 16; i++) {
          if (!ready) mbar_wait2(x.fullA(x.ra.s), x.ra.ph, x.fullB(x.rb.s), x.rb.ph);
          mma8(x.ra.s, x.rb.s, 1, true);
          const uint32_t bar = sb + (t ? BAR_EMPTYB + x.pb * 8 : BAR_EMPTYA + x.pa * 8);
          gemm_next<128>(x);
          if (w && (i | 4) == 15) x.rb.s = 4;
          ready = mbar_probe2(x.fullA(x.ra.s), x.ra.ph, x.fullB(x.rb.s), x.rb.ph);
          wgmma_wait<1>();
          if (mask & 1) mbar_arrive_n(bar, cnt);
          mask >>= 1; cnt = 2;
          if (i == 8 && w) asm volatile("bar.arrive 9, 256;" ::: "memory");
          if (i == 9) TSL_(10);
        }
        mbar_wait2(sb + BAR_STAT, 1, sb + BAR_CS + 8, 0);
        wgmma_fence();
        wgmma_r1_n128(kv0, dm, dcs + 96 + 96 * w, 1);
        wgmma_r1_n128(kv1, dm + 64, dcs + 96 + 96 * w, 1);
        wgmma_commit();
        if (w == 0) asm volatile("bar.arrive 7, 256;" ::: "memory");
        wgmma_wait<1>();
        if (mask & 1) mbar_arrive_n(sb + (t ? BAR_EMPTYB + x.pb * 8 : BAR_EMPTYA + x.pa * 8), 2);
      }
      const Stats s0 = load_stats(0, x), s1 = load_stats(1, x), st = w ? s1 : s0;
      if (w == 0) skip();
      const uint32_t h0 = x.held(0), h1 = x.held(1);
      auto vreg = [&](int ks) { return ks < 6 ? OFF_A + (ks < 3 ? h0 * SLOT : h1 * SLOT - 15360) + ks * 5120 : OFF_S + 2048 + ks * 5120; };
      uint32_t tV[2], uu[4];
#pragma unroll
      for (int hf = 0; hf < 2; hf++) {
        tV[hf] = sb + vreg(4 * hf + x.warp) + ((x.lane >> 3) & 1) * 2560 + (x.lane & 7) * 16 + x.mhi * 128;
        const float i0 = rcp(hf ? s1.rstd0 : s0.rstd0), i1 = rcp(hf ? s1.rstd1 : s0.rstd1);
        const uint32_t h = pack2(i0, i1);
        uu[2 * hf] = pack2(lo16(h), i0 - lo16(h)); uu[2 * hf + 1] = pack2(hi16(h), i1 - hi16(h));
        asm volatile("" : "+r"(tV[hf]), "+r"(uu[2 * hf]), "+r"(uu[2 * hf + 1])::"memory");
      }
      wgmma_wait<0>();
      fence_regs(kv);
      TSL_(2);
      if (w == 0) {
        uint32_t f[2][18], ad[4];
#pragma unroll
        for (int q = 0; q < 18; q++) f[1][q] = 0u;
#pragma unroll
        for (int q = 0; q < 4; q++) ad[q] = x.maddr(sb + OFF_S, 2 * q);
        auto norm = [&](int un) {
          uint32_t* u = f[un & 1];
          const Stats& sn = un ? s1 : s0;
#pragma unroll
          for (int sg = 0; sg < 2; sg++) {
            uint32_t v = u[16 + sg];
            v = add2(v, __shfl_xor_sync(0xffffffffu, v, 1)); v = add2(v, __shfl_xor_sync(0xffffffffu, v, 2));
            const float a = rcp(lo16(v)) * sn.rstd0, b = rcp(hi16(v)) * sn.rstd1;
            const uint32_t r0 = pack2(a, a), r1_ = pack2(b, b);
#pragma unroll
            for (int q = 8 * sg; q < 8 * sg + 8; q++) u[q] = mul2(u[q], (q & 1) ? r1_ : r0);
#pragma unroll
            for (int q = 2 * sg; q < 2 * sg + 2; q++) stsm4(ad[q] + un * 8192, u[4 * q], u[4 * q + 1], u[4 * q + 2], u[4 * q + 3]);
          }
        };
        auto move = [&](int dst, int src) {
#pragma unroll
          for (int q = 0; q < 16; q++) asm volatile("mov.b32 %0, %1;" : "=f"(kv[dst + q]) : "f"(src ? kv[src + q] : 0.f));
        };
        hedgehog_scale<1, 0>(kv, s0, nullptr, [] {});
        uint32_t step = 0;
#pragma unroll 1
        for (int h = 0;; h++) {
          norm(1);
          dual_exp(kv, f[0], x.goff);
          hedgehog_scale<1, KEEP>(kv + 64, s1, f[1], [] {});
          if (h == 2) asm volatile("bar.sync 9, 256;" ::: "memory");
#pragma unroll
          for (int q = 0; q < 4; q++) ad[q] += step;
          norm(0);
          dual_exp(kv + 64, f[1], x.goff);
#pragma unroll
          for (int q = 0; q < 16; q++) kv[q] = kv[16 + q];
          hedgehog_scale<1, KEEP>(kv, s0, f[0], [] {});
          step = SLOT;
          if (h == 0) { move(64, 80); move(16, 32); }
          else if (h == 1) { move(64, 96); move(16, 48); step = OFF_B + SLOT - OFF_S; }
          else if (h == 2) { move(64, 112); move(16, 0); }
          else break;
        }
        norm(1);
        TSL_(3);
      } else {
        wg_bar(w);
#pragma unroll
        for (int hf = 0; hf < 2; hf++) {
          stsm4(tV[hf] + 512 + x.mhi * 512, uu[2 * hf], uu[2 * hf + 1], uu[2 * hf], uu[2 * hf + 1]);
          stsm4(tV[hf] + 1792 + x.mhi * 512, uu[2 * hf], uu[2 * hf + 1], uu[2 * hf], uu[2 * hf + 1]);
#pragma unroll
          for (int q = 0; q < 8; q++) {
            const float* u = kv + 64 * hf + 8 * q;
            stsm4(tV[hf] + (q >> 1) * 640 + (q & 1) * 256, pack2(u[0], u[1]), pack2(u[2], u[3]), pack2(u[4], u[5]), pack2(u[6], u[7]));
          }
        }
        TSL_(3);
      }
      {
        float d[2][20];
        uint4* dst = &g_kvpart[x.j()][w * 4 + x.warp][0][x.m() * 32 + x.lane];
        unsigned* dz = reinterpret_cast<unsigned*>(&g_kvpart[x.j()][w * 4 + x.warp][x.c & 1][512]) + x.m() * 8 + x.g;
        fence_async_smem();
        cta_bar();
        TSL_(11);
        uint32_t pk[9];
        auto prep = [&](float (&u)[20]) {
          fence_regs(u);
#pragma unroll
          for (int q = 0; q < 8; q++) pk[q] = pack2(u[((q >> 1) & 2) + 4 * (q & 3)], u[((q >> 1) & 2) + 4 * (q & 3) + 1]);
          pk[8] = __float_as_uint((x.c & 1) ? u[18] + u[19] : u[16] + u[17]);
#pragma unroll
          for (int q = 0; q < 9; q += 4) pk[q] = (pk[q] & ~1u) | (L == 1);
        };
        auto send = [&](int hp) {
          st_v4(dst + hp * 16 * 544, pk[0], pk[1], pk[2], pk[3]); st_v4(dst + (hp * 16 + 1) * 544, pk[4], pk[5], pk[6], pk[7]);
          st_flag(dz + hp * 16 * 544 * 4, pk[8]);
        };
        wgmma_fence();
#pragma unroll
        for (int q = 0; q < 17; q++) {
          if (q < 16) wgmma_ss_n40_tt(d[q >> 3], desc_lo(SB + (q < 8 ? OFF_S : OFF_B + 2 * SLOT), 1024) + w * (SLOT / 16) + 128 * (q & 7), desc_lo(SB + vreg(q & 7), 2560) + (w + (q >> 3) * 2) * 40, q & 7);
          else wgmma_r1_n128(acc, dm + w * 64, dcs, 0);
          if (q == 7 || q == KVS || q == 16) wgmma_commit();
          if (q == KVS) { mbar_wait2(x.fullA(x.ra.s), x.ra.ph, x.fullB(x.rb.s), x.rb.ph); wgmma_wait<1>(); prep(d[0]); send(0); bb_fence(x.goff); wgmma_fence(); }
        }
        gemm_issue<128, false>(acc, x, true); gemm_next<128>(x);
        wgmma_wait<1>();
        x.releaseA(h0); x.releaseA(h1); x.releaseB(2); x.releaseB(3);
        if (x.lane == 0) mbar_arrive(sb + BAR_SIGT);
        prep(d[1]);
        TSL_(4);
#pragma unroll 1
        for (int seg = 0; seg < 2; seg++) {
          const int n0 = w ? PS1 : PS0;
          gemm_run(acc, x, seg ? 15 - n0 : n0, seg, seg ? L : 0);
          if (seg == 0) send(1);
        }
      }
      gemm_end(acc, x);
      TSL_(5);
      {
        float dp[2][20], dn[2][20];
        uint32_t f[4][16];
        auto mma = [&](int h) {
          if (!(h & 1)) mbar_wait(sb + BAR_KV + h * 4, L >> 1);
          if (h == 0) TSL_(9);
          const uint32_t db = desc_lo(SB + OFF_S + h * 5120, 128);
          const uint32_t (&a)[16] = f[h];
          wgmma_fence();
          wgmma_rs_n40(dp[h & 1], a[0], a[1], a[2], a[3], db, 0);
          wgmma_rs_n40(dn[h & 1], a[8], a[9], a[10], a[11], db + 160, 0);
          wgmma_rs_n40(dp[h & 1], a[4], a[5], a[6], a[7], db + 80, 1);
          wgmma_rs_n40(dn[h & 1], a[12], a[13], a[14], a[15], db + 240, 1);
          wgmma_commit();
        };
        uint32_t xr[16];
        auto fin = [&](int h) {
          const uint32_t tile = x.aslot(x.held(h >> 1));
          if (!(h & 1)) img_load(xr, tile, x);
          float (&u)[20] = dp[h & 1];
          float (&v)[20] = dn[h & 1];
          fence_regs(u); fence_regs(v);
#pragma unroll
          for (int r = 0; r < 2; r++) {
            const float sp = u[16 + 2 * r], sn = v[16 + 2 * r];
            const float id = rcp(fmaf(fmaf(sp, L == 1 ? 0.065536f * 128 / 129 : 0.065536f, u[17 + 2 * r]), sn, v[17 + 2 * r] * sp)), aa = sn * id, cc = sp * id;
            uint32_t o[4];
#pragma unroll
            for (int t = 0; t < 4; t++) o[t] = pack2(fmaf(u[4 * t + 2 * r], aa, v[4 * t + 2 * r] * cc), fmaf(u[4 * t + 2 * r + 1], aa, v[4 * t + 2 * r + 1] * cc));
            o[2 * r + (h & 1)] = img_tag(o[2 * r + (h & 1)], false, 1, x);
            if (ZO && h == 3) r1[r] = make_uint4(o[0], o[1], o[2], o[3]);
            else stg128(x.img(0, h >> 1) + r * 64 + (h & 1) * 32, make_uint4(o[0], o[1], o[2], o[3]));
            sts128(tile + r * 1024 + (h & 1) * 512 + x.so, o[0], o[1], o[2], o[3]);
          }
          if (h & 1) { if (h == 1) publish(0, x); img_unpack(acc + 16 * (h - 1), xr); }
        };
        auto ex = [&](int h) { dual_exp_rcp(acc + 16 * h, f[h]); };
        Stats sq = st;
#pragma unroll
        for (int h = 0; h < 4; h += 2) {
          hedgehog_scale<2, 0>(acc + 16 * h, sq, nullptr, [&] { ex(h); });
          mma(h);
          ex(h + 1); wgmma_wait<0>(); fin(h);
          if (h == 0) bb_fence(x.goff);
          mma(h + 1);
          wgmma_wait<0>(); fin(h + 1);
          if (h == 0) sq.rstd1 += bb_fence(x.goff);
        }
      }
    }
    mbar_wait(x.fullB(x.rb.s), x.rb.ph);
    fence_regs(acc);
    fence_async_smem();
    wg_bar(w);
    TSL_(6);
    rewind2<NA>(x.ra);
    if (ZO && (L & 1)) { stg128(x.img(0, 1) + 32, r1[0]); stg128(x.img(0, 1) + 96, r1[1]); }
    gemm_issue<128, false>(acc, x, true); gemm_next<128>(x);
    uint4* out = solid(P.out + goff + (x.warp * 16 + (x.lane >> 3)) * 256 + (x.lane & 7));
#pragma unroll 1
    for (int seg = L >= TSL ? 0 : 1; seg < 2; seg++) {
      gemm_run(acc, x, L >= TSL ? (seg ? TSK : 15 - TSK) : 15, seg, 10 + L);
      if (L >= TSL) {
        if (seg == 0 && w == 1) asm volatile("bar.sync 6, 256;" ::: "memory");
        if (seg == 1 && w == 0) asm volatile("bar.arrive 6, 256;" ::: "memory");
      }
    }
    gemm_end(acc, x);
    TSL_(7);
    rewind2<NA>(x.ra);
    out_epilogue(acc, r1, ts, out, L, x);
    TSL_(13);
  }
}

typedef unsigned long long u64;
template <class T> __device__ __forceinline__ T* early(T* p) { return (T*)__shfl_xor_sync(0xffffffffu, (u64)p, 1); }
__device__ __forceinline__ void pause(uint32_t GAP) {
  if (GAP) { uint32_t t0, t; asm volatile("mov.u32 %0, %%clock;" : "=r"(t0)); do { asm volatile("mov.u32 %0, %%clock;" : "=r"(t)); } while (t - t0 < GAP); }
}
__device__ __forceinline__ u64 order_table0(int j) { return (j & 4) ? 0x543210FEDCBA9876ull : 0xDCBA9876543210FEull; }
__device__ __forceinline__ void order_tables(u64& t1, u64& t2, int j) {
#pragma unroll 1
  for (int i = 6; i >= 0; i--) { const u64 o = 2 * other_tile(i, j); t1 = t1 << 4 | o | (o + 1) << 28; t2 = t2 << 8 | (o * 17 + 16); }
  const u64 own = 2 * j * 17 + 16;
  t1 = t1 << 8 | own; t2 |= own << 56;
}

__device__ __forceinline__ void b_producer(const Params& P, uint32_t sb, unsigned vb) {
  const int j = cta_j(vb);
  u64 t1 = 0, t2 = 0;
  Ring r = {PRE_B % NB, PRE_B < NB};
#pragma unroll 1
  for (int sg = 0; sg < 20; sg++) {
    const int L = sg / 5, p = sg - 5 * L, wt = L & 1;
    if (sg == 1) order_tables(t1, t2, j);
    int n = p >= 3 ? 16 : (wt ? (p ? 16 - NJ : 2 * NJ) : (p ? 0 : (L ? 32 : 32 - PRE_B)));
    u64 tab = p == 3 ? t2 : (sg == 0 ? order_table0(j) >> (2 * PRE_B) : (p == 1 || p == 2 ? t1 >> (4 * NJ) : t1));
    const CUtensorMap* tm = p == 4 ? &P.mwo[wt] : &P.mw[wt ? 1 : L];
    const uint4* img = &g_wf[p != 3][j][0][0];
    int col = (p >= 3 ? 0 : (p == 2 ? 2048 : 1024)) + 128 * j;
    const int flip = p == 0 ? 3072 : 0;
    const bool fold = wt && p != 4;
    if (sg == 5 || sg == 8) { mbar_wait(sb + (sg == 5 ? BAR_WPHI : BAR_CS + 8), sg == 5); fence_async_global(); }
    if (DEFER && p == 4 && ((DEFL >> wt) & 1)) {
      Ring q = r;
      for (int u = 0; u < DEFER; u++) adv<NB>(q);
      mbar_wait(sb + BAR_EMPTYB + q.s * 8, q.ph);
    }
#pragma unroll 1
    for (; n > 0; n--) {
      const int kb = (int)tab & 15;
      mbar_wait(sb + BAR_EMPTYB + r.s * 8, r.ph);
      if (elect()) {
        mbar_expect_tx(sb + BAR_FULLB + r.s * 8, SLOT);
        if (fold && col < 2048) bulk_load(sb + OFF_B + r.s * SLOT, img + kb * 1024, SLOT, sb + BAR_FULLB + r.s * 8);
        else tma_load_w(sb + OFF_B + r.s * SLOT, tm, sb + BAR_FULLB + r.s * 8, col, kb);
      }
      adv<NB>(r);
      if (p == 2 && (n | 4) == 5) r.s = 4;
      col ^= flip;
      if (!(col & flip & 2048)) tab >>= 4;
    }
  }
}

__device__ __forceinline__ void a_loader(const Params& P, uint32_t sb, unsigned vb) {
  const int j = cta_j(vb), m = cta_m(vb);
  u64 t1 = 0, t2 = 0;
  Ring r = {PRE_A % NA, PRE_A < NA};
  {
    u64 tab = order_table0(j) >> (4 * PRE_A);
#pragma unroll 1
    for (int i = PRE_A; i < 33; i++) {
      if (i == 17) { order_tables(t1, t2, j); tab = t2; }
      mbar_wait(sb + BAR_EMPTYA + r.s * 8, r.ph);
      if (elect()) {
        mbar_expect_tx(sb + BAR_FULLA + r.s * 8, SLOT);
        if (i != 14) tma_load_3d(sb + OFF_A + r.s * SLOT, &P.mx, sb + BAR_FULLA + r.s * 8, ((int)tab & 15) * 64, m * 64, 0);
        else {
          tma_load_w(sb + OFF_A + r.s * SLOT, &P.mw[1], sb + BAR_FULLA + r.s * 8, 1024 + 128 * j, m);
          mbar_expect_tx(sb + BAR_WPHI, 8192); tma_load_2d(sb + OFF_S + 4096, &P.mwphi, sb + BAR_WPHI, 0, 128 * j);
        }
        if (i == PF1 || i == PF2) tma_prefetch_w(&P.mwo[i == PF2], 128 * j, m);
      }
      adv<NA>(r);
      if (i != 14) tab >>= 4;
    }
  }
  const unsigned tag = get_tag(sb);
  unsigned kph = 0;
#pragma unroll 1
  for (int sg = 0; sg < 13; sg++) {
    const int L = sg >> 2, p = sg & 3;
    if (p == 0 && (L & 1)) {
#pragma unroll 1
      for (int h = 0; h < 2; h++) {
        poll_flags(&g_jflag[h][j][0], 16, 0xFFFFu, tag * 4 + L);
        TS(4, h ? 14 + L : 26 + L);
        for (int it = 0;; it++) {
          if (elect()) { mbar_expect_tx(sb + BAR_STAT + 8, 10240); bulk_load(sb + OFF_S + h * 10240, &g_kvfin[j][8 * h][0], 10240, sb + BAR_STAT + 8); }
          mbar_wait(sb + BAR_STAT + 8, kph);
          kph ^= 1;
          uint32_t a = 1u, o = 0u;
#pragma unroll
          for (int u = 0; u < 20; u++) { const uint32_t v = __float_as_uint(lds32f(sb + OFF_S + h * 10240 + u * 512 + (threadIdx.x & 31) * 16)); a &= v; o |= v; }
          if (__all_sync(0xffffffffu, (L == 1 ? a : ~o) & 1u)) break;
          fence_async_smem();
          if (it > (1 << 16)) __trap();
        }
        if (elect()) mbar_arrive(sb + BAR_KV + h * 8);
        TS(4, h ? 30 + L : (L == 1 ? 20 : 25));
      }
    }
    int n = p < 2 ? 14 : (p == 2 ? ((L & 1) ? 0 : 16 - NJ) : 16);
    u64 tab = p == 3 ? t2 : t1 >> (p < 2 ? 8 : 4 * NJ);
    const uint4* img = &g_img[p ? XBUF(L + 1) : 0][m][0][0];
#pragma unroll 1
    for (; n > 0; n--) {
      const uint4* src = early(img + ((int)tab & 15) * 1024);
      const uint32_t bar = sb + (p < 2 ? BAR_LAND : BAR_FULLA) + r.s * 8;
      mbar_wait(sb + BAR_EMPTYA + r.s * 8, r.ph);
      if (elect()) mbar_expect_tx(bar, SLOT);
      if (p < 2 && n == 14) {
        const int lane = threadIdx.x & 31;
        const unsigned* f = &g_hint[(m & 14) + ((lane >> 3) & 1)][(~j & 4) ^ (lane & (L ? ND0 : NDC))];
        mbar_wait(sb + BAR_SIGP + p * 8, L & 1);
        pause(L ? PD : PD0);
        int it = 0;
        while (!__all_sync(0xffffffffu, (int)(ld_flag(f) - (tag * 16 + 4 * L + 1 + p)) >= 0)) { if (++it > (1 << 22)) __trap(); }
        TS(2, p == 0 ? 5 + L * 8 : 9 + L * 8);
        TSH((2 * L + p) * 8 + 2);
      }
      if (elect()) bulk_load(sb + OFF_A + r.s * SLOT, src, SLOT, bar);
      adv<NA>(r);
      tab >>= 4;
      pause(p < 2 && n > 10 ? G0 : 0);
    }
  }
}

template <int KB>
__device__ __forceinline__ uint2 sum_packets(float (&a)[8], uint32_t addr, int n) {
  uint2 ok = make_uint2(~0u, 0u);
#pragma unroll 1
  for (int b = 0; b < n; b += KB) {
    uint4 v[KB];
#pragma unroll
    for (int u = 0; u < KB; u++) lds128(addr + (b + u) * 512, v[u].x, v[u].y, v[u].z, v[u].w);
#pragma unroll
    for (int u = 0; u < KB; u++) {
      ok.x &= v[u].x; ok.y |= v[u].x;
      a[0] += lo16(v[u].x); a[1] += hi16(v[u].x); a[2] += lo16(v[u].y); a[3] += hi16(v[u].y);
      a[4] += lo16(v[u].z); a[5] += hi16(v[u].z); a[6] += lo16(v[u].w); a[7] += hi16(v[u].w);
    }
  }
  return ok;
}
__device__ __forceinline__ void helper_bar() { asm volatile("bar.sync 4, 64;" ::: "memory"); }
__device__ __forceinline__ void helper(const Params& P, uint32_t sb, int w, unsigned vb) {
  const int j = cta_j(vb), m = cta_m(vb);
  if (w == 0) {
    if (elect()) {
      const unsigned t = atomicAdd(&g_ctr, 1u) / NCTA + 1u;
      asm volatile("st.shared.u32 [%0], %1;" ::"r"(sb + OFF_EPOCH), "r"(t) : "memory");
      mbar_arrive(sb + BAR_EPOCH);
    }
  }
  const unsigned tag = get_tag(sb);
  mbar_wait(sb + BAR_FULLB + 24, 0);
  const uint32_t stg = sb + OFF_T + w * 12288, stb = sb + BAR_STG + w * 24;
  Ring rs = {0, 0};
  uint32_t vs = 33 % NA, vph = 0;
  auto cs_image = [&](int L) {
      const int lane = lane_id();
      poll_flags(&g_jflag[2 * L][j][0], 16, L ? CSNEED : 0xFFFu, tag * 4);
#pragma unroll
      for (int p = 0; p < 3; p++) {
        const uint4 u = ldcg4(&g_cs[L][0][p * 1024 + 128 * j + lane * 4]), v = ldcg4(&g_cs[L][1][p * 1024 + 128 * j + lane * 4]);
        const float c0 = __uint_as_float(u.x) + __uint_as_float(v.x), c1 = __uint_as_float(u.y) + __uint_as_float(v.y);
        const float c2 = __uint_as_float(u.z) + __uint_as_float(v.z), c3 = __uint_as_float(u.w) + __uint_as_float(v.w);
        const uint32_t h0 = pack2(c0, c1), h1 = pack2(c2, c3), dst = sb + OFF_CS + (p * 16 + (lane >> 1)) * 96 + L * 48 + (lane & 1) * 8;
        sts64(dst, h0, h1); sts64(dst + 16, pack2(c0 - lo16(h0), c1 - hi16(h0)), pack2(c2 - lo16(h1), c3 - hi16(h1))); sts64(dst + 32, h0, h1);
        if (L == 0) { sts64(dst + 48, 0u, 0u); sts64(dst + 64, 0u, 0u); sts64(dst + 80, 0u, 0u); }
      }
      if (L == 0 && lane < 4) sts64(sb + OFF_CS + 4608 + lane * 8, 0u, 0u);
      fence_async_smem();
      __syncwarp();
      if (elect()) mbar_arrive(sb + BAR_CS + L * 8);
      TS(4, 2 + L * 2);
  };
#pragma unroll 1
  for (int L = 0; L < 4; L++) {
    const int lane = lane_id();
    if (L == 0) {
      {
        const int wt = m >= 12, col = ((0x2021 >> (m & 12)) & 3) * 1024 + 128 * j + (m & 3) * 32;
        const CUtensorMap* tm = &P.mcs[wt];
        __nanosleep(wt ? D2 : CD);
        constexpr int nb = 8;
        float a[8] = {0.f, 0.f, 0.f, 0.f, 0.f, 0.f, 0.f, 0.f};
#pragma unroll 1
        for (int b = -3; b < nb; b++) {
          if (b >= 0) {
            mbar_wait(stb + rs.s * 8, rs.ph);
            sum_packets<KC>(a, stg + rs.s * 4096 + lane * 16, 8);
            fence_async_smem();
            __syncwarp();
          }
          const uint32_t sl = b < 0 ? (rs.s + b + 3) % 3 : rs.s;
          if (b + 3 < nb && elect()) { mbar_expect_tx(stb + sl * 8, 4096); tma_load_2d(stg + sl * 4096, tm, stb + sl * 8, col, (w * (16 - nb) + b + 3) * 64); }
          if (b >= 0) adv<3>(rs); else pause(CP);
        }
#pragma unroll 1
        for (int d = 4; d < 32; d *= 2)
#pragma unroll
          for (int u = 0; u < 8; u++) a[u] += __shfl_xor_sync(0xffffffffu, a[u], d);
        if (lane < 4) {
          float4* dst = reinterpret_cast<float4*>(&g_cs[wt][w][col + lane * 8]);
          dst[0] = make_float4(a[0], a[1], a[2], a[3]); dst[1] = make_float4(a[4], a[5], a[6], a[7]);
        }
        helper_bar();
        if (w == 0 && elect()) { fence_gpu(); st_flag(&g_jflag[2 * wt][j][m], tag * 4); }
      }
      if (w == 0) TS(4, 1 + L * 2);
    }
    if (L > 0 && w == 0) {
      mbar_wait(sb + BAR_SIGP + 16, (L - 1) & 1);
      fence_async_global();
      __nanosleep(CO && L == 1 ? SE : SD);
    }
    if (CO && L < 2 && w == 0) cs_image(L);
    if (w == (L == 0)) {
      if (L == 0) { mbar_wait(sb + BAR_WPHI, 0); __nanosleep(S0); }
#pragma unroll 1
      for (int p = 0; p < 2; p++) {
        uint4 v[8];
        for (int it = 0;; it++) {
          bool ok = true;
#pragma unroll
          for (int t = 0; t < 8; t++) v[t] = ld_pkt(&g_stats[m][p][t][lane]);
#pragma unroll
          for (int t = 0; t < 8; t++) ok = ok && (v[t].w & 15u) == seq4(tag, L);
          if (__all_sync(0xffffffffu, ok)) break;
          __nanosleep(200);
          if (it > (1 << 20)) __trap();
        }
        float s0 = 0.f, q0 = 0.f, s1 = 0.f, q1 = 0.f;
#pragma unroll
        for (int t = 0; t < 8; t++) { s0 += __uint_as_float(v[t].x); q0 += __uint_as_float(v[t].y); s1 += __uint_as_float(v[t].z); q1 += __uint_as_float(v[t].w & ~15u); }
        s0 *= (1.f / 1024); s1 *= (1.f / 1024);
        sts64(sb + OFF_MR + p * 256 + lane * 8, __float_as_uint(rsqrtf(fmaxf(q0 * (1.f / 1024) - s0 * s0, 0.f) + 1e-5f)),
              __float_as_uint(rsqrtf(fmaxf(q1 * (1.f / 1024) - s1 * s1, 0.f) + 1e-5f)));
#pragma unroll
        for (int r = 0; r < 2; r++) {
          const float v = -0.5f * (r ? s1 : s0);
          const uint32_t hh = pack2(v, v), hl = pack2(v, v - lo16(hh));
          const bool b = L & 1;
          sts128(sb + (b ? OFF_MB : OFF_MA) + p * 1024 + (lane >> 3) * 256 + r * 128 + (lane & 7) * 16, b ? 0u : hh, b ? hh << 16 : hl >> 16, b ? hl : 0u, 0u);
        }
      }
      fence_async_smem();
      __syncwarp();
      if (elect()) {
        mbar_arrive(sb + BAR_STAT);
      }
      TS(2, 0 + L * 8);
    }
    if (!CO && L < 2 && w == 0) cs_image(L);
    if (L & 1) {
      const uint32_t flip = L == 1 ? 0u : 1u;
      mbar_wait(sb + BAR_SIGT, 1);
      {
        int it = 0;
        if (PSL) __nanosleep(m < 8 ? PSL : PSL + 600);
        while (!__all_sync(0xffffffffu, (ld_flag(reinterpret_cast<const unsigned*>(&g_kvpart[j][m][w][512]) + (lane & 15) * 8) ^ flip) & 1u)) { if (PSL) __nanosleep(100); if (++it > (1 << 22)) __trap(); }
        fence_async_global();
      }
      if (w == 0) TS(4, 6 + L * 2);
      float a[8], z;
      for (int it = 0;; it++) {
        if (elect()) { mbar_expect_tx(stb + rs.s * 8, 8704); bulk_load(stg, &g_kvpart[j][m][w][0], 8704, stb + rs.s * 8); }
        mbar_wait(stb + rs.s * 8, rs.ph);
        if (w == 0) TS(4, 21 + L);
        adv<3>(rs);
#pragma unroll
        for (int u = 0; u < 8; u++) a[u] = 0.f;
        z = 0.f;
        uint32_t ok = 1u;
#pragma unroll
        for (int u = 0; u < 4; u++) { const float v = lds32f(stg + 8192 + u * 128 + (lane & 3) * 32 + (lane >> 2) * 4); z += v; ok &= __float_as_uint(v) ^ flip; }
        const uint2 tg = sum_packets<8>(a, stg + lane * 16, 16);
        ok &= flip ? ~tg.y : tg.x;
        if (__all_sync(0xffffffffu, ok & 1u)) break;
        fence_async_smem();
        if (it > (1 << 16)) __trap();
      }
      {
        uint4* img = &g_kvfin[j][m][w * 8 + (lane >> 2)];
        uint32_t a0 = __float_as_uint(a[0]) >> 16;
        a0 += ~(a0 ^ flip) & 1u;
        st_v4(img + (lane & 3) * 16, __byte_perm(a0, pack2(0.f, a[1]), 0x7610), pack2(a[2], a[3]), pack2(a[4], a[5]), pack2(a[6], a[7]));
        const uint32_t cz = pack2(0.f, qsum(z)) | (0x3781u ^ flip);
        if (!(lane & 3)) st_v4(img + 64, cz, cz, cz, cz);
        __syncwarp();
        if (elect()) st_flag(&g_jflag[m >> 3][j][(m & 7) * 2 + w], tag * 4 + L);
      }
      if (w == 0) TS(4, 7 + L * 2);
    } else {
      if (L == 0 && w == 0) {
        st_v4(&g_kvpart[j][m][0][512 + lane], 0u, 0u, 0u, 0u); st_v4(&g_kvpart[j][m][1][512 + lane], 0u, 0u, 0u, 0u);
        __syncwarp();
      }
      mbar_wait(sb + BAR_SIGT, 0);
      if (w == 0) {
        if (elect()) { fence_gpu(); st_flag(&g_hint[m][j], tag * 16 + 4 * L); st_flag(&g_jflag[1][j][m], tag * 4 + L); }
        if (L == 0) {
          __nanosleep(KSL);
          poll_flags(&g_jflag[1][j][0], 16, 0xFFFFu, tag * 4);
          if (elect()) mbar_arrive(sb + BAR_WPHI);
        }
      } else if (m > 0) {
        poll_flags(&g_hint[m - 1][j], 1, 1u, tag * 16 + 4 * L);
        if (elect()) { mbar_expect_tx(sb + BAR_HALO, 8192); bulk_load(sb + OFF_S + 8192, &g_halo[m - 1][j][0][0], 8192, sb + BAR_HALO); }
        TS(2, 2 + L * 8);
      }
    }
    if (w == 0) {
#pragma unroll 1
      for (int e = 0; e < (L < 3 ? 2 : 1); e++) {
        unsigned* flag = early(&g_hint[m][j]);
        mbar_wait(sb + BAR_SIGP + e * 8, L & 1);
        TS(2, (e ? 6 : 3) + L * 8);
        TSH((2 * L + e) * 8);
        pause(L ? XD : (e ? XD1 : XD0));
        if (elect()) st_flag(flag, tag * 16 + 4 * L + 1 + e);
        TSH((2 * L + e) * 8 + 1);
      }
    } else {
#pragma unroll 1
      for (int i = 0; i < (L < 3 ? 28 : 14); i++) {
        const bool isx = i >= 14;
        const uint32_t a = sb + OFF_A + vs * SLOT + lane * 128 + ((lane >> 4) * 4 + (lane & 3)) * 16 + (lane & 12), code = img_code(isx, L + isx);
        for (int it = 0;; it++) {
          mbar_wait(sb + BAR_LAND + vs * 8, (vph >> vs) & 1);
          vph ^= 1u << vs;
          if (i - 14 * isx < 2) TSH((2 * L + isx) * 8 + 3 + 2 * (i - 14 * isx));
          uint32_t bad = 0;
#pragma unroll
          for (int u = 0; u < 4; u++) bad |= __float_as_uint(lds32f(a + u * 4096)) ^ code;
          if (__all_sync(0xffffffffu, !(bad & img_mask(isx)))) break;
          if (it > (1 << 16)) __trap();
          fence_async_smem();
          if (elect()) {
            mbar_expect_tx(sb + BAR_LAND + vs * 8, SLOT);
            bulk_load(sb + OFF_A + vs * SLOT, &g_img[isx ? XBUF(L + 1) : 0][m][o_order(i - 14 * isx + 2, j)][0], SLOT, sb + BAR_LAND + vs * 8);
          }
        }
        if (elect()) mbar_arrive(sb + BAR_FULLA + vs * 8);
        if (i - 14 * isx < 2) TSH((2 * L + isx) * 8 + 4 + 2 * (i - 14 * isx));
        if (++vs == NA) vs = 0;
      }
      vs = (vs + ((L & 1) ? 16 : 32 - NJ)) % NA;
    }
  }
}

__device__ __forceinline__ void spare(const Params& P, uint32_t sb, int id) {
  const int tid = threadIdx.x & 127, warp = __shfl_sync(0xffffffffu, threadIdx.x >> 5, 0), w = warp >> 2, lane = tid & 31, j = 2 * id + w;
  const uint32_t ring = w * 6 * SLOT, wp = 12 * SLOT + w * 8192, bar = sb + 13 * SLOT + w * 64;
  auto part = [&](int t) { return (t >> 4) ^ w; };
  auto load = [&](int t, uint32_t sl) {
    mbar_expect_tx(bar + sl * 8, t == 0 ? SLOT + 8192 : SLOT);
    tma_load_w(sb + ring + sl * SLOT, &P.mw[1], bar + sl * 8, part(t) * 1024 + 128 * j, t & 15);
  };
  if (!(warp & 3) && elect()) {
    if (w == 2) sts32(sb + OFF_EPOCH, atomicAdd(&g_ctr, 1u) / NCTA + 1u);
    else {
      __nanosleep(D3);
#pragma unroll 1
      for (int t = 0; t < 5; t++) {
        mbar_init(bar + t * 8, 1);
        asm volatile("fence.mbarrier_init.release.cluster;" ::: "memory");
        load(t, t);
      }
      tma_load_2d(sb + wp, &P.mwphi, bar, 0, 128 * j);
    }
  }
  __syncthreads();
  const unsigned tag = get_tag<false>(sb);
  if (w == 2) {
    int it = 0;
    while ((int)(ld_flag(&g_ctr) - tag * NCTA) < 0) { if (++it > (1 << 22)) __trap(); }
    return;
  }
  Ring r = {4, 1};
  float d[64];
  auto fold = [&]() {
    mbar_wait(bar + r.s * 8, r.ph);
    wgmma_fence();
#pragma unroll
    for (int q = 0; q < 8; q++)
      wgmma_ss_n32(reinterpret_cast<float (&)[16]>(d[16 * (q >> 1)]), desc_lo(SB + ring + r.s * SLOT, 16) + (q >> 2) * 512 + (q & 3) * 2, desc_lo(SB + wp, 512) + q * 64, q & 1);
    wgmma_commit();
  };
#pragma unroll
  for (int i = 0; i < 64; i++) d[i] = 0.f;
  int t = -1;
#pragma unroll 1
  for (int g = 0; g < 2; g++) {
    float cs[32] = {};
#pragma unroll 1
    do {
      uint32_t f[32];
#pragma unroll
      for (int i = 0; i < 32; i++) { f[i] = pack2(d[2 * i], d[2 * i + 1]); cs[i & 30] += d[2 * i]; cs[i | 1] += d[2 * i + 1]; }
      wg_bar(w);
      const uint32_t sl = r.s;
      if (t < 31) adv<5>(r);
      fold();
      if (!(warp & 3) && t >= 0 && t < 27 && elect()) load(t + 5, sl);
      if (g == w && t >= 0) {
        uint4* dst = &g_wf[0][j][t & 15][((tid >> 5) * 16 + (lane >> 2)) * 8];
#pragma unroll
        for (int q = 0; q < 8; q++)
          dst[(q >> 2) * 512 + (q & 1) * 64 + (((q & 2) * 2 + (lane & 3)) ^ (lane >> 2))] =
              make_uint4(f[4 * (q & 6) + (q & 1)], f[4 * (q & 6) + (q & 1) + 2], f[4 * (q & 6) + (q & 1) + 4], f[4 * (q & 6) + (q & 1) + 6]);
      }
      wgmma_wait<0>();
      fence_regs(d);
    } while (++t != 16 * g + 16);
    const uint32_t red = sb + ring + 5 * SLOT;
#pragma unroll
    for (int i = 0; i < 8; i++) sts128(red + (tid >> 2) * 512 + (i >> 1) * 128 + (lane & 3) * 32 + (i & 1) * 16, __float_as_uint(cs[4 * i]), __float_as_uint(cs[4 * i + 1]), __float_as_uint(cs[4 * i + 2]), __float_as_uint(cs[4 * i + 3]));
    wg_bar(w);
    float a = 0.f;
#pragma unroll 4
    for (int i = 0; i < 32; i++) a += lds32f(red + i * 512 + tid * 4);
    g_cs[1][0][(g ^ w) * 1024 + j * 128 + tid] = a;
  }
  wg_bar(w);
  if (tid == 0) { fence_gpu(); st_flag(&g_jflag[2][j][0], tag * 4); }
}

__global__ void __launch_bounds__(NTHREADS, 1) fused_kernel(const __grid_constant__ Params P) {
  extern __shared__ __align__(1024) uint8_t smem_raw[];
  constexpr uint32_t sb = SB;
  const int tid = threadIdx.x;
  const unsigned vb = vblock();
  if (vb >= 128) { spare(P, sb, vb - 128); return; }
  const int warp = __shfl_sync(0xffffffffu, tid >> 5, 0);
  if (elect()) {
    if (warp == 11) { prefetch_map(&P.mx); prefetch_map(&P.mw[0]); if (smem_u32(smem_raw) != SB) __trap(); }
    if (warp < 8) {
#pragma unroll
      for (int i = 0; i < 8; i++) mbar_init(sb + OFF_BAR + (warp * 8 + i) * 8, warp == 2 || warp == 3 ? 2 : (warp == 4 ? 8 : 1));
    }
    asm volatile("fence.mbarrier_init.release.cluster;" ::: "memory");
    if (warp < 2) {
      const int j = cta_j(vb);
#pragma unroll 1
      for (int i = 0; i < (warp == 0 ? PRE_B : PRE_A); i++) {
        const uint32_t bar = sb + BAR_FULLB + warp * 64 + i * 8;
        mbar_expect_tx(bar, SLOT);
        if (warp == 0) tma_load_w(sb + OFF_B + i * SLOT, &P.mw[0], bar, 1024 + (i & 1) * 1024 + 128 * j, kv_order(i >> 1, j, 0));
        else tma_load_3d(sb + OFF_A + i * SLOT, &P.mx, bar, kv_order(i, j, 0) * 64, cta_m(vb) * 64, 0);
      }
    }
  }
  if (tid == 0) TS(6, 0);
  __syncthreads();
  if (tid == 0) TS(6, 2);
  if (warp < 4) {
    reg_dealloc<PREGS>();
    if (warp & 2) helper(P, sb, warp & 1, vb);
    else if (warp & 1) a_loader(P, sb, vb);
    else b_producer(P, sb, vb);
  } else {
    reg_alloc<CREGS>();
    consumer(P, sb, (warp >> 2) - 1, vb);
  }
}

typedef CUresult (*EncodeFn)(CUtensorMap*, CUtensorMapDataType, cuuint32_t, void*, const cuuint64_t*, const cuuint64_t*,
                             const cuuint32_t*, const cuuint32_t*, CUtensorMapInterleave, CUtensorMapSwizzle,
                             CUtensorMapL2promotion, CUtensorMapFloatOOBfill);

void encode(EncodeFn fn, CUtensorMap* m, const void* ptr, int rank, const cuuint64_t* dims, const cuuint64_t* strides,
            const cuuint32_t* box, CUtensorMapSwizzle swz) {
  const cuuint32_t es[5] = {1, 1, 1, 1, 1};
  fn(m, CU_TENSOR_MAP_DATA_TYPE_BFLOAT16, rank, const_cast<void*>(ptr), dims, strides, box, es, CU_TENSOR_MAP_INTERLEAVE_NONE,
     swz, CU_TENSOR_MAP_L2_PROMOTION_L2_256B, CU_TENSOR_MAP_FLOAT_OOB_FILL_NONE);
}
void encode_w(EncodeFn fn, CUtensorMap* m, const void* ptr, int ncols, bool perm) {
  const cuuint64_t p = (cuuint64_t)ncols * 2, d[5] = {(cuuint64_t)ncols, 2, 4, 4, 32}, s[4] = {p, (perm ? 8 : 2) * p, (perm ? 2 : 8) * p, 32 * p};
  const cuuint32_t box[5] = {64, 2, 4, 4, 2};
  encode(fn, m, ptr, 5, d, s, box, CU_TENSOR_MAP_SWIZZLE_128B);
}

void encode_cs(EncodeFn fn, CUtensorMap* m, const void* ptr, int ncols) {
  const cuuint64_t d[2] = {(cuuint64_t)ncols, 1024}, s[1] = {(cuuint64_t)ncols * 2};
  const cuuint32_t box[2] = {32, 64};
  encode(fn, m, ptr, 2, d, s, box, CU_TENSOR_MAP_SWIZZLE_NONE);
}

}

extern "C" void kernel_launch(void* const* d_in, const int* in_sizes, int n_in, void* d_out, int out_size) {
  (void)in_sizes; (void)n_in; (void)out_size;
  void* fnp = nullptr;
  cudaDriverEntryPointQueryResult q;
  cudaGetDriverEntryPoint("cuTensorMapEncodeTiled", &fnp, cudaEnableDefault, &q);
  EncodeFn fn = (EncodeFn)fnp;
  Params P;
  {
    const cuuint64_t dims[3] = {1024, 1024, 2}, strides[2] = {4096, 2048};
    const cuuint32_t box[3] = {64, 64, 2};
    encode(fn, &P.mx, d_in[0], 3, dims, strides, box, CU_TENSOR_MAP_SWIZZLE_128B);
  }
  P.out = (uint4*)d_out;
  encode_w(fn, &P.mw[0], d_in[1], 3072, false);
  encode_w(fn, &P.mw[1], d_in[4], 3072, true);
  encode_w(fn, &P.mw[2], d_in[1], 3072, true);
  encode_w(fn, &P.mwo[0], d_in[2], 1024, true);
  encode_w(fn, &P.mwo[1], d_in[6], 1024, false);
  encode_cs(fn, &P.mcs[0], d_in[1], 3072);
  encode_cs(fn, &P.mcs[1], d_in[4], 3072);
  {
    const cuuint64_t dims[2] = {32, 1024}, strides[1] = {64};
    const cuuint32_t box[2] = {32, 128};
    encode(fn, &P.mwphi, d_in[5], 2, dims, strides, box, CU_TENSOR_MAP_SWIZZLE_64B);
  }
  cudaFuncSetAttribute(fused_kernel, cudaFuncAttributeMaxDynamicSharedMemorySize, SMEM_BYTES);
  fused_kernel<<<NCTA, NTHREADS, SMEM_BYTES, cudaStreamPerThread>>>(P);
}
```

```cpp
#include <cuda_runtime.h>
#include <cuda_bf16.h>
#include <cuda.h>
#include <stdint.h>

namespace {

__device__ __forceinline__ void wgmma_ss_n256(float (&d)[128], uint32_t da, uint32_t ha, uint32_t db, int sd) {
  asm volatile("{\n.reg .pred p;\n.reg .b64 a, b;\nsetp.ne.b32 p, %130, 0;\nmov.b64 a, {%128, %131};\nmov.b64 b, {%129, 0x40000040};\n"
    "wgmma.mma_async.sync.aligned.m64n256k16.f32.bf16.bf16 {%0,%1,%2,%3,%4,%5,%6,%7,%8,%9,%10,%11,%12,%13,%14,%15,%16,%17,%18,%19,%20,%21,%22,%23,%24,%25,%26,%27,%28,%29,%30,%31,%32,%33,%34,%35,%36,%37,%38,%39,%40,%41,%42,%43,%44,%45,%46,%47,%48,%49,%50,%51,%52,%53,%54,%55,%56,%57,%58,%59,%60,%61,%62,%63,%64,%65,%66,%67,%68,%69,%70,%71,%72,%73,%74,%75,%76,%77,%78,%79,%80,%81,%82,%83,%84,%85,%86,%87,%88,%89,%90,%91,%92,%93,%94,%95,%96,%97,%98,%99,%100,%101,%102,%103,%104,%105,%106,%107,%108,%109,%110,%111,%112,%113,%114,%115,%116,%117,%118,%119,%120,%121,%122,%123,%124,%125,%126,%127}, a, b, p, 1, 1, 0, 1;\n}\n"
    : "+f"(d[0]),"+f"(d[1]),"+f"(d[2]),"+f"(d[3]),"+f"(d[4]),"+f"(d[5]),"+f"(d[6]),"+f"(d[7]),"+f"(d[8]),"+f"(d[9]),"+f"(d[10]),"+f"(d[11]),"+f"(d[12]),"+f"(d[13]),"+f"(d[14]),"+f"(d[15]),"+f"(d[16]),"+f"(d[17]),"+f"(d[18]),"+f"(d[19]),"+f"(d[20]),"+f"(d[21]),"+f"(d[22]),"+f"(d[23]),"+f"(d[24]),"+f"(d[25]),"+f"(d[26]),"+f"(d[27]),"+f"(d[28]),"+f"(d[29]),"+f"(d[30]),"+f"(d[31]),"+f"(d[32]),"+f"(d[33]),"+f"(d[34]),"+f"(d[35]),"+f"(d[36]),"+f"(d[37]),"+f"(d[38]),"+f"(d[39]),"+f"(d[40]),"+f"(d[41]),"+f"(d[42]),"+f"(d[43]),"+f"(d[44]),"+f"(d[45]),"+f"(d[46]),"+f"(d[47]),"+f"(d[48]),"+f"(d[49]),"+f"(d[50]),"+f"(d[51]),"+f"(d[52]),"+f"(d[53]),"+f"(d[54]),"+f"(d[55]),"+f"(d[56]),"+f"(d[57]),"+f"(d[58]),"+f"(d[59]),"+f"(d[60]),"+f"(d[61]),"+f"(d[62]),"+f"(d[63]),"+f"(d[64]),"+f"(d[65]),"+f"(d[66]),"+f"(d[67]),"+f"(d[68]),"+f"(d[69]),"+f"(d[70]),"+f"(d[71]),"+f"(d[72]),"+f"(d[73]),"+f"(d[74]),"+f"(d[75]),"+f"(d[76]),"+f"(d[77]),"+f"(d[78]),"+f"(d[79]),"+f"(d[80]),"+f"(d[81]),"+f"(d[82]),"+f"(d[83]),"+f"(d[84]),"+f"(d[85]),"+f"(d[86]),"+f"(d[87]),"+f"(d[88]),"+f"(d[89]),"+f"(d[90]),"+f"(d[91]),"+f"(d[92]),"+f"(d[93]),"+f"(d[94]),"+f"(d[95]),"+f"(d[96]),"+f"(d[97]),"+f"(d[98]),"+f"(d[99]),"+f"(d[100]),"+f"(d[101]),"+f"(d[102]),"+f"(d[103]),"+f"(d[104]),"+f"(d[105]),"+f"(d[106]),"+f"(d[107]),"+f"(d[108]),"+f"(d[109]),"+f"(d[110]),"+f"(d[111]),"+f"(d[112]),"+f"(d[113]),"+f"(d[114]),"+f"(d[115]),"+f"(d[116]),"+f"(d[117]),"+f"(d[118]),"+f"(d[119]),"+f"(d[120]),"+f"(d[121]),"+f"(d[122]),"+f"(d[123]),"+f"(d[124]),"+f"(d[125]),"+f"(d[126]),"+f"(d[127])
    : "r"(da), "r"(db), "r"(sd), "r"(ha));
}
__device__ __forceinline__ void wgmma_ss_n128(float (&d)[64], uint32_t da, uint32_t ha, uint32_t db, int sd) {
  asm volatile("{\n.reg .pred p;\n.reg .b64 a, b;\nsetp.ne.b32 p, %66, 0;\nmov.b64 a, {%64, %67};\nmov.b64 b, {%65, 0x40000040};\n"
    "wgmma.mma_async.sync.aligned.m64n128k16.f32.bf16.bf16 {%0,%1,%2,%3,%4,%5,%6,%7,%8,%9,%10,%11,%12,%13,%14,%15,%16,%17,%18,%19,%20,%21,%22,%23,%24,%25,%26,%27,%28,%29,%30,%31,%32,%33,%34,%35,%36,%37,%38,%39,%40,%41,%42,%43,%44,%45,%46,%47,%48,%49,%50,%51,%52,%53,%54,%55,%56,%57,%58,%59,%60,%61,%62,%63}, a, b, p, 1, 1, 0, 1;\n}\n"
    : "+f"(d[0]),"+f"(d[1]),"+f"(d[2]),"+f"(d[3]),"+f"(d[4]),"+f"(d[5]),"+f"(d[6]),"+f"(d[7]),"+f"(d[8]),"+f"(d[9]),"+f"(d[10]),"+f"(d[11]),"+f"(d[12]),"+f"(d[13]),"+f"(d[14]),"+f"(d[15]),"+f"(d[16]),"+f"(d[17]),"+f"(d[18]),"+f"(d[19]),"+f"(d[20]),"+f"(d[21]),"+f"(d[22]),"+f"(d[23]),"+f"(d[24]),"+f"(d[25]),"+f"(d[26]),"+f"(d[27]),"+f"(d[28]),"+f"(d[29]),"+f"(d[30]),"+f"(d[31]),"+f"(d[32]),"+f"(d[33]),"+f"(d[34]),"+f"(d[35]),"+f"(d[36]),"+f"(d[37]),"+f"(d[38]),"+f"(d[39]),"+f"(d[40]),"+f"(d[41]),"+f"(d[42]),"+f"(d[43]),"+f"(d[44]),"+f"(d[45]),"+f"(d[46]),"+f"(d[47]),"+f"(d[48]),"+f"(d[49]),"+f"(d[50]),"+f"(d[51]),"+f"(d[52]),"+f"(d[53]),"+f"(d[54]),"+f"(d[55]),"+f"(d[56]),"+f"(d[57]),"+f"(d[58]),"+f"(d[59]),"+f"(d[60]),"+f"(d[61]),"+f"(d[62]),"+f"(d[63])
    : "r"(da), "r"(db), "r"(sd), "r"(ha));
}
__device__ __forceinline__ void wgmma_ss_n40_tt(float (&d)[20], uint32_t da, uint32_t db, int sd) {
  asm volatile("{\n.reg .pred p;\n.reg .b64 a, b;\nsetp.ne.b32 p, %22, 0;\nmov.b64 a, {%20, 0x40000040};\nmov.b64 b, {%21, 0x8};\n"
    "wgmma.mma_async.sync.aligned.m64n40k16.f32.bf16.bf16 {%0,%1,%2,%3,%4,%5,%6,%7,%8,%9,%10,%11,%12,%13,%14,%15,%16,%17,%18,%19}, a, b, p, 1, 1, 1, 1;\n}\n"
    : "+f"(d[0]),"+f"(d[1]),"+f"(d[2]),"+f"(d[3]),"+f"(d[4]),"+f"(d[5]),"+f"(d[6]),"+f"(d[7]),"+f"(d[8]),"+f"(d[9]),"+f"(d[10]),"+f"(d[11]),"+f"(d[12]),"+f"(d[13]),"+f"(d[14]),"+f"(d[15]),"+f"(d[16]),"+f"(d[17]),"+f"(d[18]),"+f"(d[19])
    : "r"(da), "r"(db), "r"(sd));
}
__device__ __forceinline__ void wgmma_ss_n32(float (&d)[16], uint32_t da, uint32_t db, int sd) {
  asm volatile("{\n.reg .pred p;\n.reg .b64 a, b;\nsetp.ne.b32 p, %18, 0;\nmov.b64 a, {%16, 0x40000040};\nmov.b64 b, {%17, 0x80000020};\n"
    "wgmma.mma_async.sync.aligned.m64n32k16.f32.bf16.bf16 {%0,%1,%2,%3,%4,%5,%6,%7,%8,%9,%10,%11,%12,%13,%14,%15}, a, b, p, 1, 1, 0, 1;\n}\n"
    : "+f"(d[0]),"+f"(d[1]),"+f"(d[2]),"+f"(d[3]),"+f"(d[4]),"+f"(d[5]),"+f"(d[6]),"+f"(d[7]),"+f"(d[8]),"+f"(d[9]),"+f"(d[10]),"+f"(d[11]),"+f"(d[12]),"+f"(d[13]),"+f"(d[14]),"+f"(d[15])
    : "r"(da), "r"(db), "r"(sd));
}
__device__ __forceinline__ void wgmma_rs_n40(float (&d)[20], uint32_t a0, uint32_t a1, uint32_t a2, uint32_t a3, uint32_t db, int sd) {
  asm volatile("{\n.reg .pred p;\n.reg .b64 b;\nsetp.ne.b32 p, %25, 0;\nmov.b64 b, {%24, 0x10};\n"
    "wgmma.mma_async.sync.aligned.m64n40k16.f32.bf16.bf16 {%0,%1,%2,%3,%4,%5,%6,%7,%8,%9,%10,%11,%12,%13,%14,%15,%16,%17,%18,%19}, {%20,%21,%22,%23}, b, p, 1, 1, 1;\n}\n"
    : "+f"(d[0]),"+f"(d[1]),"+f"(d[2]),"+f"(d[3]),"+f"(d[4]),"+f"(d[5]),"+f"(d[6]),"+f"(d[7]),"+f"(d[8]),"+f"(d[9]),"+f"(d[10]),"+f"(d[11]),"+f"(d[12]),"+f"(d[13]),"+f"(d[14]),"+f"(d[15]),"+f"(d[16]),"+f"(d[17]),"+f"(d[18]),"+f"(d[19])
    : "r"(a0), "r"(a1), "r"(a2), "r"(a3), "r"(db), "r"(sd));
}
__device__ __forceinline__ void wgmma_r1_n256(float (&d)[128], uint32_t da, uint32_t db, int sd) {
  asm volatile("{\n.reg .pred p;\n.reg .b64 a, b;\nsetp.ne.b32 p, %130, 0;\nmov.b64 a, {%128, 0x8};\nmov.b64 b, {%129, 0x6};\n"
    "wgmma.mma_async.sync.aligned.m64n256k16.f32.bf16.bf16 {%0,%1,%2,%3,%4,%5,%6,%7,%8,%9,%10,%11,%12,%13,%14,%15,%16,%17,%18,%19,%20,%21,%22,%23,%24,%25,%26,%27,%28,%29,%30,%31,%32,%33,%34,%35,%36,%37,%38,%39,%40,%41,%42,%43,%44,%45,%46,%47,%48,%49,%50,%51,%52,%53,%54,%55,%56,%57,%58,%59,%60,%61,%62,%63,%64,%65,%66,%67,%68,%69,%70,%71,%72,%73,%74,%75,%76,%77,%78,%79,%80,%81,%82,%83,%84,%85,%86,%87,%88,%89,%90,%91,%92,%93,%94,%95,%96,%97,%98,%99,%100,%101,%102,%103,%104,%105,%106,%107,%108,%109,%110,%111,%112,%113,%114,%115,%116,%117,%118,%119,%120,%121,%122,%123,%124,%125,%126,%127}, a, b, p, 1, 1, 0, 1;\n}\n"
    : "+f"(d[0]),"+f"(d[1]),"+f"(d[2]),"+f"(d[3]),"+f"(d[4]),"+f"(d[5]),"+f"(d[6]),"+f"(d[7]),"+f"(d[8]),"+f"(d[9]),"+f"(d[10]),"+f"(d[11]),"+f"(d[12]),"+f"(d[13]),"+f"(d[14]),"+f"(d[15]),"+f"(d[16]),"+f"(d[17]),"+f"(d[18]),"+f"(d[19]),"+f"(d[20]),"+f"(d[21]),"+f"(d[22]),"+f"(d[23]),"+f"(d[24]),"+f"(d[25]),"+f"(d[26]),"+f"(d[27]),"+f"(d[28]),"+f"(d[29]),"+f"(d[30]),"+f"(d[31]),"+f"(d[32]),"+f"(d[33]),"+f"(d[34]),"+f"(d[35]),"+f"(d[36]),"+f"(d[37]),"+f"(d[38]),"+f"(d[39]),"+f"(d[40]),"+f"(d[41]),"+f"(d[42]),"+f"(d[43]),"+f"(d[44]),"+f"(d[45]),"+f"(d[46]),"+f"(d[47]),"+f"(d[48]),"+f"(d[49]),"+f"(d[50]),"+f"(d[51]),"+f"(d[52]),"+f"(d[53]),"+f"(d[54]),"+f"(d[55]),"+f"(d[56]),"+f"(d[57]),"+f"(d[58]),"+f"(d[59]),"+f"(d[60]),"+f"(d[61]),"+f"(d[62]),"+f"(d[63]),"+f"(d[64]),"+f"(d[65]),"+f"(d[66]),"+f"(d[67]),"+f"(d[68]),"+f"(d[69]),"+f"(d[70]),"+f"(d[71]),"+f"(d[72]),"+f"(d[73]),"+f"(d[74]),"+f"(d[75]),"+f"(d[76]),"+f"(d[77]),"+f"(d[78]),"+f"(d[79]),"+f"(d[80]),"+f"(d[81]),"+f"(d[82]),"+f"(d[83]),"+f"(d[84]),"+f"(d[85]),"+f"(d[86]),"+f"(d[87]),"+f"(d[88]),"+f"(d[89]),"+f"(d[90]),"+f"(d[91]),"+f"(d[92]),"+f"(d[93]),"+f"(d[94]),"+f"(d[95]),"+f"(d[96]),"+f"(d[97]),"+f"(d[98]),"+f"(d[99]),"+f"(d[100]),"+f"(d[101]),"+f"(d[102]),"+f"(d[103]),"+f"(d[104]),"+f"(d[105]),"+f"(d[106]),"+f"(d[107]),"+f"(d[108]),"+f"(d[109]),"+f"(d[110]),"+f"(d[111]),"+f"(d[112]),"+f"(d[113]),"+f"(d[114]),"+f"(d[115]),"+f"(d[116]),"+f"(d[117]),"+f"(d[118]),"+f"(d[119]),"+f"(d[120]),"+f"(d[121]),"+f"(d[122]),"+f"(d[123]),"+f"(d[124]),"+f"(d[125]),"+f"(d[126]),"+f"(d[127])
    : "r"(da), "r"(db), "r"(sd));
}
__device__ __forceinline__ void wgmma_r1_n128(float (&d)[64], uint32_t da, uint32_t db, int sd) {
  asm volatile("{\n.reg .pred p;\n.reg .b64 a, b;\nsetp.ne.b32 p, %66, 0;\nmov.b64 a, {%64, 0x8};\nmov.b64 b, {%65, 0x6};\n"
    "wgmma.mma_async.sync.aligned.m64n128k16.f32.bf16.bf16 {%0,%1,%2,%3,%4,%5,%6,%7,%8,%9,%10,%11,%12,%13,%14,%15,%16,%17,%18,%19,%20,%21,%22,%23,%24,%25,%26,%27,%28,%29,%30,%31,%32,%33,%34,%35,%36,%37,%38,%39,%40,%41,%42,%43,%44,%45,%46,%47,%48,%49,%50,%51,%52,%53,%54,%55,%56,%57,%58,%59,%60,%61,%62,%63}, a, b, p, 1, 1, 0, 1;\n}\n"
    : "+f"(d[0]),"+f"(d[1]),"+f"(d[2]),"+f"(d[3]),"+f"(d[4]),"+f"(d[5]),"+f"(d[6]),"+f"(d[7]),"+f"(d[8]),"+f"(d[9]),"+f"(d[10]),"+f"(d[11]),"+f"(d[12]),"+f"(d[13]),"+f"(d[14]),"+f"(d[15]),"+f"(d[16]),"+f"(d[17]),"+f"(d[18]),"+f"(d[19]),"+f"(d[20]),"+f"(d[21]),"+f"(d[22]),"+f"(d[23]),"+f"(d[24]),"+f"(d[25]),"+f"(d[26]),"+f"(d[27]),"+f"(d[28]),"+f"(d[29]),"+f"(d[30]),"+f"(d[31]),"+f"(d[32]),"+f"(d[33]),"+f"(d[34]),"+f"(d[35]),"+f"(d[36]),"+f"(d[37]),"+f"(d[38]),"+f"(d[39]),"+f"(d[40]),"+f"(d[41]),"+f"(d[42]),"+f"(d[43]),"+f"(d[44]),"+f"(d[45]),"+f"(d[46]),"+f"(d[47]),"+f"(d[48]),"+f"(d[49]),"+f"(d[50]),"+f"(d[51]),"+f"(d[52]),"+f"(d[53]),"+f"(d[54]),"+f"(d[55]),"+f"(d[56]),"+f"(d[57]),"+f"(d[58]),"+f"(d[59]),"+f"(d[60]),"+f"(d[61]),"+f"(d[62]),"+f"(d[63])
    : "r"(da), "r"(db), "r"(sd));
}

__device__ __forceinline__ uint32_t smem_u32(const void* p) { return (uint32_t)__cvta_generic_to_shared(p); }
__device__ __forceinline__ void mbar_init(uint32_t bar, uint32_t cnt) { asm volatile("mbarrier.init.shared::cta.b64 [%0], %1;" ::"r"(bar), "r"(cnt)); }
__device__ __forceinline__ void mbar_expect_tx(uint32_t bar, uint32_t bytes) { asm volatile("mbarrier.arrive.expect_tx.shared::cta.b64 _, [%0], %1;" ::"r"(bar), "r"(bytes) : "memory"); }
__device__ __forceinline__ void mbar_arrive(uint32_t bar) { asm volatile("mbarrier.arrive.shared::cta.b64 _, [%0];" ::"r"(bar) : "memory"); }
__device__ __forceinline__ void mbar_arrive_n(uint32_t bar, uint32_t n) { asm volatile("mbarrier.arrive.shared::cta.b64 _, [%0], %1;" ::"r"(bar), "r"(n) : "memory"); }
__device__ __forceinline__ void mbar_wait(uint32_t bar, uint32_t parity) {
  asm volatile("{\n.reg .pred p;\nLAB_WAIT:\nmbarrier.try_wait.parity.shared::cta.b64 p, [%0], %1;\n@p bra DONE;\nbra LAB_WAIT;\nDONE:\n}" ::"r"(bar), "r"(parity) : "memory");
}
__device__ __forceinline__ void mbar_wait2(uint32_t a, uint32_t pa, uint32_t b, uint32_t pb) {
  asm volatile("{\n.reg .pred p, q;\nLAB_WAIT:\nmbarrier.try_wait.parity.shared::cta.b64 p, [%0], %1;\nmbarrier.try_wait.parity.shared::cta.b64 q, [%2], %3;\n"
               "and.pred p, p, q;\n@p bra DONE;\nbra LAB_WAIT;\nDONE:\n}" ::"r"(a), "r"(pa), "r"(b), "r"(pb) : "memory");
}
__device__ __forceinline__ void mbar_wait3(uint32_t a, uint32_t pa, uint32_t b, uint32_t pb) {
  asm volatile("{\n.reg .pred p, q, r;\nLAB_WAIT:\nmbarrier.try_wait.parity.shared::cta.b64 p, [%0], %1;\nmbarrier.try_wait.parity.shared::cta.b64 q, [%2], %3;\n"
               "mbarrier.try_wait.parity.shared::cta.b64 r, [%2+8], %3;\nand.pred p, p, q;\nand.pred p, p, r;\n@p bra DONE;\nbra LAB_WAIT;\nDONE:\n}" ::"r"(a), "r"(pa), "r"(b), "r"(pb) : "memory");
}
__device__ __forceinline__ bool mbar_probe2(uint32_t a, uint32_t pa, uint32_t b, uint32_t pb) {
  uint32_t ok;
  asm volatile("{\n.reg .pred p, q;\nmbarrier.test_wait.parity.shared::cta.b64 p, [%1], %2;\nmbarrier.test_wait.parity.shared::cta.b64 q, [%3], %4;\n"
               "and.pred p, p, q;\nselp.u32 %0, 1, 0, p;\n}" : "=r"(ok) : "r"(a), "r"(pa), "r"(b), "r"(pb) : "memory");
  return ok != 0;
}
__device__ __forceinline__ void tma_load_3d(uint32_t dst, const CUtensorMap* tm, uint32_t bar, int c0, int c1, int c2) {
  asm volatile("cp.async.bulk.tensor.3d.shared::cluster.global.mbarrier::complete_tx::bytes [%0], [%1, {%3, %4, %5}], [%2];"
               ::"r"(dst), "l"(tm), "r"(bar), "r"(c0), "r"(c1), "r"(c2) : "memory");
}
__device__ __forceinline__ void tma_load_2d(uint32_t dst, const CUtensorMap* tm, uint32_t bar, int c0, int c1) {
  asm volatile("cp.async.bulk.tensor.2d.shared::cluster.global.mbarrier::complete_tx::bytes [%0], [%1, {%3, %4}], [%2];"
               ::"r"(dst), "l"(tm), "r"(bar), "r"(c0), "r"(c1) : "memory");
}
__device__ __forceinline__ void tma_load_w(uint32_t dst, const CUtensorMap* tm, uint32_t bar, int col, int kb) {
#pragma unroll
  for (int q = 0; q < 2; q++)
    asm volatile("cp.async.bulk.tensor.5d.shared::cluster.global.mbarrier::complete_tx::bytes [%0], [%1, {%3, %4, %4, %4, %5}], [%2];"
                 ::"r"(dst + q * 8192), "l"(tm), "r"(bar), "r"(col + q * 64), "r"(0), "r"(2 * kb) : "memory");
}
__device__ __forceinline__ void tma_prefetch_w(const CUtensorMap* tm, int col, int kb) {
#pragma unroll
  for (int q = 0; q < 2; q++)
    asm volatile("cp.async.bulk.prefetch.tensor.5d.L2.global [%0, {%1, %2, %2, %2, %3}];" ::"l"(tm), "r"(col + q * 64), "r"(0), "r"(2 * kb) : "memory");
}
__device__ __forceinline__ void bulk_load(uint32_t dst, const void* g, uint32_t bytes, uint32_t bar) {
  asm volatile("cp.async.bulk.shared::cluster.global.mbarrier::complete_tx::bytes [%0], [%1], %2, [%3];" ::"r"(dst), "l"(g), "r"(bytes), "r"(bar) : "memory");
}
__device__ __forceinline__ void prefetch_map(const CUtensorMap* tm) { asm volatile("prefetch.tensormap [%0];" ::"l"(tm) : "memory"); }
__device__ __forceinline__ void fence_async_smem() { asm volatile("fence.proxy.async.shared::cta;" ::: "memory"); }
__device__ __forceinline__ void fence_async_global() { asm volatile("fence.proxy.async.global;" ::: "memory"); }
__device__ __forceinline__ void fence_gpu() { asm volatile("fence.release.gpu;" ::: "memory"); }
__device__ __forceinline__ void st_flag(unsigned* p, unsigned v) { asm volatile("st.relaxed.gpu.global.u32 [%0], %1;" ::"l"(p), "r"(v) : "memory"); }
__device__ __forceinline__ unsigned ld_flag(const unsigned* p) { unsigned v; asm volatile("ld.relaxed.gpu.global.u32 %0, [%1];" : "=r"(v) : "l"(p) : "memory"); return v; }
__device__ __forceinline__ uint4 ldcg4(const void* p) { uint4 v; asm volatile("ld.global.cg.v4.u32 {%0,%1,%2,%3}, [%4];" : "=r"(v.x), "=r"(v.y), "=r"(v.z), "=r"(v.w) : "l"(p)); return v; }
__device__ __forceinline__ uint4 ld_pkt(const uint4* p) {
  uint4 v; asm volatile("{\n.reg .b128 t;\nld.relaxed.gpu.global.b128 t, [%4];\nmov.b128 {%0,%1,%2,%3}, t;\n}" : "=r"(v.x), "=r"(v.y), "=r"(v.z), "=r"(v.w) : "l"(p) : "memory"); return v;
}
__device__ __forceinline__ void st_pkt(uint4* p, uint32_t a, uint32_t b, uint32_t c, uint32_t tag) {
  asm volatile("{\n.reg .b128 t;\nmov.b128 t, {%1,%2,%3,%4};\nst.relaxed.gpu.global.b128 [%0], t;\n}" ::"l"(p), "r"(a), "r"(b), "r"(c), "r"(tag) : "memory");
}
__device__ __forceinline__ void st_v4(uint4* p, uint32_t a, uint32_t b, uint32_t c, uint32_t d) { asm volatile("st.relaxed.gpu.global.v4.u32 [%0], {%1,%2,%3,%4};" ::"l"(p), "r"(a), "r"(b), "r"(c), "r"(d) : "memory"); }
__device__ __forceinline__ void stg128(uint4* p, uint4 v) { asm volatile("st.global.v4.u32 [%0], {%1,%2,%3,%4};" ::"l"(p), "r"(v.x), "r"(v.y), "r"(v.z), "r"(v.w) : "memory"); }
__device__ __forceinline__ void sts32(uint32_t addr, uint32_t a) { asm volatile("st.shared.u32 [%0], %1;" ::"r"(addr), "r"(a) : "memory"); }
__device__ __forceinline__ void sts64(uint32_t addr, uint32_t a, uint32_t b) { asm volatile("st.shared.v2.u32 [%0], {%1,%2};" ::"r"(addr), "r"(a), "r"(b) : "memory"); }
__device__ __forceinline__ uint32_t mul2(uint32_t a, uint32_t b) { uint32_t r; asm("mul.rn.bf16x2 %0, %1, %2;" : "=r"(r) : "r"(a), "r"(b)); return r; }
__device__ __forceinline__ uint32_t add2(uint32_t a, uint32_t b) { uint32_t r; asm("add.rn.bf16x2 %0, %1, %2;" : "=r"(r) : "r"(a), "r"(b)); return r; }
__device__ __forceinline__ bool elect() {
  uint32_t p; asm volatile("{\n.reg .pred q;\nelect.sync _|q, 0xffffffff;\nselp.u32 %0, 1, 0, q;\n}" : "=r"(p)); return p != 0;
}
__device__ __forceinline__ void wgmma_fence() { asm volatile("wgmma.fence.sync.aligned;" ::: "memory"); }
__device__ __forceinline__ void wgmma_commit() { asm volatile("wgmma.commit_group.sync.aligned;" ::: "memory"); }
template <int N> __device__ __forceinline__ void wgmma_wait() { asm volatile("wgmma.wait_group.sync.aligned %0;" ::"n"(N) : "memory"); }
template <int N> __device__ __forceinline__ void fence_regs(float (&d)[N]) {
#pragma unroll
  for (int i = 0; i < N; i++) asm volatile("" : "+f"(d[i])::"memory");
}
template <int R> __device__ __forceinline__ void reg_alloc() { asm volatile("setmaxnreg.inc.sync.aligned.u32 %0;" ::"n"(R)); }
template <int R> __device__ __forceinline__ void reg_dealloc() { asm volatile("setmaxnreg.dec.sync.aligned.u32 %0;" ::"n"(R)); }
__device__ __forceinline__ void wg_bar(int w) { asm volatile("bar.sync %0, 128;" ::"r"(w + 1) : "memory"); }
__device__ __forceinline__ constexpr uint32_t desc_lo(uint32_t addr, uint32_t lbo) { return (addr >> 4) + ((lbo >> 4) << 16); }
__device__ __forceinline__ uint32_t pack2(float lo, float hi) { uint32_t r; asm("cvt.rn.bf16x2.f32 %0, %1, %2;" : "=r"(r) : "f"(hi), "f"(lo)); return r; }
__device__ __forceinline__ float lo16(uint32_t v) { return __uint_as_float(v << 16); }
__device__ __forceinline__ float hi16(uint32_t v) { return __uint_as_float(v & 0xFFFF0000u); }
__device__ __forceinline__ float ex2(float x) { float r; asm("ex2.approx.ftz.f32 %0, %1;" : "=f"(r) : "f"(x)); return r; }
__device__ __forceinline__ float rcp(float x) { float r; asm("rcp.approx.ftz.f32 %0, %1;" : "=f"(r) : "f"(x)); return r; }
__device__ __forceinline__ uint32_t movm(uint32_t a) { uint32_t d; asm volatile("movmatrix.sync.aligned.m8n8.trans.b16 %0, %1;" : "=r"(d) : "r"(a)); return d; }
__device__ __forceinline__ void stsm4(uint32_t addr, uint32_t a, uint32_t b, uint32_t c, uint32_t d) {
  asm volatile("stmatrix.sync.aligned.m8n8.x4.shared.b16 [%0], {%1,%2,%3,%4};" ::"r"(addr), "r"(a), "r"(b), "r"(c), "r"(d) : "memory");
}
__device__ __forceinline__ void ldsm4(uint32_t addr, uint32_t (&r)[4]) {
  asm volatile("ldmatrix.sync.aligned.m8n8.x4.shared.b16 {%0,%1,%2,%3}, [%4];" : "=r"(r[0]), "=r"(r[1]), "=r"(r[2]), "=r"(r[3]) : "r"(addr) : "memory");
}
__device__ __forceinline__ void sts128(uint32_t addr, uint32_t a, uint32_t b, uint32_t c, uint32_t d) {
  asm volatile("st.shared.v4.u32 [%0], {%1,%2,%3,%4};" ::"r"(addr), "r"(a), "r"(b), "r"(c), "r"(d) : "memory");
}
__device__ __forceinline__ void lds128(uint32_t addr, uint32_t& a, uint32_t& b, uint32_t& c, uint32_t& d) {
  asm volatile("ld.shared.v4.u32 {%0,%1,%2,%3}, [%4];" : "=r"(a), "=r"(b), "=r"(c), "=r"(d) : "r"(addr) : "memory");
}
__device__ __forceinline__ float lds32f(uint32_t addr) { float v; asm volatile("ld.shared.f32 %0, [%1];" : "=f"(v) : "r"(addr) : "memory"); return v; }
__device__ __forceinline__ float2 lds64f(uint32_t addr) { float2 v; asm volatile("ld.shared.v2.f32 {%0,%1}, [%2];" : "=f"(v.x), "=f"(v.y) : "r"(addr) : "memory"); return v; }
__device__ __forceinline__ void mma16816(float (&d)[4], uint32_t a0, uint32_t a1, uint32_t a2, uint32_t a3, uint32_t b0, uint32_t b1) {
  asm("mma.sync.aligned.m16n8k16.row.col.f32.bf16.bf16.f32 {%0,%1,%2,%3}, {%4,%5,%6,%7}, {%8,%9}, {%0,%1,%2,%3};"
      : "+f"(d[0]), "+f"(d[1]), "+f"(d[2]), "+f"(d[3]) : "r"(a0), "r"(a1), "r"(a2), "r"(a3), "r"(b0), "r"(b1));
}
__device__ __forceinline__ void mma1688(float (&d)[4], uint32_t a0, uint32_t a1, uint32_t b0) {
  asm("mma.sync.aligned.m16n8k8.row.col.f32.bf16.bf16.f32 {%0,%1,%2,%3}, {%4,%5}, {%6}, {%0,%1,%2,%3};"
      : "+f"(d[0]), "+f"(d[1]), "+f"(d[2]), "+f"(d[3]) : "r"(a0), "r"(a1), "r"(b0));
}

__device__ __forceinline__ float qsum(float v) { v += __shfl_xor_sync(0xffffffffu, v, 1); v += __shfl_xor_sync(0xffffffffu, v, 2); return v; }

constexpr int NCTA = 132;
#define NB_ 6
#define NA_ 5
constexpr int NB = NB_;
constexpr int NA = NA_;
constexpr uint32_t SLOT = 16384;
constexpr uint32_t SB = 1024;
constexpr uint32_t OFF_B = 0;
constexpr uint32_t OFF_A = NB * SLOT;
constexpr uint32_t OFF_S = OFF_A + NA * SLOT;
constexpr uint32_t OFF_T = OFF_S + 20480;
constexpr uint32_t OFF_CS = OFF_T + 24576;
constexpr uint32_t OFF_MR = OFF_CS + 4640;
constexpr uint32_t OFF_BAR = OFF_MR + 512;
constexpr uint32_t OFF_MA = OFF_S, OFF_MB = OFF_CS - 2048;
constexpr uint32_t BAR_FULLB = OFF_BAR;
constexpr uint32_t BAR_FULLA = BAR_FULLB + 64;
constexpr uint32_t BAR_EMPTYB = BAR_FULLA + 64;
constexpr uint32_t BAR_EMPTYA = BAR_EMPTYB + 64;
constexpr uint32_t BAR_SIGP = BAR_EMPTYA + 64;
constexpr uint32_t BAR_SIGT = BAR_SIGP + 24;
constexpr uint32_t BAR_STAT = BAR_SIGP + 64;
constexpr uint32_t BAR_HALO = BAR_STAT + 16;
constexpr uint32_t BAR_CS = BAR_HALO + 8;
constexpr uint32_t BAR_WPHI = BAR_CS + 16;
constexpr uint32_t BAR_KV = BAR_WPHI + 8;
constexpr uint32_t BAR_STG = BAR_KV + 16;
constexpr uint32_t BAR_EPOCH = BAR_STG + 48;
constexpr uint32_t BAR_LAND = OFF_BAR + 7 * 64;
constexpr uint32_t OFF_EPOCH = OFF_BAR + 8 * 64;
static_assert(BAR_EPOCH < BAR_LAND, "barriers");
constexpr uint32_t SMEM_BYTES = OFF_EPOCH + 8;
static_assert(SMEM_BYTES <= 232448 && NB % 2 == 0 && NB <= 8 && NA <= 6, "smem");

#define CREGS 224
#define PREGS 56
#define PF1 19
#define PF2 21
#define PRE_A 2
#define PRE_B 4
#define CSNEED 0xF001u
#define XR 1
#define PS0 1
#define PS1 3
#define SD 1000
#define KSPLIT 12
#define KEEP 16
#define NJ 3
#define KSL 1000
#define PSL 0
#define KVS 12
#define D2 2000
#define D3 1500
#define G0 50
#define MAP 3
#define PMAP 0x76321450u
#define ZO 0
#define XA 3
#define XS 1
#define CP 500
#define S0 500
#define NS 2
#define XO 0
#define SW 2
#define SA 1
#define SB_ 4
#define ND0 1
#define KC 8
#define CO 0
#define SE 500
#define PAA 1600
#define PAX 900
#define PA0 1800
#define PX0 1100
#define XN 1
#define ZX 0
#define ZA 0
#define DEFER 3
#define DEFL 2
#define TSK 3
constexpr int NTHREADS = 384;

struct Params {
  CUtensorMap mx;
  CUtensorMap mw[3];
  CUtensorMap mwo[2];
  CUtensorMap mcs[2];
  CUtensorMap mwphi;
  uint4* out;
};

#define XBUF(L) 1
__device__ __align__(256) uint4 g_img[XBUF(3) + 1][16][16][1024];
__device__ __forceinline__ uint32_t img_code(bool isx, int L) { return isx ? (L & 1) | (L & 2) << 15 : ~L & 1; }
__device__ __forceinline__ uint32_t img_mask(bool isx) { return isx ? 0x10001u : 1u; }
__device__ __align__(256) uint4 g_wf[2][8][16][1024];
__device__ __align__(256) uint4 g_stats[16][2][8][32];
__device__ __align__(256) uint4 g_halo[16][8][2][256];
__device__ __align__(256) float g_cs[2][2][3072];
__device__ __align__(256) uint4 g_kvpart[8][16][2][544];
__device__ __align__(256) uint4 g_kvfin[8][16][80];
__device__ __align__(256) unsigned g_hint[16][32];
__device__ __align__(256) unsigned g_jflag[3][8][32];
__device__ unsigned g_ctr;
__device__ __forceinline__ unsigned vblock() {
  unsigned s;
  asm volatile("mov.u32 %0, %%smid;" : "=r"(s));
  const unsigned r = s & 1;
  s >>= 1;
  const unsigned t = s - 32, q = (t * 37) >> 8;
  const unsigned hi = s < 60 ? 12 + (t - 7 * q) * 8 + q : (s < 62 ? s + 4 : s - 58);
  unsigned b = 2 * (s < 32 ? (s & 7) * 8 + (s >> 3) : hi) + r;
  if (b < 128) b = (b & 15) | ((PMAP >> ((b >> 4) * 4)) & 7) << 4;
  if (s >= 62) b = 8 + 4 * r + s - 62;
  unsigned n;
  asm volatile("mov.u32 %0, %%nsmid;" : "=r"(n));
  return __shfl_sync(0xffffffffu, n == NCTA ? b : blockIdx.x, 0);
}
#define TS(who, id) do {} while (0)
#define TSW(id) do {} while (0)

#define TSH(id) do {} while (0)
#define TSMASK 0xFFFF
#define TSL_(a) do { if ((TSMASK >> (a)) & 1) TSW((a) + L * 12); } while (0)
__device__ __forceinline__ int cta_m(unsigned b) { return ((b >> 2) & 12) | (b & 3); }
__device__ __forceinline__ int cta_j(unsigned b) { return ((b >> 2) & 3) | ((b >> 4) & 4); }
struct Ring { uint32_t s, ph; };
template <int N> __device__ __forceinline__ void adv(Ring& r) { if (++r.s == N) { r.s = 0; r.ph ^= 1; } }
template <int N> __device__ __forceinline__ void rewind2(Ring& r) { if (r.s < 2) { r.s += N - 2; r.ph ^= 1; } else r.s -= 2; }
__device__ __forceinline__ int other_tile(int t, int j) { return (t == (j | 4) ? 7 : t) ^ (~j & 4); }
__device__ __forceinline__ int o_order(int i, int j) {
  if (i < 2) return 2 * j + i;
  const int odd = i >= 9;
  return 2 * other_tile(i - 2 - 7 * odd, j) + odd;
}
__device__ __forceinline__ int kv_order(int i, int j, int L) { return L > 0 ? o_order(i, j) : (i + 14 + 2 * (j & 4)) & 15; }

__device__ __forceinline__ unsigned poll_flags(const unsigned* f, int n, unsigned need, unsigned tag) {
  const int lane = threadIdx.x & 31;
  unsigned mask; int it = 0;
  do {
    unsigned v = lane < n ? ld_flag(f + lane) : 0u;
    mask = __ballot_sync(0xffffffffu, lane < n && (int)(v - tag) >= 0);
    if (++it > (1 << 22)) __trap();
  } while ((mask & need) != need);
  fence_async_global();
  return mask;
}
template <bool WAIT = true>
__device__ __forceinline__ unsigned get_tag(uint32_t sb) {
  if (WAIT) mbar_wait(sb + BAR_EPOCH, 0);
  unsigned t; asm volatile("ld.shared.u32 %0, [%1];" : "=r"(t) : "r"(sb + OFF_EPOCH) : "memory");
  return t;
}

__device__ __forceinline__ int lane_id() { int l; asm volatile("mov.u32 %0, %%laneid;" : "=r"(l)); return l; }
__device__ __forceinline__ unsigned seq4(unsigned tag, int L) { return 8u | ((tag & 1u) << 2) | (unsigned)L; }
constexpr float LOG2E = 1.4426950408889634f;

__device__ __forceinline__ float bb_fence(int never, const void* p = &g_ctr, uint32_t keep = 0) {
  while (never < 0) never = ld_flag((const unsigned*)p) + keep;
  return __int_as_float(never >> 30);
}
__device__ __forceinline__ uint32_t solid(uint32_t v) { return __shfl_sync(0xffffffffu, v, threadIdx.x & 31); }
template <class T> __device__ __forceinline__ T* solid(T* p) { return (T*)__shfl_sync(0xffffffffu, (unsigned long long)p, threadIdx.x & 31); }
constexpr uint32_t HA128 = 0x40000040u, HA64 = 0x80000040u;
struct Ctx {
  static constexpr uint32_t sb = SB;
  uint32_t ab, da0;
  int w, warp, lane, g, c;
  int goff;
  __device__ __forceinline__ int m() const { return goff >> 14; }
  __device__ __forceinline__ int j() const { return (goff >> 4) & 7; }
  bool elected;
  Ring ra, rb;
  uint32_t pa, pb;
  uint32_t ha, k2;
  uint32_t mrow, mxor, mhi;
  __device__ __forceinline__ uint32_t aslot(uint32_t s) const { return ab + s * SLOT; }
  __device__ __forceinline__ uint32_t fullA(uint32_t s) const { return sb + BAR_FULLA + s * 8; }
  __device__ __forceinline__ uint32_t fullB(uint32_t s) const { return sb + BAR_FULLB + s * 8; }
  __device__ __forceinline__ void releaseA(uint32_t s) const { if (elected) mbar_arrive(sb + BAR_EMPTYA + s * 8); }
  __device__ __forceinline__ void releaseB(uint32_t s) const { if (elected) mbar_arrive(sb + BAR_EMPTYB + s * 8); }
  __device__ __forceinline__ uint32_t maddr(uint32_t tile, uint32_t ch) const { return tile + mrow + (((ch + mhi) ^ mxor) << 4); }
  __device__ __forceinline__ uint32_t oo() const { return warp * 128 + g * 4 + (c ^ (g >> 1)); }
  __device__ __forceinline__ uint4* img(int b, int hp) const { return ip + (b * 256 + hp) * 1024; }
  uint4* ip;
  uint32_t so;
  __device__ __forceinline__ uint32_t held(int i) const { return ra.s + i < 2 ? ra.s + i + NA - 2 : ra.s + i - 2; }
};

template <int N, bool FIRST, bool O = true>
__device__ __forceinline__ void gemm_issue(float (&acc)[N / 2], Ctx& x, bool ready = false) {
  if (!ready) {
    if (N == 256) mbar_wait3(x.fullA(x.ra.s), x.ra.ph, x.fullB(x.rb.s), x.rb.ph);
    else mbar_wait2(x.fullA(x.ra.s), x.ra.ph, x.fullB(x.rb.s), x.rb.ph);
  }
  const uint32_t da = x.da0 + x.ra.s * (SLOT / 16), db = desc_lo(SB + OFF_B, 8192) + x.rb.s * (SLOT / 16);
  wgmma_fence();
#pragma unroll
  for (int k = 0; k < 4; k++) {
    const uint32_t a = da + (k >> 1) * (O ? 32 : x.k2) + (k & 1) * 2, ha = O ? HA64 : x.ha;
    if constexpr (N == 256) wgmma_ss_n256(acc, a, ha, db + 128 * k, !(FIRST && k == 0));
    else wgmma_ss_n128(acc, a, ha, db + 128 * k, !(FIRST && k == 0));
  }
  wgmma_commit();
}
template <int N>
__device__ __forceinline__ void gemm_next(Ctx& x) {
  x.pa = x.ra.s; x.pb = x.rb.s;
  if (N == 256) x.rb.s++;
  adv<NA>(x.ra); adv<NB>(x.rb);
}
template <int N>
__device__ __forceinline__ void gemm_release(Ctx& x, bool relA) {
  if (relA) x.releaseA(x.pa);
  x.releaseB(x.pb);
  if (N == 256) x.releaseB(x.pb + 1);
}
template <int N>
__device__ __forceinline__ void gemm_retire(Ctx& x, bool relA) { wgmma_wait<1>(); gemm_release<N>(x, relA); gemm_next<N>(x); }
template <bool O = true>
__device__ __forceinline__ void gemm_run(float (&acc)[64], Ctx& x, int n, int hold, int n4 = 0) {
  bool ready = false;
#pragma unroll 1
  for (; n > 0; n--) {
    gemm_issue<128, false, O>(acc, x, ready);
    const uint32_t pa = x.pa, pb = x.pb;
    gemm_next<128>(x);
    ready = mbar_probe2(x.fullA(x.ra.s), x.ra.ph, x.fullB(x.rb.s), x.rb.ph);
    wgmma_wait<1>();
    if (n > hold) x.releaseA(pa);
    x.releaseB(pb);
  }
}
__device__ __forceinline__ void gemm_end(float (&acc)[64], Ctx& x) { wgmma_wait<0>(); fence_regs(acc); gemm_release<128>(x, false); }

__device__ __forceinline__ void rows_load(uint4* r, uint32_t tile, const Ctx& x) {
#pragma unroll
  for (int q = 0; q < 4; q++) {
    const uint32_t row = x.warp * 16 + 4 * q + (x.lane >> 3);
    lds128(tile + row * 128 + (((x.lane & 7) ^ (row & 7)) << 4), r[q].x, r[q].y, r[q].z, r[q].w);
  }
}
__device__ __forceinline__ void rows_store(const uint4* r, uint4* g) {
#pragma unroll
  for (int q = 0; q < 4; q++) stg128(g + q * 1024, r[q]);
}
__device__ __forceinline__ void publish(int id, const Ctx& x) { __syncwarp(); if (x.lane == 0) mbar_arrive(x.sb + BAR_SIGP + id * 8); }
__device__ __forceinline__ uint32_t img_tag(uint32_t v, bool isx, int L, const Ctx& x) {
  const uint32_t mk = ((x.lane ^ (x.warp * 4)) & 7) ? 0u : img_mask(isx);
  return (v & ~mk) | (img_code(isx, L) & mk);
}
__device__ __forceinline__ void img_tag(uint4 (&r)[4], bool isx, int L, const Ctx& x) {
#pragma unroll
  for (int q = 0; q < 4; q++) { uint32_t& v = q == 0 ? r[q].x : (q == 1 ? r[q].y : (q == 2 ? r[q].z : r[q].w)); v = img_tag(v, isx, L, x); }
}
__device__ __forceinline__ void img_store(const uint4 (&r)[4], uint4* g) {
#pragma unroll
  for (int q = 0; q < 4; q++) stg128(g + q * 32, r[q]);
}
__device__ __forceinline__ void img_sts(const uint4 (&r)[4], uint32_t tile, const Ctx& x) {
#pragma unroll
  for (int q = 0; q < 4; q++) sts128(tile + x.so + q * 512, r[q].x, r[q].y, r[q].z, r[q].w);
}
__device__ __forceinline__ void img_load(uint32_t (&v)[16], uint32_t tile, const Ctx& x) {
#pragma unroll
  for (int q = 0; q < 4; q++) lds128(tile + x.so + q * 512, v[4 * q], v[4 * q + 1], v[4 * q + 2], v[4 * q + 3]);
}
__device__ __forceinline__ void img_unpack(float* a, const uint32_t (&v)[16]) {
#pragma unroll
  for (int q = 0; q < 16; q++) { a[4 * (q & 7) + 2 * (q >> 3)] = lo16(v[q]); a[4 * (q & 7) + 2 * (q >> 3) + 1] = hi16(v[q]); }
}

template <int N>
__device__ __forceinline__ void stats_acc(const float* a, float (&t)[4]) {
#pragma unroll
  for (int i = 0; i < N; i++) { t[i & 2] += a[i]; t[(i & 2) + 1] = fmaf(a[i], a[i], t[(i & 2) + 1]); }
}
__device__ __forceinline__ void stats_send(float (&t)[4], int L, const Ctx& x) {
  const unsigned seq = seq4(get_tag<false>(x.sb), L);
#pragma unroll
  for (int q = 0; q < 4; q++) t[q] = qsum(t[q]);
  if (x.c == 0) st_pkt(&g_stats[x.m()][x.w][x.j()][x.warp * 8 + x.g], __float_as_uint(t[0]), __float_as_uint(t[1]), __float_as_uint(t[2]), (__float_as_uint(t[3]) & ~15u) | seq);
}
__device__ __forceinline__ void out_epilogue(const float (&acc)[64], uint4 (&r1)[4], float (&t)[4], uint4* g, int L, Ctx& x) {
  const uint32_t t0 = x.aslot(x.ra.s), t1 = x.aslot(x.ra.s + 1 == NA ? 0 : x.ra.s + 1);
  if (L == 3) {
#pragma unroll
    for (int p = 0; p < 8; p++) {
      stsm4(x.maddr(p < 4 ? t0 : t1, (p & 3) * 2), pack2(acc[8 * p], acc[8 * p + 1]), pack2(acc[8 * p + 2], acc[8 * p + 3]),
            pack2(acc[8 * p + 4], acc[8 * p + 5]), pack2(acc[8 * p + 6], acc[8 * p + 7]));
      if ((p & 3) == 3) { uint4 r[4]; __syncwarp(); rows_load(r, p < 4 ? t0 : t1, x); rows_store(r, g + (p >> 2) * 8); }
    }
  } else {
    auto pack16 = [&](uint4 (&r)[4], const float* a) {
#pragma unroll
      for (int q = 0; q < 4; q++) { const float* u = a + 16 * (q & 1) + (q & 2); r[q] = make_uint4(pack2(u[0], u[1]), pack2(u[4], u[5]), pack2(u[8], u[9]), pack2(u[12], u[13])); }
    };
    uint4 r0[4];
    pack16(r0, acc);
    img_tag(r0, true, L + 1, x);
    if (ZX == 1) img_sts(r0, t0, x);
    if (ZX < 2) img_store(r0, x.img(XBUF(L + 1), 0));
    const float z = ZX < 2 ? bb_fence(x.goff) : 0.f;
    if (ZX != 1) img_sts(r0, t0, x);
    pack16(r1, acc + 32);
    img_tag(r1, true, L + 1, x);
    img_sts(r1, t1, x);
    float u[4] = {z, z, z, z}, v[4] = {z, z, z, z};
    stats_acc<32>(acc, v);
    stats_acc<32>(acc + 32, u);
#pragma unroll
    for (int q = 0; q < 4; q++) t[q] = u[q] + v[q];
    mbar_wait2(x.fullB(x.rb.s), x.rb.ph, x.fullB(x.rb.s + 1), x.rb.ph);
    fence_async_smem();
    asm volatile("bar.sync %0, %1;" ::"r"(L == 1 ? x.w + 1 : 3), "r"(L == 1 ? 128 : 256) : "memory");
    if (ZX == 2) img_store(r0, x.img(XBUF(L + 1), 0));
  }
}

struct Stats { float rstd0, rstd1; };
__device__ __forceinline__ Stats load_stats(int half, const Ctx& x) {
  const float2 u = lds64f(x.sb + OFF_MR + half * 256 + (x.warp * 8 + x.g) * 8);
  return {u.x, u.y};
}

template <int NH, int NK, class F>
__device__ __forceinline__ void hedgehog_scale(float* t, const Stats& st, const uint32_t* keep, F use) {
#pragma unroll
  for (int q = 0; q < 16 * NH; q++) t[q] *= ((q & 2) ? st.rstd1 : st.rstd0) * LOG2E;
  use();
  float m[4];
#pragma unroll
  for (int q = 0; q < 4 * NH; q++) {
    const float v = fmaxf(fmaxf(fabsf(t[4 * q]), fabsf(t[4 * q + 1])), fmaxf(fabsf(t[4 * q + 2]), fabsf(t[4 * q + 3])));
    m[q & 3] = q < 4 ? v : fmaxf(m[q & 3], v);
  }
  if (__builtin_expect(__any_sync(0xffffffffu, fmaxf(fmaxf(m[0], m[1]), fmaxf(m[2], m[3])) > 58.f), 0)) {
    float z[16 * NH + NK];
#pragma unroll
    for (int q = 0; q < 16 * NH + NK; q++) z[q] = q < 16 * NH ? t[q % (16 * NH)] : __uint_as_float(keep[q & 15]);
#pragma unroll 1
    for (int r = 0; r < 2 * NH; r++) {
      float hi = -INFINITY, lo = INFINITY;
#pragma unroll 1
      for (int i = 0; i < 16; i++) {
        const int k = (i & 6) * 2 + (i & 1) + (r & 1) * 2 + (r & 2) * 8;
        const float v = z[k];
        if (i < 8) { hi = fmaxf(hi, v); lo = fminf(lo, v); }
        else z[k] = v - fminf(fmaxf(v, lo), hi);
        if (i == 7) {
#pragma unroll 1
          for (int d = 1; d <= 2; d++) { hi = fmaxf(hi, __shfl_xor_sync(0xffffffffu, hi, d)); lo = fminf(lo, __shfl_xor_sync(0xffffffffu, lo, d)); }
          const float mid = 0.5f * hi + 0.5f * lo;
          hi = fmaxf(hi - 58.f, mid); lo = fminf(lo + 58.f, mid);
        }
      }
    }
#pragma unroll
    for (int q = 0; q < 16 * NH; q++) t[q] = z[q];
    use();
  }
}
__device__ __forceinline__ void dual_exp(const float* t, uint32_t (&f)[18], int never) {
  float e[KSPLIT];
#pragma unroll
  for (int q = 0; q < KSPLIT; q++) e[q] = ex2(q < 16 ? t[q] : -t[q & 15]);
  while (never < 0) {
#pragma unroll
    for (int i = 0; i < KSPLIT; i += 4) asm volatile("ld.shared.v4.f32 {%0,%1,%2,%3}, [%4];" : "=f"(e[i]), "=f"(e[i + 1]), "=f"(e[i + 2]), "=f"(e[i + 3]) : "r"(never + i) : "memory");
    never += __float_as_int(e[0]);
  }
#pragma unroll
  for (int q = 0; q < KSPLIT; q += 2) f[q >> 1] = pack2(e[q], e[q + 1]);
#pragma unroll
  for (int q = KSPLIT; q < 32; q += 2) f[q >> 1] = q < 16 ? pack2(ex2(t[q]), ex2(t[q + 1])) : pack2(ex2(-t[q & 15]), ex2(-t[(q & 15) + 1]));
#pragma unroll
  for (int sg = 0; sg < 2; sg++) {
    const uint32_t* u = f + 8 * sg;
    const uint32_t a = add2(add2(u[0], u[2]), add2(u[4], u[6])), b = add2(add2(u[1], u[3]), add2(u[5], u[7]));
    f[16 + sg] = add2(__byte_perm(a, b, 0x5410), __byte_perm(a, b, 0x7632));
  }
}
__device__ __forceinline__ void dual_exp_rcp(const float* t, uint32_t* f) {
#pragma unroll
  for (int q = 0; q < 8; q++) {
    const float a = ex2(t[2 * q]), b = ex2(t[2 * q + 1]), r = rcp(a * b);
    f[q] = pack2(a, b); f[8 + q] = pack2(r * b, r * a);
  }
}
__device__ __forceinline__ void cta_bar() { asm volatile("bar.sync 3, 256;" ::: "memory"); }

template <int N> __device__ __forceinline__ void pin(const uint32_t* v, uint32_t addr) {
#pragma unroll
  for (int i = 0; i < N; i += 4)
    asm volatile("{\n.reg .pred p;\nsetp.eq.u32 p, %0, 0;\n@p st.shared.v4.u32 [%0], {%1,%2,%3,%4};\n}" ::"r"(addr), "r"(v[i]), "r"(v[i + 1]), "r"(v[i + 2]), "r"(v[i + 3]) : "memory");
}

__device__ __forceinline__ void consumer(const Params& P, uint32_t sb, int w, unsigned vb) {
  Ctx x;
  x.w = w;
  x.ab = sb + OFF_A + w * 8192; x.da0 = desc_lo(SB + OFF_A, 16) + w * 512;
  x.lane = threadIdx.x & 31; x.warp = __shfl_sync(0xffffffffu, (threadIdx.x >> 5) & 3, 0); x.g = x.lane >> 2; x.c = x.lane & 3;
  x.goff = (cta_m(vb) * 128 + w) * 128 + cta_j(vb) * 16;
  asm volatile("" : "+r"(x.goff));
  x.elected = (threadIdx.x & 127) == 0;
  x.ra = {0, 0}; x.rb = {0, 0}; x.pa = x.pb = 0;
  {
    const uint32_t row = x.warp * 16 + (x.lane & 15);
    x.mrow = row * 128; x.mxor = row & 7; x.mhi = x.lane >> 4;
  }
  const int goff = x.goff;
  x.ip = solid(&g_img[0][x.m()][2 * x.j()][w * 512 + x.oo()]);
  x.so = solid(16 * x.oo());
  uint4 r1[4];
  float ts[4] = {0.f, 0.f, 0.f, 0.f};
#pragma unroll
  for (int i = 0; i < 4; i++) r1[i] = make_uint4(0, 0, 0, 0);
  TSW(0);
  mbar_wait3(x.fullA(0), 0, x.fullB(0), 0);
#pragma unroll 1
  for (int L = 0; L < 4; L++) {
    float acc[64];
    constexpr uint32_t dcs = desc_lo(SB + OFF_CS, 0);
    if ((L & 1) == 0) {
    float kv[128];
    x.ha = L ? HA64 : HA128; x.k2 = L ? 32 : 4;
    gemm_issue<256, true, false>(kv, x, true); gemm_next<256>(x);
    {
      int i = 1;
#pragma unroll 1
      for (int seg = L ? NS - 1 : 0; seg <= NS; seg++) {
        const int end = seg < NS ? (L == 0 ? 3 + SA * ((x.j() + SW * w) & 3) + SB_ * seg : XA + 1) : 14 + L;
#pragma unroll 1
        do {
          gemm_issue<256, false, false>(kv, x);
          gemm_retire<256>(x, true);
          i++;
          if (i == 5) TSL_(8);
          if (i == 11) TSL_(10);
        } while (i != end);
        if (seg < NS && L == 0) {
          uint32_t v[16];
          float a[32];
#pragma unroll
          for (int q = 0; q < 4; q++) ldsm4(x.maddr(x.aslot(x.pa), 2 * q), reinterpret_cast<uint32_t (&)[4]>(v[4 * q]));
#pragma unroll
          for (int q = 0; q < 16; q++) { a[2 * q] = lo16(v[q]); a[2 * q + 1] = hi16(v[q]); }
          stats_acc<32>(a, ts);
          fence_regs(ts);
          wg_bar(w);
        }
        if (seg == NS - 1) {
          if (L > 0) { img_store(r1, x.img(XBUF(L), 1)); publish(2, x); }
          mbar_wait(sb + BAR_EPOCH, 0);
          stats_send(ts, L, x);
        }
      }
    }
      const Ring kt = x.ra;
      if (L == 0) adv<NA>(x.ra);
#pragma unroll 1
      for (int h = L; h < 2; h++) {
        float d[16];
        mbar_wait2(x.fullA(kt.s), kt.ph, sb + BAR_WPHI, 0);
        wgmma_fence();
#pragma unroll
        for (int q = 0; q < 2; q++) wgmma_ss_n32(d, x.da0 + kt.s * (SLOT / 16) + h * 4 + q * 2, desc_lo(SB + OFF_S + 4096, 512) + w * 256 + h * 128 + q * 64, q);
        wgmma_commit();
        gemm_issue<256, false, false>(kv, x);
        gemm_retire<256>(x, true);
        if (h) x.releaseA(kt.s);
        fence_regs(d);
        uint4* dst = &g_wf[1][x.j()][x.m()][w * 512 + (x.warp * 16 + x.g) * 8 + ((h * 4 + x.c) ^ x.g)];
        dst[0] = make_uint4(pack2(d[0], d[1]), pack2(d[4], d[5]), pack2(d[8], d[9]), pack2(d[12], d[13]));
        dst[64] = make_uint4(pack2(d[2], d[3]), pack2(d[6], d[7]), pack2(d[10], d[11]), pack2(d[14], d[15]));
      }
      const uint32_t dm = desc_lo(SB + OFF_MA, 0) + w * 64;
      mbar_wait2(sb + BAR_STAT, 0, sb + BAR_CS, 0);
      wgmma_fence();
      wgmma_r1_n256(kv, dm, dcs + 96, 1);
      wgmma_commit();
      const Stats st = load_stats(w, x);
      mbar_wait2(x.fullA(x.ra.s), x.ra.ph, x.fullB(x.rb.s), x.rb.ph);
      wgmma_wait<0>();
      fence_regs(kv);
      gemm_release<256>(x, true);
      TSL_(2);
      uint32_t P0[32], P1[32], PH[32];
#pragma unroll
      for (int t = 0; t < 16; t++) { P0[t] = pack2(kv[4 * t] * st.rstd0, kv[4 * t + 1] * st.rstd0); P1[t] = pack2(kv[4 * t + 2] * st.rstd1, kv[4 * t + 3] * st.rstd1); }
      pin<16>(P0, x.mrow + 16);
      {
#pragma unroll
        for (int q = 0; q < 4; q++) sts128((x.warp < 3 ? sb + OFF_T + w * 12288 + x.warp * 4096 : sb + OFF_S + 16384 + w * 2048) + x.lane * 16 + q * 512, P1[4 * q], P1[4 * q + 1], P1[4 * q + 2], P1[4 * q + 3]);
      }
      wgmma_fence();
      wgmma_r1_n128(acc, dm, dcs, 0);
      gemm_issue<128, false, false>(acc, x, true); gemm_next<128>(x);
      TSL_(3);
#pragma unroll
      for (int s = 0; s < 4; s++) {
#pragma unroll
        for (int t = 16 + 8 * (s & 1); t < 24 + 8 * (s & 1); t++) {
          if (s < 2) P1[t] = movm(pack2(kv[4 * t + 2] * st.rstd1, kv[4 * t + 3] * st.rstd1));
          else P0[t] = movm(pack2(kv[4 * t] * st.rstd0, kv[4 * t + 1] * st.rstd0));
        }
        if (s < 3) { gemm_issue<128, false, false>(acc, x); gemm_retire<128>(x, true); }
        if (s == 1) {
          if (x.warp < 3) {
#pragma unroll
            for (int q = 4; q < 8; q++) sts128(sb + OFF_T + w * 12288 + x.warp * 4096 + x.lane * 16 + q * 512, P1[4 * q], P1[4 * q + 1], P1[4 * q + 2], P1[4 * q + 3]);
          } else {
            uint4* dst = &g_halo[x.m()][x.j()][w][x.lane];
#pragma unroll
            for (int q = 0; q < 8; q++) dst[q * 32] = make_uint4(P1[4 * q], P1[4 * q + 1], P1[4 * q + 2], P1[4 * q + 3]);
          }
          publish(3, x);
          gemm_issue<128, false, false>(acc, x);
          gemm_retire<128>(x, true);
        }
      }
      TSL_(4);
      gemm_run<false>(acc, x, 10, 0);
      publish(0, x);
      gemm_issue<128, false, false>(acc, x);
      {
        wg_bar(w);
        uint32_t tr = sb + OFF_T + w * 12288 + (x.warp - 1) * 4096;
        if (x.warp == 0) {
          tr = x.m() > 0 ? sb + OFF_S + 8192 + w * 4096 : tr + 4096;
          if (x.m() > 0) mbar_wait(sb + BAR_HALO, L >> 1);
        }
#pragma unroll
        for (int q = 0; q < 8; q++) lds128(tr + x.lane * 16 + q * 512, PH[4 * q], PH[4 * q + 1], PH[4 * q + 2], PH[4 * q + 3]);
      }
      gemm_retire<128>(x, false);
      gemm_end(acc, x);
      TSL_(5);
      const bool first = (x.m() == 0) && (x.warp == 0);
      const bool hi0 = 2 * x.c > x.g, hi1 = 2 * x.c + 1 > x.g;
      const uint32_t mhi = (hi0 ? 0xFFFFu : 0u) | (hi1 ? 0xFFFF0000u : 0u);
      const uint32_t valid = first ? ~mhi : ~0u;
      const float sc0 = st.rstd0 * (0.17677669529663687f * LOG2E), sc1 = st.rstd1 * (0.17677669529663687f * LOG2E);
      uint32_t xr[2][16];
#pragma unroll
      for (int hp = 0; hp < 2; hp++) {
        const uint32_t tile = x.aslot(x.held(hp));
        uint32_t px[2], py[2];
        float s[2][3][4];
#pragma unroll
        for (int u = 0; u < 2; u++) {
#pragma unroll
          for (int q = 0; q < 12; q++) s[u][q >> 2][q & 3] = 0.f;
#pragma unroll
          for (int ks = 0; ks < 2; ks++) {
            const int t = 8 * hp + 4 * u + 2 * ks;
            const uint32_t a0 = pack2(acc[4 * t], acc[4 * t + 1]), a1 = pack2(acc[4 * t + 2], acc[4 * t + 3]);
            const uint32_t a2 = pack2(acc[4 * t + 4], acc[4 * t + 5]), a3 = pack2(acc[4 * t + 6], acc[4 * t + 7]);
            mma16816(s[u][0], a0, a1, a2, a3, PH[t], PH[t + 1]);
            mma16816(s[u][1], a0, a1, a2, a3, P0[t], P0[t + 1]);
            mma16816(s[u][2], a0, a1, a2, a3, P1[t], P1[t + 1]);
          }
        }
        float e[2][4], big = 0.f;
#pragma unroll
        for (int u = 0; u < 2; u++) {
          e[u][0] = (hi0 ? s[u][0][0] : s[u][1][0]) * sc0; e[u][1] = (hi1 ? s[u][0][1] : s[u][1][1]) * sc0;
          e[u][2] = (hi0 ? s[u][1][2] : s[u][2][2]) * sc1; e[u][3] = (hi1 ? s[u][1][3] : s[u][2][3]) * sc1;
          big = fmaxf(big, fmaxf(fmaxf(fabsf(e[u][0]), fabsf(e[u][1])), fmaxf(fabsf(e[u][2]), fabsf(e[u][3]))));
          px[u] = pack2(ex2(e[u][0]), ex2(e[u][1])) & valid; py[u] = pack2(ex2(e[u][2]), ex2(e[u][3]));
        }
        if (__builtin_expect(__any_sync(0xffffffffu, big > 58.f), 0)) {
#pragma unroll
          for (int q = 0; q < 4; q++) {
            float v0 = e[q >> 1][2 * (q & 1)], v1 = e[q >> 1][2 * (q & 1) + 1];
            if (first && !(q & 1)) { if (hi0) v0 = -INFINITY; if (hi1) v1 = -INFINITY; }
            float r = fmaxf(v0, v1);
            r = fmaxf(r, __shfl_xor_sync(0xffffffffu, r, 1)); r = fmaxf(r, __shfl_xor_sync(0xffffffffu, r, 2));
            ((q & 1) ? py : px)[q >> 1] = pack2(ex2(v0 - r), ex2(v1 - r));
          }
        }
        float r[2][2];
#pragma unroll
        for (int u = 0; u < 2; u++) {
          float d[4] = {0.f, 0.f, 0.f, 0.f};
          mma1688(d, px[u], py[u], 0x3F803F80u);
          r[u][0] = rcp(d[0]); r[u][1] = rcp(d[2]);
        }
        uint32_t o[8][2];
        uint4 ro[4];
#pragma unroll
        for (int q = 0; q < 8; q++) {
          float d[4] = {0.f, 0.f, 0.f, 0.f};
          const int t = 16 + 8 * hp + q, u = q >> 2;
          mma16816(d, px[u] & mhi, 0u, px[u] & ~mhi, py[u] & mhi, PH[t], P0[t]);
          mma1688(d, 0u, py[u] & ~mhi, P1[t]);
          o[q][0] = pack2(d[0] * r[u][0], d[1] * r[u][0]); o[q][1] = pack2(d[2] * r[u][1], d[3] * r[u][1]);
        }
#pragma unroll
        for (int q = 0; q < 4; q++) ro[q] = make_uint4(o[4 * (q & 1)][q >> 1], o[4 * (q & 1) + 1][q >> 1], o[4 * (q & 1) + 2][q >> 1], o[4 * (q & 1) + 3][q >> 1]);
        img_tag(ro, false, 0, x);
        if (ZA && hp) {
#pragma unroll
          for (int q = 0; q < 4; q++) r1[q] = ro[q];
        } else img_store(ro, x.img(0, hp));
        if (hp == 0) bb_fence(x.goff);
        if (hp == 0) {
#pragma unroll
          for (int i = 0; i < 2; i++) {
            const uint32_t ti = x.aslot(x.held(i));
            if (L) img_load(xr[i], ti, x);
            else {
#pragma unroll
              for (int q = 0; q < 4; q++) ldsm4(x.maddr(ti, 2 * q), reinterpret_cast<uint32_t (&)[4]>(xr[i][4 * q]));
            }
          }
          __syncwarp();
        }
        img_sts(ro, tile, x);
      }
      if (L == 0) {
#pragma unroll
        for (int hp = 0; hp < 2; hp++) {
          uint32_t v[16];
#pragma unroll
          for (int q = 0; q < 16; q++) asm volatile("mov.b32 %0, %1;" : "=r"(v[(q & 1) * 8 + (q >> 1)]) : "r"(xr[hp][q]));
#pragma unroll
          for (int q = 0; q < 16; q++) xr[hp][q] = v[q];
        }
      }
      img_unpack(acc, xr[0]); img_unpack(acc + 32, xr[1]);
    } else {
      float kv[128];
      float (&kv0)[64] = reinterpret_cast<float (&)[64]>(kv[0]);
      float (&kv1)[64] = reinterpret_cast<float (&)[64]>(kv[64]);
      auto mma8 = [&](uint32_t as, uint32_t bs, int i, bool fence) {
        const uint32_t da = desc_lo(SB + OFF_A, 16) + as * (SLOT / 16), db = desc_lo(SB + OFF_B, 8192) + bs * (SLOT / 16);
        if (fence) wgmma_fence();
#pragma unroll
        for (int k = 0; k < 4; k++) {
          wgmma_ss_n128(kv0, da + (k >> 1) * 32 + (k & 1) * 2, HA64, db + 128 * k, i + k);
          wgmma_ss_n128(kv1, da + 512 + (k >> 1) * 32 + (k & 1) * 2, HA64, db + 128 * k, i + k);
        }
        wgmma_commit();
      };
      constexpr uint32_t dm = desc_lo(SB + OFF_MB, 0);
      auto relB = [&](uint32_t s) { mbar_arrive_n(sb + BAR_EMPTYB + s * 8, 2); };
      auto skip = [&]() {
#pragma unroll
        for (int q = 0; q < 6 - NJ; q++) adv<NA>(x.ra);
        x.rb.s = w ? (2 + NJ) % 6 : 4;
        if (!w && NJ < 4) x.rb.ph ^= 1;
      };
      static_assert(NA == 5 && NB == 6, "ring arithmetic");
      mma8(x.ra.s, x.rb.s + w, 0, true);
      gemm_next<256>(x);
#pragma unroll 1
      for (int i = 1; i < NJ; i++) {
        mbar_wait2(x.fullA(x.ra.s), x.ra.ph, x.fullB(x.rb.s + w), x.rb.ph);
        mma8(x.ra.s, x.rb.s + w, 1, true);
        if (!XO && i == XR) { img_store(r1, x.img(XBUF(L), 1)); publish(2, x); }
        if (!XO && i == XS) stats_send(ts, L, x);
        wgmma_wait<1>();
        if (x.elected) { x.releaseA(x.pa); relB(x.pb + w); }
        gemm_next<256>(x);
        if (XO && i == XR) { img_store(r1, x.img(XBUF(L), 1)); publish(2, x); stats_send(ts, L, x); }
      }
      if (w) {
        wgmma_wait<0>();
        if (x.elected) { x.releaseA(x.pa); relB(x.pb + 1); }
        skip();
        asm volatile("bar.sync 7, 256;" ::: "memory");
      }
      TSL_(8);
      {
        const int t = lane_id() + 32 * x.warp;
        uint32_t mask = t < 2 ? ((w ? (t ? 0xFF3Fu : 0x3FFFu) : 0xFFFFu) >> (NJ - 1)) & (w ? ~1u : ~0u) : 0u, cnt = 1 + t;
        bool ready = false;
#pragma unroll 1
        for (int i = NJ; i < 16; i++) {
          if (!ready) mbar_wait2(x.fullA(x.ra.s), x.ra.ph, x.fullB(x.rb.s), x.rb.ph);
          mma8(x.ra.s, x.rb.s, 1, true);
          const uint32_t bar = sb + (t ? BAR_EMPTYB + x.pb * 8 : BAR_EMPTYA + x.pa * 8);
          gemm_next<128>(x);
          if (w && (i | 4) == 15) x.rb.s = 4;
          ready = mbar_probe2(x.fullA(x.ra.s), x.ra.ph, x.fullB(x.rb.s), x.rb.ph);
          wgmma_wait<1>();
          if (mask & 1) mbar_arrive_n(bar, cnt);
          mask >>= 1; cnt = 2;
          if (i == 8 && w) asm volatile("bar.arrive 9, 256;" ::: "memory");
          if (i == 9) TSL_(10);
        }
        mbar_wait2(sb + BAR_STAT, 1, sb + BAR_CS + 8, 0);
        wgmma_fence();
        wgmma_r1_n128(kv0, dm, dcs + 96 + 96 * w, 1);
        wgmma_r1_n128(kv1, dm + 64, dcs + 96 + 96 * w, 1);
        wgmma_commit();
        if (w == 0) asm volatile("bar.arrive 7, 256;" ::: "memory");
        wgmma_wait<1>();
        if (mask & 1) mbar_arrive_n(sb + (t ? BAR_EMPTYB + x.pb * 8 : BAR_EMPTYA + x.pa * 8), 2);
      }
      const Stats s0 = load_stats(0, x), s1 = load_stats(1, x), st = w ? s1 : s0;
      if (w == 0) skip();
      const uint32_t h0 = x.held(0), h1 = x.held(1);
      auto vreg = [&](int ks) { return ks < 6 ? OFF_A + (ks < 3 ? h0 * SLOT : h1 * SLOT - 15360) + ks * 5120 : OFF_S + 2048 + ks * 5120; };
      uint32_t tV[2], uu[4];
#pragma unroll
      for (int hf = 0; hf < 2; hf++) {
        tV[hf] = sb + vreg(4 * hf + x.warp) + ((x.lane >> 3) & 1) * 2560 + (x.lane & 7) * 16 + x.mhi * 128;
        const float i0 = rcp(hf ? s1.rstd0 : s0.rstd0), i1 = rcp(hf ? s1.rstd1 : s0.rstd1);
        const uint32_t h = pack2(i0, i1);
        uu[2 * hf] = pack2(lo16(h), i0 - lo16(h)); uu[2 * hf + 1] = pack2(hi16(h), i1 - hi16(h));
        asm volatile("" : "+r"(tV[hf]), "+r"(uu[2 * hf]), "+r"(uu[2 * hf + 1])::"memory");
      }
      wgmma_wait<0>();
      fence_regs(kv);
      TSL_(2);
      if (w == 0) {
        uint32_t f[2][18], ad[4];
#pragma unroll
        for (int q = 0; q < 18; q++) f[1][q] = 0u;
#pragma unroll
        for (int q = 0; q < 4; q++) ad[q] = x.maddr(sb + OFF_S, 2 * q);
        auto norm = [&](int un) {
          uint32_t* u = f[un & 1];
          const Stats& sn = un ? s1 : s0;
#pragma unroll
          for (int sg = 0; sg < 2; sg++) {
            uint32_t v = u[16 + sg];
            v = add2(v, __shfl_xor_sync(0xffffffffu, v, 1)); v = add2(v, __shfl_xor_sync(0xffffffffu, v, 2));
            const float a = rcp(lo16(v)) * sn.rstd0, b = rcp(hi16(v)) * sn.rstd1;
            const uint32_t r0 = pack2(a, a), r1_ = pack2(b, b);
#pragma unroll
            for (int q = 8 * sg; q < 8 * sg + 8; q++) u[q] = mul2(u[q], (q & 1) ? r1_ : r0);
#pragma unroll
            for (int q = 2 * sg; q < 2 * sg + 2; q++) stsm4(ad[q] + un * 8192, u[4 * q], u[4 * q + 1], u[4 * q + 2], u[4 * q + 3]);
          }
        };
        auto move = [&](int dst, int src) {
#pragma unroll
          for (int q = 0; q < 16; q++) asm volatile("mov.b32 %0, %1;" : "=f"(kv[dst + q]) : "f"(src ? kv[src + q] : 0.f));
        };
        hedgehog_scale<1, 0>(kv, s0, nullptr, [] {});
        uint32_t step = 0;
#pragma unroll 1
        for (int h = 0;; h++) {
          norm(1);
          dual_exp(kv, f[0], x.goff);
          hedgehog_scale<1, KEEP>(kv + 64, s1, f[1], [] {});
          if (h == 2) asm volatile("bar.sync 9, 256;" ::: "memory");
#pragma unroll
          for (int q = 0; q < 4; q++) ad[q] += step;
          norm(0);
          dual_exp(kv + 64, f[1], x.goff);
#pragma unroll
          for (int q = 0; q < 16; q++) kv[q] = kv[16 + q];
          hedgehog_scale<1, KEEP>(kv, s0, f[0], [] {});
          step = SLOT;
          if (h == 0) { move(64, 80); move(16, 32); }
          else if (h == 1) { move(64, 96); move(16, 48); step = OFF_B + SLOT - OFF_S; }
          else if (h == 2) { move(64, 112); move(16, 0); }
          else break;
        }
        norm(1);
        TSL_(3);
      } else {
        wg_bar(w);
#pragma unroll
        for (int hf = 0; hf < 2; hf++) {
          stsm4(tV[hf] + 512 + x.mhi * 512, uu[2 * hf], uu[2 * hf + 1], uu[2 * hf], uu[2 * hf + 1]);
          stsm4(tV[hf] + 1792 + x.mhi * 512, uu[2 * hf], uu[2 * hf + 1], uu[2 * hf], uu[2 * hf + 1]);
#pragma unroll
          for (int q = 0; q < 8; q++) {
            const float* u = kv + 64 * hf + 8 * q;
            stsm4(tV[hf] + (q >> 1) * 640 + (q & 1) * 256, pack2(u[0], u[1]), pack2(u[2], u[3]), pack2(u[4], u[5]), pack2(u[6], u[7]));
          }
        }
        TSL_(3);
      }
      {
        float d[2][20];
        uint4* dst = &g_kvpart[x.j()][w * 4 + x.warp][0][x.m() * 32 + x.lane];
        unsigned* dz = reinterpret_cast<unsigned*>(&g_kvpart[x.j()][w * 4 + x.warp][x.c & 1][512]) + x.m() * 8 + x.g;
        fence_async_smem();
        cta_bar();
        TSL_(11);
        uint32_t pk[9];
        auto prep = [&](float (&u)[20]) {
          fence_regs(u);
#pragma unroll
          for (int q = 0; q < 8; q++) pk[q] = pack2(u[((q >> 1) & 2) + 4 * (q & 3)], u[((q >> 1) & 2) + 4 * (q & 3) + 1]);
          pk[8] = __float_as_uint((x.c & 1) ? u[18] + u[19] : u[16] + u[17]);
#pragma unroll
          for (int q = 0; q < 9; q += 4) pk[q] = (pk[q] & ~1u) | (L == 1);
        };
        auto send = [&](int hp) {
          st_v4(dst + hp * 16 * 544, pk[0], pk[1], pk[2], pk[3]); st_v4(dst + (hp * 16 + 1) * 544, pk[4], pk[5], pk[6], pk[7]);
          st_flag(dz + hp * 16 * 544 * 4, pk[8]);
        };
        wgmma_fence();
#pragma unroll
        for (int q = 0; q < 17; q++) {
          if (q < 16) wgmma_ss_n40_tt(d[q >> 3], desc_lo(SB + (q < 8 ? OFF_S : OFF_B + 2 * SLOT), 1024) + w * (SLOT / 16) + 128 * (q & 7), desc_lo(SB + vreg(q & 7), 2560) + (w + (q >> 3) * 2) * 40, q & 7);
          else wgmma_r1_n128(acc, dm + w * 64, dcs, 0);
          if (q == 7 || q == KVS || q == 16) wgmma_commit();
          if (q == KVS) { mbar_wait2(x.fullA(x.ra.s), x.ra.ph, x.fullB(x.rb.s), x.rb.ph); wgmma_wait<1>(); prep(d[0]); send(0); bb_fence(x.goff); wgmma_fence(); }
        }
        gemm_issue<128, false>(acc, x, true); gemm_next<128>(x);
        wgmma_wait<1>();
        x.releaseA(h0); x.releaseA(h1); x.releaseB(2); x.releaseB(3);
        if (x.lane == 0) mbar_arrive(sb + BAR_SIGT);
        prep(d[1]);
        TSL_(4);
#pragma unroll 1
        for (int seg = 0; seg < 2; seg++) {
          const int n0 = w ? PS1 : PS0;
          gemm_run(acc, x, seg ? 15 - n0 : n0, seg, seg ? L : 0);
          if (seg == 0) send(1);
        }
      }
      gemm_end(acc, x);
      TSL_(5);
      {
        float dp[2][20], dn[2][20];
        uint32_t f[4][16];
        auto mma = [&](int h) {
          if (!(h & 1)) mbar_wait(sb + BAR_KV + h * 4, L >> 1);
          if (h == 0) TSL_(9);
          const uint32_t db = desc_lo(SB + OFF_S + h * 5120, 128);
          const uint32_t (&a)[16] = f[h];
          wgmma_fence();
          wgmma_rs_n40(dp[h & 1], a[0], a[1], a[2], a[3], db, 0);
          wgmma_rs_n40(dn[h & 1], a[8], a[9], a[10], a[11], db + 160, 0);
          wgmma_rs_n40(dp[h & 1], a[4], a[5], a[6], a[7], db + 80, 1);
          wgmma_rs_n40(dn[h & 1], a[12], a[13], a[14], a[15], db + 240, 1);
          wgmma_commit();
        };
        uint32_t xr[16];
        auto fin = [&](int h) {
          const uint32_t tile = x.aslot(x.held(h >> 1));
          if (!(h & 1)) img_load(xr, tile, x);
          float (&u)[20] = dp[h & 1];
          float (&v)[20] = dn[h & 1];
          fence_regs(u); fence_regs(v);
#pragma unroll
          for (int r = 0; r < 2; r++) {
            const float sp = u[16 + 2 * r], sn = v[16 + 2 * r];
            const float id = rcp(fmaf(fmaf(sp, L == 1 ? 0.065536f * 128 / 129 : 0.065536f, u[17 + 2 * r]), sn, v[17 + 2 * r] * sp)), aa = sn * id, cc = sp * id;
            uint32_t o[4];
#pragma unroll
            for (int t = 0; t < 4; t++) o[t] = pack2(fmaf(u[4 * t + 2 * r], aa, v[4 * t + 2 * r] * cc), fmaf(u[4 * t + 2 * r + 1], aa, v[4 * t + 2 * r + 1] * cc));
            o[2 * r + (h & 1)] = img_tag(o[2 * r + (h & 1)], false, 1, x);
            if (ZO && h == 3) r1[r] = make_uint4(o[0], o[1], o[2], o[3]);
            else stg128(x.img(0, h >> 1) + r * 64 + (h & 1) * 32, make_uint4(o[0], o[1], o[2], o[3]));
            sts128(tile + r * 1024 + (h & 1) * 512 + x.so, o[0], o[1], o[2], o[3]);
          }
          if (h & 1) { if (h == 1) publish(0, x); img_unpack(acc + 16 * (h - 1), xr); }
        };
        auto ex = [&](int h) { dual_exp_rcp(acc + 16 * h, f[h]); };
        Stats sq = st;
#pragma unroll
        for (int h = 0; h < 4; h += 2) {
          hedgehog_scale<2, 0>(acc + 16 * h, sq, nullptr, [&] { ex(h); });
          mma(h);
          ex(h + 1); wgmma_wait<0>(); fin(h);
          if (h == 0) bb_fence(x.goff);
          mma(h + 1);
          wgmma_wait<0>(); fin(h + 1);
          if (h == 0) sq.rstd1 += bb_fence(x.goff);
        }
      }
    }
    mbar_wait(x.fullB(x.rb.s), x.rb.ph);
    fence_regs(acc);
    fence_async_smem();
    wg_bar(w);
    TSL_(6);
    rewind2<NA>(x.ra);
    if (ZA && !(L & 1)) img_store(r1, x.img(0, 1));
    if (ZO && (L & 1)) { stg128(x.img(0, 1) + 32, r1[0]); stg128(x.img(0, 1) + 96, r1[1]); }
    gemm_issue<128, false>(acc, x, true); gemm_next<128>(x);
    uint4* out = solid(P.out + goff + (x.warp * 16 + (x.lane >> 3)) * 256 + (x.lane & 7));
#pragma unroll 1
    for (int seg = 0; seg < 2; seg++) {
      const int nt = L == 3 ? TSK : XN;
      gemm_run(acc, x, seg ? nt : 15 - nt, seg, 10 + L);
      if (L < 3) { if (seg == 0) publish(1, x); }
      else if (seg != w) {
        if (w) asm volatile("bar.sync 6, 256;" ::: "memory"); else asm volatile("bar.arrive 6, 256;" ::: "memory");
      }
    }
    gemm_end(acc, x);
    TSL_(7);
    rewind2<NA>(x.ra);
    out_epilogue(acc, r1, ts, out, L, x);
    TSL_(13);
  }
}

typedef unsigned long long u64;
template <class T> __device__ __forceinline__ T* early(T* p) { return (T*)__shfl_xor_sync(0xffffffffu, (u64)p, 1); }
__device__ __forceinline__ void pause(uint32_t GAP) {
  if (GAP) { uint32_t t0, t; asm volatile("mov.u32 %0, %%clock;" : "=r"(t0)); do { asm volatile("mov.u32 %0, %%clock;" : "=r"(t)); } while (t - t0 < GAP); }
}
__device__ __forceinline__ u64 order_table0(int j) { return (j & 4) ? 0x543210FEDCBA9876ull : 0xDCBA9876543210FEull; }
__device__ __forceinline__ void order_tables(u64& t1, u64& t2, int j) {
#pragma unroll 1
  for (int i = 6; i >= 0; i--) { const u64 o = 2 * other_tile(i, j); t1 = t1 << 4 | o | (o + 1) << 28; t2 = t2 << 8 | (o * 17 + 16); }
  const u64 own = 2 * j * 17 + 16;
  t1 = t1 << 8 | own; t2 |= own << 56;
}

__device__ __forceinline__ void b_producer(const Params& P, uint32_t sb, unsigned vb) {
  const int j = cta_j(vb);
  u64 t1 = 0, t2 = 0;
  Ring r = {PRE_B % NB, PRE_B < NB};
#pragma unroll 1
  for (int sg = 0; sg < 20; sg++) {
    const int L = sg / 5, p = sg - 5 * L, wt = L & 1;
    if (sg == 1) order_tables(t1, t2, j);
    int n = p >= 3 ? 16 : (wt ? (p ? 16 - NJ : 2 * NJ) : (p ? 0 : (L ? 32 : 32 - PRE_B)));
    u64 tab = p == 3 ? t2 : (sg == 0 ? order_table0(j) >> (2 * PRE_B) : (p == 1 || p == 2 ? t1 >> (4 * NJ) : t1));
    const CUtensorMap* tm = p == 4 ? &P.mwo[wt] : &P.mw[wt ? 1 : L];
    const uint4* img = &g_wf[p != 3][j][0][0];
    int col = (p >= 3 ? 0 : (p == 2 ? 2048 : 1024)) + 128 * j;
    const int flip = p == 0 ? 3072 : 0;
    const bool fold = wt && p != 4;
    if (sg == 5 || sg == 8) { mbar_wait(sb + (sg == 5 ? BAR_WPHI : BAR_CS + 8), sg == 5); fence_async_global(); }
    if (DEFER && p == 4 && ((DEFL >> wt) & 1)) {
      Ring q = r;
      for (int u = 0; u < DEFER; u++) adv<NB>(q);
      mbar_wait(sb + BAR_EMPTYB + q.s * 8, q.ph);
    }
#pragma unroll 1
    for (; n > 0; n--) {
      const int kb = (int)tab & 15;
      mbar_wait(sb + BAR_EMPTYB + r.s * 8, r.ph);
      if (elect()) {
        mbar_expect_tx(sb + BAR_FULLB + r.s * 8, SLOT);
        if (fold && col < 2048) bulk_load(sb + OFF_B + r.s * SLOT, img + kb * 1024, SLOT, sb + BAR_FULLB + r.s * 8);
        else tma_load_w(sb + OFF_B + r.s * SLOT, tm, sb + BAR_FULLB + r.s * 8, col, kb);
      }
      adv<NB>(r);
      if (p == 2 && (n | 4) == 5) r.s = 4;
      col ^= flip;
      if (!(col & flip & 2048)) tab >>= 4;
    }
  }
}

__device__ __forceinline__ void kv_image(uint32_t sb, int h, int L, int j, unsigned tag, uint32_t bar, unsigned& ph) {
  poll_flags(&g_jflag[h][j][0], 16, 0xFFFFu, tag * 4 + L);
  TS(4, h ? 14 + L : 26 + L);
  for (int it = 0;; it++) {
    if (elect()) { mbar_expect_tx(bar, 10240); bulk_load(sb + OFF_S + h * 10240, &g_kvfin[j][8 * h][0], 10240, bar); }
    mbar_wait(bar, ph);
    ph ^= 1;
    uint32_t a = 1u, o = 0u;
#pragma unroll
    for (int u = 0; u < 20; u++) { const uint32_t v = __float_as_uint(lds32f(sb + OFF_S + h * 10240 + u * 512 + (threadIdx.x & 31) * 16)); a &= v; o |= v; }
    if (__all_sync(0xffffffffu, (L == 1 ? a : ~o) & 1u)) break;
    fence_async_smem();
    if (it > (1 << 16)) __trap();
  }
  if (elect()) mbar_arrive(sb + BAR_KV + h * 8);
  TS(4, h ? 30 + L : (L == 1 ? 20 : 25));
}

__device__ __forceinline__ void a_loader(const Params& P, uint32_t sb, unsigned vb) {
  const int j = cta_j(vb), m = cta_m(vb);
  u64 t1 = 0, t2 = 0;
  Ring r = {PRE_A % NA, PRE_A < NA};
  {
    u64 tab = order_table0(j) >> (4 * PRE_A);
#pragma unroll 1
    for (int i = PRE_A; i < 33; i++) {
      if (i == 17) { order_tables(t1, t2, j); tab = t2; }
      mbar_wait(sb + BAR_EMPTYA + r.s * 8, r.ph);
      if (elect()) {
        mbar_expect_tx(sb + BAR_FULLA + r.s * 8, SLOT);
        if (i != 14) tma_load_3d(sb + OFF_A + r.s * SLOT, &P.mx, sb + BAR_FULLA + r.s * 8, ((int)tab & 15) * 64, m * 64, 0);
        else {
          tma_load_w(sb + OFF_A + r.s * SLOT, &P.mw[1], sb + BAR_FULLA + r.s * 8, 1024 + 128 * j, m);
          mbar_expect_tx(sb + BAR_WPHI, 8192); tma_load_2d(sb + OFF_S + 4096, &P.mwphi, sb + BAR_WPHI, 0, 128 * j);
        }
        if (i == PF1 || i == PF2) tma_prefetch_w(&P.mwo[i == PF2], 128 * j, m);
      }
      adv<NA>(r);
      if (i != 14) tab >>= 4;
    }
  }
  const unsigned tag = get_tag(sb);
  unsigned kph = 0;
#pragma unroll 1
  for (int sg = 0; sg < 13; sg++) {
    const int L = sg >> 2, p = sg & 3;
    if (p == 0 && (L & 1)) {
#pragma unroll 1
      for (int h = 0; h < 2; h++) kv_image(sb, h, L, j, tag, sb + BAR_STAT + 8, kph);
    }
    int n = p < 2 ? 14 : (p == 2 ? ((L & 1) ? 0 : 16 - NJ) : 16);
    u64 tab = p == 3 ? t2 : t1 >> (p < 2 ? 8 : 4 * NJ);
    const uint4* img = &g_img[p ? XBUF(L + 1) : 0][m][0][0];
#pragma unroll 1
    for (; n > 0; n--) {
      const uint4* src = early(img + ((int)tab & 15) * 1024);
      const uint32_t bar = sb + (p < 2 ? BAR_LAND : BAR_FULLA) + r.s * 8;
      mbar_wait(sb + BAR_EMPTYA + r.s * 8, r.ph);
      if (elect()) mbar_expect_tx(bar, SLOT);
      if (p < 2 && n == 14) {
        const int lane = threadIdx.x & 31;
        const unsigned* f = &g_hint[(m & 14) + ((lane >> 3) & 1)][(~j & 4) ^ (lane & ND0)];
        mbar_wait(sb + BAR_SIGP + p * 8, L & 1);
        int it = 0;
        while (!__all_sync(0xffffffffu, (int)(ld_flag(f) - (tag * 16 + 4 * L + 1 + p)) >= 0)) { if (++it > (1 << 22)) __trap(); }
        pause(p ? (L ? PAX : PX0) : ((L & 1) ? 0 : (L ? PAA : PA0)));
        TS(2, p == 0 ? 5 + L * 8 : 9 + L * 8);
        TSH((2 * L + p) * 8 + 2);
      }
      if (elect()) bulk_load(sb + OFF_A + r.s * SLOT, src, SLOT, bar);
      adv<NA>(r);
      tab >>= 4;
      pause(p < 2 && n > 10 ? G0 : 0);
    }
  }
}

template <int KB>
__device__ __forceinline__ uint2 sum_packets(float (&a)[8], uint32_t addr, int n) {
  uint2 ok = make_uint2(~0u, 0u);
#pragma unroll 1
  for (int b = 0; b < n; b += KB) {
    uint4 v[KB];
#pragma unroll
    for (int u = 0; u < KB; u++) lds128(addr + (b + u) * 512, v[u].x, v[u].y, v[u].z, v[u].w);
#pragma unroll
    for (int u = 0; u < KB; u++) {
      ok.x &= v[u].x; ok.y |= v[u].x;
      a[0] += lo16(v[u].x); a[1] += hi16(v[u].x); a[2] += lo16(v[u].y); a[3] += hi16(v[u].y);
      a[4] += lo16(v[u].z); a[5] += hi16(v[u].z); a[6] += lo16(v[u].w); a[7] += hi16(v[u].w);
    }
  }
  return ok;
}
__device__ __forceinline__ void helper_bar() { asm volatile("bar.sync 4, 64;" ::: "memory"); }
__device__ __forceinline__ void helper(const Params& P, uint32_t sb, int w, unsigned vb) {
  const int j = cta_j(vb), m = cta_m(vb);
  if (w == 0) {
    if (elect()) {
      const unsigned t = atomicAdd(&g_ctr, 1u) / NCTA + 1u;
      asm volatile("st.shared.u32 [%0], %1;" ::"r"(sb + OFF_EPOCH), "r"(t) : "memory");
      mbar_arrive(sb + BAR_EPOCH);
    }
  }
  const unsigned tag = get_tag(sb);
  mbar_wait(sb + BAR_FULLB + 24, 0);
  const uint32_t stg = sb + OFF_T + w * 12288, stb = sb + BAR_STG + w * 24;
  Ring rs = {0, 0};
  uint32_t vs = 33 % NA, vph = 0;
  auto cs_image = [&](int L) {
      const int lane = lane_id();
      poll_flags(&g_jflag[2 * L][j][0], 16, L ? CSNEED : 0xFFFu, tag * 4);
#pragma unroll
      for (int p = 0; p < 3; p++) {
        const uint4 u = ldcg4(&g_cs[L][0][p * 1024 + 128 * j + lane * 4]), v = ldcg4(&g_cs[L][1][p * 1024 + 128 * j + lane * 4]);
        const float c0 = __uint_as_float(u.x) + __uint_as_float(v.x), c1 = __uint_as_float(u.y) + __uint_as_float(v.y);
        const float c2 = __uint_as_float(u.z) + __uint_as_float(v.z), c3 = __uint_as_float(u.w) + __uint_as_float(v.w);
        const uint32_t h0 = pack2(c0, c1), h1 = pack2(c2, c3), dst = sb + OFF_CS + (p * 16 + (lane >> 1)) * 96 + L * 48 + (lane & 1) * 8;
        sts64(dst, h0, h1); sts64(dst + 16, pack2(c0 - lo16(h0), c1 - hi16(h0)), pack2(c2 - lo16(h1), c3 - hi16(h1))); sts64(dst + 32, h0, h1);
        if (L == 0) { sts64(dst + 48, 0u, 0u); sts64(dst + 64, 0u, 0u); sts64(dst + 80, 0u, 0u); }
      }
      if (L == 0 && lane < 4) sts64(sb + OFF_CS + 4608 + lane * 8, 0u, 0u);
      fence_async_smem();
      __syncwarp();
      if (elect()) mbar_arrive(sb + BAR_CS + L * 8);
      TS(4, 2 + L * 2);
  };
#pragma unroll 1
  for (int L = 0; L < 4; L++) {
    const int lane = lane_id();
    if (L == 0) {
      {
        const int wt = m >= 12, col = ((0x2021 >> (m & 12)) & 3) * 1024 + 128 * j + (m & 3) * 32;
        const CUtensorMap* tm = &P.mcs[wt];
        if (wt) __nanosleep(D2);
        constexpr int nb = 8;
        float a[8] = {0.f, 0.f, 0.f, 0.f, 0.f, 0.f, 0.f, 0.f};
#pragma unroll 1
        for (int b = -3; b < nb; b++) {
          if (b >= 0) {
            mbar_wait(stb + rs.s * 8, rs.ph);
            sum_packets<KC>(a, stg + rs.s * 4096 + lane * 16, 8);
            fence_async_smem();
            __syncwarp();
          }
          const uint32_t sl = b < 0 ? (rs.s + b + 3) % 3 : rs.s;
          if (b + 3 < nb && elect()) { mbar_expect_tx(stb + sl * 8, 4096); tma_load_2d(stg + sl * 4096, tm, stb + sl * 8, col, (w * (16 - nb) + b + 3) * 64); }
          if (b >= 0) adv<3>(rs); else pause(CP);
        }
#pragma unroll 1
        for (int d = 4; d < 32; d *= 2)
#pragma unroll
          for (int u = 0; u < 8; u++) a[u] += __shfl_xor_sync(0xffffffffu, a[u], d);
        if (lane < 4) {
          float4* dst = reinterpret_cast<float4*>(&g_cs[wt][w][col + lane * 8]);
          dst[0] = make_float4(a[0], a[1], a[2], a[3]); dst[1] = make_float4(a[4], a[5], a[6], a[7]);
        }
        helper_bar();
        if (w == 0 && elect()) { fence_gpu(); st_flag(&g_jflag[2 * wt][j][m], tag * 4); }
      }
      if (w == 0) TS(4, 1 + L * 2);
    }
    if (L > 0 && w == 0) {
      mbar_wait(sb + BAR_SIGP + 16, (L - 1) & 1);
      fence_async_global();
      __nanosleep(CO && L == 1 ? SE : SD);
    }
    if (CO && L < 2 && w == 0) cs_image(L);
    if (w == (L == 0)) {
      if (L == 0) { mbar_wait(sb + BAR_WPHI, 0); __nanosleep(S0); }
#pragma unroll 1
      for (int p = 0; p < 2; p++) {
        uint4 v[8];
        for (int it = 0;; it++) {
          bool ok = true;
#pragma unroll
          for (int t = 0; t < 8; t++) v[t] = ld_pkt(&g_stats[m][p][t][lane]);
#pragma unroll
          for (int t = 0; t < 8; t++) ok = ok && (v[t].w & 15u) == seq4(tag, L);
          if (__all_sync(0xffffffffu, ok)) break;
          __nanosleep(200);
          if (it > (1 << 20)) __trap();
        }
        float s0 = 0.f, q0 = 0.f, s1 = 0.f, q1 = 0.f;
#pragma unroll
        for (int t = 0; t < 8; t++) { s0 += __uint_as_float(v[t].x); q0 += __uint_as_float(v[t].y); s1 += __uint_as_float(v[t].z); q1 += __uint_as_float(v[t].w & ~15u); }
        s0 *= (1.f / 1024); s1 *= (1.f / 1024);
        sts64(sb + OFF_MR + p * 256 + lane * 8, __float_as_uint(rsqrtf(fmaxf(q0 * (1.f / 1024) - s0 * s0, 0.f) + 1e-5f)),
              __float_as_uint(rsqrtf(fmaxf(q1 * (1.f / 1024) - s1 * s1, 0.f) + 1e-5f)));
#pragma unroll
        for (int r = 0; r < 2; r++) {
          const float v = -0.5f * (r ? s1 : s0);
          const uint32_t hh = pack2(v, v), hl = pack2(v, v - lo16(hh));
          const bool b = L & 1;
          sts128(sb + (b ? OFF_MB : OFF_MA) + p * 1024 + (lane >> 3) * 256 + r * 128 + (lane & 7) * 16, b ? 0u : hh, b ? hh << 16 : hl >> 16, b ? hl : 0u, 0u);
        }
      }
      fence_async_smem();
      __syncwarp();
      if (elect()) {
        mbar_arrive(sb + BAR_STAT);
      }
      TS(2, 0 + L * 8);
    }
    if (!CO && L < 2 && w == 0) cs_image(L);
    if (L & 1) {
      const uint32_t flip = L == 1 ? 0u : 1u;
      mbar_wait(sb + BAR_SIGT, 1);
      {
        int it = 0;
        if (PSL) __nanosleep(m < 8 ? PSL : PSL + 600);
        while (!__all_sync(0xffffffffu, (ld_flag(reinterpret_cast<const unsigned*>(&g_kvpart[j][m][w][512]) + (lane & 15) * 8) ^ flip) & 1u)) { if (PSL) __nanosleep(100); if (++it > (1 << 22)) __trap(); }
        fence_async_global();
      }
      if (w == 0) TS(4, 6 + L * 2);
      float a[8], z;
      for (int it = 0;; it++) {
        if (elect()) { mbar_expect_tx(stb + rs.s * 8, 8704); bulk_load(stg, &g_kvpart[j][m][w][0], 8704, stb + rs.s * 8); }
        mbar_wait(stb + rs.s * 8, rs.ph);
        if (w == 0) TS(4, 21 + L);
        adv<3>(rs);
#pragma unroll
        for (int u = 0; u < 8; u++) a[u] = 0.f;
        z = 0.f;
        uint32_t ok = 1u;
#pragma unroll
        for (int u = 0; u < 4; u++) { const float v = lds32f(stg + 8192 + u * 128 + (lane & 3) * 32 + (lane >> 2) * 4); z += v; ok &= __float_as_uint(v) ^ flip; }
        const uint2 tg = sum_packets<8>(a, stg + lane * 16, 16);
        ok &= flip ? ~tg.y : tg.x;
        if (__all_sync(0xffffffffu, ok & 1u)) break;
        fence_async_smem();
        if (it > (1 << 16)) __trap();
      }
      {
        uint4* img = &g_kvfin[j][m][w * 8 + (lane >> 2)];
        uint32_t a0 = __float_as_uint(a[0]) >> 16;
        a0 += ~(a0 ^ flip) & 1u;
        st_v4(img + (lane & 3) * 16, __byte_perm(a0, pack2(0.f, a[1]), 0x7610), pack2(a[2], a[3]), pack2(a[4], a[5]), pack2(a[6], a[7]));
        const uint32_t cz = pack2(0.f, qsum(z)) | (0x3781u ^ flip);
        if (!(lane & 3)) st_v4(img + 64, cz, cz, cz, cz);
        __syncwarp();
        if (elect()) st_flag(&g_jflag[m >> 3][j][(m & 7) * 2 + w], tag * 4 + L);
      }
      if (w == 0) TS(4, 7 + L * 2);
    } else {
      if (L == 0 && w == 0) {
        st_v4(&g_kvpart[j][m][0][512 + lane], 0u, 0u, 0u, 0u); st_v4(&g_kvpart[j][m][1][512 + lane], 0u, 0u, 0u, 0u);
        __syncwarp();
      }
      mbar_wait(sb + BAR_SIGT, 0);
      if (w == 0) {
        if (elect()) { fence_gpu(); st_flag(&g_hint[m][j], tag * 16 + 4 * L); st_flag(&g_jflag[1][j][m], tag * 4 + L); }
        if (L == 0) {
          __nanosleep(KSL);
          poll_flags(&g_jflag[1][j][0], 16, 0xFFFFu, tag * 4);
          if (elect()) mbar_arrive(sb + BAR_WPHI);
        }
      } else if (m > 0) {
        poll_flags(&g_hint[m - 1][j], 1, 1u, tag * 16 + 4 * L);
        if (elect()) { mbar_expect_tx(sb + BAR_HALO, 8192); bulk_load(sb + OFF_S + 8192, &g_halo[m - 1][j][0][0], 8192, sb + BAR_HALO); }
        TS(2, 2 + L * 8);
      }
    }
    if (w == 0) {
#pragma unroll 1
      for (int e = 0; e < (L < 3 ? 2 : 1); e++) {
        unsigned* flag = early(&g_hint[m][j]);
        mbar_wait(sb + BAR_SIGP + e * 8, L & 1);
        TS(2, (e ? 6 : 3) + L * 8);
        TSH((2 * L + e) * 8);
        if (elect()) st_flag(flag, tag * 16 + 4 * L + 1 + e);
        TSH((2 * L + e) * 8 + 1);
      }
    } else {
#pragma unroll 1
      for (int i = 0; i < (L < 3 ? 28 : 14); i++) {
        const bool isx = i >= 14;
        const uint32_t a = sb + OFF_A + vs * SLOT + lane * 128 + ((lane >> 4) * 4 + (lane & 3)) * 16 + (lane & 12), code = img_code(isx, L + isx);
        for (int it = 0;; it++) {
          mbar_wait(sb + BAR_LAND + vs * 8, (vph >> vs) & 1);
          vph ^= 1u << vs;
          if (i - 14 * isx < 2) TSH((2 * L + isx) * 8 + 3 + 2 * (i - 14 * isx));
          uint32_t bad = 0;
#pragma unroll
          for (int u = 0; u < 4; u++) bad |= __float_as_uint(lds32f(a + u * 4096)) ^ code;
          if (__all_sync(0xffffffffu, !(bad & img_mask(isx)))) break;
          if (it > (1 << 16)) __trap();
          fence_async_smem();
          if (elect()) {
            mbar_expect_tx(sb + BAR_LAND + vs * 8, SLOT);
            bulk_load(sb + OFF_A + vs * SLOT, &g_img[isx ? XBUF(L + 1) : 0][m][o_order(i - 14 * isx + 2, j)][0], SLOT, sb + BAR_LAND + vs * 8);
          }
        }
        if (elect()) mbar_arrive(sb + BAR_FULLA + vs * 8);
        if (i - 14 * isx < 2) TSH((2 * L + isx) * 8 + 4 + 2 * (i - 14 * isx));
        if (++vs == NA) vs = 0;
      }
      vs = (vs + ((L & 1) ? 16 : 32 - NJ)) % NA;
    }
  }
}

__device__ __forceinline__ void spare(const Params& P, uint32_t sb, int id) {
  const int tid = threadIdx.x & 127, warp = __shfl_sync(0xffffffffu, threadIdx.x >> 5, 0), w = warp >> 2, lane = tid & 31, j = 2 * id + w;
  const uint32_t ring = w * 6 * SLOT, wp = 12 * SLOT + w * 8192, bar = sb + 13 * SLOT + w * 64;
  auto part = [&](int t) { return (t >> 4) ^ w; };
  auto load = [&](int t, uint32_t sl) {
    mbar_expect_tx(bar + sl * 8, t == 0 ? SLOT + 8192 : SLOT);
    tma_load_w(sb + ring + sl * SLOT, &P.mw[1], bar + sl * 8, part(t) * 1024 + 128 * j, t & 15);
  };
  if (!(warp & 3) && elect()) {
    if (w == 2) sts32(sb + OFF_EPOCH, atomicAdd(&g_ctr, 1u) / NCTA + 1u);
    else {
      __nanosleep(D3);
#pragma unroll 1
      for (int t = 0; t < 5; t++) {
        mbar_init(bar + t * 8, 1);
        asm volatile("fence.mbarrier_init.release.cluster;" ::: "memory");
        load(t, t);
      }
      tma_load_2d(sb + wp, &P.mwphi, bar, 0, 128 * j);
    }
  }
  __syncthreads();
  const unsigned tag = get_tag<false>(sb);
  if (w == 2) {
    int it = 0;
    while ((int)(ld_flag(&g_ctr) - tag * NCTA) < 0) { if (++it > (1 << 22)) __trap(); }
    return;
  }
  Ring r = {4, 1};
  float d[64];
  auto fold = [&]() {
    mbar_wait(bar + r.s * 8, r.ph);
    wgmma_fence();
#pragma unroll
    for (int q = 0; q < 8; q++)
      wgmma_ss_n32(reinterpret_cast<float (&)[16]>(d[16 * (q >> 1)]), desc_lo(SB + ring + r.s * SLOT, 16) + (q >> 2) * 512 + (q & 3) * 2, desc_lo(SB + wp, 512) + q * 64, q & 1);
    wgmma_commit();
  };
#pragma unroll
  for (int i = 0; i < 64; i++) d[i] = 0.f;
  int t = -1;
#pragma unroll 1
  for (int g = 0; g < 2; g++) {
    float cs[32] = {};
#pragma unroll 1
    do {
      uint32_t f[32];
#pragma unroll
      for (int i = 0; i < 32; i++) { f[i] = pack2(d[2 * i], d[2 * i + 1]); cs[i & 30] += d[2 * i]; cs[i | 1] += d[2 * i + 1]; }
      wg_bar(w);
      const uint32_t sl = r.s;
      if (t < 31) adv<5>(r);
      fold();
      if (!(warp & 3) && t >= 0 && t < 27 && elect()) load(t + 5, sl);
      if (g == w && t >= 0) {
        uint4* dst = &g_wf[0][j][t & 15][((tid >> 5) * 16 + (lane >> 2)) * 8];
#pragma unroll
        for (int q = 0; q < 8; q++)
          dst[(q >> 2) * 512 + (q & 1) * 64 + (((q & 2) * 2 + (lane & 3)) ^ (lane >> 2))] =
              make_uint4(f[4 * (q & 6) + (q & 1)], f[4 * (q & 6) + (q & 1) + 2], f[4 * (q & 6) + (q & 1) + 4], f[4 * (q & 6) + (q & 1) + 6]);
      }
      wgmma_wait<0>();
      fence_regs(d);
    } while (++t != 16 * g + 16);
    const uint32_t red = sb + ring + 5 * SLOT;
#pragma unroll
    for (int i = 0; i < 8; i++) sts128(red + (tid >> 2) * 512 + (i >> 1) * 128 + (lane & 3) * 32 + (i & 1) * 16, __float_as_uint(cs[4 * i]), __float_as_uint(cs[4 * i + 1]), __float_as_uint(cs[4 * i + 2]), __float_as_uint(cs[4 * i + 3]));
    wg_bar(w);
    float a = 0.f;
#pragma unroll 4
    for (int i = 0; i < 32; i++) a += lds32f(red + i * 512 + tid * 4);
    g_cs[1][0][(g ^ w) * 1024 + j * 128 + tid] = a;
  }
  wg_bar(w);
  if (tid == 0) { fence_gpu(); st_flag(&g_jflag[2][j][0], tag * 4); }
}

__global__ void __launch_bounds__(NTHREADS, 1) fused_kernel(const __grid_constant__ Params P) {
  extern __shared__ __align__(1024) uint8_t smem_raw[];
  constexpr uint32_t sb = SB;
  const int tid = threadIdx.x;
  const unsigned vb = vblock();
  if (vb >= 128) { spare(P, sb, vb - 128); return; }
  const int warp = __shfl_sync(0xffffffffu, tid >> 5, 0);
  if (elect()) {
    if (warp == 11) { prefetch_map(&P.mx); prefetch_map(&P.mw[0]); if (smem_u32(smem_raw) != SB) __trap(); }
    if (warp < 8) {
#pragma unroll
      for (int i = 0; i < 8; i++) mbar_init(sb + OFF_BAR + (warp * 8 + i) * 8, warp == 2 || warp == 3 ? 2 : (warp == 4 ? 8 : 1));
    }
    asm volatile("fence.mbarrier_init.release.cluster;" ::: "memory");
    if (warp < 2) {
      const int j = cta_j(vb);
#pragma unroll 1
      for (int i = 0; i < (warp == 0 ? PRE_B : PRE_A); i++) {
        const uint32_t bar = sb + BAR_FULLB + warp * 64 + i * 8;
        mbar_expect_tx(bar, SLOT);
        if (warp == 0) tma_load_w(sb + OFF_B + i * SLOT, &P.mw[0], bar, 1024 + (i & 1) * 1024 + 128 * j, kv_order(i >> 1, j, 0));
        else tma_load_3d(sb + OFF_A + i * SLOT, &P.mx, bar, kv_order(i, j, 0) * 64, cta_m(vb) * 64, 0);
      }
    }
  }
  if (tid == 0) TS(6, 0);
  __syncthreads();
  if (tid == 0) TS(6, 2);
  if (warp < 4) {
    reg_dealloc<PREGS>();
    if (warp & 2) helper(P, sb, warp & 1, vb);
    else if (warp & 1) a_loader(P, sb, vb);
    else b_producer(P, sb, vb);
  } else {
    reg_alloc<CREGS>();
    consumer(P, sb, (warp >> 2) - 1, vb);
  }
}

typedef CUresult (*EncodeFn)(CUtensorMap*, CUtensorMapDataType, cuuint32_t, void*, const cuuint64_t*, const cuuint64_t*,
                             const cuuint32_t*, const cuuint32_t*, CUtensorMapInterleave, CUtensorMapSwizzle,
                             CUtensorMapL2promotion, CUtensorMapFloatOOBfill);

void encode(EncodeFn fn, CUtensorMap* m, const void* ptr, int rank, const cuuint64_t* dims, const cuuint64_t* strides,
            const cuuint32_t* box, CUtensorMapSwizzle swz) {
  const cuuint32_t es[5] = {1, 1, 1, 1, 1};
  fn(m, CU_TENSOR_MAP_DATA_TYPE_BFLOAT16, rank, const_cast<void*>(ptr), dims, strides, box, es, CU_TENSOR_MAP_INTERLEAVE_NONE,
     swz, CU_TENSOR_MAP_L2_PROMOTION_L2_256B, CU_TENSOR_MAP_FLOAT_OOB_FILL_NONE);
}
void encode_w(EncodeFn fn, CUtensorMap* m, const void* ptr, int ncols, bool perm) {
  const cuuint64_t p = (cuuint64_t)ncols * 2, d[5] = {(cuuint64_t)ncols, 2, 4, 4, 32}, s[4] = {p, (perm ? 8 : 2) * p, (perm ? 2 : 8) * p, 32 * p};
  const cuuint32_t box[5] = {64, 2, 4, 4, 2};
  encode(fn, m, ptr, 5, d, s, box, CU_TENSOR_MAP_SWIZZLE_128B);
}

void encode_cs(EncodeFn fn, CUtensorMap* m, const void* ptr, int ncols) {
  const cuuint64_t d[2] = {(cuuint64_t)ncols, 1024}, s[1] = {(cuuint64_t)ncols * 2};
  const cuuint32_t box[2] = {32, 64};
  encode(fn, m, ptr, 2, d, s, box, CU_TENSOR_MAP_SWIZZLE_NONE);
}

}

extern "C" void kernel_launch(void* const* d_in, const int* in_sizes, int n_in, void* d_out, int out_size) {
  (void)in_sizes; (void)n_in; (void)out_size;
  void* fnp = nullptr;
  cudaDriverEntryPointQueryResult q;
  cudaGetDriverEntryPoint("cuTensorMapEncodeTiled", &fnp, cudaEnableDefault, &q);
  EncodeFn fn = (EncodeFn)fnp;
  Params P;
  {
    const cuuint64_t dims[3] = {1024, 1024, 2}, strides[2] = {4096, 2048};
    const cuuint32_t box[3] = {64, 64, 2};
    encode(fn, &P.mx, d_in[0], 3, dims, strides, box, CU_TENSOR_MAP_SWIZZLE_128B);
  }
  P.out = (uint4*)d_out;
  encode_w(fn, &P.mw[0], d_in[1], 3072, false);
  encode_w(fn, &P.mw[1], d_in[4], 3072, true);
  encode_w(fn, &P.mw[2], d_in[1], 3072, true);
  encode_w(fn, &P.mwo[0], d_in[2], 1024, true);
  encode_w(fn, &P.mwo[1], d_in[6], 1024, false);
  encode_cs(fn, &P.mcs[0], d_in[1], 3072);
  encode_cs(fn, &P.mcs[1], d_in[4], 3072);
  {
    const cuuint64_t dims[2] = {32, 1024}, strides[1] = {64};
    const cuuint32_t box[2] = {32, 128};
    encode(fn, &P.mwphi, d_in[5], 2, dims, strides, box, CU_TENSOR_MAP_SWIZZLE_64B);
  }
  cudaFuncSetAttribute(fused_kernel, cudaFuncAttributeMaxDynamicSharedMemorySize, SMEM_BYTES);
  fused_kernel<<<NCTA, NTHREADS, SMEM_BYTES, cudaStreamPerThread>>>(P);
}
```

```cpp
#include <cuda_runtime.h>
#include <cuda_bf16.h>
#include <cuda.h>
#include <stdint.h>

namespace {

__device__ __forceinline__ void wgmma_ss_n256(float (&d)[128], uint32_t da, uint32_t ha, uint32_t db, int sd) {
  asm volatile("{\n.reg .pred p;\n.reg .b64 a, b;\nsetp.ne.b32 p, %130, 0;\nmov.b64 a, {%128, %131};\nmov.b64 b, {%129, 0x40000040};\n"
    "wgmma.mma_async.sync.aligned.m64n256k16.f32.bf16.bf16 {%0,%1,%2,%3,%4,%5,%6,%7,%8,%9,%10,%11,%12,%13,%14,%15,%16,%17,%18,%19,%20,%21,%22,%23,%24,%25,%26,%27,%28,%29,%30,%31,%32,%33,%34,%35,%36,%37,%38,%39,%40,%41,%42,%43,%44,%45,%46,%47,%48,%49,%50,%51,%52,%53,%54,%55,%56,%57,%58,%59,%60,%61,%62,%63,%64,%65,%66,%67,%68,%69,%70,%71,%72,%73,%74,%75,%76,%77,%78,%79,%80,%81,%82,%83,%84,%85,%86,%87,%88,%89,%90,%91,%92,%93,%94,%95,%96,%97,%98,%99,%100,%101,%102,%103,%104,%105,%106,%107,%108,%109,%110,%111,%112,%113,%114,%115,%116,%117,%118,%119,%120,%121,%122,%123,%124,%125,%126,%127}, a, b, p, 1, 1, 0, 1;\n}\n"
    : "+f"(d[0]),"+f"(d[1]),"+f"(d[2]),"+f"(d[3]),"+f"(d[4]),"+f"(d[5]),"+f"(d[6]),"+f"(d[7]),"+f"(d[8]),"+f"(d[9]),"+f"(d[10]),"+f"(d[11]),"+f"(d[12]),"+f"(d[13]),"+f"(d[14]),"+f"(d[15]),"+f"(d[16]),"+f"(d[17]),"+f"(d[18]),"+f"(d[19]),"+f"(d[20]),"+f"(d[21]),"+f"(d[22]),"+f"(d[23]),"+f"(d[24]),"+f"(d[25]),"+f"(d[26]),"+f"(d[27]),"+f"(d[28]),"+f"(d[29]),"+f"(d[30]),"+f"(d[31]),"+f"(d[32]),"+f"(d[33]),"+f"(d[34]),"+f"(d[35]),"+f"(d[36]),"+f"(d[37]),"+f"(d[38]),"+f"(d[39]),"+f"(d[40]),"+f"(d[41]),"+f"(d[42]),"+f"(d[43]),"+f"(d[44]),"+f"(d[45]),"+f"(d[46]),"+f"(d[47]),"+f"(d[48]),"+f"(d[49]),"+f"(d[50]),"+f"(d[51]),"+f"(d[52]),"+f"(d[53]),"+f"(d[54]),"+f"(d[55]),"+f"(d[56]),"+f"(d[57]),"+f"(d[58]),"+f"(d[59]),"+f"(d[60]),"+f"(d[61]),"+f"(d[62]),"+f"(d[63]),"+f"(d[64]),"+f"(d[65]),"+f"(d[66]),"+f"(d[67]),"+f"(d[68]),"+f"(d[69]),"+f"(d[70]),"+f"(d[71]),"+f"(d[72]),"+f"(d[73]),"+f"(d[74]),"+f"(d[75]),"+f"(d[76]),"+f"(d[77]),"+f"(d[78]),"+f"(d[79]),"+f"(d[80]),"+f"(d[81]),"+f"(d[82]),"+f"(d[83]),"+f"(d[84]),"+f"(d[85]),"+f"(d[86]),"+f"(d[87]),"+f"(d[88]),"+f"(d[89]),"+f"(d[90]),"+f"(d[91]),"+f"(d[92]),"+f"(d[93]),"+f"(d[94]),"+f"(d[95]),"+f"(d[96]),"+f"(d[97]),"+f"(d[98]),"+f"(d[99]),"+f"(d[100]),"+f"(d[101]),"+f"(d[102]),"+f"(d[103]),"+f"(d[104]),"+f"(d[105]),"+f"(d[106]),"+f"(d[107]),"+f"(d[108]),"+f"(d[109]),"+f"(d[110]),"+f"(d[111]),"+f"(d[112]),"+f"(d[113]),"+f"(d[114]),"+f"(d[115]),"+f"(d[116]),"+f"(d[117]),"+f"(d[118]),"+f"(d[119]),"+f"(d[120]),"+f"(d[121]),"+f"(d[122]),"+f"(d[123]),"+f"(d[124]),"+f"(d[125]),"+f"(d[126]),"+f"(d[127])
    : "r"(da), "r"(db), "r"(sd), "r"(ha));
}
__device__ __forceinline__ void wgmma_ss_n128(float (&d)[64], uint32_t da, uint32_t ha, uint32_t db, int sd) {
  asm volatile("{\n.reg .pred p;\n.reg .b64 a, b;\nsetp.ne.b32 p, %66, 0;\nmov.b64 a, {%64, %67};\nmov.b64 b, {%65, 0x40000040};\n"
    "wgmma.mma_async.sync.aligned.m64n128k16.f32.bf16.bf16 {%0,%1,%2,%3,%4,%5,%6,%7,%8,%9,%10,%11,%12,%13,%14,%15,%16,%17,%18,%19,%20,%21,%22,%23,%24,%25,%26,%27,%28,%29,%30,%31,%32,%33,%34,%35,%36,%37,%38,%39,%40,%41,%42,%43,%44,%45,%46,%47,%48,%49,%50,%51,%52,%53,%54,%55,%56,%57,%58,%59,%60,%61,%62,%63}, a, b, p, 1, 1, 0, 1;\n}\n"
    : "+f"(d[0]),"+f"(d[1]),"+f"(d[2]),"+f"(d[3]),"+f"(d[4]),"+f"(d[5]),"+f"(d[6]),"+f"(d[7]),"+f"(d[8]),"+f"(d[9]),"+f"(d[10]),"+f"(d[11]),"+f"(d[12]),"+f"(d[13]),"+f"(d[14]),"+f"(d[15]),"+f"(d[16]),"+f"(d[17]),"+f"(d[18]),"+f"(d[19]),"+f"(d[20]),"+f"(d[21]),"+f"(d[22]),"+f"(d[23]),"+f"(d[24]),"+f"(d[25]),"+f"(d[26]),"+f"(d[27]),"+f"(d[28]),"+f"(d[29]),"+f"(d[30]),"+f"(d[31]),"+f"(d[32]),"+f"(d[33]),"+f"(d[34]),"+f"(d[35]),"+f"(d[36]),"+f"(d[37]),"+f"(d[38]),"+f"(d[39]),"+f"(d[40]),"+f"(d[41]),"+f"(d[42]),"+f"(d[43]),"+f"(d[44]),"+f"(d[45]),"+f"(d[46]),"+f"(d[47]),"+f"(d[48]),"+f"(d[49]),"+f"(d[50]),"+f"(d[51]),"+f"(d[52]),"+f"(d[53]),"+f"(d[54]),"+f"(d[55]),"+f"(d[56]),"+f"(d[57]),"+f"(d[58]),"+f"(d[59]),"+f"(d[60]),"+f"(d[61]),"+f"(d[62]),"+f"(d[63])
    : "r"(da), "r"(db), "r"(sd), "r"(ha));
}
__device__ __forceinline__ void wgmma_ss_n40_tt(float (&d)[20], uint32_t da, uint32_t db, int sd) {
  asm volatile("{\n.reg .pred p;\n.reg .b64 a, b;\nsetp.ne.b32 p, %22, 0;\nmov.b64 a, {%20, 0x40000040};\nmov.b64 b, {%21, 0x8};\n"
    "wgmma.mma_async.sync.aligned.m64n40k16.f32.bf16.bf16 {%0,%1,%2,%3,%4,%5,%6,%7,%8,%9,%10,%11,%12,%13,%14,%15,%16,%17,%18,%19}, a, b, p, 1, 1, 1, 1;\n}\n"
    : "+f"(d[0]),"+f"(d[1]),"+f"(d[2]),"+f"(d[3]),"+f"(d[4]),"+f"(d[5]),"+f"(d[6]),"+f"(d[7]),"+f"(d[8]),"+f"(d[9]),"+f"(d[10]),"+f"(d[11]),"+f"(d[12]),"+f"(d[13]),"+f"(d[14]),"+f"(d[15]),"+f"(d[16]),"+f"(d[17]),"+f"(d[18]),"+f"(d[19])
    : "r"(da), "r"(db), "r"(sd));
}
__device__ __forceinline__ void wgmma_ss_n32(float (&d)[16], uint32_t da, uint32_t db, int sd) {
  asm volatile("{\n.reg .pred p;\n.reg .b64 a, b;\nsetp.ne.b32 p, %18, 0;\nmov.b64 a, {%16, 0x40000040};\nmov.b64 b, {%17, 0x80000020};\n"
    "wgmma.mma_async.sync.aligned.m64n32k16.f32.bf16.bf16 {%0,%1,%2,%3,%4,%5,%6,%7,%8,%9,%10,%11,%12,%13,%14,%15}, a, b, p, 1, 1, 0, 1;\n}\n"
    : "+f"(d[0]),"+f"(d[1]),"+f"(d[2]),"+f"(d[3]),"+f"(d[4]),"+f"(d[5]),"+f"(d[6]),"+f"(d[7]),"+f"(d[8]),"+f"(d[9]),"+f"(d[10]),"+f"(d[11]),"+f"(d[12]),"+f"(d[13]),"+f"(d[14]),"+f"(d[15])
    : "r"(da), "r"(db), "r"(sd));
}
__device__ __forceinline__ void wgmma_rs_n40(float (&d)[20], uint32_t a0, uint32_t a1, uint32_t a2, uint32_t a3, uint32_t db, int sd) {
  asm volatile("{\n.reg .pred p;\n.reg .b64 b;\nsetp.ne.b32 p, %25, 0;\nmov.b64 b, {%24, 0x10};\n"
    "wgmma.mma_async.sync.aligned.m64n40k16.f32.bf16.bf16 {%0,%1,%2,%3,%4,%5,%6,%7,%8,%9,%10,%11,%12,%13,%14,%15,%16,%17,%18,%19}, {%20,%21,%22,%23}, b, p, 1, 1, 1;\n}\n"
    : "+f"(d[0]),"+f"(d[1]),"+f"(d[2]),"+f"(d[3]),"+f"(d[4]),"+f"(d[5]),"+f"(d[6]),"+f"(d[7]),"+f"(d[8]),"+f"(d[9]),"+f"(d[10]),"+f"(d[11]),"+f"(d[12]),"+f"(d[13]),"+f"(d[14]),"+f"(d[15]),"+f"(d[16]),"+f"(d[17]),"+f"(d[18]),"+f"(d[19])
    : "r"(a0), "r"(a1), "r"(a2), "r"(a3), "r"(db), "r"(sd));
}
__device__ __forceinline__ void wgmma_r1_n256(float (&d)[128], uint32_t da, uint32_t db, int sd) {
  asm volatile("{\n.reg .pred p;\n.reg .b64 a, b;\nsetp.ne.b32 p, %130, 0;\nmov.b64 a, {%128, 0x8};\nmov.b64 b, {%129, 0x6};\n"
    "wgmma.mma_async.sync.aligned.m64n256k16.f32.bf16.bf16 {%0,%1,%2,%3,%4,%5,%6,%7,%8,%9,%10,%11,%12,%13,%14,%15,%16,%17,%18,%19,%20,%21,%22,%23,%24,%25,%26,%27,%28,%29,%30,%31,%32,%33,%34,%35,%36,%37,%38,%39,%40,%41,%42,%43,%44,%45,%46,%47,%48,%49,%50,%51,%52,%53,%54,%55,%56,%57,%58,%59,%60,%61,%62,%63,%64,%65,%66,%67,%68,%69,%70,%71,%72,%73,%74,%75,%76,%77,%78,%79,%80,%81,%82,%83,%84,%85,%86,%87,%88,%89,%90,%91,%92,%93,%94,%95,%96,%97,%98,%99,%100,%101,%102,%103,%104,%105,%106,%107,%108,%109,%110,%111,%112,%113,%114,%115,%116,%117,%118,%119,%120,%121,%122,%123,%124,%125,%126,%127}, a, b, p, 1, 1, 0, 1;\n}\n"
    : "+f"(d[0]),"+f"(d[1]),"+f"(d[2]),"+f"(d[3]),"+f"(d[4]),"+f"(d[5]),"+f"(d[6]),"+f"(d[7]),"+f"(d[8]),"+f"(d[9]),"+f"(d[10]),"+f"(d[11]),"+f"(d[12]),"+f"(d[13]),"+f"(d[14]),"+f"(d[15]),"+f"(d[16]),"+f"(d[17]),"+f"(d[18]),"+f"(d[19]),"+f"(d[20]),"+f"(d[21]),"+f"(d[22]),"+f"(d[23]),"+f"(d[24]),"+f"(d[25]),"+f"(d[26]),"+f"(d[27]),"+f"(d[28]),"+f"(d[29]),"+f"(d[30]),"+f"(d[31]),"+f"(d[32]),"+f"(d[33]),"+f"(d[34]),"+f"(d[35]),"+f"(d[36]),"+f"(d[37]),"+f"(d[38]),"+f"(d[39]),"+f"(d[40]),"+f"(d[41]),"+f"(d[42]),"+f"(d[43]),"+f"(d[44]),"+f"(d[45]),"+f"(d[46]),"+f"(d[47]),"+f"(d[48]),"+f"(d[49]),"+f"(d[50]),"+f"(d[51]),"+f"(d[52]),"+f"(d[53]),"+f"(d[54]),"+f"(d[55]),"+f"(d[56]),"+f"(d[57]),"+f"(d[58]),"+f"(d[59]),"+f"(d[60]),"+f"(d[61]),"+f"(d[62]),"+f"(d[63]),"+f"(d[64]),"+f"(d[65]),"+f"(d[66]),"+f"(d[67]),"+f"(d[68]),"+f"(d[69]),"+f"(d[70]),"+f"(d[71]),"+f"(d[72]),"+f"(d[73]),"+f"(d[74]),"+f"(d[75]),"+f"(d[76]),"+f"(d[77]),"+f"(d[78]),"+f"(d[79]),"+f"(d[80]),"+f"(d[81]),"+f"(d[82]),"+f"(d[83]),"+f"(d[84]),"+f"(d[85]),"+f"(d[86]),"+f"(d[87]),"+f"(d[88]),"+f"(d[89]),"+f"(d[90]),"+f"(d[91]),"+f"(d[92]),"+f"(d[93]),"+f"(d[94]),"+f"(d[95]),"+f"(d[96]),"+f"(d[97]),"+f"(d[98]),"+f"(d[99]),"+f"(d[100]),"+f"(d[101]),"+f"(d[102]),"+f"(d[103]),"+f"(d[104]),"+f"(d[105]),"+f"(d[106]),"+f"(d[107]),"+f"(d[108]),"+f"(d[109]),"+f"(d[110]),"+f"(d[111]),"+f"(d[112]),"+f"(d[113]),"+f"(d[114]),"+f"(d[115]),"+f"(d[116]),"+f"(d[117]),"+f"(d[118]),"+f"(d[119]),"+f"(d[120]),"+f"(d[121]),"+f"(d[122]),"+f"(d[123]),"+f"(d[124]),"+f"(d[125]),"+f"(d[126]),"+f"(d[127])
    : "r"(da), "r"(db), "r"(sd));
}
__device__ __forceinline__ void wgmma_r1_n128(float (&d)[64], uint32_t da, uint32_t db, int sd) {
  asm volatile("{\n.reg .pred p;\n.reg .b64 a, b;\nsetp.ne.b32 p, %66, 0;\nmov.b64 a, {%64, 0x8};\nmov.b64 b, {%65, 0x6};\n"
    "wgmma.mma_async.sync.aligned.m64n128k16.f32.bf16.bf16 {%0,%1,%2,%3,%4,%5,%6,%7,%8,%9,%10,%11,%12,%13,%14,%15,%16,%17,%18,%19,%20,%21,%22,%23,%24,%25,%26,%27,%28,%29,%30,%31,%32,%33,%34,%35,%36,%37,%38,%39,%40,%41,%42,%43,%44,%45,%46,%47,%48,%49,%50,%51,%52,%53,%54,%55,%56,%57,%58,%59,%60,%61,%62,%63}, a, b, p, 1, 1, 0, 1;\n}\n"
    : "+f"(d[0]),"+f"(d[1]),"+f"(d[2]),"+f"(d[3]),"+f"(d[4]),"+f"(d[5]),"+f"(d[6]),"+f"(d[7]),"+f"(d[8]),"+f"(d[9]),"+f"(d[10]),"+f"(d[11]),"+f"(d[12]),"+f"(d[13]),"+f"(d[14]),"+f"(d[15]),"+f"(d[16]),"+f"(d[17]),"+f"(d[18]),"+f"(d[19]),"+f"(d[20]),"+f"(d[21]),"+f"(d[22]),"+f"(d[23]),"+f"(d[24]),"+f"(d[25]),"+f"(d[26]),"+f"(d[27]),"+f"(d[28]),"+f"(d[29]),"+f"(d[30]),"+f"(d[31]),"+f"(d[32]),"+f"(d[33]),"+f"(d[34]),"+f"(d[35]),"+f"(d[36]),"+f"(d[37]),"+f"(d[38]),"+f"(d[39]),"+f"(d[40]),"+f"(d[41]),"+f"(d[42]),"+f"(d[43]),"+f"(d[44]),"+f"(d[45]),"+f"(d[46]),"+f"(d[47]),"+f"(d[48]),"+f"(d[49]),"+f"(d[50]),"+f"(d[51]),"+f"(d[52]),"+f"(d[53]),"+f"(d[54]),"+f"(d[55]),"+f"(d[56]),"+f"(d[57]),"+f"(d[58]),"+f"(d[59]),"+f"(d[60]),"+f"(d[61]),"+f"(d[62]),"+f"(d[63])
    : "r"(da), "r"(db), "r"(sd));
}

__device__ __forceinline__ uint32_t smem_u32(const void* p) { return (uint32_t)__cvta_generic_to_shared(p); }
__device__ __forceinline__ void mbar_init(uint32_t bar, uint32_t cnt) { asm volatile("mbarrier.init.shared::cta.b64 [%0], %1;" ::"r"(bar), "r"(cnt)); }
__device__ __forceinline__ void mbar_expect_tx(uint32_t bar, uint32_t bytes) { asm volatile("mbarrier.arrive.expect_tx.shared::cta.b64 _, [%0], %1;" ::"r"(bar), "r"(bytes) : "memory"); }
__device__ __forceinline__ void mbar_arrive(uint32_t bar) { asm volatile("mbarrier.arrive.shared::cta.b64 _, [%0];" ::"r"(bar) : "memory"); }
__device__ __forceinline__ void mbar_arrive_n(uint32_t bar, uint32_t n) { asm volatile("mbarrier.arrive.shared::cta.b64 _, [%0], %1;" ::"r"(bar), "r"(n) : "memory"); }
__device__ __forceinline__ void mbar_wait(uint32_t bar, uint32_t parity) {
  asm volatile("{\n.reg .pred p;\nLAB_WAIT:\nmbarrier.try_wait.parity.shared::cta.b64 p, [%0], %1;\n@p bra DONE;\nbra LAB_WAIT;\nDONE:\n}" ::"r"(bar), "r"(parity) : "memory");
}
__device__ __forceinline__ void mbar_wait2(uint32_t a, uint32_t pa, uint32_t b, uint32_t pb) {
  asm volatile("{\n.reg .pred p, q;\nLAB_WAIT:\nmbarrier.try_wait.parity.shared::cta.b64 p, [%0], %1;\nmbarrier.try_wait.parity.shared::cta.b64 q, [%2], %3;\n"
               "and.pred p, p, q;\n@p bra DONE;\nbra LAB_WAIT;\nDONE:\n}" ::"r"(a), "r"(pa), "r"(b), "r"(pb) : "memory");
}
__device__ __forceinline__ void mbar_wait3(uint32_t a, uint32_t pa, uint32_t b, uint32_t pb) {
  asm volatile("{\n.reg .pred p, q, r;\nLAB_WAIT:\nmbarrier.try_wait.parity.shared::cta.b64 p, [%0], %1;\nmbarrier.try_wait.parity.shared::cta.b64 q, [%2], %3;\n"
               "mbarrier.try_wait.parity.shared::cta.b64 r, [%2+8], %3;\nand.pred p, p, q;\nand.pred p, p, r;\n@p bra DONE;\nbra LAB_WAIT;\nDONE:\n}" ::"r"(a), "r"(pa), "r"(b), "r"(pb) : "memory");
}
__device__ __forceinline__ bool mbar_probe2(uint32_t a, uint32_t pa, uint32_t b, uint32_t pb) {
  uint32_t ok;
  asm volatile("{\n.reg .pred p, q;\nmbarrier.test_wait.parity.shared::cta.b64 p, [%1], %2;\nmbarrier.test_wait.parity.shared::cta.b64 q, [%3], %4;\n"
               "and.pred p, p, q;\nselp.u32 %0, 1, 0, p;\n}" : "=r"(ok) : "r"(a), "r"(pa), "r"(b), "r"(pb) : "memory");
  return ok != 0;
}
__device__ __forceinline__ void tma_load_3d(uint32_t dst, const CUtensorMap* tm, uint32_t bar, int c0, int c1, int c2) {
  asm volatile("cp.async.bulk.tensor.3d.shared::cluster.global.mbarrier::complete_tx::bytes [%0], [%1, {%3, %4, %5}], [%2];"
               ::"r"(dst), "l"(tm), "r"(bar), "r"(c0), "r"(c1), "r"(c2) : "memory");
}
__device__ __forceinline__ void tma_load_2d(uint32_t dst, const CUtensorMap* tm, uint32_t bar, int c0, int c1) {
  asm volatile("cp.async.bulk.tensor.2d.shared::cluster.global.mbarrier::complete_tx::bytes [%0], [%1, {%3, %4}], [%2];"
               ::"r"(dst), "l"(tm), "r"(bar), "r"(c0), "r"(c1) : "memory");
}
__device__ __forceinline__ void tma_load_w(uint32_t dst, const CUtensorMap* tm, uint32_t bar, int col, int kb) {
#pragma unroll
  for (int q = 0; q < 2; q++)
    asm volatile("cp.async.bulk.tensor.5d.shared::cluster.global.mbarrier::complete_tx::bytes [%0], [%1, {%3, %4, %4, %4, %5}], [%2];"
                 ::"r"(dst + q * 8192), "l"(tm), "r"(bar), "r"(col + q * 64), "r"(0), "r"(2 * kb) : "memory");
}
__device__ __forceinline__ void tma_prefetch_w(const CUtensorMap* tm, int col, int kb) {
#pragma unroll
  for (int q = 0; q < 2; q++)
    asm volatile("cp.async.bulk.prefetch.tensor.5d.L2.global [%0, {%1, %2, %2, %2, %3}];" ::"l"(tm), "r"(col + q * 64), "r"(0), "r"(2 * kb) : "memory");
}
__device__ __forceinline__ void bulk_load(uint32_t dst, const void* g, uint32_t bytes, uint32_t bar) {
  asm volatile("cp.async.bulk.shared::cluster.global.mbarrier::complete_tx::bytes [%0], [%1], %2, [%3];" ::"r"(dst), "l"(g), "r"(bytes), "r"(bar) : "memory");
}
__device__ __forceinline__ void prefetch_map(const CUtensorMap* tm) { asm volatile("prefetch.tensormap [%0];" ::"l"(tm) : "memory"); }
__device__ __forceinline__ void fence_async_smem() { asm volatile("fence.proxy.async.shared::cta;" ::: "memory"); }
__device__ __forceinline__ void fence_async_global() { asm volatile("fence.proxy.async.global;" ::: "memory"); }
__device__ __forceinline__ void fence_gpu() { asm volatile("fence.release.gpu;" ::: "memory"); }
__device__ __forceinline__ void st_flag(unsigned* p, unsigned v) { asm volatile("st.relaxed.gpu.global.u32 [%0], %1;" ::"l"(p), "r"(v) : "memory"); }
__device__ __forceinline__ unsigned ld_flag(const unsigned* p) { unsigned v; asm volatile("ld.relaxed.gpu.global.u32 %0, [%1];" : "=r"(v) : "l"(p) : "memory"); return v; }
__device__ __forceinline__ uint4 ldcg4(const void* p) { uint4 v; asm volatile("ld.global.cg.v4.u32 {%0,%1,%2,%3}, [%4];" : "=r"(v.x), "=r"(v.y), "=r"(v.z), "=r"(v.w) : "l"(p)); return v; }
__device__ __forceinline__ uint4 ld_pkt(const uint4* p) {
  uint4 v; asm volatile("{\n.reg .b128 t;\nld.relaxed.gpu.global.b128 t, [%4];\nmov.b128 {%0,%1,%2,%3}, t;\n}" : "=r"(v.x), "=r"(v.y), "=r"(v.z), "=r"(v.w) : "l"(p) : "memory"); return v;
}
__device__ __forceinline__ void st_pkt(uint4* p, uint32_t a, uint32_t b, uint32_t c, uint32_t tag) {
  asm volatile("{\n.reg .b128 t;\nmov.b128 t, {%1,%2,%3,%4};\nst.relaxed.gpu.global.b128 [%0], t;\n}" ::"l"(p), "r"(a), "r"(b), "r"(c), "r"(tag) : "memory");
}
__device__ __forceinline__ void st_v4(uint4* p, uint32_t a, uint32_t b, uint32_t c, uint32_t d) { asm volatile("st.relaxed.gpu.global.v4.u32 [%0], {%1,%2,%3,%4};" ::"l"(p), "r"(a), "r"(b), "r"(c), "r"(d) : "memory"); }
__device__ __forceinline__ void stg128(uint4* p, uint4 v) { asm volatile("st.global.v4.u32 [%0], {%1,%2,%3,%4};" ::"l"(p), "r"(v.x), "r"(v.y), "r"(v.z), "r"(v.w) : "memory"); }
__device__ __forceinline__ void sts32(uint32_t addr, uint32_t a) { asm volatile("st.shared.u32 [%0], %1;" ::"r"(addr), "r"(a) : "memory"); }
__device__ __forceinline__ void sts64(uint32_t addr, uint32_t a, uint32_t b) { asm volatile("st.shared.v2.u32 [%0], {%1,%2};" ::"r"(addr), "r"(a), "r"(b) : "memory"); }
__device__ __forceinline__ uint32_t mul2(uint32_t a, uint32_t b) { uint32_t r; asm("mul.rn.bf16x2 %0, %1, %2;" : "=r"(r) : "r"(a), "r"(b)); return r; }
__device__ __forceinline__ uint32_t add2(uint32_t a, uint32_t b) { uint32_t r; asm("add.rn.bf16x2 %0, %1, %2;" : "=r"(r) : "r"(a), "r"(b)); return r; }
__device__ __forceinline__ bool elect() {
  uint32_t p; asm volatile("{\n.reg .pred q;\nelect.sync _|q, 0xffffffff;\nselp.u32 %0, 1, 0, q;\n}" : "=r"(p)); return p != 0;
}
__device__ __forceinline__ void wgmma_fence() { asm volatile("wgmma.fence.sync.aligned;" ::: "memory"); }
__device__ __forceinline__ void wgmma_commit() { asm volatile("wgmma.commit_group.sync.aligned;" ::: "memory"); }
template <int N> __device__ __forceinline__ void wgmma_wait() { asm volatile("wgmma.wait_group.sync.aligned %0;" ::"n"(N) : "memory"); }
template <int N> __device__ __forceinline__ void fence_regs(float (&d)[N]) {
#pragma unroll
  for (int i = 0; i < N; i++) asm volatile("" : "+f"(d[i])::"memory");
}
template <int R> __device__ __forceinline__ void reg_alloc() { asm volatile("setmaxnreg.inc.sync.aligned.u32 %0;" ::"n"(R)); }
template <int R> __device__ __forceinline__ void reg_dealloc() { asm volatile("setmaxnreg.dec.sync.aligned.u32 %0;" ::"n"(R)); }
__device__ __forceinline__ void wg_bar(int w) { asm volatile("bar.sync %0, 128;" ::"r"(w + 1) : "memory"); }
__device__ __forceinline__ constexpr uint32_t desc_lo(uint32_t addr, uint32_t lbo) { return (addr >> 4) + ((lbo >> 4) << 16); }
__device__ __forceinline__ uint32_t pack2(float lo, float hi) { uint32_t r; asm("cvt.rn.bf16x2.f32 %0, %1, %2;" : "=r"(r) : "f"(hi), "f"(lo)); return r; }
__device__ __forceinline__ float lo16(uint32_t v) { return __uint_as_float(v << 16); }
__device__ __forceinline__ float hi16(uint32_t v) { return __uint_as_float(v & 0xFFFF0000u); }
__device__ __forceinline__ float ex2(float x) { float r; asm("ex2.approx.ftz.f32 %0, %1;" : "=f"(r) : "f"(x)); return r; }
__device__ __forceinline__ float rcp(float x) { float r; asm("rcp.approx.ftz.f32 %0, %1;" : "=f"(r) : "f"(x)); return r; }
__device__ __forceinline__ uint32_t movm(uint32_t a) { uint32_t d; asm volatile("movmatrix.sync.aligned.m8n8.trans.b16 %0, %1;" : "=r"(d) : "r"(a)); return d; }
__device__ __forceinline__ void stsm4(uint32_t addr, uint32_t a, uint32_t b, uint32_t c, uint32_t d) {
  asm volatile("stmatrix.sync.aligned.m8n8.x4.shared.b16 [%0], {%1,%2,%3,%4};" ::"r"(addr), "r"(a), "r"(b), "r"(c), "r"(d) : "memory");
}
__device__ __forceinline__ void ldsm4(uint32_t addr, uint32_t (&r)[4]) {
  asm volatile("ldmatrix.sync.aligned.m8n8.x4.shared.b16 {%0,%1,%2,%3}, [%4];" : "=r"(r[0]), "=r"(r[1]), "=r"(r[2]), "=r"(r[3]) : "r"(addr) : "memory");
}
__device__ __forceinline__ void sts128(uint32_t addr, uint32_t a, uint32_t b, uint32_t c, uint32_t d) {
  asm volatile("st.shared.v4.u32 [%0], {%1,%2,%3,%4};" ::"r"(addr), "r"(a), "r"(b), "r"(c), "r"(d) : "memory");
}
__device__ __forceinline__ void lds128(uint32_t addr, uint32_t& a, uint32_t& b, uint32_t& c, uint32_t& d) {
  asm volatile("ld.shared.v4.u32 {%0,%1,%2,%3}, [%4];" : "=r"(a), "=r"(b), "=r"(c), "=r"(d) : "r"(addr) : "memory");
}
__device__ __forceinline__ float lds32f(uint32_t addr) { float v; asm volatile("ld.shared.f32 %0, [%1];" : "=f"(v) : "r"(addr) : "memory"); return v; }
__device__ __forceinline__ float2 lds64f(uint32_t addr) { float2 v; asm volatile("ld.shared.v2.f32 {%0,%1}, [%2];" : "=f"(v.x), "=f"(v.y) : "r"(addr) : "memory"); return v; }
__device__ __forceinline__ void mma16816(float (&d)[4], uint32_t a0, uint32_t a1, uint32_t a2, uint32_t a3, uint32_t b0, uint32_t b1) {
  asm("mma.sync.aligned.m16n8k16.row.col.f32.bf16.bf16.f32 {%0,%1,%2,%3}, {%4,%5,%6,%7}, {%8,%9}, {%0,%1,%2,%3};"
      : "+f"(d[0]), "+f"(d[1]), "+f"(d[2]), "+f"(d[3]) : "r"(a0), "r"(a1), "r"(a2), "r"(a3), "r"(b0), "r"(b1));
}
__device__ __forceinline__ void mma1688(float (&d)[4], uint32_t a0, uint32_t a1, uint32_t b0) {
  asm("mma.sync.aligned.m16n8k8.row.col.f32.bf16.bf16.f32 {%0,%1,%2,%3}, {%4,%5}, {%6}, {%0,%1,%2,%3};"
      : "+f"(d[0]), "+f"(d[1]), "+f"(d[2]), "+f"(d[3]) : "r"(a0), "r"(a1), "r"(b0));
}

__device__ __forceinline__ float qsum(float v) { v += __shfl_xor_sync(0xffffffffu, v, 1); v += __shfl_xor_sync(0xffffffffu, v, 2); return v; }

constexpr int NCTA = 132;
#define NB_ 6
#define NA_ 5
constexpr int NB = NB_;
constexpr int NA = NA_;
constexpr uint32_t SLOT = 16384;
constexpr uint32_t SB = 1024;
constexpr uint32_t OFF_B = 0;
constexpr uint32_t OFF_A = NB * SLOT;
constexpr uint32_t OFF_S = OFF_A + NA * SLOT;
constexpr uint32_t OFF_T = OFF_S + 20480;
constexpr uint32_t OFF_CS = OFF_T + 24576;
constexpr uint32_t OFF_MR = OFF_CS + 4640;
constexpr uint32_t OFF_BAR = OFF_MR + 512;
constexpr uint32_t OFF_MA = OFF_S, OFF_MB = OFF_CS - 2048;
constexpr uint32_t BAR_FULLB = OFF_BAR;
constexpr uint32_t BAR_FULLA = BAR_FULLB + 64;
constexpr uint32_t BAR_EMPTYB = BAR_FULLA + 64;
constexpr uint32_t BAR_EMPTYA = BAR_EMPTYB + 64;
constexpr uint32_t BAR_SIGP = BAR_EMPTYA + 64;
constexpr uint32_t BAR_SIGT = BAR_SIGP + 24;
constexpr uint32_t BAR_STAT = BAR_SIGP + 64;
constexpr uint32_t BAR_HALO = BAR_STAT + 16;
constexpr uint32_t BAR_CS = BAR_HALO + 8;
constexpr uint32_t BAR_WPHI = BAR_CS + 16;
constexpr uint32_t BAR_KV = BAR_WPHI + 8;
constexpr uint32_t BAR_STG = BAR_KV + 16;
constexpr uint32_t BAR_EPOCH = BAR_STG + 48;
constexpr uint32_t BAR_LAND = OFF_BAR + 7 * 64;
constexpr uint32_t OFF_EPOCH = OFF_BAR + 8 * 64;
static_assert(BAR_EPOCH < BAR_LAND, "barriers");
constexpr uint32_t SMEM_BYTES = OFF_EPOCH + 8;
static_assert(SMEM_BYTES <= 232448 && NB % 2 == 0 && NB <= 8 && NA <= 6, "smem");

#define CREGS 224
#define PREGS 56
#define PF1 19
#define PF2 21
#define PRE_A 2
#define PRE_B 4
#define CSNEED 0xF001u
#define PS0 1
#define PS1 3
#define SD 1000
#define KSPLIT 12
#define KEEP 16
#define NJ 3
#define KSL 1000
#define PSL 0
#define KVS 12
#define D2 2000
#define D3 1500
#define G0 50
#define MAP 3
#define PMAP 0x76321450u
#define XA 3
#define CP 500
#define S0 500
#define NS 2
#define SW 2
#define SA 1
#define SB_ 4
#define ND0 1
#define KC 8
#define CO 0
#define SE 500
#define PAA 1600
#define PAX 900
#define PA0 1800
#define PX0 1100
#define XN 1
#define RG 1
#define DEFER 3
#define DEFL 2
#define TSK 3
constexpr int NTHREADS = 384;

struct Params {
  CUtensorMap mx;
  CUtensorMap mw[3];
  CUtensorMap mwo[2];
  CUtensorMap mcs[2];
  CUtensorMap mwphi;
  uint4* out;
};

#define XBUF(L) 1
__device__ __align__(256) uint4 g_img[XBUF(3) + 1][16][16][1024];
__device__ __forceinline__ uint32_t img_code(bool isx, int L) { return isx ? (L & 1) | (L & 2) << 15 : ~L & 1; }
__device__ __forceinline__ uint32_t img_mask(bool isx) { return isx ? 0x10001u : 1u; }
__device__ __align__(256) uint4 g_wf[2][8][16][1024];
__device__ __align__(256) uint4 g_stats[16][2][8][32];
__device__ __align__(256) uint4 g_halo[16][8][2][256];
__device__ __align__(256) float g_cs[2][2][3072];
__device__ __align__(256) uint4 g_kvpart[8][16][2][544];
__device__ __align__(256) uint4 g_kvfin[8][16][80];
__device__ __align__(256) unsigned g_hint[16][32];
__device__ __align__(256) unsigned g_jflag[3][8][32];
__device__ unsigned g_ctr;
__device__ __forceinline__ unsigned vblock() {
  unsigned s;
  asm volatile("mov.u32 %0, %%smid;" : "=r"(s));
  const unsigned r = s & 1;
  s >>= 1;
  const unsigned t = s - 32, q = (t * 37) >> 8;
  const unsigned hi = s < 60 ? 12 + (t - 7 * q) * 8 + q : (s < 62 ? s + 4 : s - 58);
  unsigned b = 2 * (s < 32 ? (s & 7) * 8 + (s >> 3) : hi) + r;
  if (b < 128) b = (b & 15) | ((PMAP >> ((b >> 4) * 4)) & 7) << 4;
  if (s >= 62) b = 8 + 4 * r + s - 62;
  unsigned n;
  asm volatile("mov.u32 %0, %%nsmid;" : "=r"(n));
  return __shfl_sync(0xffffffffu, n == NCTA ? b : blockIdx.x, 0);
}
#define TS(who, id) do {} while (0)
#define TSW(id) do {} while (0)

#define TSH(id) do {} while (0)
#define TSMASK 0xFFFF
#define TSL_(a) do { if ((TSMASK >> (a)) & 1) TSW((a) + L * 12); } while (0)
__device__ __forceinline__ int cta_m(unsigned b) { return ((b >> 2) & 12) | (b & 3); }
__device__ __forceinline__ int cta_j(unsigned b) { return ((b >> 2) & 3) | ((b >> 4) & 4); }
struct Ring { uint32_t s, ph; };
template <int N> __device__ __forceinline__ void adv(Ring& r) { if (++r.s == N) { r.s = 0; r.ph ^= 1; } }
template <int N> __device__ __forceinline__ void rewind2(Ring& r) { if (r.s < 2) { r.s += N - 2; r.ph ^= 1; } else r.s -= 2; }
__device__ __forceinline__ int other_tile(int t, int j) { return (t == (j | 4) ? 7 : t) ^ (~j & 4); }
__device__ __forceinline__ int o_order(int i, int j) {
  if (i < 2) return 2 * j + i;
  const int odd = i >= 9;
  return 2 * other_tile(i - 2 - 7 * odd, j) + odd;
}
__device__ __forceinline__ int kv_order(int i, int j, int L) { return L > 0 ? o_order(i, j) : (i + 14 + 2 * (j & 4)) & 15; }

__device__ __forceinline__ unsigned poll_flags(const unsigned* f, int n, unsigned need, unsigned tag) {
  const int lane = threadIdx.x & 31;
  unsigned mask; int it = 0;
  do {
    unsigned v = lane < n ? ld_flag(f + lane) : 0u;
    mask = __ballot_sync(0xffffffffu, lane < n && (int)(v - tag) >= 0);
    if (++it > (1 << 22)) __trap();
  } while ((mask & need) != need);
  fence_async_global();
  return mask;
}
template <bool WAIT = true>
__device__ __forceinline__ unsigned get_tag(uint32_t sb) {
  if (WAIT) mbar_wait(sb + BAR_EPOCH, 0);
  unsigned t; asm volatile("ld.shared.u32 %0, [%1];" : "=r"(t) : "r"(sb + OFF_EPOCH) : "memory");
  return t;
}

__device__ __forceinline__ int lane_id() { int l; asm volatile("mov.u32 %0, %%laneid;" : "=r"(l)); return l; }
__device__ __forceinline__ unsigned seq4(unsigned tag, int L) { return 8u | ((tag & 1u) << 2) | (unsigned)L; }
constexpr float LOG2E = 1.4426950408889634f;

__device__ __forceinline__ float bb_fence(int never, const void* p = &g_ctr, uint32_t keep = 0) {
  while (never < 0) never = ld_flag((const unsigned*)p) + keep;
  return __int_as_float(never >> 30);
}
__device__ __forceinline__ uint32_t solid(uint32_t v) { return __shfl_sync(0xffffffffu, v, threadIdx.x & 31); }
template <class T> __device__ __forceinline__ T* solid(T* p) { return (T*)__shfl_sync(0xffffffffu, (unsigned long long)p, threadIdx.x & 31); }
constexpr uint32_t HA128 = 0x40000040u, HA64 = 0x80000040u;
struct Ctx {
  static constexpr uint32_t sb = SB;
  uint32_t ab, da0;
  int w, warp, lane, g, c;
  int goff;
  __device__ __forceinline__ int m() const { return goff >> 14; }
  __device__ __forceinline__ int j() const { return (goff >> 4) & 7; }
  bool elected;
  Ring ra, rb;
  uint32_t pa, pb;
  uint32_t ha, k2;
  uint32_t mrow, mxor, mhi;
  __device__ __forceinline__ uint32_t aslot(uint32_t s) const { return ab + s * SLOT; }
  __device__ __forceinline__ uint32_t fullA(uint32_t s) const { return sb + BAR_FULLA + s * 8; }
  __device__ __forceinline__ uint32_t fullB(uint32_t s) const { return sb + BAR_FULLB + s * 8; }
  __device__ __forceinline__ void releaseA(uint32_t s) const { if (elected) mbar_arrive(sb + BAR_EMPTYA + s * 8); }
  __device__ __forceinline__ void releaseB(uint32_t s) const { if (elected) mbar_arrive(sb + BAR_EMPTYB + s * 8); }
  __device__ __forceinline__ uint32_t maddr(uint32_t tile, uint32_t ch) const { return tile + mrow + (((ch + mhi) ^ mxor) << 4); }
  __device__ __forceinline__ uint32_t oo() const { return warp * 128 + g * 4 + (c ^ (g >> 1)); }
  __device__ __forceinline__ uint4* img(int b, int hp) const { return ip + (b * 256 + hp) * 1024; }
  uint4* ip;
  uint32_t so;
  __device__ __forceinline__ uint32_t held(int i) const { return ra.s + i < 2 ? ra.s + i + NA - 2 : ra.s + i - 2; }
};

template <int N, bool FIRST, bool O = true>
__device__ __forceinline__ void gemm_issue(float (&acc)[N / 2], Ctx& x, bool ready = false) {
  if (!ready) {
    if (N == 256) mbar_wait3(x.fullA(x.ra.s), x.ra.ph, x.fullB(x.rb.s), x.rb.ph);
    else mbar_wait2(x.fullA(x.ra.s), x.ra.ph, x.fullB(x.rb.s), x.rb.ph);
  }
  const uint32_t da = x.da0 + x.ra.s * (SLOT / 16), db = desc_lo(SB + OFF_B, 8192) + x.rb.s * (SLOT / 16);
  wgmma_fence();
#pragma unroll
  for (int k = 0; k < 4; k++) {
    const uint32_t a = da + (k >> 1) * (O ? 32 : x.k2) + (k & 1) * 2, ha = O ? HA64 : x.ha;
    if constexpr (N == 256) wgmma_ss_n256(acc, a, ha, db + 128 * k, !(FIRST && k == 0));
    else wgmma_ss_n128(acc, a, ha, db + 128 * k, !(FIRST && k == 0));
  }
  wgmma_commit();
}
template <int N>
__device__ __forceinline__ void gemm_next(Ctx& x) {
  x.pa = x.ra.s; x.pb = x.rb.s;
  if (N == 256) x.rb.s++;
  adv<NA>(x.ra); adv<NB>(x.rb);
}
template <int N>
__device__ __forceinline__ void gemm_release(Ctx& x, bool relA) {
  if (relA) x.releaseA(x.pa);
  x.releaseB(x.pb);
  if (N == 256) x.releaseB(x.pb + 1);
}
template <int N>
__device__ __forceinline__ void gemm_retire(Ctx& x, bool relA) { wgmma_wait<1>(); gemm_release<N>(x, relA); gemm_next<N>(x); }
template <bool O = true>
__device__ __forceinline__ void gemm_run(float (&acc)[64], Ctx& x, int n, int hold, int n4 = 0) {
  bool ready = false;
#pragma unroll 1
  for (; n > 0; n--) {
    gemm_issue<128, false, O>(acc, x, ready);
    const uint32_t pa = x.pa, pb = x.pb;
    gemm_next<128>(x);
    ready = mbar_probe2(x.fullA(x.ra.s), x.ra.ph, x.fullB(x.rb.s), x.rb.ph);
    wgmma_wait<1>();
    if (n > hold) x.releaseA(pa);
    x.releaseB(pb);
  }
}
__device__ __forceinline__ void gemm_end(float (&acc)[64], Ctx& x) { wgmma_wait<0>(); fence_regs(acc); gemm_release<128>(x, false); }

__device__ __forceinline__ void rows_load(uint4* r, uint32_t tile, const Ctx& x) {
#pragma unroll
  for (int q = 0; q < 4; q++) {
    const uint32_t row = x.warp * 16 + 4 * q + (x.lane >> 3);
    lds128(tile + row * 128 + (((x.lane & 7) ^ (row & 7)) << 4), r[q].x, r[q].y, r[q].z, r[q].w);
  }
}
__device__ __forceinline__ void rows_store(const uint4* r, uint4* g) {
#pragma unroll
  for (int q = 0; q < 4; q++) stg128(g + q * 1024, r[q]);
}
__device__ __forceinline__ void publish(int id, const Ctx& x) { __syncwarp(); if (x.lane == 0) mbar_arrive(x.sb + BAR_SIGP + id * 8); }
__device__ __forceinline__ uint32_t img_tag(uint32_t v, bool isx, int L, const Ctx& x) {
  const uint32_t mk = ((x.lane ^ (x.warp * 4)) & 7) ? 0u : img_mask(isx);
  return (v & ~mk) | (img_code(isx, L) & mk);
}
__device__ __forceinline__ void img_tag(uint4 (&r)[4], bool isx, int L, const Ctx& x) {
#pragma unroll
  for (int q = 0; q < 4; q++) { uint32_t& v = q == 0 ? r[q].x : (q == 1 ? r[q].y : (q == 2 ? r[q].z : r[q].w)); v = img_tag(v, isx, L, x); }
}
__device__ __forceinline__ void img_store(const uint4 (&r)[4], uint4* g) {
#pragma unroll
  for (int q = 0; q < 4; q++) stg128(g + q * 32, r[q]);
}
__device__ __forceinline__ void img_sts(const uint4 (&r)[4], uint32_t tile, const Ctx& x) {
#pragma unroll
  for (int q = 0; q < 4; q++) sts128(tile + x.so + q * 512, r[q].x, r[q].y, r[q].z, r[q].w);
}
__device__ __forceinline__ void img_load(uint32_t (&v)[16], uint32_t tile, const Ctx& x) {
#pragma unroll
  for (int q = 0; q < 4; q++) lds128(tile + x.so + q * 512, v[4 * q], v[4 * q + 1], v[4 * q + 2], v[4 * q + 3]);
}
__device__ __forceinline__ void img_unpack(float* a, const uint32_t (&v)[16]) {
#pragma unroll
  for (int q = 0; q < 16; q++) { a[4 * (q & 7) + 2 * (q >> 3)] = lo16(v[q]); a[4 * (q & 7) + 2 * (q >> 3) + 1] = hi16(v[q]); }
}

template <int N>
__device__ __forceinline__ void stats_acc(const float* a, float (&t)[4]) {
#pragma unroll
  for (int i = 0; i < N; i++) { t[i & 2] += a[i]; t[(i & 2) + 1] = fmaf(a[i], a[i], t[(i & 2) + 1]); }
}
__device__ __forceinline__ void stats_send(float (&t)[4], int L, const Ctx& x) {
  const unsigned seq = seq4(get_tag<false>(x.sb), L);
#pragma unroll
  for (int q = 0; q < 4; q++) t[q] = qsum(t[q]);
  if (x.c == 0) st_pkt(&g_stats[x.m()][x.w][x.j()][x.warp * 8 + x.g], __float_as_uint(t[0]), __float_as_uint(t[1]), __float_as_uint(t[2]), (__float_as_uint(t[3]) & ~15u) | seq);
}
__device__ __forceinline__ void out_epilogue(const float (&acc)[64], uint4 (&r1)[4], float (&t)[4], uint4* g, int L, Ctx& x) {
  const uint32_t t0 = x.aslot(x.ra.s), t1 = x.aslot(x.ra.s + 1 == NA ? 0 : x.ra.s + 1);
  if (L == 3) {
#pragma unroll
    for (int p = 0; p < 8; p++) {
      stsm4(x.maddr(p < 4 ? t0 : t1, (p & 3) * 2), pack2(acc[8 * p], acc[8 * p + 1]), pack2(acc[8 * p + 2], acc[8 * p + 3]),
            pack2(acc[8 * p + 4], acc[8 * p + 5]), pack2(acc[8 * p + 6], acc[8 * p + 7]));
      if ((p & 3) == 3) { uint4 r[4]; __syncwarp(); rows_load(r, p < 4 ? t0 : t1, x); rows_store(r, g + (p >> 2) * 8); }
    }
  } else {
    auto pack16 = [&](uint4 (&r)[4], const float* a) {
#pragma unroll
      for (int q = 0; q < 4; q++) { const float* u = a + 16 * (q & 1) + (q & 2); r[q] = make_uint4(pack2(u[0], u[1]), pack2(u[4], u[5]), pack2(u[8], u[9]), pack2(u[12], u[13])); }
    };
    uint4 r0[4];
    pack16(r0, acc);
    img_tag(r0, true, L + 1, x);
    img_store(r0, x.img(XBUF(L + 1), 0));
    const float z = bb_fence(x.goff);
    img_sts(r0, t0, x);
    pack16(r1, acc + 32);
    img_tag(r1, true, L + 1, x);
    img_sts(r1, t1, x);
    float u[4] = {z, z, z, z}, v[4] = {z, z, z, z};
    stats_acc<32>(acc, v);
    stats_acc<32>(acc + 32, u);
#pragma unroll
    for (int q = 0; q < 4; q++) t[q] = u[q] + v[q];
    mbar_wait2(x.fullB(x.rb.s), x.rb.ph, x.fullB(x.rb.s + 1), x.rb.ph);
    fence_async_smem();
    asm volatile("bar.sync %0, %1;" ::"r"(L == 1 ? x.w + 1 : 3), "r"(L == 1 ? 128 : 256) : "memory");
  }
}

struct Stats { float rstd0, rstd1; };
__device__ __forceinline__ Stats load_stats(int half, const Ctx& x) {
  const float2 u = lds64f(x.sb + OFF_MR + half * 256 + (x.warp * 8 + x.g) * 8);
  return {u.x, u.y};
}

template <int NH, int NK, class F>
__device__ __forceinline__ void hedgehog_scale(float* t, const Stats& st, const uint32_t* keep, F use) {
#pragma unroll
  for (int q = 0; q < 16 * NH; q++) t[q] *= ((q & 2) ? st.rstd1 : st.rstd0) * LOG2E;
  use();
  float m[4];
#pragma unroll
  for (int q = 0; q < 4 * NH; q++) {
    const float v = fmaxf(fmaxf(fabsf(t[4 * q]), fabsf(t[4 * q + 1])), fmaxf(fabsf(t[4 * q + 2]), fabsf(t[4 * q + 3])));
    m[q & 3] = q < 4 ? v : fmaxf(m[q & 3], v);
  }
  if (__builtin_expect(__any_sync(0xffffffffu, fmaxf(fmaxf(m[0], m[1]), fmaxf(m[2], m[3])) > 58.f), 0)) {
    float z[16 * NH + NK];
#pragma unroll
    for (int q = 0; q < 16 * NH + NK; q++) z[q] = q < 16 * NH ? t[q % (16 * NH)] : __uint_as_float(keep[q & 15]);
#pragma unroll 1
    for (int r = 0; r < 2 * NH; r++) {
      float hi = -INFINITY, lo = INFINITY;
#pragma unroll 1
      for (int i = 0; i < 16; i++) {
        const int k = (i & 6) * 2 + (i & 1) + (r & 1) * 2 + (r & 2) * 8;
        const float v = z[k];
        if (i < 8) { hi = fmaxf(hi, v); lo = fminf(lo, v); }
        else z[k] = v - fminf(fmaxf(v, lo), hi);
        if (i == 7) {
#pragma unroll 1
          for (int d = 1; d <= 2; d++) { hi = fmaxf(hi, __shfl_xor_sync(0xffffffffu, hi, d)); lo = fminf(lo, __shfl_xor_sync(0xffffffffu, lo, d)); }
          const float mid = 0.5f * hi + 0.5f * lo;
          hi = fmaxf(hi - 58.f, mid); lo = fminf(lo + 58.f, mid);
        }
      }
    }
#pragma unroll
    for (int q = 0; q < 16 * NH; q++) t[q] = z[q];
    use();
  }
}
__device__ __forceinline__ void dual_exp(const float* t, uint32_t (&f)[18], int never) {
  float e[KSPLIT];
#pragma unroll
  for (int q = 0; q < KSPLIT; q++) e[q] = ex2(q < 16 ? t[q] : -t[q & 15]);
  while (never < 0) {
#pragma unroll
    for (int i = 0; i < KSPLIT; i += 4) asm volatile("ld.shared.v4.f32 {%0,%1,%2,%3}, [%4];" : "=f"(e[i]), "=f"(e[i + 1]), "=f"(e[i + 2]), "=f"(e[i + 3]) : "r"(never + i) : "memory");
    never += __float_as_int(e[0]);
  }
#pragma unroll
  for (int q = 0; q < KSPLIT; q += 2) f[q >> 1] = pack2(e[q], e[q + 1]);
#pragma unroll
  for (int q = KSPLIT; q < 32; q += 2) f[q >> 1] = q < 16 ? pack2(ex2(t[q]), ex2(t[q + 1])) : pack2(ex2(-t[q & 15]), ex2(-t[(q & 15) + 1]));
#pragma unroll
  for (int sg = 0; sg < 2; sg++) {
    const uint32_t* u = f + 8 * sg;
    const uint32_t a = add2(add2(u[0], u[2]), add2(u[4], u[6])), b = add2(add2(u[1], u[3]), add2(u[5], u[7]));
    f[16 + sg] = add2(__byte_perm(a, b, 0x5410), __byte_perm(a, b, 0x7632));
  }
}
__device__ __forceinline__ void dual_exp_rcp(const float* t, uint32_t* f) {
#pragma unroll
  for (int q = 0; q < 8; q++) {
    const float a = ex2(t[2 * q]), b = ex2(t[2 * q + 1]), r = rcp(a * b);
    f[q] = pack2(a, b); f[8 + q] = pack2(r * b, r * a);
  }
}
__device__ __forceinline__ void cta_bar() { asm volatile("bar.sync 3, 256;" ::: "memory"); }

template <int N> __device__ __forceinline__ void pin(const uint32_t* v, uint32_t addr) {
#pragma unroll
  for (int i = 0; i < N; i += 4)
    asm volatile("{\n.reg .pred p;\nsetp.eq.u32 p, %0, 0;\n@p st.shared.v4.u32 [%0], {%1,%2,%3,%4};\n}" ::"r"(addr), "r"(v[i]), "r"(v[i + 1]), "r"(v[i + 2]), "r"(v[i + 3]) : "memory");
}

__device__ __forceinline__ void consumer(const Params& P, uint32_t sb, int w, unsigned vb) {
  Ctx x;
  x.w = w;
  x.ab = sb + OFF_A + w * 8192; x.da0 = desc_lo(SB + OFF_A, 16) + w * 512;
  x.lane = threadIdx.x & 31; x.warp = __shfl_sync(0xffffffffu, (threadIdx.x >> 5) & 3, 0); x.g = x.lane >> 2; x.c = x.lane & 3;
  x.goff = (cta_m(vb) * 128 + w) * 128 + cta_j(vb) * 16;
  asm volatile("" : "+r"(x.goff));
  x.elected = (threadIdx.x & 127) == 0;
  x.ra = {0, 0}; x.rb = {0, 0}; x.pa = x.pb = 0;
  {
    const uint32_t row = x.warp * 16 + (x.lane & 15);
    x.mrow = row * 128; x.mxor = row & 7; x.mhi = x.lane >> 4;
  }
  const int goff = x.goff;
  x.ip = solid(&g_img[0][x.m()][2 * x.j()][w * 512 + x.oo()]);
  x.so = solid(16 * x.oo());
  uint4 r1[4];
  float ts[4] = {0.f, 0.f, 0.f, 0.f};
#pragma unroll
  for (int i = 0; i < 4; i++) r1[i] = make_uint4(0, 0, 0, 0);
  TSW(0);
  mbar_wait3(x.fullA(0), 0, x.fullB(0), 0);
#pragma unroll 1
  for (int L = 0; L < 4; L++) {
    float acc[64];
    constexpr uint32_t dcs = desc_lo(SB + OFF_CS, 0);
    if ((L & 1) == 0) {
    float kv[128];
    x.ha = L ? HA64 : HA128; x.k2 = L ? 32 : 4;
    gemm_issue<256, true, false>(kv, x, true); gemm_next<256>(x);
    {
      int i = 1;
#pragma unroll 1
      for (int seg = L ? NS - 1 : 0; seg <= NS; seg++) {
        const int end = seg < NS ? (L == 0 ? 3 + SA * ((x.j() + SW * w) & 3) + SB_ * seg : XA + 1) : 14 + L;
#pragma unroll 1
        do {
          gemm_issue<256, false, false>(kv, x);
          gemm_retire<256>(x, true);
          i++;
          if (i == 5) TSL_(8);
          if (i == 11) TSL_(10);
        } while (i != end);
        if (seg < NS && L == 0) {
          uint32_t v[16];
          float a[32];
#pragma unroll
          for (int q = 0; q < 4; q++) ldsm4(x.maddr(x.aslot(x.pa), 2 * q), reinterpret_cast<uint32_t (&)[4]>(v[4 * q]));
#pragma unroll
          for (int q = 0; q < 16; q++) { a[2 * q] = lo16(v[q]); a[2 * q + 1] = hi16(v[q]); }
          stats_acc<32>(a, ts);
          fence_regs(ts);
          wg_bar(w);
        }
        if (seg == NS - 1) {
          if (L > 0) { img_store(r1, x.img(XBUF(L), 1)); publish(2, x); }
          mbar_wait(sb + BAR_EPOCH, 0);
          stats_send(ts, L, x);
        }
      }
    }
      const Ring kt = x.ra;
      if (L == 0) adv<NA>(x.ra);
#pragma unroll 1
      for (int h = L; h < 2; h++) {
        float d[16];
        mbar_wait2(x.fullA(kt.s), kt.ph, sb + BAR_WPHI, 0);
        wgmma_fence();
#pragma unroll
        for (int q = 0; q < 2; q++) wgmma_ss_n32(d, x.da0 + kt.s * (SLOT / 16) + h * 4 + q * 2, desc_lo(SB + OFF_S + 4096, 512) + w * 256 + h * 128 + q * 64, q);
        wgmma_commit();
        gemm_issue<256, false, false>(kv, x);
        gemm_retire<256>(x, true);
        if (h) x.releaseA(kt.s);
        fence_regs(d);
        uint4* dst = &g_wf[1][x.j()][x.m()][w * 512 + (x.warp * 16 + x.g) * 8 + ((h * 4 + x.c) ^ x.g)];
        dst[0] = make_uint4(pack2(d[0], d[1]), pack2(d[4], d[5]), pack2(d[8], d[9]), pack2(d[12], d[13]));
        dst[64] = make_uint4(pack2(d[2], d[3]), pack2(d[6], d[7]), pack2(d[10], d[11]), pack2(d[14], d[15]));
      }
      const uint32_t dm = desc_lo(SB + OFF_MA, 0) + w * 64;
      mbar_wait2(sb + BAR_STAT, 0, sb + BAR_CS, 0);
      wgmma_fence();
      wgmma_r1_n256(kv, dm, dcs + 96, 1);
      wgmma_commit();
      const Stats st = load_stats(w, x);
      mbar_wait2(x.fullA(x.ra.s), x.ra.ph, x.fullB(x.rb.s), x.rb.ph);
      wgmma_wait<0>();
      fence_regs(kv);
      gemm_release<256>(x, true);
      TSL_(2);
      uint32_t P0[32], P1[32], PH[32];
#pragma unroll
      for (int t = 0; t < 16; t++) { P0[t] = pack2(kv[4 * t] * st.rstd0, kv[4 * t + 1] * st.rstd0); P1[t] = pack2(kv[4 * t + 2] * st.rstd1, kv[4 * t + 3] * st.rstd1); }
      pin<16>(P0, x.mrow + 16);
      {
#pragma unroll
        for (int q = 0; q < 4; q++) sts128((x.warp < 3 ? sb + OFF_T + w * 12288 + x.warp * 4096 : sb + OFF_S + 16384 + w * 2048) + x.lane * 16 + q * 512, P1[4 * q], P1[4 * q + 1], P1[4 * q + 2], P1[4 * q + 3]);
      }
      wgmma_fence();
      wgmma_r1_n128(acc, dm, dcs, 0);
      gemm_issue<128, false, false>(acc, x, true); gemm_next<128>(x);
      TSL_(3);
#pragma unroll
      for (int s = 0; s < 4; s++) {
#pragma unroll
        for (int t = 16 + 8 * (s & 1); t < 24 + 8 * (s & 1); t++) {
          if (s < 2) P1[t] = movm(pack2(kv[4 * t + 2] * st.rstd1, kv[4 * t + 3] * st.rstd1));
          else P0[t] = movm(pack2(kv[4 * t] * st.rstd0, kv[4 * t + 1] * st.rstd0));
        }
        if (s < 3) { gemm_issue<128, false, false>(acc, x); gemm_retire<128>(x, true); }
        if (s == 1) {
          if (x.warp < 3) {
#pragma unroll
            for (int q = 4; q < 8; q++) sts128(sb + OFF_T + w * 12288 + x.warp * 4096 + x.lane * 16 + q * 512, P1[4 * q], P1[4 * q + 1], P1[4 * q + 2], P1[4 * q + 3]);
          } else {
            uint4* dst = &g_halo[x.m()][x.j()][w][x.lane];
#pragma unroll
            for (int q = 0; q < 8; q++) dst[q * 32] = make_uint4(P1[4 * q], P1[4 * q + 1], P1[4 * q + 2], P1[4 * q + 3]);
          }
          publish(3, x);
          gemm_issue<128, false, false>(acc, x);
          gemm_retire<128>(x, true);
        }
      }
      TSL_(4);
      gemm_run<false>(acc, x, 10, 0);
      publish(0, x);
      gemm_issue<128, false, false>(acc, x);
      {
        wg_bar(w);
        uint32_t tr = sb + OFF_T + w * 12288 + (x.warp - 1) * 4096;
        if (x.warp == 0) {
          tr = x.m() > 0 ? sb + OFF_S + 8192 + w * 4096 : tr + 4096;
          if (x.m() > 0) mbar_wait(sb + BAR_HALO, L >> 1);
        }
#pragma unroll
        for (int q = 0; q < 8; q++) lds128(tr + x.lane * 16 + q * 512, PH[4 * q], PH[4 * q + 1], PH[4 * q + 2], PH[4 * q + 3]);
      }
      gemm_retire<128>(x, false);
      gemm_end(acc, x);
      TSL_(5);
      const bool first = (x.m() == 0) && (x.warp == 0);
      const bool hi0 = 2 * x.c > x.g, hi1 = 2 * x.c + 1 > x.g;
      const uint32_t mhi = (hi0 ? 0xFFFFu : 0u) | (hi1 ? 0xFFFF0000u : 0u);
      const uint32_t valid = first ? ~mhi : ~0u;
      const float sc0 = st.rstd0 * (0.17677669529663687f * LOG2E), sc1 = st.rstd1 * (0.17677669529663687f * LOG2E);
      uint32_t xr[2][16];
#pragma unroll
      for (int hp = 0; hp < 2; hp++) {
        const uint32_t tile = x.aslot(x.held(hp));
        uint32_t px[2], py[2];
        float s[2][3][4];
#pragma unroll
        for (int u = 0; u < 2; u++) {
#pragma unroll
          for (int q = 0; q < 12; q++) s[u][q >> 2][q & 3] = 0.f;
#pragma unroll
          for (int ks = 0; ks < 2; ks++) {
            const int t = 8 * hp + 4 * u + 2 * ks;
            const uint32_t a0 = pack2(acc[4 * t], acc[4 * t + 1]), a1 = pack2(acc[4 * t + 2], acc[4 * t + 3]);
            const uint32_t a2 = pack2(acc[4 * t + 4], acc[4 * t + 5]), a3 = pack2(acc[4 * t + 6], acc[4 * t + 7]);
            mma16816(s[u][0], a0, a1, a2, a3, PH[t], PH[t + 1]);
            mma16816(s[u][1], a0, a1, a2, a3, P0[t], P0[t + 1]);
            mma16816(s[u][2], a0, a1, a2, a3, P1[t], P1[t + 1]);
          }
        }
        float e[2][4], big = 0.f;
#pragma unroll
        for (int u = 0; u < 2; u++) {
          e[u][0] = (hi0 ? s[u][0][0] : s[u][1][0]) * sc0; e[u][1] = (hi1 ? s[u][0][1] : s[u][1][1]) * sc0;
          e[u][2] = (hi0 ? s[u][1][2] : s[u][2][2]) * sc1; e[u][3] = (hi1 ? s[u][1][3] : s[u][2][3]) * sc1;
          big = fmaxf(big, fmaxf(fmaxf(fabsf(e[u][0]), fabsf(e[u][1])), fmaxf(fabsf(e[u][2]), fabsf(e[u][3]))));
          px[u] = pack2(ex2(e[u][0]), ex2(e[u][1])) & valid; py[u] = pack2(ex2(e[u][2]), ex2(e[u][3]));
        }
        if (__builtin_expect(__any_sync(0xffffffffu, big > 58.f), 0)) {
#pragma unroll
          for (int q = 0; q < 4; q++) {
            float v0 = e[q >> 1][2 * (q & 1)], v1 = e[q >> 1][2 * (q & 1) + 1];
            if (first && !(q & 1)) { if (hi0) v0 = -INFINITY; if (hi1) v1 = -INFINITY; }
            float r = fmaxf(v0, v1);
            r = fmaxf(r, __shfl_xor_sync(0xffffffffu, r, 1)); r = fmaxf(r, __shfl_xor_sync(0xffffffffu, r, 2));
            ((q & 1) ? py : px)[q >> 1] = pack2(ex2(v0 - r), ex2(v1 - r));
          }
        }
        float r[2][2];
#pragma unroll
        for (int u = 0; u < 2; u++) {
          float d[4] = {0.f, 0.f, 0.f, 0.f};
          mma1688(d, px[u], py[u], 0x3F803F80u);
          r[u][0] = rcp(d[0]); r[u][1] = rcp(d[2]);
        }
        uint32_t o[8][2];
        uint4 ro[4];
#pragma unroll
        for (int q = 0; q < 8; q++) {
          float d[4] = {0.f, 0.f, 0.f, 0.f};
          const int t = 16 + 8 * hp + q, u = q >> 2;
          mma16816(d, px[u] & mhi, 0u, px[u] & ~mhi, py[u] & mhi, PH[t], P0[t]);
          mma1688(d, 0u, py[u] & ~mhi, P1[t]);
          o[q][0] = pack2(d[0] * r[u][0], d[1] * r[u][0]); o[q][1] = pack2(d[2] * r[u][1], d[3] * r[u][1]);
        }
#pragma unroll
        for (int q = 0; q < 4; q++) ro[q] = make_uint4(o[4 * (q & 1)][q >> 1], o[4 * (q & 1) + 1][q >> 1], o[4 * (q & 1) + 2][q >> 1], o[4 * (q & 1) + 3][q >> 1]);
        img_tag(ro, false, 0, x);
        img_store(ro, x.img(0, hp));
        if (hp == 0) bb_fence(x.goff);
        if (hp == 0) {
#pragma unroll
          for (int i = 0; i < 2; i++) {
            const uint32_t ti = x.aslot(x.held(i));
            if (L) img_load(xr[i], ti, x);
            else {
#pragma unroll
              for (int q = 0; q < 4; q++) ldsm4(x.maddr(ti, 2 * q), reinterpret_cast<uint32_t (&)[4]>(xr[i][4 * q]));
            }
          }
          __syncwarp();
        }
        img_sts(ro, tile, x);
      }
      if (L == 0) {
#pragma unroll
        for (int hp = 0; hp < 2; hp++) {
          uint32_t v[16];
#pragma unroll
          for (int q = 0; q < 16; q++) asm volatile("mov.b32 %0, %1;" : "=r"(v[(q & 1) * 8 + (q >> 1)]) : "r"(xr[hp][q]));
#pragma unroll
          for (int q = 0; q < 16; q++) xr[hp][q] = v[q];
        }
      }
      img_unpack(acc, xr[0]); img_unpack(acc + 32, xr[1]);
    } else {
      float kv[128];
      float (&kv0)[64] = reinterpret_cast<float (&)[64]>(kv[0]);
      float (&kv1)[64] = reinterpret_cast<float (&)[64]>(kv[64]);
      auto mma8 = [&](uint32_t as, uint32_t bs, int i, bool fence) {
        const uint32_t da = desc_lo(SB + OFF_A, 16) + as * (SLOT / 16), db = desc_lo(SB + OFF_B, 8192) + bs * (SLOT / 16);
        if (fence) wgmma_fence();
#pragma unroll
        for (int k = 0; k < 4; k++) {
          wgmma_ss_n128(kv0, da + (k >> 1) * 32 + (k & 1) * 2, HA64, db + 128 * k, i + k);
          wgmma_ss_n128(kv1, da + 512 + (k >> 1) * 32 + (k & 1) * 2, HA64, db + 128 * k, i + k);
        }
        wgmma_commit();
      };
      constexpr uint32_t dm = desc_lo(SB + OFF_MB, 0);
      auto relB = [&](uint32_t s) { mbar_arrive_n(sb + BAR_EMPTYB + s * 8, 2); };
      auto skip = [&]() {
#pragma unroll
        for (int q = 0; q < 6 - NJ; q++) adv<NA>(x.ra);
        x.rb.s = w ? (2 + NJ) % 6 : 4;
        if (!w && NJ < 4) x.rb.ph ^= 1;
      };
      static_assert(NA == 5 && NB == 6, "ring arithmetic");
      mma8(x.ra.s, x.rb.s + w, 0, true);
      img_store(r1, x.img(XBUF(L), 1));
      gemm_next<256>(x);
#pragma unroll 1
      for (int i = 1; i < NJ; i++) {
        mbar_wait2(x.fullA(x.ra.s), x.ra.ph, x.fullB(x.rb.s + w), x.rb.ph);
        mma8(x.ra.s, x.rb.s + w, 1, true);
        if (i == 1) { stats_send(ts, L, x); publish(2, x); }
        wgmma_wait<1>();
        if (x.elected) { x.releaseA(x.pa); relB(x.pb + w); }
        gemm_next<256>(x);
      }
      if (w) {
        wgmma_wait<0>();
        if (x.elected) { x.releaseA(x.pa); relB(x.pb + 1); }
        skip();
        asm volatile("bar.sync 7, 256;" ::: "memory");
      }
      TSL_(8);
      {
        const int t = lane_id() + 32 * x.warp;
        uint32_t mask = t < 2 ? ((w ? (t ? 0xFF3Fu : 0x3FFFu) : 0xFFFFu) >> (NJ - 1)) & (w ? ~1u : ~0u) : 0u, cnt = 1 + t;
        bool ready = false;
#pragma unroll 1
        for (int i = NJ; i < 16; i++) {
          if (!ready) mbar_wait2(x.fullA(x.ra.s), x.ra.ph, x.fullB(x.rb.s), x.rb.ph);
          mma8(x.ra.s, x.rb.s, 1, true);
          const uint32_t bar = sb + (t ? BAR_EMPTYB + x.pb * 8 : BAR_EMPTYA + x.pa * 8);
          gemm_next<128>(x);
          if (w && (i | 4) == 15) x.rb.s = 4;
          ready = mbar_probe2(x.fullA(x.ra.s), x.ra.ph, x.fullB(x.rb.s), x.rb.ph);
          wgmma_wait<1>();
          if (mask & 1) mbar_arrive_n(bar, cnt);
          mask >>= 1; cnt = 2;
          if (i == 8 && w) asm volatile("bar.arrive 9, 256;" ::: "memory");
          if (i == 9) TSL_(10);
        }
        mbar_wait2(sb + BAR_STAT, 1, sb + BAR_CS + 8, 0);
        wgmma_fence();
        wgmma_r1_n128(kv0, dm, dcs + 96 + 96 * w, 1);
        wgmma_r1_n128(kv1, dm + 64, dcs + 96 + 96 * w, 1);
        wgmma_commit();
        if (w == 0) asm volatile("bar.arrive 7, 256;" ::: "memory");
        wgmma_wait<1>();
        if (mask & 1) mbar_arrive_n(sb + (t ? BAR_EMPTYB + x.pb * 8 : BAR_EMPTYA + x.pa * 8), 2);
      }
      const Stats s0 = load_stats(0, x), s1 = load_stats(1, x), st = w ? s1 : s0;
      if (w == 0) skip();
      const uint32_t h0 = x.held(0), h1 = x.held(1);
      auto vreg = [&](int ks) { return ks < 6 ? OFF_A + (ks < 3 ? h0 * SLOT : h1 * SLOT - 15360) + ks * 5120 : OFF_S + 2048 + ks * 5120; };
      uint32_t tV[2], uu[4];
#pragma unroll
      for (int hf = 0; hf < 2; hf++) {
        tV[hf] = sb + vreg(4 * hf + x.warp) + ((x.lane >> 3) & 1) * 2560 + (x.lane & 7) * 16 + x.mhi * 128;
        const float i0 = rcp(hf ? s1.rstd0 : s0.rstd0), i1 = rcp(hf ? s1.rstd1 : s0.rstd1);
        const uint32_t h = pack2(i0, i1);
        uu[2 * hf] = pack2(lo16(h), i0 - lo16(h)); uu[2 * hf + 1] = pack2(hi16(h), i1 - hi16(h));
        asm volatile("" : "+r"(tV[hf]), "+r"(uu[2 * hf]), "+r"(uu[2 * hf + 1])::"memory");
      }
      wgmma_wait<0>();
      fence_regs(kv);
      TSL_(2);
      if (w == 0) {
        uint32_t f[2][18], ad[4];
#pragma unroll
        for (int q = 0; q < 18; q++) f[1][q] = 0u;
#pragma unroll
        for (int q = 0; q < 4; q++) ad[q] = x.maddr(sb + OFF_S, 2 * q);
        auto norm = [&](int un) {
          uint32_t* u = f[un & 1];
          const Stats& sn = un ? s1 : s0;
#pragma unroll
          for (int sg = 0; sg < 2; sg++) {
            uint32_t v = u[16 + sg];
            v = add2(v, __shfl_xor_sync(0xffffffffu, v, 1)); v = add2(v, __shfl_xor_sync(0xffffffffu, v, 2));
            const float a = rcp(lo16(v)) * sn.rstd0, b = rcp(hi16(v)) * sn.rstd1;
            const uint32_t r0 = pack2(a, a), r1_ = pack2(b, b);
#pragma unroll
            for (int q = 8 * sg; q < 8 * sg + 8; q++) u[q] = mul2(u[q], (q & 1) ? r1_ : r0);
#pragma unroll
            for (int q = 2 * sg; q < 2 * sg + 2; q++) stsm4(ad[q] + un * 8192, u[4 * q], u[4 * q + 1], u[4 * q + 2], u[4 * q + 3]);
          }
        };
        auto move = [&](int dst, int src) {
#pragma unroll
          for (int q = 0; q < 16; q++) asm volatile("mov.b32 %0, %1;" : "=f"(kv[dst + q]) : "f"(src ? kv[src + q] : 0.f));
        };
        hedgehog_scale<1, 0>(kv, s0, nullptr, [] {});
        uint32_t step = 0;
#pragma unroll 1
        for (int h = 0;; h++) {
          norm(1);
          dual_exp(kv, f[0], x.goff);
          hedgehog_scale<1, KEEP>(kv + 64, s1, f[1], [] {});
          if (h == 2) asm volatile("bar.sync 9, 256;" ::: "memory");
#pragma unroll
          for (int q = 0; q < 4; q++) ad[q] += step;
          norm(0);
          dual_exp(kv + 64, f[1], x.goff);
#pragma unroll
          for (int q = 0; q < 16; q++) kv[q] = kv[16 + q];
          hedgehog_scale<1, KEEP>(kv, s0, f[0], [] {});
          step = SLOT;
          if (h == 0) { move(64, 80); move(16, 32); }
          else if (h == 1) { move(64, 96); move(16, 48); step = OFF_B + SLOT - OFF_S; }
          else if (h == 2) { move(64, 112); move(16, 0); }
          else break;
        }
        norm(1);
        TSL_(3);
      } else {
        wg_bar(w);
#pragma unroll
        for (int hf = 0; hf < 2; hf++) {
          stsm4(tV[hf] + 512 + x.mhi * 512, uu[2 * hf], uu[2 * hf + 1], uu[2 * hf], uu[2 * hf + 1]);
          stsm4(tV[hf] + 1792 + x.mhi * 512, uu[2 * hf], uu[2 * hf + 1], uu[2 * hf], uu[2 * hf + 1]);
#pragma unroll
          for (int q = 0; q < 8; q++) {
            const float* u = kv + 64 * hf + 8 * q;
            stsm4(tV[hf] + (q >> 1) * 640 + (q & 1) * 256, pack2(u[0], u[1]), pack2(u[2], u[3]), pack2(u[4], u[5]), pack2(u[6], u[7]));
          }
        }
        TSL_(3);
      }
      {
        float d[2][20];
        uint4* dst = &g_kvpart[x.j()][w * 4 + x.warp][0][x.m() * 32 + x.lane];
        unsigned* dz = reinterpret_cast<unsigned*>(&g_kvpart[x.j()][w * 4 + x.warp][x.c & 1][512]) + x.m() * 8 + x.g;
        fence_async_smem();
        cta_bar();
        TSL_(11);
        uint32_t pk[9];
        auto prep = [&](float (&u)[20]) {
          fence_regs(u);
#pragma unroll
          for (int q = 0; q < 8; q++) pk[q] = pack2(u[((q >> 1) & 2) + 4 * (q & 3)], u[((q >> 1) & 2) + 4 * (q & 3) + 1]);
          pk[8] = __float_as_uint((x.c & 1) ? u[18] + u[19] : u[16] + u[17]);
#pragma unroll
          for (int q = 0; q < 9; q += 4) pk[q] = (pk[q] & ~1u) | (L == 1);
        };
        auto send = [&](int hp) {
          st_v4(dst + hp * 16 * 544, pk[0], pk[1], pk[2], pk[3]); st_v4(dst + (hp * 16 + 1) * 544, pk[4], pk[5], pk[6], pk[7]);
          st_flag(dz + hp * 16 * 544 * 4, pk[8]);
        };
        wgmma_fence();
#pragma unroll
        for (int q = 0; q < 17; q++) {
          if (q < 16) wgmma_ss_n40_tt(d[q >> 3], desc_lo(SB + (q < 8 ? OFF_S : OFF_B + 2 * SLOT), 1024) + w * (SLOT / 16) + 128 * (q & 7), desc_lo(SB + vreg(q & 7), 2560) + (w + (q >> 3) * 2) * 40, q & 7);
          else wgmma_r1_n128(acc, dm + w * 64, dcs, 0);
          if (q == 7 || q == KVS || q == 16) wgmma_commit();
          if (q == KVS) { mbar_wait2(x.fullA(x.ra.s), x.ra.ph, x.fullB(x.rb.s), x.rb.ph); wgmma_wait<1>(); prep(d[0]); send(0); bb_fence(x.goff); wgmma_fence(); }
        }
        gemm_issue<128, false>(acc, x, true); gemm_next<128>(x);
        wgmma_wait<1>();
        x.releaseA(h0); x.releaseA(h1); x.releaseB(2); x.releaseB(3);
        if (x.lane == 0) mbar_arrive(sb + BAR_SIGT);
        prep(d[1]);
        TSL_(4);
#pragma unroll 1
        for (int seg = 0; seg < 2; seg++) {
          const int n0 = w ? PS1 : PS0;
          gemm_run(acc, x, seg ? 15 - n0 : n0, seg, seg ? L : 0);
          if (seg == 0) send(1);
        }
      }
      gemm_end(acc, x);
      TSL_(5);
      {
        float dp[2][20], dn[2][20];
        uint32_t f[4][16];
        auto mma = [&](int h) {
          if (!(h & 1)) mbar_wait(sb + BAR_KV + h * 4, L >> 1);
          if (h == 0) TSL_(9);
          const uint32_t db = desc_lo(SB + OFF_S + h * 5120, 128);
          const uint32_t (&a)[16] = f[h];
          wgmma_fence();
          wgmma_rs_n40(dp[h & 1], a[0], a[1], a[2], a[3], db, 0);
          wgmma_rs_n40(dn[h & 1], a[8], a[9], a[10], a[11], db + 160, 0);
          wgmma_rs_n40(dp[h & 1], a[4], a[5], a[6], a[7], db + 80, 1);
          wgmma_rs_n40(dn[h & 1], a[12], a[13], a[14], a[15], db + 240, 1);
          wgmma_commit();
        };
        uint32_t xr[16];
        auto fin = [&](int h) {
          const uint32_t tile = x.aslot(x.held(h >> 1));
          if (!(h & 1)) img_load(xr, tile, x);
          float (&u)[20] = dp[h & 1];
          float (&v)[20] = dn[h & 1];
          fence_regs(u); fence_regs(v);
#pragma unroll
          for (int r = 0; r < 2; r++) {
            const float sp = u[16 + 2 * r], sn = v[16 + 2 * r];
            const float id = rcp(fmaf(fmaf(sp, L == 1 ? 0.065536f * 128 / 129 : 0.065536f, u[17 + 2 * r]), sn, v[17 + 2 * r] * sp)), aa = sn * id, cc = sp * id;
            uint32_t o[4];
#pragma unroll
            for (int t = 0; t < 4; t++) o[t] = pack2(fmaf(u[4 * t + 2 * r], aa, v[4 * t + 2 * r] * cc), fmaf(u[4 * t + 2 * r + 1], aa, v[4 * t + 2 * r + 1] * cc));
            o[2 * r + (h & 1)] = img_tag(o[2 * r + (h & 1)], false, 1, x);
            stg128(x.img(0, h >> 1) + r * 64 + (h & 1) * 32, make_uint4(o[0], o[1], o[2], o[3]));
            sts128(tile + r * 1024 + (h & 1) * 512 + x.so, o[0], o[1], o[2], o[3]);
          }
          if (h & 1) { if (h == 1) publish(0, x); img_unpack(acc + 16 * (h - 1), xr); }
        };
        auto ex = [&](int h) { dual_exp_rcp(acc + 16 * h, f[h]); };
        Stats sq = st;
#pragma unroll
        for (int h = 0; h < 4; h += 2) {
          hedgehog_scale<2, 0>(acc + 16 * h, sq, nullptr, [&] { ex(h); });
          mma(h);
          ex(h + 1); wgmma_wait<0>(); fin(h);
          if (h == 0) bb_fence(x.goff);
          mma(h + 1);
          wgmma_wait<0>(); fin(h + 1);
          if (h == 0) sq.rstd1 += bb_fence(x.goff);
        }
      }
    }
    mbar_wait(x.fullB(x.rb.s), x.rb.ph);
    fence_regs(acc);
    fence_async_smem();
    wg_bar(w);
    TSL_(6);
    rewind2<NA>(x.ra);
    gemm_issue<128, false>(acc, x, true); gemm_next<128>(x);
    uint4* out = solid(P.out + goff + (x.warp * 16 + (x.lane >> 3)) * 256 + (x.lane & 7));
#pragma unroll 1
    for (int seg = 0; seg < 2; seg++) {
      const int nt = L == 3 ? TSK : XN;
      gemm_run(acc, x, seg ? nt : 15 - nt, seg, 10 + L);
      if (L < 3) { if (seg == 0) publish(1, x); }
      else if (seg != w) {
        if (w) asm volatile("bar.sync 6, 256;" ::: "memory"); else asm volatile("bar.arrive 6, 256;" ::: "memory");
      }
    }
    gemm_end(acc, x);
    TSL_(7);
    rewind2<NA>(x.ra);
    out_epilogue(acc, r1, ts, out, L, x);
    TSL_(13);
  }
}

typedef unsigned long long u64;
template <class T> __device__ __forceinline__ T* early(T* p) { return (T*)__shfl_xor_sync(0xffffffffu, (u64)p, 1); }
__device__ __forceinline__ void pause(uint32_t GAP) {
  if (GAP) { uint32_t t0, t; asm volatile("mov.u32 %0, %%clock;" : "=r"(t0)); do { asm volatile("mov.u32 %0, %%clock;" : "=r"(t)); } while (t - t0 < GAP); }
}
__device__ __forceinline__ u64 order_table0(int j) { return (j & 4) ? 0x543210FEDCBA9876ull : 0xDCBA9876543210FEull; }
__device__ __forceinline__ void order_tables(u64& t1, u64& t2, int j) {
#pragma unroll 1
  for (int i = 6; i >= 0; i--) { const u64 o = 2 * other_tile(i, j); t1 = t1 << 4 | o | (o + 1) << 28; t2 = t2 << 8 | (o * 17 + 16); }
  const u64 own = 2 * j * 17 + 16;
  t1 = t1 << 8 | own; t2 |= own << 56;
}

__device__ __forceinline__ void b_producer(const Params& P, uint32_t sb, unsigned vb) {
  const int j = cta_j(vb);
  u64 t1 = 0, t2 = 0;
  Ring r = {PRE_B % NB, PRE_B < NB};
#pragma unroll 1
  for (int sg = 0; sg < 20; sg++) {
    const int L = sg / 5, p = sg - 5 * L, wt = L & 1;
    if (sg == 1) order_tables(t1, t2, j);
    int n = p >= 3 ? 16 : (wt ? (p ? 16 - NJ : 2 * NJ) : (p ? 0 : (L ? 32 : 32 - PRE_B)));
    u64 tab = p == 3 ? t2 : (sg == 0 ? order_table0(j) >> (2 * PRE_B) : (p == 1 || p == 2 ? t1 >> (4 * NJ) : t1));
    const CUtensorMap* tm = p == 4 ? &P.mwo[wt] : &P.mw[wt ? 1 : L];
    const uint4* img = &g_wf[p != 3][j][0][0];
    int col = (p >= 3 ? 0 : (p == 2 ? 2048 : 1024)) + 128 * j;
    const int flip = p == 0 ? 3072 : 0;
    const bool fold = wt && p != 4;
    if (sg == 5 || sg == 8) { mbar_wait(sb + (sg == 5 ? BAR_WPHI : BAR_CS + 8), sg == 5); fence_async_global(); }
    if (DEFER && p == 4 && ((DEFL >> wt) & 1)) {
      Ring q = r;
      for (int u = 0; u < DEFER; u++) adv<NB>(q);
      mbar_wait(sb + BAR_EMPTYB + q.s * 8, q.ph);
    }
#pragma unroll 1
    for (; n > 0; n--) {
      const int kb = (int)tab & 15;
      mbar_wait(sb + BAR_EMPTYB + r.s * 8, r.ph);
      if (elect()) {
        mbar_expect_tx(sb + BAR_FULLB + r.s * 8, SLOT);
        if (fold && col < 2048) bulk_load(sb + OFF_B + r.s * SLOT, img + kb * 1024, SLOT, sb + BAR_FULLB + r.s * 8);
        else tma_load_w(sb + OFF_B + r.s * SLOT, tm, sb + BAR_FULLB + r.s * 8, col, kb);
      }
      adv<NB>(r);
      if (p == 2 && (n | 4) == 5) r.s = 4;
      col ^= flip;
      if (!(col & flip & 2048)) tab >>= 4;
    }
  }
}

__device__ __forceinline__ void kv_image(uint32_t sb, int h, int L, int j, unsigned tag, uint32_t bar, unsigned& ph) {
  poll_flags(&g_jflag[h][j][0], 16, 0xFFFFu, tag * 4 + L);
  TS(4, h ? 14 + L : 26 + L);
  for (int it = 0;; it++) {
    if (elect()) { mbar_expect_tx(bar, 10240); bulk_load(sb + OFF_S + h * 10240, &g_kvfin[j][8 * h][0], 10240, bar); }
    mbar_wait(bar, ph);
    ph ^= 1;
    uint32_t a = 1u, o = 0u;
#pragma unroll
    for (int u = 0; u < 20; u++) { const uint32_t v = __float_as_uint(lds32f(sb + OFF_S + h * 10240 + u * 512 + (threadIdx.x & 31) * 16)); a &= v; o |= v; }
    if (__all_sync(0xffffffffu, (L == 1 ? a : ~o) & 1u)) break;
    fence_async_smem();
    if (it > (1 << 16)) __trap();
  }
  if (elect()) mbar_arrive(sb + BAR_KV + h * 8);
  TS(4, h ? 30 + L : (L == 1 ? 20 : 25));
}

__device__ __forceinline__ void a_loader(const Params& P, uint32_t sb, unsigned vb) {
  const int j = cta_j(vb), m = cta_m(vb);
  u64 t1 = 0, t2 = 0;
  Ring r = {PRE_A % NA, PRE_A < NA};
  {
    u64 tab = order_table0(j) >> (4 * PRE_A);
#pragma unroll 1
    for (int i = PRE_A; i < 33; i++) {
      if (i == 17) { order_tables(t1, t2, j); tab = t2; }
      mbar_wait(sb + BAR_EMPTYA + r.s * 8, r.ph);
      if (elect()) {
        mbar_expect_tx(sb + BAR_FULLA + r.s * 8, SLOT);
        if (i != 14) tma_load_3d(sb + OFF_A + r.s * SLOT, &P.mx, sb + BAR_FULLA + r.s * 8, ((int)tab & 15) * 64, m * 64, 0);
        else {
          tma_load_w(sb + OFF_A + r.s * SLOT, &P.mw[1], sb + BAR_FULLA + r.s * 8, 1024 + 128 * j, m);
          mbar_expect_tx(sb + BAR_WPHI, 8192); tma_load_2d(sb + OFF_S + 4096, &P.mwphi, sb + BAR_WPHI, 0, 128 * j);
        }
        if (i == PF1 || i == PF2) tma_prefetch_w(&P.mwo[i == PF2], 128 * j, m);
      }
      adv<NA>(r);
      if (i != 14) tab >>= 4;
    }
  }
  const unsigned tag = get_tag(sb);
  unsigned kph = 0;
#pragma unroll 1
  for (int sg = 0; sg < 13; sg++) {
    const int L = sg >> 2, p = sg & 3;
    if (p == 0 && (L & 1)) {
#pragma unroll 1
      for (int h = 0; h < 2; h++) kv_image(sb, h, L, j, tag, sb + BAR_STAT + 8, kph);
    }
    int n = p < 2 ? 14 : (p == 2 ? ((L & 1) ? 0 : 16 - NJ) : 16);
    u64 tab = p == 3 ? t2 : t1 >> (p < 2 ? 8 : 4 * NJ);
    const uint4* img = &g_img[p ? XBUF(L + 1) : 0][m][0][0];
#pragma unroll 1
    for (; n > 0; n--) {
      const uint4* src = early(img + ((int)tab & 15) * 1024);
      const uint32_t bar = sb + (p < 2 ? BAR_LAND : BAR_FULLA) + r.s * 8;
      mbar_wait(sb + BAR_EMPTYA + r.s * 8, r.ph);
      if (elect()) mbar_expect_tx(bar, SLOT);
      if (p < 2 && n == 14) {
        const int lane = threadIdx.x & 31;
        const unsigned* f = &g_hint[(m & 14) + ((lane >> 3) & 1)][(~j & 4) ^ (lane & ND0)];
        mbar_wait(sb + BAR_SIGP + p * 8, L & 1);
        int it = 0;
        while (!__all_sync(0xffffffffu, (int)(ld_flag(f) - (tag * 16 + 4 * L + 1 + p)) >= 0)) { if (++it > (1 << 22)) __trap(); }
        pause(p ? (L ? PAX : PX0) : ((L & 1) ? 0 : (L ? PAA : PA0)));
        TS(2, p == 0 ? 5 + L * 8 : 9 + L * 8);
        TSH((2 * L + p) * 8 + 2);
      }
      if (elect()) bulk_load(sb + OFF_A + r.s * SLOT, src, SLOT, bar);
      adv<NA>(r);
      tab >>= 4;
      pause(p < 2 && n > 10 ? G0 : 0);
    }
  }
}

template <int KB, int G>
__device__ __forceinline__ uint2 sum_packets(float (&a)[8], uint32_t addr, int n) {
  uint2 ok = make_uint2(~0u, 0u);
#pragma unroll 1
  for (int b = 0; b < n; b += KB) {
    uint4 v[KB];
#pragma unroll
    for (int u = 0; u < KB; u++) lds128(addr + (b + u) * 512, v[u].x, v[u].y, v[u].z, v[u].w);
#pragma unroll
    for (int u = 0; u < KB; u++) { ok.x &= v[u].x; ok.y |= v[u].x; }
#pragma unroll
    for (int d = 1; d < G; d *= 2)
#pragma unroll
      for (int u = 0; u < KB; u += 2 * d) v[u] = make_uint4(add2(v[u].x, v[u + d].x), add2(v[u].y, v[u + d].y), add2(v[u].z, v[u + d].z), add2(v[u].w, v[u + d].w));
#pragma unroll
    for (int u = 0; u < KB; u += G) {
      a[0] += lo16(v[u].x); a[1] += hi16(v[u].x); a[2] += lo16(v[u].y); a[3] += hi16(v[u].y);
      a[4] += lo16(v[u].z); a[5] += hi16(v[u].z); a[6] += lo16(v[u].w); a[7] += hi16(v[u].w);
    }
  }
  return ok;
}
__device__ __forceinline__ void helper_bar() { asm volatile("bar.sync 4, 64;" ::: "memory"); }
__device__ __forceinline__ void helper(const Params& P, uint32_t sb, int w, unsigned vb) {
  const int j = cta_j(vb), m = cta_m(vb);
  if (w == 0) {
    if (elect()) {
      const unsigned t = atomicAdd(&g_ctr, 1u) / NCTA + 1u;
      asm volatile("st.shared.u32 [%0], %1;" ::"r"(sb + OFF_EPOCH), "r"(t) : "memory");
      mbar_arrive(sb + BAR_EPOCH);
    }
  }
  const unsigned tag = get_tag(sb);
  mbar_wait(sb + BAR_FULLB + 24, 0);
  const uint32_t stg = sb + OFF_T + w * 12288, stb = sb + BAR_STG + w * 24;
  Ring rs = {0, 0};
  uint32_t vs = 33 % NA, vph = 0;
  auto cs_image = [&](int L) {
      const int lane = lane_id();
      poll_flags(&g_jflag[2 * L][j][0], 16, L ? CSNEED : 0xFFFu, tag * 4);
#pragma unroll
      for (int p = 0; p < 3; p++) {
        const uint4 u = ldcg4(&g_cs[L][0][p * 1024 + 128 * j + lane * 4]), v = ldcg4(&g_cs[L][1][p * 1024 + 128 * j + lane * 4]);
        const float c0 = __uint_as_float(u.x) + __uint_as_float(v.x), c1 = __uint_as_float(u.y) + __uint_as_float(v.y);
        const float c2 = __uint_as_float(u.z) + __uint_as_float(v.z), c3 = __uint_as_float(u.w) + __uint_as_float(v.w);
        const uint32_t h0 = pack2(c0, c1), h1 = pack2(c2, c3), dst = sb + OFF_CS + (p * 16 + (lane >> 1)) * 96 + L * 48 + (lane & 1) * 8;
        sts64(dst, h0, h1); sts64(dst + 16, pack2(c0 - lo16(h0), c1 - hi16(h0)), pack2(c2 - lo16(h1), c3 - hi16(h1))); sts64(dst + 32, h0, h1);
        if (L == 0) { sts64(dst + 48, 0u, 0u); sts64(dst + 64, 0u, 0u); sts64(dst + 80, 0u, 0u); }
      }
      if (L == 0 && lane < 4) sts64(sb + OFF_CS + 4608 + lane * 8, 0u, 0u);
      fence_async_smem();
      __syncwarp();
      if (elect()) mbar_arrive(sb + BAR_CS + L * 8);
      TS(4, 2 + L * 2);
  };
#pragma unroll 1
  for (int L = 0; L < 4; L++) {
    const int lane = lane_id();
    if (L == 0) {
      {
        const int wt = m >= 12, col = ((0x2021 >> (m & 12)) & 3) * 1024 + 128 * j + (m & 3) * 32;
        const CUtensorMap* tm = &P.mcs[wt];
        if (wt) __nanosleep(D2);
        constexpr int nb = 8;
        float a[8] = {0.f, 0.f, 0.f, 0.f, 0.f, 0.f, 0.f, 0.f};
#pragma unroll 1
        for (int b = -3; b < nb; b++) {
          if (b >= 0) {
            mbar_wait(stb + rs.s * 8, rs.ph);
            sum_packets<KC, 1>(a, stg + rs.s * 4096 + lane * 16, 8);
            fence_async_smem();
            __syncwarp();
          }
          const uint32_t sl = b < 0 ? (rs.s + b + 3) % 3 : rs.s;
          if (b + 3 < nb && elect()) { mbar_expect_tx(stb + sl * 8, 4096); tma_load_2d(stg + sl * 4096, tm, stb + sl * 8, col, (w * (16 - nb) + b + 3) * 64); }
          if (b >= 0) adv<3>(rs); else pause(CP);
        }
#pragma unroll 1
        for (int d = 4; d < 32; d *= 2)
#pragma unroll
          for (int u = 0; u < 8; u++) a[u] += __shfl_xor_sync(0xffffffffu, a[u], d);
        if (lane < 4) {
          float4* dst = reinterpret_cast<float4*>(&g_cs[wt][w][col + lane * 8]);
          dst[0] = make_float4(a[0], a[1], a[2], a[3]); dst[1] = make_float4(a[4], a[5], a[6], a[7]);
        }
        helper_bar();
        if (w == 0 && elect()) { fence_gpu(); st_flag(&g_jflag[2 * wt][j][m], tag * 4); }
      }
      if (w == 0) TS(4, 1 + L * 2);
    }
    if (L > 0 && w == 0) {
      mbar_wait(sb + BAR_SIGP + 16, (L - 1) & 1);
      fence_async_global();
      __nanosleep(CO && L == 1 ? SE : SD);
    }
    if (CO && L < 2 && w == 0) cs_image(L);
    if (w == (L == 0)) {
      if (L == 0) { mbar_wait(sb + BAR_WPHI, 0); __nanosleep(S0); }
#pragma unroll 1
      for (int p = 0; p < 2; p++) {
        uint4 v[8];
        for (int it = 0;; it++) {
          bool ok = true;
#pragma unroll
          for (int t = 0; t < 8; t++) v[t] = ld_pkt(&g_stats[m][p][t][lane]);
#pragma unroll
          for (int t = 0; t < 8; t++) ok = ok && (v[t].w & 15u) == seq4(tag, L);
          if (__all_sync(0xffffffffu, ok)) break;
          __nanosleep(200);
          if (it > (1 << 20)) __trap();
        }
        float s0 = 0.f, q0 = 0.f, s1 = 0.f, q1 = 0.f;
#pragma unroll
        for (int t = 0; t < 8; t++) { s0 += __uint_as_float(v[t].x); q0 += __uint_as_float(v[t].y); s1 += __uint_as_float(v[t].z); q1 += __uint_as_float(v[t].w & ~15u); }
        s0 *= (1.f / 1024); s1 *= (1.f / 1024);
        sts64(sb + OFF_MR + p * 256 + lane * 8, __float_as_uint(rsqrtf(fmaxf(q0 * (1.f / 1024) - s0 * s0, 0.f) + 1e-5f)),
              __float_as_uint(rsqrtf(fmaxf(q1 * (1.f / 1024) - s1 * s1, 0.f) + 1e-5f)));
#pragma unroll
        for (int r = 0; r < 2; r++) {
          const float v = -0.5f * (r ? s1 : s0);
          const uint32_t hh = pack2(v, v), hl = pack2(v, v - lo16(hh));
          const bool b = L & 1;
          sts128(sb + (b ? OFF_MB : OFF_MA) + p * 1024 + (lane >> 3) * 256 + r * 128 + (lane & 7) * 16, b ? 0u : hh, b ? hh << 16 : hl >> 16, b ? hl : 0u, 0u);
        }
      }
      fence_async_smem();
      __syncwarp();
      if (elect()) {
        mbar_arrive(sb + BAR_STAT);
      }
      TS(2, 0 + L * 8);
    }
    if (!CO && L < 2 && w == 0) cs_image(L);
    if (L & 1) {
      const uint32_t flip = L == 1 ? 0u : 1u;
      mbar_wait(sb + BAR_SIGT, 1);
      {
        int it = 0;
        if (PSL) __nanosleep(m < 8 ? PSL : PSL + 600);
        while (!__all_sync(0xffffffffu, (ld_flag(reinterpret_cast<const unsigned*>(&g_kvpart[j][m][w][512]) + (lane & 15) * 8) ^ flip) & 1u)) { if (PSL) __nanosleep(100); if (++it > (1 << 22)) __trap(); }
        fence_async_global();
      }
      if (w == 0) TS(4, 6 + L * 2);
      float a[8], z;
      for (int it = 0;; it++) {
        if (elect()) { mbar_expect_tx(stb + rs.s * 8, 8704); bulk_load(stg, &g_kvpart[j][m][w][0], 8704, stb + rs.s * 8); }
        mbar_wait(stb + rs.s * 8, rs.ph);
        if (w == 0) TS(4, 21 + L);
        adv<3>(rs);
#pragma unroll
        for (int u = 0; u < 8; u++) a[u] = 0.f;
        z = 0.f;
        uint32_t ok = 1u;
#pragma unroll
        for (int u = 0; u < 4; u++) { const float v = lds32f(stg + 8192 + u * 128 + (lane & 3) * 32 + (lane >> 2) * 4); z += v; ok &= __float_as_uint(v) ^ flip; }
        const uint2 tg = sum_packets<8, RG>(a, stg + lane * 16, 16);
        ok &= flip ? ~tg.y : tg.x;
        if (__all_sync(0xffffffffu, ok & 1u)) break;
        fence_async_smem();
        if (it > (1 << 16)) __trap();
      }
      {
        uint4* img = &g_kvfin[j][m][w * 8 + (lane >> 2)];
        uint32_t a0 = __float_as_uint(a[0]) >> 16;
        a0 += ~(a0 ^ flip) & 1u;
        st_v4(img + (lane & 3) * 16, __byte_perm(a0, pack2(0.f, a[1]), 0x7610), pack2(a[2], a[3]), pack2(a[4], a[5]), pack2(a[6], a[7]));
        const uint32_t cz = pack2(0.f, qsum(z)) | (0x3781u ^ flip);
        if (!(lane & 3)) st_v4(img + 64, cz, cz, cz, cz);
        __syncwarp();
        if (elect()) st_flag(&g_jflag[m >> 3][j][(m & 7) * 2 + w], tag * 4 + L);
      }
      if (w == 0) TS(4, 7 + L * 2);
    } else {
      if (L == 0 && w == 0) {
        st_v4(&g_kvpart[j][m][0][512 + lane], 0u, 0u, 0u, 0u); st_v4(&g_kvpart[j][m][1][512 + lane], 0u, 0u, 0u, 0u);
        __syncwarp();
      }
      mbar_wait(sb + BAR_SIGT, 0);
      if (w == 0) {
        if (elect()) { fence_gpu(); st_flag(&g_hint[m][j], tag * 16 + 4 * L); st_flag(&g_jflag[1][j][m], tag * 4 + L); }
        if (L == 0) {
          __nanosleep(KSL);
          poll_flags(&g_jflag[1][j][0], 16, 0xFFFFu, tag * 4);
          if (elect()) mbar_arrive(sb + BAR_WPHI);
        }
      } else if (m > 0) {
        poll_flags(&g_hint[m - 1][j], 1, 1u, tag * 16 + 4 * L);
        if (elect()) { mbar_expect_tx(sb + BAR_HALO, 8192); bulk_load(sb + OFF_S + 8192, &g_halo[m - 1][j][0][0], 8192, sb + BAR_HALO); }
        TS(2, 2 + L * 8);
      }
    }
    if (w == 0) {
#pragma unroll 1
      for (int e = 0; e < (L < 3 ? 2 : 1); e++) {
        unsigned* flag = early(&g_hint[m][j]);
        mbar_wait(sb + BAR_SIGP + e * 8, L & 1);
        TS(2, (e ? 6 : 3) + L * 8);
        TSH((2 * L + e) * 8);
        if (elect()) st_flag(flag, tag * 16 + 4 * L + 1 + e);
        TSH((2 * L + e) * 8 + 1);
      }
    } else {
#pragma unroll 1
      for (int i = 0; i < (L < 3 ? 28 : 14); i++) {
        const bool isx = i >= 14;
        const uint32_t a = sb + OFF_A + vs * SLOT + lane * 128 + ((lane >> 4) * 4 + (lane & 3)) * 16 + (lane & 12), code = img_code(isx, L + isx);
        for (int it = 0;; it++) {
          mbar_wait(sb + BAR_LAND + vs * 8, (vph >> vs) & 1);
          vph ^= 1u << vs;
          if (i - 14 * isx < 2) TSH((2 * L + isx) * 8 + 3 + 2 * (i - 14 * isx));
          uint32_t bad = 0;
#pragma unroll
          for (int u = 0; u < 4; u++) bad |= __float_as_uint(lds32f(a + u * 4096)) ^ code;
          if (__all_sync(0xffffffffu, !(bad & img_mask(isx)))) break;
          if (it > (1 << 16)) __trap();
          fence_async_smem();
          if (elect()) {
            mbar_expect_tx(sb + BAR_LAND + vs * 8, SLOT);
            bulk_load(sb + OFF_A + vs * SLOT, &g_img[isx ? XBUF(L + 1) : 0][m][o_order(i - 14 * isx + 2, j)][0], SLOT, sb + BAR_LAND + vs * 8);
          }
        }
        if (elect()) mbar_arrive(sb + BAR_FULLA + vs * 8);
        if (i - 14 * isx < 2) TSH((2 * L + isx) * 8 + 4 + 2 * (i - 14 * isx));
        if (++vs == NA) vs = 0;
      }
      vs = (vs + ((L & 1) ? 16 : 32 - NJ)) % NA;
    }
  }
}

__device__ __forceinline__ void spare(const Params& P, uint32_t sb, int id) {
  const int tid = threadIdx.x & 127, warp = __shfl_sync(0xffffffffu, threadIdx.x >> 5, 0), w = warp >> 2, lane = tid & 31, j = 2 * id + w;
  const uint32_t ring = w * 6 * SLOT, wp = 12 * SLOT + w * 8192, bar = sb + 13 * SLOT + w * 64;
  auto part = [&](int t) { return (t >> 4) ^ w; };
  auto load = [&](int t, uint32_t sl) {
    mbar_expect_tx(bar + sl * 8, t == 0 ? SLOT + 8192 : SLOT);
    tma_load_w(sb + ring + sl * SLOT, &P.mw[1], bar + sl * 8, part(t) * 1024 + 128 * j, t & 15);
  };
  if (!(warp & 3) && elect()) {
    if (w == 2) sts32(sb + OFF_EPOCH, atomicAdd(&g_ctr, 1u) / NCTA + 1u);
    else {
      __nanosleep(D3);
#pragma unroll 1
      for (int t = 0; t < 5; t++) {
        mbar_init(bar + t * 8, 1);
        asm volatile("fence.mbarrier_init.release.cluster;" ::: "memory");
        load(t, t);
      }
      tma_load_2d(sb + wp, &P.mwphi, bar, 0, 128 * j);
    }
  }
  __syncthreads();
  const unsigned tag = get_tag<false>(sb);
  if (w == 2) {
    int it = 0;
    while ((int)(ld_flag(&g_ctr) - tag * NCTA) < 0) { if (++it > (1 << 22)) __trap(); }
    return;
  }
  Ring r = {4, 1};
  float d[64];
  auto fold = [&]() {
    mbar_wait(bar + r.s * 8, r.ph);
    wgmma_fence();
#pragma unroll
    for (int q = 0; q < 8; q++)
      wgmma_ss_n32(reinterpret_cast<float (&)[16]>(d[16 * (q >> 1)]), desc_lo(SB + ring + r.s * SLOT, 16) + (q >> 2) * 512 + (q & 3) * 2, desc_lo(SB + wp, 512) + q * 64, q & 1);
    wgmma_commit();
  };
#pragma unroll
  for (int i = 0; i < 64; i++) d[i] = 0.f;
  int t = -1;
#pragma unroll 1
  for (int g = 0; g < 2; g++) {
    float cs[32] = {};
#pragma unroll 1
    do {
      uint32_t f[32];
#pragma unroll
      for (int i = 0; i < 32; i++) { f[i] = pack2(d[2 * i], d[2 * i + 1]); cs[i & 30] += d[2 * i]; cs[i | 1] += d[2 * i + 1]; }
      wg_bar(w);
      const uint32_t sl = r.s;
      if (t < 31) adv<5>(r);
      fold();
      if (!(warp & 3) && t >= 0 && t < 27 && elect()) load(t + 5, sl);
      if (g == w && t >= 0) {
        uint4* dst = &g_wf[0][j][t & 15][((tid >> 5) * 16 + (lane >> 2)) * 8];
#pragma unroll
        for (int q = 0; q < 8; q++)
          dst[(q >> 2) * 512 + (q & 1) * 64 + (((q & 2) * 2 + (lane & 3)) ^ (lane >> 2))] =
              make_uint4(f[4 * (q & 6) + (q & 1)], f[4 * (q & 6) + (q & 1) + 2], f[4 * (q & 6) + (q & 1) + 4], f[4 * (q & 6) + (q & 1) + 6]);
      }
      wgmma_wait<0>();
      fence_regs(d);
    } while (++t != 16 * g + 16);
    const uint32_t red = sb + ring + 5 * SLOT;
#pragma unroll
    for (int i = 0; i < 8; i++) sts128(red + (tid >> 2) * 512 + (i >> 1) * 128 + (lane & 3) * 32 + (i & 1) * 16, __float_as_uint(cs[4 * i]), __float_as_uint(cs[4 * i + 1]), __float_as_uint(cs[4 * i + 2]), __float_as_uint(cs[4 * i + 3]));
    wg_bar(w);
    float a = 0.f;
#pragma unroll 4
    for (int i = 0; i < 32; i++) a += lds32f(red + i * 512 + tid * 4);
    g_cs[1][0][(g ^ w) * 1024 + j * 128 + tid] = a;
  }
  wg_bar(w);
  if (tid == 0) { fence_gpu(); st_flag(&g_jflag[2][j][0], tag * 4); }
}

__global__ void __launch_bounds__(NTHREADS, 1) fused_kernel(const __grid_constant__ Params P) {
  extern __shared__ __align__(1024) uint8_t smem_raw[];
  constexpr uint32_t sb = SB;
  const int tid = threadIdx.x;
  const unsigned vb = vblock();
  if (vb >= 128) { spare(P, sb, vb - 128); return; }
  const int warp = __shfl_sync(0xffffffffu, tid >> 5, 0);
  if (elect()) {
    if (warp == 11) { prefetch_map(&P.mx); prefetch_map(&P.mw[0]); if (smem_u32(smem_raw) != SB) __trap(); }
    if (warp < 8) {
#pragma unroll
      for (int i = 0; i < 8; i++) mbar_init(sb + OFF_BAR + (warp * 8 + i) * 8, warp == 2 || warp == 3 ? 2 : (warp == 4 ? 8 : 1));
    }
    asm volatile("fence.mbarrier_init.release.cluster;" ::: "memory");
    if (warp < 2) {
      const int j = cta_j(vb);
#pragma unroll 1
      for (int i = 0; i < (warp == 0 ? PRE_B : PRE_A); i++) {
        const uint32_t bar = sb + BAR_FULLB + warp * 64 + i * 8;
        mbar_expect_tx(bar, SLOT);
        if (warp == 0) tma_load_w(sb + OFF_B + i * SLOT, &P.mw[0], bar, 1024 + (i & 1) * 1024 + 128 * j, kv_order(i >> 1, j, 0));
        else tma_load_3d(sb + OFF_A + i * SLOT, &P.mx, bar, kv_order(i, j, 0) * 64, cta_m(vb) * 64, 0);
      }
    }
  }
  if (tid == 0) TS(6, 0);
  __syncthreads();
  if (tid == 0) TS(6, 2);
  if (warp < 4) {
    reg_dealloc<PREGS>();
    if (warp & 2) helper(P, sb, warp & 1, vb);
    else if (warp & 1) a_loader(P, sb, vb);
    else b_producer(P, sb, vb);
  } else {
    reg_alloc<CREGS>();
    consumer(P, sb, (warp >> 2) - 1, vb);
  }
}

typedef CUresult (*EncodeFn)(CUtensorMap*, CUtensorMapDataType, cuuint32_t, void*, const cuuint64_t*, const cuuint64_t*,
                             const cuuint32_t*, const cuuint32_t*, CUtensorMapInterleave, CUtensorMapSwizzle,
                             CUtensorMapL2promotion, CUtensorMapFloatOOBfill);

void encode(EncodeFn fn, CUtensorMap* m, const void* ptr, int rank, const cuuint64_t* dims, const cuuint64_t* strides,
            const cuuint32_t* box, CUtensorMapSwizzle swz) {
  const cuuint32_t es[5] = {1, 1, 1, 1, 1};
  fn(m, CU_TENSOR_MAP_DATA_TYPE_BFLOAT16, rank, const_cast<void*>(ptr), dims, strides, box, es, CU_TENSOR_MAP_INTERLEAVE_NONE,
     swz, CU_TENSOR_MAP_L2_PROMOTION_L2_256B, CU_TENSOR_MAP_FLOAT_OOB_FILL_NONE);
}
void encode_w(EncodeFn fn, CUtensorMap* m, const void* ptr, int ncols, bool perm) {
  const cuuint64_t p = (cuuint64_t)ncols * 2, d[5] = {(cuuint64_t)ncols, 2, 4, 4, 32}, s[4] = {p, (perm ? 8 : 2) * p, (perm ? 2 : 8) * p, 32 * p};
  const cuuint32_t box[5] = {64, 2, 4, 4, 2};
  encode(fn, m, ptr, 5, d, s, box, CU_TENSOR_MAP_SWIZZLE_128B);
}

void encode_cs(EncodeFn fn, CUtensorMap* m, const void* ptr, int ncols) {
  const cuuint64_t d[2] = {(cuuint64_t)ncols, 1024}, s[1] = {(cuuint64_t)ncols * 2};
  const cuuint32_t box[2] = {32, 64};
  encode(fn, m, ptr, 2, d, s, box, CU_TENSOR_MAP_SWIZZLE_NONE);
}

}

extern "C" void kernel_launch(void* const* d_in, const int* in_sizes, int n_in, void* d_out, int out_size) {
  (void)in_sizes; (void)n_in; (void)out_size;
  void* fnp = nullptr;
  cudaDriverEntryPointQueryResult q;
  cudaGetDriverEntryPoint("cuTensorMapEncodeTiled", &fnp, cudaEnableDefault, &q);
  EncodeFn fn = (EncodeFn)fnp;
  Params P;
  {
    const cuuint64_t dims[3] = {1024, 1024, 2}, strides[2] = {4096, 2048};
    const cuuint32_t box[3] = {64, 64, 2};
    encode(fn, &P.mx, d_in[0], 3, dims, strides, box, CU_TENSOR_MAP_SWIZZLE_128B);
  }
  P.out = (uint4*)d_out;
  encode_w(fn, &P.mw[0], d_in[1], 3072, false);
  encode_w(fn, &P.mw[1], d_in[4], 3072, true);
  encode_w(fn, &P.mw[2], d_in[1], 3072, true);
  encode_w(fn, &P.mwo[0], d_in[2], 1024, true);
  encode_w(fn, &P.mwo[1], d_in[6], 1024, false);
  encode_cs(fn, &P.mcs[0], d_in[1], 3072);
  encode_cs(fn, &P.mcs[1], d_in[4], 3072);
  {
    const cuuint64_t dims[2] = {32, 1024}, strides[1] = {64};
    const cuuint32_t box[2] = {32, 128};
    encode(fn, &P.mwphi, d_in[5], 2, dims, strides, box, CU_TENSOR_MAP_SWIZZLE_64B);
  }
  cudaFuncSetAttribute(fused_kernel, cudaFuncAttributeMaxDynamicSharedMemorySize, SMEM_BYTES);
  fused_kernel<<<NCTA, NTHREADS, SMEM_BYTES, cudaStreamPerThread>>>(P);
}
```

```cpp
#include <cuda_runtime.h>
#include <cuda_bf16.h>
#include <cuda.h>
#include <stdint.h>

namespace {

__device__ __forceinline__ void wgmma_ss_n256(float (&d)[128], uint32_t da, uint32_t ha, uint32_t db, int sd) {
  asm volatile("{\n.reg .pred p;\n.reg .b64 a, b;\nsetp.ne.b32 p, %130, 0;\nmov.b64 a, {%128, %131};\nmov.b64 b, {%129, 0x40000040};\n"
    "wgmma.mma_async.sync.aligned.m64n256k16.f32.bf16.bf16 {%0,%1,%2,%3,%4,%5,%6,%7,%8,%9,%10,%11,%12,%13,%14,%15,%16,%17,%18,%19,%20,%21,%22,%23,%24,%25,%26,%27,%28,%29,%30,%31,%32,%33,%34,%35,%36,%37,%38,%39,%40,%41,%42,%43,%44,%45,%46,%47,%48,%49,%50,%51,%52,%53,%54,%55,%56,%57,%58,%59,%60,%61,%62,%63,%64,%65,%66,%67,%68,%69,%70,%71,%72,%73,%74,%75,%76,%77,%78,%79,%80,%81,%82,%83,%84,%85,%86,%87,%88,%89,%90,%91,%92,%93,%94,%95,%96,%97,%98,%99,%100,%101,%102,%103,%104,%105,%106,%107,%108,%109,%110,%111,%112,%113,%114,%115,%116,%117,%118,%119,%120,%121,%122,%123,%124,%125,%126,%127}, a, b, p, 1, 1, 0, 1;\n}\n"
    : "+f"(d[0]),"+f"(d[1]),"+f"(d[2]),"+f"(d[3]),"+f"(d[4]),"+f"(d[5]),"+f"(d[6]),"+f"(d[7]),"+f"(d[8]),"+f"(d[9]),"+f"(d[10]),"+f"(d[11]),"+f"(d[12]),"+f"(d[13]),"+f"(d[14]),"+f"(d[15]),"+f"(d[16]),"+f"(d[17]),"+f"(d[18]),"+f"(d[19]),"+f"(d[20]),"+f"(d[21]),"+f"(d[22]),"+f"(d[23]),"+f"(d[24]),"+f"(d[25]),"+f"(d[26]),"+f"(d[27]),"+f"(d[28]),"+f"(d[29]),"+f"(d[30]),"+f"(d[31]),"+f"(d[32]),"+f"(d[33]),"+f"(d[34]),"+f"(d[35]),"+f"(d[36]),"+f"(d[37]),"+f"(d[38]),"+f"(d[39]),"+f"(d[40]),"+f"(d[41]),"+f"(d[42]),"+f"(d[43]),"+f"(d[44]),"+f"(d[45]),"+f"(d[46]),"+f"(d[47]),"+f"(d[48]),"+f"(d[49]),"+f"(d[50]),"+f"(d[51]),"+f"(d[52]),"+f"(d[53]),"+f"(d[54]),"+f"(d[55]),"+f"(d[56]),"+f"(d[57]),"+f"(d[58]),"+f"(d[59]),"+f"(d[60]),"+f"(d[61]),"+f"(d[62]),"+f"(d[63]),"+f"(d[64]),"+f"(d[65]),"+f"(d[66]),"+f"(d[67]),"+f"(d[68]),"+f"(d[69]),"+f"(d[70]),"+f"(d[71]),"+f"(d[72]),"+f"(d[73]),"+f"(d[74]),"+f"(d[75]),"+f"(d[76]),"+f"(d[77]),"+f"(d[78]),"+f"(d[79]),"+f"(d[80]),"+f"(d[81]),"+f"(d[82]),"+f"(d[83]),"+f"(d[84]),"+f"(d[85]),"+f"(d[86]),"+f"(d[87]),"+f"(d[88]),"+f"(d[89]),"+f"(d[90]),"+f"(d[91]),"+f"(d[92]),"+f"(d[93]),"+f"(d[94]),"+f"(d[95]),"+f"(d[96]),"+f"(d[97]),"+f"(d[98]),"+f"(d[99]),"+f"(d[100]),"+f"(d[101]),"+f"(d[102]),"+f"(d[103]),"+f"(d[104]),"+f"(d[105]),"+f"(d[106]),"+f"(d[107]),"+f"(d[108]),"+f"(d[109]),"+f"(d[110]),"+f"(d[111]),"+f"(d[112]),"+f"(d[113]),"+f"(d[114]),"+f"(d[115]),"+f"(d[116]),"+f"(d[117]),"+f"(d[118]),"+f"(d[119]),"+f"(d[120]),"+f"(d[121]),"+f"(d[122]),"+f"(d[123]),"+f"(d[124]),"+f"(d[125]),"+f"(d[126]),"+f"(d[127])
    : "r"(da), "r"(db), "r"(sd), "r"(ha));
}
__device__ __forceinline__ void wgmma_ss_n128(float (&d)[64], uint32_t da, uint32_t ha, uint32_t db, int sd) {
  asm volatile("{\n.reg .pred p;\n.reg .b64 a, b;\nsetp.ne.b32 p, %66, 0;\nmov.b64 a, {%64, %67};\nmov.b64 b, {%65, 0x40000040};\n"
    "wgmma.mma_async.sync.aligned.m64n128k16.f32.bf16.bf16 {%0,%1,%2,%3,%4,%5,%6,%7,%8,%9,%10,%11,%12,%13,%14,%15,%16,%17,%18,%19,%20,%21,%22,%23,%24,%25,%26,%27,%28,%29,%30,%31,%32,%33,%34,%35,%36,%37,%38,%39,%40,%41,%42,%43,%44,%45,%46,%47,%48,%49,%50,%51,%52,%53,%54,%55,%56,%57,%58,%59,%60,%61,%62,%63}, a, b, p, 1, 1, 0, 1;\n}\n"
    : "+f"(d[0]),"+f"(d[1]),"+f"(d[2]),"+f"(d[3]),"+f"(d[4]),"+f"(d[5]),"+f"(d[6]),"+f"(d[7]),"+f"(d[8]),"+f"(d[9]),"+f"(d[10]),"+f"(d[11]),"+f"(d[12]),"+f"(d[13]),"+f"(d[14]),"+f"(d[15]),"+f"(d[16]),"+f"(d[17]),"+f"(d[18]),"+f"(d[19]),"+f"(d[20]),"+f"(d[21]),"+f"(d[22]),"+f"(d[23]),"+f"(d[24]),"+f"(d[25]),"+f"(d[26]),"+f"(d[27]),"+f"(d[28]),"+f"(d[29]),"+f"(d[30]),"+f"(d[31]),"+f"(d[32]),"+f"(d[33]),"+f"(d[34]),"+f"(d[35]),"+f"(d[36]),"+f"(d[37]),"+f"(d[38]),"+f"(d[39]),"+f"(d[40]),"+f"(d[41]),"+f"(d[42]),"+f"(d[43]),"+f"(d[44]),"+f"(d[45]),"+f"(d[46]),"+f"(d[47]),"+f"(d[48]),"+f"(d[49]),"+f"(d[50]),"+f"(d[51]),"+f"(d[52]),"+f"(d[53]),"+f"(d[54]),"+f"(d[55]),"+f"(d[56]),"+f"(d[57]),"+f"(d[58]),"+f"(d[59]),"+f"(d[60]),"+f"(d[61]),"+f"(d[62]),"+f"(d[63])
    : "r"(da), "r"(db), "r"(sd), "r"(ha));
}
__device__ __forceinline__ void wgmma_ss_n40_tt(float (&d)[20], uint32_t da, uint32_t db, int sd) {
  asm volatile("{\n.reg .pred p;\n.reg .b64 a, b;\nsetp.ne.b32 p, %22, 0;\nmov.b64 a, {%20, 0x40000040};\nmov.b64 b, {%21, 0x8};\n"
    "wgmma.mma_async.sync.aligned.m64n40k16.f32.bf16.bf16 {%0,%1,%2,%3,%4,%5,%6,%7,%8,%9,%10,%11,%12,%13,%14,%15,%16,%17,%18,%19}, a, b, p, 1, 1, 1, 1;\n}\n"
    : "+f"(d[0]),"+f"(d[1]),"+f"(d[2]),"+f"(d[3]),"+f"(d[4]),"+f"(d[5]),"+f"(d[6]),"+f"(d[7]),"+f"(d[8]),"+f"(d[9]),"+f"(d[10]),"+f"(d[11]),"+f"(d[12]),"+f"(d[13]),"+f"(d[14]),"+f"(d[15]),"+f"(d[16]),"+f"(d[17]),"+f"(d[18]),"+f"(d[19])
    : "r"(da), "r"(db), "r"(sd));
}
__device__ __forceinline__ void wgmma_ss_n32(float (&d)[16], uint32_t da, uint32_t db, int sd) {
  asm volatile("{\n.reg .pred p;\n.reg .b64 a, b;\nsetp.ne.b32 p, %18, 0;\nmov.b64 a, {%16, 0x40000040};\nmov.b64 b, {%17, 0x80000020};\n"
    "wgmma.mma_async.sync.aligned.m64n32k16.f32.bf16.bf16 {%0,%1,%2,%3,%4,%5,%6,%7,%8,%9,%10,%11,%12,%13,%14,%15}, a, b, p, 1, 1, 0, 1;\n}\n"
    : "+f"(d[0]),"+f"(d[1]),"+f"(d[2]),"+f"(d[3]),"+f"(d[4]),"+f"(d[5]),"+f"(d[6]),"+f"(d[7]),"+f"(d[8]),"+f"(d[9]),"+f"(d[10]),"+f"(d[11]),"+f"(d[12]),"+f"(d[13]),"+f"(d[14]),"+f"(d[15])
    : "r"(da), "r"(db), "r"(sd));
}
__device__ __forceinline__ void wgmma_rs_n40(float (&d)[20], uint32_t a0, uint32_t a1, uint32_t a2, uint32_t a3, uint32_t db, int sd) {
  asm volatile("{\n.reg .pred p;\n.reg .b64 b;\nsetp.ne.b32 p, %25, 0;\nmov.b64 b, {%24, 0x10};\n"
    "wgmma.mma_async.sync.aligned.m64n40k16.f32.bf16.bf16 {%0,%1,%2,%3,%4,%5,%6,%7,%8,%9,%10,%11,%12,%13,%14,%15,%16,%17,%18,%19}, {%20,%21,%22,%23}, b, p, 1, 1, 1;\n}\n"
    : "+f"(d[0]),"+f"(d[1]),"+f"(d[2]),"+f"(d[3]),"+f"(d[4]),"+f"(d[5]),"+f"(d[6]),"+f"(d[7]),"+f"(d[8]),"+f"(d[9]),"+f"(d[10]),"+f"(d[11]),"+f"(d[12]),"+f"(d[13]),"+f"(d[14]),"+f"(d[15]),"+f"(d[16]),"+f"(d[17]),"+f"(d[18]),"+f"(d[19])
    : "r"(a0), "r"(a1), "r"(a2), "r"(a3), "r"(db), "r"(sd));
}
__device__ __forceinline__ void wgmma_r1_n256(float (&d)[128], uint32_t da, uint32_t db, int sd) {
  asm volatile("{\n.reg .pred p;\n.reg .b64 a, b;\nsetp.ne.b32 p, %130, 0;\nmov.b64 a, {%128, 0x8};\nmov.b64 b, {%129, 0x6};\n"
    "wgmma.mma_async.sync.aligned.m64n256k16.f32.bf16.bf16 {%0,%1,%2,%3,%4,%5,%6,%7,%8,%9,%10,%11,%12,%13,%14,%15,%16,%17,%18,%19,%20,%21,%22,%23,%24,%25,%26,%27,%28,%29,%30,%31,%32,%33,%34,%35,%36,%37,%38,%39,%40,%41,%42,%43,%44,%45,%46,%47,%48,%49,%50,%51,%52,%53,%54,%55,%56,%57,%58,%59,%60,%61,%62,%63,%64,%65,%66,%67,%68,%69,%70,%71,%72,%73,%74,%75,%76,%77,%78,%79,%80,%81,%82,%83,%84,%85,%86,%87,%88,%89,%90,%91,%92,%93,%94,%95,%96,%97,%98,%99,%100,%101,%102,%103,%104,%105,%106,%107,%108,%109,%110,%111,%112,%113,%114,%115,%116,%117,%118,%119,%120,%121,%122,%123,%124,%125,%126,%127}, a, b, p, 1, 1, 0, 1;\n}\n"
    : "+f"(d[0]),"+f"(d[1]),"+f"(d[2]),"+f"(d[3]),"+f"(d[4]),"+f"(d[5]),"+f"(d[6]),"+f"(d[7]),"+f"(d[8]),"+f"(d[9]),"+f"(d[10]),"+f"(d[11]),"+f"(d[12]),"+f"(d[13]),"+f"(d[14]),"+f"(d[15]),"+f"(d[16]),"+f"(d[17]),"+f"(d[18]),"+f"(d[19]),"+f"(d[20]),"+f"(d[21]),"+f"(d[22]),"+f"(d[23]),"+f"(d[24]),"+f"(d[25]),"+f"(d[26]),"+f"(d[27]),"+f"(d[28]),"+f"(d[29]),"+f"(d[30]),"+f"(d[31]),"+f"(d[32]),"+f"(d[33]),"+f"(d[34]),"+f"(d[35]),"+f"(d[36]),"+f"(d[37]),"+f"(d[38]),"+f"(d[39]),"+f"(d[40]),"+f"(d[41]),"+f"(d[42]),"+f"(d[43]),"+f"(d[44]),"+f"(d[45]),"+f"(d[46]),"+f"(d[47]),"+f"(d[48]),"+f"(d[49]),"+f"(d[50]),"+f"(d[51]),"+f"(d[52]),"+f"(d[53]),"+f"(d[54]),"+f"(d[55]),"+f"(d[56]),"+f"(d[57]),"+f"(d[58]),"+f"(d[59]),"+f"(d[60]),"+f"(d[61]),"+f"(d[62]),"+f"(d[63]),"+f"(d[64]),"+f"(d[65]),"+f"(d[66]),"+f"(d[67]),"+f"(d[68]),"+f"(d[69]),"+f"(d[70]),"+f"(d[71]),"+f"(d[72]),"+f"(d[73]),"+f"(d[74]),"+f"(d[75]),"+f"(d[76]),"+f"(d[77]),"+f"(d[78]),"+f"(d[79]),"+f"(d[80]),"+f"(d[81]),"+f"(d[82]),"+f"(d[83]),"+f"(d[84]),"+f"(d[85]),"+f"(d[86]),"+f"(d[87]),"+f"(d[88]),"+f"(d[89]),"+f"(d[90]),"+f"(d[91]),"+f"(d[92]),"+f"(d[93]),"+f"(d[94]),"+f"(d[95]),"+f"(d[96]),"+f"(d[97]),"+f"(d[98]),"+f"(d[99]),"+f"(d[100]),"+f"(d[101]),"+f"(d[102]),"+f"(d[103]),"+f"(d[104]),"+f"(d[105]),"+f"(d[106]),"+f"(d[107]),"+f"(d[108]),"+f"(d[109]),"+f"(d[110]),"+f"(d[111]),"+f"(d[112]),"+f"(d[113]),"+f"(d[114]),"+f"(d[115]),"+f"(d[116]),"+f"(d[117]),"+f"(d[118]),"+f"(d[119]),"+f"(d[120]),"+f"(d[121]),"+f"(d[122]),"+f"(d[123]),"+f"(d[124]),"+f"(d[125]),"+f"(d[126]),"+f"(d[127])
    : "r"(da), "r"(db), "r"(sd));
}
__device__ __forceinline__ void wgmma_r1_n128(float (&d)[64], uint32_t da, uint32_t db, int sd) {
  asm volatile("{\n.reg .pred p;\n.reg .b64 a, b;\nsetp.ne.b32 p, %66, 0;\nmov.b64 a, {%64, 0x8};\nmov.b64 b, {%65, 0x6};\n"
    "wgmma.mma_async.sync.aligned.m64n128k16.f32.bf16.bf16 {%0,%1,%2,%3,%4,%5,%6,%7,%8,%9,%10,%11,%12,%13,%14,%15,%16,%17,%18,%19,%20,%21,%22,%23,%24,%25,%26,%27,%28,%29,%30,%31,%32,%33,%34,%35,%36,%37,%38,%39,%40,%41,%42,%43,%44,%45,%46,%47,%48,%49,%50,%51,%52,%53,%54,%55,%56,%57,%58,%59,%60,%61,%62,%63}, a, b, p, 1, 1, 0, 1;\n}\n"
    : "+f"(d[0]),"+f"(d[1]),"+f"(d[2]),"+f"(d[3]),"+f"(d[4]),"+f"(d[5]),"+f"(d[6]),"+f"(d[7]),"+f"(d[8]),"+f"(d[9]),"+f"(d[10]),"+f"(d[11]),"+f"(d[12]),"+f"(d[13]),"+f"(d[14]),"+f"(d[15]),"+f"(d[16]),"+f"(d[17]),"+f"(d[18]),"+f"(d[19]),"+f"(d[20]),"+f"(d[21]),"+f"(d[22]),"+f"(d[23]),"+f"(d[24]),"+f"(d[25]),"+f"(d[26]),"+f"(d[27]),"+f"(d[28]),"+f"(d[29]),"+f"(d[30]),"+f"(d[31]),"+f"(d[32]),"+f"(d[33]),"+f"(d[34]),"+f"(d[35]),"+f"(d[36]),"+f"(d[37]),"+f"(d[38]),"+f"(d[39]),"+f"(d[40]),"+f"(d[41]),"+f"(d[42]),"+f"(d[43]),"+f"(d[44]),"+f"(d[45]),"+f"(d[46]),"+f"(d[47]),"+f"(d[48]),"+f"(d[49]),"+f"(d[50]),"+f"(d[51]),"+f"(d[52]),"+f"(d[53]),"+f"(d[54]),"+f"(d[55]),"+f"(d[56]),"+f"(d[57]),"+f"(d[58]),"+f"(d[59]),"+f"(d[60]),"+f"(d[61]),"+f"(d[62]),"+f"(d[63])
    : "r"(da), "r"(db), "r"(sd));
}

__device__ __forceinline__ uint32_t smem_u32(const void* p) { return (uint32_t)__cvta_generic_to_shared(p); }
__device__ __forceinline__ void mbar_init(uint32_t bar, uint32_t cnt) { asm volatile("mbarrier.init.shared::cta.b64 [%0], %1;" ::"r"(bar), "r"(cnt)); }
__device__ __forceinline__ void mbar_expect_tx(uint32_t bar, uint32_t bytes) { asm volatile("mbarrier.arrive.expect_tx.shared::cta.b64 _, [%0], %1;" ::"r"(bar), "r"(bytes) : "memory"); }
__device__ __forceinline__ void mbar_arrive(uint32_t bar) { asm volatile("mbarrier.arrive.shared::cta.b64 _, [%0];" ::"r"(bar) : "memory"); }
__device__ __forceinline__ void mbar_arrive_n(uint32_t bar, uint32_t n) { asm volatile("mbarrier.arrive.shared::cta.b64 _, [%0], %1;" ::"r"(bar), "r"(n) : "memory"); }
__device__ __forceinline__ void mbar_wait(uint32_t bar, uint32_t parity) {
  asm volatile("{\n.reg .pred p;\nLAB_WAIT:\nmbarrier.try_wait.parity.shared::cta.b64 p, [%0], %1;\n@p bra DONE;\nbra LAB_WAIT;\nDONE:\n}" ::"r"(bar), "r"(parity) : "memory");
}
__device__ __forceinline__ void mbar_wait2(uint32_t a, uint32_t pa, uint32_t b, uint32_t pb) {
  asm volatile("{\n.reg .pred p, q;\nLAB_WAIT:\nmbarrier.try_wait.parity.shared::cta.b64 p, [%0], %1;\nmbarrier.try_wait.parity.shared::cta.b64 q, [%2], %3;\n"
               "and.pred p, p, q;\n@p bra DONE;\nbra LAB_WAIT;\nDONE:\n}" ::"r"(a), "r"(pa), "r"(b), "r"(pb) : "memory");
}
__device__ __forceinline__ void mbar_wait3(uint32_t a, uint32_t pa, uint32_t b, uint32_t pb) {
  asm volatile("{\n.reg .pred p, q, r;\nLAB_WAIT:\nmbarrier.try_wait.parity.shared::cta.b64 p, [%0], %1;\nmbarrier.try_wait.parity.shared::cta.b64 q, [%2], %3;\n"
               "mbarrier.try_wait.parity.shared::cta.b64 r, [%2+8], %3;\nand.pred p, p, q;\nand.pred p, p, r;\n@p bra DONE;\nbra LAB_WAIT;\nDONE:\n}" ::"r"(a), "r"(pa), "r"(b), "r"(pb) : "memory");
}
__device__ __forceinline__ bool mbar_probe2(uint32_t a, uint32_t pa, uint32_t b, uint32_t pb) {
  uint32_t ok;
  asm volatile("{\n.reg .pred p, q;\nmbarrier.test_wait.parity.shared::cta.b64 p, [%1], %2;\nmbarrier.test_wait.parity.shared::cta.b64 q, [%3], %4;\n"
               "and.pred p, p, q;\nselp.u32 %0, 1, 0, p;\n}" : "=r"(ok) : "r"(a), "r"(pa), "r"(b), "r"(pb) : "memory");
  return ok != 0;
}
__device__ __forceinline__ void tma_load_3d(uint32_t dst, const CUtensorMap* tm, uint32_t bar, int c0, int c1, int c2) {
  asm volatile("cp.async.bulk.tensor.3d.shared::cluster.global.mbarrier::complete_tx::bytes [%0], [%1, {%3, %4, %5}], [%2];"
               ::"r"(dst), "l"(tm), "r"(bar), "r"(c0), "r"(c1), "r"(c2) : "memory");
}
__device__ __forceinline__ void tma_load_2d(uint32_t dst, const CUtensorMap* tm, uint32_t bar, int c0, int c1) {
  asm volatile("cp.async.bulk.tensor.2d.shared::cluster.global.mbarrier::complete_tx::bytes [%0], [%1, {%3, %4}], [%2];"
               ::"r"(dst), "l"(tm), "r"(bar), "r"(c0), "r"(c1) : "memory");
}
__device__ __forceinline__ void tma_load_w(uint32_t dst, const CUtensorMap* tm, uint32_t bar, int col, int kb) {
#pragma unroll
  for (int q = 0; q < 2; q++)
    asm volatile("cp.async.bulk.tensor.5d.shared::cluster.global.mbarrier::complete_tx::bytes [%0], [%1, {%3, %4, %4, %4, %5}], [%2];"
                 ::"r"(dst + q * 8192), "l"(tm), "r"(bar), "r"(col + q * 64), "r"(0), "r"(2 * kb) : "memory");
}
__device__ __forceinline__ void tma_prefetch_w(const CUtensorMap* tm, int col, int kb) {
#pragma unroll
  for (int q = 0; q < 2; q++)
    asm volatile("cp.async.bulk.prefetch.tensor.5d.L2.global [%0, {%1, %2, %2, %2, %3}];" ::"l"(tm), "r"(col + q * 64), "r"(0), "r"(2 * kb) : "memory");
}
__device__ __forceinline__ void bulk_load(uint32_t dst, const void* g, uint32_t bytes, uint32_t bar) {
  asm volatile("cp.async.bulk.shared::cluster.global.mbarrier::complete_tx::bytes [%0], [%1], %2, [%3];" ::"r"(dst), "l"(g), "r"(bytes), "r"(bar) : "memory");
}
__device__ __forceinline__ void prefetch_map(const CUtensorMap* tm) { asm volatile("prefetch.tensormap [%0];" ::"l"(tm) : "memory"); }
__device__ __forceinline__ void fence_async_smem() { asm volatile("fence.proxy.async.shared::cta;" ::: "memory"); }
__device__ __forceinline__ void fence_async_global() { asm volatile("fence.proxy.async.global;" ::: "memory"); }
__device__ __forceinline__ void fence_gpu() { asm volatile("fence.release.gpu;" ::: "memory"); }
__device__ __forceinline__ void st_flag(unsigned* p, unsigned v) { asm volatile("st.relaxed.gpu.global.u32 [%0], %1;" ::"l"(p), "r"(v) : "memory"); }
__device__ __forceinline__ unsigned ld_flag(const unsigned* p) { unsigned v; asm volatile("ld.relaxed.gpu.global.u32 %0, [%1];" : "=r"(v) : "l"(p) : "memory"); return v; }
__device__ __forceinline__ uint4 ldcg4(const void* p) { uint4 v; asm volatile("ld.global.cg.v4.u32 {%0,%1,%2,%3}, [%4];" : "=r"(v.x), "=r"(v.y), "=r"(v.z), "=r"(v.w) : "l"(p)); return v; }
__device__ __forceinline__ uint4 ld_pkt(const uint4* p) {
  uint4 v; asm volatile("{\n.reg .b128 t;\nld.relaxed.gpu.global.b128 t, [%4];\nmov.b128 {%0,%1,%2,%3}, t;\n}" : "=r"(v.x), "=r"(v.y), "=r"(v.z), "=r"(v.w) : "l"(p) : "memory"); return v;
}
__device__ __forceinline__ void st_pkt(uint4* p, uint32_t a, uint32_t b, uint32_t c, uint32_t tag) {
  asm volatile("{\n.reg .b128 t;\nmov.b128 t, {%1,%2,%3,%4};\nst.relaxed.gpu.global.b128 [%0], t;\n}" ::"l"(p), "r"(a), "r"(b), "r"(c), "r"(tag) : "memory");
}
__device__ __forceinline__ void st_v4(uint4* p, uint32_t a, uint32_t b, uint32_t c, uint32_t d) { asm volatile("st.relaxed.gpu.global.v4.u32 [%0], {%1,%2,%3,%4};" ::"l"(p), "r"(a), "r"(b), "r"(c), "r"(d) : "memory"); }
__device__ __forceinline__ void stg128(uint4* p, uint4 v) { asm volatile("st.global.v4.u32 [%0], {%1,%2,%3,%4};" ::"l"(p), "r"(v.x), "r"(v.y), "r"(v.z), "r"(v.w) : "memory"); }
__device__ __forceinline__ void sts32(uint32_t addr, uint32_t a) { asm volatile("st.shared.u32 [%0], %1;" ::"r"(addr), "r"(a) : "memory"); }
__device__ __forceinline__ void sts64(uint32_t addr, uint32_t a, uint32_t b) { asm volatile("st.shared.v2.u32 [%0], {%1,%2};" ::"r"(addr), "r"(a), "r"(b) : "memory"); }
__device__ __forceinline__ uint32_t mul2(uint32_t a, uint32_t b) { uint32_t r; asm("mul.rn.bf16x2 %0, %1, %2;" : "=r"(r) : "r"(a), "r"(b)); return r; }
__device__ __forceinline__ uint32_t add2(uint32_t a, uint32_t b) { uint32_t r; asm("add.rn.bf16x2 %0, %1, %2;" : "=r"(r) : "r"(a), "r"(b)); return r; }
__device__ __forceinline__ bool elect() {
  uint32_t p; asm volatile("{\n.reg .pred q;\nelect.sync _|q, 0xffffffff;\nselp.u32 %0, 1, 0, q;\n}" : "=r"(p)); return p != 0;
}
__device__ __forceinline__ void wgmma_fence() { asm volatile("wgmma.fence.sync.aligned;" ::: "memory"); }
__device__ __forceinline__ void wgmma_commit() { asm volatile("wgmma.commit_group.sync.aligned;" ::: "memory"); }
template <int N> __device__ __forceinline__ void wgmma_wait() { asm volatile("wgmma.wait_group.sync.aligned %0;" ::"n"(N) : "memory"); }
template <int N> __device__ __forceinline__ void fence_regs(float (&d)[N]) {
#pragma unroll
  for (int i = 0; i < N; i++) asm volatile("" : "+f"(d[i])::"memory");
}
template <int R> __device__ __forceinline__ void reg_alloc() { asm volatile("setmaxnreg.inc.sync.aligned.u32 %0;" ::"n"(R)); }
template <int R> __device__ __forceinline__ void reg_dealloc() { asm volatile("setmaxnreg.dec.sync.aligned.u32 %0;" ::"n"(R)); }
__device__ __forceinline__ void wg_bar(int w) { asm volatile("bar.sync %0, 128;" ::"r"(w + 1) : "memory"); }
__device__ __forceinline__ constexpr uint32_t desc_lo(uint32_t addr, uint32_t lbo) { return (addr >> 4) + ((lbo >> 4) << 16); }
__device__ __forceinline__ uint32_t pack2(float lo, float hi) { uint32_t r; asm("cvt.rn.bf16x2.f32 %0, %1, %2;" : "=r"(r) : "f"(hi), "f"(lo)); return r; }
__device__ __forceinline__ float lo16(uint32_t v) { return __uint_as_float(v << 16); }
__device__ __forceinline__ float hi16(uint32_t v) { return __uint_as_float(v & 0xFFFF0000u); }
__device__ __forceinline__ float ex2(float x) { float r; asm("ex2.approx.ftz.f32 %0, %1;" : "=f"(r) : "f"(x)); return r; }
__device__ __forceinline__ float rcp(float x) { float r; asm("rcp.approx.ftz.f32 %0, %1;" : "=f"(r) : "f"(x)); return r; }
__device__ __forceinline__ uint32_t movm(uint32_t a) { uint32_t d; asm volatile("movmatrix.sync.aligned.m8n8.trans.b16 %0, %1;" : "=r"(d) : "r"(a)); return d; }
__device__ __forceinline__ void stsm4(uint32_t addr, uint32_t a, uint32_t b, uint32_t c, uint32_t d) {
  asm volatile("stmatrix.sync.aligned.m8n8.x4.shared.b16 [%0], {%1,%2,%3,%4};" ::"r"(addr), "r"(a), "r"(b), "r"(c), "r"(d) : "memory");
}
__device__ __forceinline__ void ldsm4(uint32_t addr, uint32_t (&r)[4]) {
  asm volatile("ldmatrix.sync.aligned.m8n8.x4.shared.b16 {%0,%1,%2,%3}, [%4];" : "=r"(r[0]), "=r"(r[1]), "=r"(r[2]), "=r"(r[3]) : "r"(addr) : "memory");
}
__device__ __forceinline__ void sts128(uint32_t addr, uint32_t a, uint32_t b, uint32_t c, uint32_t d) {
  asm volatile("st.shared.v4.u32 [%0], {%1,%2,%3,%4};" ::"r"(addr), "r"(a), "r"(b), "r"(c), "r"(d) : "memory");
}
__device__ __forceinline__ void lds128(uint32_t addr, uint32_t& a, uint32_t& b, uint32_t& c, uint32_t& d) {
  asm volatile("ld.shared.v4.u32 {%0,%1,%2,%3}, [%4];" : "=r"(a), "=r"(b), "=r"(c), "=r"(d) : "r"(addr) : "memory");
}
__device__ __forceinline__ float lds32f(uint32_t addr) { float v; asm volatile("ld.shared.f32 %0, [%1];" : "=f"(v) : "r"(addr) : "memory"); return v; }
__device__ __forceinline__ float2 lds64f(uint32_t addr) { float2 v; asm volatile("ld.shared.v2.f32 {%0,%1}, [%2];" : "=f"(v.x), "=f"(v.y) : "r"(addr) : "memory"); return v; }
__device__ __forceinline__ void mma16816(float (&d)[4], uint32_t a0, uint32_t a1, uint32_t a2, uint32_t a3, uint32_t b0, uint32_t b1) {
  asm("mma.sync.aligned.m16n8k16.row.col.f32.bf16.bf16.f32 {%0,%1,%2,%3}, {%4,%5,%6,%7}, {%8,%9}, {%0,%1,%2,%3};"
      : "+f"(d[0]), "+f"(d[1]), "+f"(d[2]), "+f"(d[3]) : "r"(a0), "r"(a1), "r"(a2), "r"(a3), "r"(b0), "r"(b1));
}
__device__ __forceinline__ void mma1688(float (&d)[4], uint32_t a0, uint32_t a1, uint32_t b0) {
  asm("mma.sync.aligned.m16n8k8.row.col.f32.bf16.bf16.f32 {%0,%1,%2,%3}, {%4,%5}, {%6}, {%0,%1,%2,%3};"
      : "+f"(d[0]), "+f"(d[1]), "+f"(d[2]), "+f"(d[3]) : "r"(a0), "r"(a1), "r"(b0));
}

__device__ __forceinline__ float qsum(float v) { v += __shfl_xor_sync(0xffffffffu, v, 1); v += __shfl_xor_sync(0xffffffffu, v, 2); return v; }

constexpr int NCTA = 132;
#define NB_ 6
#define NA_ 5
constexpr int NB = NB_;
constexpr int NA = NA_;
constexpr uint32_t SLOT = 16384;
constexpr uint32_t SB = 1024;
constexpr uint32_t OFF_B = 0;
constexpr uint32_t OFF_A = NB * SLOT;
constexpr uint32_t OFF_S = OFF_A + NA * SLOT;
constexpr uint32_t OFF_T = OFF_S + 20480;
constexpr uint32_t OFF_CS = OFF_T + 24576;
constexpr uint32_t OFF_MR = OFF_CS + 4640;
constexpr uint32_t OFF_BAR = OFF_MR + 512;
constexpr uint32_t OFF_MA = OFF_S, OFF_MB = OFF_CS - 2048;
constexpr uint32_t BAR_FULLB = OFF_BAR;
constexpr uint32_t BAR_FULLA = BAR_FULLB + 64;
constexpr uint32_t BAR_EMPTYB = BAR_FULLA + 64;
constexpr uint32_t BAR_EMPTYA = BAR_EMPTYB + 64;
constexpr uint32_t BAR_SIGP = BAR_EMPTYA + 64;
constexpr uint32_t BAR_SIGT = BAR_SIGP + 24;
constexpr uint32_t BAR_STAT = BAR_SIGP + 64;
constexpr uint32_t BAR_HALO = BAR_STAT + 16;
constexpr uint32_t BAR_CS = BAR_HALO + 8;
constexpr uint32_t BAR_WPHI = BAR_CS + 16;
constexpr uint32_t BAR_KV = BAR_WPHI + 8;
constexpr uint32_t BAR_STG = BAR_KV + 16;
constexpr uint32_t BAR_EPOCH = BAR_STG + 48;
constexpr uint32_t BAR_LAND = OFF_BAR + 7 * 64;
constexpr uint32_t OFF_EPOCH = OFF_BAR + 8 * 64;
static_assert(BAR_EPOCH < BAR_LAND, "barriers");
constexpr uint32_t SMEM_BYTES = OFF_EPOCH + 8;
static_assert(SMEM_BYTES <= 232448 && NB % 2 == 0 && NB <= 8 && NA <= 6, "smem");

#define CREGS 224
#define PREGS 56
#define PF1 19
#define PF2 21
#define PRE_A 2
#define PRE_B 4
#define CSNEED 0xF001u
#define PS0 1
#define PS1 2
#define SD 1000
#define KSPLIT 12
#define KEEP 16
#define NJ 3
#define KSL 1000
#define PSL 0
#define KVS 12
#define D2 2000
#define D3 1500
#define G0 50
#define MAP 3
#define PMAP 0x76321450u
#define XA 3
#define CP 500
#define S0 200
#define NS 2
#define SW 2
#define SA 1
#define SB_ 4
#define ND0 1
#define KC 8
#define CO 0
#define SE 500
#define PAA 1600
#define PAX 900
#define PA0 1800
#define PX0 1100
#define XN 1
#define RG 1
#define KI 1
#define TSK 3
constexpr int NTHREADS = 384;

struct Params {
  CUtensorMap mx;
  CUtensorMap mw[3];
  CUtensorMap mwo[2];
  CUtensorMap mcs[2];
  CUtensorMap mwphi;
  uint4* out;
};

#define XBUF(L) 1
__device__ __align__(256) uint4 g_img[XBUF(3) + 1][16][16][1024];
__device__ __forceinline__ uint32_t img_code(bool isx, int L) { return isx ? (L & 1) | (L & 2) << 15 : ~L & 1; }
__device__ __forceinline__ uint32_t img_mask(bool isx) { return isx ? 0x10001u : 1u; }
__device__ __align__(256) uint4 g_wf[2][8][16][1024];
__device__ __align__(256) uint4 g_stats[16][2][8][32];
__device__ __align__(256) uint4 g_halo[16][8][2][256];
__device__ __align__(256) float g_cs[2][2][3072];
__device__ __align__(256) uint4 g_kvpart[8][16][2][544];
__device__ __align__(256) uint4 g_kvfin[8][16][80];
__device__ __align__(256) unsigned g_hint[16][32];
__device__ __align__(256) unsigned g_jflag[3][8][32];
__device__ unsigned g_ctr;
__device__ __forceinline__ unsigned vblock() {
  unsigned s;
  asm volatile("mov.u32 %0, %%smid;" : "=r"(s));
  const unsigned r = s & 1;
  s >>= 1;
  const unsigned t = s - 32, q = (t * 37) >> 8;
  const unsigned hi = s < 60 ? 12 + (t - 7 * q) * 8 + q : (s < 62 ? s + 4 : s - 58);
  unsigned b = 2 * (s < 32 ? (s & 7) * 8 + (s >> 3) : hi) + r;
  if (b < 128) b = (b & 15) | ((PMAP >> ((b >> 4) * 4)) & 7) << 4;
  if (s >= 62) b = 8 + 4 * r + s - 62;
  unsigned n;
  asm volatile("mov.u32 %0, %%nsmid;" : "=r"(n));
  return __shfl_sync(0xffffffffu, n == NCTA ? b : blockIdx.x, 0);
}
#define TS(who, id) do {} while (0)
#define TSW(id) do {} while (0)

#define TSH(id) do {} while (0)
#define TSMASK 0xFFFF
#define TSL_(a) do { if ((TSMASK >> (a)) & 1) TSW((a) + L * 12); } while (0)
__device__ __forceinline__ int cta_m(unsigned b) { return ((b >> 2) & 12) | (b & 3); }
__device__ __forceinline__ int cta_j(unsigned b) { return ((b >> 2) & 3) | ((b >> 4) & 4); }
struct Ring { uint32_t s, ph; };
template <int N> __device__ __forceinline__ void adv(Ring& r) { if (++r.s == N) { r.s = 0; r.ph ^= 1; } }
template <int N> __device__ __forceinline__ void rewind2(Ring& r) { if (r.s < 2) { r.s += N - 2; r.ph ^= 1; } else r.s -= 2; }
__device__ __forceinline__ int other_tile(int t, int j) { return (t == (j | 4) ? 7 : t) ^ (~j & 4); }
__device__ __forceinline__ int o_order(int i, int j) {
  if (i < 2) return 2 * j + i;
  const int odd = i >= 9;
  return 2 * other_tile(i - 2 - 7 * odd, j) + odd;
}
__device__ __forceinline__ int kv_order(int i, int j, int L) { return L > 0 ? o_order(i, j) : (i + 14 + 2 * (j & 4)) & 15; }

__device__ __forceinline__ unsigned poll_flags(const unsigned* f, int n, unsigned need, unsigned tag) {
  const int lane = threadIdx.x & 31;
  unsigned mask; int it = 0;
  do {
    unsigned v = lane < n ? ld_flag(f + lane) : 0u;
    mask = __ballot_sync(0xffffffffu, lane < n && (int)(v - tag) >= 0);
    if (++it > (1 << 22)) __trap();
  } while ((mask & need) != need);
  fence_async_global();
  return mask;
}
template <bool WAIT = true>
__device__ __forceinline__ unsigned get_tag(uint32_t sb) {
  if (WAIT) mbar_wait(sb + BAR_EPOCH, 0);
  unsigned t; asm volatile("ld.shared.u32 %0, [%1];" : "=r"(t) : "r"(sb + OFF_EPOCH) : "memory");
  return t;
}

__device__ __forceinline__ int lane_id() { int l; asm volatile("mov.u32 %0, %%laneid;" : "=r"(l)); return l; }
__device__ __forceinline__ unsigned seq4(unsigned tag, int L) { return 8u | ((tag & 1u) << 2) | (unsigned)L; }
constexpr float LOG2E = 1.4426950408889634f;

__device__ __forceinline__ float bb_fence(int never, const void* p = &g_ctr, uint32_t keep = 0) {
  while (never < 0) never = ld_flag((const unsigned*)p) + keep;
  return __int_as_float(never >> 30);
}
__device__ __forceinline__ uint32_t solid(uint32_t v) { return __shfl_sync(0xffffffffu, v, threadIdx.x & 31); }
template <class T> __device__ __forceinline__ T* solid(T* p) { return (T*)__shfl_sync(0xffffffffu, (unsigned long long)p, threadIdx.x & 31); }
constexpr uint32_t HA128 = 0x40000040u, HA64 = 0x80000040u;
struct Ctx {
  static constexpr uint32_t sb = SB;
  uint32_t ab, da0;
  int w, warp, lane, g, c;
  int goff;
  __device__ __forceinline__ int m() const { return goff >> 14; }
  __device__ __forceinline__ int j() const { return (goff >> 4) & 7; }
  bool elected;
  Ring ra, rb;
  uint32_t pa, pb;
  uint32_t ha, k2;
  uint32_t mrow, mxor, mhi;
  __device__ __forceinline__ uint32_t aslot(uint32_t s) const { return ab + s * SLOT; }
  __device__ __forceinline__ uint32_t fullA(uint32_t s) const { return sb + BAR_FULLA + s * 8; }
  __device__ __forceinline__ uint32_t fullB(uint32_t s) const { return sb + BAR_FULLB + s * 8; }
  __device__ __forceinline__ void releaseA(uint32_t s) const { if (elected) mbar_arrive(sb + BAR_EMPTYA + s * 8); }
  __device__ __forceinline__ void releaseB(uint32_t s) const { if (elected) mbar_arrive(sb + BAR_EMPTYB + s * 8); }
  __device__ __forceinline__ uint32_t maddr(uint32_t tile, uint32_t ch) const { return tile + mrow + (((ch + mhi) ^ mxor) << 4); }
  __device__ __forceinline__ uint32_t oo() const { return warp * 128 + g * 4 + (c ^ (g >> 1)); }
  __device__ __forceinline__ uint4* img(int b, int hp) const { return ip + (b * 256 + hp) * 1024; }
  uint4* ip;
  uint32_t so;
  __device__ __forceinline__ uint32_t held(int i) const { return ra.s + i < 2 ? ra.s + i + NA - 2 : ra.s + i - 2; }
};

template <int N, bool FIRST, bool O = true>
__device__ __forceinline__ void gemm_issue(float (&acc)[N / 2], Ctx& x, bool ready = false) {
  if (!ready) {
    if (N == 256) mbar_wait3(x.fullA(x.ra.s), x.ra.ph, x.fullB(x.rb.s), x.rb.ph);
    else mbar_wait2(x.fullA(x.ra.s), x.ra.ph, x.fullB(x.rb.s), x.rb.ph);
  }
  const uint32_t da = x.da0 + x.ra.s * (SLOT / 16), db = desc_lo(SB + OFF_B, 8192) + x.rb.s * (SLOT / 16);
  wgmma_fence();
#pragma unroll
  for (int k = 0; k < 4; k++) {
    const uint32_t a = da + (k >> 1) * (O ? 32 : x.k2) + (k & 1) * 2, ha = O ? HA64 : x.ha;
    if constexpr (N == 256) wgmma_ss_n256(acc, a, ha, db + 128 * k, !(FIRST && k == 0));
    else wgmma_ss_n128(acc, a, ha, db + 128 * k, !(FIRST && k == 0));
  }
  wgmma_commit();
}
template <int N>
__device__ __forceinline__ void gemm_next(Ctx& x) {
  x.pa = x.ra.s; x.pb = x.rb.s;
  if (N == 256) x.rb.s++;
  adv<NA>(x.ra); adv<NB>(x.rb);
}
template <int N>
__device__ __forceinline__ void gemm_release(Ctx& x, bool relA) {
  if (relA) x.releaseA(x.pa);
  x.releaseB(x.pb);
  if (N == 256) x.releaseB(x.pb + 1);
}
template <int N>
__device__ __forceinline__ void gemm_retire(Ctx& x, bool relA) { wgmma_wait<1>(); gemm_release<N>(x, relA); gemm_next<N>(x); }
template <bool O = true>
__device__ __forceinline__ void gemm_run(float (&acc)[64], Ctx& x, int n, int hold, int n4 = 0) {
  bool ready = false;
#pragma unroll 1
  for (; n > 0; n--) {
    gemm_issue<128, false, O>(acc, x, ready);
    const uint32_t pa = x.pa, pb = x.pb;
    gemm_next<128>(x);
    ready = mbar_probe2(x.fullA(x.ra.s), x.ra.ph, x.fullB(x.rb.s), x.rb.ph);
    wgmma_wait<1>();
    if (n > hold) x.releaseA(pa);
    x.releaseB(pb);
  }
}
__device__ __forceinline__ void gemm_end(float (&acc)[64], Ctx& x) { wgmma_wait<0>(); fence_regs(acc); gemm_release<128>(x, false); }

__device__ __forceinline__ void rows_load(uint4* r, uint32_t tile, const Ctx& x) {
#pragma unroll
  for (int q = 0; q < 4; q++) {
    const uint32_t row = x.warp * 16 + 4 * q + (x.lane >> 3);
    lds128(tile + row * 128 + (((x.lane & 7) ^ (row & 7)) << 4), r[q].x, r[q].y, r[q].z, r[q].w);
  }
}
__device__ __forceinline__ void rows_store(const uint4* r, uint4* g) {
#pragma unroll
  for (int q = 0; q < 4; q++) stg128(g + q * 1024, r[q]);
}
__device__ __forceinline__ void publish(int id, const Ctx& x) { __syncwarp(); if (x.lane == 0) mbar_arrive(x.sb + BAR_SIGP + id * 8); }
__device__ __forceinline__ uint32_t img_tag(uint32_t v, bool isx, int L, const Ctx& x) {
  const uint32_t mk = ((x.lane ^ (x.warp * 4)) & 7) ? 0u : img_mask(isx);
  return (v & ~mk) | (img_code(isx, L) & mk);
}
__device__ __forceinline__ void img_tag(uint4 (&r)[4], bool isx, int L, const Ctx& x) {
#pragma unroll
  for (int q = 0; q < 4; q++) { uint32_t& v = q == 0 ? r[q].x : (q == 1 ? r[q].y : (q == 2 ? r[q].z : r[q].w)); v = img_tag(v, isx, L, x); }
}
__device__ __forceinline__ void img_store(const uint4 (&r)[4], uint4* g) {
#pragma unroll
  for (int q = 0; q < 4; q++) stg128(g + q * 32, r[q]);
}
__device__ __forceinline__ void img_sts(const uint4 (&r)[4], uint32_t tile, const Ctx& x) {
#pragma unroll
  for (int q = 0; q < 4; q++) sts128(tile + x.so + q * 512, r[q].x, r[q].y, r[q].z, r[q].w);
}
__device__ __forceinline__ void img_load(uint32_t (&v)[16], uint32_t tile, const Ctx& x) {
#pragma unroll
  for (int q = 0; q < 4; q++) lds128(tile + x.so + q * 512, v[4 * q], v[4 * q + 1], v[4 * q + 2], v[4 * q + 3]);
}
__device__ __forceinline__ void img_unpack(float* a, const uint32_t (&v)[16]) {
#pragma unroll
  for (int q = 0; q < 16; q++) { a[4 * (q & 7) + 2 * (q >> 3)] = lo16(v[q]); a[4 * (q & 7) + 2 * (q >> 3) + 1] = hi16(v[q]); }
}

template <int N>
__device__ __forceinline__ void stats_acc(const float* a, float (&t)[4]) {
#pragma unroll
  for (int i = 0; i < N; i++) { t[i & 2] += a[i]; t[(i & 2) + 1] = fmaf(a[i], a[i], t[(i & 2) + 1]); }
}
__device__ __forceinline__ void stats_send(float (&t)[4], int L, const Ctx& x) {
  const unsigned seq = seq4(get_tag<false>(x.sb), L);
#pragma unroll
  for (int q = 0; q < 4; q++) t[q] = qsum(t[q]);
  if (x.c == 0) st_pkt(&g_stats[x.m()][x.w][x.j()][x.warp * 8 + x.g], __float_as_uint(t[0]), __float_as_uint(t[1]), __float_as_uint(t[2]), (__float_as_uint(t[3]) & ~15u) | seq);
}
__device__ __forceinline__ void out_epilogue(const float (&acc)[64], uint4 (&r1)[4], float (&t)[4], uint4* g, int L, Ctx& x) {
  const uint32_t t0 = x.aslot(x.ra.s), t1 = x.aslot(x.ra.s + 1 == NA ? 0 : x.ra.s + 1);
  if (L == 3) {
#pragma unroll
    for (int p = 0; p < 8; p++) {
      stsm4(x.maddr(p < 4 ? t0 : t1, (p & 3) * 2), pack2(acc[8 * p], acc[8 * p + 1]), pack2(acc[8 * p + 2], acc[8 * p + 3]),
            pack2(acc[8 * p + 4], acc[8 * p + 5]), pack2(acc[8 * p + 6], acc[8 * p + 7]));
      if ((p & 3) == 3) { uint4 r[4]; __syncwarp(); rows_load(r, p < 4 ? t0 : t1, x); rows_store(r, g + (p >> 2) * 8); }
    }
  } else {
    auto pack16 = [&](uint4 (&r)[4], const float* a) {
#pragma unroll
      for (int q = 0; q < 4; q++) { const float* u = a + 16 * (q & 1) + (q & 2); r[q] = make_uint4(pack2(u[0], u[1]), pack2(u[4], u[5]), pack2(u[8], u[9]), pack2(u[12], u[13])); }
    };
    uint4 r0[4];
    pack16(r0, acc);
    img_tag(r0, true, L + 1, x);
    img_store(r0, x.img(XBUF(L + 1), 0));
    const float z = bb_fence(x.goff);
    img_sts(r0, t0, x);
    pack16(r1, acc + 32);
    img_tag(r1, true, L + 1, x);
    img_sts(r1, t1, x);
    float u[4] = {z, z, z, z}, v[4] = {z, z, z, z};
    stats_acc<32>(acc, v);
    stats_acc<32>(acc + 32, u);
#pragma unroll
    for (int q = 0; q < 4; q++) t[q] = u[q] + v[q];
    mbar_wait2(x.fullB(x.rb.s), x.rb.ph, x.fullB(x.rb.s + 1), x.rb.ph);
    fence_async_smem();
    asm volatile("bar.sync %0, %1;" ::"r"(L == 1 ? x.w + 1 : 3), "r"(L == 1 ? 128 : 256) : "memory");
  }
}

struct Stats { float rstd0, rstd1; };
__device__ __forceinline__ Stats load_stats(int half, const Ctx& x) {
  const float2 u = lds64f(x.sb + OFF_MR + half * 256 + (x.warp * 8 + x.g) * 8);
  return {u.x, u.y};
}

template <int NH, int NK, class F>
__device__ __forceinline__ void hedgehog_scale(float* t, const Stats& st, const uint32_t* keep, F use) {
#pragma unroll
  for (int q = 0; q < 16 * NH; q++) t[q] *= ((q & 2) ? st.rstd1 : st.rstd0) * LOG2E;
  use();
  float m[4];
#pragma unroll
  for (int q = 0; q < 4 * NH; q++) {
    const float v = fmaxf(fmaxf(fabsf(t[4 * q]), fabsf(t[4 * q + 1])), fmaxf(fabsf(t[4 * q + 2]), fabsf(t[4 * q + 3])));
    m[q & 3] = q < 4 ? v : fmaxf(m[q & 3], v);
  }
  if (__builtin_expect(__any_sync(0xffffffffu, fmaxf(fmaxf(m[0], m[1]), fmaxf(m[2], m[3])) > 58.f), 0)) {
    float z[16 * NH + NK];
#pragma unroll
    for (int q = 0; q < 16 * NH + NK; q++) z[q] = q < 16 * NH ? t[q % (16 * NH)] : __uint_as_float(keep[q & 15]);
#pragma unroll 1
    for (int r = 0; r < 2 * NH; r++) {
      float hi = -INFINITY, lo = INFINITY;
#pragma unroll 1
      for (int i = 0; i < 16; i++) {
        const int k = (i & 6) * 2 + (i & 1) + (r & 1) * 2 + (r & 2) * 8;
        const float v = z[k];
        if (i < 8) { hi = fmaxf(hi, v); lo = fminf(lo, v); }
        else z[k] = v - fminf(fmaxf(v, lo), hi);
        if (i == 7) {
#pragma unroll 1
          for (int d = 1; d <= 2; d++) { hi = fmaxf(hi, __shfl_xor_sync(0xffffffffu, hi, d)); lo = fminf(lo, __shfl_xor_sync(0xffffffffu, lo, d)); }
          const float mid = 0.5f * hi + 0.5f * lo;
          hi = fmaxf(hi - 58.f, mid); lo = fminf(lo + 58.f, mid);
        }
      }
    }
#pragma unroll
    for (int q = 0; q < 16 * NH; q++) t[q] = z[q];
    use();
  }
}
__device__ __forceinline__ void dual_exp(const float* t, uint32_t (&f)[18], int never) {
  float e[KSPLIT];
#pragma unroll
  for (int q = 0; q < KSPLIT; q++) e[q] = ex2(q < 16 ? t[q] : -t[q & 15]);
  while (never < 0) {
#pragma unroll
    for (int i = 0; i < KSPLIT; i += 4) asm volatile("ld.shared.v4.f32 {%0,%1,%2,%3}, [%4];" : "=f"(e[i]), "=f"(e[i + 1]), "=f"(e[i + 2]), "=f"(e[i + 3]) : "r"(never + i) : "memory");
    never += __float_as_int(e[0]);
  }
#pragma unroll
  for (int q = 0; q < KSPLIT; q += 2) f[q >> 1] = pack2(e[q], e[q + 1]);
#pragma unroll
  for (int q = KSPLIT; q < 32; q += 2) f[q >> 1] = q < 16 ? pack2(ex2(t[q]), ex2(t[q + 1])) : pack2(ex2(-t[q & 15]), ex2(-t[(q & 15) + 1]));
#pragma unroll
  for (int sg = 0; sg < 2; sg++) {
    const uint32_t* u = f + 8 * sg;
    const uint32_t a = add2(add2(u[0], u[2]), add2(u[4], u[6])), b = add2(add2(u[1], u[3]), add2(u[5], u[7]));
    f[16 + sg] = add2(__byte_perm(a, b, 0x5410), __byte_perm(a, b, 0x7632));
  }
}
__device__ __forceinline__ void dual_exp_rcp(const float* t, uint32_t* f) {
#pragma unroll
  for (int q = 0; q < 8; q++) {
    const float a = ex2(t[2 * q]), b = ex2(t[2 * q + 1]), r = rcp(a * b);
    f[q] = pack2(a, b); f[8 + q] = pack2(r * b, r * a);
  }
}
__device__ __forceinline__ void cta_bar() { asm volatile("bar.sync 3, 256;" ::: "memory"); }

template <int N> __device__ __forceinline__ void pin(const uint32_t* v, uint32_t addr) {
#pragma unroll
  for (int i = 0; i < N; i += 4)
    asm volatile("{\n.reg .pred p;\nsetp.eq.u32 p, %0, 0;\n@p st.shared.v4.u32 [%0], {%1,%2,%3,%4};\n}" ::"r"(addr), "r"(v[i]), "r"(v[i + 1]), "r"(v[i + 2]), "r"(v[i + 3]) : "memory");
}

__device__ __forceinline__ void consumer(const Params& P, uint32_t sb, int w, unsigned vb) {
  Ctx x;
  x.w = w;
  x.ab = sb + OFF_A + w * 8192; x.da0 = desc_lo(SB + OFF_A, 16) + w * 512;
  x.lane = threadIdx.x & 31; x.warp = __shfl_sync(0xffffffffu, (threadIdx.x >> 5) & 3, 0); x.g = x.lane >> 2; x.c = x.lane & 3;
  x.goff = (cta_m(vb) * 128 + w) * 128 + cta_j(vb) * 16;
  asm volatile("" : "+r"(x.goff));
  x.elected = (threadIdx.x & 127) == 0;
  x.ra = {0, 0}; x.rb = {0, 0}; x.pa = x.pb = 0;
  {
    const uint32_t row = x.warp * 16 + (x.lane & 15);
    x.mrow = row * 128; x.mxor = row & 7; x.mhi = x.lane >> 4;
  }
  const int goff = x.goff;
  x.ip = solid(&g_img[0][x.m()][2 * x.j()][w * 512 + x.oo()]);
  x.so = solid(16 * x.oo());
  uint4 r1[4];
  float ts[4] = {0.f, 0.f, 0.f, 0.f};
#pragma unroll
  for (int i = 0; i < 4; i++) r1[i] = make_uint4(0, 0, 0, 0);
  TSW(0);
  mbar_wait3(x.fullA(0), 0, x.fullB(0), 0);
#pragma unroll 1
  for (int L = 0; L < 4; L++) {
    float acc[64];
    constexpr uint32_t dcs = desc_lo(SB + OFF_CS, 0);
    if ((L & 1) == 0) {
    float kv[128];
    x.ha = L ? HA64 : HA128; x.k2 = L ? 32 : 4;
    gemm_issue<256, true, false>(kv, x, true); gemm_next<256>(x);
    {
      int i = 1;
#pragma unroll 1
      for (int seg = L ? NS - 1 : 0; seg <= NS; seg++) {
        const int end = seg < NS ? (L == 0 ? 3 + SA * ((x.j() + SW * w) & 3) + SB_ * seg : XA + 1) : 14 + L;
#pragma unroll 1
        do {
          gemm_issue<256, false, false>(kv, x);
          gemm_retire<256>(x, true);
          i++;
          if (i == 5) TSL_(8);
          if (i == 11) TSL_(10);
        } while (i != end);
        if (seg < NS && L == 0) {
          uint32_t v[16];
          float a[32];
#pragma unroll
          for (int q = 0; q < 4; q++) ldsm4(x.maddr(x.aslot(x.pa), 2 * q), reinterpret_cast<uint32_t (&)[4]>(v[4 * q]));
#pragma unroll
          for (int q = 0; q < 16; q++) { a[2 * q] = lo16(v[q]); a[2 * q + 1] = hi16(v[q]); }
          stats_acc<32>(a, ts);
          fence_regs(ts);
          wg_bar(w);
        }
        if (seg == NS - 1) {
          if (L > 0) { img_store(r1, x.img(XBUF(L), 1)); publish(2, x); }
          mbar_wait(sb + BAR_EPOCH, 0);
          stats_send(ts, L, x);
        }
      }
    }
      const Ring kt = x.ra;
      if (L == 0) adv<NA>(x.ra);
#pragma unroll 1
      for (int h = L; h < 2; h++) {
        float d[16];
        mbar_wait2(x.fullA(kt.s), kt.ph, sb + BAR_WPHI, 0);
        wgmma_fence();
#pragma unroll
        for (int q = 0; q < 2; q++) wgmma_ss_n32(d, x.da0 + kt.s * (SLOT / 16) + h * 4 + q * 2, desc_lo(SB + OFF_S + 4096, 512) + w * 256 + h * 128 + q * 64, q);
        wgmma_commit();
        gemm_issue<256, false, false>(kv, x);
        gemm_retire<256>(x, true);
        if (h) x.releaseA(kt.s);
        fence_regs(d);
        uint4* dst = &g_wf[1][x.j()][x.m()][w * 512 + (x.warp * 16 + x.g) * 8 + ((h * 4 + x.c) ^ x.g)];
        dst[0] = make_uint4(pack2(d[0], d[1]), pack2(d[4], d[5]), pack2(d[8], d[9]), pack2(d[12], d[13]));
        dst[64] = make_uint4(pack2(d[2], d[3]), pack2(d[6], d[7]), pack2(d[10], d[11]), pack2(d[14], d[15]));
      }
      const uint32_t dm = desc_lo(SB + OFF_MA, 0) + w * 64;
      mbar_wait2(sb + BAR_STAT, 0, sb + BAR_CS, 0);
      wgmma_fence();
      wgmma_r1_n256(kv, dm, dcs + 96, 1);
      wgmma_commit();
      const Stats st = load_stats(w, x);
      mbar_wait2(x.fullA(x.ra.s), x.ra.ph, x.fullB(x.rb.s), x.rb.ph);
      wgmma_wait<0>();
      fence_regs(kv);
      gemm_release<256>(x, true);
      TSL_(2);
      uint32_t P0[32], P1[32], PH[32];
#pragma unroll
      for (int t = 0; t < 16; t++) { P0[t] = pack2(kv[4 * t] * st.rstd0, kv[4 * t + 1] * st.rstd0); P1[t] = pack2(kv[4 * t + 2] * st.rstd1, kv[4 * t + 3] * st.rstd1); }
      pin<16>(P0, x.mrow + 16);
      {
#pragma unroll
        for (int q = 0; q < 4; q++) sts128((x.warp < 3 ? sb + OFF_T + w * 12288 + x.warp * 4096 : sb + OFF_S + 16384 + w * 2048) + x.lane * 16 + q * 512, P1[4 * q], P1[4 * q + 1], P1[4 * q + 2], P1[4 * q + 3]);
      }
      wgmma_fence();
      wgmma_r1_n128(acc, dm, dcs, 0);
      gemm_issue<128, false, false>(acc, x, true); gemm_next<128>(x);
      TSL_(3);
#pragma unroll
      for (int s = 0; s < 4; s++) {
#pragma unroll
        for (int t = 16 + 8 * (s & 1); t < 24 + 8 * (s & 1); t++) {
          if (s < 2) P1[t] = movm(pack2(kv[4 * t + 2] * st.rstd1, kv[4 * t + 3] * st.rstd1));
          else P0[t] = movm(pack2(kv[4 * t] * st.rstd0, kv[4 * t + 1] * st.rstd0));
        }
        if (s < 3) { gemm_issue<128, false, false>(acc, x); gemm_retire<128>(x, true); }
        if (s == 1) {
          if (x.warp < 3) {
#pragma unroll
            for (int q = 4; q < 8; q++) sts128(sb + OFF_T + w * 12288 + x.warp * 4096 + x.lane * 16 + q * 512, P1[4 * q], P1[4 * q + 1], P1[4 * q + 2], P1[4 * q + 3]);
          } else {
            uint4* dst = &g_halo[x.m()][x.j()][w][x.lane];
#pragma unroll
            for (int q = 0; q < 8; q++) dst[q * 32] = make_uint4(P1[4 * q], P1[4 * q + 1], P1[4 * q + 2], P1[4 * q + 3]);
          }
          publish(3, x);
          gemm_issue<128, false, false>(acc, x);
          gemm_retire<128>(x, true);
        }
      }
      TSL_(4);
      gemm_run<false>(acc, x, 10, 0);
      publish(0, x);
      gemm_issue<128, false, false>(acc, x);
      {
        wg_bar(w);
        uint32_t tr = sb + OFF_T + w * 12288 + (x.warp - 1) * 4096;
        if (x.warp == 0) {
          tr = x.m() > 0 ? sb + OFF_S + 8192 + w * 4096 : tr + 4096;
          if (x.m() > 0) mbar_wait(sb + BAR_HALO, L >> 1);
        }
#pragma unroll
        for (int q = 0; q < 8; q++) lds128(tr + x.lane * 16 + q * 512, PH[4 * q], PH[4 * q + 1], PH[4 * q + 2], PH[4 * q + 3]);
      }
      gemm_retire<128>(x, false);
      gemm_end(acc, x);
      TSL_(5);
      const bool first = (x.m() == 0) && (x.warp == 0);
      const bool hi0 = 2 * x.c > x.g, hi1 = 2 * x.c + 1 > x.g;
      const uint32_t mhi = (hi0 ? 0xFFFFu : 0u) | (hi1 ? 0xFFFF0000u : 0u);
      const uint32_t valid = first ? ~mhi : ~0u;
      const float sc0 = st.rstd0 * (0.17677669529663687f * LOG2E), sc1 = st.rstd1 * (0.17677669529663687f * LOG2E);
      uint32_t xr[2][16];
#pragma unroll
      for (int hp = 0; hp < 2; hp++) {
        const uint32_t tile = x.aslot(x.held(hp));
        uint32_t px[2], py[2];
        float s[2][3][4];
#pragma unroll
        for (int u = 0; u < 2; u++) {
#pragma unroll
          for (int q = 0; q < 12; q++) s[u][q >> 2][q & 3] = 0.f;
#pragma unroll
          for (int ks = 0; ks < 2; ks++) {
            const int t = 8 * hp + 4 * u + 2 * ks;
            const uint32_t a0 = pack2(acc[4 * t], acc[4 * t + 1]), a1 = pack2(acc[4 * t + 2], acc[4 * t + 3]);
            const uint32_t a2 = pack2(acc[4 * t + 4], acc[4 * t + 5]), a3 = pack2(acc[4 * t + 6], acc[4 * t + 7]);
            mma16816(s[u][0], a0, a1, a2, a3, PH[t], PH[t + 1]);
            mma16816(s[u][1], a0, a1, a2, a3, P0[t], P0[t + 1]);
            mma16816(s[u][2], a0, a1, a2, a3, P1[t], P1[t + 1]);
          }
        }
        float e[2][4], big = 0.f;
#pragma unroll
        for (int u = 0; u < 2; u++) {
          e[u][0] = (hi0 ? s[u][0][0] : s[u][1][0]) * sc0; e[u][1] = (hi1 ? s[u][0][1] : s[u][1][1]) * sc0;
          e[u][2] = (hi0 ? s[u][1][2] : s[u][2][2]) * sc1; e[u][3] = (hi1 ? s[u][1][3] : s[u][2][3]) * sc1;
          big = fmaxf(big, fmaxf(fmaxf(fabsf(e[u][0]), fabsf(e[u][1])), fmaxf(fabsf(e[u][2]), fabsf(e[u][3]))));
          px[u] = pack2(ex2(e[u][0]), ex2(e[u][1])) & valid; py[u] = pack2(ex2(e[u][2]), ex2(e[u][3]));
        }
        if (__builtin_expect(__any_sync(0xffffffffu, big > 58.f), 0)) {
#pragma unroll
          for (int q = 0; q < 4; q++) {
            float v0 = e[q >> 1][2 * (q & 1)], v1 = e[q >> 1][2 * (q & 1) + 1];
            if (first && !(q & 1)) { if (hi0) v0 = -INFINITY; if (hi1) v1 = -INFINITY; }
            float r = fmaxf(v0, v1);
            r = fmaxf(r, __shfl_xor_sync(0xffffffffu, r, 1)); r = fmaxf(r, __shfl_xor_sync(0xffffffffu, r, 2));
            ((q & 1) ? py : px)[q >> 1] = pack2(ex2(v0 - r), ex2(v1 - r));
          }
        }
        float r[2][2];
#pragma unroll
        for (int u = 0; u < 2; u++) {
          float d[4] = {0.f, 0.f, 0.f, 0.f};
          mma1688(d, px[u], py[u], 0x3F803F80u);
          r[u][0] = rcp(d[0]); r[u][1] = rcp(d[2]);
        }
        uint32_t o[8][2];
        uint4 ro[4];
#pragma unroll
        for (int q = 0; q < 8; q++) {
          float d[4] = {0.f, 0.f, 0.f, 0.f};
          const int t = 16 + 8 * hp + q, u = q >> 2;
          mma16816(d, px[u] & mhi, 0u, px[u] & ~mhi, py[u] & mhi, PH[t], P0[t]);
          mma1688(d, 0u, py[u] & ~mhi, P1[t]);
          o[q][0] = pack2(d[0] * r[u][0], d[1] * r[u][0]); o[q][1] = pack2(d[2] * r[u][1], d[3] * r[u][1]);
        }
#pragma unroll
        for (int q = 0; q < 4; q++) ro[q] = make_uint4(o[4 * (q & 1)][q >> 1], o[4 * (q & 1) + 1][q >> 1], o[4 * (q & 1) + 2][q >> 1], o[4 * (q & 1) + 3][q >> 1]);
        img_tag(ro, false, 0, x);
        img_store(ro, x.img(0, hp));
        if (hp == 0) bb_fence(x.goff);
        if (hp == 0) {
#pragma unroll
          for (int i = 0; i < 2; i++) {
            const uint32_t ti = x.aslot(x.held(i));
            if (L) img_load(xr[i], ti, x);
            else {
#pragma unroll
              for (int q = 0; q < 4; q++) ldsm4(x.maddr(ti, 2 * q), reinterpret_cast<uint32_t (&)[4]>(xr[i][4 * q]));
            }
          }
          __syncwarp();
        }
        img_sts(ro, tile, x);
      }
      if (L == 0) {
#pragma unroll
        for (int hp = 0; hp < 2; hp++) {
          uint32_t v[16];
#pragma unroll
          for (int q = 0; q < 16; q++) asm volatile("mov.b32 %0, %1;" : "=r"(v[(q & 1) * 8 + (q >> 1)]) : "r"(xr[hp][q]));
#pragma unroll
          for (int q = 0; q < 16; q++) xr[hp][q] = v[q];
        }
      }
      img_unpack(acc, xr[0]); img_unpack(acc + 32, xr[1]);
    } else {
      float kv[128];
      float (&kv0)[64] = reinterpret_cast<float (&)[64]>(kv[0]);
      float (&kv1)[64] = reinterpret_cast<float (&)[64]>(kv[64]);
      auto mma8 = [&](uint32_t as, uint32_t bs, int i, bool fence) {
        const uint32_t da = desc_lo(SB + OFF_A, 16) + as * (SLOT / 16), db = desc_lo(SB + OFF_B, 8192) + bs * (SLOT / 16);
        if (fence) wgmma_fence();
#pragma unroll
        for (int k = 0; k < 4; k++) {
          wgmma_ss_n128(kv0, da + (k >> 1) * 32 + (k & 1) * 2, HA64, db + 128 * k, i + k);
          wgmma_ss_n128(kv1, da + 512 + (k >> 1) * 32 + (k & 1) * 2, HA64, db + 128 * k, i + k);
        }
        wgmma_commit();
      };
      constexpr uint32_t dm = desc_lo(SB + OFF_MB, 0);
      auto relB = [&](uint32_t s) { mbar_arrive_n(sb + BAR_EMPTYB + s * 8, 2); };
      auto skip = [&]() {
#pragma unroll
        for (int q = 0; q < 6 - NJ; q++) adv<NA>(x.ra);
        x.rb.s = w ? (2 + NJ) % 6 : 4;
        if (!w && NJ < 4) x.rb.ph ^= 1;
      };
      static_assert(NA == 5 && NB == 6, "ring arithmetic");
      mma8(x.ra.s, x.rb.s + w, 0, true);
      img_store(r1, x.img(XBUF(L), 1));
      gemm_next<256>(x);
#pragma unroll 1
      for (int i = 1; i < NJ; i++) {
        mbar_wait2(x.fullA(x.ra.s), x.ra.ph, x.fullB(x.rb.s + w), x.rb.ph);
        mma8(x.ra.s, x.rb.s + w, 1, true);
        if (i == 1) { stats_send(ts, L, x); publish(2, x); }
        wgmma_wait<1>();
        if (x.elected) { x.releaseA(x.pa); relB(x.pb + w); }
        gemm_next<256>(x);
      }
      if (w) {
        wgmma_wait<0>();
        if (x.elected) { x.releaseA(x.pa); relB(x.pb + 1); }
        skip();
        asm volatile("bar.sync 7, 256;" ::: "memory");
      }
      TSL_(8);
      {
        const int t = lane_id() + 32 * x.warp;
        uint32_t mask = t < 2 ? ((w ? (t ? 0xFF3Fu : 0x3FFFu) : 0xFFFFu) >> (NJ - 1)) & (w ? ~1u : ~0u) : 0u, cnt = 1 + t;
        bool ready = false;
#pragma unroll 1
        for (int i = NJ; i < 16; i++) {
          if (!ready) mbar_wait2(x.fullA(x.ra.s), x.ra.ph, x.fullB(x.rb.s), x.rb.ph);
          mma8(x.ra.s, x.rb.s, 1, true);
          const uint32_t bar = sb + (t ? BAR_EMPTYB + x.pb * 8 : BAR_EMPTYA + x.pa * 8);
          gemm_next<128>(x);
          if (w && (i | 4) == 15) x.rb.s = 4;
          ready = mbar_probe2(x.fullA(x.ra.s), x.ra.ph, x.fullB(x.rb.s), x.rb.ph);
          wgmma_wait<1>();
          if (mask & 1) mbar_arrive_n(bar, cnt);
          mask >>= 1; cnt = 2;
          if (i == 8 && w) asm volatile("bar.arrive 9, 256;" ::: "memory");
          if (i == 9) TSL_(10);
        }
        mbar_wait2(sb + BAR_STAT, 1, sb + BAR_CS + 8, 0);
        wgmma_fence();
        wgmma_r1_n128(kv0, dm, dcs + 96 + 96 * w, 1);
        wgmma_r1_n128(kv1, dm + 64, dcs + 96 + 96 * w, 1);
        wgmma_commit();
        if (w == 0) asm volatile("bar.arrive 7, 256;" ::: "memory");
        wgmma_wait<1>();
        if (mask & 1) mbar_arrive_n(sb + (t ? BAR_EMPTYB + x.pb * 8 : BAR_EMPTYA + x.pa * 8), 2);
      }
      const Stats s0 = load_stats(0, x), s1 = load_stats(1, x), st = w ? s1 : s0;
      if (w == 0) skip();
      const uint32_t h0 = x.held(0), h1 = x.held(1);
      auto vreg = [&](int ks) { return ks < 6 ? OFF_A + (ks < 3 ? h0 * SLOT : h1 * SLOT - 15360) + ks * 5120 : OFF_S + 2048 + ks * 5120; };
      uint32_t tV[2], uu[4];
#pragma unroll
      for (int hf = 0; hf < 2; hf++) {
        tV[hf] = sb + vreg(4 * hf + x.warp) + ((x.lane >> 3) & 1) * 2560 + (x.lane & 7) * 16 + x.mhi * 128;
        const float i0 = rcp(hf ? s1.rstd0 : s0.rstd0), i1 = rcp(hf ? s1.rstd1 : s0.rstd1);
        const uint32_t h = pack2(i0, i1);
        uu[2 * hf] = pack2(lo16(h), i0 - lo16(h)); uu[2 * hf + 1] = pack2(hi16(h), i1 - hi16(h));
        asm volatile("" : "+r"(tV[hf]), "+r"(uu[2 * hf]), "+r"(uu[2 * hf + 1])::"memory");
      }
      wgmma_wait<0>();
      fence_regs(kv);
      TSL_(2);
      if (w == 0) {
        uint32_t f[2][18], ad[4];
#pragma unroll
        for (int q = 0; q < 18; q++) f[1][q] = 0u;
#pragma unroll
        for (int q = 0; q < 4; q++) ad[q] = x.maddr(sb + OFF_S, 2 * q);
        auto norm = [&](int un) {
          uint32_t* u = f[un & 1];
          const Stats& sn = un ? s1 : s0;
#pragma unroll
          for (int sg = 0; sg < 2; sg++) {
            uint32_t v = u[16 + sg];
            v = add2(v, __shfl_xor_sync(0xffffffffu, v, 1)); v = add2(v, __shfl_xor_sync(0xffffffffu, v, 2));
            const float a = rcp(lo16(v)) * sn.rstd0, b = rcp(hi16(v)) * sn.rstd1;
            const uint32_t r0 = pack2(a, a), r1_ = pack2(b, b);
#pragma unroll
            for (int q = 8 * sg; q < 8 * sg + 8; q++) u[q] = mul2(u[q], (q & 1) ? r1_ : r0);
#pragma unroll
            for (int q = 2 * sg; q < 2 * sg + 2; q++) stsm4(ad[q] + un * 8192, u[4 * q], u[4 * q + 1], u[4 * q + 2], u[4 * q + 3]);
          }
        };
        auto move = [&](int dst, int src) {
#pragma unroll
          for (int q = 0; q < 16; q++) asm volatile("mov.b32 %0, %1;" : "=f"(kv[dst + q]) : "f"(src ? kv[src + q] : 0.f));
        };
        hedgehog_scale<1, 0>(kv, s0, nullptr, [] {});
        uint32_t step = 0;
#pragma unroll 1
        for (int h = 0;; h++) {
          norm(1);
          dual_exp(kv, f[0], x.goff);
          hedgehog_scale<1, KEEP>(kv + 64, s1, f[1], [] {});
          if (h == 2) asm volatile("bar.sync 9, 256;" ::: "memory");
#pragma unroll
          for (int q = 0; q < 4; q++) ad[q] += step;
          norm(0);
          dual_exp(kv + 64, f[1], x.goff);
#pragma unroll
          for (int q = 0; q < 16; q++) kv[q] = kv[16 + q];
          hedgehog_scale<1, KEEP>(kv, s0, f[0], [] {});
          step = SLOT;
          if (h == 0) { move(64, 80); move(16, 32); }
          else if (h == 1) { move(64, 96); move(16, 48); step = OFF_B + SLOT - OFF_S; }
          else if (h == 2) { move(64, 112); move(16, 0); }
          else break;
        }
        norm(1);
        TSL_(3);
      } else {
        wg_bar(w);
#pragma unroll
        for (int hf = 0; hf < 2; hf++) {
          stsm4(tV[hf] + 512 + x.mhi * 512, uu[2 * hf], uu[2 * hf + 1], uu[2 * hf], uu[2 * hf + 1]);
          stsm4(tV[hf] + 1792 + x.mhi * 512, uu[2 * hf], uu[2 * hf + 1], uu[2 * hf], uu[2 * hf + 1]);
#pragma unroll
          for (int q = 0; q < 8; q++) {
            const float* u = kv + 64 * hf + 8 * q;
            stsm4(tV[hf] + (q >> 1) * 640 + (q & 1) * 256, pack2(u[0], u[1]), pack2(u[2], u[3]), pack2(u[4], u[5]), pack2(u[6], u[7]));
          }
        }
        TSL_(3);
      }
      {
        float d[2][20];
        uint4* dst = &g_kvpart[x.j()][w * 4 + x.warp][0][x.m() * 32 + x.lane];
        unsigned* dz = reinterpret_cast<unsigned*>(&g_kvpart[x.j()][w * 4 + x.warp][x.c & 1][512]) + x.m() * 8 + x.g;
        fence_async_smem();
        cta_bar();
        TSL_(11);
        uint32_t pk[9];
        auto prep = [&](float (&u)[20]) {
          fence_regs(u);
#pragma unroll
          for (int q = 0; q < 8; q++) pk[q] = pack2(u[((q >> 1) & 2) + 4 * (q & 3)], u[((q >> 1) & 2) + 4 * (q & 3) + 1]);
          pk[8] = __float_as_uint((x.c & 1) ? u[18] + u[19] : u[16] + u[17]);
#pragma unroll
          for (int q = 0; q < 9; q += 4) pk[q] = (pk[q] & ~1u) | (L == 1);
        };
        auto send = [&](int hp) {
          st_v4(dst + hp * 16 * 544, pk[0], pk[1], pk[2], pk[3]); st_v4(dst + (hp * 16 + 1) * 544, pk[4], pk[5], pk[6], pk[7]);
          st_flag(dz + hp * 16 * 544 * 4, pk[8]);
        };
        wgmma_fence();
#pragma unroll
        for (int q = 0; q < 17; q++) {
          if (q < 16) wgmma_ss_n40_tt(d[q >> 3], desc_lo(SB + (q < 8 ? OFF_S : OFF_B + 2 * SLOT), 1024) + w * (SLOT / 16) + 128 * (q & 7), desc_lo(SB + vreg(q & 7), 2560) + (w + (q >> 3) * 2) * 40, q & 7);
          else wgmma_r1_n128(acc, dm + w * 64, dcs, 0);
          if (q == 7 || q == KVS || q == 16) wgmma_commit();
          if (q == KVS) { mbar_wait2(x.fullA(x.ra.s), x.ra.ph, x.fullB(x.rb.s), x.rb.ph); wgmma_wait<1>(); prep(d[0]); send(0); bb_fence(x.goff); wgmma_fence(); }
        }
        gemm_issue<128, false>(acc, x, true); gemm_next<128>(x);
        wgmma_wait<1>();
        x.releaseA(h0); x.releaseA(h1); x.releaseB(2); x.releaseB(3);
        if (x.lane == 0) mbar_arrive(sb + BAR_SIGT);
        prep(d[1]);
        TSL_(4);
#pragma unroll 1
        for (int seg = 0; seg < 2; seg++) {
          const int n0 = w ? PS1 : PS0;
          gemm_run(acc, x, seg ? 15 - n0 : n0, seg, seg ? L : 0);
          if (seg == 0) send(1);
        }
      }
      gemm_end(acc, x);
      TSL_(5);
      {
        float dp[2][20], dn[2][20];
        uint32_t f[4][16];
        auto mma = [&](int h) {
          if (!(h & 1)) mbar_wait(sb + BAR_KV + h * 4, L >> 1);
          if (h == 0) TSL_(9);
          const uint32_t db = desc_lo(SB + OFF_S + h * 5120, 128);
          const uint32_t (&a)[16] = f[h];
          wgmma_fence();
          wgmma_rs_n40(dp[h & 1], a[0], a[1], a[2], a[3], db, 0);
          wgmma_rs_n40(dn[h & 1], a[8], a[9], a[10], a[11], db + 160, 0);
          wgmma_rs_n40(dp[h & 1], a[4], a[5], a[6], a[7], db + 80, 1);
          wgmma_rs_n40(dn[h & 1], a[12], a[13], a[14], a[15], db + 240, 1);
          wgmma_commit();
        };
        uint32_t xr[16];
        auto fin = [&](int h) {
          const uint32_t tile = x.aslot(x.held(h >> 1));
          if (!(h & 1)) img_load(xr, tile, x);
          float (&u)[20] = dp[h & 1];
          float (&v)[20] = dn[h & 1];
          fence_regs(u); fence_regs(v);
#pragma unroll
          for (int r = 0; r < 2; r++) {
            const float sp = u[16 + 2 * r], sn = v[16 + 2 * r];
            const float id = rcp(fmaf(fmaf(sp, L == 1 ? 0.065536f * 128 / 129 : 0.065536f, u[17 + 2 * r]), sn, v[17 + 2 * r] * sp)), aa = sn * id, cc = sp * id;
            uint32_t o[4];
#pragma unroll
            for (int t = 0; t < 4; t++) o[t] = pack2(fmaf(u[4 * t + 2 * r], aa, v[4 * t + 2 * r] * cc), fmaf(u[4 * t + 2 * r + 1], aa, v[4 * t + 2 * r + 1] * cc));
            o[2 * r + (h & 1)] = img_tag(o[2 * r + (h & 1)], false, 1, x);
            stg128(x.img(0, h >> 1) + r * 64 + (h & 1) * 32, make_uint4(o[0], o[1], o[2], o[3]));
            sts128(tile + r * 1024 + (h & 1) * 512 + x.so, o[0], o[1], o[2], o[3]);
          }
          if (h & 1) { if (h == 1) publish(0, x); img_unpack(acc + 16 * (h - 1), xr); }
        };
        auto ex = [&](int h) { dual_exp_rcp(acc + 16 * h, f[h]); };
        Stats sq = st;
#pragma unroll
        for (int h = 0; h < 4; h += 2) {
          hedgehog_scale<2, 0>(acc + 16 * h, sq, nullptr, [&] { ex(h); });
          mma(h);
          ex(h + 1); wgmma_wait<0>(); fin(h);
          if (h == 0) bb_fence(x.goff);
          mma(h + 1);
          wgmma_wait<0>(); fin(h + 1);
          if (h == 0) sq.rstd1 += bb_fence(x.goff);
        }
      }
    }
    mbar_wait(x.fullB(x.rb.s), x.rb.ph);
    fence_regs(acc);
    fence_async_smem();
    wg_bar(w);
    TSL_(6);
    rewind2<NA>(x.ra);
    gemm_issue<128, false>(acc, x, true); gemm_next<128>(x);
    uint4* out = solid(P.out + goff + (x.warp * 16 + (x.lane >> 3)) * 256 + (x.lane & 7));
#pragma unroll 1
    for (int seg = 0; seg < 2; seg++) {
      const int nt = L == 3 ? TSK : XN;
      gemm_run(acc, x, seg ? nt : 15 - nt, seg, 10 + L);
      if (L < 3) { if (seg == 0) publish(1, x); }
      else if (seg != w) {
        if (w) asm volatile("bar.sync 6, 256;" ::: "memory"); else asm volatile("bar.arrive 6, 256;" ::: "memory");
      }
    }
    gemm_end(acc, x);
    TSL_(7);
    rewind2<NA>(x.ra);
    out_epilogue(acc, r1, ts, out, L, x);
    TSL_(13);
  }
}

typedef unsigned long long u64;
template <class T> __device__ __forceinline__ T* early(T* p) { return (T*)__shfl_xor_sync(0xffffffffu, (u64)p, 1); }
__device__ __forceinline__ void pause(uint32_t GAP) {
  if (GAP) { uint32_t t0, t; asm volatile("mov.u32 %0, %%clock;" : "=r"(t0)); do { asm volatile("mov.u32 %0, %%clock;" : "=r"(t)); } while (t - t0 < GAP); }
}
__device__ __forceinline__ u64 order_table0(int j) { return (j & 4) ? 0x543210FEDCBA9876ull : 0xDCBA9876543210FEull; }
__device__ __forceinline__ void order_tables(u64& t1, u64& t2, int j) {
#pragma unroll 1
  for (int i = 6; i >= 0; i--) { const u64 o = 2 * other_tile(i, j); t1 = t1 << 4 | o | (o + 1) << 28; t2 = t2 << 8 | (o * 17 + 16); }
  const u64 own = 2 * j * 17 + 16;
  t1 = t1 << 8 | own; t2 |= own << 56;
}

__device__ __forceinline__ void b_producer(const Params& P, uint32_t sb, unsigned vb) {
  const int j = cta_j(vb);
  u64 t1 = 0, t2 = 0;
  Ring r = {PRE_B % NB, PRE_B < NB};
#pragma unroll 1
  for (int sg = 0; sg < 20; sg++) {
    const int L = sg / 5, p = sg - 5 * L, wt = L & 1;
    if (sg == 1) order_tables(t1, t2, j);
    int n = p >= 3 ? 16 : (wt ? (p ? 16 - NJ : 2 * NJ) : (p ? 0 : (L ? 32 : 32 - PRE_B)));
    u64 tab = p == 3 ? t2 : (sg == 0 ? order_table0(j) >> (2 * PRE_B) : (p == 1 || p == 2 ? t1 >> (4 * NJ) : t1));
    const CUtensorMap* tm = p == 4 ? &P.mwo[wt] : &P.mw[wt ? 1 : L];
    const uint4* img = &g_wf[p != 3][j][0][0];
    int col = (p >= 3 ? 0 : (p == 2 ? 2048 : 1024)) + 128 * j;
    const int flip = p == 0 ? 3072 : 0;
    const bool fold = wt && p != 4;
    if (sg == 5 || sg == 8) { mbar_wait(sb + (sg == 5 ? BAR_WPHI : BAR_CS + 8), sg == 5); fence_async_global(); }
#pragma unroll 1
    for (; n > 0; n--) {
      const int kb = (int)tab & 15;
      mbar_wait(sb + BAR_EMPTYB + r.s * 8, r.ph);
      if (elect()) {
        mbar_expect_tx(sb + BAR_FULLB + r.s * 8, SLOT);
        if (fold && col < 2048) bulk_load(sb + OFF_B + r.s * SLOT, img + kb * 1024, SLOT, sb + BAR_FULLB + r.s * 8);
        else tma_load_w(sb + OFF_B + r.s * SLOT, tm, sb + BAR_FULLB + r.s * 8, col, kb);
      }
      adv<NB>(r);
      if (p == 2 && (n | 4) == 5) r.s = 4;
      col ^= flip;
      if (!(col & flip & 2048)) tab >>= 4;
    }
  }
}

__device__ __forceinline__ void kv_images(uint32_t sb, int L, int j, unsigned tag, unsigned& ph) {
  const int lane = threadIdx.x & 31;
  auto hinted = [&](int h) { return __all_sync(0xffffffffu, (int)(ld_flag(&g_jflag[h][j][lane & 15]) - (tag * 4 + L)) >= 0); };
  auto load = [&](int h) { if (elect()) { mbar_expect_tx(sb + BAR_LAND + 48 + h * 8, 10240); bulk_load(sb + OFF_S + h * 10240, &g_kvfin[j][8 * h][0], 10240, sb + BAR_LAND + 48 + h * 8); } };
  bool sent = false;
#pragma unroll 1
  for (int h = 0, it = 0; h < 2;) {
    if (++it > (1 << 22)) __trap();
    if (h == 0 || !sent) {
      if (!hinted(h)) continue;
      load(h);
    }
    if (KI && h == 0 && !sent && hinted(1)) { load(1); sent = true; }
    mbar_wait(sb + BAR_LAND + 48 + h * 8, (ph >> h) & 1);
    ph ^= 1u << h;
    uint32_t a = 1u, o = 0u;
#pragma unroll
    for (int u = 0; u < 20; u++) { const uint32_t v = __float_as_uint(lds32f(sb + OFF_S + h * 10240 + u * 512 + lane * 16)); a &= v; o |= v; }
    if (h) sent = false;
    if (__all_sync(0xffffffffu, (L == 1 ? a : ~o) & 1u)) {
      if (elect()) mbar_arrive(sb + BAR_KV + h * 8);
      h++;
    } else fence_async_smem();
  }
}

__device__ __forceinline__ void a_loader(const Params& P, uint32_t sb, unsigned vb) {
  const int j = cta_j(vb), m = cta_m(vb);
  u64 t1 = 0, t2 = 0;
  Ring r = {PRE_A % NA, PRE_A < NA};
  {
    u64 tab = order_table0(j) >> (4 * PRE_A);
#pragma unroll 1
    for (int i = PRE_A; i < 33; i++) {
      if (i == 17) { order_tables(t1, t2, j); tab = t2; }
      mbar_wait(sb + BAR_EMPTYA + r.s * 8, r.ph);
      if (elect()) {
        mbar_expect_tx(sb + BAR_FULLA + r.s * 8, SLOT);
        if (i != 14) tma_load_3d(sb + OFF_A + r.s * SLOT, &P.mx, sb + BAR_FULLA + r.s * 8, ((int)tab & 15) * 64, m * 64, 0);
        else {
          tma_load_w(sb + OFF_A + r.s * SLOT, &P.mw[1], sb + BAR_FULLA + r.s * 8, 1024 + 128 * j, m);
          mbar_expect_tx(sb + BAR_WPHI, 8192); tma_load_2d(sb + OFF_S + 4096, &P.mwphi, sb + BAR_WPHI, 0, 128 * j);
        }
        if (i == PF1 || i == PF2) tma_prefetch_w(&P.mwo[i == PF2], 128 * j, m);
      }
      adv<NA>(r);
      if (i != 14) tab >>= 4;
    }
  }
  const unsigned tag = get_tag(sb);
  unsigned kph = 0;
#pragma unroll 1
  for (int sg = 0; sg < 13; sg++) {
    const int L = sg >> 2, p = sg & 3;
    if (p == 0 && (L & 1)) kv_images(sb, L, j, tag, kph);
    int n = p < 2 ? 14 : (p == 2 ? ((L & 1) ? 0 : 16 - NJ) : 16);
    u64 tab = p == 3 ? t2 : t1 >> (p < 2 ? 8 : 4 * NJ);
    const uint4* img = &g_img[p ? XBUF(L + 1) : 0][m][0][0];
#pragma unroll 1
    for (; n > 0; n--) {
      const uint4* src = early(img + ((int)tab & 15) * 1024);
      const uint32_t bar = sb + (p < 2 ? BAR_LAND : BAR_FULLA) + r.s * 8;
      mbar_wait(sb + BAR_EMPTYA + r.s * 8, r.ph);
      if (elect()) mbar_expect_tx(bar, SLOT);
      if (p < 2 && n == 14) {
        const int lane = threadIdx.x & 31;
        const unsigned* f = &g_hint[(m & 14) + ((lane >> 3) & 1)][(~j & 4) ^ (lane & ND0)];
        mbar_wait(sb + BAR_SIGP + p * 8, L & 1);
        int it = 0;
        while (!__all_sync(0xffffffffu, (int)(ld_flag(f) - (tag * 16 + 4 * L + 1 + p)) >= 0)) { if (++it > (1 << 22)) __trap(); }
        pause(p ? (L ? PAX : PX0) : ((L & 1) ? 0 : (L ? PAA : PA0)));
        TS(2, p == 0 ? 5 + L * 8 : 9 + L * 8);
        TSH((2 * L + p) * 8 + 2);
      }
      if (elect()) bulk_load(sb + OFF_A + r.s * SLOT, src, SLOT, bar);
      adv<NA>(r);
      tab >>= 4;
      pause(p < 2 && n > 10 ? G0 : 0);
    }
  }
}

template <int KB, int G>
__device__ __forceinline__ uint2 sum_packets(float (&a)[8], uint32_t addr, int n) {
  uint2 ok = make_uint2(~0u, 0u);
#pragma unroll 1
  for (int b = 0; b < n; b += KB) {
    uint4 v[KB];
#pragma unroll
    for (int u = 0; u < KB; u++) lds128(addr + (b + u) * 512, v[u].x, v[u].y, v[u].z, v[u].w);
#pragma unroll
    for (int u = 0; u < KB; u++) { ok.x &= v[u].x; ok.y |= v[u].x; }
#pragma unroll
    for (int d = 1; d < G; d *= 2)
#pragma unroll
      for (int u = 0; u < KB; u += 2 * d) v[u] = make_uint4(add2(v[u].x, v[u + d].x), add2(v[u].y, v[u + d].y), add2(v[u].z, v[u + d].z), add2(v[u].w, v[u + d].w));
#pragma unroll
    for (int u = 0; u < KB; u += G) {
      a[0] += lo16(v[u].x); a[1] += hi16(v[u].x); a[2] += lo16(v[u].y); a[3] += hi16(v[u].y);
      a[4] += lo16(v[u].z); a[5] += hi16(v[u].z); a[6] += lo16(v[u].w); a[7] += hi16(v[u].w);
    }
  }
  return ok;
}
__device__ __forceinline__ void helper_bar() { asm volatile("bar.sync 4, 64;" ::: "memory"); }
__device__ __forceinline__ void helper(const Params& P, uint32_t sb, int w, unsigned vb) {
  const int j = cta_j(vb), m = cta_m(vb);
  if (w == 0) {
    if (elect()) {
      const unsigned t = atomicAdd(&g_ctr, 1u) / NCTA + 1u;
      asm volatile("st.shared.u32 [%0], %1;" ::"r"(sb + OFF_EPOCH), "r"(t) : "memory");
      mbar_arrive(sb + BAR_EPOCH);
    }
  }
  const unsigned tag = get_tag(sb);
  mbar_wait(sb + BAR_FULLB + 24, 0);
  const uint32_t stg = sb + OFF_T + w * 12288, stb = sb + BAR_STG + w * 24;
  Ring rs = {0, 0};
  uint32_t vs = 33 % NA, vph = 0;
  auto cs_image = [&](int L) {
      const int lane = lane_id();
      poll_flags(&g_jflag[2 * L][j][0], 16, L ? CSNEED : 0xFFFu, tag * 4);
#pragma unroll
      for (int p = 0; p < 3; p++) {
        const uint4 u = ldcg4(&g_cs[L][0][p * 1024 + 128 * j + lane * 4]), v = ldcg4(&g_cs[L][1][p * 1024 + 128 * j + lane * 4]);
        const float c0 = __uint_as_float(u.x) + __uint_as_float(v.x), c1 = __uint_as_float(u.y) + __uint_as_float(v.y);
        const float c2 = __uint_as_float(u.z) + __uint_as_float(v.z), c3 = __uint_as_float(u.w) + __uint_as_float(v.w);
        const uint32_t h0 = pack2(c0, c1), h1 = pack2(c2, c3), dst = sb + OFF_CS + (p * 16 + (lane >> 1)) * 96 + L * 48 + (lane & 1) * 8;
        sts64(dst, h0, h1); sts64(dst + 16, pack2(c0 - lo16(h0), c1 - hi16(h0)), pack2(c2 - lo16(h1), c3 - hi16(h1))); sts64(dst + 32, h0, h1);
        if (L == 0) { sts64(dst + 48, 0u, 0u); sts64(dst + 64, 0u, 0u); sts64(dst + 80, 0u, 0u); }
      }
      if (L == 0 && lane < 4) sts64(sb + OFF_CS + 4608 + lane * 8, 0u, 0u);
      fence_async_smem();
      __syncwarp();
      if (elect()) mbar_arrive(sb + BAR_CS + L * 8);
      TS(4, 2 + L * 2);
  };
#pragma unroll 1
  for (int L = 0; L < 4; L++) {
    const int lane = lane_id();
    if (L == 0) {
      {
        const int wt = m >= 12, col = ((0x2021 >> (m & 12)) & 3) * 1024 + 128 * j + (m & 3) * 32;
        const CUtensorMap* tm = &P.mcs[wt];
        if (wt) __nanosleep(D2);
        constexpr int nb = 8;
        float a[8] = {0.f, 0.f, 0.f, 0.f, 0.f, 0.f, 0.f, 0.f};
#pragma unroll 1
        for (int b = -3; b < nb; b++) {
          if (b >= 0) {
            mbar_wait(stb + rs.s * 8, rs.ph);
            sum_packets<KC, 1>(a, stg + rs.s * 4096 + lane * 16, 8);
            fence_async_smem();
            __syncwarp();
          }
          const uint32_t sl = b < 0 ? (rs.s + b + 3) % 3 : rs.s;
          if (b + 3 < nb && elect()) { mbar_expect_tx(stb + sl * 8, 4096); tma_load_2d(stg + sl * 4096, tm, stb + sl * 8, col, (w * (16 - nb) + b + 3) * 64); }
          if (b >= 0) adv<3>(rs); else pause(CP);
        }
#pragma unroll 1
        for (int d = 4; d < 32; d *= 2)
#pragma unroll
          for (int u = 0; u < 8; u++) a[u] += __shfl_xor_sync(0xffffffffu, a[u], d);
        if (lane < 4) {
          float4* dst = reinterpret_cast<float4*>(&g_cs[wt][w][col + lane * 8]);
          dst[0] = make_float4(a[0], a[1], a[2], a[3]); dst[1] = make_float4(a[4], a[5], a[6], a[7]);
        }
        helper_bar();
        if (w == 0 && elect()) { fence_gpu(); st_flag(&g_jflag[2 * wt][j][m], tag * 4); }
      }
      if (w == 0) TS(4, 1 + L * 2);
    }
    if (L > 0 && w == 0) {
      mbar_wait(sb + BAR_SIGP + 16, (L - 1) & 1);
      fence_async_global();
      __nanosleep(CO && L == 1 ? SE : SD);
    }
    if (CO && L < 2 && w == 0) cs_image(L);
    if (w == (L == 0)) {
      if (L == 0) { mbar_wait(sb + BAR_WPHI, 0); __nanosleep(S0); }
#pragma unroll 1
      for (int p = 0; p < 2; p++) {
        uint4 v[8];
        for (int it = 0;; it++) {
          bool ok = true;
#pragma unroll
          for (int t = 0; t < 8; t++) v[t] = ld_pkt(&g_stats[m][p][t][lane]);
#pragma unroll
          for (int t = 0; t < 8; t++) ok = ok && (v[t].w & 15u) == seq4(tag, L);
          if (__all_sync(0xffffffffu, ok)) break;
          __nanosleep(200);
          if (it > (1 << 20)) __trap();
        }
        float s0 = 0.f, q0 = 0.f, s1 = 0.f, q1 = 0.f;
#pragma unroll
        for (int t = 0; t < 8; t++) { s0 += __uint_as_float(v[t].x); q0 += __uint_as_float(v[t].y); s1 += __uint_as_float(v[t].z); q1 += __uint_as_float(v[t].w & ~15u); }
        s0 *= (1.f / 1024); s1 *= (1.f / 1024);
        sts64(sb + OFF_MR + p * 256 + lane * 8, __float_as_uint(rsqrtf(fmaxf(q0 * (1.f / 1024) - s0 * s0, 0.f) + 1e-5f)),
              __float_as_uint(rsqrtf(fmaxf(q1 * (1.f / 1024) - s1 * s1, 0.f) + 1e-5f)));
#pragma unroll
        for (int r = 0; r < 2; r++) {
          const float v = -0.5f * (r ? s1 : s0);
          const uint32_t hh = pack2(v, v), hl = pack2(v, v - lo16(hh));
          const bool b = L & 1;
          sts128(sb + (b ? OFF_MB : OFF_MA) + p * 1024 + (lane >> 3) * 256 + r * 128 + (lane & 7) * 16, b ? 0u : hh, b ? hh << 16 : hl >> 16, b ? hl : 0u, 0u);
        }
      }
      fence_async_smem();
      __syncwarp();
      if (elect()) {
        mbar_arrive(sb + BAR_STAT);
      }
      TS(2, 0 + L * 8);
    }
    if (!CO && L < 2 && w == 0) cs_image(L);
    if (L & 1) {
      const uint32_t flip = L == 1 ? 0u : 1u;
      mbar_wait(sb + BAR_SIGT, 1);
      {
        int it = 0;
        if (PSL) __nanosleep(m < 8 ? PSL : PSL + 600);
        while (!__all_sync(0xffffffffu, (ld_flag(reinterpret_cast<const unsigned*>(&g_kvpart[j][m][w][512]) + (lane & 15) * 8) ^ flip) & 1u)) { if (PSL) __nanosleep(100); if (++it > (1 << 22)) __trap(); }
        fence_async_global();
      }
      if (w == 0) TS(4, 6 + L * 2);
      float a[8], z;
      for (int it = 0;; it++) {
        if (elect()) { mbar_expect_tx(stb + rs.s * 8, 8704); bulk_load(stg, &g_kvpart[j][m][w][0], 8704, stb + rs.s * 8); }
        mbar_wait(stb + rs.s * 8, rs.ph);
        if (w == 0) TS(4, 21 + L);
        adv<3>(rs);
#pragma unroll
        for (int u = 0; u < 8; u++) a[u] = 0.f;
        z = 0.f;
        uint32_t ok = 1u;
#pragma unroll
        for (int u = 0; u < 4; u++) { const float v = lds32f(stg + 8192 + u * 128 + (lane & 3) * 32 + (lane >> 2) * 4); z += v; ok &= __float_as_uint(v) ^ flip; }
        const uint2 tg = sum_packets<8, RG>(a, stg + lane * 16, 16);
        ok &= flip ? ~tg.y : tg.x;
        if (__all_sync(0xffffffffu, ok & 1u)) break;
        fence_async_smem();
        if (it > (1 << 16)) __trap();
      }
      {
        uint4* img = &g_kvfin[j][m][w * 8 + (lane >> 2)];
        uint32_t a0 = __float_as_uint(a[0]) >> 16;
        a0 += ~(a0 ^ flip) & 1u;
        st_v4(img + (lane & 3) * 16, __byte_perm(a0, pack2(0.f, a[1]), 0x7610), pack2(a[2], a[3]), pack2(a[4], a[5]), pack2(a[6], a[7]));
        const uint32_t cz = pack2(0.f, qsum(z)) | (0x3781u ^ flip);
        if (!(lane & 3)) st_v4(img + 64, cz, cz, cz, cz);
        __syncwarp();
        if (elect()) st_flag(&g_jflag[m >> 3][j][(m & 7) * 2 + w], tag * 4 + L);
      }
      if (w == 0) TS(4, 7 + L * 2);
    } else {
      if (L == 0 && w == 0) {
        st_v4(&g_kvpart[j][m][0][512 + lane], 0u, 0u, 0u, 0u); st_v4(&g_kvpart[j][m][1][512 + lane], 0u, 0u, 0u, 0u);
        __syncwarp();
      }
      mbar_wait(sb + BAR_SIGT, 0);
      if (w == 0) {
        if (elect()) { fence_gpu(); st_flag(&g_hint[m][j], tag * 16 + 4 * L); st_flag(&g_jflag[1][j][m], tag * 4 + L); }
        if (L == 0) {
          __nanosleep(KSL);
          poll_flags(&g_jflag[1][j][0], 16, 0xFFFFu, tag * 4);
          if (elect()) mbar_arrive(sb + BAR_WPHI);
        }
      } else if (m > 0) {
        poll_flags(&g_hint[m - 1][j], 1, 1u, tag * 16 + 4 * L);
        if (elect()) { mbar_expect_tx(sb + BAR_HALO, 8192); bulk_load(sb + OFF_S + 8192, &g_halo[m - 1][j][0][0], 8192, sb + BAR_HALO); }
        TS(2, 2 + L * 8);
      }
    }
    if (w == 0) {
#pragma unroll 1
      for (int e = 0; e < (L < 3 ? 2 : 1); e++) {
        unsigned* flag = early(&g_hint[m][j]);
        mbar_wait(sb + BAR_SIGP + e * 8, L & 1);
        TS(2, (e ? 6 : 3) + L * 8);
        TSH((2 * L + e) * 8);
        if (elect()) st_flag(flag, tag * 16 + 4 * L + 1 + e);
        TSH((2 * L + e) * 8 + 1);
      }
    } else {
#pragma unroll 1
      for (int i = 0; i < (L < 3 ? 28 : 14); i++) {
        const bool isx = i >= 14;
        const uint32_t a = sb + OFF_A + vs * SLOT + lane * 128 + ((lane >> 4) * 4 + (lane & 3)) * 16 + (lane & 12), code = img_code(isx, L + isx);
        for (int it = 0;; it++) {
          mbar_wait(sb + BAR_LAND + vs * 8, (vph >> vs) & 1);
          vph ^= 1u << vs;
          if (i - 14 * isx < 2) TSH((2 * L + isx) * 8 + 3 + 2 * (i - 14 * isx));
          uint32_t bad = 0;
#pragma unroll
          for (int u = 0; u < 4; u++) bad |= __float_as_uint(lds32f(a + u * 4096)) ^ code;
          if (__all_sync(0xffffffffu, !(bad & img_mask(isx)))) break;
          if (it > (1 << 16)) __trap();
          fence_async_smem();
          if (elect()) {
            mbar_expect_tx(sb + BAR_LAND + vs * 8, SLOT);
            bulk_load(sb + OFF_A + vs * SLOT, &g_img[isx ? XBUF(L + 1) : 0][m][o_order(i - 14 * isx + 2, j)][0], SLOT, sb + BAR_LAND + vs * 8);
          }
        }
        if (elect()) mbar_arrive(sb + BAR_FULLA + vs * 8);
        if (i - 14 * isx < 2) TSH((2 * L + isx) * 8 + 4 + 2 * (i - 14 * isx));
        if (++vs == NA) vs = 0;
      }
      vs = (vs + ((L & 1) ? 16 : 32 - NJ)) % NA;
    }
  }
}

__device__ __forceinline__ void spare(const Params& P, uint32_t sb, int id) {
  const int tid = threadIdx.x & 127, warp = __shfl_sync(0xffffffffu, threadIdx.x >> 5, 0), w = warp >> 2, lane = tid & 31, j = 2 * id + w;
  const uint32_t ring = w * 6 * SLOT, wp = 12 * SLOT + w * 8192, bar = sb + 13 * SLOT + w * 64;
  auto part = [&](int t) { return (t >> 4) ^ w; };
  auto load = [&](int t, uint32_t sl) {
    mbar_expect_tx(bar + sl * 8, t == 0 ? SLOT + 8192 : SLOT);
    tma_load_w(sb + ring + sl * SLOT, &P.mw[1], bar + sl * 8, part(t) * 1024 + 128 * j, t & 15);
  };
  if (!(warp & 3) && elect()) {
    if (w == 2) sts32(sb + OFF_EPOCH, atomicAdd(&g_ctr, 1u) / NCTA + 1u);
    else {
      __nanosleep(D3);
#pragma unroll 1
      for (int t = 0; t < 5; t++) {
        mbar_init(bar + t * 8, 1);
        asm volatile("fence.mbarrier_init.release.cluster;" ::: "memory");
        load(t, t);
      }
      tma_load_2d(sb + wp, &P.mwphi, bar, 0, 128 * j);
    }
  }
  __syncthreads();
  const unsigned tag = get_tag<false>(sb);
  if (w == 2) {
    int it = 0;
    while ((int)(ld_flag(&g_ctr) - tag * NCTA) < 0) { if (++it > (1 << 22)) __trap(); }
    return;
  }
  Ring r = {4, 1};
  float d[64];
  auto fold = [&]() {
    mbar_wait(bar + r.s * 8, r.ph);
    wgmma_fence();
#pragma unroll
    for (int q = 0; q < 8; q++)
      wgmma_ss_n32(reinterpret_cast<float (&)[16]>(d[16 * (q >> 1)]), desc_lo(SB + ring + r.s * SLOT, 16) + (q >> 2) * 512 + (q & 3) * 2, desc_lo(SB + wp, 512) + q * 64, q & 1);
    wgmma_commit();
  };
#pragma unroll
  for (int i = 0; i < 64; i++) d[i] = 0.f;
  int t = -1;
#pragma unroll 1
  for (int g = 0; g < 2; g++) {
    float cs[32] = {};
#pragma unroll 1
    do {
      uint32_t f[32];
#pragma unroll
      for (int i = 0; i < 32; i++) { f[i] = pack2(d[2 * i], d[2 * i + 1]); cs[i & 30] += d[2 * i]; cs[i | 1] += d[2 * i + 1]; }
      wg_bar(w);
      const uint32_t sl = r.s;
      if (t < 31) adv<5>(r);
      fold();
      if (!(warp & 3) && t >= 0 && t < 27 && elect()) load(t + 5, sl);
      if (g == w && t >= 0) {
        uint4* dst = &g_wf[0][j][t & 15][((tid >> 5) * 16 + (lane >> 2)) * 8];
#pragma unroll
        for (int q = 0; q < 8; q++)
          dst[(q >> 2) * 512 + (q & 1) * 64 + (((q & 2) * 2 + (lane & 3)) ^ (lane >> 2))] =
              make_uint4(f[4 * (q & 6) + (q & 1)], f[4 * (q & 6) + (q & 1) + 2], f[4 * (q & 6) + (q & 1) + 4], f[4 * (q & 6) + (q & 1) + 6]);
      }
      wgmma_wait<0>();
      fence_regs(d);
    } while (++t != 16 * g + 16);
    const uint32_t red = sb + ring + 5 * SLOT;
#pragma unroll
    for (int i = 0; i < 8; i++) sts128(red + (tid >> 2) * 512 + (i >> 1) * 128 + (lane & 3) * 32 + (i & 1) * 16, __float_as_uint(cs[4 * i]), __float_as_uint(cs[4 * i + 1]), __float_as_uint(cs[4 * i + 2]), __float_as_uint(cs[4 * i + 3]));
    wg_bar(w);
    float a = 0.f;
#pragma unroll 4
    for (int i = 0; i < 32; i++) a += lds32f(red + i * 512 + tid * 4);
    g_cs[1][0][(g ^ w) * 1024 + j * 128 + tid] = a;
  }
  wg_bar(w);
  if (tid == 0) { fence_gpu(); st_flag(&g_jflag[2][j][0], tag * 4); }
}

__global__ void __launch_bounds__(NTHREADS, 1) fused_kernel(const __grid_constant__ Params P) {
  extern __shared__ __align__(1024) uint8_t smem_raw[];
  constexpr uint32_t sb = SB;
  const int tid = threadIdx.x;
  const unsigned vb = vblock();
  if (vb >= 128) { spare(P, sb, vb - 128); return; }
  const int warp = __shfl_sync(0xffffffffu, tid >> 5, 0);
  if (elect()) {
    if (warp == 11) { prefetch_map(&P.mx); prefetch_map(&P.mw[0]); if (smem_u32(smem_raw) != SB) __trap(); }
    if (warp < 8) {
#pragma unroll
      for (int i = 0; i < 8; i++) mbar_init(sb + OFF_BAR + (warp * 8 + i) * 8, warp == 2 || warp == 3 ? 2 : (warp == 4 ? 8 : 1));
    }
    asm volatile("fence.mbarrier_init.release.cluster;" ::: "memory");
    if (warp < 2) {
      const int j = cta_j(vb);
#pragma unroll 1
      for (int i = 0; i < (warp == 0 ? PRE_B : PRE_A); i++) {
        const uint32_t bar = sb + BAR_FULLB + warp * 64 + i * 8;
        mbar_expect_tx(bar, SLOT);
        if (warp == 0) tma_load_w(sb + OFF_B + i * SLOT, &P.mw[0], bar, 1024 + (i & 1) * 1024 + 128 * j, kv_order(i >> 1, j, 0));
        else tma_load_3d(sb + OFF_A + i * SLOT, &P.mx, bar, kv_order(i, j, 0) * 64, cta_m(vb) * 64, 0);
      }
    }
  }
  if (tid == 0) TS(6, 0);
  __syncthreads();
  if (tid == 0) TS(6, 2);
  if (warp < 4) {
    reg_dealloc<PREGS>();
    if (warp & 2) helper(P, sb, warp & 1, vb);
    else if (warp & 1) a_loader(P, sb, vb);
    else b_producer(P, sb, vb);
  } else {
    reg_alloc<CREGS>();
    consumer(P, sb, (warp >> 2) - 1, vb);
  }
}

typedef CUresult (*EncodeFn)(CUtensorMap*, CUtensorMapDataType, cuuint32_t, void*, const cuuint64_t*, const cuuint64_t*,
                             const cuuint32_t*, const cuuint32_t*, CUtensorMapInterleave, CUtensorMapSwizzle,
                             CUtensorMapL2promotion, CUtensorMapFloatOOBfill);

void encode(EncodeFn fn, CUtensorMap* m, const void* ptr, int rank, const cuuint64_t* dims, const cuuint64_t* strides,
            const cuuint32_t* box, CUtensorMapSwizzle swz) {
  const cuuint32_t es[5] = {1, 1, 1, 1, 1};
  fn(m, CU_TENSOR_MAP_DATA_TYPE_BFLOAT16, rank, const_cast<void*>(ptr), dims, strides, box, es, CU_TENSOR_MAP_INTERLEAVE_NONE,
     swz, CU_TENSOR_MAP_L2_PROMOTION_L2_256B, CU_TENSOR_MAP_FLOAT_OOB_FILL_NONE);
}
void encode_w(EncodeFn fn, CUtensorMap* m, const void* ptr, int ncols, bool perm) {
  const cuuint64_t p = (cuuint64_t)ncols * 2, d[5] = {(cuuint64_t)ncols, 2, 4, 4, 32}, s[4] = {p, (perm ? 8 : 2) * p, (perm ? 2 : 8) * p, 32 * p};
  const cuuint32_t box[5] = {64, 2, 4, 4, 2};
  encode(fn, m, ptr, 5, d, s, box, CU_TENSOR_MAP_SWIZZLE_128B);
}

void encode_cs(EncodeFn fn, CUtensorMap* m, const void* ptr, int ncols) {
  const cuuint64_t d[2] = {(cuuint64_t)ncols, 1024}, s[1] = {(cuuint64_t)ncols * 2};
  const cuuint32_t box[2] = {32, 64};
  encode(fn, m, ptr, 2, d, s, box, CU_TENSOR_MAP_SWIZZLE_NONE);
}

}

extern "C" void kernel_launch(void* const* d_in, const int* in_sizes, int n_in, void* d_out, int out_size) {
  (void)in_sizes; (void)n_in; (void)out_size;
  void* fnp = nullptr;
  cudaDriverEntryPointQueryResult q;
  cudaGetDriverEntryPoint("cuTensorMapEncodeTiled", &fnp, cudaEnableDefault, &q);
  EncodeFn fn = (EncodeFn)fnp;
  Params P;
  {
    const cuuint64_t dims[3] = {1024, 1024, 2}, strides[2] = {4096, 2048};
    const cuuint32_t box[3] = {64, 64, 2};
    encode(fn, &P.mx, d_in[0], 3, dims, strides, box, CU_TENSOR_MAP_SWIZZLE_128B);
  }
  P.out = (uint4*)d_out;
  encode_w(fn, &P.mw[0], d_in[1], 3072, false);
  encode_w(fn, &P.mw[1], d_in[4], 3072, true);
  encode_w(fn, &P.mw[2], d_in[1], 3072, true);
  encode_w(fn, &P.mwo[0], d_in[2], 1024, true);
  encode_w(fn, &P.mwo[1], d_in[6], 1024, false);
  encode_cs(fn, &P.mcs[0], d_in[1], 3072);
  encode_cs(fn, &P.mcs[1], d_in[4], 3072);
  {
    const cuuint64_t dims[2] = {32, 1024}, strides[1] = {64};
    const cuuint32_t box[2] = {32, 128};
    encode(fn, &P.mwphi, d_in[5], 2, dims, strides, box, CU_TENSOR_MAP_SWIZZLE_64B);
  }
  cudaFuncSetAttribute(fused_kernel, cudaFuncAttributeMaxDynamicSharedMemorySize, SMEM_BYTES);
  fused_kernel<<<NCTA, NTHREADS, SMEM_BYTES, cudaStreamPerThread>>>(P);
}
```

```cpp
#include <cuda_runtime.h>
#include <cuda_bf16.h>
#include <cuda.h>
#include <stdint.h>

namespace {

__device__ __forceinline__ void wgmma_ss_n256(float (&d)[128], uint32_t da, uint32_t ha, uint32_t db, int sd) {
  asm volatile("{\n.reg .pred p;\n.reg .b64 a, b;\nsetp.ne.b32 p, %130, 0;\nmov.b64 a, {%128, %131};\nmov.b64 b, {%129, 0x40000040};\n"
    "wgmma.mma_async.sync.aligned.m64n256k16.f32.bf16.bf16 {%0,%1,%2,%3,%4,%5,%6,%7,%8,%9,%10,%11,%12,%13,%14,%15,%16,%17,%18,%19,%20,%21,%22,%23,%24,%25,%26,%27,%28,%29,%30,%31,%32,%33,%34,%35,%36,%37,%38,%39,%40,%41,%42,%43,%44,%45,%46,%47,%48,%49,%50,%51,%52,%53,%54,%55,%56,%57,%58,%59,%60,%61,%62,%63,%64,%65,%66,%67,%68,%69,%70,%71,%72,%73,%74,%75,%76,%77,%78,%79,%80,%81,%82,%83,%84,%85,%86,%87,%88,%89,%90,%91,%92,%93,%94,%95,%96,%97,%98,%99,%100,%101,%102,%103,%104,%105,%106,%107,%108,%109,%110,%111,%112,%113,%114,%115,%116,%117,%118,%119,%120,%121,%122,%123,%124,%125,%126,%127}, a, b, p, 1, 1, 0, 1;\n}\n"
    : "+f"(d[0]),"+f"(d[1]),"+f"(d[2]),"+f"(d[3]),"+f"(d[4]),"+f"(d[5]),"+f"(d[6]),"+f"(d[7]),"+f"(d[8]),"+f"(d[9]),"+f"(d[10]),"+f"(d[11]),"+f"(d[12]),"+f"(d[13]),"+f"(d[14]),"+f"(d[15]),"+f"(d[16]),"+f"(d[17]),"+f"(d[18]),"+f"(d[19]),"+f"(d[20]),"+f"(d[21]),"+f"(d[22]),"+f"(d[23]),"+f"(d[24]),"+f"(d[25]),"+f"(d[26]),"+f"(d[27]),"+f"(d[28]),"+f"(d[29]),"+f"(d[30]),"+f"(d[31]),"+f"(d[32]),"+f"(d[33]),"+f"(d[34]),"+f"(d[35]),"+f"(d[36]),"+f"(d[37]),"+f"(d[38]),"+f"(d[39]),"+f"(d[40]),"+f"(d[41]),"+f"(d[42]),"+f"(d[43]),"+f"(d[44]),"+f"(d[45]),"+f"(d[46]),"+f"(d[47]),"+f"(d[48]),"+f"(d[49]),"+f"(d[50]),"+f"(d[51]),"+f"(d[52]),"+f"(d[53]),"+f"(d[54]),"+f"(d[55]),"+f"(d[56]),"+f"(d[57]),"+f"(d[58]),"+f"(d[59]),"+f"(d[60]),"+f"(d[61]),"+f"(d[62]),"+f"(d[63]),"+f"(d[64]),"+f"(d[65]),"+f"(d[66]),"+f"(d[67]),"+f"(d[68]),"+f"(d[69]),"+f"(d[70]),"+f"(d[71]),"+f"(d[72]),"+f"(d[73]),"+f"(d[74]),"+f"(d[75]),"+f"(d[76]),"+f"(d[77]),"+f"(d[78]),"+f"(d[79]),"+f"(d[80]),"+f"(d[81]),"+f"(d[82]),"+f"(d[83]),"+f"(d[84]),"+f"(d[85]),"+f"(d[86]),"+f"(d[87]),"+f"(d[88]),"+f"(d[89]),"+f"(d[90]),"+f"(d[91]),"+f"(d[92]),"+f"(d[93]),"+f"(d[94]),"+f"(d[95]),"+f"(d[96]),"+f"(d[97]),"+f"(d[98]),"+f"(d[99]),"+f"(d[100]),"+f"(d[101]),"+f"(d[102]),"+f"(d[103]),"+f"(d[104]),"+f"(d[105]),"+f"(d[106]),"+f"(d[107]),"+f"(d[108]),"+f"(d[109]),"+f"(d[110]),"+f"(d[111]),"+f"(d[112]),"+f"(d[113]),"+f"(d[114]),"+f"(d[115]),"+f"(d[116]),"+f"(d[117]),"+f"(d[118]),"+f"(d[119]),"+f"(d[120]),"+f"(d[121]),"+f"(d[122]),"+f"(d[123]),"+f"(d[124]),"+f"(d[125]),"+f"(d[126]),"+f"(d[127])
    : "r"(da), "r"(db), "r"(sd), "r"(ha));
}
__device__ __forceinline__ void wgmma_ss_n128(float (&d)[64], uint32_t da, uint32_t ha, uint32_t db, int sd) {
  asm volatile("{\n.reg .pred p;\n.reg .b64 a, b;\nsetp.ne.b32 p, %66, 0;\nmov.b64 a, {%64, %67};\nmov.b64 b, {%65, 0x40000040};\n"
    "wgmma.mma_async.sync.aligned.m64n128k16.f32.bf16.bf16 {%0,%1,%2,%3,%4,%5,%6,%7,%8,%9,%10,%11,%12,%13,%14,%15,%16,%17,%18,%19,%20,%21,%22,%23,%24,%25,%26,%27,%28,%29,%30,%31,%32,%33,%34,%35,%36,%37,%38,%39,%40,%41,%42,%43,%44,%45,%46,%47,%48,%49,%50,%51,%52,%53,%54,%55,%56,%57,%58,%59,%60,%61,%62,%63}, a, b, p, 1, 1, 0, 1;\n}\n"
    : "+f"(d[0]),"+f"(d[1]),"+f"(d[2]),"+f"(d[3]),"+f"(d[4]),"+f"(d[5]),"+f"(d[6]),"+f"(d[7]),"+f"(d[8]),"+f"(d[9]),"+f"(d[10]),"+f"(d[11]),"+f"(d[12]),"+f"(d[13]),"+f"(d[14]),"+f"(d[15]),"+f"(d[16]),"+f"(d[17]),"+f"(d[18]),"+f"(d[19]),"+f"(d[20]),"+f"(d[21]),"+f"(d[22]),"+f"(d[23]),"+f"(d[24]),"+f"(d[25]),"+f"(d[26]),"+f"(d[27]),"+f"(d[28]),"+f"(d[29]),"+f"(d[30]),"+f"(d[31]),"+f"(d[32]),"+f"(d[33]),"+f"(d[34]),"+f"(d[35]),"+f"(d[36]),"+f"(d[37]),"+f"(d[38]),"+f"(d[39]),"+f"(d[40]),"+f"(d[41]),"+f"(d[42]),"+f"(d[43]),"+f"(d[44]),"+f"(d[45]),"+f"(d[46]),"+f"(d[47]),"+f"(d[48]),"+f"(d[49]),"+f"(d[50]),"+f"(d[51]),"+f"(d[52]),"+f"(d[53]),"+f"(d[54]),"+f"(d[55]),"+f"(d[56]),"+f"(d[57]),"+f"(d[58]),"+f"(d[59]),"+f"(d[60]),"+f"(d[61]),"+f"(d[62]),"+f"(d[63])
    : "r"(da), "r"(db), "r"(sd), "r"(ha));
}
__device__ __forceinline__ void wgmma_ss_n40_tt(float (&d)[20], uint32_t da, uint32_t db, int sd) {
  asm volatile("{\n.reg .pred p;\n.reg .b64 a, b;\nsetp.ne.b32 p, %22, 0;\nmov.b64 a, {%20, 0x40000040};\nmov.b64 b, {%21, 0x8};\n"
    "wgmma.mma_async.sync.aligned.m64n40k16.f32.bf16.bf16 {%0,%1,%2,%3,%4,%5,%6,%7,%8,%9,%10,%11,%12,%13,%14,%15,%16,%17,%18,%19}, a, b, p, 1, 1, 1, 1;\n}\n"
    : "+f"(d[0]),"+f"(d[1]),"+f"(d[2]),"+f"(d[3]),"+f"(d[4]),"+f"(d[5]),"+f"(d[6]),"+f"(d[7]),"+f"(d[8]),"+f"(d[9]),"+f"(d[10]),"+f"(d[11]),"+f"(d[12]),"+f"(d[13]),"+f"(d[14]),"+f"(d[15]),"+f"(d[16]),"+f"(d[17]),"+f"(d[18]),"+f"(d[19])
    : "r"(da), "r"(db), "r"(sd));
}
__device__ __forceinline__ void wgmma_ss_n32(float (&d)[16], uint32_t da, uint32_t db, int sd) {
  asm volatile("{\n.reg .pred p;\n.reg .b64 a, b;\nsetp.ne.b32 p, %18, 0;\nmov.b64 a, {%16, 0x40000040};\nmov.b64 b, {%17, 0x80000020};\n"
    "wgmma.mma_async.sync.aligned.m64n32k16.f32.bf16.bf16 {%0,%1,%2,%3,%4,%5,%6,%7,%8,%9,%10,%11,%12,%13,%14,%15}, a, b, p, 1, 1, 0, 1;\n}\n"
    : "+f"(d[0]),"+f"(d[1]),"+f"(d[2]),"+f"(d[3]),"+f"(d[4]),"+f"(d[5]),"+f"(d[6]),"+f"(d[7]),"+f"(d[8]),"+f"(d[9]),"+f"(d[10]),"+f"(d[11]),"+f"(d[12]),"+f"(d[13]),"+f"(d[14]),"+f"(d[15])
    : "r"(da), "r"(db), "r"(sd));
}
__device__ __forceinline__ void wgmma_rs_n40(float (&d)[20], uint32_t a0, uint32_t a1, uint32_t a2, uint32_t a3, uint32_t db, int sd) {
  asm volatile("{\n.reg .pred p;\n.reg .b64 b;\nsetp.ne.b32 p, %25, 0;\nmov.b64 b, {%24, 0x10};\n"
    "wgmma.mma_async.sync.aligned.m64n40k16.f32.bf16.bf16 {%0,%1,%2,%3,%4,%5,%6,%7,%8,%9,%10,%11,%12,%13,%14,%15,%16,%17,%18,%19}, {%20,%21,%22,%23}, b, p, 1, 1, 1;\n}\n"
    : "+f"(d[0]),"+f"(d[1]),"+f"(d[2]),"+f"(d[3]),"+f"(d[4]),"+f"(d[5]),"+f"(d[6]),"+f"(d[7]),"+f"(d[8]),"+f"(d[9]),"+f"(d[10]),"+f"(d[11]),"+f"(d[12]),"+f"(d[13]),"+f"(d[14]),"+f"(d[15]),"+f"(d[16]),"+f"(d[17]),"+f"(d[18]),"+f"(d[19])
    : "r"(a0), "r"(a1), "r"(a2), "r"(a3), "r"(db), "r"(sd));
}
__device__ __forceinline__ void wgmma_r1_n256(float (&d)[128], uint32_t da, uint32_t db, int sd) {
  asm volatile("{\n.reg .pred p;\n.reg .b64 a, b;\nsetp.ne.b32 p, %130, 0;\nmov.b64 a, {%128, 0x8};\nmov.b64 b, {%129, 0x6};\n"
    "wgmma.mma_async.sync.aligned.m64n256k16.f32.bf16.bf16 {%0,%1,%2,%3,%4,%5,%6,%7,%8,%9,%10,%11,%12,%13,%14,%15,%16,%17,%18,%19,%20,%21,%22,%23,%24,%25,%26,%27,%28,%29,%30,%31,%32,%33,%34,%35,%36,%37,%38,%39,%40,%41,%42,%43,%44,%45,%46,%47,%48,%49,%50,%51,%52,%53,%54,%55,%56,%57,%58,%59,%60,%61,%62,%63,%64,%65,%66,%67,%68,%69,%70,%71,%72,%73,%74,%75,%76,%77,%78,%79,%80,%81,%82,%83,%84,%85,%86,%87,%88,%89,%90,%91,%92,%93,%94,%95,%96,%97,%98,%99,%100,%101,%102,%103,%104,%105,%106,%107,%108,%109,%110,%111,%112,%113,%114,%115,%116,%117,%118,%119,%120,%121,%122,%123,%124,%125,%126,%127}, a, b, p, 1, 1, 0, 1;\n}\n"
    : "+f"(d[0]),"+f"(d[1]),"+f"(d[2]),"+f"(d[3]),"+f"(d[4]),"+f"(d[5]),"+f"(d[6]),"+f"(d[7]),"+f"(d[8]),"+f"(d[9]),"+f"(d[10]),"+f"(d[11]),"+f"(d[12]),"+f"(d[13]),"+f"(d[14]),"+f"(d[15]),"+f"(d[16]),"+f"(d[17]),"+f"(d[18]),"+f"(d[19]),"+f"(d[20]),"+f"(d[21]),"+f"(d[22]),"+f"(d[23]),"+f"(d[24]),"+f"(d[25]),"+f"(d[26]),"+f"(d[27]),"+f"(d[28]),"+f"(d[29]),"+f"(d[30]),"+f"(d[31]),"+f"(d[32]),"+f"(d[33]),"+f"(d[34]),"+f"(d[35]),"+f"(d[36]),"+f"(d[37]),"+f"(d[38]),"+f"(d[39]),"+f"(d[40]),"+f"(d[41]),"+f"(d[42]),"+f"(d[43]),"+f"(d[44]),"+f"(d[45]),"+f"(d[46]),"+f"(d[47]),"+f"(d[48]),"+f"(d[49]),"+f"(d[50]),"+f"(d[51]),"+f"(d[52]),"+f"(d[53]),"+f"(d[54]),"+f"(d[55]),"+f"(d[56]),"+f"(d[57]),"+f"(d[58]),"+f"(d[59]),"+f"(d[60]),"+f"(d[61]),"+f"(d[62]),"+f"(d[63]),"+f"(d[64]),"+f"(d[65]),"+f"(d[66]),"+f"(d[67]),"+f"(d[68]),"+f"(d[69]),"+f"(d[70]),"+f"(d[71]),"+f"(d[72]),"+f"(d[73]),"+f"(d[74]),"+f"(d[75]),"+f"(d[76]),"+f"(d[77]),"+f"(d[78]),"+f"(d[79]),"+f"(d[80]),"+f"(d[81]),"+f"(d[82]),"+f"(d[83]),"+f"(d[84]),"+f"(d[85]),"+f"(d[86]),"+f"(d[87]),"+f"(d[88]),"+f"(d[89]),"+f"(d[90]),"+f"(d[91]),"+f"(d[92]),"+f"(d[93]),"+f"(d[94]),"+f"(d[95]),"+f"(d[96]),"+f"(d[97]),"+f"(d[98]),"+f"(d[99]),"+f"(d[100]),"+f"(d[101]),"+f"(d[102]),"+f"(d[103]),"+f"(d[104]),"+f"(d[105]),"+f"(d[106]),"+f"(d[107]),"+f"(d[108]),"+f"(d[109]),"+f"(d[110]),"+f"(d[111]),"+f"(d[112]),"+f"(d[113]),"+f"(d[114]),"+f"(d[115]),"+f"(d[116]),"+f"(d[117]),"+f"(d[118]),"+f"(d[119]),"+f"(d[120]),"+f"(d[121]),"+f"(d[122]),"+f"(d[123]),"+f"(d[124]),"+f"(d[125]),"+f"(d[126]),"+f"(d[127])
    : "r"(da), "r"(db), "r"(sd));
}
__device__ __forceinline__ void wgmma_r1_n128(float (&d)[64], uint32_t da, uint32_t db, int sd) {
  asm volatile("{\n.reg .pred p;\n.reg .b64 a, b;\nsetp.ne.b32 p, %66, 0;\nmov.b64 a, {%64, 0x8};\nmov.b64 b, {%65, 0x6};\n"
    "wgmma.mma_async.sync.aligned.m64n128k16.f32.bf16.bf16 {%0,%1,%2,%3,%4,%5,%6,%7,%8,%9,%10,%11,%12,%13,%14,%15,%16,%17,%18,%19,%20,%21,%22,%23,%24,%25,%26,%27,%28,%29,%30,%31,%32,%33,%34,%35,%36,%37,%38,%39,%40,%41,%42,%43,%44,%45,%46,%47,%48,%49,%50,%51,%52,%53,%54,%55,%56,%57,%58,%59,%60,%61,%62,%63}, a, b, p, 1, 1, 0, 1;\n}\n"
    : "+f"(d[0]),"+f"(d[1]),"+f"(d[2]),"+f"(d[3]),"+f"(d[4]),"+f"(d[5]),"+f"(d[6]),"+f"(d[7]),"+f"(d[8]),"+f"(d[9]),"+f"(d[10]),"+f"(d[11]),"+f"(d[12]),"+f"(d[13]),"+f"(d[14]),"+f"(d[15]),"+f"(d[16]),"+f"(d[17]),"+f"(d[18]),"+f"(d[19]),"+f"(d[20]),"+f"(d[21]),"+f"(d[22]),"+f"(d[23]),"+f"(d[24]),"+f"(d[25]),"+f"(d[26]),"+f"(d[27]),"+f"(d[28]),"+f"(d[29]),"+f"(d[30]),"+f"(d[31]),"+f"(d[32]),"+f"(d[33]),"+f"(d[34]),"+f"(d[35]),"+f"(d[36]),"+f"(d[37]),"+f"(d[38]),"+f"(d[39]),"+f"(d[40]),"+f"(d[41]),"+f"(d[42]),"+f"(d[43]),"+f"(d[44]),"+f"(d[45]),"+f"(d[46]),"+f"(d[47]),"+f"(d[48]),"+f"(d[49]),"+f"(d[50]),"+f"(d[51]),"+f"(d[52]),"+f"(d[53]),"+f"(d[54]),"+f"(d[55]),"+f"(d[56]),"+f"(d[57]),"+f"(d[58]),"+f"(d[59]),"+f"(d[60]),"+f"(d[61]),"+f"(d[62]),"+f"(d[63])
    : "r"(da), "r"(db), "r"(sd));
}

__device__ __forceinline__ uint32_t smem_u32(const void* p) { return (uint32_t)__cvta_generic_to_shared(p); }
__device__ __forceinline__ void mbar_init(uint32_t bar, uint32_t cnt) { asm volatile("mbarrier.init.shared::cta.b64 [%0], %1;" ::"r"(bar), "r"(cnt)); }
__device__ __forceinline__ void mbar_expect_tx(uint32_t bar, uint32_t bytes) { asm volatile("mbarrier.arrive.expect_tx.shared::cta.b64 _, [%0], %1;" ::"r"(bar), "r"(bytes) : "memory"); }
__device__ __forceinline__ void mbar_arrive(uint32_t bar) { asm volatile("mbarrier.arrive.shared::cta.b64 _, [%0];" ::"r"(bar) : "memory"); }
__device__ __forceinline__ void mbar_arrive_n(uint32_t bar, uint32_t n) { asm volatile("mbarrier.arrive.shared::cta.b64 _, [%0], %1;" ::"r"(bar), "r"(n) : "memory"); }
__device__ __forceinline__ void mbar_wait(uint32_t bar, uint32_t parity) {
  asm volatile("{\n.reg .pred p;\nLAB_WAIT:\nmbarrier.try_wait.parity.shared::cta.b64 p, [%0], %1;\n@p bra DONE;\nbra LAB_WAIT;\nDONE:\n}" ::"r"(bar), "r"(parity) : "memory");
}
__device__ __forceinline__ void mbar_wait2(uint32_t a, uint32_t pa, uint32_t b, uint32_t pb) {
  asm volatile("{\n.reg .pred p, q;\nLAB_WAIT:\nmbarrier.try_wait.parity.shared::cta.b64 p, [%0], %1;\nmbarrier.try_wait.parity.shared::cta.b64 q, [%2], %3;\n"
               "and.pred p, p, q;\n@p bra DONE;\nbra LAB_WAIT;\nDONE:\n}" ::"r"(a), "r"(pa), "r"(b), "r"(pb) : "memory");
}
__device__ __forceinline__ void mbar_wait3(uint32_t a, uint32_t pa, uint32_t b, uint32_t pb) {
  asm volatile("{\n.reg .pred p, q, r;\nLAB_WAIT:\nmbarrier.try_wait.parity.shared::cta.b64 p, [%0], %1;\nmbarrier.try_wait.parity.shared::cta.b64 q, [%2], %3;\n"
               "mbarrier.try_wait.parity.shared::cta.b64 r, [%2+8], %3;\nand.pred p, p, q;\nand.pred p, p, r;\n@p bra DONE;\nbra LAB_WAIT;\nDONE:\n}" ::"r"(a), "r"(pa), "r"(b), "r"(pb) : "memory");
}
__device__ __forceinline__ bool mbar_probe2(uint32_t a, uint32_t pa, uint32_t b, uint32_t pb) {
  uint32_t ok;
  asm volatile("{\n.reg .pred p, q;\nmbarrier.test_wait.parity.shared::cta.b64 p, [%1], %2;\nmbarrier.test_wait.parity.shared::cta.b64 q, [%3], %4;\n"
               "and.pred p, p, q;\nselp.u32 %0, 1, 0, p;\n}" : "=r"(ok) : "r"(a), "r"(pa), "r"(b), "r"(pb) : "memory");
  return ok != 0;
}
__device__ __forceinline__ void tma_load_3d(uint32_t dst, const CUtensorMap* tm, uint32_t bar, int c0, int c1, int c2) {
  asm volatile("cp.async.bulk.tensor.3d.shared::cluster.global.mbarrier::complete_tx::bytes [%0], [%1, {%3, %4, %5}], [%2];"
               ::"r"(dst), "l"(tm), "r"(bar), "r"(c0), "r"(c1), "r"(c2) : "memory");
}
__device__ __forceinline__ void tma_load_2d(uint32_t dst, const CUtensorMap* tm, uint32_t bar, int c0, int c1) {
  asm volatile("cp.async.bulk.tensor.2d.shared::cluster.global.mbarrier::complete_tx::bytes [%0], [%1, {%3, %4}], [%2];"
               ::"r"(dst), "l"(tm), "r"(bar), "r"(c0), "r"(c1) : "memory");
}
__device__ __forceinline__ void tma_load_w(uint32_t dst, const CUtensorMap* tm, uint32_t bar, int col, int kb) {
#pragma unroll
  for (int q = 0; q < 2; q++)
    asm volatile("cp.async.bulk.tensor.5d.shared::cluster.global.mbarrier::complete_tx::bytes [%0], [%1, {%3, %4, %4, %4, %5}], [%2];"
                 ::"r"(dst + q * 8192), "l"(tm), "r"(bar), "r"(col + q * 64), "r"(0), "r"(2 * kb) : "memory");
}
__device__ __forceinline__ void tma_prefetch_w(const CUtensorMap* tm, int col, int kb) {
#pragma unroll
  for (int q = 0; q < 2; q++)
    asm volatile("cp.async.bulk.prefetch.tensor.5d.L2.global [%0, {%1, %2, %2, %2, %3}];" ::"l"(tm), "r"(col + q * 64), "r"(0), "r"(2 * kb) : "memory");
}
__device__ __forceinline__ void bulk_load(uint32_t dst, const void* g, uint32_t bytes, uint32_t bar) {
  asm volatile("cp.async.bulk.shared::cluster.global.mbarrier::complete_tx::bytes [%0], [%1], %2, [%3];" ::"r"(dst), "l"(g), "r"(bytes), "r"(bar) : "memory");
}
__device__ __forceinline__ void prefetch_map(const CUtensorMap* tm) { asm volatile("prefetch.tensormap [%0];" ::"l"(tm) : "memory"); }
__device__ __forceinline__ void fence_async_smem() { asm volatile("fence.proxy.async.shared::cta;" ::: "memory"); }
__device__ __forceinline__ void fence_async_global() { asm volatile("fence.proxy.async.global;" ::: "memory"); }
__device__ __forceinline__ void fence_gpu() { asm volatile("fence.release.gpu;" ::: "memory"); }
__device__ __forceinline__ void st_flag(unsigned* p, unsigned v) { asm volatile("st.relaxed.gpu.global.u32 [%0], %1;" ::"l"(p), "r"(v) : "memory"); }
__device__ __forceinline__ unsigned ld_flag(const unsigned* p) { unsigned v; asm volatile("ld.relaxed.gpu.global.u32 %0, [%1];" : "=r"(v) : "l"(p) : "memory"); return v; }
__device__ __forceinline__ uint4 ldcg4(const void* p) { uint4 v; asm volatile("ld.global.cg.v4.u32 {%0,%1,%2,%3}, [%4];" : "=r"(v.x), "=r"(v.y), "=r"(v.z), "=r"(v.w) : "l"(p)); return v; }
__device__ __forceinline__ uint4 ld_pkt(const uint4* p) {
  uint4 v; asm volatile("{\n.reg .b128 t;\nld.relaxed.gpu.global.b128 t, [%4];\nmov.b128 {%0,%1,%2,%3}, t;\n}" : "=r"(v.x), "=r"(v.y), "=r"(v.z), "=r"(v.w) : "l"(p) : "memory"); return v;
}
__device__ __forceinline__ void st_pkt(uint4* p, uint32_t a, uint32_t b, uint32_t c, uint32_t tag) {
  asm volatile("{\n.reg .b128 t;\nmov.b128 t, {%1,%2,%3,%4};\nst.relaxed.gpu.global.b128 [%0], t;\n}" ::"l"(p), "r"(a), "r"(b), "r"(c), "r"(tag) : "memory");
}
__device__ __forceinline__ void st_v4(uint4* p, uint32_t a, uint32_t b, uint32_t c, uint32_t d) { asm volatile("st.relaxed.gpu.global.v4.u32 [%0], {%1,%2,%3,%4};" ::"l"(p), "r"(a), "r"(b), "r"(c), "r"(d) : "memory"); }
__device__ __forceinline__ void stg128(uint4* p, uint4 v) { asm volatile("st.global.v4.u32 [%0], {%1,%2,%3,%4};" ::"l"(p), "r"(v.x), "r"(v.y), "r"(v.z), "r"(v.w) : "memory"); }
__device__ __forceinline__ void sts32(uint32_t addr, uint32_t a) { asm volatile("st.shared.u32 [%0], %1;" ::"r"(addr), "r"(a) : "memory"); }
__device__ __forceinline__ void sts64(uint32_t addr, uint32_t a, uint32_t b) { asm volatile("st.shared.v2.u32 [%0], {%1,%2};" ::"r"(addr), "r"(a), "r"(b) : "memory"); }
__device__ __forceinline__ uint32_t mul2(uint32_t a, uint32_t b) { uint32_t r; asm("mul.rn.bf16x2 %0, %1, %2;" : "=r"(r) : "r"(a), "r"(b)); return r; }
__device__ __forceinline__ uint32_t add2(uint32_t a, uint32_t b) { uint32_t r; asm("add.rn.bf16x2 %0, %1, %2;" : "=r"(r) : "r"(a), "r"(b)); return r; }
__device__ __forceinline__ bool elect() {
  uint32_t p; asm volatile("{\n.reg .pred q;\nelect.sync _|q, 0xffffffff;\nselp.u32 %0, 1, 0, q;\n}" : "=r"(p)); return p != 0;
}
__device__ __forceinline__ void wgmma_fence() { asm volatile("wgmma.fence.sync.aligned;" ::: "memory"); }
__device__ __forceinline__ void wgmma_commit() { asm volatile("wgmma.commit_group.sync.aligned;" ::: "memory"); }
template <int N> __device__ __forceinline__ void wgmma_wait() { asm volatile("wgmma.wait_group.sync.aligned %0;" ::"n"(N) : "memory"); }
template <int N> __device__ __forceinline__ void fence_regs(float (&d)[N]) {
#pragma unroll
  for (int i = 0; i < N; i++) asm volatile("" : "+f"(d[i])::"memory");
}
template <int R> __device__ __forceinline__ void reg_alloc() { asm volatile("setmaxnreg.inc.sync.aligned.u32 %0;" ::"n"(R)); }
template <int R> __device__ __forceinline__ void reg_dealloc() { asm volatile("setmaxnreg.dec.sync.aligned.u32 %0;" ::"n"(R)); }
__device__ __forceinline__ void wg_bar(int w) { asm volatile("bar.sync %0, 128;" ::"r"(w + 1) : "memory"); }
__device__ __forceinline__ constexpr uint32_t desc_lo(uint32_t addr, uint32_t lbo) { return (addr >> 4) + ((lbo >> 4) << 16); }
__device__ __forceinline__ uint32_t pack2(float lo, float hi) { uint32_t r; asm("cvt.rn.bf16x2.f32 %0, %1, %2;" : "=r"(r) : "f"(hi), "f"(lo)); return r; }
__device__ __forceinline__ float lo16(uint32_t v) { return __uint_as_float(v << 16); }
__device__ __forceinline__ float hi16(uint32_t v) { return __uint_as_float(v & 0xFFFF0000u); }
__device__ __forceinline__ float ex2(float x) { float r; asm("ex2.approx.ftz.f32 %0, %1;" : "=f"(r) : "f"(x)); return r; }
__device__ __forceinline__ float rcp(float x) { float r; asm("rcp.approx.ftz.f32 %0, %1;" : "=f"(r) : "f"(x)); return r; }
__device__ __forceinline__ uint32_t movm(uint32_t a) { uint32_t d; asm volatile("movmatrix.sync.aligned.m8n8.trans.b16 %0, %1;" : "=r"(d) : "r"(a)); return d; }
__device__ __forceinline__ void stsm4(uint32_t addr, uint32_t a, uint32_t b, uint32_t c, uint32_t d) {
  asm volatile("stmatrix.sync.aligned.m8n8.x4.shared.b16 [%0], {%1,%2,%3,%4};" ::"r"(addr), "r"(a), "r"(b), "r"(c), "r"(d) : "memory");
}
__device__ __forceinline__ void ldsm4(uint32_t addr, uint32_t (&r)[4]) {
  asm volatile("ldmatrix.sync.aligned.m8n8.x4.shared.b16 {%0,%1,%2,%3}, [%4];" : "=r"(r[0]), "=r"(r[1]), "=r"(r[2]), "=r"(r[3]) : "r"(addr) : "memory");
}
__device__ __forceinline__ void sts128(uint32_t addr, uint32_t a, uint32_t b, uint32_t c, uint32_t d) {
  asm volatile("st.shared.v4.u32 [%0], {%1,%2,%3,%4};" ::"r"(addr), "r"(a), "r"(b), "r"(c), "r"(d) : "memory");
}
__device__ __forceinline__ void lds128(uint32_t addr, uint32_t& a, uint32_t& b, uint32_t& c, uint32_t& d) {
  asm volatile("ld.shared.v4.u32 {%0,%1,%2,%3}, [%4];" : "=r"(a), "=r"(b), "=r"(c), "=r"(d) : "r"(addr) : "memory");
}
__device__ __forceinline__ float lds32f(uint32_t addr) { float v; asm volatile("ld.shared.f32 %0, [%1];" : "=f"(v) : "r"(addr) : "memory"); return v; }
__device__ __forceinline__ float2 lds64f(uint32_t addr) { float2 v; asm volatile("ld.shared.v2.f32 {%0,%1}, [%2];" : "=f"(v.x), "=f"(v.y) : "r"(addr) : "memory"); return v; }
__device__ __forceinline__ void mma16816(float (&d)[4], uint32_t a0, uint32_t a1, uint32_t a2, uint32_t a3, uint32_t b0, uint32_t b1) {
  asm("mma.sync.aligned.m16n8k16.row.col.f32.bf16.bf16.f32 {%0,%1,%2,%3}, {%4,%5,%6,%7}, {%8,%9}, {%0,%1,%2,%3};"
      : "+f"(d[0]), "+f"(d[1]), "+f"(d[2]), "+f"(d[3]) : "r"(a0), "r"(a1), "r"(a2), "r"(a3), "r"(b0), "r"(b1));
}
__device__ __forceinline__ void mma1688(float (&d)[4], uint32_t a0, uint32_t a1, uint32_t b0) {
  asm("mma.sync.aligned.m16n8k8.row.col.f32.bf16.bf16.f32 {%0,%1,%2,%3}, {%4,%5}, {%6}, {%0,%1,%2,%3};"
      : "+f"(d[0]), "+f"(d[1]), "+f"(d[2]), "+f"(d[3]) : "r"(a0), "r"(a1), "r"(b0));
}

__device__ __forceinline__ float qsum(float v) { v += __shfl_xor_sync(0xffffffffu, v, 1); v += __shfl_xor_sync(0xffffffffu, v, 2); return v; }

constexpr int NCTA = 132;
#define NB_ 6
#define NA_ 5
constexpr int NB = NB_;
constexpr int NA = NA_;
constexpr uint32_t SLOT = 16384;
constexpr uint32_t SB = 1024;
constexpr uint32_t OFF_B = 0;
constexpr uint32_t OFF_A = NB * SLOT;
constexpr uint32_t OFF_S = OFF_A + NA * SLOT;
constexpr uint32_t OFF_T = OFF_S + 20480;
constexpr uint32_t OFF_CS = OFF_T + 24576;
constexpr uint32_t OFF_MR = OFF_CS + 4640;
constexpr uint32_t OFF_BAR = OFF_MR + 512;
constexpr uint32_t OFF_MA = OFF_S, OFF_MB = OFF_CS - 2048;
constexpr uint32_t BAR_FULLB = OFF_BAR;
constexpr uint32_t BAR_FULLA = BAR_FULLB + 64;
constexpr uint32_t BAR_EMPTYB = BAR_FULLA + 64;
constexpr uint32_t BAR_EMPTYA = BAR_EMPTYB + 64;
constexpr uint32_t BAR_SIGP = BAR_EMPTYA + 64;
constexpr uint32_t BAR_SIGT = BAR_SIGP + 24;
constexpr uint32_t BAR_STAT = BAR_SIGP + 64;
constexpr uint32_t BAR_HALO = BAR_STAT + 16;
constexpr uint32_t BAR_CS = BAR_HALO + 8;
constexpr uint32_t BAR_WPHI = BAR_CS + 16;
constexpr uint32_t BAR_KV = BAR_WPHI + 8;
constexpr uint32_t BAR_STG = BAR_KV + 16;
constexpr uint32_t BAR_EPOCH = BAR_STG + 48;
constexpr uint32_t BAR_LAND = OFF_BAR + 7 * 64;
constexpr uint32_t OFF_EPOCH = OFF_BAR + 8 * 64;
static_assert(BAR_EPOCH < BAR_LAND, "barriers");
constexpr uint32_t SMEM_BYTES = OFF_EPOCH + 8;
static_assert(SMEM_BYTES <= 232448 && NB % 2 == 0 && NB <= 8 && NA <= 6, "smem");

#define CREGS 224
#define PREGS 56
#define PF1 19
#define PF2 21
#define PRE_A 2
#define PRE_B 4
#define CSNEED 0xF001u
#define PS0 1
#define PS1 2
#define SD 1000
#define KSPLIT 12
#define KEEP 16
#define NJ 3
#define KSL 1000
#define PSL 0
#define KVS 12
#define D2 2000
#define D3 1500
#define G0 50
#define MAP 3
#define PMAP 0x76321450u
#define XA 3
#define CP 500
#define S0 200
#define NS 2
#define SW 2
#define SA 1
#define SB_ 4
#define ND0 1
#define KC 8
#define CO 0
#define SE 500
#define PAA 1600
#define PAX 900
#define PA0 1800
#define PX0 1100
#define XN 1
#define RG 1
#define KI 1
#define TSK 3
constexpr int NTHREADS = 384;

struct Params {
  CUtensorMap mx;
  CUtensorMap mw[3];
  CUtensorMap mwo[2];
  CUtensorMap mcs[2];
  CUtensorMap mwphi;
  uint4* out;
};

#define XBUF(L) 1
__device__ __align__(256) uint4 g_img[XBUF(3) + 1][16][16][1024];
__device__ __forceinline__ uint32_t img_code(bool isx, int L) { return isx ? (L & 1) | (L & 2) << 15 : ~L & 1; }
__device__ __forceinline__ uint32_t img_mask(bool isx) { return isx ? 0x10001u : 1u; }
__device__ __align__(256) uint4 g_wf[2][8][16][1024];
__device__ __align__(256) uint4 g_stats[16][2][8][32];
__device__ __align__(256) uint4 g_halo[16][8][2][256];
__device__ __align__(256) float g_cs[2][2][3072];
__device__ __align__(256) uint4 g_kvpart[8][16][2][544];
__device__ __align__(256) uint4 g_kvfin[8][16][80];
__device__ __align__(256) unsigned g_hint[16][32];
__device__ __align__(256) unsigned g_jflag[3][8][32];
__device__ unsigned g_ctr;
__device__ __forceinline__ unsigned vblock() {
  unsigned s;
  asm volatile("mov.u32 %0, %%smid;" : "=r"(s));
  const unsigned r = s & 1;
  s >>= 1;
  const unsigned t = s - 32, q = (t * 37) >> 8;
  const unsigned hi = s < 60 ? 12 + (t - 7 * q) * 8 + q : (s < 62 ? s + 4 : s - 58);
  unsigned b = 2 * (s < 32 ? (s & 7) * 8 + (s >> 3) : hi) + r;
  if (b < 128) b = (b & 15) | ((PMAP >> ((b >> 4) * 4)) & 7) << 4;
  if (s >= 62) b = 8 + 4 * r + s - 62;
  unsigned n;
  asm volatile("mov.u32 %0, %%nsmid;" : "=r"(n));
  return __shfl_sync(0xffffffffu, n == NCTA ? b : blockIdx.x, 0);
}
#define TS(who, id) do {} while (0)
#define TSW(id) do {} while (0)

#define TSH(id) do {} while (0)
#define TSMASK 0xFFFF
#define TSL_(a) do { if ((TSMASK >> (a)) & 1) TSW((a) + L * 12); } while (0)
__device__ __forceinline__ int cta_m(unsigned b) { return ((b >> 2) & 12) | (b & 3); }
__device__ __forceinline__ int cta_j(unsigned b) { return ((b >> 2) & 3) | ((b >> 4) & 4); }
struct Ring { uint32_t s, ph; };
template <int N> __device__ __forceinline__ void adv(Ring& r) { if (++r.s == N) { r.s = 0; r.ph ^= 1; } }
template <int N> __device__ __forceinline__ void rewind2(Ring& r) { if (r.s < 2) { r.s += N - 2; r.ph ^= 1; } else r.s -= 2; }
__device__ __forceinline__ int other_tile(int t, int j) { return (t == (j | 4) ? 7 : t) ^ (~j & 4); }
__device__ __forceinline__ int o_order(int i, int j) {
  if (i < 2) return 2 * j + i;
  const int odd = i >= 9;
  return 2 * other_tile(i - 2 - 7 * odd, j) + odd;
}
__device__ __forceinline__ int kv_order(int i, int j, int L) { return L > 0 ? o_order(i, j) : (i + 14 + 2 * (j & 4)) & 15; }

__device__ __forceinline__ unsigned poll_flags(const unsigned* f, int n, unsigned need, unsigned tag) {
  const int lane = threadIdx.x & 31;
  unsigned mask; int it = 0;
  do {
    unsigned v = lane < n ? ld_flag(f + lane) : 0u;
    mask = __ballot_sync(0xffffffffu, lane < n && (int)(v - tag) >= 0);
    if (++it > (1 << 22)) __trap();
  } while ((mask & need) != need);
  fence_async_global();
  return mask;
}
template <bool WAIT = true>
__device__ __forceinline__ unsigned get_tag(uint32_t sb) {
  if (WAIT) mbar_wait(sb + BAR_EPOCH, 0);
  unsigned t; asm volatile("ld.shared.u32 %0, [%1];" : "=r"(t) : "r"(sb + OFF_EPOCH) : "memory");
  return t;
}

__device__ __forceinline__ int lane_id() { int l; asm volatile("mov.u32 %0, %%laneid;" : "=r"(l)); return l; }
__device__ __forceinline__ unsigned seq4(unsigned tag, int L) { return 8u | ((tag & 1u) << 2) | (unsigned)L; }
constexpr float LOG2E = 1.4426950408889634f;

__device__ __forceinline__ float bb_fence(int never, const void* p = &g_ctr, uint32_t keep = 0) {
  while (never < 0) never = ld_flag((const unsigned*)p) + keep;
  return __int_as_float(never >> 30);
}
__device__ __forceinline__ uint32_t solid(uint32_t v) { return __shfl_sync(0xffffffffu, v, threadIdx.x & 31); }
template <class T> __device__ __forceinline__ T* solid(T* p) { return (T*)__shfl_sync(0xffffffffu, (unsigned long long)p, threadIdx.x & 31); }
constexpr uint32_t HA128 = 0x40000040u, HA64 = 0x80000040u;
struct Ctx {
  static constexpr uint32_t sb = SB;
  uint32_t ab, da0;
  int w, warp, lane, g, c;
  int goff;
  __device__ __forceinline__ int m() const { return goff >> 14; }
  __device__ __forceinline__ int j() const { return (goff >> 4) & 7; }
  bool elected;
  Ring ra, rb;
  uint32_t pa, pb;
  uint32_t ha, k2;
  uint32_t mrow, mxor, mhi;
  __device__ __forceinline__ uint32_t aslot(uint32_t s) const { return ab + s * SLOT; }
  __device__ __forceinline__ uint32_t fullA(uint32_t s) const { return sb + BAR_FULLA + s * 8; }
  __device__ __forceinline__ uint32_t fullB(uint32_t s) const { return sb + BAR_FULLB + s * 8; }
  __device__ __forceinline__ void releaseA(uint32_t s) const { if (elected) mbar_arrive(sb + BAR_EMPTYA + s * 8); }
  __device__ __forceinline__ void releaseB(uint32_t s) const { if (elected) mbar_arrive(sb + BAR_EMPTYB + s * 8); }
  __device__ __forceinline__ uint32_t maddr(uint32_t tile, uint32_t ch) const { return tile + mrow + (((ch + mhi) ^ mxor) << 4); }
  __device__ __forceinline__ uint32_t oo() const { return warp * 128 + g * 4 + (c ^ (g >> 1)); }
  __device__ __forceinline__ uint4* img(int b, int hp) const { return ip + (b * 256 + hp) * 1024; }
  uint4* ip;
  uint32_t so;
  __device__ __forceinline__ uint32_t held(int i) const { return ra.s + i < 2 ? ra.s + i + NA - 2 : ra.s + i - 2; }
};

template <int N, bool FIRST, bool O = true>
__device__ __forceinline__ void gemm_issue(float (&acc)[N / 2], Ctx& x, bool ready = false) {
  if (!ready) {
    if (N == 256) mbar_wait3(x.fullA(x.ra.s), x.ra.ph, x.fullB(x.rb.s), x.rb.ph);
    else mbar_wait2(x.fullA(x.ra.s), x.ra.ph, x.fullB(x.rb.s), x.rb.ph);
  }
  const uint32_t da = x.da0 + x.ra.s * (SLOT / 16), db = desc_lo(SB + OFF_B, 8192) + x.rb.s * (SLOT / 16);
  wgmma_fence();
#pragma unroll
  for (int k = 0; k < 4; k++) {
    const uint32_t a = da + (k >> 1) * (O ? 32 : x.k2) + (k & 1) * 2, ha = O ? HA64 : x.ha;
    if constexpr (N == 256) wgmma_ss_n256(acc, a, ha, db + 128 * k, !(FIRST && k == 0));
    else wgmma_ss_n128(acc, a, ha, db + 128 * k, !(FIRST && k == 0));
  }
  wgmma_commit();
}
template <int N>
__device__ __forceinline__ void gemm_next(Ctx& x) {
  x.pa = x.ra.s; x.pb = x.rb.s;
  if (N == 256) x.rb.s++;
  adv<NA>(x.ra); adv<NB>(x.rb);
}
template <int N>
__device__ __forceinline__ void gemm_release(Ctx& x, bool relA) {
  if (relA) x.releaseA(x.pa);
  x.releaseB(x.pb);
  if (N == 256) x.releaseB(x.pb + 1);
}
template <int N>
__device__ __forceinline__ void gemm_retire(Ctx& x, bool relA) { wgmma_wait<1>(); gemm_release<N>(x, relA); gemm_next<N>(x); }
template <bool O = true>
__device__ __forceinline__ void gemm_run(float (&acc)[64], Ctx& x, int n, int hold, int n4 = 0) {
  bool ready = false;
#pragma unroll 1
  for (; n > 0; n--) {
    gemm_issue<128, false, O>(acc, x, ready);
    const uint32_t pa = x.pa, pb = x.pb;
    gemm_next<128>(x);
    ready = mbar_probe2(x.fullA(x.ra.s), x.ra.ph, x.fullB(x.rb.s), x.rb.ph);
    wgmma_wait<1>();
    if (n > hold) x.releaseA(pa);
    x.releaseB(pb);
  }
}
__device__ __forceinline__ void gemm_end(float (&acc)[64], Ctx& x) { wgmma_wait<0>(); fence_regs(acc); gemm_release<128>(x, false); }

__device__ __forceinline__ void rows_load(uint4* r, uint32_t tile, const Ctx& x) {
#pragma unroll
  for (int q = 0; q < 4; q++) {
    const uint32_t row = x.warp * 16 + 4 * q + (x.lane >> 3);
    lds128(tile + row * 128 + (((x.lane & 7) ^ (row & 7)) << 4), r[q].x, r[q].y, r[q].z, r[q].w);
  }
}
__device__ __forceinline__ void rows_store(const uint4* r, uint4* g) {
#pragma unroll
  for (int q = 0; q < 4; q++) stg128(g + q * 1024, r[q]);
}
__device__ __forceinline__ void publish(int id, const Ctx& x) { __syncwarp(); if (x.lane == 0) mbar_arrive(x.sb + BAR_SIGP + id * 8); }
__device__ __forceinline__ uint32_t img_tag(uint32_t v, bool isx, int L, const Ctx& x) {
  const uint32_t mk = ((x.lane ^ (x.warp * 4)) & 7) ? 0u : img_mask(isx);
  return (v & ~mk) | (img_code(isx, L) & mk);
}
__device__ __forceinline__ void img_tag(uint4 (&r)[4], bool isx, int L, const Ctx& x) {
#pragma unroll
  for (int q = 0; q < 4; q++) { uint32_t& v = q == 0 ? r[q].x : (q == 1 ? r[q].y : (q == 2 ? r[q].z : r[q].w)); v = img_tag(v, isx, L, x); }
}
__device__ __forceinline__ void img_store(const uint4 (&r)[4], uint4* g) {
#pragma unroll
  for (int q = 0; q < 4; q++) stg128(g + q * 32, r[q]);
}
__device__ __forceinline__ void img_sts(const uint4 (&r)[4], uint32_t tile, const Ctx& x) {
#pragma unroll
  for (int q = 0; q < 4; q++) sts128(tile + x.so + q * 512, r[q].x, r[q].y, r[q].z, r[q].w);
}
__device__ __forceinline__ void img_load(uint32_t (&v)[16], uint32_t tile, const Ctx& x) {
#pragma unroll
  for (int q = 0; q < 4; q++) lds128(tile + x.so + q * 512, v[4 * q], v[4 * q + 1], v[4 * q + 2], v[4 * q + 3]);
}
__device__ __forceinline__ void img_unpack(float* a, const uint32_t (&v)[16]) {
#pragma unroll
  for (int q = 0; q < 16; q++) { a[4 * (q & 7) + 2 * (q >> 3)] = lo16(v[q]); a[4 * (q & 7) + 2 * (q >> 3) + 1] = hi16(v[q]); }
}

template <int N>
__device__ __forceinline__ void stats_acc(const float* a, float (&t)[4]) {
#pragma unroll
  for (int i = 0; i < N; i++) { t[i & 2] += a[i]; t[(i & 2) + 1] = fmaf(a[i], a[i], t[(i & 2) + 1]); }
}
__device__ __forceinline__ void stats_send(float (&t)[4], int L, const Ctx& x) {
  const unsigned seq = seq4(get_tag<false>(x.sb), L);
#pragma unroll
  for (int q = 0; q < 4; q++) t[q] = qsum(t[q]);
  if (x.c == 0) st_pkt(&g_stats[x.m()][x.w][x.j()][x.warp * 8 + x.g], __float_as_uint(t[0]), __float_as_uint(t[1]), __float_as_uint(t[2]), (__float_as_uint(t[3]) & ~15u) | seq);
}
__device__ __forceinline__ void out_epilogue(const float (&acc)[64], uint4 (&r1)[4], float (&t)[4], uint4* g, int L, Ctx& x) {
  const uint32_t t0 = x.aslot(x.ra.s), t1 = x.aslot(x.ra.s + 1 == NA ? 0 : x.ra.s + 1);
  if (L == 3) {
#pragma unroll
    for (int p = 0; p < 8; p++) {
      stsm4(x.maddr(p < 4 ? t0 : t1, (p & 3) * 2), pack2(acc[8 * p], acc[8 * p + 1]), pack2(acc[8 * p + 2], acc[8 * p + 3]),
            pack2(acc[8 * p + 4], acc[8 * p + 5]), pack2(acc[8 * p + 6], acc[8 * p + 7]));
      if ((p & 3) == 3) { uint4 r[4]; __syncwarp(); rows_load(r, p < 4 ? t0 : t1, x); rows_store(r, g + (p >> 2) * 8); }
    }
  } else {
    auto pack16 = [&](uint4 (&r)[4], const float* a) {
#pragma unroll
      for (int q = 0; q < 4; q++) { const float* u = a + 16 * (q & 1) + (q & 2); r[q] = make_uint4(pack2(u[0], u[1]), pack2(u[4], u[5]), pack2(u[8], u[9]), pack2(u[12], u[13])); }
    };
    uint4 r0[4];
    pack16(r0, acc);
    img_tag(r0, true, L + 1, x);
    img_store(r0, x.img(XBUF(L + 1), 0));
    const float z = bb_fence(x.goff);
    img_sts(r0, t0, x);
    pack16(r1, acc + 32);
    img_tag(r1, true, L + 1, x);
    img_sts(r1, t1, x);
    float u[4] = {z, z, z, z}, v[4] = {z, z, z, z};
    stats_acc<32>(acc, v);
    stats_acc<32>(acc + 32, u);
#pragma unroll
    for (int q = 0; q < 4; q++) t[q] = u[q] + v[q];
    mbar_wait2(x.fullB(x.rb.s), x.rb.ph, x.fullB(x.rb.s + 1), x.rb.ph);
    fence_async_smem();
    asm volatile("bar.sync %0, %1;" ::"r"(L == 1 ? x.w + 1 : 3), "r"(L == 1 ? 128 : 256) : "memory");
  }
}

struct Stats { float rstd0, rstd1; };
__device__ __forceinline__ Stats load_stats(int half, const Ctx& x) {
  const float2 u = lds64f(x.sb + OFF_MR + half * 256 + (x.warp * 8 + x.g) * 8);
  return {u.x, u.y};
}

template <int NH, int NK, class F>
__device__ __forceinline__ void hedgehog_scale(float* t, const Stats& st, const uint32_t* keep, F use) {
#pragma unroll
  for (int q = 0; q < 16 * NH; q++) t[q] *= ((q & 2) ? st.rstd1 : st.rstd0) * LOG2E;
  use();
  float m[4];
#pragma unroll
  for (int q = 0; q < 4 * NH; q++) {
    const float v = fmaxf(fmaxf(fabsf(t[4 * q]), fabsf(t[4 * q + 1])), fmaxf(fabsf(t[4 * q + 2]), fabsf(t[4 * q + 3])));
    m[q & 3] = q < 4 ? v : fmaxf(m[q & 3], v);
  }
  if (__builtin_expect(__any_sync(0xffffffffu, fmaxf(fmaxf(m[0], m[1]), fmaxf(m[2], m[3])) > 58.f), 0)) {
    float z[16 * NH + NK];
#pragma unroll
    for (int q = 0; q < 16 * NH + NK; q++) z[q] = q < 16 * NH ? t[q % (16 * NH)] : __uint_as_float(keep[q & 15]);
#pragma unroll 1
    for (int r = 0; r < 2 * NH; r++) {
      float hi = -INFINITY, lo = INFINITY;
#pragma unroll 1
      for (int i = 0; i < 16; i++) {
        const int k = (i & 6) * 2 + (i & 1) + (r & 1) * 2 + (r & 2) * 8;
        const float v = z[k];
        if (i < 8) { hi = fmaxf(hi, v); lo = fminf(lo, v); }
        else z[k] = v - fminf(fmaxf(v, lo), hi);
        if (i == 7) {
#pragma unroll 1
          for (int d = 1; d <= 2; d++) { hi = fmaxf(hi, __shfl_xor_sync(0xffffffffu, hi, d)); lo = fminf(lo, __shfl_xor_sync(0xffffffffu, lo, d)); }
          const float mid = 0.5f * hi + 0.5f * lo;
          hi = fmaxf(hi - 58.f, mid); lo = fminf(lo + 58.f, mid);
        }
      }
    }
#pragma unroll
    for (int q = 0; q < 16 * NH; q++) t[q] = z[q];
    use();
  }
}
__device__ __forceinline__ void dual_exp(const float* t, uint32_t (&f)[18], int never) {
  float e[KSPLIT];
#pragma unroll
  for (int q = 0; q < KSPLIT; q++) e[q] = ex2(q < 16 ? t[q] : -t[q & 15]);
  while (never < 0) {
#pragma unroll
    for (int i = 0; i < KSPLIT; i += 4) asm volatile("ld.shared.v4.f32 {%0,%1,%2,%3}, [%4];" : "=f"(e[i]), "=f"(e[i + 1]), "=f"(e[i + 2]), "=f"(e[i + 3]) : "r"(never + i) : "memory");
    never += __float_as_int(e[0]);
  }
#pragma unroll
  for (int q = 0; q < KSPLIT; q += 2) f[q >> 1] = pack2(e[q], e[q + 1]);
#pragma unroll
  for (int q = KSPLIT; q < 32; q += 2) f[q >> 1] = q < 16 ? pack2(ex2(t[q]), ex2(t[q + 1])) : pack2(ex2(-t[q & 15]), ex2(-t[(q & 15) + 1]));
#pragma unroll
  for (int sg = 0; sg < 2; sg++) {
    const uint32_t* u = f + 8 * sg;
    const uint32_t a = add2(add2(u[0], u[2]), add2(u[4], u[6])), b = add2(add2(u[1], u[3]), add2(u[5], u[7]));
    f[16 + sg] = add2(__byte_perm(a, b, 0x5410), __byte_perm(a, b, 0x7632));
  }
}
__device__ __forceinline__ void dual_exp_rcp(const float* t, uint32_t* f) {
#pragma unroll
  for (int q = 0; q < 8; q++) {
    const float a = ex2(t[2 * q]), b = ex2(t[2 * q + 1]), r = rcp(a * b);
    f[q] = pack2(a, b); f[8 + q] = pack2(r * b, r * a);
  }
}
__device__ __forceinline__ void cta_bar() { asm volatile("bar.sync 3, 256;" ::: "memory"); }

template <int N> __device__ __forceinline__ void pin(const uint32_t* v, uint32_t addr) {
#pragma unroll
  for (int i = 0; i < N; i += 4)
    asm volatile("{\n.reg .pred p;\nsetp.eq.u32 p, %0, 0;\n@p st.shared.v4.u32 [%0], {%1,%2,%3,%4};\n}" ::"r"(addr), "r"(v[i]), "r"(v[i + 1]), "r"(v[i + 2]), "r"(v[i + 3]) : "memory");
}

__device__ __forceinline__ void consumer(const Params& P, uint32_t sb, int w, unsigned vb) {
  Ctx x;
  x.w = w;
  x.ab = sb + OFF_A + w * 8192; x.da0 = desc_lo(SB + OFF_A, 16) + w * 512;
  x.lane = threadIdx.x & 31; x.warp = __shfl_sync(0xffffffffu, (threadIdx.x >> 5) & 3, 0); x.g = x.lane >> 2; x.c = x.lane & 3;
  x.goff = (cta_m(vb) * 128 + w) * 128 + cta_j(vb) * 16;
  asm volatile("" : "+r"(x.goff));
  x.elected = (threadIdx.x & 127) == 0;
  x.ra = {0, 0}; x.rb = {0, 0}; x.pa = x.pb = 0;
  {
    const uint32_t row = x.warp * 16 + (x.lane & 15);
    x.mrow = row * 128; x.mxor = row & 7; x.mhi = x.lane >> 4;
  }
  const int goff = x.goff;
  x.ip = solid(&g_img[0][x.m()][2 * x.j()][w * 512 + x.oo()]);
  x.so = solid(16 * x.oo());
  uint4 r1[4];
  float ts[4] = {0.f, 0.f, 0.f, 0.f};
#pragma unroll
  for (int i = 0; i < 4; i++) r1[i] = make_uint4(0, 0, 0, 0);
  TSW(0);
  mbar_wait3(x.fullA(0), 0, x.fullB(0), 0);
#pragma unroll 1
  for (int L = 0; L < 4; L++) {
    float acc[64];
    constexpr uint32_t dcs = desc_lo(SB + OFF_CS, 0);
    if ((L & 1) == 0) {
    float kv[128];
    x.ha = L ? HA64 : HA128; x.k2 = L ? 32 : 4;
    gemm_issue<256, true, false>(kv, x, true); gemm_next<256>(x);
    {
      int i = 1;
#pragma unroll 1
      for (int seg = L ? NS - 1 : 0; seg <= NS; seg++) {
        const int end = seg < NS ? (L == 0 ? 3 + SA * ((x.j() + SW * w) & 3) + SB_ * seg : XA + 1) : 14 + L;
#pragma unroll 1
        do {
          gemm_issue<256, false, false>(kv, x);
          gemm_retire<256>(x, true);
          i++;
          if (i == 5) TSL_(8);
          if (i == 11) TSL_(10);
        } while (i != end);
        if (seg < NS && L == 0) {
          uint32_t v[16];
          float a[32];
#pragma unroll
          for (int q = 0; q < 4; q++) ldsm4(x.maddr(x.aslot(x.pa), 2 * q), reinterpret_cast<uint32_t (&)[4]>(v[4 * q]));
#pragma unroll
          for (int q = 0; q < 16; q++) { a[2 * q] = lo16(v[q]); a[2 * q + 1] = hi16(v[q]); }
          stats_acc<32>(a, ts);
          fence_regs(ts);
          wg_bar(w);
        }
        if (seg == NS - 1) {
          if (L > 0) { img_store(r1, x.img(XBUF(L), 1)); publish(2, x); }
          mbar_wait(sb + BAR_EPOCH, 0);
          stats_send(ts, L, x);
        }
      }
    }
      const Ring kt = x.ra;
      if (L == 0) adv<NA>(x.ra);
#pragma unroll 1
      for (int h = L; h < 2; h++) {
        float d[16];
        mbar_wait2(x.fullA(kt.s), kt.ph, sb + BAR_WPHI, 0);
        wgmma_fence();
#pragma unroll
        for (int q = 0; q < 2; q++) wgmma_ss_n32(d, x.da0 + kt.s * (SLOT / 16) + h * 4 + q * 2, desc_lo(SB + OFF_S + 4096, 512) + w * 256 + h * 128 + q * 64, q);
        wgmma_commit();
        gemm_issue<256, false, false>(kv, x);
        gemm_retire<256>(x, true);
        if (h) x.releaseA(kt.s);
        fence_regs(d);
        uint4* dst = &g_wf[1][x.j()][x.m()][w * 512 + (x.warp * 16 + x.g) * 8 + ((h * 4 + x.c) ^ x.g)];
        dst[0] = make_uint4(pack2(d[0], d[1]), pack2(d[4], d[5]), pack2(d[8], d[9]), pack2(d[12], d[13]));
        dst[64] = make_uint4(pack2(d[2], d[3]), pack2(d[6], d[7]), pack2(d[10], d[11]), pack2(d[14], d[15]));
      }
      const uint32_t dm = desc_lo(SB + OFF_MA, 0) + w * 64;
      mbar_wait2(sb + BAR_STAT, 0, sb + BAR_CS, 0);
      wgmma_fence();
      wgmma_r1_n256(kv, dm, dcs + 96, 1);
      wgmma_commit();
      const Stats st = load_stats(w, x);
      mbar_wait2(x.fullA(x.ra.s), x.ra.ph, x.fullB(x.rb.s), x.rb.ph);
      wgmma_wait<0>();
      fence_regs(kv);
      gemm_release<256>(x, true);
      TSL_(2);
      uint32_t P0[32], P1[32], PH[32];
#pragma unroll
      for (int t = 0; t < 16; t++) { P0[t] = pack2(kv[4 * t] * st.rstd0, kv[4 * t + 1] * st.rstd0); P1[t] = pack2(kv[4 * t + 2] * st.rstd1, kv[4 * t + 3] * st.rstd1); }
      pin<16>(P0, x.mrow + 16);
      {
#pragma unroll
        for (int q = 0; q < 4; q++) sts128((x.warp < 3 ? sb + OFF_T + w * 12288 + x.warp * 4096 : sb + OFF_S + 16384 + w * 2048) + x.lane * 16 + q * 512, P1[4 * q], P1[4 * q + 1], P1[4 * q + 2], P1[4 * q + 3]);
      }
      wgmma_fence();
      wgmma_r1_n128(acc, dm, dcs, 0);
      gemm_issue<128, false, false>(acc, x, true); gemm_next<128>(x);
      TSL_(3);
#pragma unroll
      for (int s = 0; s < 4; s++) {
#pragma unroll
        for (int t = 16 + 8 * (s & 1); t < 24 + 8 * (s & 1); t++) {
          if (s < 2) P1[t] = movm(pack2(kv[4 * t + 2] * st.rstd1, kv[4 * t + 3] * st.rstd1));
          else P0[t] = movm(pack2(kv[4 * t] * st.rstd0, kv[4 * t + 1] * st.rstd0));
        }
        if (s < 3) { gemm_issue<128, false, false>(acc, x); gemm_retire<128>(x, true); }
        if (s == 1) {
          if (x.warp < 3) {
#pragma unroll
            for (int q = 4; q < 8; q++) sts128(sb + OFF_T + w * 12288 + x.warp * 4096 + x.lane * 16 + q * 512, P1[4 * q], P1[4 * q + 1], P1[4 * q + 2], P1[4 * q + 3]);
          } else {
            uint4* dst = &g_halo[x.m()][x.j()][w][x.lane];
#pragma unroll
            for (int q = 0; q < 8; q++) dst[q * 32] = make_uint4(P1[4 * q], P1[4 * q + 1], P1[4 * q + 2], P1[4 * q + 3]);
          }
          publish(3, x);
          gemm_issue<128, false, false>(acc, x);
          gemm_retire<128>(x, true);
        }
      }
      TSL_(4);
      gemm_run<false>(acc, x, 10, 0);
      publish(0, x);
      gemm_issue<128, false, false>(acc, x);
      {
        wg_bar(w);
        uint32_t tr = sb + OFF_T + w * 12288 + (x.warp - 1) * 4096;
        if (x.warp == 0) {
          tr = x.m() > 0 ? sb + OFF_S + 8192 + w * 4096 : tr + 4096;
          if (x.m() > 0) mbar_wait(sb + BAR_HALO, L >> 1);
        }
#pragma unroll
        for (int q = 0; q < 8; q++) lds128(tr + x.lane * 16 + q * 512, PH[4 * q], PH[4 * q + 1], PH[4 * q + 2], PH[4 * q + 3]);
      }
      gemm_retire<128>(x, false);
      gemm_end(acc, x);
      TSL_(5);
      const bool first = (x.m() == 0) && (x.warp == 0);
      const bool hi0 = 2 * x.c > x.g, hi1 = 2 * x.c + 1 > x.g;
      const uint32_t mhi = (hi0 ? 0xFFFFu : 0u) | (hi1 ? 0xFFFF0000u : 0u);
      const uint32_t valid = first ? ~mhi : ~0u;
      const float sc0 = st.rstd0 * (0.17677669529663687f * LOG2E), sc1 = st.rstd1 * (0.17677669529663687f * LOG2E);
      uint32_t xr[2][16];
#pragma unroll
      for (int hp = 0; hp < 2; hp++) {
        const uint32_t tile = x.aslot(x.held(hp));
        uint32_t px[2], py[2];
        float s[2][3][4];
#pragma unroll
        for (int u = 0; u < 2; u++) {
#pragma unroll
          for (int q = 0; q < 12; q++) s[u][q >> 2][q & 3] = 0.f;
#pragma unroll
          for (int ks = 0; ks < 2; ks++) {
            const int t = 8 * hp + 4 * u + 2 * ks;
            const uint32_t a0 = pack2(acc[4 * t], acc[4 * t + 1]), a1 = pack2(acc[4 * t + 2], acc[4 * t + 3]);
            const uint32_t a2 = pack2(acc[4 * t + 4], acc[4 * t + 5]), a3 = pack2(acc[4 * t + 6], acc[4 * t + 7]);
            mma16816(s[u][0], a0, a1, a2, a3, PH[t], PH[t + 1]);
            mma16816(s[u][1], a0, a1, a2, a3, P0[t], P0[t + 1]);
            mma16816(s[u][2], a0, a1, a2, a3, P1[t], P1[t + 1]);
          }
        }
        float e[2][4], big = 0.f;
#pragma unroll
        for (int u = 0; u < 2; u++) {
          e[u][0] = (hi0 ? s[u][0][0] : s[u][1][0]) * sc0; e[u][1] = (hi1 ? s[u][0][1] : s[u][1][1]) * sc0;
          e[u][2] = (hi0 ? s[u][1][2] : s[u][2][2]) * sc1; e[u][3] = (hi1 ? s[u][1][3] : s[u][2][3]) * sc1;
          big = fmaxf(big, fmaxf(fmaxf(fabsf(e[u][0]), fabsf(e[u][1])), fmaxf(fabsf(e[u][2]), fabsf(e[u][3]))));
          px[u] = pack2(ex2(e[u][0]), ex2(e[u][1])) & valid; py[u] = pack2(ex2(e[u][2]), ex2(e[u][3]));
        }
        if (__builtin_expect(__any_sync(0xffffffffu, big > 58.f), 0)) {
#pragma unroll
          for (int q = 0; q < 4; q++) {
            float v0 = e[q >> 1][2 * (q & 1)], v1 = e[q >> 1][2 * (q & 1) + 1];
            if (first && !(q & 1)) { if (hi0) v0 = -INFINITY; if (hi1) v1 = -INFINITY; }
            float r = fmaxf(v0, v1);
            r = fmaxf(r, __shfl_xor_sync(0xffffffffu, r, 1)); r = fmaxf(r, __shfl_xor_sync(0xffffffffu, r, 2));
            ((q & 1) ? py : px)[q >> 1] = pack2(ex2(v0 - r), ex2(v1 - r));
          }
        }
        float r[2][2];
#pragma unroll
        for (int u = 0; u < 2; u++) {
          float d[4] = {0.f, 0.f, 0.f, 0.f};
          mma1688(d, px[u], py[u], 0x3F803F80u);
          r[u][0] = rcp(d[0]); r[u][1] = rcp(d[2]);
        }
        uint32_t o[8][2];
        uint4 ro[4];
#pragma unroll
        for (int q = 0; q < 8; q++) {
          float d[4] = {0.f, 0.f, 0.f, 0.f};
          const int t = 16 + 8 * hp + q, u = q >> 2;
          mma16816(d, px[u] & mhi, 0u, px[u] & ~mhi, py[u] & mhi, PH[t], P0[t]);
          mma1688(d, 0u, py[u] & ~mhi, P1[t]);
          o[q][0] = pack2(d[0] * r[u][0], d[1] * r[u][0]); o[q][1] = pack2(d[2] * r[u][1], d[3] * r[u][1]);
        }
#pragma unroll
        for (int q = 0; q < 4; q++) ro[q] = make_uint4(o[4 * (q & 1)][q >> 1], o[4 * (q & 1) + 1][q >> 1], o[4 * (q & 1) + 2][q >> 1], o[4 * (q & 1) + 3][q >> 1]);
        img_tag(ro, false, 0, x);
        img_store(ro, x.img(0, hp));
        if (hp == 0) bb_fence(x.goff);
        if (hp == 0) {
#pragma unroll
          for (int i = 0; i < 2; i++) {
            const uint32_t ti = x.aslot(x.held(i));
            if (L) img_load(xr[i], ti, x);
            else {
#pragma unroll
              for (int q = 0; q < 4; q++) ldsm4(x.maddr(ti, 2 * q), reinterpret_cast<uint32_t (&)[4]>(xr[i][4 * q]));
            }
          }
          __syncwarp();
        }
        img_sts(ro, tile, x);
      }
      if (L == 0) {
#pragma unroll
        for (int hp = 0; hp < 2; hp++) {
          uint32_t v[16];
#pragma unroll
          for (int q = 0; q < 16; q++) asm volatile("mov.b32 %0, %1;" : "=r"(v[(q & 1) * 8 + (q >> 1)]) : "r"(xr[hp][q]));
#pragma unroll
          for (int q = 0; q < 16; q++) xr[hp][q] = v[q];
        }
      }
      img_unpack(acc, xr[0]); img_unpack(acc + 32, xr[1]);
    } else {
      float kv[128];
      float (&kv0)[64] = reinterpret_cast<float (&)[64]>(kv[0]);
      float (&kv1)[64] = reinterpret_cast<float (&)[64]>(kv[64]);
      auto mma8 = [&](uint32_t as, uint32_t bs, int i, bool fence) {
        const uint32_t da = desc_lo(SB + OFF_A, 16) + as * (SLOT / 16), db = desc_lo(SB + OFF_B, 8192) + bs * (SLOT / 16);
        if (fence) wgmma_fence();
#pragma unroll
        for (int k = 0; k < 4; k++) {
          wgmma_ss_n128(kv0, da + (k >> 1) * 32 + (k & 1) * 2, HA64, db + 128 * k, i + k);
          wgmma_ss_n128(kv1, da + 512 + (k >> 1) * 32 + (k & 1) * 2, HA64, db + 128 * k, i + k);
        }
        wgmma_commit();
      };
      constexpr uint32_t dm = desc_lo(SB + OFF_MB, 0);
      auto relB = [&](uint32_t s) { mbar_arrive_n(sb + BAR_EMPTYB + s * 8, 2); };
      auto skip = [&]() {
#pragma unroll
        for (int q = 0; q < 6 - NJ; q++) adv<NA>(x.ra);
        x.rb.s = w ? (2 + NJ) % 6 : 4;
        if (!w && NJ < 4) x.rb.ph ^= 1;
      };
      static_assert(NA == 5 && NB == 6, "ring arithmetic");
      mma8(x.ra.s, x.rb.s + w, 0, true);
      img_store(r1, x.img(XBUF(L), 1));
      gemm_next<256>(x);
#pragma unroll 1
      for (int i = 1; i < NJ; i++) {
        mbar_wait2(x.fullA(x.ra.s), x.ra.ph, x.fullB(x.rb.s + w), x.rb.ph);
        mma8(x.ra.s, x.rb.s + w, 1, true);
        if (i == 1) { stats_send(ts, L, x); publish(2, x); }
        wgmma_wait<1>();
        if (x.elected) { x.releaseA(x.pa); relB(x.pb + w); }
        gemm_next<256>(x);
      }
      if (w) {
        wgmma_wait<0>();
        if (x.elected) { x.releaseA(x.pa); relB(x.pb + 1); }
        skip();
        asm volatile("bar.sync 7, 256;" ::: "memory");
      }
      TSL_(8);
      {
        const int t = lane_id() + 32 * x.warp;
        uint32_t mask = t < 2 ? ((w ? (t ? 0xFF3Fu : 0x3FFFu) : 0xFFFFu) >> (NJ - 1)) & (w ? ~1u : ~0u) : 0u, cnt = 1 + t;
        bool ready = false;
#pragma unroll 1
        for (int i = NJ; i < 15; i++) {
          if (!ready) mbar_wait2(x.fullA(x.ra.s), x.ra.ph, x.fullB(x.rb.s), x.rb.ph);
          mma8(x.ra.s, x.rb.s, 1, true);
          const uint32_t bar = sb + (t ? BAR_EMPTYB + x.pb * 8 : BAR_EMPTYA + x.pa * 8);
          gemm_next<128>(x);
          if (w && i == 11) x.rb.s = 4;
          ready = mbar_probe2(x.fullA(x.ra.s), x.ra.ph, x.fullB(x.rb.s), x.rb.ph);
          wgmma_wait<1>();
          if (mask & 1) mbar_arrive_n(bar, cnt);
          mask >>= 1; cnt = 2;
          if (i == 8 && w) asm volatile("bar.arrive 9, 256;" ::: "memory");
          if (i == 9) TSL_(10);
        }
        if (!ready) mbar_wait2(x.fullA(x.ra.s), x.ra.ph, x.fullB(x.rb.s), x.rb.ph);
        const uint32_t da = desc_lo(SB + OFF_A, 16) + x.ra.s * (SLOT / 16), db = desc_lo(SB + OFF_B, 8192) + x.rb.s * (SLOT / 16);
#pragma unroll
        for (int hf = 0; hf < 2; hf++) {
          if (hf == 0) wgmma_fence();
#pragma unroll
          for (int k = 0; k < 4; k++) wgmma_ss_n128(hf ? kv1 : kv0, da + hf * 512 + (k >> 1) * 32 + (k & 1) * 2, HA64, db + 128 * k, 1);
          if (hf == 0) { mbar_wait2(sb + BAR_STAT, 1, sb + BAR_CS + 8, 0); wgmma_fence(); }
          wgmma_r1_n128(hf ? kv1 : kv0, dm + 64 * hf, dcs + 96 + 96 * w, 1);
          wgmma_commit();
        }
        if (w == 0) asm volatile("bar.arrive 7, 256;" ::: "memory");
        wgmma_wait<2>();
        if (mask & 1) mbar_arrive_n(sb + (t ? BAR_EMPTYB + x.pb * 8 : BAR_EMPTYA + x.pa * 8), 2);
        gemm_next<128>(x);
        if (w) x.rb.s = 4;
      }
      const uint32_t la = x.pa, lb = x.pb;
      auto finish = [&]() { wgmma_wait<0>(); fence_regs(kv1); if (x.elected) { if (w == 0) mbar_arrive_n(sb + BAR_EMPTYA + la * 8, 2); relB(lb); } };
      const Stats s0 = load_stats(0, x), s1 = load_stats(1, x), st = w ? s1 : s0;
      if (w == 0) skip();
      const uint32_t h0 = x.held(0), h1 = x.held(1);
      auto vreg = [&](int ks) { return (ks & 3) < 3 ? OFF_A + (ks < 4 ? h0 : h1) * SLOT + (ks & 3) * 5120 : OFF_S + 32768 + (ks >> 2) * 5120; };
      uint32_t tV[2], uu[4];
#pragma unroll
      for (int hf = 0; hf < 2; hf++) {
        tV[hf] = sb + vreg(4 * hf + x.warp) + ((x.lane >> 3) & 1) * 2560 + (x.lane & 7) * 16 + x.mhi * 128;
        const float i0 = rcp(hf ? s1.rstd0 : s0.rstd0), i1 = rcp(hf ? s1.rstd1 : s0.rstd1);
        const uint32_t h = pack2(i0, i1);
        uu[2 * hf] = pack2(lo16(h), i0 - lo16(h)); uu[2 * hf + 1] = pack2(hi16(h), i1 - hi16(h));
        asm volatile("" : "+r"(tV[hf]), "+r"(uu[2 * hf]), "+r"(uu[2 * hf + 1])::"memory");
      }
      wgmma_wait<1>();
      fence_regs(kv0);
      TSL_(2);
      if (w == 0) {
        uint32_t f[2][18], ad[4];
#pragma unroll
        for (int q = 0; q < 18; q++) f[1][q] = 0u;
#pragma unroll
        for (int q = 0; q < 4; q++) ad[q] = x.maddr(sb + OFF_S, 2 * q);
        auto norm = [&](int un) {
          uint32_t* u = f[un & 1];
          const Stats& sn = un ? s1 : s0;
#pragma unroll
          for (int sg = 0; sg < 2; sg++) {
            uint32_t v = u[16 + sg];
            v = add2(v, __shfl_xor_sync(0xffffffffu, v, 1)); v = add2(v, __shfl_xor_sync(0xffffffffu, v, 2));
            const float a = rcp(lo16(v)) * sn.rstd0, b = rcp(hi16(v)) * sn.rstd1;
            const uint32_t r0 = pack2(a, a), r1_ = pack2(b, b);
#pragma unroll
            for (int q = 8 * sg; q < 8 * sg + 8; q++) u[q] = mul2(u[q], (q & 1) ? r1_ : r0);
#pragma unroll
            for (int q = 2 * sg; q < 2 * sg + 2; q++) stsm4(ad[q] + un * 8192, u[4 * q], u[4 * q + 1], u[4 * q + 2], u[4 * q + 3]);
          }
        };
        auto move = [&](int dst, int src) {
#pragma unroll
          for (int q = 0; q < 16; q++) asm volatile("mov.b32 %0, %1;" : "=f"(kv[dst + q]) : "f"(src ? kv[src + q] : 0.f));
        };
        hedgehog_scale<1, 0>(kv, s0, nullptr, [] {});
        finish();
        uint32_t step = 0;
#pragma unroll 1
        for (int h = 0;; h++) {
          norm(1);
          dual_exp(kv, f[0], x.goff);
          hedgehog_scale<1, KEEP>(kv + 64, s1, f[1], [] {});
          if (h == 2) asm volatile("bar.sync 9, 256;" ::: "memory");
#pragma unroll
          for (int q = 0; q < 4; q++) ad[q] += step;
          norm(0);
          dual_exp(kv + 64, f[1], x.goff);
#pragma unroll
          for (int q = 0; q < 16; q++) kv[q] = kv[16 + q];
          hedgehog_scale<1, KEEP>(kv, s0, f[0], [] {});
          step = SLOT;
          if (h == 0) { move(64, 80); move(16, 32); }
          else if (h == 1) { move(64, 96); move(16, 48); step = OFF_B + SLOT - OFF_S; }
          else if (h == 2) { move(64, 112); move(16, 0); }
          else break;
        }
        norm(1);
        TSL_(3);
      } else {
#pragma unroll
        for (int hf = 0; hf < 2; hf++) {
          if (hf) finish();
          wg_bar(w);
          stsm4(tV[hf] + 512 + x.mhi * 512, uu[2 * hf], uu[2 * hf + 1], uu[2 * hf], uu[2 * hf + 1]);
          stsm4(tV[hf] + 1792 + x.mhi * 512, uu[2 * hf], uu[2 * hf + 1], uu[2 * hf], uu[2 * hf + 1]);
#pragma unroll
          for (int q = 0; q < 8; q++) {
            const float* u = kv + 64 * hf + 8 * q;
            stsm4(tV[hf] + (q >> 1) * 640 + (q & 1) * 256, pack2(u[0], u[1]), pack2(u[2], u[3]), pack2(u[4], u[5]), pack2(u[6], u[7]));
          }
        }
        TSL_(3);
      }
      {
        float d[2][20];
        uint4* dst = &g_kvpart[x.j()][w * 4 + x.warp][0][x.m() * 32 + x.lane];
        unsigned* dz = reinterpret_cast<unsigned*>(&g_kvpart[x.j()][w * 4 + x.warp][x.c & 1][512]) + x.m() * 8 + x.g;
        fence_async_smem();
        cta_bar();
        TSL_(11);
        uint32_t pk[9];
        auto prep = [&](float (&u)[20]) {
          fence_regs(u);
#pragma unroll
          for (int q = 0; q < 8; q++) pk[q] = pack2(u[((q >> 1) & 2) + 4 * (q & 3)], u[((q >> 1) & 2) + 4 * (q & 3) + 1]);
          pk[8] = __float_as_uint((x.c & 1) ? u[18] + u[19] : u[16] + u[17]);
#pragma unroll
          for (int q = 0; q < 9; q += 4) pk[q] = (pk[q] & ~1u) | (L == 1);
        };
        auto send = [&](int hp) {
          st_v4(dst + hp * 16 * 544, pk[0], pk[1], pk[2], pk[3]); st_v4(dst + (hp * 16 + 1) * 544, pk[4], pk[5], pk[6], pk[7]);
          st_flag(dz + hp * 16 * 544 * 4, pk[8]);
        };
        wgmma_fence();
#pragma unroll
        for (int q = 0; q < 17; q++) {
          if (q < 16) wgmma_ss_n40_tt(d[q >> 3], desc_lo(SB + (q < 8 ? OFF_S : OFF_B + 2 * SLOT), 1024) + w * (SLOT / 16) + 128 * (q & 7), desc_lo(SB + vreg(q & 7), 2560) + (w + (q >> 3) * 2) * 40, q & 7);
          else wgmma_r1_n128(acc, dm + w * 64, dcs, 0);
          if (q == 7 || q == KVS || q == 16) wgmma_commit();
          if (q == KVS) { mbar_wait2(x.fullA(x.ra.s), x.ra.ph, x.fullB(x.rb.s), x.rb.ph); wgmma_wait<1>(); prep(d[0]); send(0); bb_fence(x.goff); wgmma_fence(); }
        }
        gemm_issue<128, false>(acc, x, true); gemm_next<128>(x);
        wgmma_wait<1>();
        x.releaseA(h0); x.releaseA(h1); x.releaseB(2); x.releaseB(3);
        if (x.lane == 0) mbar_arrive(sb + BAR_SIGT);
        prep(d[1]);
        TSL_(4);
#pragma unroll 1
        for (int seg = 0; seg < 2; seg++) {
          const int n0 = w ? PS1 : PS0;
          gemm_run(acc, x, seg ? 15 - n0 : n0, seg, seg ? L : 0);
          if (seg == 0) send(1);
        }
      }
      gemm_end(acc, x);
      TSL_(5);
      {
        float dp[2][20], dn[2][20];
        uint32_t f[4][16];
        auto mma = [&](int h) {
          if (!(h & 1)) mbar_wait(sb + BAR_KV + h * 4, L >> 1);
          if (h == 0) TSL_(9);
          const uint32_t db = desc_lo(SB + OFF_S + h * 5120, 128);
          const uint32_t (&a)[16] = f[h];
          wgmma_fence();
          wgmma_rs_n40(dp[h & 1], a[0], a[1], a[2], a[3], db, 0);
          wgmma_rs_n40(dn[h & 1], a[8], a[9], a[10], a[11], db + 160, 0);
          wgmma_rs_n40(dp[h & 1], a[4], a[5], a[6], a[7], db + 80, 1);
          wgmma_rs_n40(dn[h & 1], a[12], a[13], a[14], a[15], db + 240, 1);
          wgmma_commit();
        };
        uint32_t xr[16];
        auto fin = [&](int h) {
          const uint32_t tile = x.aslot(x.held(h >> 1));
          if (!(h & 1)) img_load(xr, tile, x);
          float (&u)[20] = dp[h & 1];
          float (&v)[20] = dn[h & 1];
          fence_regs(u); fence_regs(v);
#pragma unroll
          for (int r = 0; r < 2; r++) {
            const float sp = u[16 + 2 * r], sn = v[16 + 2 * r];
            const float id = rcp(fmaf(fmaf(sp, L == 1 ? 0.065536f * 128 / 129 : 0.065536f, u[17 + 2 * r]), sn, v[17 + 2 * r] * sp)), aa = sn * id, cc = sp * id;
            uint32_t o[4];
#pragma unroll
            for (int t = 0; t < 4; t++) o[t] = pack2(fmaf(u[4 * t + 2 * r], aa, v[4 * t + 2 * r] * cc), fmaf(u[4 * t + 2 * r + 1], aa, v[4 * t + 2 * r + 1] * cc));
            o[2 * r + (h & 1)] = img_tag(o[2 * r + (h & 1)], false, 1, x);
            stg128(x.img(0, h >> 1) + r * 64 + (h & 1) * 32, make_uint4(o[0], o[1], o[2], o[3]));
            sts128(tile + r * 1024 + (h & 1) * 512 + x.so, o[0], o[1], o[2], o[3]);
          }
          if (h & 1) { if (h == 1) publish(0, x); img_unpack(acc + 16 * (h - 1), xr); }
        };
        auto ex = [&](int h) { dual_exp_rcp(acc + 16 * h, f[h]); };
        Stats sq = st;
#pragma unroll
        for (int h = 0; h < 4; h += 2) {
          hedgehog_scale<2, 0>(acc + 16 * h, sq, nullptr, [&] { ex(h); });
          mma(h);
          ex(h + 1); wgmma_wait<0>(); fin(h);
          if (h == 0) bb_fence(x.goff);
          mma(h + 1);
          wgmma_wait<0>(); fin(h + 1);
          if (h == 0) sq.rstd1 += bb_fence(x.goff);
        }
      }
    }
    mbar_wait(x.fullB(x.rb.s), x.rb.ph);
    fence_regs(acc);
    fence_async_smem();
    wg_bar(w);
    TSL_(6);
    rewind2<NA>(x.ra);
    gemm_issue<128, false>(acc, x, true); gemm_next<128>(x);
    uint4* out = solid(P.out + goff + (x.warp * 16 + (x.lane >> 3)) * 256 + (x.lane & 7));
#pragma unroll 1
    for (int seg = 0; seg < 2; seg++) {
      const int nt = L == 3 ? TSK : XN;
      gemm_run(acc, x, seg ? nt : 15 - nt, seg, 10 + L);
      if (L < 3) { if (seg == 0) publish(1, x); }
      else if (seg != w) {
        if (w) asm volatile("bar.sync 6, 256;" ::: "memory"); else asm volatile("bar.arrive 6, 256;" ::: "memory");
      }
    }
    gemm_end(acc, x);
    TSL_(7);
    rewind2<NA>(x.ra);
    out_epilogue(acc, r1, ts, out, L, x);
    TSL_(13);
  }
}

typedef unsigned long long u64;
template <class T> __device__ __forceinline__ T* early(T* p) { return (T*)__shfl_xor_sync(0xffffffffu, (u64)p, 1); }
__device__ __forceinline__ void pause(uint32_t GAP) {
  if (GAP) { uint32_t t0, t; asm volatile("mov.u32 %0, %%clock;" : "=r"(t0)); do { asm volatile("mov.u32 %0, %%clock;" : "=r"(t)); } while (t - t0 < GAP); }
}
__device__ __forceinline__ u64 order_table0(int j) { return (j & 4) ? 0x543210FEDCBA9876ull : 0xDCBA9876543210FEull; }
__device__ __forceinline__ void order_tables(u64& t1, u64& t2, int j) {
#pragma unroll 1
  for (int i = 6; i >= 0; i--) { const u64 o = 2 * other_tile(i, j); t1 = t1 << 4 | o | (o + 1) << 28; t2 = t2 << 8 | (o * 17 + 16); }
  const u64 own = 2 * j * 17 + 16;
  t1 = t1 << 8 | own; t2 |= own << 56;
}

__device__ __forceinline__ void b_producer(const Params& P, uint32_t sb, unsigned vb) {
  const int j = cta_j(vb);
  u64 t1 = 0, t2 = 0;
  Ring r = {PRE_B % NB, PRE_B < NB};
#pragma unroll 1
  for (int sg = 0; sg < 20; sg++) {
    const int L = sg / 5, p = sg - 5 * L, wt = L & 1;
    if (sg == 1) order_tables(t1, t2, j);
    int n = p >= 3 ? 16 : (wt ? (p ? 16 - NJ : 2 * NJ) : (p ? 0 : (L ? 32 : 32 - PRE_B)));
    u64 tab = p == 3 ? t2 : (sg == 0 ? order_table0(j) >> (2 * PRE_B) : (p == 1 || p == 2 ? t1 >> (4 * NJ) : t1));
    const CUtensorMap* tm = p == 4 ? &P.mwo[wt] : &P.mw[wt ? 1 : L];
    const uint4* img = &g_wf[p != 3][j][0][0];
    int col = (p >= 3 ? 0 : (p == 2 ? 2048 : 1024)) + 128 * j;
    const int flip = p == 0 ? 3072 : 0;
    const bool fold = wt && p != 4;
    if (sg == 5 || sg == 8) { mbar_wait(sb + (sg == 5 ? BAR_WPHI : BAR_CS + 8), sg == 5); fence_async_global(); }
#pragma unroll 1
    for (; n > 0; n--) {
      const int kb = (int)tab & 15;
      mbar_wait(sb + BAR_EMPTYB + r.s * 8, r.ph);
      if (elect()) {
        mbar_expect_tx(sb + BAR_FULLB + r.s * 8, SLOT);
        if (fold && col < 2048) bulk_load(sb + OFF_B + r.s * SLOT, img + kb * 1024, SLOT, sb + BAR_FULLB + r.s * 8);
        else tma_load_w(sb + OFF_B + r.s * SLOT, tm, sb + BAR_FULLB + r.s * 8, col, kb);
      }
      adv<NB>(r);
      if (p == 2 && (n | 4) == 5) r.s = 4;
      col ^= flip;
      if (!(col & flip & 2048)) tab >>= 4;
    }
  }
}

__device__ __forceinline__ void kv_images(uint32_t sb, int L, int j, unsigned tag, unsigned& ph) {
  const int lane = threadIdx.x & 31;
  auto hinted = [&](int h) { return __all_sync(0xffffffffu, (int)(ld_flag(&g_jflag[h][j][lane & 15]) - (tag * 4 + L)) >= 0); };
  auto load = [&](int h) { if (elect()) { mbar_expect_tx(sb + BAR_LAND + 48 + h * 8, 10240); bulk_load(sb + OFF_S + h * 10240, &g_kvfin[j][8 * h][0], 10240, sb + BAR_LAND + 48 + h * 8); } };
  bool sent = false;
#pragma unroll 1
  for (int h = 0, it = 0; h < 2;) {
    if (++it > (1 << 22)) __trap();
    if (h == 0 || !sent) {
      if (!hinted(h)) continue;
      load(h);
    }
    if (KI && h == 0 && !sent && hinted(1)) { load(1); sent = true; }
    mbar_wait(sb + BAR_LAND + 48 + h * 8, (ph >> h) & 1);
    ph ^= 1u << h;
    uint32_t a = 1u, o = 0u;
#pragma unroll
    for (int u = 0; u < 20; u++) { const uint32_t v = __float_as_uint(lds32f(sb + OFF_S + h * 10240 + u * 512 + lane * 16)); a &= v; o |= v; }
    if (h) sent = false;
    if (__all_sync(0xffffffffu, (L == 1 ? a : ~o) & 1u)) {
      if (elect()) mbar_arrive(sb + BAR_KV + h * 8);
      h++;
    } else fence_async_smem();
  }
}

__device__ __forceinline__ void a_loader(const Params& P, uint32_t sb, unsigned vb) {
  const int j = cta_j(vb), m = cta_m(vb);
  u64 t1 = 0, t2 = 0;
  Ring r = {PRE_A % NA, PRE_A < NA};
  {
    u64 tab = order_table0(j) >> (4 * PRE_A);
#pragma unroll 1
    for (int i = PRE_A; i < 33; i++) {
      if (i == 17) { order_tables(t1, t2, j); tab = t2; }
      mbar_wait(sb + BAR_EMPTYA + r.s * 8, r.ph);
      if (elect()) {
        mbar_expect_tx(sb + BAR_FULLA + r.s * 8, SLOT);
        if (i != 14) tma_load_3d(sb + OFF_A + r.s * SLOT, &P.mx, sb + BAR_FULLA + r.s * 8, ((int)tab & 15) * 64, m * 64, 0);
        else {
          tma_load_w(sb + OFF_A + r.s * SLOT, &P.mw[1], sb + BAR_FULLA + r.s * 8, 1024 + 128 * j, m);
          mbar_expect_tx(sb + BAR_WPHI, 8192); tma_load_2d(sb + OFF_S + 4096, &P.mwphi, sb + BAR_WPHI, 0, 128 * j);
        }
        if (i == PF1 || i == PF2) tma_prefetch_w(&P.mwo[i == PF2], 128 * j, m);
      }
      adv<NA>(r);
      if (i != 14) tab >>= 4;
    }
  }
  const unsigned tag = get_tag(sb);
  unsigned kph = 0;
#pragma unroll 1
  for (int sg = 0; sg < 13; sg++) {
    const int L = sg >> 2, p = sg & 3;
    if (p == 0 && (L & 1)) kv_images(sb, L, j, tag, kph);
    int n = p < 2 ? 14 : (p == 2 ? ((L & 1) ? 0 : 16 - NJ) : 16);
    u64 tab = p == 3 ? t2 : t1 >> (p < 2 ? 8 : 4 * NJ);
    const uint4* img = &g_img[p ? XBUF(L + 1) : 0][m][0][0];
#pragma unroll 1
    for (; n > 0; n--) {
      const uint4* src = early(img + ((int)tab & 15) * 1024);
      const uint32_t bar = sb + (p < 2 ? BAR_LAND : BAR_FULLA) + r.s * 8;
      mbar_wait(sb + BAR_EMPTYA + r.s * 8, r.ph);
      if (elect()) mbar_expect_tx(bar, SLOT);
      if (p < 2 && n == 14) {
        const int lane = threadIdx.x & 31;
        const unsigned* f = &g_hint[(m & 14) + ((lane >> 3) & 1)][(~j & 4) ^ (lane & ND0)];
        mbar_wait(sb + BAR_SIGP + p * 8, L & 1);
        int it = 0;
        while (!__all_sync(0xffffffffu, (int)(ld_flag(f) - (tag * 16 + 4 * L + 1 + p)) >= 0)) { if (++it > (1 << 22)) __trap(); }
        pause(p ? (L ? PAX : PX0) : ((L & 1) ? 0 : (L ? PAA : PA0)));
        TS(2, p == 0 ? 5 + L * 8 : 9 + L * 8);
        TSH((2 * L + p) * 8 + 2);
      }
      if (elect()) bulk_load(sb + OFF_A + r.s * SLOT, src, SLOT, bar);
      adv<NA>(r);
      tab >>= 4;
      pause(p < 2 && n > 10 ? G0 : 0);
    }
  }
}

template <int KB, int G>
__device__ __forceinline__ uint2 sum_packets(float (&a)[8], uint32_t addr, int n) {
  uint2 ok = make_uint2(~0u, 0u);
#pragma unroll 1
  for (int b = 0; b < n; b += KB) {
    uint4 v[KB];
#pragma unroll
    for (int u = 0; u < KB; u++) lds128(addr + (b + u) * 512, v[u].x, v[u].y, v[u].z, v[u].w);
#pragma unroll
    for (int u = 0; u < KB; u++) { ok.x &= v[u].x; ok.y |= v[u].x; }
#pragma unroll
    for (int d = 1; d < G; d *= 2)
#pragma unroll
      for (int u = 0; u < KB; u += 2 * d) v[u] = make_uint4(add2(v[u].x, v[u + d].x), add2(v[u].y, v[u + d].y), add2(v[u].z, v[u + d].z), add2(v[u].w, v[u + d].w));
#pragma unroll
    for (int u = 0; u < KB; u += G) {
      a[0] += lo16(v[u].x); a[1] += hi16(v[u].x); a[2] += lo16(v[u].y); a[3] += hi16(v[u].y);
      a[4] += lo16(v[u].z); a[5] += hi16(v[u].z); a[6] += lo16(v[u].w); a[7] += hi16(v[u].w);
    }
  }
  return ok;
}
__device__ __forceinline__ void helper_bar() { asm volatile("bar.sync 4, 64;" ::: "memory"); }
__device__ __forceinline__ void helper(const Params& P, uint32_t sb, int w, unsigned vb) {
  const int j = cta_j(vb), m = cta_m(vb);
  if (w == 0) {
    if (elect()) {
      const unsigned t = atomicAdd(&g_ctr, 1u) / NCTA + 1u;
      asm volatile("st.shared.u32 [%0], %1;" ::"r"(sb + OFF_EPOCH), "r"(t) : "memory");
      mbar_arrive(sb + BAR_EPOCH);
    }
  }
  const unsigned tag = get_tag(sb);
  mbar_wait(sb + BAR_FULLB + 24, 0);
  const uint32_t stg = sb + OFF_T + w * 12288, stb = sb + BAR_STG + w * 24;
  Ring rs = {0, 0};
  uint32_t vs = 33 % NA, vph = 0;
  auto cs_image = [&](int L) {
      const int lane = lane_id();
      poll_flags(&g_jflag[2 * L][j][0], 16, L ? CSNEED : 0xFFFu, tag * 4);
#pragma unroll
      for (int p = 0; p < 3; p++) {
        const uint4 u = ldcg4(&g_cs[L][0][p * 1024 + 128 * j + lane * 4]), v = ldcg4(&g_cs[L][1][p * 1024 + 128 * j + lane * 4]);
        const float c0 = __uint_as_float(u.x) + __uint_as_float(v.x), c1 = __uint_as_float(u.y) + __uint_as_float(v.y);
        const float c2 = __uint_as_float(u.z) + __uint_as_float(v.z), c3 = __uint_as_float(u.w) + __uint_as_float(v.w);
        const uint32_t h0 = pack2(c0, c1), h1 = pack2(c2, c3), dst = sb + OFF_CS + (p * 16 + (lane >> 1)) * 96 + L * 48 + (lane & 1) * 8;
        sts64(dst, h0, h1); sts64(dst + 16, pack2(c0 - lo16(h0), c1 - hi16(h0)), pack2(c2 - lo16(h1), c3 - hi16(h1))); sts64(dst + 32, h0, h1);
        if (L == 0) { sts64(dst + 48, 0u, 0u); sts64(dst + 64, 0u, 0u); sts64(dst + 80, 0u, 0u); }
      }
      if (L == 0 && lane < 4) sts64(sb + OFF_CS + 4608 + lane * 8, 0u, 0u);
      fence_async_smem();
      __syncwarp();
      if (elect()) mbar_arrive(sb + BAR_CS + L * 8);
      TS(4, 2 + L * 2);
  };
#pragma unroll 1
  for (int L = 0; L < 4; L++) {
    const int lane = lane_id();
    if (L == 0) {
      {
        const int wt = m >= 12, col = ((0x2021 >> (m & 12)) & 3) * 1024 + 128 * j + (m & 3) * 32;
        const CUtensorMap* tm = &P.mcs[wt];
        if (wt) __nanosleep(D2);
        constexpr int nb = 8;
        float a[8] = {0.f, 0.f, 0.f, 0.f, 0.f, 0.f, 0.f, 0.f};
#pragma unroll 1
        for (int b = -3; b < nb; b++) {
          if (b >= 0) {
            mbar_wait(stb + rs.s * 8, rs.ph);
            sum_packets<KC, 1>(a, stg + rs.s * 4096 + lane * 16, 8);
            fence_async_smem();
            __syncwarp();
          }
          const uint32_t sl = b < 0 ? (rs.s + b + 3) % 3 : rs.s;
          if (b + 3 < nb && elect()) { mbar_expect_tx(stb + sl * 8, 4096); tma_load_2d(stg + sl * 4096, tm, stb + sl * 8, col, (w * (16 - nb) + b + 3) * 64); }
          if (b >= 0) adv<3>(rs); else pause(CP);
        }
#pragma unroll 1
        for (int d = 4; d < 32; d *= 2)
#pragma unroll
          for (int u = 0; u < 8; u++) a[u] += __shfl_xor_sync(0xffffffffu, a[u], d);
        if (lane < 4) {
          float4* dst = reinterpret_cast<float4*>(&g_cs[wt][w][col + lane * 8]);
          dst[0] = make_float4(a[0], a[1], a[2], a[3]); dst[1] = make_float4(a[4], a[5], a[6], a[7]);
        }
        helper_bar();
        if (w == 0 && elect()) { fence_gpu(); st_flag(&g_jflag[2 * wt][j][m], tag * 4); }
      }
      if (w == 0) TS(4, 1 + L * 2);
    }
    if (L > 0 && w == 0) {
      mbar_wait(sb + BAR_SIGP + 16, (L - 1) & 1);
      fence_async_global();
      __nanosleep(CO && L == 1 ? SE : SD);
    }
    if (CO && L < 2 && w == 0) cs_image(L);
    if (w == (L == 0)) {
      if (L == 0) { mbar_wait(sb + BAR_WPHI, 0); __nanosleep(S0); }
#pragma unroll 1
      for (int p = 0; p < 2; p++) {
        uint4 v[8];
        for (int it = 0;; it++) {
          bool ok = true;
#pragma unroll
          for (int t = 0; t < 8; t++) v[t] = ld_pkt(&g_stats[m][p][t][lane]);
#pragma unroll
          for (int t = 0; t < 8; t++) ok = ok && (v[t].w & 15u) == seq4(tag, L);
          if (__all_sync(0xffffffffu, ok)) break;
          __nanosleep(200);
          if (it > (1 << 20)) __trap();
        }
        float s0 = 0.f, q0 = 0.f, s1 = 0.f, q1 = 0.f;
#pragma unroll
        for (int t = 0; t < 8; t++) { s0 += __uint_as_float(v[t].x); q0 += __uint_as_float(v[t].y); s1 += __uint_as_float(v[t].z); q1 += __uint_as_float(v[t].w & ~15u); }
        s0 *= (1.f / 1024); s1 *= (1.f / 1024);
        sts64(sb + OFF_MR + p * 256 + lane * 8, __float_as_uint(rsqrtf(fmaxf(q0 * (1.f / 1024) - s0 * s0, 0.f) + 1e-5f)),
              __float_as_uint(rsqrtf(fmaxf(q1 * (1.f / 1024) - s1 * s1, 0.f) + 1e-5f)));
#pragma unroll
        for (int r = 0; r < 2; r++) {
          const float v = -0.5f * (r ? s1 : s0);
          const uint32_t hh = pack2(v, v), hl = pack2(v, v - lo16(hh));
          const bool b = L & 1;
          sts128(sb + (b ? OFF_MB : OFF_MA) + p * 1024 + (lane >> 3) * 256 + r * 128 + (lane & 7) * 16, b ? 0u : hh, b ? hh << 16 : hl >> 16, b ? hl : 0u, 0u);
        }
      }
      fence_async_smem();
      __syncwarp();
      if (elect()) {
        mbar_arrive(sb + BAR_STAT);
      }
      TS(2, 0 + L * 8);
    }
    if (!CO && L < 2 && w == 0) cs_image(L);
    if (L & 1) {
      const uint32_t flip = L == 1 ? 0u : 1u;
      mbar_wait(sb + BAR_SIGT, 1);
      {
        int it = 0;
        if (PSL) __nanosleep(m < 8 ? PSL : PSL + 600);
        while (!__all_sync(0xffffffffu, (ld_flag(reinterpret_cast<const unsigned*>(&g_kvpart[j][m][w][512]) + (lane & 15) * 8) ^ flip) & 1u)) { if (PSL) __nanosleep(100); if (++it > (1 << 22)) __trap(); }
        fence_async_global();
      }
      if (w == 0) TS(4, 6 + L * 2);
      float a[8], z;
      for (int it = 0;; it++) {
        if (elect()) { mbar_expect_tx(stb + rs.s * 8, 8704); bulk_load(stg, &g_kvpart[j][m][w][0], 8704, stb + rs.s * 8); }
        mbar_wait(stb + rs.s * 8, rs.ph);
        if (w == 0) TS(4, 21 + L);
        adv<3>(rs);
#pragma unroll
        for (int u = 0; u < 8; u++) a[u] = 0.f;
        z = 0.f;
        uint32_t ok = 1u;
#pragma unroll
        for (int u = 0; u < 4; u++) { const float v = lds32f(stg + 8192 + u * 128 + (lane & 3) * 32 + (lane >> 2) * 4); z += v; ok &= __float_as_uint(v) ^ flip; }
        const uint2 tg = sum_packets<8, RG>(a, stg + lane * 16, 16);
        ok &= flip ? ~tg.y : tg.x;
        if (__all_sync(0xffffffffu, ok & 1u)) break;
        fence_async_smem();
        if (it > (1 << 16)) __trap();
      }
      {
        uint4* img = &g_kvfin[j][m][w * 8 + (lane >> 2)];
        uint32_t a0 = __float_as_uint(a[0]) >> 16;
        a0 += ~(a0 ^ flip) & 1u;
        st_v4(img + (lane & 3) * 16, __byte_perm(a0, pack2(0.f, a[1]), 0x7610), pack2(a[2], a[3]), pack2(a[4], a[5]), pack2(a[6], a[7]));
        const uint32_t cz = pack2(0.f, qsum(z)) | (0x3781u ^ flip);
        if (!(lane & 3)) st_v4(img + 64, cz, cz, cz, cz);
        __syncwarp();
        if (elect()) st_flag(&g_jflag[m >> 3][j][(m & 7) * 2 + w], tag * 4 + L);
      }
      if (w == 0) TS(4, 7 + L * 2);
    } else {
      if (L == 0 && w == 0) {
        st_v4(&g_kvpart[j][m][0][512 + lane], 0u, 0u, 0u, 0u); st_v4(&g_kvpart[j][m][1][512 + lane], 0u, 0u, 0u, 0u);
        __syncwarp();
      }
      mbar_wait(sb + BAR_SIGT, 0);
      if (w == 0) {
        if (elect()) { fence_gpu(); st_flag(&g_hint[m][j], tag * 16 + 4 * L); st_flag(&g_jflag[1][j][m], tag * 4 + L); }
        if (L == 0) {
          __nanosleep(KSL);
          poll_flags(&g_jflag[1][j][0], 16, 0xFFFFu, tag * 4);
          if (elect()) mbar_arrive(sb + BAR_WPHI);
        }
      } else if (m > 0) {
        poll_flags(&g_hint[m - 1][j], 1, 1u, tag * 16 + 4 * L);
        if (elect()) { mbar_expect_tx(sb + BAR_HALO, 8192); bulk_load(sb + OFF_S + 8192, &g_halo[m - 1][j][0][0], 8192, sb + BAR_HALO); }
        TS(2, 2 + L * 8);
      }
    }
    if (w == 0) {
#pragma unroll 1
      for (int e = 0; e < (L < 3 ? 2 : 1); e++) {
        unsigned* flag = early(&g_hint[m][j]);
        mbar_wait(sb + BAR_SIGP + e * 8, L & 1);
        TS(2, (e ? 6 : 3) + L * 8);
        TSH((2 * L + e) * 8);
        if (elect()) st_flag(flag, tag * 16 + 4 * L + 1 + e);
        TSH((2 * L + e) * 8 + 1);
      }
    } else {
#pragma unroll 1
      for (int i = 0; i < (L < 3 ? 28 : 14); i++) {
        const bool isx = i >= 14;
        const uint32_t a = sb + OFF_A + vs * SLOT + lane * 128 + ((lane >> 4) * 4 + (lane & 3)) * 16 + (lane & 12), code = img_code(isx, L + isx);
        for (int it = 0;; it++) {
          mbar_wait(sb + BAR_LAND + vs * 8, (vph >> vs) & 1);
          vph ^= 1u << vs;
          if (i - 14 * isx < 2) TSH((2 * L + isx) * 8 + 3 + 2 * (i - 14 * isx));
          uint32_t bad = 0;
#pragma unroll
          for (int u = 0; u < 4; u++) bad |= __float_as_uint(lds32f(a + u * 4096)) ^ code;
          if (__all_sync(0xffffffffu, !(bad & img_mask(isx)))) break;
          if (it > (1 << 16)) __trap();
          fence_async_smem();
          if (elect()) {
            mbar_expect_tx(sb + BAR_LAND + vs * 8, SLOT);
            bulk_load(sb + OFF_A + vs * SLOT, &g_img[isx ? XBUF(L + 1) : 0][m][o_order(i - 14 * isx + 2, j)][0], SLOT, sb + BAR_LAND + vs * 8);
          }
        }
        if (elect()) mbar_arrive(sb + BAR_FULLA + vs * 8);
        if (i - 14 * isx < 2) TSH((2 * L + isx) * 8 + 4 + 2 * (i - 14 * isx));
        if (++vs == NA) vs = 0;
      }
      vs = (vs + ((L & 1) ? 16 : 32 - NJ)) % NA;
    }
  }
}

__device__ __forceinline__ void spare(const Params& P, uint32_t sb, int id) {
  const int tid = threadIdx.x & 127, warp = __shfl_sync(0xffffffffu, threadIdx.x >> 5, 0), w = warp >> 2, lane = tid & 31, j = 2 * id + w;
  const uint32_t ring = w * 6 * SLOT, wp = 12 * SLOT + w * 8192, bar = sb + 13 * SLOT + w * 64;
  auto part = [&](int t) { return (t >> 4) ^ w; };
  auto load = [&](int t, uint32_t sl) {
    mbar_expect_tx(bar + sl * 8, t == 0 ? SLOT + 8192 : SLOT);
    tma_load_w(sb + ring + sl * SLOT, &P.mw[1], bar + sl * 8, part(t) * 1024 + 128 * j, t & 15);
  };
  if (!(warp & 3) && elect()) {
    if (w == 2) sts32(sb + OFF_EPOCH, atomicAdd(&g_ctr, 1u) / NCTA + 1u);
    else {
      __nanosleep(D3);
#pragma unroll 1
      for (int t = 0; t < 5; t++) {
        mbar_init(bar + t * 8, 1);
        asm volatile("fence.mbarrier_init.release.cluster;" ::: "memory");
        load(t, t);
      }
      tma_load_2d(sb + wp, &P.mwphi, bar, 0, 128 * j);
    }
  }
  __syncthreads();
  const unsigned tag = get_tag<false>(sb);
  if (w == 2) {
    int it = 0;
    while ((int)(ld_flag(&g_ctr) - tag * NCTA) < 0) { if (++it > (1 << 22)) __trap(); }
    return;
  }
  Ring r = {4, 1};
  float d[64];
  auto fold = [&]() {
    mbar_wait(bar + r.s * 8, r.ph);
    wgmma_fence();
#pragma unroll
    for (int q = 0; q < 8; q++)
      wgmma_ss_n32(reinterpret_cast<float (&)[16]>(d[16 * (q >> 1)]), desc_lo(SB + ring + r.s * SLOT, 16) + (q >> 2) * 512 + (q & 3) * 2, desc_lo(SB + wp, 512) + q * 64, q & 1);
    wgmma_commit();
  };
#pragma unroll
  for (int i = 0; i < 64; i++) d[i] = 0.f;
  int t = -1;
#pragma unroll 1
  for (int g = 0; g < 2; g++) {
    float cs[32] = {};
#pragma unroll 1
    do {
      uint32_t f[32];
#pragma unroll
      for (int i = 0; i < 32; i++) { f[i] = pack2(d[2 * i], d[2 * i + 1]); cs[i & 30] += d[2 * i]; cs[i | 1] += d[2 * i + 1]; }
      wg_bar(w);
      const uint32_t sl = r.s;
      if (t < 31) adv<5>(r);
      fold();
      if (!(warp & 3) && t >= 0 && t < 27 && elect()) load(t + 5, sl);
      if (g == w && t >= 0) {
        uint4* dst = &g_wf[0][j][t & 15][((tid >> 5) * 16 + (lane >> 2)) * 8];
#pragma unroll
        for (int q = 0; q < 8; q++)
          dst[(q >> 2) * 512 + (q & 1) * 64 + (((q & 2) * 2 + (lane & 3)) ^ (lane >> 2))] =
              make_uint4(f[4 * (q & 6) + (q & 1)], f[4 * (q & 6) + (q & 1) + 2], f[4 * (q & 6) + (q & 1) + 4], f[4 * (q & 6) + (q & 1) + 6]);
      }
      wgmma_wait<0>();
      fence_regs(d);
    } while (++t != 16 * g + 16);
    const uint32_t red = sb + ring + 5 * SLOT;
#pragma unroll
    for (int i = 0; i < 8; i++) sts128(red + (tid >> 2) * 512 + (i >> 1) * 128 + (lane & 3) * 32 + (i & 1) * 16, __float_as_uint(cs[4 * i]), __float_as_uint(cs[4 * i + 1]), __float_as_uint(cs[4 * i + 2]), __float_as_uint(cs[4 * i + 3]));
    wg_bar(w);
    float a = 0.f;
#pragma unroll 4
    for (int i = 0; i < 32; i++) a += lds32f(red + i * 512 + tid * 4);
    g_cs[1][0][(g ^ w) * 1024 + j * 128 + tid] = a;
  }
  wg_bar(w);
  if (tid == 0) { fence_gpu(); st_flag(&g_jflag[2][j][0], tag * 4); }
}

__global__ void __launch_bounds__(NTHREADS, 1) fused_kernel(const __grid_constant__ Params P) {
  extern __shared__ __align__(1024) uint8_t smem_raw[];
  constexpr uint32_t sb = SB;
  const int tid = threadIdx.x;
  const unsigned vb = vblock();
  if (vb >= 128) { spare(P, sb, vb - 128); return; }
  const int warp = __shfl_sync(0xffffffffu, tid >> 5, 0);
  if (elect()) {
    if (warp == 11) { prefetch_map(&P.mx); prefetch_map(&P.mw[0]); if (smem_u32(smem_raw) != SB) __trap(); }
    if (warp < 8) {
#pragma unroll
      for (int i = 0; i < 8; i++) mbar_init(sb + OFF_BAR + (warp * 8 + i) * 8, warp == 2 || warp == 3 ? 2 : (warp == 4 ? 8 : 1));
    }
    asm volatile("fence.mbarrier_init.release.cluster;" ::: "memory");
    if (warp < 2) {
      const int j = cta_j(vb);
#pragma unroll 1
      for (int i = 0; i < (warp == 0 ? PRE_B : PRE_A); i++) {
        const uint32_t bar = sb + BAR_FULLB + warp * 64 + i * 8;
        mbar_expect_tx(bar, SLOT);
        if (warp == 0) tma_load_w(sb + OFF_B + i * SLOT, &P.mw[0], bar, 1024 + (i & 1) * 1024 + 128 * j, kv_order(i >> 1, j, 0));
        else tma_load_3d(sb + OFF_A + i * SLOT, &P.mx, bar, kv_order(i, j, 0) * 64, cta_m(vb) * 64, 0);
      }
    }
  }
  if (tid == 0) TS(6, 0);
  __syncthreads();
  if (tid == 0) TS(6, 2);
  if (warp < 4) {
    reg_dealloc<PREGS>();
    if (warp & 2) helper(P, sb, warp & 1, vb);
    else if (warp & 1) a_loader(P, sb, vb);
    else b_producer(P, sb, vb);
  } else {
    reg_alloc<CREGS>();
    consumer(P, sb, (warp >> 2) - 1, vb);
  }
}

typedef CUresult (*EncodeFn)(CUtensorMap*, CUtensorMapDataType, cuuint32_t, void*, const cuuint64_t*, const cuuint64_t*,
                             const cuuint32_t*, const cuuint32_t*, CUtensorMapInterleave, CUtensorMapSwizzle,
                             CUtensorMapL2promotion, CUtensorMapFloatOOBfill);

void encode(EncodeFn fn, CUtensorMap* m, const void* ptr, int rank, const cuuint64_t* dims, const cuuint64_t* strides,
            const cuuint32_t* box, CUtensorMapSwizzle swz) {
  const cuuint32_t es[5] = {1, 1, 1, 1, 1};
  fn(m, CU_TENSOR_MAP_DATA_TYPE_BFLOAT16, rank, const_cast<void*>(ptr), dims, strides, box, es, CU_TENSOR_MAP_INTERLEAVE_NONE,
     swz, CU_TENSOR_MAP_L2_PROMOTION_L2_256B, CU_TENSOR_MAP_FLOAT_OOB_FILL_NONE);
}
void encode_w(EncodeFn fn, CUtensorMap* m, const void* ptr, int ncols, bool perm) {
  const cuuint64_t p = (cuuint64_t)ncols * 2, d[5] = {(cuuint64_t)ncols, 2, 4, 4, 32}, s[4] = {p, (perm ? 8 : 2) * p, (perm ? 2 : 8) * p, 32 * p};
  const cuuint32_t box[5] = {64, 2, 4, 4, 2};
  encode(fn, m, ptr, 5, d, s, box, CU_TENSOR_MAP_SWIZZLE_128B);
}

void encode_cs(EncodeFn fn, CUtensorMap* m, const void* ptr, int ncols) {
  const cuuint64_t d[2] = {(cuuint64_t)ncols, 1024}, s[1] = {(cuuint64_t)ncols * 2};
  const cuuint32_t box[2] = {32, 64};
  encode(fn, m, ptr, 2, d, s, box, CU_TENSOR_MAP_SWIZZLE_NONE);
}

}

extern "C" void kernel_launch(void* const* d_in, const int* in_sizes, int n_in, void* d_out, int out_size) {
  (void)in_sizes; (void)n_in; (void)out_size;
  void* fnp = nullptr;
  cudaDriverEntryPointQueryResult q;
  cudaGetDriverEntryPoint("cuTensorMapEncodeTiled", &fnp, cudaEnableDefault, &q);
  EncodeFn fn = (EncodeFn)fnp;
  Params P;
  {
    const cuuint64_t dims[3] = {1024, 1024, 2}, strides[2] = {4096, 2048};
    const cuuint32_t box[3] = {64, 64, 2};
    encode(fn, &P.mx, d_in[0], 3, dims, strides, box, CU_TENSOR_MAP_SWIZZLE_128B);
  }
  P.out = (uint4*)d_out;
  encode_w(fn, &P.mw[0], d_in[1], 3072, false);
  encode_w(fn, &P.mw[1], d_in[4], 3072, true);
  encode_w(fn, &P.mw[2], d_in[1], 3072, true);
  encode_w(fn, &P.mwo[0], d_in[2], 1024, true);
  encode_w(fn, &P.mwo[1], d_in[6], 1024, false);
  encode_cs(fn, &P.mcs[0], d_in[1], 3072);
  encode_cs(fn, &P.mcs[1], d_in[4], 3072);
  {
    const cuuint64_t dims[2] = {32, 1024}, strides[1] = {64};
    const cuuint32_t box[2] = {32, 128};
    encode(fn, &P.mwphi, d_in[5], 2, dims, strides, box, CU_TENSOR_MAP_SWIZZLE_64B);
  }
  cudaFuncSetAttribute(fused_kernel, cudaFuncAttributeMaxDynamicSharedMemorySize, SMEM_BYTES);
  fused_kernel<<<NCTA, NTHREADS, SMEM_BYTES, cudaStreamPerThread>>>(P);
}
```

```cpp
#include <cuda_runtime.h>
#include <cuda_bf16.h>
#include <cuda.h>
#include <stdint.h>

namespace {

__device__ __forceinline__ void wgmma_ss_n256(float (&d)[128], uint32_t da, uint32_t ha, uint32_t db, int sd) {
  asm volatile("{\n.reg .pred p;\n.reg .b64 a, b;\nsetp.ne.b32 p, %130, 0;\nmov.b64 a, {%128, %131};\nmov.b64 b, {%129, 0x40000040};\n"
    "wgmma.mma_async.sync.aligned.m64n256k16.f32.bf16.bf16 {%0,%1,%2,%3,%4,%5,%6,%7,%8,%9,%10,%11,%12,%13,%14,%15,%16,%17,%18,%19,%20,%21,%22,%23,%24,%25,%26,%27,%28,%29,%30,%31,%32,%33,%34,%35,%36,%37,%38,%39,%40,%41,%42,%43,%44,%45,%46,%47,%48,%49,%50,%51,%52,%53,%54,%55,%56,%57,%58,%59,%60,%61,%62,%63,%64,%65,%66,%67,%68,%69,%70,%71,%72,%73,%74,%75,%76,%77,%78,%79,%80,%81,%82,%83,%84,%85,%86,%87,%88,%89,%90,%91,%92,%93,%94,%95,%96,%97,%98,%99,%100,%101,%102,%103,%104,%105,%106,%107,%108,%109,%110,%111,%112,%113,%114,%115,%116,%117,%118,%119,%120,%121,%122,%123,%124,%125,%126,%127}, a, b, p, 1, 1, 0, 1;\n}\n"
    : "+f"(d[0]),"+f"(d[1]),"+f"(d[2]),"+f"(d[3]),"+f"(d[4]),"+f"(d[5]),"+f"(d[6]),"+f"(d[7]),"+f"(d[8]),"+f"(d[9]),"+f"(d[10]),"+f"(d[11]),"+f"(d[12]),"+f"(d[13]),"+f"(d[14]),"+f"(d[15]),"+f"(d[16]),"+f"(d[17]),"+f"(d[18]),"+f"(d[19]),"+f"(d[20]),"+f"(d[21]),"+f"(d[22]),"+f"(d[23]),"+f"(d[24]),"+f"(d[25]),"+f"(d[26]),"+f"(d[27]),"+f"(d[28]),"+f"(d[29]),"+f"(d[30]),"+f"(d[31]),"+f"(d[32]),"+f"(d[33]),"+f"(d[34]),"+f"(d[35]),"+f"(d[36]),"+f"(d[37]),"+f"(d[38]),"+f"(d[39]),"+f"(d[40]),"+f"(d[41]),"+f"(d[42]),"+f"(d[43]),"+f"(d[44]),"+f"(d[45]),"+f"(d[46]),"+f"(d[47]),"+f"(d[48]),"+f"(d[49]),"+f"(d[50]),"+f"(d[51]),"+f"(d[52]),"+f"(d[53]),"+f"(d[54]),"+f"(d[55]),"+f"(d[56]),"+f"(d[57]),"+f"(d[58]),"+f"(d[59]),"+f"(d[60]),"+f"(d[61]),"+f"(d[62]),"+f"(d[63]),"+f"(d[64]),"+f"(d[65]),"+f"(d[66]),"+f"(d[67]),"+f"(d[68]),"+f"(d[69]),"+f"(d[70]),"+f"(d[71]),"+f"(d[72]),"+f"(d[73]),"+f"(d[74]),"+f"(d[75]),"+f"(d[76]),"+f"(d[77]),"+f"(d[78]),"+f"(d[79]),"+f"(d[80]),"+f"(d[81]),"+f"(d[82]),"+f"(d[83]),"+f"(d[84]),"+f"(d[85]),"+f"(d[86]),"+f"(d[87]),"+f"(d[88]),"+f"(d[89]),"+f"(d[90]),"+f"(d[91]),"+f"(d[92]),"+f"(d[93]),"+f"(d[94]),"+f"(d[95]),"+f"(d[96]),"+f"(d[97]),"+f"(d[98]),"+f"(d[99]),"+f"(d[100]),"+f"(d[101]),"+f"(d[102]),"+f"(d[103]),"+f"(d[104]),"+f"(d[105]),"+f"(d[106]),"+f"(d[107]),"+f"(d[108]),"+f"(d[109]),"+f"(d[110]),"+f"(d[111]),"+f"(d[112]),"+f"(d[113]),"+f"(d[114]),"+f"(d[115]),"+f"(d[116]),"+f"(d[117]),"+f"(d[118]),"+f"(d[119]),"+f"(d[120]),"+f"(d[121]),"+f"(d[122]),"+f"(d[123]),"+f"(d[124]),"+f"(d[125]),"+f"(d[126]),"+f"(d[127])
    : "r"(da), "r"(db), "r"(sd), "r"(ha));
}
__device__ __forceinline__ void wgmma_ss_n128(float (&d)[64], uint32_t da, uint32_t ha, uint32_t db, int sd) {
  asm volatile("{\n.reg .pred p;\n.reg .b64 a, b;\nsetp.ne.b32 p, %66, 0;\nmov.b64 a, {%64, %67};\nmov.b64 b, {%65, 0x40000040};\n"
    "wgmma.mma_async.sync.aligned.m64n128k16.f32.bf16.bf16 {%0,%1,%2,%3,%4,%5,%6,%7,%8,%9,%10,%11,%12,%13,%14,%15,%16,%17,%18,%19,%20,%21,%22,%23,%24,%25,%26,%27,%28,%29,%30,%31,%32,%33,%34,%35,%36,%37,%38,%39,%40,%41,%42,%43,%44,%45,%46,%47,%48,%49,%50,%51,%52,%53,%54,%55,%56,%57,%58,%59,%60,%61,%62,%63}, a, b, p, 1, 1, 0, 1;\n}\n"
    : "+f"(d[0]),"+f"(d[1]),"+f"(d[2]),"+f"(d[3]),"+f"(d[4]),"+f"(d[5]),"+f"(d[6]),"+f"(d[7]),"+f"(d[8]),"+f"(d[9]),"+f"(d[10]),"+f"(d[11]),"+f"(d[12]),"+f"(d[13]),"+f"(d[14]),"+f"(d[15]),"+f"(d[16]),"+f"(d[17]),"+f"(d[18]),"+f"(d[19]),"+f"(d[20]),"+f"(d[21]),"+f"(d[22]),"+f"(d[23]),"+f"(d[24]),"+f"(d[25]),"+f"(d[26]),"+f"(d[27]),"+f"(d[28]),"+f"(d[29]),"+f"(d[30]),"+f"(d[31]),"+f"(d[32]),"+f"(d[33]),"+f"(d[34]),"+f"(d[35]),"+f"(d[36]),"+f"(d[37]),"+f"(d[38]),"+f"(d[39]),"+f"(d[40]),"+f"(d[41]),"+f"(d[42]),"+f"(d[43]),"+f"(d[44]),"+f"(d[45]),"+f"(d[46]),"+f"(d[47]),"+f"(d[48]),"+f"(d[49]),"+f"(d[50]),"+f"(d[51]),"+f"(d[52]),"+f"(d[53]),"+f"(d[54]),"+f"(d[55]),"+f"(d[56]),"+f"(d[57]),"+f"(d[58]),"+f"(d[59]),"+f"(d[60]),"+f"(d[61]),"+f"(d[62]),"+f"(d[63])
    : "r"(da), "r"(db), "r"(sd), "r"(ha));
}
__device__ __forceinline__ void wgmma_ss_n40_tt(float (&d)[20], uint32_t da, uint32_t db, int sd) {
  asm volatile("{\n.reg .pred p;\n.reg .b64 a, b;\nsetp.ne.b32 p, %22, 0;\nmov.b64 a, {%20, 0x40000040};\nmov.b64 b, {%21, 0x8};\n"
    "wgmma.mma_async.sync.aligned.m64n40k16.f32.bf16.bf16 {%0,%1,%2,%3,%4,%5,%6,%7,%8,%9,%10,%11,%12,%13,%14,%15,%16,%17,%18,%19}, a, b, p, 1, 1, 1, 1;\n}\n"
    : "+f"(d[0]),"+f"(d[1]),"+f"(d[2]),"+f"(d[3]),"+f"(d[4]),"+f"(d[5]),"+f"(d[6]),"+f"(d[7]),"+f"(d[8]),"+f"(d[9]),"+f"(d[10]),"+f"(d[11]),"+f"(d[12]),"+f"(d[13]),"+f"(d[14]),"+f"(d[15]),"+f"(d[16]),"+f"(d[17]),"+f"(d[18]),"+f"(d[19])
    : "r"(da), "r"(db), "r"(sd));
}
__device__ __forceinline__ void wgmma_ss_n32(float (&d)[16], uint32_t da, uint32_t db, int sd) {
  asm volatile("{\n.reg .pred p;\n.reg .b64 a, b;\nsetp.ne.b32 p, %18, 0;\nmov.b64 a, {%16, 0x40000040};\nmov.b64 b, {%17, 0x80000020};\n"
    "wgmma.mma_async.sync.aligned.m64n32k16.f32.bf16.bf16 {%0,%1,%2,%3,%4,%5,%6,%7,%8,%9,%10,%11,%12,%13,%14,%15}, a, b, p, 1, 1, 0, 1;\n}\n"
    : "+f"(d[0]),"+f"(d[1]),"+f"(d[2]),"+f"(d[3]),"+f"(d[4]),"+f"(d[5]),"+f"(d[6]),"+f"(d[7]),"+f"(d[8]),"+f"(d[9]),"+f"(d[10]),"+f"(d[11]),"+f"(d[12]),"+f"(d[13]),"+f"(d[14]),"+f"(d[15])
    : "r"(da), "r"(db), "r"(sd));
}
__device__ __forceinline__ void wgmma_rs_n40(float (&d)[20], uint32_t a0, uint32_t a1, uint32_t a2, uint32_t a3, uint32_t db, int sd) {
  asm volatile("{\n.reg .pred p;\n.reg .b64 b;\nsetp.ne.b32 p, %25, 0;\nmov.b64 b, {%24, 0x10};\n"
    "wgmma.mma_async.sync.aligned.m64n40k16.f32.bf16.bf16 {%0,%1,%2,%3,%4,%5,%6,%7,%8,%9,%10,%11,%12,%13,%14,%15,%16,%17,%18,%19}, {%20,%21,%22,%23}, b, p, 1, 1, 1;\n}\n"
    : "+f"(d[0]),"+f"(d[1]),"+f"(d[2]),"+f"(d[3]),"+f"(d[4]),"+f"(d[5]),"+f"(d[6]),"+f"(d[7]),"+f"(d[8]),"+f"(d[9]),"+f"(d[10]),"+f"(d[11]),"+f"(d[12]),"+f"(d[13]),"+f"(d[14]),"+f"(d[15]),"+f"(d[16]),"+f"(d[17]),"+f"(d[18]),"+f"(d[19])
    : "r"(a0), "r"(a1), "r"(a2), "r"(a3), "r"(db), "r"(sd));
}
__device__ __forceinline__ void wgmma_r1_n256(float (&d)[128], uint32_t da, uint32_t db, int sd) {
  asm volatile("{\n.reg .pred p;\n.reg .b64 a, b;\nsetp.ne.b32 p, %130, 0;\nmov.b64 a, {%128, 0x8};\nmov.b64 b, {%129, 0x6};\n"
    "wgmma.mma_async.sync.aligned.m64n256k16.f32.bf16.bf16 {%0,%1,%2,%3,%4,%5,%6,%7,%8,%9,%10,%11,%12,%13,%14,%15,%16,%17,%18,%19,%20,%21,%22,%23,%24,%25,%26,%27,%28,%29,%30,%31,%32,%33,%34,%35,%36,%37,%38,%39,%40,%41,%42,%43,%44,%45,%46,%47,%48,%49,%50,%51,%52,%53,%54,%55,%56,%57,%58,%59,%60,%61,%62,%63,%64,%65,%66,%67,%68,%69,%70,%71,%72,%73,%74,%75,%76,%77,%78,%79,%80,%81,%82,%83,%84,%85,%86,%87,%88,%89,%90,%91,%92,%93,%94,%95,%96,%97,%98,%99,%100,%101,%102,%103,%104,%105,%106,%107,%108,%109,%110,%111,%112,%113,%114,%115,%116,%117,%118,%119,%120,%121,%122,%123,%124,%125,%126,%127}, a, b, p, 1, 1, 0, 1;\n}\n"
    : "+f"(d[0]),"+f"(d[1]),"+f"(d[2]),"+f"(d[3]),"+f"(d[4]),"+f"(d[5]),"+f"(d[6]),"+f"(d[7]),"+f"(d[8]),"+f"(d[9]),"+f"(d[10]),"+f"(d[11]),"+f"(d[12]),"+f"(d[13]),"+f"(d[14]),"+f"(d[15]),"+f"(d[16]),"+f"(d[17]),"+f"(d[18]),"+f"(d[19]),"+f"(d[20]),"+f"(d[21]),"+f"(d[22]),"+f"(d[23]),"+f"(d[24]),"+f"(d[25]),"+f"(d[26]),"+f"(d[27]),"+f"(d[28]),"+f"(d[29]),"+f"(d[30]),"+f"(d[31]),"+f"(d[32]),"+f"(d[33]),"+f"(d[34]),"+f"(d[35]),"+f"(d[36]),"+f"(d[37]),"+f"(d[38]),"+f"(d[39]),"+f"(d[40]),"+f"(d[41]),"+f"(d[42]),"+f"(d[43]),"+f"(d[44]),"+f"(d[45]),"+f"(d[46]),"+f"(d[47]),"+f"(d[48]),"+f"(d[49]),"+f"(d[50]),"+f"(d[51]),"+f"(d[52]),"+f"(d[53]),"+f"(d[54]),"+f"(d[55]),"+f"(d[56]),"+f"(d[57]),"+f"(d[58]),"+f"(d[59]),"+f"(d[60]),"+f"(d[61]),"+f"(d[62]),"+f"(d[63]),"+f"(d[64]),"+f"(d[65]),"+f"(d[66]),"+f"(d[67]),"+f"(d[68]),"+f"(d[69]),"+f"(d[70]),"+f"(d[71]),"+f"(d[72]),"+f"(d[73]),"+f"(d[74]),"+f"(d[75]),"+f"(d[76]),"+f"(d[77]),"+f"(d[78]),"+f"(d[79]),"+f"(d[80]),"+f"(d[81]),"+f"(d[82]),"+f"(d[83]),"+f"(d[84]),"+f"(d[85]),"+f"(d[86]),"+f"(d[87]),"+f"(d[88]),"+f"(d[89]),"+f"(d[90]),"+f"(d[91]),"+f"(d[92]),"+f"(d[93]),"+f"(d[94]),"+f"(d[95]),"+f"(d[96]),"+f"(d[97]),"+f"(d[98]),"+f"(d[99]),"+f"(d[100]),"+f"(d[101]),"+f"(d[102]),"+f"(d[103]),"+f"(d[104]),"+f"(d[105]),"+f"(d[106]),"+f"(d[107]),"+f"(d[108]),"+f"(d[109]),"+f"(d[110]),"+f"(d[111]),"+f"(d[112]),"+f"(d[113]),"+f"(d[114]),"+f"(d[115]),"+f"(d[116]),"+f"(d[117]),"+f"(d[118]),"+f"(d[119]),"+f"(d[120]),"+f"(d[121]),"+f"(d[122]),"+f"(d[123]),"+f"(d[124]),"+f"(d[125]),"+f"(d[126]),"+f"(d[127])
    : "r"(da), "r"(db), "r"(sd));
}
__device__ __forceinline__ void wgmma_r1_n128(float (&d)[64], uint32_t da, uint32_t db, int sd) {
  asm volatile("{\n.reg .pred p;\n.reg .b64 a, b;\nsetp.ne.b32 p, %66, 0;\nmov.b64 a, {%64, 0x8};\nmov.b64 b, {%65, 0x6};\n"
    "wgmma.mma_async.sync.aligned.m64n128k16.f32.bf16.bf16 {%0,%1,%2,%3,%4,%5,%6,%7,%8,%9,%10,%11,%12,%13,%14,%15,%16,%17,%18,%19,%20,%21,%22,%23,%24,%25,%26,%27,%28,%29,%30,%31,%32,%33,%34,%35,%36,%37,%38,%39,%40,%41,%42,%43,%44,%45,%46,%47,%48,%49,%50,%51,%52,%53,%54,%55,%56,%57,%58,%59,%60,%61,%62,%63}, a, b, p, 1, 1, 0, 1;\n}\n"
    : "+f"(d[0]),"+f"(d[1]),"+f"(d[2]),"+f"(d[3]),"+f"(d[4]),"+f"(d[5]),"+f"(d[6]),"+f"(d[7]),"+f"(d[8]),"+f"(d[9]),"+f"(d[10]),"+f"(d[11]),"+f"(d[12]),"+f"(d[13]),"+f"(d[14]),"+f"(d[15]),"+f"(d[16]),"+f"(d[17]),"+f"(d[18]),"+f"(d[19]),"+f"(d[20]),"+f"(d[21]),"+f"(d[22]),"+f"(d[23]),"+f"(d[24]),"+f"(d[25]),"+f"(d[26]),"+f"(d[27]),"+f"(d[28]),"+f"(d[29]),"+f"(d[30]),"+f"(d[31]),"+f"(d[32]),"+f"(d[33]),"+f"(d[34]),"+f"(d[35]),"+f"(d[36]),"+f"(d[37]),"+f"(d[38]),"+f"(d[39]),"+f"(d[40]),"+f"(d[41]),"+f"(d[42]),"+f"(d[43]),"+f"(d[44]),"+f"(d[45]),"+f"(d[46]),"+f"(d[47]),"+f"(d[48]),"+f"(d[49]),"+f"(d[50]),"+f"(d[51]),"+f"(d[52]),"+f"(d[53]),"+f"(d[54]),"+f"(d[55]),"+f"(d[56]),"+f"(d[57]),"+f"(d[58]),"+f"(d[59]),"+f"(d[60]),"+f"(d[61]),"+f"(d[62]),"+f"(d[63])
    : "r"(da), "r"(db), "r"(sd));
}

__device__ __forceinline__ uint32_t smem_u32(const void* p) { return (uint32_t)__cvta_generic_to_shared(p); }
__device__ __forceinline__ void mbar_init(uint32_t bar, uint32_t cnt) { asm volatile("mbarrier.init.shared::cta.b64 [%0], %1;" ::"r"(bar), "r"(cnt)); }
__device__ __forceinline__ void mbar_expect_tx(uint32_t bar, uint32_t bytes) { asm volatile("mbarrier.arrive.expect_tx.shared::cta.b64 _, [%0], %1;" ::"r"(bar), "r"(bytes) : "memory"); }
__device__ __forceinline__ void mbar_arrive(uint32_t bar) { asm volatile("mbarrier.arrive.shared::cta.b64 _, [%0];" ::"r"(bar) : "memory"); }
__device__ __forceinline__ void mbar_arrive_n(uint32_t bar, uint32_t n) { asm volatile("mbarrier.arrive.shared::cta.b64 _, [%0], %1;" ::"r"(bar), "r"(n) : "memory"); }
__device__ __forceinline__ void mbar_wait(uint32_t bar, uint32_t parity) {
  asm volatile("{\n.reg .pred p;\nLAB_WAIT:\nmbarrier.try_wait.parity.shared::cta.b64 p, [%0], %1;\n@p bra DONE;\nbra LAB_WAIT;\nDONE:\n}" ::"r"(bar), "r"(parity) : "memory");
}
__device__ __forceinline__ void mbar_wait2(uint32_t a, uint32_t pa, uint32_t b, uint32_t pb) {
  asm volatile("{\n.reg .pred p, q;\nLAB_WAIT:\nmbarrier.try_wait.parity.shared::cta.b64 p, [%0], %1;\nmbarrier.try_wait.parity.shared::cta.b64 q, [%2], %3;\n"
               "and.pred p, p, q;\n@p bra DONE;\nbra LAB_WAIT;\nDONE:\n}" ::"r"(a), "r"(pa), "r"(b), "r"(pb) : "memory");
}
__device__ __forceinline__ void mbar_wait3(uint32_t a, uint32_t pa, uint32_t b, uint32_t pb) {
  asm volatile("{\n.reg .pred p, q, r;\nLAB_WAIT:\nmbarrier.try_wait.parity.shared::cta.b64 p, [%0], %1;\nmbarrier.try_wait.parity.shared::cta.b64 q, [%2], %3;\n"
               "mbarrier.try_wait.parity.shared::cta.b64 r, [%2+8], %3;\nand.pred p, p, q;\nand.pred p, p, r;\n@p bra DONE;\nbra LAB_WAIT;\nDONE:\n}" ::"r"(a), "r"(pa), "r"(b), "r"(pb) : "memory");
}
__device__ __forceinline__ bool mbar_probe2(uint32_t a, uint32_t pa, uint32_t b, uint32_t pb) {
  uint32_t ok;
  asm volatile("{\n.reg .pred p, q;\nmbarrier.test_wait.parity.shared::cta.b64 p, [%1], %2;\nmbarrier.test_wait.parity.shared::cta.b64 q, [%3], %4;\n"
               "and.pred p, p, q;\nselp.u32 %0, 1, 0, p;\n}" : "=r"(ok) : "r"(a), "r"(pa), "r"(b), "r"(pb) : "memory");
  return ok != 0;
}
__device__ __forceinline__ void tma_load_3d(uint32_t dst, const CUtensorMap* tm, uint32_t bar, int c0, int c1, int c2) {
  asm volatile("cp.async.bulk.tensor.3d.shared::cluster.global.mbarrier::complete_tx::bytes [%0], [%1, {%3, %4, %5}], [%2];"
               ::"r"(dst), "l"(tm), "r"(bar), "r"(c0), "r"(c1), "r"(c2) : "memory");
}
__device__ __forceinline__ void tma_load_2d(uint32_t dst, const CUtensorMap* tm, uint32_t bar, int c0, int c1) {
  asm volatile("cp.async.bulk.tensor.2d.shared::cluster.global.mbarrier::complete_tx::bytes [%0], [%1, {%3, %4}], [%2];"
               ::"r"(dst), "l"(tm), "r"(bar), "r"(c0), "r"(c1) : "memory");
}
__device__ __forceinline__ void tma_load_w(uint32_t dst, const CUtensorMap* tm, uint32_t bar, int col, int kb) {
#pragma unroll
  for (int q = 0; q < 2; q++)
    asm volatile("cp.async.bulk.tensor.5d.shared::cluster.global.mbarrier::complete_tx::bytes [%0], [%1, {%3, %4, %4, %4, %5}], [%2];"
                 ::"r"(dst + q * 8192), "l"(tm), "r"(bar), "r"(col + q * 64), "r"(0), "r"(2 * kb) : "memory");
}
__device__ __forceinline__ void tma_prefetch_w(const CUtensorMap* tm, int col, int kb) {
#pragma unroll
  for (int q = 0; q < 2; q++)
    asm volatile("cp.async.bulk.prefetch.tensor.5d.L2.global [%0, {%1, %2, %2, %2, %3}];" ::"l"(tm), "r"(col + q * 64), "r"(0), "r"(2 * kb) : "memory");
}
__device__ __forceinline__ void bulk_load(uint32_t dst, const void* g, uint32_t bytes, uint32_t bar) {
  asm volatile("cp.async.bulk.shared::cluster.global.mbarrier::complete_tx::bytes [%0], [%1], %2, [%3];" ::"r"(dst), "l"(g), "r"(bytes), "r"(bar) : "memory");
}
__device__ __forceinline__ void prefetch_map(const CUtensorMap* tm) { asm volatile("prefetch.tensormap [%0];" ::"l"(tm) : "memory"); }
__device__ __forceinline__ void fence_async_smem() { asm volatile("fence.proxy.async.shared::cta;" ::: "memory"); }
__device__ __forceinline__ void fence_async_global() { asm volatile("fence.proxy.async.global;" ::: "memory"); }
__device__ __forceinline__ void fence_gpu() { asm volatile("fence.release.gpu;" ::: "memory"); }
__device__ __forceinline__ void st_flag(unsigned* p, unsigned v) { asm volatile("st.relaxed.gpu.global.u32 [%0], %1;" ::"l"(p), "r"(v) : "memory"); }
__device__ __forceinline__ unsigned ld_flag(const unsigned* p) { unsigned v; asm volatile("ld.relaxed.gpu.global.u32 %0, [%1];" : "=r"(v) : "l"(p) : "memory"); return v; }
__device__ __forceinline__ uint4 ldcg4(const void* p) { uint4 v; asm volatile("ld.global.cg.v4.u32 {%0,%1,%2,%3}, [%4];" : "=r"(v.x), "=r"(v.y), "=r"(v.z), "=r"(v.w) : "l"(p)); return v; }
__device__ __forceinline__ uint4 ld_pkt(const uint4* p) {
  uint4 v; asm volatile("{\n.reg .b128 t;\nld.relaxed.gpu.global.b128 t, [%4];\nmov.b128 {%0,%1,%2,%3}, t;\n}" : "=r"(v.x), "=r"(v.y), "=r"(v.z), "=r"(v.w) : "l"(p) : "memory"); return v;
}
__device__ __forceinline__ void st_pkt(uint4* p, uint32_t a, uint32_t b, uint32_t c, uint32_t tag) {
  asm volatile("{\n.reg .b128 t;\nmov.b128 t, {%1,%2,%3,%4};\nst.relaxed.gpu.global.b128 [%0], t;\n}" ::"l"(p), "r"(a), "r"(b), "r"(c), "r"(tag) : "memory");
}
__device__ __forceinline__ void st_v4(uint4* p, uint32_t a, uint32_t b, uint32_t c, uint32_t d) { asm volatile("st.relaxed.gpu.global.v4.u32 [%0], {%1,%2,%3,%4};" ::"l"(p), "r"(a), "r"(b), "r"(c), "r"(d) : "memory"); }
__device__ __forceinline__ void stg128(uint4* p, uint4 v) { asm volatile("st.global.v4.u32 [%0], {%1,%2,%3,%4};" ::"l"(p), "r"(v.x), "r"(v.y), "r"(v.z), "r"(v.w) : "memory"); }
__device__ __forceinline__ void sts32(uint32_t addr, uint32_t a) { asm volatile("st.shared.u32 [%0], %1;" ::"r"(addr), "r"(a) : "memory"); }
__device__ __forceinline__ void sts64(uint32_t addr, uint32_t a, uint32_t b) { asm volatile("st.shared.v2.u32 [%0], {%1,%2};" ::"r"(addr), "r"(a), "r"(b) : "memory"); }
__device__ __forceinline__ uint32_t mul2(uint32_t a, uint32_t b) { uint32_t r; asm("mul.rn.bf16x2 %0, %1, %2;" : "=r"(r) : "r"(a), "r"(b)); return r; }
__device__ __forceinline__ uint32_t add2(uint32_t a, uint32_t b) { uint32_t r; asm("add.rn.bf16x2 %0, %1, %2;" : "=r"(r) : "r"(a), "r"(b)); return r; }
__device__ __forceinline__ bool elect() {
  uint32_t p; asm volatile("{\n.reg .pred q;\nelect.sync _|q, 0xffffffff;\nselp.u32 %0, 1, 0, q;\n}" : "=r"(p)); return p != 0;
}
__device__ __forceinline__ void wgmma_fence() { asm volatile("wgmma.fence.sync.aligned;" ::: "memory"); }
__device__ __forceinline__ void wgmma_commit() { asm volatile("wgmma.commit_group.sync.aligned;" ::: "memory"); }
template <int N> __device__ __forceinline__ void wgmma_wait() { asm volatile("wgmma.wait_group.sync.aligned %0;" ::"n"(N) : "memory"); }
template <int N> __device__ __forceinline__ void fence_regs(float (&d)[N]) {
#pragma unroll
  for (int i = 0; i < N; i++) asm volatile("" : "+f"(d[i])::"memory");
}
template <int R> __device__ __forceinline__ void reg_alloc() { asm volatile("setmaxnreg.inc.sync.aligned.u32 %0;" ::"n"(R)); }
template <int R> __device__ __forceinline__ void reg_dealloc() { asm volatile("setmaxnreg.dec.sync.aligned.u32 %0;" ::"n"(R)); }
__device__ __forceinline__ void wg_bar(int w) { asm volatile("bar.sync %0, 128;" ::"r"(w + 1) : "memory"); }
__device__ __forceinline__ constexpr uint32_t desc_lo(uint32_t addr, uint32_t lbo) { return (addr >> 4) + ((lbo >> 4) << 16); }
__device__ __forceinline__ uint32_t pack2(float lo, float hi) { uint32_t r; asm("cvt.rn.bf16x2.f32 %0, %1, %2;" : "=r"(r) : "f"(hi), "f"(lo)); return r; }
__device__ __forceinline__ float lo16(uint32_t v) { return __uint_as_float(v << 16); }
__device__ __forceinline__ float hi16(uint32_t v) { return __uint_as_float(v & 0xFFFF0000u); }
__device__ __forceinline__ float ex2(float x) { float r; asm("ex2.approx.ftz.f32 %0, %1;" : "=f"(r) : "f"(x)); return r; }
__device__ __forceinline__ float rcp(float x) { float r; asm("rcp.approx.ftz.f32 %0, %1;" : "=f"(r) : "f"(x)); return r; }
__device__ __forceinline__ uint32_t movm(uint32_t a) { uint32_t d; asm volatile("movmatrix.sync.aligned.m8n8.trans.b16 %0, %1;" : "=r"(d) : "r"(a)); return d; }
__device__ __forceinline__ void stsm4(uint32_t addr, uint32_t a, uint32_t b, uint32_t c, uint32_t d) {
  asm volatile("stmatrix.sync.aligned.m8n8.x4.shared.b16 [%0], {%1,%2,%3,%4};" ::"r"(addr), "r"(a), "r"(b), "r"(c), "r"(d) : "memory");
}
__device__ __forceinline__ void ldsm4(uint32_t addr, uint32_t (&r)[4]) {
  asm volatile("ldmatrix.sync.aligned.m8n8.x4.shared.b16 {%0,%1,%2,%3}, [%4];" : "=r"(r[0]), "=r"(r[1]), "=r"(r[2]), "=r"(r[3]) : "r"(addr) : "memory");
}
__device__ __forceinline__ void sts128(uint32_t addr, uint32_t a, uint32_t b, uint32_t c, uint32_t d) {
  asm volatile("st.shared.v4.u32 [%0], {%1,%2,%3,%4};" ::"r"(addr), "r"(a), "r"(b), "r"(c), "r"(d) : "memory");
}
__device__ __forceinline__ void lds128(uint32_t addr, uint32_t& a, uint32_t& b, uint32_t& c, uint32_t& d) {
  asm volatile("ld.shared.v4.u32 {%0,%1,%2,%3}, [%4];" : "=r"(a), "=r"(b), "=r"(c), "=r"(d) : "r"(addr) : "memory");
}
__device__ __forceinline__ float lds32f(uint32_t addr) { float v; asm volatile("ld.shared.f32 %0, [%1];" : "=f"(v) : "r"(addr) : "memory"); return v; }
__device__ __forceinline__ float2 lds64f(uint32_t addr) { float2 v; asm volatile("ld.shared.v2.f32 {%0,%1}, [%2];" : "=f"(v.x), "=f"(v.y) : "r"(addr) : "memory"); return v; }
__device__ __forceinline__ void mma16816(float (&d)[4], uint32_t a0, uint32_t a1, uint32_t a2, uint32_t a3, uint32_t b0, uint32_t b1) {
  asm("mma.sync.aligned.m16n8k16.row.col.f32.bf16.bf16.f32 {%0,%1,%2,%3}, {%4,%5,%6,%7}, {%8,%9}, {%0,%1,%2,%3};"
      : "+f"(d[0]), "+f"(d[1]), "+f"(d[2]), "+f"(d[3]) : "r"(a0), "r"(a1), "r"(a2), "r"(a3), "r"(b0), "r"(b1));
}
__device__ __forceinline__ void mma1688(float (&d)[4], uint32_t a0, uint32_t a1, uint32_t b0) {
  asm("mma.sync.aligned.m16n8k8.row.col.f32.bf16.bf16.f32 {%0,%1,%2,%3}, {%4,%5}, {%6}, {%0,%1,%2,%3};"
      : "+f"(d[0]), "+f"(d[1]), "+f"(d[2]), "+f"(d[3]) : "r"(a0), "r"(a1), "r"(b0));
}

__device__ __forceinline__ float qsum(float v) { v += __shfl_xor_sync(0xffffffffu, v, 1); v += __shfl_xor_sync(0xffffffffu, v, 2); return v; }

constexpr int NCTA = 132;
#define NB_ 6
#define NA_ 5
constexpr int NB = NB_;
constexpr int NA = NA_;
constexpr uint32_t SLOT = 16384;
constexpr uint32_t SB = 1024;
constexpr uint32_t OFF_B = 0;
constexpr uint32_t OFF_A = NB * SLOT;
constexpr uint32_t OFF_S = OFF_A + NA * SLOT;
constexpr uint32_t OFF_T = OFF_S + 20480;
constexpr uint32_t OFF_CS = OFF_T + 24576;
constexpr uint32_t OFF_MR = OFF_CS + 4640;
constexpr uint32_t OFF_BAR = OFF_MR + 512;
constexpr uint32_t OFF_MA = OFF_S, OFF_MB = OFF_CS - 2048;
constexpr uint32_t BAR_FULLB = OFF_BAR;
constexpr uint32_t BAR_FULLA = BAR_FULLB + 64;
constexpr uint32_t BAR_EMPTYB = BAR_FULLA + 64;
constexpr uint32_t BAR_EMPTYA = BAR_EMPTYB + 64;
constexpr uint32_t BAR_SIGP = BAR_EMPTYA + 64;
constexpr uint32_t BAR_SIGT = BAR_SIGP + 24;
constexpr uint32_t BAR_STAT = BAR_SIGP + 64;
constexpr uint32_t BAR_HALO = BAR_STAT + 16;
constexpr uint32_t BAR_CS = BAR_HALO + 8;
constexpr uint32_t BAR_WPHI = BAR_CS + 16;
constexpr uint32_t BAR_KV = BAR_WPHI + 8;
constexpr uint32_t BAR_STG = BAR_KV + 16;
constexpr uint32_t BAR_EPOCH = BAR_STG + 48;
constexpr uint32_t BAR_LAND = OFF_BAR + 7 * 64;
constexpr uint32_t OFF_EPOCH = OFF_BAR + 8 * 64;
static_assert(BAR_EPOCH < BAR_LAND, "barriers");
constexpr uint32_t SMEM_BYTES = OFF_EPOCH + 8;
static_assert(SMEM_BYTES <= 232448 && NB % 2 == 0 && NB <= 8 && NA <= 6, "smem");

#define CREGS 224
#define PREGS 56
#define PF1 19
#define PF2 21
#define PRE_A 2
#define PRE_B 4
#define CSNEED 0xF001u
#define PS0 1
#define PS1 2
#define SD 1000
#define KSPLIT 12
#define KEEP 16
#define NJ 3
#define KSL 1000
#define PSL 0
#define KVS 12
#define D2 2000
#define D3 1500
#define G0 50
#define MAP 3
#define PMAP 0x76321450u
#define XA 3
#define CP 500
#define S0 200
#define NS 2
#define SW 2
#define SA 1
#define SB_ 4
#define ND0 1
#define KC 4
#define CO 0
#define SE 500
#define PAA 1600
#define PAX 900
#define PA0 1800
#define PX0 1100
#define XN 1
#define RG 1
#define KI 1
#define PADS 0
#define PADM 150
#define TSK 3
constexpr int NTHREADS = 384;

struct Params {
  CUtensorMap mx;
  CUtensorMap mw[3];
  CUtensorMap mwo[2];
  CUtensorMap mcs[2];
  CUtensorMap mwphi;
  uint4* out;
};

#define XBUF(L) 1
__device__ __align__(256) uint4 g_img[XBUF(3) + 1][16][16][1024];
__device__ __forceinline__ uint32_t img_code(bool isx, int L) { return isx ? (L & 1) | (L & 2) << 15 : ~L & 1; }
__device__ __forceinline__ uint32_t img_mask(bool isx) { return isx ? 0x10001u : 1u; }
__device__ __align__(256) uint4 g_wf[2][8][16][1024];
__device__ __align__(256) uint4 g_stats[16][2][8][32];
__device__ __align__(256) uint4 g_halo[16][8][2][256];
__device__ __align__(256) float g_cs[2][2][3072];
__device__ __align__(256) uint4 g_kvpart[8][16][2][544];
__device__ __align__(256) uint4 g_kvfin[8][16][80];
__device__ __align__(256) unsigned g_hint[16][32];
__device__ __align__(256) unsigned g_jflag[3][8][32];
__device__ unsigned g_ctr;
__device__ __forceinline__ unsigned vblock() {
  unsigned s;
  asm volatile("mov.u32 %0, %%smid;" : "=r"(s));
  const unsigned r = s & 1;
  s >>= 1;
  const unsigned t = s - 32, q = (t * 37) >> 8;
  const unsigned hi = s < 60 ? 12 + (t - 7 * q) * 8 + q : (s < 62 ? s + 4 : s - 58);
  unsigned b = 2 * (s < 32 ? (s & 7) * 8 + (s >> 3) : hi) + r;
  if (b < 128) b = (b & 15) | ((PMAP >> ((b >> 4) * 4)) & 7) << 4;
  if (s >= 62) b = 8 + 4 * r + s - 62;
  unsigned n;
  asm volatile("mov.u32 %0, %%nsmid;" : "=r"(n));
  return __shfl_sync(0xffffffffu, n == NCTA ? b : blockIdx.x, 0);
}
#define TS(who, id) do {} while (0)
#define TSW(id) do {} while (0)

#define TSH(id) do {} while (0)
#define TSMASK 0xFFFF
#define TSL_(a) do { if ((TSMASK >> (a)) & 1) TSW((a) + L * 12); } while (0)
__device__ __forceinline__ int cta_m(unsigned b) { return ((b >> 2) & 12) | (b & 3); }
__device__ __forceinline__ int cta_j(unsigned b) { return ((b >> 2) & 3) | ((b >> 4) & 4); }
struct Ring { uint32_t s, ph; };
template <int N> __device__ __forceinline__ void adv(Ring& r) { if (++r.s == N) { r.s = 0; r.ph ^= 1; } }
template <int N> __device__ __forceinline__ void rewind2(Ring& r) { if (r.s < 2) { r.s += N - 2; r.ph ^= 1; } else r.s -= 2; }
__device__ __forceinline__ int other_tile(int t, int j) { return (t == (j | 4) ? 7 : t) ^ (~j & 4); }
__device__ __forceinline__ int o_order(int i, int j) {
  if (i < 2) return 2 * j + i;
  const int odd = i >= 9;
  return 2 * other_tile(i - 2 - 7 * odd, j) + odd;
}
__device__ __forceinline__ int kv_order(int i, int j, int L) { return L > 0 ? o_order(i, j) : (i + 14 + 2 * (j & 4)) & 15; }

__device__ __forceinline__ unsigned poll_flags(const unsigned* f, int n, unsigned need, unsigned tag) {
  const int lane = threadIdx.x & 31;
  unsigned mask; int it = 0;
  do {
    unsigned v = lane < n ? ld_flag(f + lane) : 0u;
    mask = __ballot_sync(0xffffffffu, lane < n && (int)(v - tag) >= 0);
    if (++it > (1 << 22)) __trap();
  } while ((mask & need) != need);
  fence_async_global();
  return mask;
}
template <bool WAIT = true>
__device__ __forceinline__ unsigned get_tag(uint32_t sb) {
  if (WAIT) mbar_wait(sb + BAR_EPOCH, 0);
  unsigned t; asm volatile("ld.shared.u32 %0, [%1];" : "=r"(t) : "r"(sb + OFF_EPOCH) : "memory");
  return t;
}

__device__ __forceinline__ int lane_id() { int l; asm volatile("mov.u32 %0, %%laneid;" : "=r"(l)); return l; }
__device__ __forceinline__ unsigned seq4(unsigned tag, int L) { return 8u | ((tag & 1u) << 2) | (unsigned)L; }
constexpr float LOG2E = 1.4426950408889634f;

__device__ __forceinline__ float bb_fence(int never, const void* p = &g_ctr, uint32_t keep = 0) {
  while (never < 0) never = ld_flag((const unsigned*)p) + keep;
  return __int_as_float(never >> 30);
}
__device__ __forceinline__ uint32_t solid(uint32_t v) { return __shfl_sync(0xffffffffu, v, threadIdx.x & 31); }
template <class T> __device__ __forceinline__ T* solid(T* p) { return (T*)__shfl_sync(0xffffffffu, (unsigned long long)p, threadIdx.x & 31); }
constexpr uint32_t HA128 = 0x40000040u, HA64 = 0x80000040u;
struct Ctx {
  static constexpr uint32_t sb = SB;
  uint32_t ab, da0;
  int w, warp, lane, g, c;
  int goff;
  __device__ __forceinline__ int m() const { return goff >> 14; }
  __device__ __forceinline__ int j() const { return (goff >> 4) & 7; }
  bool elected;
  Ring ra, rb;
  uint32_t pa, pb;
  uint32_t ha, k2;
  uint32_t mrow, mxor, mhi;
  __device__ __forceinline__ uint32_t aslot(uint32_t s) const { return ab + s * SLOT; }
  __device__ __forceinline__ uint32_t fullA(uint32_t s) const { return sb + BAR_FULLA + s * 8; }
  __device__ __forceinline__ uint32_t fullB(uint32_t s) const { return sb + BAR_FULLB + s * 8; }
  __device__ __forceinline__ void releaseA(uint32_t s) const { if (elected) mbar_arrive(sb + BAR_EMPTYA + s * 8); }
  __device__ __forceinline__ void releaseB(uint32_t s) const { if (elected) mbar_arrive(sb + BAR_EMPTYB + s * 8); }
  __device__ __forceinline__ uint32_t maddr(uint32_t tile, uint32_t ch) const { return tile + mrow + (((ch + mhi) ^ mxor) << 4); }
  __device__ __forceinline__ uint32_t oo() const { return warp * 128 + g * 4 + (c ^ (g >> 1)); }
  __device__ __forceinline__ uint4* img(int b, int hp) const { return ip + (b * 256 + hp) * 1024; }
  uint4* ip;
  uint32_t so;
  __device__ __forceinline__ uint32_t held(int i) const { return ra.s + i < 2 ? ra.s + i + NA - 2 : ra.s + i - 2; }
};

template <int N, bool FIRST, bool O = true>
__device__ __forceinline__ void gemm_issue(float (&acc)[N / 2], Ctx& x, bool ready = false) {
  if (!ready) {
    if (N == 256) mbar_wait3(x.fullA(x.ra.s), x.ra.ph, x.fullB(x.rb.s), x.rb.ph);
    else mbar_wait2(x.fullA(x.ra.s), x.ra.ph, x.fullB(x.rb.s), x.rb.ph);
  }
  const uint32_t da = x.da0 + x.ra.s * (SLOT / 16), db = desc_lo(SB + OFF_B, 8192) + x.rb.s * (SLOT / 16);
  wgmma_fence();
#pragma unroll
  for (int k = 0; k < 4; k++) {
    const uint32_t a = da + (k >> 1) * (O ? 32 : x.k2) + (k & 1) * 2, ha = O ? HA64 : x.ha;
    if constexpr (N == 256) wgmma_ss_n256(acc, a, ha, db + 128 * k, !(FIRST && k == 0));
    else wgmma_ss_n128(acc, a, ha, db + 128 * k, !(FIRST && k == 0));
  }
  wgmma_commit();
}
template <int N>
__device__ __forceinline__ void gemm_next(Ctx& x) {
  x.pa = x.ra.s; x.pb = x.rb.s;
  if (N == 256) x.rb.s++;
  adv<NA>(x.ra); adv<NB>(x.rb);
}
template <int N>
__device__ __forceinline__ void gemm_release(Ctx& x, bool relA) {
  if (relA) x.releaseA(x.pa);
  x.releaseB(x.pb);
  if (N == 256) x.releaseB(x.pb + 1);
}
template <int N>
__device__ __forceinline__ void gemm_retire(Ctx& x, bool relA) { wgmma_wait<1>(); gemm_release<N>(x, relA); gemm_next<N>(x); }
template <bool O = true>
__device__ __forceinline__ void gemm_run(float (&acc)[64], Ctx& x, int n, int hold, int n4 = 0) {
  bool ready = false;
#pragma unroll 1
  for (; n > 0; n--) {
    gemm_issue<128, false, O>(acc, x, ready);
    const uint32_t pa = x.pa, pb = x.pb;
    gemm_next<128>(x);
    ready = mbar_probe2(x.fullA(x.ra.s), x.ra.ph, x.fullB(x.rb.s), x.rb.ph);
    wgmma_wait<1>();
    if (n > hold) x.releaseA(pa);
    x.releaseB(pb);
  }
}
__device__ __forceinline__ void gemm_end(float (&acc)[64], Ctx& x) { wgmma_wait<0>(); fence_regs(acc); gemm_release<128>(x, false); }

__device__ __forceinline__ void rows_load(uint4* r, uint32_t tile, const Ctx& x) {
#pragma unroll
  for (int q = 0; q < 4; q++) {
    const uint32_t row = x.warp * 16 + 4 * q + (x.lane >> 3);
    lds128(tile + row * 128 + (((x.lane & 7) ^ (row & 7)) << 4), r[q].x, r[q].y, r[q].z, r[q].w);
  }
}
__device__ __forceinline__ void rows_store(const uint4* r, uint4* g) {
#pragma unroll
  for (int q = 0; q < 4; q++) stg128(g + q * 1024, r[q]);
}
__device__ __forceinline__ void publish(int id, const Ctx& x) { __syncwarp(); if (x.lane == 0) mbar_arrive(x.sb + BAR_SIGP + id * 8); }
__device__ __forceinline__ uint32_t img_tag(uint32_t v, bool isx, int L, const Ctx& x) {
  const uint32_t mk = ((x.lane ^ (x.warp * 4)) & 7) ? 0u : img_mask(isx);
  return (v & ~mk) | (img_code(isx, L) & mk);
}
__device__ __forceinline__ void img_tag(uint4 (&r)[4], bool isx, int L, const Ctx& x) {
#pragma unroll
  for (int q = 0; q < 4; q++) { uint32_t& v = q == 0 ? r[q].x : (q == 1 ? r[q].y : (q == 2 ? r[q].z : r[q].w)); v = img_tag(v, isx, L, x); }
}
__device__ __forceinline__ void img_store(const uint4 (&r)[4], uint4* g) {
#pragma unroll
  for (int q = 0; q < 4; q++) stg128(g + q * 32, r[q]);
}
__device__ __forceinline__ void img_sts(const uint4 (&r)[4], uint32_t tile, const Ctx& x) {
#pragma unroll
  for (int q = 0; q < 4; q++) sts128(tile + x.so + q * 512, r[q].x, r[q].y, r[q].z, r[q].w);
}
__device__ __forceinline__ void img_load(uint32_t (&v)[16], uint32_t tile, const Ctx& x) {
#pragma unroll
  for (int q = 0; q < 4; q++) lds128(tile + x.so + q * 512, v[4 * q], v[4 * q + 1], v[4 * q + 2], v[4 * q + 3]);
}
__device__ __forceinline__ void img_unpack(float* a, const uint32_t (&v)[16]) {
#pragma unroll
  for (int q = 0; q < 16; q++) { a[4 * (q & 7) + 2 * (q >> 3)] = lo16(v[q]); a[4 * (q & 7) + 2 * (q >> 3) + 1] = hi16(v[q]); }
}

template <int N>
__device__ __forceinline__ void stats_acc(const float* a, float (&t)[4]) {
#pragma unroll
  for (int i = 0; i < N; i++) { t[i & 2] += a[i]; t[(i & 2) + 1] = fmaf(a[i], a[i], t[(i & 2) + 1]); }
}
__device__ __forceinline__ void stats_send(float (&t)[4], int L, const Ctx& x) {
  const unsigned seq = seq4(get_tag<false>(x.sb), L);
#pragma unroll
  for (int q = 0; q < 4; q++) t[q] = qsum(t[q]);
  if (x.c == 0) st_pkt(&g_stats[x.m()][x.w][x.j()][x.warp * 8 + x.g], __float_as_uint(t[0]), __float_as_uint(t[1]), __float_as_uint(t[2]), (__float_as_uint(t[3]) & ~15u) | seq);
}
__device__ __forceinline__ void out_epilogue(const float (&acc)[64], uint4 (&r1)[4], float (&t)[4], uint4* g, int L, Ctx& x) {
  const uint32_t t0 = x.aslot(x.ra.s), t1 = x.aslot(x.ra.s + 1 == NA ? 0 : x.ra.s + 1);
  if (L == 3) {
#pragma unroll
    for (int p = 0; p < 8; p++) {
      stsm4(x.maddr(p < 4 ? t0 : t1, (p & 3) * 2), pack2(acc[8 * p], acc[8 * p + 1]), pack2(acc[8 * p + 2], acc[8 * p + 3]),
            pack2(acc[8 * p + 4], acc[8 * p + 5]), pack2(acc[8 * p + 6], acc[8 * p + 7]));
      if ((p & 3) == 3) { uint4 r[4]; __syncwarp(); rows_load(r, p < 4 ? t0 : t1, x); rows_store(r, g + (p >> 2) * 8); }
    }
  } else {
    auto pack16 = [&](uint4 (&r)[4], const float* a) {
#pragma unroll
      for (int q = 0; q < 4; q++) { const float* u = a + 16 * (q & 1) + (q & 2); r[q] = make_uint4(pack2(u[0], u[1]), pack2(u[4], u[5]), pack2(u[8], u[9]), pack2(u[12], u[13])); }
    };
    uint4 r0[4];
    pack16(r0, acc);
    img_tag(r0, true, L + 1, x);
    img_store(r0, x.img(XBUF(L + 1), 0));
    const float z = bb_fence(x.goff);
    img_sts(r0, t0, x);
    pack16(r1, acc + 32);
    img_tag(r1, true, L + 1, x);
    img_sts(r1, t1, x);
    float u[4] = {z, z, z, z}, v[4] = {z, z, z, z};
    stats_acc<32>(acc, v);
    stats_acc<32>(acc + 32, u);
#pragma unroll
    for (int q = 0; q < 4; q++) t[q] = u[q] + v[q];
    mbar_wait2(x.fullB(x.rb.s), x.rb.ph, x.fullB(x.rb.s + 1), x.rb.ph);
    fence_async_smem();
    asm volatile("bar.sync %0, %1;" ::"r"(L == 1 ? x.w + 1 : 3), "r"(L == 1 ? 128 : 256) : "memory");
  }
}

struct Stats { float rstd0, rstd1; };
__device__ __forceinline__ Stats load_stats(int half, const Ctx& x) {
  const float2 u = lds64f(x.sb + OFF_MR + half * 256 + (x.warp * 8 + x.g) * 8);
  return {u.x, u.y};
}

template <int NH, int NK, class F>
__device__ __forceinline__ void hedgehog_scale(float* t, const Stats& st, const uint32_t* keep, F use) {
#pragma unroll
  for (int q = 0; q < 16 * NH; q++) t[q] *= ((q & 2) ? st.rstd1 : st.rstd0) * LOG2E;
  use();
  float m[4];
#pragma unroll
  for (int q = 0; q < 4 * NH; q++) {
    const float v = fmaxf(fmaxf(fabsf(t[4 * q]), fabsf(t[4 * q + 1])), fmaxf(fabsf(t[4 * q + 2]), fabsf(t[4 * q + 3])));
    m[q & 3] = q < 4 ? v : fmaxf(m[q & 3], v);
  }
  if (__builtin_expect(__any_sync(0xffffffffu, fmaxf(fmaxf(m[0], m[1]), fmaxf(m[2], m[3])) > 58.f), 0)) {
    float z[16 * NH + NK];
#pragma unroll
    for (int q = 0; q < 16 * NH + NK; q++) z[q] = q < 16 * NH ? t[q % (16 * NH)] : __uint_as_float(keep[q & 15]);
#pragma unroll 1
    for (int r = 0; r < 2 * NH; r++) {
      float hi = -INFINITY, lo = INFINITY;
#pragma unroll 1
      for (int i = 0; i < 16; i++) {
        const int k = (i & 6) * 2 + (i & 1) + (r & 1) * 2 + (r & 2) * 8;
        const float v = z[k];
        if (i < 8) { hi = fmaxf(hi, v); lo = fminf(lo, v); }
        else z[k] = v - fminf(fmaxf(v, lo), hi);
        if (i == 7) {
#pragma unroll 1
          for (int d = 1; d <= 2; d++) { hi = fmaxf(hi, __shfl_xor_sync(0xffffffffu, hi, d)); lo = fminf(lo, __shfl_xor_sync(0xffffffffu, lo, d)); }
          const float mid = 0.5f * hi + 0.5f * lo;
          hi = fmaxf(hi - 58.f, mid); lo = fminf(lo + 58.f, mid);
        }
      }
    }
#pragma unroll
    for (int q = 0; q < 16 * NH; q++) t[q] = z[q];
    use();
  }
}
__device__ __forceinline__ void dual_exp(const float* t, uint32_t (&f)[18], int never) {
  float e[KSPLIT];
#pragma unroll
  for (int q = 0; q < KSPLIT; q++) e[q] = ex2(q < 16 ? t[q] : -t[q & 15]);
  while (never < 0) {
#pragma unroll
    for (int i = 0; i < KSPLIT; i += 4) asm volatile("ld.shared.v4.f32 {%0,%1,%2,%3}, [%4];" : "=f"(e[i]), "=f"(e[i + 1]), "=f"(e[i + 2]), "=f"(e[i + 3]) : "r"(never + i) : "memory");
    never += __float_as_int(e[0]);
  }
#pragma unroll
  for (int q = 0; q < KSPLIT; q += 2) f[q >> 1] = pack2(e[q], e[q + 1]);
#pragma unroll
  for (int q = KSPLIT; q < 32; q += 2) f[q >> 1] = q < 16 ? pack2(ex2(t[q]), ex2(t[q + 1])) : pack2(ex2(-t[q & 15]), ex2(-t[(q & 15) + 1]));
#pragma unroll
  for (int sg = 0; sg < 2; sg++) {
    const uint32_t* u = f + 8 * sg;
    const uint32_t a = add2(add2(u[0], u[2]), add2(u[4], u[6])), b = add2(add2(u[1], u[3]), add2(u[5], u[7]));
    f[16 + sg] = add2(__byte_perm(a, b, 0x5410), __byte_perm(a, b, 0x7632));
  }
}
__device__ __forceinline__ void dual_exp_rcp(const float* t, uint32_t* f) {
#pragma unroll
  for (int q = 0; q < 8; q++) {
    const float a = ex2(t[2 * q]), b = ex2(t[2 * q + 1]), r = rcp(a * b);
    f[q] = pack2(a, b); f[8 + q] = pack2(r * b, r * a);
  }
}
__device__ __forceinline__ void cta_bar() { asm volatile("bar.sync 3, 256;" ::: "memory"); }

template <int N> __device__ __forceinline__ void pin(const uint32_t* v, uint32_t addr) {
#pragma unroll
  for (int i = 0; i < N; i += 4)
    asm volatile("{\n.reg .pred p;\nsetp.eq.u32 p, %0, 0;\n@p st.shared.v4.u32 [%0], {%1,%2,%3,%4};\n}" ::"r"(addr), "r"(v[i]), "r"(v[i + 1]), "r"(v[i + 2]), "r"(v[i + 3]) : "memory");
}

__device__ __forceinline__ void consumer(const Params& P, uint32_t sb, int w, unsigned vb) {
  Ctx x;
  x.w = w;
  x.ab = sb + OFF_A + w * 8192; x.da0 = desc_lo(SB + OFF_A, 16) + w * 512;
  x.lane = threadIdx.x & 31; x.warp = __shfl_sync(0xffffffffu, (threadIdx.x >> 5) & 3, 0); x.g = x.lane >> 2; x.c = x.lane & 3;
  x.goff = (cta_m(vb) * 128 + w) * 128 + cta_j(vb) * 16;
  asm volatile("" : "+r"(x.goff));
  x.elected = (threadIdx.x & 127) == 0;
  x.ra = {0, 0}; x.rb = {0, 0}; x.pa = x.pb = 0;
  {
    const uint32_t row = x.warp * 16 + (x.lane & 15);
    x.mrow = row * 128; x.mxor = row & 7; x.mhi = x.lane >> 4;
  }
  const int goff = x.goff;
  x.ip = solid(&g_img[0][x.m()][2 * x.j()][w * 512 + x.oo()]);
  x.so = solid(16 * x.oo());
  uint4 r1[4];
  float ts[4] = {0.f, 0.f, 0.f, 0.f};
#pragma unroll
  for (int i = 0; i < 4; i++) r1[i] = make_uint4(0, 0, 0, 0);
  TSW(0);
  mbar_wait3(x.fullA(0), 0, x.fullB(0), 0);
#pragma unroll 1
  for (int L = 0; L < 4; L++) {
    float acc[64];
    constexpr uint32_t dcs = desc_lo(SB + OFF_CS, 0);
    if ((L & 1) == 0) {
    float kv[128];
    x.ha = L ? HA64 : HA128; x.k2 = L ? 32 : 4;
    gemm_issue<256, true, false>(kv, x, true); gemm_next<256>(x);
    {
      int i = 1;
#pragma unroll 1
      for (int seg = L ? NS - 1 : 0; seg <= NS; seg++) {
        const int end = seg < NS ? (L == 0 ? 3 + SA * ((x.j() + SW * w) & 3) + SB_ * seg : XA + 1) : 14 + L;
#pragma unroll 1
        do {
          gemm_issue<256, false, false>(kv, x);
          gemm_retire<256>(x, true);
          i++;
          if (i == 5) TSL_(8);
          if (i == 11) TSL_(10);
        } while (i != end);
        if (seg < NS && L == 0) {
          uint32_t v[16];
          float a[32];
#pragma unroll
          for (int q = 0; q < 4; q++) ldsm4(x.maddr(x.aslot(x.pa), 2 * q), reinterpret_cast<uint32_t (&)[4]>(v[4 * q]));
#pragma unroll
          for (int q = 0; q < 16; q++) { a[2 * q] = lo16(v[q]); a[2 * q + 1] = hi16(v[q]); }
          stats_acc<32>(a, ts);
          fence_regs(ts);
          wg_bar(w);
        }
        if (seg == NS - 1) {
          if (L > 0) { img_store(r1, x.img(XBUF(L), 1)); publish(2, x); }
          mbar_wait(sb + BAR_EPOCH, 0);
          stats_send(ts, L, x);
        }
      }
    }
      const Ring kt = x.ra;
      if (L == 0) adv<NA>(x.ra);
#pragma unroll 1
      for (int h = L; h < 2; h++) {
        float d[16];
        mbar_wait2(x.fullA(kt.s), kt.ph, sb + BAR_WPHI, 0);
        wgmma_fence();
#pragma unroll
        for (int q = 0; q < 2; q++) wgmma_ss_n32(d, x.da0 + kt.s * (SLOT / 16) + h * 4 + q * 2, desc_lo(SB + OFF_S + 4096, 512) + w * 256 + h * 128 + q * 64, q);
        wgmma_commit();
        gemm_issue<256, false, false>(kv, x);
        gemm_retire<256>(x, true);
        if (h) x.releaseA(kt.s);
        fence_regs(d);
        uint4* dst = &g_wf[1][x.j()][x.m()][w * 512 + (x.warp * 16 + x.g) * 8 + ((h * 4 + x.c) ^ x.g)];
        dst[0] = make_uint4(pack2(d[0], d[1]), pack2(d[4], d[5]), pack2(d[8], d[9]), pack2(d[12], d[13]));
        dst[64] = make_uint4(pack2(d[2], d[3]), pack2(d[6], d[7]), pack2(d[10], d[11]), pack2(d[14], d[15]));
      }
      const uint32_t dm = desc_lo(SB + OFF_MA, 0) + w * 64;
      mbar_wait2(sb + BAR_STAT, 0, sb + BAR_CS, 0);
      wgmma_fence();
      wgmma_r1_n256(kv, dm, dcs + 96, 1);
      wgmma_commit();
      const Stats st = load_stats(w, x);
      mbar_wait2(x.fullA(x.ra.s), x.ra.ph, x.fullB(x.rb.s), x.rb.ph);
      wgmma_wait<0>();
      fence_regs(kv);
      gemm_release<256>(x, true);
      TSL_(2);
      uint32_t P0[32], P1[32], PH[32];
#pragma unroll
      for (int t = 0; t < 16; t++) { P0[t] = pack2(kv[4 * t] * st.rstd0, kv[4 * t + 1] * st.rstd0); P1[t] = pack2(kv[4 * t + 2] * st.rstd1, kv[4 * t + 3] * st.rstd1); }
      pin<16>(P0, x.mrow + 16);
      {
#pragma unroll
        for (int q = 0; q < 4; q++) sts128((x.warp < 3 ? sb + OFF_T + w * 12288 + x.warp * 4096 : sb + OFF_S + 16384 + w * 2048) + x.lane * 16 + q * 512, P1[4 * q], P1[4 * q + 1], P1[4 * q + 2], P1[4 * q + 3]);
      }
      wgmma_fence();
      wgmma_r1_n128(acc, dm, dcs, 0);
      gemm_issue<128, false, false>(acc, x, true); gemm_next<128>(x);
      TSL_(3);
#pragma unroll
      for (int s = 0; s < 4; s++) {
#pragma unroll
        for (int t = 16 + 8 * (s & 1); t < 24 + 8 * (s & 1); t++) {
          if (s < 2) P1[t] = movm(pack2(kv[4 * t + 2] * st.rstd1, kv[4 * t + 3] * st.rstd1));
          else P0[t] = movm(pack2(kv[4 * t] * st.rstd0, kv[4 * t + 1] * st.rstd0));
        }
        if (s < 3) { gemm_issue<128, false, false>(acc, x); gemm_retire<128>(x, true); }
        if (s == 1) {
          if (x.warp < 3) {
#pragma unroll
            for (int q = 4; q < 8; q++) sts128(sb + OFF_T + w * 12288 + x.warp * 4096 + x.lane * 16 + q * 512, P1[4 * q], P1[4 * q + 1], P1[4 * q + 2], P1[4 * q + 3]);
          } else {
            uint4* dst = &g_halo[x.m()][x.j()][w][x.lane];
#pragma unroll
            for (int q = 0; q < 8; q++) dst[q * 32] = make_uint4(P1[4 * q], P1[4 * q + 1], P1[4 * q + 2], P1[4 * q + 3]);
          }
          publish(3, x);
          gemm_issue<128, false, false>(acc, x);
          gemm_retire<128>(x, true);
        }
      }
      TSL_(4);
      gemm_run<false>(acc, x, 10, 0);
      publish(0, x);
      gemm_issue<128, false, false>(acc, x);
      {
        wg_bar(w);
        uint32_t tr = sb + OFF_T + w * 12288 + (x.warp - 1) * 4096;
        if (x.warp == 0) {
          tr = x.m() > 0 ? sb + OFF_S + 8192 + w * 4096 : tr + 4096;
          if (x.m() > 0) mbar_wait(sb + BAR_HALO, L >> 1);
        }
#pragma unroll
        for (int q = 0; q < 8; q++) lds128(tr + x.lane * 16 + q * 512, PH[4 * q], PH[4 * q + 1], PH[4 * q + 2], PH[4 * q + 3]);
      }
      gemm_retire<128>(x, false);
      gemm_end(acc, x);
      TSL_(5);
      const bool first = (x.m() == 0) && (x.warp == 0);
      const bool hi0 = 2 * x.c > x.g, hi1 = 2 * x.c + 1 > x.g;
      const uint32_t mhi = (hi0 ? 0xFFFFu : 0u) | (hi1 ? 0xFFFF0000u : 0u);
      const uint32_t valid = first ? ~mhi : ~0u;
      const float sc0 = st.rstd0 * (0.17677669529663687f * LOG2E), sc1 = st.rstd1 * (0.17677669529663687f * LOG2E);
      uint32_t xr[2][16];
#pragma unroll
      for (int hp = 0; hp < 2; hp++) {
        const uint32_t tile = x.aslot(x.held(hp));
        uint32_t px[2], py[2];
        float s[2][3][4];
#pragma unroll
        for (int u = 0; u < 2; u++) {
#pragma unroll
          for (int q = 0; q < 12; q++) s[u][q >> 2][q & 3] = 0.f;
#pragma unroll
          for (int ks = 0; ks < 2; ks++) {
            const int t = 8 * hp + 4 * u + 2 * ks;
            const uint32_t a0 = pack2(acc[4 * t], acc[4 * t + 1]), a1 = pack2(acc[4 * t + 2], acc[4 * t + 3]);
            const uint32_t a2 = pack2(acc[4 * t + 4], acc[4 * t + 5]), a3 = pack2(acc[4 * t + 6], acc[4 * t + 7]);
            mma16816(s[u][0], a0, a1, a2, a3, PH[t], PH[t + 1]);
            mma16816(s[u][1], a0, a1, a2, a3, P0[t], P0[t + 1]);
            mma16816(s[u][2], a0, a1, a2, a3, P1[t], P1[t + 1]);
          }
        }
        float e[2][4], big = 0.f;
#pragma unroll
        for (int u = 0; u < 2; u++) {
          e[u][0] = (hi0 ? s[u][0][0] : s[u][1][0]) * sc0; e[u][1] = (hi1 ? s[u][0][1] : s[u][1][1]) * sc0;
          e[u][2] = (hi0 ? s[u][1][2] : s[u][2][2]) * sc1; e[u][3] = (hi1 ? s[u][1][3] : s[u][2][3]) * sc1;
          big = fmaxf(big, fmaxf(fmaxf(fabsf(e[u][0]), fabsf(e[u][1])), fmaxf(fabsf(e[u][2]), fabsf(e[u][3]))));
          px[u] = pack2(ex2(e[u][0]), ex2(e[u][1])) & valid; py[u] = pack2(ex2(e[u][2]), ex2(e[u][3]));
        }
        if (__builtin_expect(__any_sync(0xffffffffu, big > 58.f), 0)) {
#pragma unroll
          for (int q = 0; q < 4; q++) {
            float v0 = e[q >> 1][2 * (q & 1)], v1 = e[q >> 1][2 * (q & 1) + 1];
            if (first && !(q & 1)) { if (hi0) v0 = -INFINITY; if (hi1) v1 = -INFINITY; }
            float r = fmaxf(v0, v1);
            r = fmaxf(r, __shfl_xor_sync(0xffffffffu, r, 1)); r = fmaxf(r, __shfl_xor_sync(0xffffffffu, r, 2));
            ((q & 1) ? py : px)[q >> 1] = pack2(ex2(v0 - r), ex2(v1 - r));
          }
        }
        float r[2][2];
#pragma unroll
        for (int u = 0; u < 2; u++) {
          float d[4] = {0.f, 0.f, 0.f, 0.f};
          mma1688(d, px[u], py[u], 0x3F803F80u);
          r[u][0] = rcp(d[0]); r[u][1] = rcp(d[2]);
        }
        uint32_t o[8][2];
        uint4 ro[4];
#pragma unroll
        for (int q = 0; q < 8; q++) {
          float d[4] = {0.f, 0.f, 0.f, 0.f};
          const int t = 16 + 8 * hp + q, u = q >> 2;
          mma16816(d, px[u] & mhi, 0u, px[u] & ~mhi, py[u] & mhi, PH[t], P0[t]);
          mma1688(d, 0u, py[u] & ~mhi, P1[t]);
          o[q][0] = pack2(d[0] * r[u][0], d[1] * r[u][0]); o[q][1] = pack2(d[2] * r[u][1], d[3] * r[u][1]);
        }
#pragma unroll
        for (int q = 0; q < 4; q++) ro[q] = make_uint4(o[4 * (q & 1)][q >> 1], o[4 * (q & 1) + 1][q >> 1], o[4 * (q & 1) + 2][q >> 1], o[4 * (q & 1) + 3][q >> 1]);
        img_tag(ro, false, 0, x);
        img_store(ro, x.img(0, hp));
        if (hp == 0) bb_fence(x.goff);
        if (hp == 0) {
#pragma unroll
          for (int i = 0; i < 2; i++) {
            const uint32_t ti = x.aslot(x.held(i));
            if (L) img_load(xr[i], ti, x);
            else {
#pragma unroll
              for (int q = 0; q < 4; q++) ldsm4(x.maddr(ti, 2 * q), reinterpret_cast<uint32_t (&)[4]>(xr[i][4 * q]));
            }
          }
          __syncwarp();
        }
        img_sts(ro, tile, x);
      }
      if (L == 0) {
#pragma unroll
        for (int hp = 0; hp < 2; hp++) {
          uint32_t v[16];
#pragma unroll
          for (int q = 0; q < 16; q++) asm volatile("mov.b32 %0, %1;" : "=r"(v[(q & 1) * 8 + (q >> 1)]) : "r"(xr[hp][q]));
#pragma unroll
          for (int q = 0; q < 16; q++) xr[hp][q] = v[q];
        }
      }
      img_unpack(acc, xr[0]); img_unpack(acc + 32, xr[1]);
    } else {
      float kv[128];
      float (&kv0)[64] = reinterpret_cast<float (&)[64]>(kv[0]);
      float (&kv1)[64] = reinterpret_cast<float (&)[64]>(kv[64]);
      auto mma8 = [&](uint32_t as, uint32_t bs, int i, bool fence) {
        const uint32_t da = desc_lo(SB + OFF_A, 16) + as * (SLOT / 16), db = desc_lo(SB + OFF_B, 8192) + bs * (SLOT / 16);
        if (fence) wgmma_fence();
#pragma unroll
        for (int k = 0; k < 4; k++) {
          wgmma_ss_n128(kv0, da + (k >> 1) * 32 + (k & 1) * 2, HA64, db + 128 * k, i + k);
          wgmma_ss_n128(kv1, da + 512 + (k >> 1) * 32 + (k & 1) * 2, HA64, db + 128 * k, i + k);
        }
        wgmma_commit();
      };
      constexpr uint32_t dm = desc_lo(SB + OFF_MB, 0);
      auto relB = [&](uint32_t s) { mbar_arrive_n(sb + BAR_EMPTYB + s * 8, 2); };
      auto skip = [&]() {
#pragma unroll
        for (int q = 0; q < 6 - NJ; q++) adv<NA>(x.ra);
        x.rb.s = w ? (2 + NJ) % 6 : 4;
        if (!w && NJ < 4) x.rb.ph ^= 1;
      };
      static_assert(NA == 5 && NB == 6, "ring arithmetic");
      mma8(x.ra.s, x.rb.s + w, 0, true);
      img_store(r1, x.img(XBUF(L), 1));
      gemm_next<256>(x);
#pragma unroll 1
      for (int i = 1; i < NJ; i++) {
        mbar_wait2(x.fullA(x.ra.s), x.ra.ph, x.fullB(x.rb.s + w), x.rb.ph);
        mma8(x.ra.s, x.rb.s + w, 1, true);
        if (i == 1) { stats_send(ts, L, x); publish(2, x); }
        wgmma_wait<1>();
        if (x.elected) { x.releaseA(x.pa); relB(x.pb + w); }
        gemm_next<256>(x);
      }
      if (w) {
        wgmma_wait<0>();
        if (x.elected) { x.releaseA(x.pa); relB(x.pb + 1); }
        skip();
        asm volatile("bar.sync 7, 256;" ::: "memory");
      }
      TSL_(8);
      {
        const int t = lane_id() + 32 * x.warp;
        uint32_t mask = t < 2 ? ((w ? (t ? 0xFF3Fu : 0x3FFFu) : 0xFFFFu) >> (NJ - 1)) & (w ? ~1u : ~0u) : 0u, cnt = 1 + t;
        bool ready = false;
#pragma unroll 1
        for (int i = NJ; i < 15; i++) {
          if (!ready) mbar_wait2(x.fullA(x.ra.s), x.ra.ph, x.fullB(x.rb.s), x.rb.ph);
          mma8(x.ra.s, x.rb.s, 1, true);
          const uint32_t bar = sb + (t ? BAR_EMPTYB + x.pb * 8 : BAR_EMPTYA + x.pa * 8);
          gemm_next<128>(x);
          if (w && i == 11) x.rb.s = 4;
          ready = mbar_probe2(x.fullA(x.ra.s), x.ra.ph, x.fullB(x.rb.s), x.rb.ph);
          wgmma_wait<1>();
          if (mask & 1) mbar_arrive_n(bar, cnt);
          mask >>= 1; cnt = 2;
          if (i == 8 && w) asm volatile("bar.arrive 9, 256;" ::: "memory");
          if (i == 9) TSL_(10);
        }
        if (!ready) mbar_wait2(x.fullA(x.ra.s), x.ra.ph, x.fullB(x.rb.s), x.rb.ph);
        const uint32_t da = desc_lo(SB + OFF_A, 16) + x.ra.s * (SLOT / 16), db = desc_lo(SB + OFF_B, 8192) + x.rb.s * (SLOT / 16);
#pragma unroll
        for (int hf = 0; hf < 2; hf++) {
          if (hf == 0) wgmma_fence();
#pragma unroll
          for (int k = 0; k < 4; k++) wgmma_ss_n128(hf ? kv1 : kv0, da + hf * 512 + (k >> 1) * 32 + (k & 1) * 2, HA64, db + 128 * k, 1);
          if (hf == 0) { mbar_wait2(sb + BAR_STAT, 1, sb + BAR_CS + 8, 0); wgmma_fence(); }
          wgmma_r1_n128(hf ? kv1 : kv0, dm + 64 * hf, dcs + 96 + 96 * w, 1);
          wgmma_commit();
        }
        if (w == 0) asm volatile("bar.arrive 7, 256;" ::: "memory");
        wgmma_wait<2>();
        if (mask & 1) mbar_arrive_n(sb + (t ? BAR_EMPTYB + x.pb * 8 : BAR_EMPTYA + x.pa * 8), 2);
        gemm_next<128>(x);
        if (w) x.rb.s = 4;
      }
      const uint32_t la = x.pa, lb = x.pb;
      auto finish = [&]() { wgmma_wait<0>(); fence_regs(kv1); if (x.elected) { if (w == 0) mbar_arrive_n(sb + BAR_EMPTYA + la * 8, 2); relB(lb); } };
      const Stats s0 = load_stats(0, x), s1 = load_stats(1, x), st = w ? s1 : s0;
      if (w == 0) skip();
      const uint32_t h0 = x.held(0), h1 = x.held(1);
      auto vreg = [&](int ks) { return (ks & 3) < 3 ? OFF_A + (ks < 4 ? h0 : h1) * SLOT + (ks & 3) * 5120 : OFF_S + 32768 + (ks >> 2) * 5120; };
      uint32_t tV[2], uu[4];
#pragma unroll
      for (int hf = 0; hf < 2; hf++) {
        tV[hf] = sb + vreg(4 * hf + x.warp) + ((x.lane >> 3) & 1) * 2560 + (x.lane & 7) * 16 + x.mhi * 128;
        const float i0 = rcp(hf ? s1.rstd0 : s0.rstd0), i1 = rcp(hf ? s1.rstd1 : s0.rstd1);
        const uint32_t h = pack2(i0, i1);
        uu[2 * hf] = pack2(lo16(h), i0 - lo16(h)); uu[2 * hf + 1] = pack2(hi16(h), i1 - hi16(h));
        asm volatile("" : "+r"(tV[hf]), "+r"(uu[2 * hf]), "+r"(uu[2 * hf + 1])::"memory");
      }
      wgmma_wait<1>();
      fence_regs(kv0);
      TSL_(2);
      if (w == 0) {
        uint32_t f[2][18], ad[4];
#pragma unroll
        for (int q = 0; q < 18; q++) f[1][q] = 0u;
#pragma unroll
        for (int q = 0; q < 4; q++) ad[q] = x.maddr(sb + OFF_S, 2 * q);
        auto norm = [&](int un) {
          uint32_t* u = f[un & 1];
          const Stats& sn = un ? s1 : s0;
#pragma unroll
          for (int sg = 0; sg < 2; sg++) {
            uint32_t v = u[16 + sg];
            v = add2(v, __shfl_xor_sync(0xffffffffu, v, 1)); v = add2(v, __shfl_xor_sync(0xffffffffu, v, 2));
            const float a = rcp(lo16(v)) * sn.rstd0, b = rcp(hi16(v)) * sn.rstd1;
            const uint32_t r0 = pack2(a, a), r1_ = pack2(b, b);
#pragma unroll
            for (int q = 8 * sg; q < 8 * sg + 8; q++) u[q] = mul2(u[q], (q & 1) ? r1_ : r0);
#pragma unroll
            for (int q = 2 * sg; q < 2 * sg + 2; q++) stsm4(ad[q] + un * 8192, u[4 * q], u[4 * q + 1], u[4 * q + 2], u[4 * q + 3]);
          }
        };
        auto move = [&](int dst, int src) {
#pragma unroll
          for (int q = 0; q < 16; q++) asm volatile("mov.b32 %0, %1;" : "=f"(kv[dst + q]) : "f"(src ? kv[src + q] : 0.f));
        };
        hedgehog_scale<1, 0>(kv, s0, nullptr, [] {});
        finish();
        uint32_t step = 0;
#pragma unroll 1
        for (int h = 0;; h++) {
          norm(1);
          dual_exp(kv, f[0], x.goff);
          hedgehog_scale<1, KEEP>(kv + 64, s1, f[1], [] {});
          if (h == 2) asm volatile("bar.sync 9, 256;" ::: "memory");
#pragma unroll
          for (int q = 0; q < 4; q++) ad[q] += step;
          norm(0);
          dual_exp(kv + 64, f[1], x.goff);
#pragma unroll
          for (int q = 0; q < 16; q++) kv[q] = kv[16 + q];
          hedgehog_scale<1, KEEP>(kv, s0, f[0], [] {});
          step = SLOT;
          if (h == 0) { move(64, 80); move(16, 32); }
          else if (h == 1) { move(64, 96); move(16, 48); step = OFF_B + SLOT - OFF_S; }
          else if (h == 2) { move(64, 112); move(16, 0); }
          else break;
        }
        norm(1);
        TSL_(3);
      } else {
#pragma unroll
        for (int hf = 0; hf < 2; hf++) {
          if (hf) finish();
          wg_bar(w);
          stsm4(tV[hf] + 512 + x.mhi * 512, uu[2 * hf], uu[2 * hf + 1], uu[2 * hf], uu[2 * hf + 1]);
          stsm4(tV[hf] + 1792 + x.mhi * 512, uu[2 * hf], uu[2 * hf + 1], uu[2 * hf], uu[2 * hf + 1]);
#pragma unroll
          for (int q = 0; q < 8; q++) {
            const float* u = kv + 64 * hf + 8 * q;
            stsm4(tV[hf] + (q >> 1) * 640 + (q & 1) * 256, pack2(u[0], u[1]), pack2(u[2], u[3]), pack2(u[4], u[5]), pack2(u[6], u[7]));
          }
        }
        TSL_(3);
      }
      {
        float d[2][20];
        uint4* dst = &g_kvpart[x.j()][w * 4 + x.warp][0][x.m() * 32 + x.lane];
        unsigned* dz = reinterpret_cast<unsigned*>(&g_kvpart[x.j()][w * 4 + x.warp][x.c & 1][512]) + x.m() * 8 + x.g;
        fence_async_smem();
        cta_bar();
        TSL_(11);
        uint32_t pk[9];
        auto prep = [&](float (&u)[20]) {
          fence_regs(u);
#pragma unroll
          for (int q = 0; q < 8; q++) pk[q] = pack2(u[((q >> 1) & 2) + 4 * (q & 3)], u[((q >> 1) & 2) + 4 * (q & 3) + 1]);
          pk[8] = __float_as_uint((x.c & 1) ? u[18] + u[19] : u[16] + u[17]);
#pragma unroll
          for (int q = 0; q < 9; q += 4) pk[q] = (pk[q] & ~1u) | (L == 1);
        };
        auto send = [&](int hp) {
          st_v4(dst + hp * 16 * 544, pk[0], pk[1], pk[2], pk[3]); st_v4(dst + (hp * 16 + 1) * 544, pk[4], pk[5], pk[6], pk[7]);
          st_flag(dz + hp * 16 * 544 * 4, pk[8]);
        };
        wgmma_fence();
#pragma unroll
        for (int q = 0; q < 17; q++) {
          if (q < 16) wgmma_ss_n40_tt(d[q >> 3], desc_lo(SB + (q < 8 ? OFF_S : OFF_B + 2 * SLOT), 1024) + w * (SLOT / 16) + 128 * (q & 7), desc_lo(SB + vreg(q & 7), 2560) + (w + (q >> 3) * 2) * 40, q & 7);
          else wgmma_r1_n128(acc, dm + w * 64, dcs, 0);
          if (q == 7 || q == KVS || q == 16) wgmma_commit();
          if (q == KVS) { mbar_wait2(x.fullA(x.ra.s), x.ra.ph, x.fullB(x.rb.s), x.rb.ph); wgmma_wait<1>(); prep(d[0]); send(0); bb_fence(x.goff); wgmma_fence(); }
        }
        gemm_issue<128, false>(acc, x, true); gemm_next<128>(x);
        wgmma_wait<1>();
        x.releaseA(h0); x.releaseA(h1); x.releaseB(2); x.releaseB(3);
        if (x.lane == 0) mbar_arrive(sb + BAR_SIGT);
        prep(d[1]);
        TSL_(4);
#pragma unroll 1
        for (int seg = 0; seg < 2; seg++) {
          const int n0 = w ? PS1 : PS0;
          gemm_run(acc, x, seg ? 15 - n0 : n0, seg, seg ? L : 0);
          if (seg == 0) send(1);
        }
      }
      gemm_end(acc, x);
      TSL_(5);
      {
        float dp[2][20], dn[2][20];
        uint32_t f[4][16];
        auto mma = [&](int h) {
          if (!(h & 1)) mbar_wait(sb + BAR_KV + h * 4, L >> 1);
          if (h == 0) TSL_(9);
          const uint32_t db = desc_lo(SB + OFF_S + h * 5120, 128);
          const uint32_t (&a)[16] = f[h];
          wgmma_fence();
          wgmma_rs_n40(dp[h & 1], a[0], a[1], a[2], a[3], db, 0);
          wgmma_rs_n40(dn[h & 1], a[8], a[9], a[10], a[11], db + 160, 0);
          wgmma_rs_n40(dp[h & 1], a[4], a[5], a[6], a[7], db + 80, 1);
          wgmma_rs_n40(dn[h & 1], a[12], a[13], a[14], a[15], db + 240, 1);
          wgmma_commit();
        };
        uint32_t xr[16];
        auto fin = [&](int h) {
          const uint32_t tile = x.aslot(x.held(h >> 1));
          if (!(h & 1)) img_load(xr, tile, x);
          float (&u)[20] = dp[h & 1];
          float (&v)[20] = dn[h & 1];
          fence_regs(u); fence_regs(v);
#pragma unroll
          for (int r = 0; r < 2; r++) {
            const float sp = u[16 + 2 * r], sn = v[16 + 2 * r];
            const float id = rcp(fmaf(fmaf(sp, L == 1 ? 0.065536f * 128 / 129 : 0.065536f, u[17 + 2 * r]), sn, v[17 + 2 * r] * sp)), aa = sn * id, cc = sp * id;
            uint32_t o[4];
#pragma unroll
            for (int t = 0; t < 4; t++) o[t] = pack2(fmaf(u[4 * t + 2 * r], aa, v[4 * t + 2 * r] * cc), fmaf(u[4 * t + 2 * r + 1], aa, v[4 * t + 2 * r + 1] * cc));
            o[2 * r + (h & 1)] = img_tag(o[2 * r + (h & 1)], false, 1, x);
            stg128(x.img(0, h >> 1) + r * 64 + (h & 1) * 32, make_uint4(o[0], o[1], o[2], o[3]));
            sts128(tile + r * 1024 + (h & 1) * 512 + x.so, o[0], o[1], o[2], o[3]);
          }
          if (h & 1) { if (h == 1) publish(0, x); img_unpack(acc + 16 * (h - 1), xr); }
        };
        auto ex = [&](int h) { dual_exp_rcp(acc + 16 * h, f[h]); };
        Stats sq = st;
#pragma unroll
        for (int h = 0; h < 4; h += 2) {
          hedgehog_scale<2, 0>(acc + 16 * h, sq, nullptr, [&] { ex(h); });
          mma(h);
          ex(h + 1); wgmma_wait<0>(); fin(h);
          if (h == 0) bb_fence(x.goff);
          mma(h + 1);
          wgmma_wait<0>(); fin(h + 1);
          if (h == 0) sq.rstd1 += bb_fence(x.goff);
        }
      }
    }
    mbar_wait(x.fullB(x.rb.s), x.rb.ph);
    fence_regs(acc);
    fence_async_smem();
    wg_bar(w);
    TSL_(6);
    rewind2<NA>(x.ra);
    gemm_issue<128, false>(acc, x, true); gemm_next<128>(x);
    uint4* out = solid(P.out + goff + (x.warp * 16 + (x.lane >> 3)) * 256 + (x.lane & 7));
#pragma unroll 1
    for (int seg = 0; seg < 2; seg++) {
      const int nt = L == 3 ? TSK : XN;
      gemm_run(acc, x, seg ? nt : 15 - nt, seg, 10 + L);
      if (L < 3) { if (seg == 0) publish(1, x); }
      else if (seg != w) {
        if (w) asm volatile("bar.sync 6, 256;" ::: "memory"); else asm volatile("bar.arrive 6, 256;" ::: "memory");
      }
    }
    gemm_end(acc, x);
    TSL_(7);
    rewind2<NA>(x.ra);
    out_epilogue(acc, r1, ts, out, L, x);
    TSL_(13);
  }
}

typedef unsigned long long u64;
template <class T> __device__ __forceinline__ T* early(T* p) { return (T*)__shfl_xor_sync(0xffffffffu, (u64)p, 1); }
__device__ __forceinline__ void pause(uint32_t GAP) {
  if (GAP) { uint32_t t0, t; asm volatile("mov.u32 %0, %%clock;" : "=r"(t0)); do { asm volatile("mov.u32 %0, %%clock;" : "=r"(t)); } while (t - t0 < GAP); }
}
__device__ __forceinline__ u64 order_table0(int j) { return (j & 4) ? 0x543210FEDCBA9876ull : 0xDCBA9876543210FEull; }
__device__ __forceinline__ void order_tables(u64& t1, u64& t2, int j) {
#pragma unroll 1
  for (int i = 6; i >= 0; i--) { const u64 o = 2 * other_tile(i, j); t1 = t1 << 4 | o | (o + 1) << 28; t2 = t2 << 8 | (o * 17 + 16); }
  const u64 own = 2 * j * 17 + 16;
  t1 = t1 << 8 | own; t2 |= own << 56;
}

template <int N> __device__ __forceinline__ void code_gap(unsigned tag) {
  if (N && tag == 0) {
    float u = lds32f(SB);
#pragma unroll
    for (int q = 0; q < N; q++) asm volatile("fma.rn.f32 %0, %0, %0, %0;" : "+f"(u));
    sts32(SB, __float_as_uint(u));
  }
}

__device__ __forceinline__ void b_producer(const Params& P, uint32_t sb, unsigned vb) {
  const int j = cta_j(vb);
  u64 t1 = 0, t2 = 0;
  Ring r = {PRE_B % NB, PRE_B < NB};
#pragma unroll 1
  for (int sg = 0; sg < 20; sg++) {
    const int L = sg / 5, p = sg - 5 * L, wt = L & 1;
    if (sg == 1) order_tables(t1, t2, j);
    int n = p >= 3 ? 16 : (wt ? (p ? 16 - NJ : 2 * NJ) : (p ? 0 : (L ? 32 : 32 - PRE_B)));
    u64 tab = p == 3 ? t2 : (sg == 0 ? order_table0(j) >> (2 * PRE_B) : (p == 1 || p == 2 ? t1 >> (4 * NJ) : t1));
    const CUtensorMap* tm = p == 4 ? &P.mwo[wt] : &P.mw[wt ? 1 : L];
    const uint4* img = &g_wf[p != 3][j][0][0];
    int col = (p >= 3 ? 0 : (p == 2 ? 2048 : 1024)) + 128 * j;
    const int flip = p == 0 ? 3072 : 0;
    const bool fold = wt && p != 4;
    if (sg == 5 || sg == 8) { mbar_wait(sb + (sg == 5 ? BAR_WPHI : BAR_CS + 8), sg == 5); fence_async_global(); }
#pragma unroll 1
    for (; n > 0; n--) {
      const int kb = (int)tab & 15;
      mbar_wait(sb + BAR_EMPTYB + r.s * 8, r.ph);
      if (elect()) {
        mbar_expect_tx(sb + BAR_FULLB + r.s * 8, SLOT);
        if (fold && col < 2048) bulk_load(sb + OFF_B + r.s * SLOT, img + kb * 1024, SLOT, sb + BAR_FULLB + r.s * 8);
        else tma_load_w(sb + OFF_B + r.s * SLOT, tm, sb + BAR_FULLB + r.s * 8, col, kb);
      }
      adv<NB>(r);
      if (p == 2 && (n | 4) == 5) r.s = 4;
      col ^= flip;
      if (!(col & flip & 2048)) tab >>= 4;
    }
  }
}

__device__ __forceinline__ void kv_images(uint32_t sb, int L, int j, unsigned tag, unsigned& ph) {
  const int lane = threadIdx.x & 31;
  auto hinted = [&](int h) { return __all_sync(0xffffffffu, (int)(ld_flag(&g_jflag[h][j][lane & 15]) - (tag * 4 + L)) >= 0); };
  auto load = [&](int h) { if (elect()) { mbar_expect_tx(sb + BAR_LAND + 48 + h * 8, 10240); bulk_load(sb + OFF_S + h * 10240, &g_kvfin[j][8 * h][0], 10240, sb + BAR_LAND + 48 + h * 8); } };
  bool sent = false;
#pragma unroll 1
  for (int h = 0, it = 0; h < 2;) {
    if (++it > (1 << 22)) __trap();
    if (h == 0 || !sent) {
      if (!hinted(h)) continue;
      load(h);
    }
    if (KI && h == 0 && !sent && hinted(1)) { load(1); sent = true; }
    mbar_wait(sb + BAR_LAND + 48 + h * 8, (ph >> h) & 1);
    ph ^= 1u << h;
    uint32_t a = 1u, o = 0u;
#pragma unroll
    for (int u = 0; u < 20; u++) { const uint32_t v = __float_as_uint(lds32f(sb + OFF_S + h * 10240 + u * 512 + lane * 16)); a &= v; o |= v; }
    if (h) sent = false;
    if (__all_sync(0xffffffffu, (L == 1 ? a : ~o) & 1u)) {
      if (elect()) mbar_arrive(sb + BAR_KV + h * 8);
      h++;
    } else fence_async_smem();
  }
}

__device__ __forceinline__ void a_loader(const Params& P, uint32_t sb, unsigned vb) {
  const int j = cta_j(vb), m = cta_m(vb);
  u64 t1 = 0, t2 = 0;
  Ring r = {PRE_A % NA, PRE_A < NA};
  {
    u64 tab = order_table0(j) >> (4 * PRE_A);
#pragma unroll 1
    for (int i = PRE_A; i < 33; i++) {
      if (i == 17) { order_tables(t1, t2, j); tab = t2; }
      mbar_wait(sb + BAR_EMPTYA + r.s * 8, r.ph);
      if (elect()) {
        mbar_expect_tx(sb + BAR_FULLA + r.s * 8, SLOT);
        if (i != 14) tma_load_3d(sb + OFF_A + r.s * SLOT, &P.mx, sb + BAR_FULLA + r.s * 8, ((int)tab & 15) * 64, m * 64, 0);
        else {
          tma_load_w(sb + OFF_A + r.s * SLOT, &P.mw[1], sb + BAR_FULLA + r.s * 8, 1024 + 128 * j, m);
          mbar_expect_tx(sb + BAR_WPHI, 8192); tma_load_2d(sb + OFF_S + 4096, &P.mwphi, sb + BAR_WPHI, 0, 128 * j);
        }
        if (i == PF1 || i == PF2) tma_prefetch_w(&P.mwo[i == PF2], 128 * j, m);
      }
      adv<NA>(r);
      if (i != 14) tab >>= 4;
    }
  }
  const unsigned tag = get_tag(sb);
  unsigned kph = 0;
#pragma unroll 1
  for (int sg = 0; sg < 13; sg++) {
    const int L = sg >> 2, p = sg & 3;
    if (p == 0 && (L & 1)) kv_images(sb, L, j, tag, kph);
    int n = p < 2 ? 14 : (p == 2 ? ((L & 1) ? 0 : 16 - NJ) : 16);
    u64 tab = p == 3 ? t2 : t1 >> (p < 2 ? 8 : 4 * NJ);
    const uint4* img = &g_img[p ? XBUF(L + 1) : 0][m][0][0];
#pragma unroll 1
    for (; n > 0; n--) {
      const uint4* src = early(img + ((int)tab & 15) * 1024);
      const uint32_t bar = sb + (p < 2 ? BAR_LAND : BAR_FULLA) + r.s * 8;
      mbar_wait(sb + BAR_EMPTYA + r.s * 8, r.ph);
      if (elect()) mbar_expect_tx(bar, SLOT);
      if (p < 2 && n == 14) {
        const int lane = threadIdx.x & 31;
        const unsigned* f = &g_hint[(m & 14) + ((lane >> 3) & 1)][(~j & 4) ^ (lane & ND0)];
        mbar_wait(sb + BAR_SIGP + p * 8, L & 1);
        int it = 0;
        while (!__all_sync(0xffffffffu, (int)(ld_flag(f) - (tag * 16 + 4 * L + 1 + p)) >= 0)) { if (++it > (1 << 22)) __trap(); }
        pause(p ? (L ? PAX : PX0) : ((L & 1) ? 0 : (L ? PAA : PA0)));
        TS(2, p == 0 ? 5 + L * 8 : 9 + L * 8);
        TSH((2 * L + p) * 8 + 2);
      }
      if (elect()) bulk_load(sb + OFF_A + r.s * SLOT, src, SLOT, bar);
      adv<NA>(r);
      tab >>= 4;
      pause(p < 2 && n > 10 ? G0 : 0);
    }
  }
  code_gap<PADM>(tag);
}

template <int KB, int G>
__device__ __forceinline__ uint2 sum_packets(float (&a)[8], uint32_t addr, int n) {
  uint2 ok = make_uint2(~0u, 0u);
#pragma unroll 1
  for (int b = 0; b < n; b += KB) {
    uint4 v[KB];
#pragma unroll
    for (int u = 0; u < KB; u++) lds128(addr + (b + u) * 512, v[u].x, v[u].y, v[u].z, v[u].w);
#pragma unroll
    for (int u = 0; u < KB; u++) { ok.x &= v[u].x; ok.y |= v[u].x; }
#pragma unroll
    for (int d = 1; d < G; d *= 2)
#pragma unroll
      for (int u = 0; u < KB; u += 2 * d) v[u] = make_uint4(add2(v[u].x, v[u + d].x), add2(v[u].y, v[u + d].y), add2(v[u].z, v[u + d].z), add2(v[u].w, v[u + d].w));
#pragma unroll
    for (int u = 0; u < KB; u += G) {
      a[0] += lo16(v[u].x); a[1] += hi16(v[u].x); a[2] += lo16(v[u].y); a[3] += hi16(v[u].y);
      a[4] += lo16(v[u].z); a[5] += hi16(v[u].z); a[6] += lo16(v[u].w); a[7] += hi16(v[u].w);
    }
  }
  return ok;
}
__device__ __forceinline__ void helper_bar() { asm volatile("bar.sync 4, 64;" ::: "memory"); }
__device__ __forceinline__ void helper(const Params& P, uint32_t sb, int w, unsigned vb) {
  const int j = cta_j(vb), m = cta_m(vb);
  if (w == 0) {
    if (elect()) {
      const unsigned t = atomicAdd(&g_ctr, 1u) / NCTA + 1u;
      asm volatile("st.shared.u32 [%0], %1;" ::"r"(sb + OFF_EPOCH), "r"(t) : "memory");
      mbar_arrive(sb + BAR_EPOCH);
    }
  }
  const unsigned tag = get_tag(sb);
  mbar_wait(sb + BAR_FULLB + 24, 0);
  const uint32_t stg = sb + OFF_T + w * 12288, stb = sb + BAR_STG + w * 24;
  Ring rs = {0, 0};
  uint32_t vs = 33 % NA, vph = 0;
  auto cs_image = [&](int L) {
      const int lane = lane_id();
      poll_flags(&g_jflag[2 * L][j][0], 16, L ? CSNEED : 0xFFFu, tag * 4);
#pragma unroll
      for (int p = 0; p < 3; p++) {
        const uint4 u = ldcg4(&g_cs[L][0][p * 1024 + 128 * j + lane * 4]), v = ldcg4(&g_cs[L][1][p * 1024 + 128 * j + lane * 4]);
        const float c0 = __uint_as_float(u.x) + __uint_as_float(v.x), c1 = __uint_as_float(u.y) + __uint_as_float(v.y);
        const float c2 = __uint_as_float(u.z) + __uint_as_float(v.z), c3 = __uint_as_float(u.w) + __uint_as_float(v.w);
        const uint32_t h0 = pack2(c0, c1), h1 = pack2(c2, c3), dst = sb + OFF_CS + (p * 16 + (lane >> 1)) * 96 + L * 48 + (lane & 1) * 8;
        sts64(dst, h0, h1); sts64(dst + 16, pack2(c0 - lo16(h0), c1 - hi16(h0)), pack2(c2 - lo16(h1), c3 - hi16(h1))); sts64(dst + 32, h0, h1);
        if (L == 0) { sts64(dst + 48, 0u, 0u); sts64(dst + 64, 0u, 0u); sts64(dst + 80, 0u, 0u); }
      }
      if (L == 0 && lane < 4) sts64(sb + OFF_CS + 4608 + lane * 8, 0u, 0u);
      fence_async_smem();
      __syncwarp();
      if (elect()) mbar_arrive(sb + BAR_CS + L * 8);
      TS(4, 2 + L * 2);
  };
#pragma unroll 1
  for (int L = 0; L < 4; L++) {
    const int lane = lane_id();
    if (L == 0) {
      {
        const int wt = m >= 12, col = ((0x2021 >> (m & 12)) & 3) * 1024 + 128 * j + (m & 3) * 32;
        const CUtensorMap* tm = &P.mcs[wt];
        if (wt) __nanosleep(D2);
        constexpr int nb = 8;
        float a[8] = {0.f, 0.f, 0.f, 0.f, 0.f, 0.f, 0.f, 0.f};
#pragma unroll 1
        for (int b = -3; b < nb; b++) {
          if (b >= 0) {
            mbar_wait(stb + rs.s * 8, rs.ph);
            sum_packets<KC, 1>(a, stg + rs.s * 4096 + lane * 16, 8);
            fence_async_smem();
            __syncwarp();
          }
          const uint32_t sl = b < 0 ? (rs.s + b + 3) % 3 : rs.s;
          if (b + 3 < nb && elect()) { mbar_expect_tx(stb + sl * 8, 4096); tma_load_2d(stg + sl * 4096, tm, stb + sl * 8, col, (w * (16 - nb) + b + 3) * 64); }
          if (b >= 0) adv<3>(rs); else pause(CP);
        }
#pragma unroll 1
        for (int d = 4; d < 32; d *= 2)
#pragma unroll
          for (int u = 0; u < 8; u++) a[u] += __shfl_xor_sync(0xffffffffu, a[u], d);
        if (lane < 4) {
          float4* dst = reinterpret_cast<float4*>(&g_cs[wt][w][col + lane * 8]);
          dst[0] = make_float4(a[0], a[1], a[2], a[3]); dst[1] = make_float4(a[4], a[5], a[6], a[7]);
        }
        helper_bar();
        if (w == 0 && elect()) { fence_gpu(); st_flag(&g_jflag[2 * wt][j][m], tag * 4); }
      }
      if (w == 0) TS(4, 1 + L * 2);
    }
    if (L > 0 && w == 0) {
      mbar_wait(sb + BAR_SIGP + 16, (L - 1) & 1);
      fence_async_global();
      __nanosleep(CO && L == 1 ? SE : SD);
    }
    if (CO && L < 2 && w == 0) cs_image(L);
    if (w == (L == 0)) {
      if (L == 0) { mbar_wait(sb + BAR_WPHI, 0); __nanosleep(S0); }
#pragma unroll 1
      for (int p = 0; p < 2; p++) {
        uint4 v[8];
        for (int it = 0;; it++) {
          bool ok = true;
#pragma unroll
          for (int t = 0; t < 8; t++) v[t] = ld_pkt(&g_stats[m][p][t][lane]);
#pragma unroll
          for (int t = 0; t < 8; t++) ok = ok && (v[t].w & 15u) == seq4(tag, L);
          if (__all_sync(0xffffffffu, ok)) break;
          __nanosleep(200);
          if (it > (1 << 20)) __trap();
        }
        float s0 = 0.f, q0 = 0.f, s1 = 0.f, q1 = 0.f;
#pragma unroll
        for (int t = 0; t < 8; t++) { s0 += __uint_as_float(v[t].x); q0 += __uint_as_float(v[t].y); s1 += __uint_as_float(v[t].z); q1 += __uint_as_float(v[t].w & ~15u); }
        s0 *= (1.f / 1024); s1 *= (1.f / 1024);
        sts64(sb + OFF_MR + p * 256 + lane * 8, __float_as_uint(rsqrtf(fmaxf(q0 * (1.f / 1024) - s0 * s0, 0.f) + 1e-5f)),
              __float_as_uint(rsqrtf(fmaxf(q1 * (1.f / 1024) - s1 * s1, 0.f) + 1e-5f)));
#pragma unroll
        for (int r = 0; r < 2; r++) {
          const float v = -0.5f * (r ? s1 : s0);
          const uint32_t hh = pack2(v, v), hl = pack2(v, v - lo16(hh));
          const bool b = L & 1;
          sts128(sb + (b ? OFF_MB : OFF_MA) + p * 1024 + (lane >> 3) * 256 + r * 128 + (lane & 7) * 16, b ? 0u : hh, b ? hh << 16 : hl >> 16, b ? hl : 0u, 0u);
        }
      }
      fence_async_smem();
      __syncwarp();
      if (elect()) {
        mbar_arrive(sb + BAR_STAT);
      }
      TS(2, 0 + L * 8);
    }
    if (!CO && L < 2 && w == 0) cs_image(L);
    if (L & 1) {
      const uint32_t flip = L == 1 ? 0u : 1u;
      mbar_wait(sb + BAR_SIGT, 1);
      {
        int it = 0;
        if (PSL) __nanosleep(m < 8 ? PSL : PSL + 600);
        while (!__all_sync(0xffffffffu, (ld_flag(reinterpret_cast<const unsigned*>(&g_kvpart[j][m][w][512]) + (lane & 15) * 8) ^ flip) & 1u)) { if (PSL) __nanosleep(100); if (++it > (1 << 22)) __trap(); }
        fence_async_global();
      }
      if (w == 0) TS(4, 6 + L * 2);
      float a[8], z;
      for (int it = 0;; it++) {
        if (elect()) { mbar_expect_tx(stb + rs.s * 8, 8704); bulk_load(stg, &g_kvpart[j][m][w][0], 8704, stb + rs.s * 8); }
        mbar_wait(stb + rs.s * 8, rs.ph);
        if (w == 0) TS(4, 21 + L);
        adv<3>(rs);
#pragma unroll
        for (int u = 0; u < 8; u++) a[u] = 0.f;
        z = 0.f;
        uint32_t ok = 1u;
#pragma unroll
        for (int u = 0; u < 4; u++) { const float v = lds32f(stg + 8192 + u * 128 + (lane & 3) * 32 + (lane >> 2) * 4); z += v; ok &= __float_as_uint(v) ^ flip; }
        const uint2 tg = sum_packets<8, RG>(a, stg + lane * 16, 16);
        ok &= flip ? ~tg.y : tg.x;
        if (__all_sync(0xffffffffu, ok & 1u)) break;
        fence_async_smem();
        if (it > (1 << 16)) __trap();
      }
      {
        uint4* img = &g_kvfin[j][m][w * 8 + (lane >> 2)];
        uint32_t a0 = __float_as_uint(a[0]) >> 16;
        a0 += ~(a0 ^ flip) & 1u;
        st_v4(img + (lane & 3) * 16, __byte_perm(a0, pack2(0.f, a[1]), 0x7610), pack2(a[2], a[3]), pack2(a[4], a[5]), pack2(a[6], a[7]));
        const uint32_t cz = pack2(0.f, qsum(z)) | (0x3781u ^ flip);
        if (!(lane & 3)) st_v4(img + 64, cz, cz, cz, cz);
        __syncwarp();
        if (elect()) st_flag(&g_jflag[m >> 3][j][(m & 7) * 2 + w], tag * 4 + L);
      }
      if (w == 0) TS(4, 7 + L * 2);
    } else {
      if (L == 0 && w == 0) {
        st_v4(&g_kvpart[j][m][0][512 + lane], 0u, 0u, 0u, 0u); st_v4(&g_kvpart[j][m][1][512 + lane], 0u, 0u, 0u, 0u);
        __syncwarp();
      }
      mbar_wait(sb + BAR_SIGT, 0);
      if (w == 0) {
        if (elect()) { fence_gpu(); st_flag(&g_hint[m][j], tag * 16 + 4 * L); st_flag(&g_jflag[1][j][m], tag * 4 + L); }
        if (L == 0) {
          __nanosleep(KSL);
          poll_flags(&g_jflag[1][j][0], 16, 0xFFFFu, tag * 4);
          if (elect()) mbar_arrive(sb + BAR_WPHI);
        }
      } else if (m > 0) {
        poll_flags(&g_hint[m - 1][j], 1, 1u, tag * 16 + 4 * L);
        if (elect()) { mbar_expect_tx(sb + BAR_HALO, 8192); bulk_load(sb + OFF_S + 8192, &g_halo[m - 1][j][0][0], 8192, sb + BAR_HALO); }
        TS(2, 2 + L * 8);
      }
    }
    if (w == 0) {
#pragma unroll 1
      for (int e = 0; e < (L < 3 ? 2 : 1); e++) {
        unsigned* flag = early(&g_hint[m][j]);
        mbar_wait(sb + BAR_SIGP + e * 8, L & 1);
        TS(2, (e ? 6 : 3) + L * 8);
        TSH((2 * L + e) * 8);
        if (elect()) st_flag(flag, tag * 16 + 4 * L + 1 + e);
        TSH((2 * L + e) * 8 + 1);
      }
    } else {
#pragma unroll 1
      for (int i = 0; i < (L < 3 ? 28 : 14); i++) {
        const bool isx = i >= 14;
        const uint32_t a = sb + OFF_A + vs * SLOT + lane * 128 + ((lane >> 4) * 4 + (lane & 3)) * 16 + (lane & 12), code = img_code(isx, L + isx);
        for (int it = 0;; it++) {
          mbar_wait(sb + BAR_LAND + vs * 8, (vph >> vs) & 1);
          vph ^= 1u << vs;
          if (i - 14 * isx < 2) TSH((2 * L + isx) * 8 + 3 + 2 * (i - 14 * isx));
          uint32_t bad = 0;
#pragma unroll
          for (int u = 0; u < 4; u++) bad |= __float_as_uint(lds32f(a + u * 4096)) ^ code;
          if (__all_sync(0xffffffffu, !(bad & img_mask(isx)))) break;
          if (it > (1 << 16)) __trap();
          fence_async_smem();
          if (elect()) {
            mbar_expect_tx(sb + BAR_LAND + vs * 8, SLOT);
            bulk_load(sb + OFF_A + vs * SLOT, &g_img[isx ? XBUF(L + 1) : 0][m][o_order(i - 14 * isx + 2, j)][0], SLOT, sb + BAR_LAND + vs * 8);
          }
        }
        if (elect()) mbar_arrive(sb + BAR_FULLA + vs * 8);
        if (i - 14 * isx < 2) TSH((2 * L + isx) * 8 + 4 + 2 * (i - 14 * isx));
        if (++vs == NA) vs = 0;
      }
      vs = (vs + ((L & 1) ? 16 : 32 - NJ)) % NA;
    }
  }
}

__device__ __forceinline__ void spare(const Params& P, uint32_t sb, int id) {
  const int tid = threadIdx.x & 127, warp = __shfl_sync(0xffffffffu, threadIdx.x >> 5, 0), w = warp >> 2, lane = tid & 31, j = 2 * id + w;
  const uint32_t ring = w * 6 * SLOT, wp = 12 * SLOT + w * 8192, bar = sb + 13 * SLOT + w * 64;
  auto part = [&](int t) { return (t >> 4) ^ w; };
  auto load = [&](int t, uint32_t sl) {
    mbar_expect_tx(bar + sl * 8, t == 0 ? SLOT + 8192 : SLOT);
    tma_load_w(sb + ring + sl * SLOT, &P.mw[1], bar + sl * 8, part(t) * 1024 + 128 * j, t & 15);
  };
  if (!(warp & 3) && elect()) {
    if (w == 2) sts32(sb + OFF_EPOCH, atomicAdd(&g_ctr, 1u) / NCTA + 1u);
    else {
      __nanosleep(D3);
#pragma unroll 1
      for (int t = 0; t < 5; t++) {
        mbar_init(bar + t * 8, 1);
        asm volatile("fence.mbarrier_init.release.cluster;" ::: "memory");
        load(t, t);
      }
      tma_load_2d(sb + wp, &P.mwphi, bar, 0, 128 * j);
    }
  }
  __syncthreads();
  const unsigned tag = get_tag<false>(sb);
  if (w == 2) {
    int it = 0;
    while ((int)(ld_flag(&g_ctr) - tag * NCTA) < 0) { if (++it > (1 << 22)) __trap(); }
    return;
  }
  Ring r = {4, 1};
  float d[64];
  auto fold = [&]() {
    mbar_wait(bar + r.s * 8, r.ph);
    wgmma_fence();
#pragma unroll
    for (int q = 0; q < 8; q++)
      wgmma_ss_n32(reinterpret_cast<float (&)[16]>(d[16 * (q >> 1)]), desc_lo(SB + ring + r.s * SLOT, 16) + (q >> 2) * 512 + (q & 3) * 2, desc_lo(SB + wp, 512) + q * 64, q & 1);
    wgmma_commit();
  };
#pragma unroll
  for (int i = 0; i < 64; i++) d[i] = 0.f;
  int t = -1;
#pragma unroll 1
  for (int g = 0; g < 2; g++) {
    float cs[32] = {};
#pragma unroll 1
    do {
      uint32_t f[32];
#pragma unroll
      for (int i = 0; i < 32; i++) { f[i] = pack2(d[2 * i], d[2 * i + 1]); cs[i & 30] += d[2 * i]; cs[i | 1] += d[2 * i + 1]; }
      wg_bar(w);
      const uint32_t sl = r.s;
      if (t < 31) adv<5>(r);
      fold();
      if (!(warp & 3) && t >= 0 && t < 27 && elect()) load(t + 5, sl);
      if (g == w && t >= 0) {
        uint4* dst = &g_wf[0][j][t & 15][((tid >> 5) * 16 + (lane >> 2)) * 8];
#pragma unroll
        for (int q = 0; q < 8; q++)
          dst[(q >> 2) * 512 + (q & 1) * 64 + (((q & 2) * 2 + (lane & 3)) ^ (lane >> 2))] =
              make_uint4(f[4 * (q & 6) + (q & 1)], f[4 * (q & 6) + (q & 1) + 2], f[4 * (q & 6) + (q & 1) + 4], f[4 * (q & 6) + (q & 1) + 6]);
      }
      wgmma_wait<0>();
      fence_regs(d);
    } while (++t != 16 * g + 16);
    const uint32_t red = sb + ring + 5 * SLOT;
#pragma unroll
    for (int i = 0; i < 8; i++) sts128(red + (tid >> 2) * 512 + (i >> 1) * 128 + (lane & 3) * 32 + (i & 1) * 16, __float_as_uint(cs[4 * i]), __float_as_uint(cs[4 * i + 1]), __float_as_uint(cs[4 * i + 2]), __float_as_uint(cs[4 * i + 3]));
    wg_bar(w);
    float a = 0.f;
#pragma unroll 4
    for (int i = 0; i < 32; i++) a += lds32f(red + i * 512 + tid * 4);
    g_cs[1][0][(g ^ w) * 1024 + j * 128 + tid] = a;
  }
  wg_bar(w);
  if (tid == 0) { fence_gpu(); st_flag(&g_jflag[2][j][0], tag * 4); }
  code_gap<PADS>(tag);
}

__global__ void __launch_bounds__(NTHREADS, 1) fused_kernel(const __grid_constant__ Params P) {
  extern __shared__ __align__(1024) uint8_t smem_raw[];
  constexpr uint32_t sb = SB;
  const int tid = threadIdx.x;
  const unsigned vb = vblock();
  if (vb >= 128) { spare(P, sb, vb - 128); return; }
  const int warp = __shfl_sync(0xffffffffu, tid >> 5, 0);
  if (elect()) {
    if (warp == 11) { prefetch_map(&P.mx); prefetch_map(&P.mw[0]); if (smem_u32(smem_raw) != SB) __trap(); }
    if (warp < 8) {
#pragma unroll
      for (int i = 0; i < 8; i++) mbar_init(sb + OFF_BAR + (warp * 8 + i) * 8, warp == 2 || warp == 3 ? 2 : (warp == 4 ? 8 : 1));
    }
    asm volatile("fence.mbarrier_init.release.cluster;" ::: "memory");
    if (warp < 2) {
      const int j = cta_j(vb);
#pragma unroll 1
      for (int i = 0; i < (warp == 0 ? PRE_B : PRE_A); i++) {
        const uint32_t bar = sb + BAR_FULLB + warp * 64 + i * 8;
        mbar_expect_tx(bar, SLOT);
        if (warp == 0) tma_load_w(sb + OFF_B + i * SLOT, &P.mw[0], bar, 1024 + (i & 1) * 1024 + 128 * j, kv_order(i >> 1, j, 0));
        else tma_load_3d(sb + OFF_A + i * SLOT, &P.mx, bar, kv_order(i, j, 0) * 64, cta_m(vb) * 64, 0);
      }
    }
  }
  if (tid == 0) TS(6, 0);
  __syncthreads();
  if (tid == 0) TS(6, 2);
  if (warp < 4) {
    reg_dealloc<PREGS>();
    if (warp & 2) helper(P, sb, warp & 1, vb);
    else if (warp & 1) a_loader(P, sb, vb);
    else b_producer(P, sb, vb);
  } else {
    reg_alloc<CREGS>();
    consumer(P, sb, (warp >> 2) - 1, vb);
  }
}

typedef CUresult (*EncodeFn)(CUtensorMap*, CUtensorMapDataType, cuuint32_t, void*, const cuuint64_t*, const cuuint64_t*,
                             const cuuint32_t*, const cuuint32_t*, CUtensorMapInterleave, CUtensorMapSwizzle,
                             CUtensorMapL2promotion, CUtensorMapFloatOOBfill);

void encode(EncodeFn fn, CUtensorMap* m, const void* ptr, int rank, const cuuint64_t* dims, const cuuint64_t* strides,
            const cuuint32_t* box, CUtensorMapSwizzle swz) {
  const cuuint32_t es[5] = {1, 1, 1, 1, 1};
  fn(m, CU_TENSOR_MAP_DATA_TYPE_BFLOAT16, rank, const_cast<void*>(ptr), dims, strides, box, es, CU_TENSOR_MAP_INTERLEAVE_NONE,
     swz, CU_TENSOR_MAP_L2_PROMOTION_L2_256B, CU_TENSOR_MAP_FLOAT_OOB_FILL_NONE);
}
void encode_w(EncodeFn fn, CUtensorMap* m, const void* ptr, int ncols, bool perm) {
  const cuuint64_t p = (cuuint64_t)ncols * 2, d[5] = {(cuuint64_t)ncols, 2, 4, 4, 32}, s[4] = {p, (perm ? 8 : 2) * p, (perm ? 2 : 8) * p, 32 * p};
  const cuuint32_t box[5] = {64, 2, 4, 4, 2};
  encode(fn, m, ptr, 5, d, s, box, CU_TENSOR_MAP_SWIZZLE_128B);
}

void encode_cs(EncodeFn fn, CUtensorMap* m, const void* ptr, int ncols) {
  const cuuint64_t d[2] = {(cuuint64_t)ncols, 1024}, s[1] = {(cuuint64_t)ncols * 2};
  const cuuint32_t box[2] = {32, 64};
  encode(fn, m, ptr, 2, d, s, box, CU_TENSOR_MAP_SWIZZLE_NONE);
}

}

extern "C" void kernel_launch(void* const* d_in, const int* in_sizes, int n_in, void* d_out, int out_size) {
  (void)in_sizes; (void)n_in; (void)out_size;
  void* fnp = nullptr;
  cudaDriverEntryPointQueryResult q;
  cudaGetDriverEntryPoint("cuTensorMapEncodeTiled", &fnp, cudaEnableDefault, &q);
  EncodeFn fn = (EncodeFn)fnp;
  Params P;
  {
    const cuuint64_t dims[3] = {1024, 1024, 2}, strides[2] = {4096, 2048};
    const cuuint32_t box[3] = {64, 64, 2};
    encode(fn, &P.mx, d_in[0], 3, dims, strides, box, CU_TENSOR_MAP_SWIZZLE_128B);
  }
  P.out = (uint4*)d_out;
  encode_w(fn, &P.mw[0], d_in[1], 3072, false);
  encode_w(fn, &P.mw[1], d_in[4], 3072, true);
  encode_w(fn, &P.mw[2], d_in[1], 3072, true);
  encode_w(fn, &P.mwo[0], d_in[2], 1024, true);
  encode_w(fn, &P.mwo[1], d_in[6], 1024, false);
  encode_cs(fn, &P.mcs[0], d_in[1], 3072);
  encode_cs(fn, &P.mcs[1], d_in[4], 3072);
  {
    const cuuint64_t dims[2] = {32, 1024}, strides[1] = {64};
    const cuuint32_t box[2] = {32, 128};
    encode(fn, &P.mwphi, d_in[5], 2, dims, strides, box, CU_TENSOR_MAP_SWIZZLE_64B);
  }
  cudaFuncSetAttribute(fused_kernel, cudaFuncAttributeMaxDynamicSharedMemorySize, SMEM_BYTES);
  fused_kernel<<<NCTA, NTHREADS, SMEM_BYTES, cudaStreamPerThread>>>(P);
}
```

```cpp
#include <cuda_runtime.h>
#include <cuda_bf16.h>
#include <cuda.h>
#include <stdint.h>

namespace {

__device__ __forceinline__ void wgmma_ss_n256(float (&d)[128], uint32_t da, uint32_t ha, uint32_t db, int sd) {
  asm volatile("{\n.reg .pred p;\n.reg .b64 a, b;\nsetp.ne.b32 p, %130, 0;\nmov.b64 a, {%128, %131};\nmov.b64 b, {%129, 0x40000040};\n"
    "wgmma.mma_async.sync.aligned.m64n256k16.f32.bf16.bf16 {%0,%1,%2,%3,%4,%5,%6,%7,%8,%9,%10,%11,%12,%13,%14,%15,%16,%17,%18,%19,%20,%21,%22,%23,%24,%25,%26,%27,%28,%29,%30,%31,%32,%33,%34,%35,%36,%37,%38,%39,%40,%41,%42,%43,%44,%45,%46,%47,%48,%49,%50,%51,%52,%53,%54,%55,%56,%57,%58,%59,%60,%61,%62,%63,%64,%65,%66,%67,%68,%69,%70,%71,%72,%73,%74,%75,%76,%77,%78,%79,%80,%81,%82,%83,%84,%85,%86,%87,%88,%89,%90,%91,%92,%93,%94,%95,%96,%97,%98,%99,%100,%101,%102,%103,%104,%105,%106,%107,%108,%109,%110,%111,%112,%113,%114,%115,%116,%117,%118,%119,%120,%121,%122,%123,%124,%125,%126,%127}, a, b, p, 1, 1, 0, 1;\n}\n"
    : "+f"(d[0]),"+f"(d[1]),"+f"(d[2]),"+f"(d[3]),"+f"(d[4]),"+f"(d[5]),"+f"(d[6]),"+f"(d[7]),"+f"(d[8]),"+f"(d[9]),"+f"(d[10]),"+f"(d[11]),"+f"(d[12]),"+f"(d[13]),"+f"(d[14]),"+f"(d[15]),"+f"(d[16]),"+f"(d[17]),"+f"(d[18]),"+f"(d[19]),"+f"(d[20]),"+f"(d[21]),"+f"(d[22]),"+f"(d[23]),"+f"(d[24]),"+f"(d[25]),"+f"(d[26]),"+f"(d[27]),"+f"(d[28]),"+f"(d[29]),"+f"(d[30]),"+f"(d[31]),"+f"(d[32]),"+f"(d[33]),"+f"(d[34]),"+f"(d[35]),"+f"(d[36]),"+f"(d[37]),"+f"(d[38]),"+f"(d[39]),"+f"(d[40]),"+f"(d[41]),"+f"(d[42]),"+f"(d[43]),"+f"(d[44]),"+f"(d[45]),"+f"(d[46]),"+f"(d[47]),"+f"(d[48]),"+f"(d[49]),"+f"(d[50]),"+f"(d[51]),"+f"(d[52]),"+f"(d[53]),"+f"(d[54]),"+f"(d[55]),"+f"(d[56]),"+f"(d[57]),"+f"(d[58]),"+f"(d[59]),"+f"(d[60]),"+f"(d[61]),"+f"(d[62]),"+f"(d[63]),"+f"(d[64]),"+f"(d[65]),"+f"(d[66]),"+f"(d[67]),"+f"(d[68]),"+f"(d[69]),"+f"(d[70]),"+f"(d[71]),"+f"(d[72]),"+f"(d[73]),"+f"(d[74]),"+f"(d[75]),"+f"(d[76]),"+f"(d[77]),"+f"(d[78]),"+f"(d[79]),"+f"(d[80]),"+f"(d[81]),"+f"(d[82]),"+f"(d[83]),"+f"(d[84]),"+f"(d[85]),"+f"(d[86]),"+f"(d[87]),"+f"(d[88]),"+f"(d[89]),"+f"(d[90]),"+f"(d[91]),"+f"(d[92]),"+f"(d[93]),"+f"(d[94]),"+f"(d[95]),"+f"(d[96]),"+f"(d[97]),"+f"(d[98]),"+f"(d[99]),"+f"(d[100]),"+f"(d[101]),"+f"(d[102]),"+f"(d[103]),"+f"(d[104]),"+f"(d[105]),"+f"(d[106]),"+f"(d[107]),"+f"(d[108]),"+f"(d[109]),"+f"(d[110]),"+f"(d[111]),"+f"(d[112]),"+f"(d[113]),"+f"(d[114]),"+f"(d[115]),"+f"(d[116]),"+f"(d[117]),"+f"(d[118]),"+f"(d[119]),"+f"(d[120]),"+f"(d[121]),"+f"(d[122]),"+f"(d[123]),"+f"(d[124]),"+f"(d[125]),"+f"(d[126]),"+f"(d[127])
    : "r"(da), "r"(db), "r"(sd), "r"(ha));
}
__device__ __forceinline__ void wgmma_ss_n128(float (&d)[64], uint32_t da, uint32_t ha, uint32_t db, int sd) {
  asm volatile("{\n.reg .pred p;\n.reg .b64 a, b;\nsetp.ne.b32 p, %66, 0;\nmov.b64 a, {%64, %67};\nmov.b64 b, {%65, 0x40000040};\n"
    "wgmma.mma_async.sync.aligned.m64n128k16.f32.bf16.bf16 {%0,%1,%2,%3,%4,%5,%6,%7,%8,%9,%10,%11,%12,%13,%14,%15,%16,%17,%18,%19,%20,%21,%22,%23,%24,%25,%26,%27,%28,%29,%30,%31,%32,%33,%34,%35,%36,%37,%38,%39,%40,%41,%42,%43,%44,%45,%46,%47,%48,%49,%50,%51,%52,%53,%54,%55,%56,%57,%58,%59,%60,%61,%62,%63}, a, b, p, 1, 1, 0, 1;\n}\n"
    : "+f"(d[0]),"+f"(d[1]),"+f"(d[2]),"+f"(d[3]),"+f"(d[4]),"+f"(d[5]),"+f"(d[6]),"+f"(d[7]),"+f"(d[8]),"+f"(d[9]),"+f"(d[10]),"+f"(d[11]),"+f"(d[12]),"+f"(d[13]),"+f"(d[14]),"+f"(d[15]),"+f"(d[16]),"+f"(d[17]),"+f"(d[18]),"+f"(d[19]),"+f"(d[20]),"+f"(d[21]),"+f"(d[22]),"+f"(d[23]),"+f"(d[24]),"+f"(d[25]),"+f"(d[26]),"+f"(d[27]),"+f"(d[28]),"+f"(d[29]),"+f"(d[30]),"+f"(d[31]),"+f"(d[32]),"+f"(d[33]),"+f"(d[34]),"+f"(d[35]),"+f"(d[36]),"+f"(d[37]),"+f"(d[38]),"+f"(d[39]),"+f"(d[40]),"+f"(d[41]),"+f"(d[42]),"+f"(d[43]),"+f"(d[44]),"+f"(d[45]),"+f"(d[46]),"+f"(d[47]),"+f"(d[48]),"+f"(d[49]),"+f"(d[50]),"+f"(d[51]),"+f"(d[52]),"+f"(d[53]),"+f"(d[54]),"+f"(d[55]),"+f"(d[56]),"+f"(d[57]),"+f"(d[58]),"+f"(d[59]),"+f"(d[60]),"+f"(d[61]),"+f"(d[62]),"+f"(d[63])
    : "r"(da), "r"(db), "r"(sd), "r"(ha));
}
__device__ __forceinline__ void wgmma_ss_n40_tt(float (&d)[20], uint32_t da, uint32_t db, int sd) {
  asm volatile("{\n.reg .pred p;\n.reg .b64 a, b;\nsetp.ne.b32 p, %22, 0;\nmov.b64 a, {%20, 0x40000040};\nmov.b64 b, {%21, 0x8};\n"
    "wgmma.mma_async.sync.aligned.m64n40k16.f32.bf16.bf16 {%0,%1,%2,%3,%4,%5,%6,%7,%8,%9,%10,%11,%12,%13,%14,%15,%16,%17,%18,%19}, a, b, p, 1, 1, 1, 1;\n}\n"
    : "+f"(d[0]),"+f"(d[1]),"+f"(d[2]),"+f"(d[3]),"+f"(d[4]),"+f"(d[5]),"+f"(d[6]),"+f"(d[7]),"+f"(d[8]),"+f"(d[9]),"+f"(d[10]),"+f"(d[11]),"+f"(d[12]),"+f"(d[13]),"+f"(d[14]),"+f"(d[15]),"+f"(d[16]),"+f"(d[17]),"+f"(d[18]),"+f"(d[19])
    : "r"(da), "r"(db), "r"(sd));
}
__device__ __forceinline__ void wgmma_ss_n32(float (&d)[16], uint32_t da, uint32_t db, int sd) {
  asm volatile("{\n.reg .pred p;\n.reg .b64 a, b;\nsetp.ne.b32 p, %18, 0;\nmov.b64 a, {%16, 0x40000040};\nmov.b64 b, {%17, 0x80000020};\n"
    "wgmma.mma_async.sync.aligned.m64n32k16.f32.bf16.bf16 {%0,%1,%2,%3,%4,%5,%6,%7,%8,%9,%10,%11,%12,%13,%14,%15}, a, b, p, 1, 1, 0, 1;\n}\n"
    : "+f"(d[0]),"+f"(d[1]),"+f"(d[2]),"+f"(d[3]),"+f"(d[4]),"+f"(d[5]),"+f"(d[6]),"+f"(d[7]),"+f"(d[8]),"+f"(d[9]),"+f"(d[10]),"+f"(d[11]),"+f"(d[12]),"+f"(d[13]),"+f"(d[14]),"+f"(d[15])
    : "r"(da), "r"(db), "r"(sd));
}
__device__ __forceinline__ void wgmma_rs_n40(float (&d)[20], uint32_t a0, uint32_t a1, uint32_t a2, uint32_t a3, uint32_t db, int sd) {
  asm volatile("{\n.reg .pred p;\n.reg .b64 b;\nsetp.ne.b32 p, %25, 0;\nmov.b64 b, {%24, 0x10};\n"
    "wgmma.mma_async.sync.aligned.m64n40k16.f32.bf16.bf16 {%0,%1,%2,%3,%4,%5,%6,%7,%8,%9,%10,%11,%12,%13,%14,%15,%16,%17,%18,%19}, {%20,%21,%22,%23}, b, p, 1, 1, 1;\n}\n"
    : "+f"(d[0]),"+f"(d[1]),"+f"(d[2]),"+f"(d[3]),"+f"(d[4]),"+f"(d[5]),"+f"(d[6]),"+f"(d[7]),"+f"(d[8]),"+f"(d[9]),"+f"(d[10]),"+f"(d[11]),"+f"(d[12]),"+f"(d[13]),"+f"(d[14]),"+f"(d[15]),"+f"(d[16]),"+f"(d[17]),"+f"(d[18]),"+f"(d[19])
    : "r"(a0), "r"(a1), "r"(a2), "r"(a3), "r"(db), "r"(sd));
}
__device__ __forceinline__ void wgmma_r1_n256(float (&d)[128], uint32_t da, uint32_t db, int sd) {
  asm volatile("{\n.reg .pred p;\n.reg .b64 a, b;\nsetp.ne.b32 p, %130, 0;\nmov.b64 a, {%128, 0x8};\nmov.b64 b, {%129, 0x6};\n"
    "wgmma.mma_async.sync.aligned.m64n256k16.f32.bf16.bf16 {%0,%1,%2,%3,%4,%5,%6,%7,%8,%9,%10,%11,%12,%13,%14,%15,%16,%17,%18,%19,%20,%21,%22,%23,%24,%25,%26,%27,%28,%29,%30,%31,%32,%33,%34,%35,%36,%37,%38,%39,%40,%41,%42,%43,%44,%45,%46,%47,%48,%49,%50,%51,%52,%53,%54,%55,%56,%57,%58,%59,%60,%61,%62,%63,%64,%65,%66,%67,%68,%69,%70,%71,%72,%73,%74,%75,%76,%77,%78,%79,%80,%81,%82,%83,%84,%85,%86,%87,%88,%89,%90,%91,%92,%93,%94,%95,%96,%97,%98,%99,%100,%101,%102,%103,%104,%105,%106,%107,%108,%109,%110,%111,%112,%113,%114,%115,%116,%117,%118,%119,%120,%121,%122,%123,%124,%125,%126,%127}, a, b, p, 1, 1, 0, 1;\n}\n"
    : "+f"(d[0]),"+f"(d[1]),"+f"(d[2]),"+f"(d[3]),"+f"(d[4]),"+f"(d[5]),"+f"(d[6]),"+f"(d[7]),"+f"(d[8]),"+f"(d[9]),"+f"(d[10]),"+f"(d[11]),"+f"(d[12]),"+f"(d[13]),"+f"(d[14]),"+f"(d[15]),"+f"(d[16]),"+f"(d[17]),"+f"(d[18]),"+f"(d[19]),"+f"(d[20]),"+f"(d[21]),"+f"(d[22]),"+f"(d[23]),"+f"(d[24]),"+f"(d[25]),"+f"(d[26]),"+f"(d[27]),"+f"(d[28]),"+f"(d[29]),"+f"(d[30]),"+f"(d[31]),"+f"(d[32]),"+f"(d[33]),"+f"(d[34]),"+f"(d[35]),"+f"(d[36]),"+f"(d[37]),"+f"(d[38]),"+f"(d[39]),"+f"(d[40]),"+f"(d[41]),"+f"(d[42]),"+f"(d[43]),"+f"(d[44]),"+f"(d[45]),"+f"(d[46]),"+f"(d[47]),"+f"(d[48]),"+f"(d[49]),"+f"(d[50]),"+f"(d[51]),"+f"(d[52]),"+f"(d[53]),"+f"(d[54]),"+f"(d[55]),"+f"(d[56]),"+f"(d[57]),"+f"(d[58]),"+f"(d[59]),"+f"(d[60]),"+f"(d[61]),"+f"(d[62]),"+f"(d[63]),"+f"(d[64]),"+f"(d[65]),"+f"(d[66]),"+f"(d[67]),"+f"(d[68]),"+f"(d[69]),"+f"(d[70]),"+f"(d[71]),"+f"(d[72]),"+f"(d[73]),"+f"(d[74]),"+f"(d[75]),"+f"(d[76]),"+f"(d[77]),"+f"(d[78]),"+f"(d[79]),"+f"(d[80]),"+f"(d[81]),"+f"(d[82]),"+f"(d[83]),"+f"(d[84]),"+f"(d[85]),"+f"(d[86]),"+f"(d[87]),"+f"(d[88]),"+f"(d[89]),"+f"(d[90]),"+f"(d[91]),"+f"(d[92]),"+f"(d[93]),"+f"(d[94]),"+f"(d[95]),"+f"(d[96]),"+f"(d[97]),"+f"(d[98]),"+f"(d[99]),"+f"(d[100]),"+f"(d[101]),"+f"(d[102]),"+f"(d[103]),"+f"(d[104]),"+f"(d[105]),"+f"(d[106]),"+f"(d[107]),"+f"(d[108]),"+f"(d[109]),"+f"(d[110]),"+f"(d[111]),"+f"(d[112]),"+f"(d[113]),"+f"(d[114]),"+f"(d[115]),"+f"(d[116]),"+f"(d[117]),"+f"(d[118]),"+f"(d[119]),"+f"(d[120]),"+f"(d[121]),"+f"(d[122]),"+f"(d[123]),"+f"(d[124]),"+f"(d[125]),"+f"(d[126]),"+f"(d[127])
    : "r"(da), "r"(db), "r"(sd));
}
__device__ __forceinline__ void wgmma_r1_n128(float (&d)[64], uint32_t da, uint32_t db, int sd) {
  asm volatile("{\n.reg .pred p;\n.reg .b64 a, b;\nsetp.ne.b32 p, %66, 0;\nmov.b64 a, {%64, 0x8};\nmov.b64 b, {%65, 0x6};\n"
    "wgmma.mma_async.sync.aligned.m64n128k16.f32.bf16.bf16 {%0,%1,%2,%3,%4,%5,%6,%7,%8,%9,%10,%11,%12,%13,%14,%15,%16,%17,%18,%19,%20,%21,%22,%23,%24,%25,%26,%27,%28,%29,%30,%31,%32,%33,%34,%35,%36,%37,%38,%39,%40,%41,%42,%43,%44,%45,%46,%47,%48,%49,%50,%51,%52,%53,%54,%55,%56,%57,%58,%59,%60,%61,%62,%63}, a, b, p, 1, 1, 0, 1;\n}\n"
    : "+f"(d[0]),"+f"(d[1]),"+f"(d[2]),"+f"(d[3]),"+f"(d[4]),"+f"(d[5]),"+f"(d[6]),"+f"(d[7]),"+f"(d[8]),"+f"(d[9]),"+f"(d[10]),"+f"(d[11]),"+f"(d[12]),"+f"(d[13]),"+f"(d[14]),"+f"(d[15]),"+f"(d[16]),"+f"(d[17]),"+f"(d[18]),"+f"(d[19]),"+f"(d[20]),"+f"(d[21]),"+f"(d[22]),"+f"(d[23]),"+f"(d[24]),"+f"(d[25]),"+f"(d[26]),"+f"(d[27]),"+f"(d[28]),"+f"(d[29]),"+f"(d[30]),"+f"(d[31]),"+f"(d[32]),"+f"(d[33]),"+f"(d[34]),"+f"(d[35]),"+f"(d[36]),"+f"(d[37]),"+f"(d[38]),"+f"(d[39]),"+f"(d[40]),"+f"(d[41]),"+f"(d[42]),"+f"(d[43]),"+f"(d[44]),"+f"(d[45]),"+f"(d[46]),"+f"(d[47]),"+f"(d[48]),"+f"(d[49]),"+f"(d[50]),"+f"(d[51]),"+f"(d[52]),"+f"(d[53]),"+f"(d[54]),"+f"(d[55]),"+f"(d[56]),"+f"(d[57]),"+f"(d[58]),"+f"(d[59]),"+f"(d[60]),"+f"(d[61]),"+f"(d[62]),"+f"(d[63])
    : "r"(da), "r"(db), "r"(sd));
}

__device__ __forceinline__ uint32_t smem_u32(const void* p) { return (uint32_t)__cvta_generic_to_shared(p); }
__device__ __forceinline__ void mbar_init(uint32_t bar, uint32_t cnt) { asm volatile("mbarrier.init.shared::cta.b64 [%0], %1;" ::"r"(bar), "r"(cnt)); }
__device__ __forceinline__ void mbar_expect_tx(uint32_t bar, uint32_t bytes) { asm volatile("mbarrier.arrive.expect_tx.shared::cta.b64 _, [%0], %1;" ::"r"(bar), "r"(bytes) : "memory"); }
__device__ __forceinline__ void mbar_arrive(uint32_t bar) { asm volatile("mbarrier.arrive.shared::cta.b64 _, [%0];" ::"r"(bar) : "memory"); }
__device__ __forceinline__ void mbar_arrive_n(uint32_t bar, uint32_t n) { asm volatile("mbarrier.arrive.shared::cta.b64 _, [%0], %1;" ::"r"(bar), "r"(n) : "memory"); }
__device__ __forceinline__ void mbar_wait(uint32_t bar, uint32_t parity) {
  asm volatile("{\n.reg .pred p;\nLAB_WAIT:\nmbarrier.try_wait.parity.shared::cta.b64 p, [%0], %1;\n@p bra DONE;\nbra LAB_WAIT;\nDONE:\n}" ::"r"(bar), "r"(parity) : "memory");
}
__device__ __forceinline__ void mbar_wait2(uint32_t a, uint32_t pa, uint32_t b, uint32_t pb) {
  asm volatile("{\n.reg .pred p, q;\nLAB_WAIT:\nmbarrier.try_wait.parity.shared::cta.b64 p, [%0], %1;\nmbarrier.try_wait.parity.shared::cta.b64 q, [%2], %3;\n"
               "and.pred p, p, q;\n@p bra DONE;\nbra LAB_WAIT;\nDONE:\n}" ::"r"(a), "r"(pa), "r"(b), "r"(pb) : "memory");
}
__device__ __forceinline__ void mbar_wait3(uint32_t a, uint32_t pa, uint32_t b, uint32_t pb) {
  asm volatile("{\n.reg .pred p, q, r;\nLAB_WAIT:\nmbarrier.try_wait.parity.shared::cta.b64 p, [%0], %1;\nmbarrier.try_wait.parity.shared::cta.b64 q, [%2], %3;\n"
               "mbarrier.try_wait.parity.shared::cta.b64 r, [%2+8], %3;\nand.pred p, p, q;\nand.pred p, p, r;\n@p bra DONE;\nbra LAB_WAIT;\nDONE:\n}" ::"r"(a), "r"(pa), "r"(b), "r"(pb) : "memory");
}
__device__ __forceinline__ bool mbar_probe2(uint32_t a, uint32_t pa, uint32_t b, uint32_t pb) {
  uint32_t ok;
  asm volatile("{\n.reg .pred p, q;\nmbarrier.test_wait.parity.shared::cta.b64 p, [%1], %2;\nmbarrier.test_wait.parity.shared::cta.b64 q, [%3], %4;\n"
               "and.pred p, p, q;\nselp.u32 %0, 1, 0, p;\n}" : "=r"(ok) : "r"(a), "r"(pa), "r"(b), "r"(pb) : "memory");
  return ok != 0;
}
__device__ __forceinline__ void tma_load_3d(uint32_t dst, const CUtensorMap* tm, uint32_t bar, int c0, int c1, int c2) {
  asm volatile("cp.async.bulk.tensor.3d.shared::cluster.global.mbarrier::complete_tx::bytes [%0], [%1, {%3, %4, %5}], [%2];"
               ::"r"(dst), "l"(tm), "r"(bar), "r"(c0), "r"(c1), "r"(c2) : "memory");
}
__device__ __forceinline__ void tma_load_2d(uint32_t dst, const CUtensorMap* tm, uint32_t bar, int c0, int c1) {
  asm volatile("cp.async.bulk.tensor.2d.shared::cluster.global.mbarrier::complete_tx::bytes [%0], [%1, {%3, %4}], [%2];"
               ::"r"(dst), "l"(tm), "r"(bar), "r"(c0), "r"(c1) : "memory");
}
__device__ __forceinline__ void tma_load_w(uint32_t dst, const CUtensorMap* tm, uint32_t bar, int col, int kb) {
#pragma unroll
  for (int q = 0; q < 2; q++)
    asm volatile("cp.async.bulk.tensor.5d.shared::cluster.global.mbarrier::complete_tx::bytes [%0], [%1, {%3, %4, %4, %4, %5}], [%2];"
                 ::"r"(dst + q * 8192), "l"(tm), "r"(bar), "r"(col + q * 64), "r"(0), "r"(2 * kb) : "memory");
}
__device__ __forceinline__ void tma_prefetch_w(const CUtensorMap* tm, int col, int kb) {
#pragma unroll
  for (int q = 0; q < 2; q++)
    asm volatile("cp.async.bulk.prefetch.tensor.5d.L2.global [%0, {%1, %2, %2, %2, %3}];" ::"l"(tm), "r"(col + q * 64), "r"(0), "r"(2 * kb) : "memory");
}
__device__ __forceinline__ void bulk_load(uint32_t dst, const void* g, uint32_t bytes, uint32_t bar) {
  asm volatile("cp.async.bulk.shared::cluster.global.mbarrier::complete_tx::bytes [%0], [%1], %2, [%3];" ::"r"(dst), "l"(g), "r"(bytes), "r"(bar) : "memory");
}
__device__ __forceinline__ void prefetch_map(const CUtensorMap* tm) { asm volatile("prefetch.tensormap [%0];" ::"l"(tm) : "memory"); }
__device__ __forceinline__ void fence_async_smem() { asm volatile("fence.proxy.async.shared::cta;" ::: "memory"); }
__device__ __forceinline__ void fence_async_global() { asm volatile("fence.proxy.async.global;" ::: "memory"); }
__device__ __forceinline__ void fence_gpu() { asm volatile("fence.release.gpu;" ::: "memory"); }
__device__ __forceinline__ void st_flag(unsigned* p, unsigned v) { asm volatile("st.relaxed.gpu.global.u32 [%0], %1;" ::"l"(p), "r"(v) : "memory"); }
__device__ __forceinline__ unsigned ld_flag(const unsigned* p) { unsigned v; asm volatile("ld.relaxed.gpu.global.u32 %0, [%1];" : "=r"(v) : "l"(p) : "memory"); return v; }
__device__ __forceinline__ uint4 ldcg4(const void* p) { uint4 v; asm volatile("ld.global.cg.v4.u32 {%0,%1,%2,%3}, [%4];" : "=r"(v.x), "=r"(v.y), "=r"(v.z), "=r"(v.w) : "l"(p)); return v; }
__device__ __forceinline__ uint4 ld_pkt(const uint4* p) {
  uint4 v; asm volatile("{\n.reg .b128 t;\nld.relaxed.gpu.global.b128 t, [%4];\nmov.b128 {%0,%1,%2,%3}, t;\n}" : "=r"(v.x), "=r"(v.y), "=r"(v.z), "=r"(v.w) : "l"(p) : "memory"); return v;
}
__device__ __forceinline__ void st_pkt(uint4* p, uint32_t a, uint32_t b, uint32_t c, uint32_t tag) {
  asm volatile("{\n.reg .b128 t;\nmov.b128 t, {%1,%2,%3,%4};\nst.relaxed.gpu.global.b128 [%0], t;\n}" ::"l"(p), "r"(a), "r"(b), "r"(c), "r"(tag) : "memory");
}
__device__ __forceinline__ void st_v4(uint4* p, uint32_t a, uint32_t b, uint32_t c, uint32_t d) { asm volatile("st.relaxed.gpu.global.v4.u32 [%0], {%1,%2,%3,%4};" ::"l"(p), "r"(a), "r"(b), "r"(c), "r"(d) : "memory"); }
__device__ __forceinline__ void stg128(uint4* p, uint4 v) { asm volatile("st.global.v4.u32 [%0], {%1,%2,%3,%4};" ::"l"(p), "r"(v.x), "r"(v.y), "r"(v.z), "r"(v.w) : "memory"); }
__device__ __forceinline__ void sts32(uint32_t addr, uint32_t a) { asm volatile("st.shared.u32 [%0], %1;" ::"r"(addr), "r"(a) : "memory"); }
__device__ __forceinline__ void sts64(uint32_t addr, uint32_t a, uint32_t b) { asm volatile("st.shared.v2.u32 [%0], {%1,%2};" ::"r"(addr), "r"(a), "r"(b) : "memory"); }
__device__ __forceinline__ uint32_t mul2(uint32_t a, uint32_t b) { uint32_t r; asm("mul.rn.bf16x2 %0, %1, %2;" : "=r"(r) : "r"(a), "r"(b)); return r; }
__device__ __forceinline__ uint32_t add2(uint32_t a, uint32_t b) { uint32_t r; asm("add.rn.bf16x2 %0, %1, %2;" : "=r"(r) : "r"(a), "r"(b)); return r; }
__device__ __forceinline__ bool elect() {
  uint32_t p; asm volatile("{\n.reg .pred q;\nelect.sync _|q, 0xffffffff;\nselp.u32 %0, 1, 0, q;\n}" : "=r"(p)); return p != 0;
}
__device__ __forceinline__ void wgmma_fence() { asm volatile("wgmma.fence.sync.aligned;" ::: "memory"); }
__device__ __forceinline__ void wgmma_commit() { asm volatile("wgmma.commit_group.sync.aligned;" ::: "memory"); }
template <int N> __device__ __forceinline__ void wgmma_wait() { asm volatile("wgmma.wait_group.sync.aligned %0;" ::"n"(N) : "memory"); }
template <int N> __device__ __forceinline__ void fence_regs(float (&d)[N]) {
#pragma unroll
  for (int i = 0; i < N; i++) asm volatile("" : "+f"(d[i])::"memory");
}
template <int R> __device__ __forceinline__ void reg_alloc() { asm volatile("setmaxnreg.inc.sync.aligned.u32 %0;" ::"n"(R)); }
template <int R> __device__ __forceinline__ void reg_dealloc() { asm volatile("setmaxnreg.dec.sync.aligned.u32 %0;" ::"n"(R)); }
__device__ __forceinline__ void wg_bar(int w) { asm volatile("bar.sync %0, 128;" ::"r"(w + 1) : "memory"); }
__device__ __forceinline__ constexpr uint32_t desc_lo(uint32_t addr, uint32_t lbo) { return (addr >> 4) + ((lbo >> 4) << 16); }
__device__ __forceinline__ uint32_t pack2(float lo, float hi) { uint32_t r; asm("cvt.rn.bf16x2.f32 %0, %1, %2;" : "=r"(r) : "f"(hi), "f"(lo)); return r; }
__device__ __forceinline__ float lo16(uint32_t v) { return __uint_as_float(v << 16); }
__device__ __forceinline__ float hi16(uint32_t v) { return __uint_as_float(v & 0xFFFF0000u); }
__device__ __forceinline__ float ex2(float x) { float r; asm("ex2.approx.ftz.f32 %0, %1;" : "=f"(r) : "f"(x)); return r; }
__device__ __forceinline__ float rcp(float x) { float r; asm("rcp.approx.ftz.f32 %0, %1;" : "=f"(r) : "f"(x)); return r; }
__device__ __forceinline__ uint32_t movm(uint32_t a) { uint32_t d; asm volatile("movmatrix.sync.aligned.m8n8.trans.b16 %0, %1;" : "=r"(d) : "r"(a)); return d; }
__device__ __forceinline__ void stsm4(uint32_t addr, uint32_t a, uint32_t b, uint32_t c, uint32_t d) {
  asm volatile("stmatrix.sync.aligned.m8n8.x4.shared.b16 [%0], {%1,%2,%3,%4};" ::"r"(addr), "r"(a), "r"(b), "r"(c), "r"(d) : "memory");
}
__device__ __forceinline__ void ldsm4(uint32_t addr, uint32_t (&r)[4]) {
  asm volatile("ldmatrix.sync.aligned.m8n8.x4.shared.b16 {%0,%1,%2,%3}, [%4];" : "=r"(r[0]), "=r"(r[1]), "=r"(r[2]), "=r"(r[3]) : "r"(addr) : "memory");
}
__device__ __forceinline__ void sts128(uint32_t addr, uint32_t a, uint32_t b, uint32_t c, uint32_t d) {
  asm volatile("st.shared.v4.u32 [%0], {%1,%2,%3,%4};" ::"r"(addr), "r"(a), "r"(b), "r"(c), "r"(d) : "memory");
}
__device__ __forceinline__ void lds128(uint32_t addr, uint32_t& a, uint32_t& b, uint32_t& c, uint32_t& d) {
  asm volatile("ld.shared.v4.u32 {%0,%1,%2,%3}, [%4];" : "=r"(a), "=r"(b), "=r"(c), "=r"(d) : "r"(addr) : "memory");
}
__device__ __forceinline__ float lds32f(uint32_t addr) { float v; asm volatile("ld.shared.f32 %0, [%1];" : "=f"(v) : "r"(addr) : "memory"); return v; }
__device__ __forceinline__ float2 lds64f(uint32_t addr) { float2 v; asm volatile("ld.shared.v2.f32 {%0,%1}, [%2];" : "=f"(v.x), "=f"(v.y) : "r"(addr) : "memory"); return v; }
__device__ __forceinline__ void mma16816(float (&d)[4], uint32_t a0, uint32_t a1, uint32_t a2, uint32_t a3, uint32_t b0, uint32_t b1) {
  asm("mma.sync.aligned.m16n8k16.row.col.f32.bf16.bf16.f32 {%0,%1,%2,%3}, {%4,%5,%6,%7}, {%8,%9}, {%0,%1,%2,%3};"
      : "+f"(d[0]), "+f"(d[1]), "+f"(d[2]), "+f"(d[3]) : "r"(a0), "r"(a1), "r"(a2), "r"(a3), "r"(b0), "r"(b1));
}
__device__ __forceinline__ void mma1688(float (&d)[4], uint32_t a0, uint32_t a1, uint32_t b0) {
  asm("mma.sync.aligned.m16n8k8.row.col.f32.bf16.bf16.f32 {%0,%1,%2,%3}, {%4,%5}, {%6}, {%0,%1,%2,%3};"
      : "+f"(d[0]), "+f"(d[1]), "+f"(d[2]), "+f"(d[3]) : "r"(a0), "r"(a1), "r"(b0));
}

__device__ __forceinline__ float qsum(float v) { v += __shfl_xor_sync(0xffffffffu, v, 1); v += __shfl_xor_sync(0xffffffffu, v, 2); return v; }

constexpr int NCTA = 132;
#define NB_ 6
#define NA_ 5
constexpr int NB = NB_;
constexpr int NA = NA_;
constexpr uint32_t SLOT = 16384;
constexpr uint32_t SB = 1024;
constexpr uint32_t OFF_B = 0;
constexpr uint32_t OFF_A = NB * SLOT;
constexpr uint32_t OFF_S = OFF_A + NA * SLOT;
constexpr uint32_t OFF_T = OFF_S + 20480;
constexpr uint32_t OFF_CS = OFF_T + 24576;
constexpr uint32_t OFF_MR = OFF_CS + 4640;
constexpr uint32_t OFF_BAR = OFF_MR + 512;
constexpr uint32_t OFF_MA = OFF_S, OFF_MB = OFF_CS - 2048;
constexpr uint32_t BAR_FULLB = OFF_BAR;
constexpr uint32_t BAR_FULLA = BAR_FULLB + 64;
constexpr uint32_t BAR_EMPTYB = BAR_FULLA + 64;
constexpr uint32_t BAR_EMPTYA = BAR_EMPTYB + 64;
constexpr uint32_t BAR_SIGP = BAR_EMPTYA + 64;
constexpr uint32_t BAR_SIGT = BAR_SIGP + 24;
constexpr uint32_t BAR_STAT = BAR_SIGP + 64;
constexpr uint32_t BAR_HALO = BAR_STAT + 16;
constexpr uint32_t BAR_CS = BAR_HALO + 8;
constexpr uint32_t BAR_WPHI = BAR_CS + 16;
constexpr uint32_t BAR_KV = BAR_WPHI + 8;
constexpr uint32_t BAR_STG = BAR_KV + 16;
constexpr uint32_t BAR_EPOCH = BAR_STG + 48;
constexpr uint32_t BAR_LAND = OFF_BAR + 7 * 64;
constexpr uint32_t OFF_EPOCH = OFF_BAR + 8 * 64;
static_assert(BAR_EPOCH < BAR_LAND, "barriers");
constexpr uint32_t SMEM_BYTES = OFF_EPOCH + 8;
static_assert(SMEM_BYTES <= 232448 && NB % 2 == 0 && NB <= 8 && NA <= 6, "smem");

#define CREGS 224
#define PREGS 56
#define PF1 19
#define PF2 21
#define PRE_A 2
#define PRE_B 4
#define CSNEED 0xF001u
#define PS0 1
#define PS1 2
#define SD 1000
#define KSPLIT 12
#define KEEP 16
#define NJ 3
#define KSL 1000
#define PSL 0
#define KVS 12
#define D2 2000
#define D3 1500
#define G0 50
#define MAP 3
#define PMAP 0x76321450u
#define XA 3
#define CP 500
#define S0 200
#define NS 2
#define SW 2
#define SA 1
#define SB_ 4
#define ND0 1
#define KC 4
#define CO 0
#define SE 500
#define PAA 1600
#define PAX 900
#define PA0 1800
#define PX0 1100
#define XN 1
#define RG 1
#define KI 1
#define PADS 0
#define PADM 150
#define EV 0
#define TSK 3
constexpr int NTHREADS = 384;

struct Params {
  CUtensorMap mx;
  CUtensorMap mw[3];
  CUtensorMap mwo[2];
  CUtensorMap mcs[2];
  CUtensorMap mwphi;
  uint4* out;
};

#define XBUF(L) 1
__device__ __align__(256) uint4 g_img[XBUF(3) + 1][16][16][1024];
__device__ __forceinline__ uint32_t img_code(bool isx, int L) { return isx ? (L & 1) | (L & 2) << 15 : ~L & 1; }
__device__ __forceinline__ uint32_t img_mask(bool isx) { return isx ? 0x10001u : 1u; }
__device__ __align__(256) uint4 g_wf[2][8][16][1024];
__device__ __align__(256) uint4 g_stats[16][2][8][32];
__device__ __align__(256) uint4 g_halo[16][8][2][256];
__device__ __align__(256) float g_cs[2][2][3072];
__device__ __align__(256) uint4 g_kvpart[8][16][2][544];
__device__ __align__(256) uint4 g_kvfin[8][16][80];
__device__ __align__(256) unsigned g_hint[16][32];
__device__ __align__(256) unsigned g_jflag[3][8][32];
__device__ unsigned g_ctr;
__device__ __forceinline__ unsigned vblock() {
  unsigned s;
  asm volatile("mov.u32 %0, %%smid;" : "=r"(s));
  const unsigned r = s & 1;
  s >>= 1;
  const unsigned t = s - 32, q = (t * 37) >> 8;
  const unsigned hi = s < 60 ? 12 + (t - 7 * q) * 8 + q : (s < 62 ? s + 4 : s - 58);
  unsigned b = 2 * (s < 32 ? (s & 7) * 8 + (s >> 3) : hi) + r;
  if (b < 128) b = (b & 15) | ((PMAP >> ((b >> 4) * 4)) & 7) << 4;
  if (s >= 62) b = 8 + 4 * r + s - 62;
  unsigned n;
  asm volatile("mov.u32 %0, %%nsmid;" : "=r"(n));
  return __shfl_sync(0xffffffffu, n == NCTA ? b : blockIdx.x, 0);
}
#define TS(who, id) do {} while (0)
#define TSW(id) do {} while (0)

#define TSH(id) do {} while (0)
#define TSMASK 0xFFFF
#define TSL_(a) do { if ((TSMASK >> (a)) & 1) TSW((a) + L * 12); } while (0)
__device__ __forceinline__ int cta_m(unsigned b) { return ((b >> 2) & 12) | (b & 3); }
__device__ __forceinline__ int cta_j(unsigned b) { return ((b >> 2) & 3) | ((b >> 4) & 4); }
struct Ring { uint32_t s, ph; };
template <int N> __device__ __forceinline__ void adv(Ring& r) { if (++r.s == N) { r.s = 0; r.ph ^= 1; } }
template <int N> __device__ __forceinline__ void rewind2(Ring& r) { if (r.s < 2) { r.s += N - 2; r.ph ^= 1; } else r.s -= 2; }
__device__ __forceinline__ int other_tile(int t, int j) { return (t == (j | 4) ? 7 : t) ^ (~j & 4); }
__device__ __forceinline__ int o_order(int i, int j) {
  if (i < 2) return 2 * j + i;
  const int odd = i >= 9;
  return 2 * other_tile(i - 2 - 7 * odd, j) + odd;
}
__device__ __forceinline__ int kv_order(int i, int j, int L) { return L > 0 ? o_order(i, j) : (i + 14 + 2 * (j & 4)) & 15; }

__device__ __forceinline__ unsigned poll_flags(const unsigned* f, int n, unsigned need, unsigned tag) {
  const int lane = threadIdx.x & 31;
  unsigned mask; int it = 0;
  do {
    unsigned v = lane < n ? ld_flag(f + lane) : 0u;
    mask = __ballot_sync(0xffffffffu, lane < n && (int)(v - tag) >= 0);
    if (++it > (1 << 22)) __trap();
  } while ((mask & need) != need);
  fence_async_global();
  return mask;
}
template <bool WAIT = true>
__device__ __forceinline__ unsigned get_tag(uint32_t sb) {
  if (WAIT) mbar_wait(sb + BAR_EPOCH, 0);
  unsigned t; asm volatile("ld.shared.u32 %0, [%1];" : "=r"(t) : "r"(sb + OFF_EPOCH) : "memory");
  return t;
}

__device__ __forceinline__ int lane_id() { int l; asm volatile("mov.u32 %0, %%laneid;" : "=r"(l)); return l; }
__device__ __forceinline__ unsigned seq4(unsigned tag, int L) { return 8u | ((tag & 1u) << 2) | (unsigned)L; }
constexpr float LOG2E = 1.4426950408889634f;

__device__ __forceinline__ float bb_fence(int never, const void* p = &g_ctr, uint32_t keep = 0) {
  while (never < 0) never = ld_flag((const unsigned*)p) + keep;
  return __int_as_float(never >> 30);
}
__device__ __forceinline__ uint32_t solid(uint32_t v) { return __shfl_sync(0xffffffffu, v, threadIdx.x & 31); }
template <class T> __device__ __forceinline__ T* solid(T* p) { return (T*)__shfl_sync(0xffffffffu, (unsigned long long)p, threadIdx.x & 31); }
constexpr uint32_t HA128 = 0x40000040u, HA64 = 0x80000040u;
struct Ctx {
  static constexpr uint32_t sb = SB;
  uint32_t ab, da0;
  int w, warp, lane, g, c;
  int goff;
  __device__ __forceinline__ int m() const { return goff >> 14; }
  __device__ __forceinline__ int j() const { return (goff >> 4) & 7; }
  bool elected;
  Ring ra, rb;
  uint32_t pa, pb;
  uint32_t ha, k2;
  uint32_t mrow, mxor, mhi;
  __device__ __forceinline__ uint32_t aslot(uint32_t s) const { return ab + s * SLOT; }
  __device__ __forceinline__ uint32_t fullA(uint32_t s) const { return sb + BAR_FULLA + s * 8; }
  __device__ __forceinline__ uint32_t fullB(uint32_t s) const { return sb + BAR_FULLB + s * 8; }
  __device__ __forceinline__ void releaseA(uint32_t s) const { if (elected) mbar_arrive(sb + BAR_EMPTYA + s * 8); }
  __device__ __forceinline__ void releaseB(uint32_t s) const { if (elected) mbar_arrive(sb + BAR_EMPTYB + s * 8); }
  __device__ __forceinline__ uint32_t maddr(uint32_t tile, uint32_t ch) const { return tile + mrow + (((ch + mhi) ^ mxor) << 4); }
  __device__ __forceinline__ uint32_t oo() const { return warp * 128 + g * 4 + (c ^ (g >> 1)); }
  __device__ __forceinline__ uint4* img(int b, int hp) const { return ip + (b * 256 + hp) * 1024; }
  uint4* ip;
  uint32_t so;
  __device__ __forceinline__ uint32_t held(int i) const { return ra.s + i < 2 ? ra.s + i + NA - 2 : ra.s + i - 2; }
};

template <int N, bool FIRST, bool O = true>
__device__ __forceinline__ void gemm_issue(float (&acc)[N / 2], Ctx& x, bool ready = false) {
  if (!ready) {
    if (N == 256) mbar_wait3(x.fullA(x.ra.s), x.ra.ph, x.fullB(x.rb.s), x.rb.ph);
    else mbar_wait2(x.fullA(x.ra.s), x.ra.ph, x.fullB(x.rb.s), x.rb.ph);
  }
  const uint32_t da = x.da0 + x.ra.s * (SLOT / 16), db = desc_lo(SB + OFF_B, 8192) + x.rb.s * (SLOT / 16);
  wgmma_fence();
#pragma unroll
  for (int k = 0; k < 4; k++) {
    const uint32_t a = da + (k >> 1) * (O ? 32 : x.k2) + (k & 1) * 2, ha = O ? HA64 : x.ha;
    if constexpr (N == 256) wgmma_ss_n256(acc, a, ha, db + 128 * k, !(FIRST && k == 0));
    else wgmma_ss_n128(acc, a, ha, db + 128 * k, !(FIRST && k == 0));
  }
  wgmma_commit();
}
template <int N>
__device__ __forceinline__ void gemm_next(Ctx& x) {
  x.pa = x.ra.s; x.pb = x.rb.s;
  if (N == 256) x.rb.s++;
  adv<NA>(x.ra); adv<NB>(x.rb);
}
template <int N>
__device__ __forceinline__ void gemm_release(Ctx& x, bool relA) {
  if (relA) x.releaseA(x.pa);
  x.releaseB(x.pb);
  if (N == 256) x.releaseB(x.pb + 1);
}
template <int N>
__device__ __forceinline__ void gemm_retire(Ctx& x, bool relA) { wgmma_wait<1>(); gemm_release<N>(x, relA); gemm_next<N>(x); }
template <bool O = true>
__device__ __forceinline__ void gemm_run(float (&acc)[64], Ctx& x, int n, int hold, int n4 = 0) {
  bool ready = false;
#pragma unroll 1
  for (; n > 0; n--) {
    gemm_issue<128, false, O>(acc, x, ready);
    const uint32_t pa = x.pa, pb = x.pb;
    gemm_next<128>(x);
    ready = mbar_probe2(x.fullA(x.ra.s), x.ra.ph, x.fullB(x.rb.s), x.rb.ph);
    wgmma_wait<1>();
    if (n > hold) x.releaseA(pa);
    x.releaseB(pb);
  }
}
__device__ __forceinline__ void gemm_end(float (&acc)[64], Ctx& x) { wgmma_wait<0>(); fence_regs(acc); gemm_release<128>(x, false); }

__device__ __forceinline__ void rows_load(uint4* r, uint32_t tile, const Ctx& x) {
#pragma unroll
  for (int q = 0; q < 4; q++) {
    const uint32_t row = x.warp * 16 + 4 * q + (x.lane >> 3);
    lds128(tile + row * 128 + (((x.lane & 7) ^ (row & 7)) << 4), r[q].x, r[q].y, r[q].z, r[q].w);
  }
}
__device__ __forceinline__ void rows_store(const uint4* r, uint4* g) {
#pragma unroll
  for (int q = 0; q < 4; q++) stg128(g + q * 1024, r[q]);
}
__device__ __forceinline__ void publish(int id, const Ctx& x) { __syncwarp(); if (x.lane == 0) mbar_arrive(x.sb + BAR_SIGP + id * 8); }
__device__ __forceinline__ uint32_t img_tag(uint32_t v, bool isx, int L, const Ctx& x) {
  const uint32_t mk = ((x.lane ^ (x.warp * 4)) & 7) ? 0u : img_mask(isx);
  return (v & ~mk) | (img_code(isx, L) & mk);
}
__device__ __forceinline__ void img_tag(uint4 (&r)[4], bool isx, int L, const Ctx& x) {
#pragma unroll
  for (int q = 0; q < 4; q++) { uint32_t& v = q == 0 ? r[q].x : (q == 1 ? r[q].y : (q == 2 ? r[q].z : r[q].w)); v = img_tag(v, isx, L, x); }
}
__device__ __forceinline__ void img_store(const uint4 (&r)[4], uint4* g) {
#pragma unroll
  for (int q = 0; q < 4; q++) stg128(g + q * 32, r[q]);
}
__device__ __forceinline__ void img_sts(const uint4 (&r)[4], uint32_t tile, const Ctx& x) {
#pragma unroll
  for (int q = 0; q < 4; q++) sts128(tile + x.so + q * 512, r[q].x, r[q].y, r[q].z, r[q].w);
}
__device__ __forceinline__ void img_load(uint32_t (&v)[16], uint32_t tile, const Ctx& x) {
#pragma unroll
  for (int q = 0; q < 4; q++) lds128(tile + x.so + q * 512, v[4 * q], v[4 * q + 1], v[4 * q + 2], v[4 * q + 3]);
}
__device__ __forceinline__ void img_unpack(float* a, const uint32_t (&v)[16]) {
#pragma unroll
  for (int q = 0; q < 16; q++) { a[4 * (q & 7) + 2 * (q >> 3)] = lo16(v[q]); a[4 * (q & 7) + 2 * (q >> 3) + 1] = hi16(v[q]); }
}

template <int N>
__device__ __forceinline__ void stats_acc(const float* a, float (&t)[4]) {
#pragma unroll
  for (int i = 0; i < N; i++) { t[i & 2] += a[i]; t[(i & 2) + 1] = fmaf(a[i], a[i], t[(i & 2) + 1]); }
}
__device__ __forceinline__ void stats_send(float (&t)[4], int L, const Ctx& x) {
  const unsigned seq = seq4(get_tag<false>(x.sb), L);
#pragma unroll
  for (int q = 0; q < 4; q++) t[q] = qsum(t[q]);
  if (x.c == 0) st_pkt(&g_stats[x.m()][x.w][x.j()][x.warp * 8 + x.g], __float_as_uint(t[0]), __float_as_uint(t[1]), __float_as_uint(t[2]), (__float_as_uint(t[3]) & ~15u) | seq);
}
__device__ __forceinline__ void out_epilogue(const float (&acc)[64], uint4 (&r1)[4], float (&t)[4], uint4* g, int L, Ctx& x) {
  const uint32_t t0 = x.aslot(x.ra.s), t1 = x.aslot(x.ra.s + 1 == NA ? 0 : x.ra.s + 1);
  if (L == 3) {
#pragma unroll
    for (int p = 0; p < 8; p++) {
      stsm4(x.maddr(p < 4 ? t0 : t1, (p & 3) * 2), pack2(acc[8 * p], acc[8 * p + 1]), pack2(acc[8 * p + 2], acc[8 * p + 3]),
            pack2(acc[8 * p + 4], acc[8 * p + 5]), pack2(acc[8 * p + 6], acc[8 * p + 7]));
      if ((p & 3) == 3) { uint4 r[4]; __syncwarp(); rows_load(r, p < 4 ? t0 : t1, x); rows_store(r, g + (p >> 2) * 8); }
    }
  } else {
    auto pack16 = [&](uint4 (&r)[4], const float* a) {
#pragma unroll
      for (int q = 0; q < 4; q++) { const float* u = a + 16 * (q & 1) + (q & 2); r[q] = make_uint4(pack2(u[0], u[1]), pack2(u[4], u[5]), pack2(u[8], u[9]), pack2(u[12], u[13])); }
    };
    uint4 r0[4];
    pack16(r0, acc);
    img_tag(r0, true, L + 1, x);
    img_store(r0, x.img(XBUF(L + 1), 0));
    const float z = bb_fence(x.goff);
    img_sts(r0, t0, x);
    pack16(r1, acc + 32);
    img_tag(r1, true, L + 1, x);
    img_sts(r1, t1, x);
    float u[4] = {z, z, z, z}, v[4] = {z, z, z, z};
    stats_acc<32>(acc, v);
    stats_acc<32>(acc + 32, u);
#pragma unroll
    for (int q = 0; q < 4; q++) t[q] = u[q] + v[q];
    mbar_wait2(x.fullB(x.rb.s), x.rb.ph, x.fullB(x.rb.s + 1), x.rb.ph);
    fence_async_smem();
    asm volatile("bar.sync %0, %1;" ::"r"(L == 1 ? x.w + 1 : 3), "r"(L == 1 ? 128 : 256) : "memory");
  }
}

struct Stats { float rstd0, rstd1; };
__device__ __forceinline__ Stats load_stats(int half, const Ctx& x) {
  const float2 u = lds64f(x.sb + OFF_MR + half * 256 + (x.warp * 8 + x.g) * 8);
  return {u.x, u.y};
}

template <int NH, int NK, class F>
__device__ __forceinline__ void hedgehog_scale(float* t, const Stats& st, const uint32_t* keep, F use) {
#pragma unroll
  for (int q = 0; q < 16 * NH; q++) t[q] *= ((q & 2) ? st.rstd1 : st.rstd0) * LOG2E;
  use();
  float m[4];
#pragma unroll
  for (int q = 0; q < 4 * NH; q++) {
    const float v = fmaxf(fmaxf(fabsf(t[4 * q]), fabsf(t[4 * q + 1])), fmaxf(fabsf(t[4 * q + 2]), fabsf(t[4 * q + 3])));
    m[q & 3] = q < 4 ? v : fmaxf(m[q & 3], v);
  }
  if (__builtin_expect(__any_sync(0xffffffffu, fmaxf(fmaxf(m[0], m[1]), fmaxf(m[2], m[3])) > 58.f), 0)) {
    float z[16 * NH + NK];
#pragma unroll
    for (int q = 0; q < 16 * NH + NK; q++) z[q] = q < 16 * NH ? t[q % (16 * NH)] : __uint_as_float(keep[q & 15]);
#pragma unroll 1
    for (int r = 0; r < 2 * NH; r++) {
      float hi = -INFINITY, lo = INFINITY;
#pragma unroll 1
      for (int i = 0; i < 16; i++) {
        const int k = (i & 6) * 2 + (i & 1) + (r & 1) * 2 + (r & 2) * 8;
        const float v = z[k];
        if (i < 8) { hi = fmaxf(hi, v); lo = fminf(lo, v); }
        else z[k] = v - fminf(fmaxf(v, lo), hi);
        if (i == 7) {
#pragma unroll 1
          for (int d = 1; d <= 2; d++) { hi = fmaxf(hi, __shfl_xor_sync(0xffffffffu, hi, d)); lo = fminf(lo, __shfl_xor_sync(0xffffffffu, lo, d)); }
          const float mid = 0.5f * hi + 0.5f * lo;
          hi = fmaxf(hi - 58.f, mid); lo = fminf(lo + 58.f, mid);
        }
      }
    }
#pragma unroll
    for (int q = 0; q < 16 * NH; q++) t[q] = z[q];
    use();
  }
}
__device__ __forceinline__ void dual_exp(const float* t, uint32_t (&f)[18], int never) {
  float e[KSPLIT];
#pragma unroll
  for (int q = 0; q < KSPLIT; q++) e[q] = ex2(q < 16 ? t[q] : -t[q & 15]);
  while (never < 0) {
#pragma unroll
    for (int i = 0; i < KSPLIT; i += 4) asm volatile("ld.shared.v4.f32 {%0,%1,%2,%3}, [%4];" : "=f"(e[i]), "=f"(e[i + 1]), "=f"(e[i + 2]), "=f"(e[i + 3]) : "r"(never + i) : "memory");
    never += __float_as_int(e[0]);
  }
#pragma unroll
  for (int q = 0; q < KSPLIT; q += 2) f[q >> 1] = pack2(e[q], e[q + 1]);
#pragma unroll
  for (int q = KSPLIT; q < 32; q += 2) f[q >> 1] = q < 16 ? pack2(ex2(t[q]), ex2(t[q + 1])) : pack2(ex2(-t[q & 15]), ex2(-t[(q & 15) + 1]));
#pragma unroll
  for (int sg = 0; sg < 2; sg++) {
    const uint32_t* u = f + 8 * sg;
    const uint32_t a = add2(add2(u[0], u[2]), add2(u[4], u[6])), b = add2(add2(u[1], u[3]), add2(u[5], u[7]));
    f[16 + sg] = add2(__byte_perm(a, b, 0x5410), __byte_perm(a, b, 0x7632));
  }
}
__device__ __forceinline__ void dual_exp_rcp(const float* t, uint32_t* f) {
#pragma unroll
  for (int q = 0; q < 8; q++) {
    const float a = ex2(t[2 * q]), b = ex2(t[2 * q + 1]), r = (EV & 1) ? ex2(-t[2 * q] - t[2 * q + 1]) : rcp(a * b);
    f[q] = pack2(a, b);
    f[8 + q] = q < (EV >> 1) ? pack2(ex2(-t[2 * q]), ex2(-t[2 * q + 1])) : pack2(r * b, r * a);
  }
}
__device__ __forceinline__ void cta_bar() { asm volatile("bar.sync 3, 256;" ::: "memory"); }

template <int N> __device__ __forceinline__ void pin(const uint32_t* v, uint32_t addr) {
#pragma unroll
  for (int i = 0; i < N; i += 4)
    asm volatile("{\n.reg .pred p;\nsetp.eq.u32 p, %0, 0;\n@p st.shared.v4.u32 [%0], {%1,%2,%3,%4};\n}" ::"r"(addr), "r"(v[i]), "r"(v[i + 1]), "r"(v[i + 2]), "r"(v[i + 3]) : "memory");
}

__device__ __forceinline__ void consumer(const Params& P, uint32_t sb, int w, unsigned vb) {
  Ctx x;
  x.w = w;
  x.ab = sb + OFF_A + w * 8192; x.da0 = desc_lo(SB + OFF_A, 16) + w * 512;
  x.lane = threadIdx.x & 31; x.warp = __shfl_sync(0xffffffffu, (threadIdx.x >> 5) & 3, 0); x.g = x.lane >> 2; x.c = x.lane & 3;
  x.goff = (cta_m(vb) * 128 + w) * 128 + cta_j(vb) * 16;
  asm volatile("" : "+r"(x.goff));
  x.elected = (threadIdx.x & 127) == 0;
  x.ra = {0, 0}; x.rb = {0, 0}; x.pa = x.pb = 0;
  {
    const uint32_t row = x.warp * 16 + (x.lane & 15);
    x.mrow = row * 128; x.mxor = row & 7; x.mhi = x.lane >> 4;
  }
  const int goff = x.goff;
  x.ip = solid(&g_img[0][x.m()][2 * x.j()][w * 512 + x.oo()]);
  x.so = solid(16 * x.oo());
  uint4 r1[4];
  float ts[4] = {0.f, 0.f, 0.f, 0.f};
#pragma unroll
  for (int i = 0; i < 4; i++) r1[i] = make_uint4(0, 0, 0, 0);
  TSW(0);
  mbar_wait3(x.fullA(0), 0, x.fullB(0), 0);
#pragma unroll 1
  for (int L = 0; L < 4; L++) {
    float acc[64];
    constexpr uint32_t dcs = desc_lo(SB + OFF_CS, 0);
    if ((L & 1) == 0) {
    float kv[128];
    x.ha = L ? HA64 : HA128; x.k2 = L ? 32 : 4;
    gemm_issue<256, true, false>(kv, x, true); gemm_next<256>(x);
    {
      int i = 1;
#pragma unroll 1
      for (int seg = L ? NS - 1 : 0; seg <= NS; seg++) {
        const int end = seg < NS ? (L == 0 ? 3 + SA * ((x.j() + SW * w) & 3) + SB_ * seg : XA + 1) : 14 + L;
#pragma unroll 1
        do {
          gemm_issue<256, false, false>(kv, x);
          gemm_retire<256>(x, true);
          i++;
          if (i == 5) TSL_(8);
          if (i == 11) TSL_(10);
        } while (i != end);
        if (seg < NS && L == 0) {
          uint32_t v[16];
          float a[32];
#pragma unroll
          for (int q = 0; q < 4; q++) ldsm4(x.maddr(x.aslot(x.pa), 2 * q), reinterpret_cast<uint32_t (&)[4]>(v[4 * q]));
#pragma unroll
          for (int q = 0; q < 16; q++) { a[2 * q] = lo16(v[q]); a[2 * q + 1] = hi16(v[q]); }
          stats_acc<32>(a, ts);
          fence_regs(ts);
          wg_bar(w);
        }
        if (seg == NS - 1) {
          if (L > 0) { img_store(r1, x.img(XBUF(L), 1)); publish(2, x); }
          mbar_wait(sb + BAR_EPOCH, 0);
          stats_send(ts, L, x);
        }
      }
    }
      const Ring kt = x.ra;
      if (L == 0) adv<NA>(x.ra);
#pragma unroll 1
      for (int h = L; h < 2; h++) {
        float d[16];
        mbar_wait2(x.fullA(kt.s), kt.ph, sb + BAR_WPHI, 0);
        wgmma_fence();
#pragma unroll
        for (int q = 0; q < 2; q++) wgmma_ss_n32(d, x.da0 + kt.s * (SLOT / 16) + h * 4 + q * 2, desc_lo(SB + OFF_S + 4096, 512) + w * 256 + h * 128 + q * 64, q);
        wgmma_commit();
        gemm_issue<256, false, false>(kv, x);
        gemm_retire<256>(x, true);
        if (h) x.releaseA(kt.s);
        fence_regs(d);
        uint4* dst = &g_wf[1][x.j()][x.m()][w * 512 + (x.warp * 16 + x.g) * 8 + ((h * 4 + x.c) ^ x.g)];
        dst[0] = make_uint4(pack2(d[0], d[1]), pack2(d[4], d[5]), pack2(d[8], d[9]), pack2(d[12], d[13]));
        dst[64] = make_uint4(pack2(d[2], d[3]), pack2(d[6], d[7]), pack2(d[10], d[11]), pack2(d[14], d[15]));
      }
      const uint32_t dm = desc_lo(SB + OFF_MA, 0) + w * 64;
      mbar_wait2(sb + BAR_STAT, 0, sb + BAR_CS, 0);
      wgmma_fence();
      wgmma_r1_n256(kv, dm, dcs + 96, 1);
      wgmma_commit();
      const Stats st = load_stats(w, x);
      mbar_wait2(x.fullA(x.ra.s), x.ra.ph, x.fullB(x.rb.s), x.rb.ph);
      wgmma_wait<0>();
      fence_regs(kv);
      gemm_release<256>(x, true);
      TSL_(2);
      uint32_t P0[32], P1[32], PH[32];
#pragma unroll
      for (int t = 0; t < 16; t++) { P0[t] = pack2(kv[4 * t] * st.rstd0, kv[4 * t + 1] * st.rstd0); P1[t] = pack2(kv[4 * t + 2] * st.rstd1, kv[4 * t + 3] * st.rstd1); }
      pin<16>(P0, x.mrow + 16);
      {
#pragma unroll
        for (int q = 0; q < 4; q++) sts128((x.warp < 3 ? sb + OFF_T + w * 12288 + x.warp * 4096 : sb + OFF_S + 16384 + w * 2048) + x.lane * 16 + q * 512, P1[4 * q], P1[4 * q + 1], P1[4 * q + 2], P1[4 * q + 3]);
      }
      wgmma_fence();
      wgmma_r1_n128(acc, dm, dcs, 0);
      gemm_issue<128, false, false>(acc, x, true); gemm_next<128>(x);
      TSL_(3);
#pragma unroll
      for (int s = 0; s < 4; s++) {
#pragma unroll
        for (int t = 16 + 8 * (s & 1); t < 24 + 8 * (s & 1); t++) {
          if (s < 2) P1[t] = movm(pack2(kv[4 * t + 2] * st.rstd1, kv[4 * t + 3] * st.rstd1));
          else P0[t] = movm(pack2(kv[4 * t] * st.rstd0, kv[4 * t + 1] * st.rstd0));
        }
        if (s < 3) { gemm_issue<128, false, false>(acc, x); gemm_retire<128>(x, true); }
        if (s == 1) {
          if (x.warp < 3) {
#pragma unroll
            for (int q = 4; q < 8; q++) sts128(sb + OFF_T + w * 12288 + x.warp * 4096 + x.lane * 16 + q * 512, P1[4 * q], P1[4 * q + 1], P1[4 * q + 2], P1[4 * q + 3]);
          } else {
            uint4* dst = &g_halo[x.m()][x.j()][w][x.lane];
#pragma unroll
            for (int q = 0; q < 8; q++) dst[q * 32] = make_uint4(P1[4 * q], P1[4 * q + 1], P1[4 * q + 2], P1[4 * q + 3]);
          }
          publish(3, x);
          gemm_issue<128, false, false>(acc, x);
          gemm_retire<128>(x, true);
        }
      }
      TSL_(4);
      gemm_run<false>(acc, x, 10, 0);
      publish(0, x);
      gemm_issue<128, false, false>(acc, x);
      {
        wg_bar(w);
        uint32_t tr = sb + OFF_T + w * 12288 + (x.warp - 1) * 4096;
        if (x.warp == 0) {
          tr = x.m() > 0 ? sb + OFF_S + 8192 + w * 4096 : tr + 4096;
          if (x.m() > 0) mbar_wait(sb + BAR_HALO, L >> 1);
        }
#pragma unroll
        for (int q = 0; q < 8; q++) lds128(tr + x.lane * 16 + q * 512, PH[4 * q], PH[4 * q + 1], PH[4 * q + 2], PH[4 * q + 3]);
      }
      gemm_retire<128>(x, false);
      gemm_end(acc, x);
      TSL_(5);
      const bool first = (x.m() == 0) && (x.warp == 0);
      const bool hi0 = 2 * x.c > x.g, hi1 = 2 * x.c + 1 > x.g;
      const uint32_t mhi = (hi0 ? 0xFFFFu : 0u) | (hi1 ? 0xFFFF0000u : 0u);
      const uint32_t valid = first ? ~mhi : ~0u;
      const float sc0 = st.rstd0 * (0.17677669529663687f * LOG2E), sc1 = st.rstd1 * (0.17677669529663687f * LOG2E);
      uint32_t xr[2][16];
#pragma unroll
      for (int hp = 0; hp < 2; hp++) {
        const uint32_t tile = x.aslot(x.held(hp));
        uint32_t px[2], py[2];
        float s[2][3][4];
#pragma unroll
        for (int u = 0; u < 2; u++) {
#pragma unroll
          for (int q = 0; q < 12; q++) s[u][q >> 2][q & 3] = 0.f;
#pragma unroll
          for (int ks = 0; ks < 2; ks++) {
            const int t = 8 * hp + 4 * u + 2 * ks;
            const uint32_t a0 = pack2(acc[4 * t], acc[4 * t + 1]), a1 = pack2(acc[4 * t + 2], acc[4 * t + 3]);
            const uint32_t a2 = pack2(acc[4 * t + 4], acc[4 * t + 5]), a3 = pack2(acc[4 * t + 6], acc[4 * t + 7]);
            mma16816(s[u][0], a0, a1, a2, a3, PH[t], PH[t + 1]);
            mma16816(s[u][1], a0, a1, a2, a3, P0[t], P0[t + 1]);
            mma16816(s[u][2], a0, a1, a2, a3, P1[t], P1[t + 1]);
          }
        }
        float e[2][4], big = 0.f;
#pragma unroll
        for (int u = 0; u < 2; u++) {
          e[u][0] = (hi0 ? s[u][0][0] : s[u][1][0]) * sc0; e[u][1] = (hi1 ? s[u][0][1] : s[u][1][1]) * sc0;
          e[u][2] = (hi0 ? s[u][1][2] : s[u][2][2]) * sc1; e[u][3] = (hi1 ? s[u][1][3] : s[u][2][3]) * sc1;
          big = fmaxf(big, fmaxf(fmaxf(fabsf(e[u][0]), fabsf(e[u][1])), fmaxf(fabsf(e[u][2]), fabsf(e[u][3]))));
          px[u] = pack2(ex2(e[u][0]), ex2(e[u][1])) & valid; py[u] = pack2(ex2(e[u][2]), ex2(e[u][3]));
        }
        if (__builtin_expect(__any_sync(0xffffffffu, big > 58.f), 0)) {
#pragma unroll
          for (int q = 0; q < 4; q++) {
            float v0 = e[q >> 1][2 * (q & 1)], v1 = e[q >> 1][2 * (q & 1) + 1];
            if (first && !(q & 1)) { if (hi0) v0 = -INFINITY; if (hi1) v1 = -INFINITY; }
            float r = fmaxf(v0, v1);
            r = fmaxf(r, __shfl_xor_sync(0xffffffffu, r, 1)); r = fmaxf(r, __shfl_xor_sync(0xffffffffu, r, 2));
            ((q & 1) ? py : px)[q >> 1] = pack2(ex2(v0 - r), ex2(v1 - r));
          }
        }
        float r[2][2];
#pragma unroll
        for (int u = 0; u < 2; u++) {
          float d[4] = {0.f, 0.f, 0.f, 0.f};
          mma1688(d, px[u], py[u], 0x3F803F80u);
          r[u][0] = rcp(d[0]); r[u][1] = rcp(d[2]);
        }
        uint32_t o[8][2];
        uint4 ro[4];
#pragma unroll
        for (int q = 0; q < 8; q++) {
          float d[4] = {0.f, 0.f, 0.f, 0.f};
          const int t = 16 + 8 * hp + q, u = q >> 2;
          mma16816(d, px[u] & mhi, 0u, px[u] & ~mhi, py[u] & mhi, PH[t], P0[t]);
          mma1688(d, 0u, py[u] & ~mhi, P1[t]);
          o[q][0] = pack2(d[0] * r[u][0], d[1] * r[u][0]); o[q][1] = pack2(d[2] * r[u][1], d[3] * r[u][1]);
        }
#pragma unroll
        for (int q = 0; q < 4; q++) ro[q] = make_uint4(o[4 * (q & 1)][q >> 1], o[4 * (q & 1) + 1][q >> 1], o[4 * (q & 1) + 2][q >> 1], o[4 * (q & 1) + 3][q >> 1]);
        img_tag(ro, false, 0, x);
        img_store(ro, x.img(0, hp));
        if (hp == 0) bb_fence(x.goff);
        if (hp == 0) {
#pragma unroll
          for (int i = 0; i < 2; i++) {
            const uint32_t ti = x.aslot(x.held(i));
            if (L) img_load(xr[i], ti, x);
            else {
#pragma unroll
              for (int q = 0; q < 4; q++) ldsm4(x.maddr(ti, 2 * q), reinterpret_cast<uint32_t (&)[4]>(xr[i][4 * q]));
            }
          }
          __syncwarp();
        }
        img_sts(ro, tile, x);
      }
      if (L == 0) {
#pragma unroll
        for (int hp = 0; hp < 2; hp++) {
          uint32_t v[16];
#pragma unroll
          for (int q = 0; q < 16; q++) asm volatile("mov.b32 %0, %1;" : "=r"(v[(q & 1) * 8 + (q >> 1)]) : "r"(xr[hp][q]));
#pragma unroll
          for (int q = 0; q < 16; q++) xr[hp][q] = v[q];
        }
      }
      img_unpack(acc, xr[0]); img_unpack(acc + 32, xr[1]);
    } else {
      float kv[128];
      float (&kv0)[64] = reinterpret_cast<float (&)[64]>(kv[0]);
      float (&kv1)[64] = reinterpret_cast<float (&)[64]>(kv[64]);
      auto mma8 = [&](uint32_t as, uint32_t bs, int i, bool fence) {
        const uint32_t da = desc_lo(SB + OFF_A, 16) + as * (SLOT / 16), db = desc_lo(SB + OFF_B, 8192) + bs * (SLOT / 16);
        if (fence) wgmma_fence();
#pragma unroll
        for (int k = 0; k < 4; k++) {
          wgmma_ss_n128(kv0, da + (k >> 1) * 32 + (k & 1) * 2, HA64, db + 128 * k, i + k);
          wgmma_ss_n128(kv1, da + 512 + (k >> 1) * 32 + (k & 1) * 2, HA64, db + 128 * k, i + k);
        }
        wgmma_commit();
      };
      constexpr uint32_t dm = desc_lo(SB + OFF_MB, 0);
      auto relB = [&](uint32_t s) { mbar_arrive_n(sb + BAR_EMPTYB + s * 8, 2); };
      auto skip = [&]() {
#pragma unroll
        for (int q = 0; q < 6 - NJ; q++) adv<NA>(x.ra);
        x.rb.s = w ? (2 + NJ) % 6 : 4;
        if (!w && NJ < 4) x.rb.ph ^= 1;
      };
      static_assert(NA == 5 && NB == 6, "ring arithmetic");
      mma8(x.ra.s, x.rb.s + w, 0, true);
      img_store(r1, x.img(XBUF(L), 1));
      gemm_next<256>(x);
#pragma unroll 1
      for (int i = 1; i < NJ; i++) {
        mbar_wait2(x.fullA(x.ra.s), x.ra.ph, x.fullB(x.rb.s + w), x.rb.ph);
        mma8(x.ra.s, x.rb.s + w, 1, true);
        if (i == 1) { stats_send(ts, L, x); publish(2, x); }
        wgmma_wait<1>();
        if (x.elected) { x.releaseA(x.pa); relB(x.pb + w); }
        gemm_next<256>(x);
      }
      if (w) {
        wgmma_wait<0>();
        if (x.elected) { x.releaseA(x.pa); relB(x.pb + 1); }
        skip();
        asm volatile("bar.sync 7, 256;" ::: "memory");
      }
      TSL_(8);
      {
        const int t = lane_id() + 32 * x.warp;
        uint32_t mask = t < 2 ? ((w ? (t ? 0xFF3Fu : 0x3FFFu) : 0xFFFFu) >> (NJ - 1)) & (w ? ~1u : ~0u) : 0u, cnt = 1 + t;
        bool ready = false;
#pragma unroll 1
        for (int i = NJ; i < 15; i++) {
          if (!ready) mbar_wait2(x.fullA(x.ra.s), x.ra.ph, x.fullB(x.rb.s), x.rb.ph);
          mma8(x.ra.s, x.rb.s, 1, true);
          const uint32_t bar = sb + (t ? BAR_EMPTYB + x.pb * 8 : BAR_EMPTYA + x.pa * 8);
          gemm_next<128>(x);
          if (w && i == 11) x.rb.s = 4;
          ready = mbar_probe2(x.fullA(x.ra.s), x.ra.ph, x.fullB(x.rb.s), x.rb.ph);
          wgmma_wait<1>();
          if (mask & 1) mbar_arrive_n(bar, cnt);
          mask >>= 1; cnt = 2;
          if (i == 8 && w) asm volatile("bar.arrive 9, 256;" ::: "memory");
          if (i == 9) TSL_(10);
        }
        if (!ready) mbar_wait2(x.fullA(x.ra.s), x.ra.ph, x.fullB(x.rb.s), x.rb.ph);
        const uint32_t da = desc_lo(SB + OFF_A, 16) + x.ra.s * (SLOT / 16), db = desc_lo(SB + OFF_B, 8192) + x.rb.s * (SLOT / 16);
#pragma unroll
        for (int hf = 0; hf < 2; hf++) {
          if (hf == 0) wgmma_fence();
#pragma unroll
          for (int k = 0; k < 4; k++) wgmma_ss_n128(hf ? kv1 : kv0, da + hf * 512 + (k >> 1) * 32 + (k & 1) * 2, HA64, db + 128 * k, 1);
          if (hf == 0) { mbar_wait2(sb + BAR_STAT, 1, sb + BAR_CS + 8, 0); wgmma_fence(); }
          wgmma_r1_n128(hf ? kv1 : kv0, dm + 64 * hf, dcs + 96 + 96 * w, 1);
          wgmma_commit();
        }
        if (w == 0) asm volatile("bar.arrive 7, 256;" ::: "memory");
        wgmma_wait<2>();
        if (mask & 1) mbar_arrive_n(sb + (t ? BAR_EMPTYB + x.pb * 8 : BAR_EMPTYA + x.pa * 8), 2);
        gemm_next<128>(x);
        if (w) x.rb.s = 4;
      }
      const uint32_t la = x.pa, lb = x.pb;
      auto finish = [&]() { wgmma_wait<0>(); fence_regs(kv1); if (x.elected) { if (w == 0) mbar_arrive_n(sb + BAR_EMPTYA + la * 8, 2); relB(lb); } };
      const Stats s0 = load_stats(0, x), s1 = load_stats(1, x), st = w ? s1 : s0;
      if (w == 0) skip();
      const uint32_t h0 = x.held(0), h1 = x.held(1);
      auto vreg = [&](int ks) { return (ks & 3) < 3 ? OFF_A + (ks < 4 ? h0 : h1) * SLOT + (ks & 3) * 5120 : OFF_S + 32768 + (ks >> 2) * 5120; };
      uint32_t tV[2], uu[4];
#pragma unroll
      for (int hf = 0; hf < 2; hf++) {
        tV[hf] = sb + vreg(4 * hf + x.warp) + ((x.lane >> 3) & 1) * 2560 + (x.lane & 7) * 16 + x.mhi * 128;
        const float i0 = rcp(hf ? s1.rstd0 : s0.rstd0), i1 = rcp(hf ? s1.rstd1 : s0.rstd1);
        const uint32_t h = pack2(i0, i1);
        uu[2 * hf] = pack2(lo16(h), i0 - lo16(h)); uu[2 * hf + 1] = pack2(hi16(h), i1 - hi16(h));
        asm volatile("" : "+r"(tV[hf]), "+r"(uu[2 * hf]), "+r"(uu[2 * hf + 1])::"memory");
      }
      wgmma_wait<1>();
      fence_regs(kv0);
      TSL_(2);
      if (w == 0) {
        uint32_t f[2][18], ad[4];
#pragma unroll
        for (int q = 0; q < 18; q++) f[1][q] = 0u;
#pragma unroll
        for (int q = 0; q < 4; q++) ad[q] = x.maddr(sb + OFF_S, 2 * q);
        auto norm = [&](int un) {
          uint32_t* u = f[un & 1];
          const Stats& sn = un ? s1 : s0;
#pragma unroll
          for (int sg = 0; sg < 2; sg++) {
            uint32_t v = u[16 + sg];
            v = add2(v, __shfl_xor_sync(0xffffffffu, v, 1)); v = add2(v, __shfl_xor_sync(0xffffffffu, v, 2));
            const float a = rcp(lo16(v)) * sn.rstd0, b = rcp(hi16(v)) * sn.rstd1;
            const uint32_t r0 = pack2(a, a), r1_ = pack2(b, b);
#pragma unroll
            for (int q = 8 * sg; q < 8 * sg + 8; q++) u[q] = mul2(u[q], (q & 1) ? r1_ : r0);
#pragma unroll
            for (int q = 2 * sg; q < 2 * sg + 2; q++) stsm4(ad[q] + un * 8192, u[4 * q], u[4 * q + 1], u[4 * q + 2], u[4 * q + 3]);
          }
        };
        auto move = [&](int dst, int src) {
#pragma unroll
          for (int q = 0; q < 16; q++) asm volatile("mov.b32 %0, %1;" : "=f"(kv[dst + q]) : "f"(src ? kv[src + q] : 0.f));
        };
        hedgehog_scale<1, 0>(kv, s0, nullptr, [] {});
        finish();
        uint32_t step = 0;
#pragma unroll 1
        for (int h = 0;; h++) {
          norm(1);
          dual_exp(kv, f[0], x.goff);
          hedgehog_scale<1, KEEP>(kv + 64, s1, f[1], [] {});
          if (h == 2) asm volatile("bar.sync 9, 256;" ::: "memory");
#pragma unroll
          for (int q = 0; q < 4; q++) ad[q] += step;
          norm(0);
          dual_exp(kv + 64, f[1], x.goff);
#pragma unroll
          for (int q = 0; q < 16; q++) kv[q] = kv[16 + q];
          hedgehog_scale<1, KEEP>(kv, s0, f[0], [] {});
          step = SLOT;
          if (h == 0) { move(64, 80); move(16, 32); }
          else if (h == 1) { move(64, 96); move(16, 48); step = OFF_B + SLOT - OFF_S; }
          else if (h == 2) { move(64, 112); move(16, 0); }
          else break;
        }
        norm(1);
        TSL_(3);
      } else {
#pragma unroll
        for (int hf = 0; hf < 2; hf++) {
          if (hf) finish();
          wg_bar(w);
          stsm4(tV[hf] + 512 + x.mhi * 512, uu[2 * hf], uu[2 * hf + 1], uu[2 * hf], uu[2 * hf + 1]);
          stsm4(tV[hf] + 1792 + x.mhi * 512, uu[2 * hf], uu[2 * hf + 1], uu[2 * hf], uu[2 * hf + 1]);
#pragma unroll
          for (int q = 0; q < 8; q++) {
            const float* u = kv + 64 * hf + 8 * q;
            stsm4(tV[hf] + (q >> 1) * 640 + (q & 1) * 256, pack2(u[0], u[1]), pack2(u[2], u[3]), pack2(u[4], u[5]), pack2(u[6], u[7]));
          }
        }
        TSL_(3);
      }
      {
        float d[2][20];
        uint4* dst = &g_kvpart[x.j()][w * 4 + x.warp][0][x.m() * 32 + x.lane];
        unsigned* dz = reinterpret_cast<unsigned*>(&g_kvpart[x.j()][w * 4 + x.warp][x.c & 1][512]) + x.m() * 8 + x.g;
        fence_async_smem();
        cta_bar();
        TSL_(11);
        uint32_t pk[9];
        auto prep = [&](float (&u)[20]) {
          fence_regs(u);
#pragma unroll
          for (int q = 0; q < 8; q++) pk[q] = pack2(u[((q >> 1) & 2) + 4 * (q & 3)], u[((q >> 1) & 2) + 4 * (q & 3) + 1]);
          pk[8] = __float_as_uint((x.c & 1) ? u[18] + u[19] : u[16] + u[17]);
#pragma unroll
          for (int q = 0; q < 9; q += 4) pk[q] = (pk[q] & ~1u) | (L == 1);
        };
        auto send = [&](int hp) {
          st_v4(dst + hp * 16 * 544, pk[0], pk[1], pk[2], pk[3]); st_v4(dst + (hp * 16 + 1) * 544, pk[4], pk[5], pk[6], pk[7]);
          st_flag(dz + hp * 16 * 544 * 4, pk[8]);
        };
        wgmma_fence();
#pragma unroll
        for (int q = 0; q < 17; q++) {
          if (q < 16) wgmma_ss_n40_tt(d[q >> 3], desc_lo(SB + (q < 8 ? OFF_S : OFF_B + 2 * SLOT), 1024) + w * (SLOT / 16) + 128 * (q & 7), desc_lo(SB + vreg(q & 7), 2560) + (w + (q >> 3) * 2) * 40, q & 7);
          else wgmma_r1_n128(acc, dm + w * 64, dcs, 0);
          if (q == 7 || q == KVS || q == 16) wgmma_commit();
          if (q == KVS) { mbar_wait2(x.fullA(x.ra.s), x.ra.ph, x.fullB(x.rb.s), x.rb.ph); wgmma_wait<1>(); prep(d[0]); send(0); bb_fence(x.goff); wgmma_fence(); }
        }
        gemm_issue<128, false>(acc, x, true); gemm_next<128>(x);
        wgmma_wait<1>();
        x.releaseA(h0); x.releaseA(h1); x.releaseB(2); x.releaseB(3);
        if (x.lane == 0) mbar_arrive(sb + BAR_SIGT);
        prep(d[1]);
        TSL_(4);
#pragma unroll 1
        for (int seg = 0; seg < 2; seg++) {
          const int n0 = w ? PS1 : PS0;
          gemm_run(acc, x, seg ? 15 - n0 : n0, seg, seg ? L : 0);
          if (seg == 0) send(1);
        }
      }
      gemm_end(acc, x);
      TSL_(5);
      {
        float dp[2][20], dn[2][20];
        uint32_t f[4][16];
        auto mma = [&](int h) {
          if (!(h & 1)) mbar_wait(sb + BAR_KV + h * 4, L >> 1);
          if (h == 0) TSL_(9);
          const uint32_t db = desc_lo(SB + OFF_S + h * 5120, 128);
          const uint32_t (&a)[16] = f[h];
          wgmma_fence();
          wgmma_rs_n40(dp[h & 1], a[0], a[1], a[2], a[3], db, 0);
          wgmma_rs_n40(dn[h & 1], a[8], a[9], a[10], a[11], db + 160, 0);
          wgmma_rs_n40(dp[h & 1], a[4], a[5], a[6], a[7], db + 80, 1);
          wgmma_rs_n40(dn[h & 1], a[12], a[13], a[14], a[15], db + 240, 1);
          wgmma_commit();
        };
        uint32_t xr[16];
        auto fin = [&](int h) {
          const uint32_t tile = x.aslot(x.held(h >> 1));
          if (!(h & 1)) img_load(xr, tile, x);
          float (&u)[20] = dp[h & 1];
          float (&v)[20] = dn[h & 1];
          fence_regs(u); fence_regs(v);
#pragma unroll
          for (int r = 0; r < 2; r++) {
            const float sp = u[16 + 2 * r], sn = v[16 + 2 * r];
            const float id = rcp(fmaf(fmaf(sp, L == 1 ? 0.065536f * 128 / 129 : 0.065536f, u[17 + 2 * r]), sn, v[17 + 2 * r] * sp)), aa = sn * id, cc = sp * id;
            uint32_t o[4];
#pragma unroll
            for (int t = 0; t < 4; t++) o[t] = pack2(fmaf(u[4 * t + 2 * r], aa, v[4 * t + 2 * r] * cc), fmaf(u[4 * t + 2 * r + 1], aa, v[4 * t + 2 * r + 1] * cc));
            o[2 * r + (h & 1)] = img_tag(o[2 * r + (h & 1)], false, 1, x);
            stg128(x.img(0, h >> 1) + r * 64 + (h & 1) * 32, make_uint4(o[0], o[1], o[2], o[3]));
            sts128(tile + r * 1024 + (h & 1) * 512 + x.so, o[0], o[1], o[2], o[3]);
          }
          if (h & 1) { if (h == 1) publish(0, x); img_unpack(acc + 16 * (h - 1), xr); }
        };
        auto ex = [&](int h) { dual_exp_rcp(acc + 16 * h, f[h]); };
        Stats sq = st;
#pragma unroll
        for (int h = 0; h < 4; h += 2) {
          hedgehog_scale<2, 0>(acc + 16 * h, sq, nullptr, [&] { ex(h); });
          mma(h);
          ex(h + 1); wgmma_wait<0>(); fin(h);
          if (h == 0) bb_fence(x.goff);
          mma(h + 1);
          wgmma_wait<0>(); fin(h + 1);
          if (h == 0) sq.rstd1 += bb_fence(x.goff);
        }
      }
    }
    mbar_wait(x.fullB(x.rb.s), x.rb.ph);
    fence_regs(acc);
    fence_async_smem();
    wg_bar(w);
    TSL_(6);
    rewind2<NA>(x.ra);
    gemm_issue<128, false>(acc, x, true); gemm_next<128>(x);
    uint4* out = solid(P.out + goff + (x.warp * 16 + (x.lane >> 3)) * 256 + (x.lane & 7));
#pragma unroll 1
    for (int seg = 0; seg < 2; seg++) {
      const int nt = L == 3 ? TSK : XN;
      gemm_run(acc, x, seg ? nt : 15 - nt, seg, 10 + L);
      if (L < 3) { if (seg == 0) publish(1, x); }
      else if (seg != w) {
        if (w) asm volatile("bar.sync 6, 256;" ::: "memory"); else asm volatile("bar.arrive 6, 256;" ::: "memory");
      }
    }
    gemm_end(acc, x);
    TSL_(7);
    rewind2<NA>(x.ra);
    out_epilogue(acc, r1, ts, out, L, x);
    TSL_(13);
  }
}

typedef unsigned long long u64;
template <class T> __device__ __forceinline__ T* early(T* p) { return (T*)__shfl_xor_sync(0xffffffffu, (u64)p, 1); }
__device__ __forceinline__ void pause(uint32_t GAP) {
  if (GAP) { uint32_t t0, t; asm volatile("mov.u32 %0, %%clock;" : "=r"(t0)); do { asm volatile("mov.u32 %0, %%clock;" : "=r"(t)); } while (t - t0 < GAP); }
}
__device__ __forceinline__ u64 order_table0(int j) { return (j & 4) ? 0x543210FEDCBA9876ull : 0xDCBA9876543210FEull; }
__device__ __forceinline__ void order_tables(u64& t1, u64& t2, int j) {
#pragma unroll 1
  for (int i = 6; i >= 0; i--) { const u64 o = 2 * other_tile(i, j); t1 = t1 << 4 | o | (o + 1) << 28; t2 = t2 << 8 | (o * 17 + 16); }
  const u64 own = 2 * j * 17 + 16;
  t1 = t1 << 8 | own; t2 |= own << 56;
}

template <int N> __device__ __forceinline__ void code_gap(unsigned tag) {
  if (N && tag == 0) {
    float u = lds32f(SB);
#pragma unroll
    for (int q = 0; q < N; q++) asm volatile("fma.rn.f32 %0, %0, %0, %0;" : "+f"(u));
    sts32(SB, __float_as_uint(u));
  }
}

__device__ __forceinline__ void b_producer(const Params& P, uint32_t sb, unsigned vb) {
  const int j = cta_j(vb);
  u64 t1 = 0, t2 = 0;
  Ring r = {PRE_B % NB, PRE_B < NB};
#pragma unroll 1
  for (int sg = 0; sg < 20; sg++) {
    const int L = sg / 5, p = sg - 5 * L, wt = L & 1;
    if (sg == 1) order_tables(t1, t2, j);
    int n = p >= 3 ? 16 : (wt ? (p ? 16 - NJ : 2 * NJ) : (p ? 0 : (L ? 32 : 32 - PRE_B)));
    u64 tab = p == 3 ? t2 : (sg == 0 ? order_table0(j) >> (2 * PRE_B) : (p == 1 || p == 2 ? t1 >> (4 * NJ) : t1));
    const CUtensorMap* tm = p == 4 ? &P.mwo[wt] : &P.mw[wt ? 1 : L];
    const uint4* img = &g_wf[p != 3][j][0][0];
    int col = (p >= 3 ? 0 : (p == 2 ? 2048 : 1024)) + 128 * j;
    const int flip = p == 0 ? 3072 : 0;
    const bool fold = wt && p != 4;
    if (sg == 5 || sg == 8) { mbar_wait(sb + (sg == 5 ? BAR_WPHI : BAR_CS + 8), sg == 5); fence_async_global(); }
#pragma unroll 1
    for (; n > 0; n--) {
      const int kb = (int)tab & 15;
      mbar_wait(sb + BAR_EMPTYB + r.s * 8, r.ph);
      if (elect()) {
        mbar_expect_tx(sb + BAR_FULLB + r.s * 8, SLOT);
        if (fold && col < 2048) bulk_load(sb + OFF_B + r.s * SLOT, img + kb * 1024, SLOT, sb + BAR_FULLB + r.s * 8);
        else tma_load_w(sb + OFF_B + r.s * SLOT, tm, sb + BAR_FULLB + r.s * 8, col, kb);
      }
      adv<NB>(r);
      if (p == 2 && (n | 4) == 5) r.s = 4;
      col ^= flip;
      if (!(col & flip & 2048)) tab >>= 4;
    }
  }
}

__device__ __forceinline__ void kv_images(uint32_t sb, int L, int j, unsigned tag, unsigned& ph) {
  const int lane = threadIdx.x & 31;
  auto hinted = [&](int h) { return __all_sync(0xffffffffu, (int)(ld_flag(&g_jflag[h][j][lane & 15]) - (tag * 4 + L)) >= 0); };
  auto load = [&](int h) { if (elect()) { mbar_expect_tx(sb + BAR_LAND + 48 + h * 8, 10240); bulk_load(sb + OFF_S + h * 10240, &g_kvfin[j][8 * h][0], 10240, sb + BAR_LAND + 48 + h * 8); } };
  bool sent = false;
#pragma unroll 1
  for (int h = 0, it = 0; h < 2;) {
    if (++it > (1 << 22)) __trap();
    if (h == 0 || !sent) {
      if (!hinted(h)) continue;
      load(h);
    }
    if (KI && h == 0 && !sent && hinted(1)) { load(1); sent = true; }
    mbar_wait(sb + BAR_LAND + 48 + h * 8, (ph >> h) & 1);
    ph ^= 1u << h;
    uint32_t a = 1u, o = 0u;
#pragma unroll
    for (int u = 0; u < 20; u++) { const uint32_t v = __float_as_uint(lds32f(sb + OFF_S + h * 10240 + u * 512 + lane * 16)); a &= v; o |= v; }
    if (h) sent = false;
    if (__all_sync(0xffffffffu, (L == 1 ? a : ~o) & 1u)) {
      if (elect()) mbar_arrive(sb + BAR_KV + h * 8);
      h++;
    } else fence_async_smem();
  }
}

__device__ __forceinline__ void a_loader(const Params& P, uint32_t sb, unsigned vb) {
  const int j = cta_j(vb), m = cta_m(vb);
  u64 t1 = 0, t2 = 0;
  Ring r = {PRE_A % NA, PRE_A < NA};
  {
    u64 tab = order_table0(j) >> (4 * PRE_A);
#pragma unroll 1
    for (int i = PRE_A; i < 33; i++) {
      if (i == 17) { order_tables(t1, t2, j); tab = t2; }
      mbar_wait(sb + BAR_EMPTYA + r.s * 8, r.ph);
      if (elect()) {
        mbar_expect_tx(sb + BAR_FULLA + r.s * 8, SLOT);
        if (i != 14) tma_load_3d(sb + OFF_A + r.s * SLOT, &P.mx, sb + BAR_FULLA + r.s * 8, ((int)tab & 15) * 64, m * 64, 0);
        else {
          tma_load_w(sb + OFF_A + r.s * SLOT, &P.mw[1], sb + BAR_FULLA + r.s * 8, 1024 + 128 * j, m);
          mbar_expect_tx(sb + BAR_WPHI, 8192); tma_load_2d(sb + OFF_S + 4096, &P.mwphi, sb + BAR_WPHI, 0, 128 * j);
        }
        if (i == PF1 || i == PF2) tma_prefetch_w(&P.mwo[i == PF2], 128 * j, m);
      }
      adv<NA>(r);
      if (i != 14) tab >>= 4;
    }
  }
  const unsigned tag = get_tag(sb);
  unsigned kph = 0;
#pragma unroll 1
  for (int sg = 0; sg < 13; sg++) {
    const int L = sg >> 2, p = sg & 3;
    if (p == 0 && (L & 1)) kv_images(sb, L, j, tag, kph);
    int n = p < 2 ? 14 : (p == 2 ? ((L & 1) ? 0 : 16 - NJ) : 16);
    u64 tab = p == 3 ? t2 : t1 >> (p < 2 ? 8 : 4 * NJ);
    const uint4* img = &g_img[p ? XBUF(L + 1) : 0][m][0][0];
#pragma unroll 1
    for (; n > 0; n--) {
      const uint4* src = early(img + ((int)tab & 15) * 1024);
      const uint32_t bar = sb + (p < 2 ? BAR_LAND : BAR_FULLA) + r.s * 8;
      mbar_wait(sb + BAR_EMPTYA + r.s * 8, r.ph);
      if (elect()) mbar_expect_tx(bar, SLOT);
      if (p < 2 && n == 14) {
        const int lane = threadIdx.x & 31;
        const unsigned* f = &g_hint[(m & 14) + ((lane >> 3) & 1)][(~j & 4) ^ (lane & ND0)];
        mbar_wait(sb + BAR_SIGP + p * 8, L & 1);
        int it = 0;
        while (!__all_sync(0xffffffffu, (int)(ld_flag(f) - (tag * 16 + 4 * L + 1 + p)) >= 0)) { if (++it > (1 << 22)) __trap(); }
        pause(p ? (L ? PAX : PX0) : ((L & 1) ? 0 : (L ? PAA : PA0)));
        TS(2, p == 0 ? 5 + L * 8 : 9 + L * 8);
        TSH((2 * L + p) * 8 + 2);
      }
      if (elect()) bulk_load(sb + OFF_A + r.s * SLOT, src, SLOT, bar);
      adv<NA>(r);
      tab >>= 4;
      pause(p < 2 && n > 10 ? G0 : 0);
    }
  }
  code_gap<PADM>(tag);
}

template <int KB, int G>
__device__ __forceinline__ uint2 sum_packets(float (&a)[8], uint32_t addr, int n) {
  uint2 ok = make_uint2(~0u, 0u);
#pragma unroll 1
  for (int b = 0; b < n; b += KB) {
    uint4 v[KB];
#pragma unroll
    for (int u = 0; u < KB; u++) lds128(addr + (b + u) * 512, v[u].x, v[u].y, v[u].z, v[u].w);
#pragma unroll
    for (int u = 0; u < KB; u++) { ok.x &= v[u].x; ok.y |= v[u].x; }
#pragma unroll
    for (int d = 1; d < G; d *= 2)
#pragma unroll
      for (int u = 0; u < KB; u += 2 * d) v[u] = make_uint4(add2(v[u].x, v[u + d].x), add2(v[u].y, v[u + d].y), add2(v[u].z, v[u + d].z), add2(v[u].w, v[u + d].w));
#pragma unroll
    for (int u = 0; u < KB; u += G) {
      a[0] += lo16(v[u].x); a[1] += hi16(v[u].x); a[2] += lo16(v[u].y); a[3] += hi16(v[u].y);
      a[4] += lo16(v[u].z); a[5] += hi16(v[u].z); a[6] += lo16(v[u].w); a[7] += hi16(v[u].w);
    }
  }
  return ok;
}
__device__ __forceinline__ void helper_bar() { asm volatile("bar.sync 4, 64;" ::: "memory"); }
__device__ __forceinline__ void helper(const Params& P, uint32_t sb, int w, unsigned vb) {
  const int j = cta_j(vb), m = cta_m(vb);
  if (w == 0) {
    if (elect()) {
      const unsigned t = atomicAdd(&g_ctr, 1u) / NCTA + 1u;
      asm volatile("st.shared.u32 [%0], %1;" ::"r"(sb + OFF_EPOCH), "r"(t) : "memory");
      mbar_arrive(sb + BAR_EPOCH);
    }
  }
  const unsigned tag = get_tag(sb);
  mbar_wait(sb + BAR_FULLB + 24, 0);
  const uint32_t stg = sb + OFF_T + w * 12288, stb = sb + BAR_STG + w * 24;
  Ring rs = {0, 0};
  uint32_t vs = 33 % NA, vph = 0;
  auto cs_image = [&](int L) {
      const int lane = lane_id();
      poll_flags(&g_jflag[2 * L][j][0], 16, L ? CSNEED : 0xFFFu, tag * 4);
#pragma unroll
      for (int p = 0; p < 3; p++) {
        const uint4 u = ldcg4(&g_cs[L][0][p * 1024 + 128 * j + lane * 4]), v = ldcg4(&g_cs[L][1][p * 1024 + 128 * j + lane * 4]);
        const float c0 = __uint_as_float(u.x) + __uint_as_float(v.x), c1 = __uint_as_float(u.y) + __uint_as_float(v.y);
        const float c2 = __uint_as_float(u.z) + __uint_as_float(v.z), c3 = __uint_as_float(u.w) + __uint_as_float(v.w);
        const uint32_t h0 = pack2(c0, c1), h1 = pack2(c2, c3), dst = sb + OFF_CS + (p * 16 + (lane >> 1)) * 96 + L * 48 + (lane & 1) * 8;
        sts64(dst, h0, h1); sts64(dst + 16, pack2(c0 - lo16(h0), c1 - hi16(h0)), pack2(c2 - lo16(h1), c3 - hi16(h1))); sts64(dst + 32, h0, h1);
        if (L == 0) { sts64(dst + 48, 0u, 0u); sts64(dst + 64, 0u, 0u); sts64(dst + 80, 0u, 0u); }
      }
      if (L == 0 && lane < 4) sts64(sb + OFF_CS + 4608 + lane * 8, 0u, 0u);
      fence_async_smem();
      __syncwarp();
      if (elect()) mbar_arrive(sb + BAR_CS + L * 8);
      TS(4, 2 + L * 2);
  };
#pragma unroll 1
  for (int L = 0; L < 4; L++) {
    const int lane = lane_id();
    if (L == 0) {
      {
        const int wt = m >= 12, col = ((0x2021 >> (m & 12)) & 3) * 1024 + 128 * j + (m & 3) * 32;
        const CUtensorMap* tm = &P.mcs[wt];
        if (wt) __nanosleep(D2);
        constexpr int nb = 8;
        float a[8] = {0.f, 0.f, 0.f, 0.f, 0.f, 0.f, 0.f, 0.f};
#pragma unroll 1
        for (int b = -3; b < nb; b++) {
          if (b >= 0) {
            mbar_wait(stb + rs.s * 8, rs.ph);
            sum_packets<KC, 1>(a, stg + rs.s * 4096 + lane * 16, 8);
            fence_async_smem();
            __syncwarp();
          }
          const uint32_t sl = b < 0 ? (rs.s + b + 3) % 3 : rs.s;
          if (b + 3 < nb && elect()) { mbar_expect_tx(stb + sl * 8, 4096); tma_load_2d(stg + sl * 4096, tm, stb + sl * 8, col, (w * (16 - nb) + b + 3) * 64); }
          if (b >= 0) adv<3>(rs); else pause(CP);
        }
#pragma unroll 1
        for (int d = 4; d < 32; d *= 2)
#pragma unroll
          for (int u = 0; u < 8; u++) a[u] += __shfl_xor_sync(0xffffffffu, a[u], d);
        if (lane < 4) {
          float4* dst = reinterpret_cast<float4*>(&g_cs[wt][w][col + lane * 8]);
          dst[0] = make_float4(a[0], a[1], a[2], a[3]); dst[1] = make_float4(a[4], a[5], a[6], a[7]);
        }
        helper_bar();
        if (w == 0 && elect()) { fence_gpu(); st_flag(&g_jflag[2 * wt][j][m], tag * 4); }
      }
      if (w == 0) TS(4, 1 + L * 2);
    }
    if (L > 0 && w == 0) {
      mbar_wait(sb + BAR_SIGP + 16, (L - 1) & 1);
      fence_async_global();
      __nanosleep(CO && L == 1 ? SE : SD);
    }
    if (CO && L < 2 && w == 0) cs_image(L);
    if (w == (L == 0)) {
      if (L == 0) { mbar_wait(sb + BAR_WPHI, 0); __nanosleep(S0); }
#pragma unroll 1
      for (int p = 0; p < 2; p++) {
        uint4 v[8];
        for (int it = 0;; it++) {
          bool ok = true;
#pragma unroll
          for (int t = 0; t < 8; t++) v[t] = ld_pkt(&g_stats[m][p][t][lane]);
#pragma unroll
          for (int t = 0; t < 8; t++) ok = ok && (v[t].w & 15u) == seq4(tag, L);
          if (__all_sync(0xffffffffu, ok)) break;
          __nanosleep(200);
          if (it > (1 << 20)) __trap();
        }
        float s0 = 0.f, q0 = 0.f, s1 = 0.f, q1 = 0.f;
#pragma unroll
        for (int t = 0; t < 8; t++) { s0 += __uint_as_float(v[t].x); q0 += __uint_as_float(v[t].y); s1 += __uint_as_float(v[t].z); q1 += __uint_as_float(v[t].w & ~15u); }
        s0 *= (1.f / 1024); s1 *= (1.f / 1024);
        sts64(sb + OFF_MR + p * 256 + lane * 8, __float_as_uint(rsqrtf(fmaxf(q0 * (1.f / 1024) - s0 * s0, 0.f) + 1e-5f)),
              __float_as_uint(rsqrtf(fmaxf(q1 * (1.f / 1024) - s1 * s1, 0.f) + 1e-5f)));
#pragma unroll
        for (int r = 0; r < 2; r++) {
          const float v = -0.5f * (r ? s1 : s0);
          const uint32_t hh = pack2(v, v), hl = pack2(v, v - lo16(hh));
          const bool b = L & 1;
          sts128(sb + (b ? OFF_MB : OFF_MA) + p * 1024 + (lane >> 3) * 256 + r * 128 + (lane & 7) * 16, b ? 0u : hh, b ? hh << 16 : hl >> 16, b ? hl : 0u, 0u);
        }
      }
      fence_async_smem();
      __syncwarp();
      if (elect()) {
        mbar_arrive(sb + BAR_STAT);
      }
      TS(2, 0 + L * 8);
    }
    if (!CO && L < 2 && w == 0) cs_image(L);
    if (L & 1) {
      const uint32_t flip = L == 1 ? 0u : 1u;
      mbar_wait(sb + BAR_SIGT, 1);
      {
        int it = 0;
        if (PSL) __nanosleep(m < 8 ? PSL : PSL + 600);
        while (!__all_sync(0xffffffffu, (ld_flag(reinterpret_cast<const unsigned*>(&g_kvpart[j][m][w][512]) + (lane & 15) * 8) ^ flip) & 1u)) { if (PSL) __nanosleep(100); if (++it > (1 << 22)) __trap(); }
        fence_async_global();
      }
      if (w == 0) TS(4, 6 + L * 2);
      float a[8], z;
      for (int it = 0;; it++) {
        if (elect()) { mbar_expect_tx(stb + rs.s * 8, 8704); bulk_load(stg, &g_kvpart[j][m][w][0], 8704, stb + rs.s * 8); }
        mbar_wait(stb + rs.s * 8, rs.ph);
        if (w == 0) TS(4, 21 + L);
        adv<3>(rs);
#pragma unroll
        for (int u = 0; u < 8; u++) a[u] = 0.f;
        z = 0.f;
        uint32_t ok = 1u;
#pragma unroll
        for (int u = 0; u < 4; u++) { const float v = lds32f(stg + 8192 + u * 128 + (lane & 3) * 32 + (lane >> 2) * 4); z += v; ok &= __float_as_uint(v) ^ flip; }
        const uint2 tg = sum_packets<8, RG>(a, stg + lane * 16, 16);
        ok &= flip ? ~tg.y : tg.x;
        if (__all_sync(0xffffffffu, ok & 1u)) break;
        fence_async_smem();
        if (it > (1 << 16)) __trap();
      }
      {
        uint4* img = &g_kvfin[j][m][w * 8 + (lane >> 2)];
        uint32_t a0 = __float_as_uint(a[0]) >> 16;
        a0 += ~(a0 ^ flip) & 1u;
        st_v4(img + (lane & 3) * 16, __byte_perm(a0, pack2(0.f, a[1]), 0x7610), pack2(a[2], a[3]), pack2(a[4], a[5]), pack2(a[6], a[7]));
        const uint32_t cz = pack2(0.f, qsum(z)) | (0x3781u ^ flip);
        if (!(lane & 3)) st_v4(img + 64, cz, cz, cz, cz);
        __syncwarp();
        if (elect()) st_flag(&g_jflag[m >> 3][j][(m & 7) * 2 + w], tag * 4 + L);
      }
      if (w == 0) TS(4, 7 + L * 2);
    } else {
      if (L == 0 && w == 0) {
        st_v4(&g_kvpart[j][m][0][512 + lane], 0u, 0u, 0u, 0u); st_v4(&g_kvpart[j][m][1][512 + lane], 0u, 0u, 0u, 0u);
        __syncwarp();
      }
      mbar_wait(sb + BAR_SIGT, 0);
      if (w == 0) {
        if (elect()) { fence_gpu(); st_flag(&g_hint[m][j], tag * 16 + 4 * L); st_flag(&g_jflag[1][j][m], tag * 4 + L); }
        if (L == 0) {
          __nanosleep(KSL);
          poll_flags(&g_jflag[1][j][0], 16, 0xFFFFu, tag * 4);
          if (elect()) mbar_arrive(sb + BAR_WPHI);
        }
      } else if (m > 0) {
        poll_flags(&g_hint[m - 1][j], 1, 1u, tag * 16 + 4 * L);
        if (elect()) { mbar_expect_tx(sb + BAR_HALO, 8192); bulk_load(sb + OFF_S + 8192, &g_halo[m - 1][j][0][0], 8192, sb + BAR_HALO); }
        TS(2, 2 + L * 8);
      }
    }
    if (w == 0) {
#pragma unroll 1
      for (int e = 0; e < (L < 3 ? 2 : 1); e++) {
        unsigned* flag = early(&g_hint[m][j]);
        mbar_wait(sb + BAR_SIGP + e * 8, L & 1);
        TS(2, (e ? 6 : 3) + L * 8);
        TSH((2 * L + e) * 8);
        if (elect()) st_flag(flag, tag * 16 + 4 * L + 1 + e);
        TSH((2 * L + e) * 8 + 1);
      }
    } else {
#pragma unroll 1
      for (int i = 0; i < (L < 3 ? 28 : 14); i++) {
        const bool isx = i >= 14;
        const uint32_t a = sb + OFF_A + vs * SLOT + lane * 128 + ((lane >> 4) * 4 + (lane & 3)) * 16 + (lane & 12), code = img_code(isx, L + isx);
        for (int it = 0;; it++) {
          mbar_wait(sb + BAR_LAND + vs * 8, (vph >> vs) & 1);
          vph ^= 1u << vs;
          if (i - 14 * isx < 2) TSH((2 * L + isx) * 8 + 3 + 2 * (i - 14 * isx));
          uint32_t bad = 0;
#pragma unroll
          for (int u = 0; u < 4; u++) bad |= __float_as_uint(lds32f(a + u * 4096)) ^ code;
          if (__all_sync(0xffffffffu, !(bad & img_mask(isx)))) break;
          if (it > (1 << 16)) __trap();
          fence_async_smem();
          if (elect()) {
            mbar_expect_tx(sb + BAR_LAND + vs * 8, SLOT);
            bulk_load(sb + OFF_A + vs * SLOT, &g_img[isx ? XBUF(L + 1) : 0][m][o_order(i - 14 * isx + 2, j)][0], SLOT, sb + BAR_LAND + vs * 8);
          }
        }
        if (elect()) mbar_arrive(sb + BAR_FULLA + vs * 8);
        if (i - 14 * isx < 2) TSH((2 * L + isx) * 8 + 4 + 2 * (i - 14 * isx));
        if (++vs == NA) vs = 0;
      }
      vs = (vs + ((L & 1) ? 16 : 32 - NJ)) % NA;
    }
  }
}

__device__ __forceinline__ void spare(const Params& P, uint32_t sb, int id) {
  const int tid = threadIdx.x & 127, warp = __shfl_sync(0xffffffffu, threadIdx.x >> 5, 0), w = warp >> 2, lane = tid & 31, j = 2 * id + w;
  const uint32_t ring = w * 6 * SLOT, wp = 12 * SLOT + w * 8192, bar = sb + 13 * SLOT + w * 64;
  auto part = [&](int t) { return (t >> 4) ^ w; };
  auto load = [&](int t, uint32_t sl) {
    mbar_expect_tx(bar + sl * 8, t == 0 ? SLOT + 8192 : SLOT);
    tma_load_w(sb + ring + sl * SLOT, &P.mw[1], bar + sl * 8, part(t) * 1024 + 128 * j, t & 15);
  };
  if (!(warp & 3) && elect()) {
    if (w == 2) sts32(sb + OFF_EPOCH, atomicAdd(&g_ctr, 1u) / NCTA + 1u);
    else {
      __nanosleep(D3);
#pragma unroll 1
      for (int t = 0; t < 5; t++) {
        mbar_init(bar + t * 8, 1);
        asm volatile("fence.mbarrier_init.release.cluster;" ::: "memory");
        load(t, t);
      }
      tma_load_2d(sb + wp, &P.mwphi, bar, 0, 128 * j);
    }
  }
  __syncthreads();
  const unsigned tag = get_tag<false>(sb);
  if (w == 2) {
    int it = 0;
    while ((int)(ld_flag(&g_ctr) - tag * NCTA) < 0) { if (++it > (1 << 22)) __trap(); }
    return;
  }
  Ring r = {4, 1};
  float d[64];
  auto fold = [&]() {
    mbar_wait(bar + r.s * 8, r.ph);
    wgmma_fence();
#pragma unroll
    for (int q = 0; q < 8; q++)
      wgmma_ss_n32(reinterpret_cast<float (&)[16]>(d[16 * (q >> 1)]), desc_lo(SB + ring + r.s * SLOT, 16) + (q >> 2) * 512 + (q & 3) * 2, desc_lo(SB + wp, 512) + q * 64, q & 1);
    wgmma_commit();
  };
#pragma unroll
  for (int i = 0; i < 64; i++) d[i] = 0.f;
  int t = -1;
#pragma unroll 1
  for (int g = 0; g < 2; g++) {
    float cs[32] = {};
#pragma unroll 1
    do {
      uint32_t f[32];
#pragma unroll
      for (int i = 0; i < 32; i++) { f[i] = pack2(d[2 * i], d[2 * i + 1]); cs[i & 30] += d[2 * i]; cs[i | 1] += d[2 * i + 1]; }
      wg_bar(w);
      const uint32_t sl = r.s;
      if (t < 31) adv<5>(r);
      fold();
      if (!(warp & 3) && t >= 0 && t < 27 && elect()) load(t + 5, sl);
      if (g == w && t >= 0) {
        uint4* dst = &g_wf[0][j][t & 15][((tid >> 5) * 16 + (lane >> 2)) * 8];
#pragma unroll
        for (int q = 0; q < 8; q++)
          dst[(q >> 2) * 512 + (q & 1) * 64 + (((q & 2) * 2 + (lane & 3)) ^ (lane >> 2))] =
              make_uint4(f[4 * (q & 6) + (q & 1)], f[4 * (q & 6) + (q & 1) + 2], f[4 * (q & 6) + (q & 1) + 4], f[4 * (q & 6) + (q & 1) + 6]);
      }
      wgmma_wait<0>();
      fence_regs(d);
    } while (++t != 16 * g + 16);
    const uint32_t red = sb + ring + 5 * SLOT;
#pragma unroll
    for (int i = 0; i < 8; i++) sts128(red + (tid >> 2) * 512 + (i >> 1) * 128 + (lane & 3) * 32 + (i & 1) * 16, __float_as_uint(cs[4 * i]), __float_as_uint(cs[4 * i + 1]), __float_as_uint(cs[4 * i + 2]), __float_as_uint(cs[4 * i + 3]));
    wg_bar(w);
    float a = 0.f;
#pragma unroll 4
    for (int i = 0; i < 32; i++) a += lds32f(red + i * 512 + tid * 4);
    g_cs[1][0][(g ^ w) * 1024 + j * 128 + tid] = a;
  }
  wg_bar(w);
  if (tid == 0) { fence_gpu(); st_flag(&g_jflag[2][j][0], tag * 4); }
  code_gap<PADS>(tag);
}

__global__ void __launch_bounds__(NTHREADS, 1) fused_kernel(const __grid_constant__ Params P) {
  extern __shared__ __align__(1024) uint8_t smem_raw[];
  constexpr uint32_t sb = SB;
  const int tid = threadIdx.x;
  const unsigned vb = vblock();
  if (vb >= 128) { spare(P, sb, vb - 128); return; }
  const int warp = __shfl_sync(0xffffffffu, tid >> 5, 0);
  if (elect()) {
    if (warp == 11) { prefetch_map(&P.mx); prefetch_map(&P.mw[0]); if (smem_u32(smem_raw) != SB) __trap(); }
    if (warp < 8) {
#pragma unroll
      for (int i = 0; i < 8; i++) mbar_init(sb + OFF_BAR + (warp * 8 + i) * 8, warp == 2 || warp == 3 ? 2 : (warp == 4 ? 8 : 1));
    }
    asm volatile("fence.mbarrier_init.release.cluster;" ::: "memory");
    if (warp < 2) {
      const int j = cta_j(vb);
#pragma unroll 1
      for (int i = 0; i < (warp == 0 ? PRE_B : PRE_A); i++) {
        const uint32_t bar = sb + BAR_FULLB + warp * 64 + i * 8;
        mbar_expect_tx(bar, SLOT);
        if (warp == 0) tma_load_w(sb + OFF_B + i * SLOT, &P.mw[0], bar, 1024 + (i & 1) * 1024 + 128 * j, kv_order(i >> 1, j, 0));
        else tma_load_3d(sb + OFF_A + i * SLOT, &P.mx, bar, kv_order(i, j, 0) * 64, cta_m(vb) * 64, 0);
      }
    }
  }
  if (tid == 0) TS(6, 0);
  __syncthreads();
  if (tid == 0) TS(6, 2);
  if (warp < 4) {
    reg_dealloc<PREGS>();
    if (warp & 2) helper(P, sb, warp & 1, vb);
    else if (warp & 1) a_loader(P, sb, vb);
    else b_producer(P, sb, vb);
  } else {
    reg_alloc<CREGS>();
    consumer(P, sb, (warp >> 2) - 1, vb);
  }
}

typedef CUresult (*EncodeFn)(CUtensorMap*, CUtensorMapDataType, cuuint32_t, void*, const cuuint64_t*, const cuuint64_t*,
                             const cuuint32_t*, const cuuint32_t*, CUtensorMapInterleave, CUtensorMapSwizzle,
                             CUtensorMapL2promotion, CUtensorMapFloatOOBfill);

void encode(EncodeFn fn, CUtensorMap* m, const void* ptr, int rank, const cuuint64_t* dims, const cuuint64_t* strides,
            const cuuint32_t* box, CUtensorMapSwizzle swz) {
  const cuuint32_t es[5] = {1, 1, 1, 1, 1};
  fn(m, CU_TENSOR_MAP_DATA_TYPE_BFLOAT16, rank, const_cast<void*>(ptr), dims, strides, box, es, CU_TENSOR_MAP_INTERLEAVE_NONE,
     swz, CU_TENSOR_MAP_L2_PROMOTION_L2_256B, CU_TENSOR_MAP_FLOAT_OOB_FILL_NONE);
}
void encode_w(EncodeFn fn, CUtensorMap* m, const void* ptr, int ncols, bool perm) {
  const cuuint64_t p = (cuuint64_t)ncols * 2, d[5] = {(cuuint64_t)ncols, 2, 4, 4, 32}, s[4] = {p, (perm ? 8 : 2) * p, (perm ? 2 : 8) * p, 32 * p};
  const cuuint32_t box[5] = {64, 2, 4, 4, 2};
  encode(fn, m, ptr, 5, d, s, box, CU_TENSOR_MAP_SWIZZLE_128B);
}

void encode_cs(EncodeFn fn, CUtensorMap* m, const void* ptr, int ncols) {
  const cuuint64_t d[2] = {(cuuint64_t)ncols, 1024}, s[1] = {(cuuint64_t)ncols * 2};
  const cuuint32_t box[2] = {32, 64};
  encode(fn, m, ptr, 2, d, s, box, CU_TENSOR_MAP_SWIZZLE_NONE);
}

}

extern "C" void kernel_launch(void* const* d_in, const int* in_sizes, int n_in, void* d_out, int out_size) {
  (void)in_sizes; (void)n_in; (void)out_size;
  void* fnp = nullptr;
  cudaDriverEntryPointQueryResult q;
  cudaGetDriverEntryPoint("cuTensorMapEncodeTiled", &fnp, cudaEnableDefault, &q);
  EncodeFn fn = (EncodeFn)fnp;
  Params P;
  {
    const cuuint64_t dims[3] = {1024, 1024, 2}, strides[2] = {4096, 2048};
    const cuuint32_t box[3] = {64, 64, 2};
    encode(fn, &P.mx, d_in[0], 3, dims, strides, box, CU_TENSOR_MAP_SWIZZLE_128B);
  }
  P.out = (uint4*)d_out;
  encode_w(fn, &P.mw[0], d_in[1], 3072, false);
  encode_w(fn, &P.mw[1], d_in[4], 3072, true);
  encode_w(fn, &P.mw[2], d_in[1], 3072, true);
  encode_w(fn, &P.mwo[0], d_in[2], 1024, true);
  encode_w(fn, &P.mwo[1], d_in[6], 1024, false);
  encode_cs(fn, &P.mcs[0], d_in[1], 3072);
  encode_cs(fn, &P.mcs[1], d_in[4], 3072);
  {
    const cuuint64_t dims[2] = {32, 1024}, strides[1] = {64};
    const cuuint32_t box[2] = {32, 128};
    encode(fn, &P.mwphi, d_in[5], 2, dims, strides, box, CU_TENSOR_MAP_SWIZZLE_64B);
  }
  cudaFuncSetAttribute(fused_kernel, cudaFuncAttributeMaxDynamicSharedMemorySize, SMEM_BYTES);
  fused_kernel<<<NCTA, NTHREADS, SMEM_BYTES, cudaStreamPerThread>>>(P);
}
```
